```python
import torch

def _softmax(x, axis=-1):
    return torch.softmax(x, dim=axis)
def _gelu(x):
    return torch.nn.functional.gelu(x, approximate="tanh")
def _silu(x):
    return torch.nn.functional.silu(x)
def _sigmoid(x):
    return torch.sigmoid(x)
def _layernorm(x, axis=-1, eps=1e-5):
    m = x.mean(dim=axis, keepdim=True)
    v = x.var(dim=axis, keepdim=True, unbiased=False)
    return (x - m) / torch.sqrt(v + eps)
def _scatter_add(tgt, idx, src, axis=0):
    return tgt.clone().index_add_(axis, idx, src)
def _segment_sum(src, seg, n):
    out = torch.zeros((n,) + src.shape[1:], dtype=src.dtype)
    return out.index_add_(0, seg, src)
def _pad(x, pw):
    flat = tuple(v for pair in reversed(pw) for v in pair)
    return torch.nn.functional.pad(x, flat)

kernel_name = 'sequential_preLN__ssm_conv_s4__moe_arch_mod__prompt'

def setup_inputs():

    _w = (lambda a: (lambda t: t.to(torch.bfloat16) if t.is_floating_point() else t)(torch.as_tensor(a)))
    def _A_setup():
        B, L, D, N = 1, 2048, 576, 128
        A_re = -(lambda _x: torch.exp(torch.as_tensor(_x)))((lambda *s: torch.randn(*s, dtype=torch.bfloat16) * 1.6)(D, N))
        A_im = torch.pi * (lambda *s: torch.randn(*s, dtype=torch.bfloat16) * 0.2)(D, N)
        B_re = (lambda *s: torch.randn(*s, dtype=torch.bfloat16) * 0.2)(D, N)
        B_im = (lambda *s: torch.randn(*s, dtype=torch.bfloat16) * 0.2)(D, N)
        C_re = (lambda *s: torch.randn(*s, dtype=torch.bfloat16) * 0.2)(D, N)
        C_im = (lambda *s: torch.randn(*s, dtype=torch.bfloat16) * 0.2)(D, N)
        log_dt = (lambda *s: torch.randn(*s, dtype=torch.bfloat16) * 0.2)(D) * 0.5 - 4.0
        Dskip = (lambda *s: torch.randn(*s, dtype=torch.bfloat16) * 0.2)(D)
        return {
            "u": _w((lambda *s: torch.randn(*s, dtype=torch.bfloat16) * 0.05)(B, L, D)),
            "A_re": _w(A_re),
            "A_im": _w(A_im),
            "B_re": _w(B_re),
            "B_im": _w(B_im),
            "C_re": _w(C_re),
            "C_im": _w(C_im),
            "log_dt": _w(log_dt),
            "Dskip": _w(Dskip),
        }
    _A_in = _A_setup()

    def _B_setup():
        B, S, D, F, C = 1, 2048, 576, 4608, 8
        return {
            "x": _w((lambda *s: torch.randn(*s, dtype=torch.bfloat16) * 0.05)(B, S, D)),
            "w_r": _w((lambda *s: torch.randn(*s, dtype=torch.bfloat16) * 0.2)(D)),
            "w_gate": _w((lambda *s: torch.randn(*s, dtype=torch.bfloat16) * 0.2)(D, F)),
            "w_up": _w((lambda *s: torch.randn(*s, dtype=torch.bfloat16) * 0.2)(D, F)),
            "w_down": _w((lambda *s: torch.randn(*s, dtype=torch.bfloat16) * 0.2)(F, D)),
        }
    _B_in = _B_setup()

    return {
        "A_u": _A_in["u"],
        "A_A_re": _A_in["A_re"],
        "A_A_im": _A_in["A_im"],
        "A_B_re": _A_in["B_re"],
        "A_B_im": _A_in["B_im"],
        "A_C_re": _A_in["C_re"],
        "A_C_im": _A_in["C_im"],
        "A_log_dt": _A_in["log_dt"],
        "A_Dskip": _A_in["Dskip"],
        "B_x": _B_in["x"],
        "B_w_r": _B_in["w_r"],
        "B_w_gate": _B_in["w_gate"],
        "B_w_up": _B_in["w_up"],
        "B_w_down": _B_in["w_down"],
    }

def reference(A_u, A_A_re, A_A_im, A_B_re, A_B_im, A_C_re, A_C_im, A_log_dt, A_Dskip, B_x, B_w_r, B_w_gate, B_w_up, B_w_down):
    def _A_ref(u, A_re, A_im, B_re, B_im, C_re, C_im, log_dt, Dskip):
        Bsz, L, D = u.shape
        dt = torch.exp(log_dt)[:, None]
        A = A_re + 1j * A_im
        Bc = B_re + 1j * B_im
        Cc = C_re + 1j * C_im
        logdA = dt * A
        dB = dt * Bc
        l = (lambda x, dt: x.to(dt))(torch.arange(L), A_re.dtype)
        P = torch.exp(logdA[:, :, None] * l[None, None, :])
        K = torch.einsum("dn,dnl,dn->dl", Cc, P, dB).real
        L2 = 2 * L
        Kp = _pad(K, ((0, 0), (0, L)))
        up = (lambda x, *d: x.permute(*d))(u, 0, 2, 1)
        up = _pad(up, ((0, 0), (0, 0), (0, L)))
        Kf = (lambda x, axes=(-2,-1): torch.fft.rfft2(x.float(), dim=axes))(Kp[:, None, :], axes=(-2, -1))
        Uf = (lambda x, axes=(-2,-1): torch.fft.rfft2(x.float(), dim=axes))(up[:, :, None, :], axes=(-2, -1))
        Yf = Uf * Kf[None, :, :, :]
        y = (lambda x, s, axes=(-2,-1): torch.fft.irfft2(x, s=s, dim=axes).to(torch.bfloat16))(Yf, (1, L2), axes=(-2, -1))[:, :, 0, :L]
        y = (lambda x, *d: x.permute(*d))(y, 0, 2, 1) + u * Dskip[None, None, :]
        return y

    def _B_ref(x, w_r, w_gate, w_up, w_down):
        B, S, D = x.shape
        C = 8
        r = x @ w_r
        idx = torch.argsort(-r, axis=-1)[:, :C]
        idx_e = (lambda x, n, axis: torch.repeat_interleave(x, n, dim=axis))(idx.reshape(B, C, 1), D, axis=2)
        x_sel = (lambda x, i, axis: torch.take_along_dim(x, i, dim=axis))(x, idx_e, axis=1)
        g = _silu(x_sel @ w_gate)
        u = x_sel @ w_up
        y = (g * u) @ w_down
        r_sel = _sigmoid((lambda x, i, axis: torch.take_along_dim(x, i, dim=axis))(r, idx, axis=1))
        y = y * r_sel.reshape(B, C, 1)
        b_off = (torch.arange(B) * S).reshape(B, 1)
        flat_idx = (idx + b_off).reshape(B * C)
        zero = (x * 0.0).reshape(B * S, D)
        upd = _scatter_add(zero, flat_idx, y.reshape(B * C, D), axis=0)
        return x + upd.reshape(B, S, D)

    x = A_u
    h = x + _A_ref(_layernorm(x, axis=-1), A_A_re, A_A_im, A_B_re, A_B_im, A_C_re, A_C_im, A_log_dt, A_Dskip)
    h2 = h + _B_ref(_layernorm(h, axis=-1), B_w_r, B_w_gate, B_w_up, B_w_down)
    return h2
```

```cpp
#include <cuda_runtime.h>
#include <cuda_bf16.h>
#include <cuda_fp16.h>
#include <cuda.h>
#include <stdint.h>

namespace {

constexpr int L_ = 2048, D_ = 576, F_ = 4608;
constexpr int NCL = 15, CS = 8, NCTA = NCL * CS, NTHR = 640;
constexpr int SPIN_LIMIT = 1 << 22;

constexpr int SM_WG   = 0;
constexpr int SM_WU   = 46080;
constexpr int SM_FAR  = 92160;
constexpr int FAR_SZ  = 12352;
constexpr int F_E5 = 0, F_O5 = 1536, F_E3 = 3088, F_O3 = 4624, F_E7 = 6176, F_O7 = 7200,
              F_E9 = 8224, F_O9 = 9264, F_E2 = 10288, F_O2 = 11312;
constexpr int SM_U    = SM_FAR + 5 * FAR_SZ;
constexpr int U_SZ    = 5280, U_PITCH = 528;
constexpr int SM_P    = SM_U + 5 * U_SZ;
constexpr int P_NEAR = 8 * 4;
constexpr int P_G0 = (528 + 8) * 4, P_GS = 48 * 4;
constexpr int P_H7 = (528 + 192 + 8) * 4, P_HS = 80 * 4;
constexpr int P_SZ = (528 + 192 + 160) * 4;
constexpr int SM_XT   = SM_P + 5 * P_SZ;
constexpr int SM_MISC = SM_XT + 21504;
constexpr int SM_M1   = SM_MISC;
constexpr int SM_RS1  = SM_M1 + 512;
constexpr int SM_M2   = SM_RS1 + 1024;
constexpr int SM_RS2  = SM_M2 + 1024;
constexpr int SM_KEY  = SM_RS2 + 1024;
constexpr int SM_CAND = SM_KEY + 1024;
constexpr int SM_RK   = SM_CAND + 256;
constexpr int SM_RMS  = SM_RK + 256;
constexpr int SM_SEL  = SM_RMS + 256;
constexpr int SM_KG   = SM_SEL + 64;
constexpr int SM_SC   = SM_KG + 160;
constexpr int SM_MB   = SM_SC + 32;
constexpr int SM_TOTAL = SM_MB + 128;
constexpr int SM_W2   = SM_FAR;
constexpr int SM_SP   = SM_U;
constexpr int SM_GU   = SM_U + 20480;
constexpr int SM_XS   = SM_P;
constexpr int SM_HS   = SM_P + 9344;
constexpr int SM_FIN  = SM_P + 9344 + 128;
constexpr int SM_RED  = SM_FAR + 46080 + 128;
static_assert(SM_RED + 10240 <= SM_U, "alias overflow");
static_assert(SM_GU + 5120 <= SM_P, "alias overflow");
static_assert(SM_FIN + 2400 <= SM_XT, "alias overflow");
static_assert(SM_TOTAL <= 232448, "smem overflow");
static_assert(SM_FAR % 128 == 0 && SM_U % 16 == 0 && SM_P % 16 == 0 && SM_XT % 16 == 0 && SM_MB % 8 == 0, "align");

enum { MB_X0 = 0, MB_Y = 5, MB_W1 = 6, MB_W2 = 7, MB_KEY = 8, MB_GU = 9 };

struct __align__(128) Ctl { unsigned epoch; unsigned hcnt; unsigned err; unsigned pad[29]; };
__device__ Ctl g_ctl;
__device__ __align__(128) uint2  g_st1[L_];
__device__ __align__(128) float4 g_acc[L_];
__device__ __align__(128) __nv_bfloat16 g_h[L_ * D_];
__device__ __align__(128) uint2  g_part[8 * NCL * D_];
#define STAMP(i)

__device__ __forceinline__ uint32_t mapa(uint32_t a, uint32_t r) { uint32_t d; asm("mapa.shared::cluster.u32 %0, %1, %2;" : "=r"(d) : "r"(a), "r"(r)); return d; }
__device__ __forceinline__ void mbar_wait(uint32_t mb) {
    uint32_t ok; int it = 0;
    do {
        asm volatile("{ .reg .pred p; mbarrier.try_wait.parity.acquire.cluster.shared::cta.b64 p, [%1], 0; selp.u32 %0, 1, 0, p; }" : "=r"(ok) : "r"(mb) : "memory");
    } while (!ok && ++it < (1 << 16));
}
__device__ __forceinline__ void bar_sync(int id, int n) { asm volatile("bar.sync %0, %1;" :: "r"(id), "r"(n) : "memory"); }
__device__ __forceinline__ void bar_arrive(int id, int n) { asm volatile("bar.arrive %0, %1;" :: "r"(id), "r"(n) : "memory"); }
__device__ __forceinline__ uint32_t lds32(uint32_t a) { uint32_t v; asm volatile("ld.shared.u32 %0, [%1];" : "=r"(v) : "r"(a) : "memory"); return v; }
__device__ __forceinline__ float ldsf(uint32_t a) { float v; asm volatile("ld.shared.f32 %0, [%1];" : "=f"(v) : "r"(a) : "memory"); return v; }
__device__ __forceinline__ uint4 lds128(uint32_t a) { uint4 v; asm volatile("ld.shared.v4.u32 {%0,%1,%2,%3}, [%4];" : "=r"(v.x), "=r"(v.y), "=r"(v.z), "=r"(v.w) : "r"(a) : "memory"); return v; }
__device__ __forceinline__ float4 lds128f(uint32_t a) { float4 v; asm volatile("ld.shared.v4.f32 {%0,%1,%2,%3}, [%4];" : "=f"(v.x), "=f"(v.y), "=f"(v.z), "=f"(v.w) : "r"(a) : "memory"); return v; }
__device__ __forceinline__ void sts16(uint32_t a, uint32_t v) { asm volatile("st.shared.u16 [%0], %1;" :: "r"(a), "h"((unsigned short)v) : "memory"); }
__device__ __forceinline__ void sts32(uint32_t a, uint32_t v) { asm volatile("st.shared.u32 [%0], %1;" :: "r"(a), "r"(v) : "memory"); }
__device__ __forceinline__ void stsf(uint32_t a, float v) { asm volatile("st.shared.f32 [%0], %1;" :: "r"(a), "f"(v) : "memory"); }
__device__ __forceinline__ void sts128(uint32_t a, uint32_t x, uint32_t y, uint32_t z, uint32_t w) { asm volatile("st.shared.v4.u32 [%0], {%1,%2,%3,%4};" :: "r"(a), "r"(x), "r"(y), "r"(z), "r"(w) : "memory"); }
__device__ __forceinline__ void sts128f(uint32_t a, float x, float y, float z, float w) { asm volatile("st.shared.v4.f32 [%0], {%1,%2,%3,%4};" :: "r"(a), "f"(x), "f"(y), "f"(z), "f"(w) : "memory"); }
__device__ __forceinline__ void ldsm4(uint32_t (&r)[4], uint32_t a) { asm volatile("ldmatrix.sync.aligned.m8n8.x4.shared.b16 {%0,%1,%2,%3}, [%4];" : "=r"(r[0]), "=r"(r[1]), "=r"(r[2]), "=r"(r[3]) : "r"(a) : "memory"); }
__device__ __forceinline__ void ldsm4t(uint32_t (&r)[4], uint32_t a) { asm volatile("ldmatrix.sync.aligned.m8n8.x4.trans.shared.b16 {%0,%1,%2,%3}, [%4];" : "=r"(r[0]), "=r"(r[1]), "=r"(r[2]), "=r"(r[3]) : "r"(a) : "memory"); }
__device__ __forceinline__ void ldsm2(uint32_t& r0, uint32_t& r1, uint32_t a) { asm volatile("ldmatrix.sync.aligned.m8n8.x2.shared.b16 {%0,%1}, [%2];" : "=r"(r0), "=r"(r1) : "r"(a) : "memory"); }
__device__ __forceinline__ void ldsm2t(uint32_t& r0, uint32_t& r1, uint32_t a) { asm volatile("ldmatrix.sync.aligned.m8n8.x2.trans.shared.b16 {%0,%1}, [%2];" : "=r"(r0), "=r"(r1) : "r"(a) : "memory"); }
__device__ __forceinline__ uint32_t lds32_nv(uint32_t a) { uint32_t v; asm volatile("ld.shared.u32 %0, [%1];" : "=r"(v) : "r"(a)); return v; }
__device__ __forceinline__ void mma_f16(float (&d)[4], uint32_t a0, uint32_t a1, uint32_t a2, uint32_t a3, uint32_t b0, uint32_t b1) {
    asm("mma.sync.aligned.m16n8k16.row.col.f32.f16.f16.f32 {%0,%1,%2,%3}, {%4,%5,%6,%7}, {%8,%9}, {%0,%1,%2,%3};"
        : "+f"(d[0]), "+f"(d[1]), "+f"(d[2]), "+f"(d[3]) : "r"(a0), "r"(a1), "r"(a2), "r"(a3), "r"(b0), "r"(b1));
}
__device__ __forceinline__ void mma_bf16(float (&d)[4], uint32_t a0, uint32_t a1, uint32_t a2, uint32_t a3, uint32_t b0, uint32_t b1) {
    asm("mma.sync.aligned.m16n8k16.row.col.f32.bf16.bf16.f32 {%0,%1,%2,%3}, {%4,%5,%6,%7}, {%8,%9}, {%0,%1,%2,%3};"
        : "+f"(d[0]), "+f"(d[1]), "+f"(d[2]), "+f"(d[3]) : "r"(a0), "r"(a1), "r"(a2), "r"(a3), "r"(b0), "r"(b1));
}
__device__ __forceinline__ uint32_t pack_f16(float lo, float hi) { uint32_t r; asm("cvt.rn.f16x2.f32 %0, %1, %2;" : "=r"(r) : "f"(hi), "f"(lo)); return r; }
__device__ __forceinline__ uint32_t pack_bf16(float lo, float hi) { uint32_t r; asm("cvt.rn.bf16x2.f32 %0, %1, %2;" : "=r"(r) : "f"(hi), "f"(lo)); return r; }
__device__ __forceinline__ float bf_lo(uint32_t v) { return __uint_as_float(v << 16); }
__device__ __forceinline__ float bf_hi(uint32_t v) { return __uint_as_float(v & 0xFFFF0000u); }
__device__ __forceinline__ float bfr(float x) { return __bfloat162float(__float2bfloat16_rn(x)); }
__device__ __forceinline__ float h_lo(uint32_t v) { return __half2float(__ushort_as_half((unsigned short)(v & 0xFFFF))); }
__device__ __forceinline__ float h_hi(uint32_t v) { return __half2float(__ushort_as_half((unsigned short)(v >> 16))); }
__device__ __forceinline__ uint32_t bsub2(uint32_t a, uint32_t b) { uint32_t r; asm("sub.rn.bf16x2 %0, %1, %2;" : "=r"(r) : "r"(a), "r"(b)); return r; }
__device__ __forceinline__ uint32_t badd2(uint32_t a, uint32_t b) { uint32_t r; asm("add.rn.bf16x2 %0, %1, %2;" : "=r"(r) : "r"(a), "r"(b)); return r; }
__device__ __forceinline__ uint32_t bmul2(uint32_t a, uint32_t b) { uint32_t r; asm("mul.rn.bf16x2 %0, %1, %2;" : "=r"(r) : "r"(a), "r"(b)); return r; }
__device__ __forceinline__ void st_async4(uint32_t a, uint32_t x, uint32_t y, uint32_t z, uint32_t w, uint32_t mb) {
    asm volatile("st.async.shared::cluster.mbarrier::complete_tx::bytes.v4.u32 [%0], {%1,%2,%3,%4}, [%5];" :: "r"(a), "r"(x), "r"(y), "r"(z), "r"(w), "r"(mb) : "memory"); }
__device__ __forceinline__ void st_async2(uint32_t a, uint32_t x, uint32_t y, uint32_t mb) {
    asm volatile("st.async.shared::cluster.mbarrier::complete_tx::bytes.v2.u32 [%0], {%1,%2}, [%3];" :: "r"(a), "r"(x), "r"(y), "r"(mb) : "memory"); }
__device__ __forceinline__ void st_async1(uint32_t a, uint32_t x, uint32_t mb) {
    asm volatile("st.async.shared::cluster.mbarrier::complete_tx::bytes.u32 [%0], %1, [%2];" :: "r"(a), "r"(x), "r"(mb) : "memory"); }
__device__ __forceinline__ unsigned ld_rlx(const void* p) { unsigned v; asm volatile("ld.relaxed.gpu.global.u32 %0, [%1];" : "=r"(v) : "l"(p) : "memory"); return v; }
__device__ __forceinline__ unsigned ld_acq(const void* p) { unsigned v; asm volatile("ld.acquire.gpu.global.u32 %0, [%1];" : "=r"(v) : "l"(p) : "memory"); return v; }
__device__ __forceinline__ uint2 ld_rlx64(const void* p) { unsigned long long v; asm volatile("ld.relaxed.gpu.global.u64 %0, [%1];" : "=l"(v) : "l"(p) : "memory"); return make_uint2((unsigned)v, (unsigned)(v >> 32)); }
__device__ __forceinline__ void st_rlx64(void* p, unsigned lo, unsigned hi) { asm volatile("st.relaxed.gpu.global.u64 [%0], %1;" :: "l"(p), "l"((unsigned long long)lo | ((unsigned long long)hi << 32)) : "memory"); }
__device__ __forceinline__ uint4 ld_rlx128(const void* p) { uint4 v; asm volatile("ld.relaxed.gpu.global.v4.u32 {%0,%1,%2,%3}, [%4];" : "=r"(v.x), "=r"(v.y), "=r"(v.z), "=r"(v.w) : "l"(p) : "memory"); return v; }
__device__ __forceinline__ void tma2d(uint32_t dst, const CUtensorMap* tm, int x, int y, uint32_t mb) {
    asm volatile("cp.async.bulk.tensor.2d.shared::cluster.global.mbarrier::complete_tx::bytes [%0], [%1, {%3, %4}], [%2];"
                 :: "r"(dst), "l"(tm), "r"(mb), "r"(x), "r"(y) : "memory");
}
__device__ __forceinline__ void cmul(float& xr, float& xi, float ar, float ai, float br, float bi) {
    xr = fmaf(ar, br, -ai * bi); xi = fmaf(ar, bi, ai * br);
}
__device__ __forceinline__ void cexp_s(float& zr, float& zi, float e2, float turns) {
    float mag; asm("ex2.approx.ftz.f32 %0, %1;" : "=f"(mag) : "f"(e2));
    float r = (turns - rintf(turns)) * 6.283185307179586f;
    zr = mag * __cosf(r); zi = mag * __sinf(r);
}

template <int NT>
__device__ __forceinline__ void near_conv(float (&acc)[6][4], uint32_t ubase, uint32_t pbase, int j0, int lane) {
    const int g8 = lane & 7, hi = (lane >> 3) & 1, sel = lane >> 4;
    const uint32_t lbase = ubase + g8 * U_PITCH + hi * 16;
    uint32_t B[NT + 34][2];
    auto loadB = [&](int i) {
        int m = j0 + NT - 1 - i - sel;
        uint32_t r[4];
        asm volatile("ldmatrix.sync.aligned.m8n8.x4.shared.b16 {%0,%1,%2,%3}, [%4];" : "=r"(r[0]), "=r"(r[1]), "=r"(r[2]), "=r"(r[3])
                     : "r"(lbase + m * 32 + (m >> 4) * 16));
        B[i][0] = r[0]; B[i][1] = r[1]; B[i + 1][0] = r[2]; B[i + 1][1] = r[3];
    };
#pragma unroll
    for (int i = 0; i < 6; i += 2) loadB(i);
    uint32_t rm = 0, r0 = lds32_nv(pbase), rp = lds32_nv(pbase + 32);
#pragma unroll
    for (int dl = 0; dl <= 32; dl++) {
        uint32_t n0 = 0, np = 0;
        if (dl < 32) n0 = lds32_nv(pbase + (dl + 1) * 64);
        if (dl < 31) np = lds32_nv(pbase + (dl + 1) * 64 + 32);
        if ((dl & 1) == 0 && dl + 6 < NT + 32) loadB(dl + 6);
#pragma unroll
        for (int t = 0; t < NT; t++) {
            const int i = NT - 1 - t + dl;
            mma_f16(acc[t], r0, rp, rm, r0, B[i][0], B[i][1]);
        }
        rm = rp; r0 = n0; rp = np;
    }
}

__device__ __forceinline__ void far_conv(uint32_t fb, uint32_t pch, int lane) {
    const int g = lane >> 2, c = lane & 3;
    float acc[7][2][4];
#pragma unroll
    for (int a = 0; a < 7; a++)
#pragma unroll
        for (int h = 0; h < 2; h++) { acc[a][h][0] = acc[a][h][1] = acc[a][h][2] = acc[a][h][3] = 0.f; }
    const uint32_t po = pch + (g - 2 * c) * 4;
    const int r16 = lane & 15, up = lane >> 4;
#pragma unroll
    for (int arr = 0; arr < 2; arr++) {
        uint32_t Ra[7], Rb[7];
        Ra[0] = Rb[0] = Ra[6] = Rb[6] = 0;
#pragma unroll
        for (int i = 0; i < 5; i++) {
            Ra[i + 1] = lds32_nv(po + P_G0 + arr * P_GS + i * 32);
            Rb[i + 1] = lds32_nv(po + P_G0 + (arr + 2) * P_GS + i * 32);
        }
        const uint32_t eb = fb + (arr ? F_E3 : F_E5), ob = fb + (arr ? F_O3 : F_O5);
        const uint32_t aEO = (up ? ob + 16 : eb) + r16 * 16;
        const uint32_t aOp = ob + r16 * 16 + up * 256;
        if (arr == 0) {
            uint32_t b0, b1;
            ldsm2t(b0, b1, r16 == 15 ? ob : fb + F_O3);
#pragma unroll
            for (int dl = 0; dl < 3; dl++) mma_f16(acc[dl][1], Ra[2 * dl + 1], Ra[2 * dl + 2], Ra[2 * dl], Ra[2 * dl + 1], b0, b1);
        }
        uint32_t op[4];
#pragma unroll
        for (int ap = 0; ap < 6; ap++) {
            uint32_t eo[4];
            ldsm4t(eo, aEO + ap * 256);
            if ((ap & 1) == 0) ldsm4t(op, aOp + ap * 256);
            const uint32_t p0 = op[(ap & 1) * 2], p1 = op[(ap & 1) * 2 + 1];
#pragma unroll
            for (int dl = 0; dl < 3; dl++) {
                const int a = ap + 1 + dl;
                if (a <= 6) {
                    mma_f16(acc[a][0], Ra[2 * dl + 1], Ra[2 * dl + 2], Ra[2 * dl], Ra[2 * dl + 1], eo[0], eo[1]);
                    mma_f16(acc[a][1], Ra[2 * dl + 1], Ra[2 * dl + 2], Ra[2 * dl], Ra[2 * dl + 1], eo[2], eo[3]);
                    mma_f16(acc[a][0], Rb[2 * dl + 1], Rb[2 * dl + 2], Rb[2 * dl], Rb[2 * dl + 1], p0, p1);
                    mma_f16(acc[a][1], Rb[2 * dl + 1], Rb[2 * dl + 2], Rb[2 * dl], Rb[2 * dl + 1], eo[0], eo[1]);
                }
            }
        }
    }
#pragma unroll
    for (int arr = 0; arr < 2; arr++) {
        uint32_t R[9];
        R[0] = 0;
#pragma unroll
        for (int i = 0; i < 8; i++) R[i + 1] = lds32_nv(po + P_H7 + arr * P_HS + i * 32);
        const uint32_t aEO = fb + (arr ? (up ? F_O9 : F_E9) : (up ? F_O7 : F_E7)) + r16 * 16;
#pragma unroll
        for (int ap = 0; ap < 4; ap++) {
            uint32_t eo[4];
            ldsm4t(eo, aEO + ap * 256);
#pragma unroll
            for (int dl = 0; dl < 4 - ap; dl++) {
                const int a = ap + 3 + dl;
                mma_f16(acc[a][0], R[2 * dl + 1], R[2 * dl + 2], R[2 * dl], R[2 * dl + 1], eo[0], eo[1]);
                mma_f16(acc[a][1], R[2 * dl + 1], R[2 * dl + 2], R[2 * dl], R[2 * dl + 1], eo[2], eo[3]);
            }
        }
    }
    {
        uint32_t kv = lds32_nv(pch + P_G0 + 32 * 4) & 0xFFFFu;
        uint32_t dg = (g == 2 * c) ? kv : ((g == 2 * c + 1) ? (kv << 16) : 0u);
        const uint32_t aEO = fb + (up ? F_O2 : F_E2) + r16 * 16;
#pragma unroll
        for (int ap = 0; ap < 4; ap++) {
            uint32_t eo[4];
            ldsm4t(eo, aEO + ap * 256);
            mma_f16(acc[ap + 3][0], dg, 0u, 0u, dg, eo[0], eo[1]);
            mma_f16(acc[ap + 3][1], dg, 0u, 0u, dg, eo[2], eo[3]);
        }
    }
    __syncwarp();
    const float ds = 1.0f / 512.0f;
#pragma unroll
    for (int h = 0; h < 2; h++)
#pragma unroll
        for (int e = 0; e < 4; e++) {
            const int beta = g + (e >> 1) * 8, p = 8 * h + 2 * c + (e & 1);
            const int row = beta * 16 + (p ^ (g & 1));
            sts128(fb + row * 16, pack_f16(0.f, acc[0][h][e] * ds), pack_f16(acc[1][h][e] * ds, acc[2][h][e] * ds),
                   pack_f16(acc[3][h][e] * ds, acc[4][h][e] * ds), pack_f16(acc[5][h][e] * ds, acc[6][h][e] * ds));
        }
}

__device__ __forceinline__ void build_far(uint32_t fb, uint32_t ubase, int r, bool seg3) {
    const int m0 = r - 1;
    const uint32_t a0 = ubase + m0 * 32 + (m0 >> 4) * 16, a1 = ubase + r * 32 + (r >> 4) * 16;
    uint4 q0 = lds128(a0), q1 = lds128(a0 + 16), q2 = lds128(a1), q3 = lds128(a1 + 16);
    const uint32_t w[16] = {q0.x, q0.y, q0.z, q0.w, q1.x, q1.y, q1.z, q1.w, q2.x, q2.y, q2.z, q2.w, q3.x, q3.y, q3.z, q3.w};
    float P[30];
    P[4] = 0.f;
#pragma unroll
    for (int e = 4; e <= 28; e++) P[e + 1] = P[e] + ((e & 1) ? h_hi(w[e >> 1]) : h_lo(w[e >> 1]));
#define BOX8(addr, lo, hi_) sts128(addr, pack_f16(P[hi_ + 1] - P[lo], P[hi_ + 2] - P[lo + 1]), pack_f16(P[hi_ + 3] - P[lo + 2], P[hi_ + 4] - P[lo + 3]), \
                                   pack_f16(P[hi_ + 5] - P[lo + 4], P[hi_ + 6] - P[lo + 5]), pack_f16(P[hi_ + 7] - P[lo + 6], P[hi_ + 8] - P[lo + 7]))
    const uint32_t rb = fb + r * 16;
    BOX8(rb + F_O5, 6, 10);
    BOX8(rb + F_E5, 14, 18);
    BOX8(rb + F_E3, 11, 13);
    BOX8(rb + F_O3 + 16, 19, 21);
    if (seg3) {
        BOX8(rb + F_E7, 5, 11);
        BOX8(rb + F_O7, 13, 19);
        BOX8(rb + F_O9, 4, 12);
        BOX8(rb + F_E9 + 16, 12, 20);
        BOX8(rb + F_E2, 12, 13);
        BOX8(rb + F_O2, 20, 21);
    }
#undef BOX8
    if (r == 0) { sts128(fb + F_O3, 0, 0, 0, 0); sts128(fb + F_E9, 0, 0, 0, 0); }
}

template <int NT>
__device__ __forceinline__ void near_finish(float (&acc)[6][4], uint32_t fb, int j0, int wbase, float inv, uint32_t ydst, uint32_t mby, int lane
) {
    const int g = lane >> 2, c = lane & 3;
    uint32_t w0[6], w1[6];
    const float s9 = 512.0f;
#pragma unroll
    for (int t = 0; t < NT; t++) {
        const int j = j0 + t;
        uint32_t f0, f1;
        ldsm2(f0, f1, fb + (j * 16 + ((lane & 15) ^ (j & 1))) * 16);
        float y0 = fmaf(h_lo(f0), s9, acc[t][0]) * inv, y1 = fmaf(h_hi(f0), s9, acc[t][1]) * inv;
        float y2 = fmaf(h_lo(f1), s9, acc[t][2]) * inv, y3 = fmaf(h_hi(f1), s9, acc[t][3]) * inv;
        w0[t] = pack_bf16(y0, y2); w1[t] = pack_bf16(y1, y3);
    }
    const uint32_t d0 = mapa(ydst + wbase * 4, 2 * c), d1 = mapa(ydst + wbase * 4, 2 * c + 1);
    const uint32_t m0 = mapa(mby, 2 * c), m1 = mapa(mby, 2 * c + 1);
    st_async4(d0 + g * 16, w0[0], w0[1], w0[2], w0[3], m0);
    st_async4(d1 + g * 16, w1[0], w1[1], w1[2], w1[3], m1);
    if (NT == 6) { st_async2(d0 + 128 + g * 8, w0[4], w0[5], m0); st_async2(d1 + 128 + g * 8, w1[4], w1[5], m1); }
    else         { st_async1(d0 + 128 + g * 4, w0[4], m0);        st_async1(d1 + 128 + g * 4, w1[4], m1); }
}

struct Params {
    const __nv_bfloat16 *x, *Are, *Aim, *Bre, *Bim, *Cre, *Cim, *logdt, *dskip, *wr, *wd;
    __nv_bfloat16* out;
};

__global__ void __cluster_dims__(CS, 1, 1) __launch_bounds__(NTHR, 1)
fused_kernel(const Params prm, const __grid_constant__ CUtensorMap tmG, const __grid_constant__ CUtensorMap tmU, const __grid_constant__ CUtensorMap tmD)
{
    extern __shared__ __align__(1024) unsigned char smem[];
    const uint32_t sb = (uint32_t)__cvta_generic_to_shared(smem);
    const int tid = threadIdx.x, lane = tid & 31, warp = tid >> 5;
    const int c = blockIdx.x >> 3, q = blockIdx.x & 7;
    const int nslot = (c < NCL - 1) ? 5 : 2;
    const int d0 = 40 * c;
    const int g = lane >> 2, cq = lane & 3;
    const int k = warp >> 2, wq = warp & 3;
    const bool kact = k < nslot;
    const uint32_t mb = sb + SM_MB;
    STAMP(0);

    const unsigned short* xs = (const unsigned short*)prm.x;
    unsigned short pAre = 0, pAim = 0, pBre = 0, pBim = 0, pCre = 0, pCim = 0, pLdt = 0;
    if (kact) {
        const int dch = d0 + 8 * k + q, idx = dch * 128 + wq * 32 + lane;
        pAre = __ldg((const unsigned short*)prm.Are + idx); pAim = __ldg((const unsigned short*)prm.Aim + idx);
        pBre = __ldg((const unsigned short*)prm.Bre + idx); pBim = __ldg((const unsigned short*)prm.Bim + idx);
        pCre = __ldg((const unsigned short*)prm.Cre + idx); pCim = __ldg((const unsigned short*)prm.Cim + idx);
        pLdt = __ldg((const unsigned short*)prm.logdt + dch);
    }
    const int lrow = 18 * c + warp;
    const bool rowact = warp < 18 && lrow < 256;
    const int trow = 256 * q + lrow;
    uint4 rx0 = make_uint4(0, 0, 0, 0), rx1 = rx0, rx2 = rx0; unsigned short rxf = 0;
    if (rowact) {
        const uint4* rp = (const uint4*)(xs + (size_t)trow * D_);
        rx0 = __ldg(rp + lane); rx1 = __ldg(rp + 32 + lane);
        if (lane < 8) rx2 = __ldg(rp + 64 + lane);
        rxf = __ldg(xs + (size_t)trow * D_);
    }
    for (int i = tid; i < 256 * nslot; i += NTHR) {
        const int t = i / nslot, kk = i - t * nslot;
        asm volatile("cp.async.cg.shared.global [%0], [%1], 16;" :: "r"(sb + SM_XT + (t >> 3) * 672 + (t & 7) * 80 + kk * 16),
                     "l"(xs + (size_t)(256 * q + t) * D_ + d0 + 8 * kk) : "memory");
    }
    asm volatile("cp.async.commit_group;" ::: "memory");
    const unsigned epoch = ld_rlx(&g_ctl.epoch) + 1;
    if (rowact && lane == 0) g_acc[trow] = make_float4(0.f, 0.f, 0.f, 0.f);
    if (tid == 0) {
#pragma unroll
        for (int i = 0; i < 10; i++) asm volatile("mbarrier.init.shared::cta.b64 [%0], 1;" :: "r"(mb + i * 8) : "memory");
        asm volatile("fence.mbarrier_init.release.cluster;" ::: "memory");
        auto arm = [&](int i, int bytes) { asm volatile("mbarrier.arrive.expect_tx.shared::cta.b64 _, [%0], %1;" :: "r"(mb + i * 8), "r"(bytes) : "memory"); };
        for (int i = 0; i < 5; i++) arm(MB_X0 + i, 4096);
        arm(MB_Y, 4096 * nslot); arm(MB_W1, 92160); arm(MB_W2, nslot == 5 ? 46080 : 23040); arm(MB_KEY, 512); arm(MB_GU, nslot * 1024);
    }
    for (int i = tid; i < 5 * P_SZ / 16; i += NTHR) sts128(sb + SM_P + i * 16, 0, 0, 0, 0);
    if (tid < 5 * 66) sts128(sb + SM_U + (tid / 66) * U_SZ + (tid % 66) * 16, 0, 0, 0, 0);
    __syncthreads();
    asm volatile("barrier.cluster.arrive.relaxed.aligned;" ::: "memory");
    if (tid == 0) {
        const int f0 = 320 * c + 8 * nslot * q;
#pragma unroll
        for (int i = 0; i < 3; i++) {
            tma2d(sb + SM_WG + i * 15360, &tmG, f0, 192 * i, mb + MB_W1 * 8);
            tma2d(sb + SM_WU + i * 15360, &tmU, f0, 192 * i, mb + MB_W1 * 8);
        }
        const char* wdp = (const char*)prm.wd + (size_t)f0 * (D_ * 2);
        for (int i = 0; i < nslot; i++)
            asm volatile("cp.async.bulk.prefetch.L2.global [%0], %1;" :: "l"(wdp + i * 9216), "r"(9216) : "memory");
    }
    if (warp == 19) {
        float s = 0.f;
        for (int i = lane; i < D_ / 2; i += 32) { uint32_t v = __ldg((const uint32_t*)prm.wr + i); s += bf_lo(v) + bf_hi(v); }
#pragma unroll
        for (int o = 16; o; o >>= 1) s += __shfl_xor_sync(~0u, s, o);
        if (lane == 0) stsf(sb + SM_SC + 24, s);
    }
    STAMP(1);

    const uint32_t fb = sb + SM_FAR + k * FAR_SZ;
    const uint32_t kb = fb + wq * 2560;
    const uint32_t pch = sb + SM_P + k * P_SZ;
    uint32_t Af[4][4];
    float wr_ = 0.f, wi_ = 0.f, z1r = 0.f, z1i = 0.f, zhr = 0.f, zhi = 0.f;
    if (kact) {
        const float dt = bfr(expf(__uint_as_float((uint32_t)pLdt << 16)));
        const float are = dt * __uint_as_float((uint32_t)pAre << 16), aim = dt * __uint_as_float((uint32_t)pAim << 16);
        const float dbr = dt * __uint_as_float((uint32_t)pBre << 16), dbi = dt * __uint_as_float((uint32_t)pBim << 16);
        cmul(wr_, wi_, __uint_as_float((uint32_t)pCre << 16), __uint_as_float((uint32_t)pCim << 16), dbr, dbi);
        unsigned mx = __reduce_max_sync(~0u, __float_as_uint(fmaxf(fabsf(wr_), fabsf(wi_))));
        float s0 = wr_;
#pragma unroll
        for (int o = 16; o; o >>= 1) s0 += __shfl_xor_sync(~0u, s0, o);
        if (lane == 0) { sts32(sb + SM_KG + warp * 8, mx); stsf(sb + SM_KG + warp * 8 + 4, s0); }
        const float e2 = are * 1.4426950408889634f, tn = aim * 0.15915494309189535f;
        float z8r, z8i;
        cexp_s(z8r, z8i, e2 * 8.f, tn * 8.f);
        cexp_s(z1r, z1i, e2, -tn);
        cexp_s(zhr, zhi, e2 * 128.f, -tn * 128.f);
        float er[16], ei[16];
        er[0] = 1.f; ei[0] = 0.f; er[1] = z8r; ei[1] = z8i;
#pragma unroll
        for (int j = 2; j < 16; j++) cmul(er[j], ei[j], er[j >> 1], ei[j >> 1], er[j - (j >> 1)], ei[j - (j >> 1)]);
        sts128(kb + lane * 16,        pack_f16(er[0], er[1]), pack_f16(er[2], er[3]), pack_f16(er[4], er[5]), pack_f16(er[6], er[7]));
        sts128(kb + 512 + lane * 16,  pack_f16(er[8], er[9]), pack_f16(er[10], er[11]), pack_f16(er[12], er[13]), pack_f16(er[14], er[15]));
        sts128(kb + 1024 + lane * 16, pack_f16(ei[0], ei[1]), pack_f16(ei[2], ei[3]), pack_f16(ei[4], ei[5]), pack_f16(ei[6], ei[7]));
        sts128(kb + 1536 + lane * 16, pack_f16(ei[8], ei[9]), pack_f16(ei[10], ei[11]), pack_f16(ei[12], ei[13]), pack_f16(ei[14], ei[15]));
        __syncwarp();
#pragma unroll
        for (int ks = 0; ks < 4; ks++) ldsm4t(Af[ks], kb + (lane >> 3) * 512 + (8 * ks + (lane & 7)) * 16);
        bar_sync(1 + k, 128);
    }
    STAMP(2);

    if (rowact) {
        const float x0 = __uint_as_float((uint32_t)rxf << 16);
        float s1 = 0.f, s2 = 0.f;
        const uint32_t v[12] = {rx0.x, rx0.y, rx0.z, rx0.w, rx1.x, rx1.y, rx1.z, rx1.w, rx2.x, rx2.y, rx2.z, rx2.w};
#pragma unroll
        for (int i = 0; i < 8; i++) { float a = bf_lo(v[i]) - x0, b = bf_hi(v[i]) - x0; s1 += a + b; s2 = fmaf(a, a, fmaf(b, b, s2)); }
        if (lane < 8) {
#pragma unroll
            for (int i = 8; i < 12; i++) { float a = bf_lo(v[i]) - x0, b = bf_hi(v[i]) - x0; s1 += a + b; s2 = fmaf(a, a, fmaf(b, b, s2)); }
        }
#pragma unroll
        for (int o = 16; o; o >>= 1) { s1 += __shfl_xor_sync(~0u, s1, o); s2 += __shfl_xor_sync(~0u, s2, o); }
        if (lane == 0) {
            const float dm = s1 * (1.f / D_);
            const float var = fmaxf(s2 * (1.f / D_) - dm * dm, 0.f);
            const float sd = sqrtf(bfr(bfr(var) + 1e-5f));
            __threadfence();
            st_rlx64(&g_st1[trow], pack_bf16(x0 + dm, sd), epoch);
        }
    }
    STAMP(3);

    if (kact) {
        uint4 m01 = lds128(sb + SM_KG + k * 32), m23 = lds128(sb + SM_KG + k * 32 + 16);
        unsigned E = max(max(m01.x, m01.z), max(m23.x, m23.z)) >> 23;
        E = min(max(E, 1u), 253u);
        const float sc = __uint_as_float((254u - E) << 23);
        if (wq == 0 && lane == 0) {
            stsf(sb + SM_SC + k * 4, __uint_as_float(E << 23));
            const float k0 = (__uint_as_float(m01.y) + __uint_as_float(m01.w) + __uint_as_float(m23.y) + __uint_as_float(m23.w)) * sc;
            const uint32_t hk = pack_f16(k0, 0.f);
            sts16(pch + P_NEAR, hk); sts16(pch + P_NEAR + 4 + 2, hk);
        }
        float tr[8], ti[8];
        float acc[5][4];
        const uint32_t la = kb + ((lane >> 3) & 1) * 512 + (8 * (lane >> 4) + (lane & 7)) * 16;
        auto tile = [&](int t) {
            sts128(kb + lane * 16,       pack_f16(tr[0], tr[1]), pack_f16(tr[2], tr[3]), pack_f16(tr[4], tr[5]), pack_f16(tr[6], tr[7]));
            sts128(kb + 512 + lane * 16, pack_f16(ti[0], ti[1]), pack_f16(ti[2], ti[3]), pack_f16(ti[4], ti[5]), pack_f16(ti[6], ti[7]));
            __syncwarp();
            uint32_t b0[4], b1[4];
            ldsm4t(b0, la); ldsm4t(b1, la + 256);
            __syncwarp();
            acc[t][0] = acc[t][1] = acc[t][2] = acc[t][3] = 0.f;
            mma_f16(acc[t], Af[0][0], Af[0][1], Af[0][2], Af[0][3], b0[0], b0[1]);
            mma_f16(acc[t], Af[1][0], Af[1][1], Af[1][2], Af[1][3], b0[2], b0[3]);
            mma_f16(acc[t], Af[2][0], Af[2][1], Af[2][2], Af[2][3], b1[0], b1[1]);
            mma_f16(acc[t], Af[3][0], Af[3][1], Af[3][2], Af[3][3], b1[2], b1[3]);
        };
        cmul(tr[0], ti[0], wr_ * sc, -wi_ * sc, z1r, z1i);
        {
            float z2r, z2i, z4r, z4i;
            cmul(z2r, z2i, z1r, z1i, z1r, z1i); cmul(z4r, z4i, z2r, z2i, z2r, z2i);
            cmul(tr[1], ti[1], tr[0], ti[0], z1r, z1i);
            cmul(tr[2], ti[2], tr[0], ti[0], z2r, z2i); cmul(tr[3], ti[3], tr[1], ti[1], z2r, z2i);
#pragma unroll
            for (int s = 4; s < 8; s++) cmul(tr[s], ti[s], tr[s - 4], ti[s - 4], z4r, z4i);
        }
        tile(0);
#pragma unroll
        for (int s = 0; s < 8; s++) { float a, b; cmul(a, b, tr[s], ti[s], zhr, zhi); tr[s] = a; ti[s] = b; }
        tile(1);
#pragma unroll
        for (int s = 0; s < 4; s++) { float a, b; cmul(a, b, tr[2 * s + 1], ti[2 * s + 1], zhr, zhi); tr[s] = a; ti[s] = b; }
#pragma unroll
        for (int s = 4; s < 8; s++) cmul(tr[s], ti[s], tr[s - 4], ti[s - 4], zhr, zhi);
        tile(2);
        { float a, b; cmul(a, b, tr[5], ti[5], zhr, zhi); tr[0] = a; ti[0] = b; cmul(a, b, tr[7], ti[7], zhr, zhi); tr[1] = a; ti[1] = b; }
#pragma unroll
        for (int s = 2; s < 8; s++) cmul(tr[s], ti[s], tr[s - 2], ti[s - 2], zhr, zhi);
        tile(3);
        {
            float zqr, zqi, a, b;
            cmul(zqr, zqi, zhr, zhi, zhr, zhi);
            cmul(a, b, tr[7], ti[7], zhr, zhi); cmul(tr[1], ti[1], tr[7], ti[7], zqr, zqi); tr[0] = a; ti[0] = b;
#pragma unroll
            for (int s = 2; s < 8; s++) cmul(tr[s], ti[s], tr[s - 2], ti[s - 2], zqr, zqi);
        }
        tile(4);
#pragma unroll
        for (int t = 0; t < 4; t++) sts128f(kb + t * 512 + lane * 16, acc[t][0], acc[t][1], acc[t][2], acc[t][3]);
#pragma unroll
        for (int e = 0; e < 4; e++) stsf(kb + 2048 + e * 128 + lane * 4, acc[4][e]);
        bar_sync(1 + k, 128);
        float v[4] = {0.f, 0.f, 0.f, 0.f}, v4 = 0.f;
#pragma unroll
        for (int w = 0; w < 4; w++) {
            float4 p = lds128f(fb + w * 2560 + wq * 512 + lane * 16);
            v[0] += p.x; v[1] += p.y; v[2] += p.z; v[3] += p.w;
            v4 += ldsf(fb + w * 2560 + 2048 + wq * 128 + lane * 4);
        }
#pragma unroll
        for (int hf = 0; hf < 2; hf++) {
            const int j = g + 8 * hf;
            float a = v[2 * hf], b = v[2 * hf + 1];
            if (wq < 2) {
                const uint32_t pa = pch + P_NEAR + (1 + 128 * wq + 8 * j + 2 * cq) * 4;
                const uint32_t w = pack_f16(b, a);
                sts16(pa, w >> 16); sts32(pa + 4, w); sts16(pa + 8 + 2, w);
                if (wq == 1 && hf == 1 && lane == 31) { sts16(pa + 8, w); sts16(pa + 12 + 2, w); }
            } else if (wq == 2) {
                const uint32_t pa = pch + P_NEAR + (258 + 4 * (cq & 1) + 128 * (cq >> 1) + 8 * j) * 4;
                if (hf == 1 && lane == 31) {
                    const uint32_t w = pack_f16(b, a - b);
                    sts16(pa, w >> 16); sts16(pa + 4 + 2, w >> 16);
                    sts16(pch + P_G0, w); sts16(pch + P_G0 + 4 + 2, w);
                } else {
                    const uint32_t w = pack_f16(b, a), wb = __byte_perm(w, w, 0x1010);
                    sts16(pa, w >> 16); sts32(pa + 4, w); sts32(pa + 8, wb); sts32(pa + 12, wb); sts16(pa + 16 + 2, w);
                }
            } else {
                const uint32_t w = pack_f16(a, b);
                const int kap = 8 * cq + (j >> 1);
                const uint32_t pa = pch + P_G0 + ((j & 1) ? 3 : 1) * P_GS + kap * 4;
                const uint32_t pb = pch + P_G0 + ((j & 1) ? 4 : 2 * P_GS) + kap * 4;
                sts16(pa, w); sts16(pa + 4 + 2, w); sts16(pb, w >> 16); sts16(pb + 4 + 2, w >> 16);
            }
        }
        {
            const int j = g + 8 * (wq >> 1), n = 2 * cq + (wq & 1);
            const uint32_t w = pack_f16(v4, 0.f);
            const uint32_t pa = pch + P_H7 + (j & 1) * P_HS + (8 * n + (j >> 1)) * 4;
            sts16(pa, w); sts16(pa + 4 + 2, w);
        }
    }
    STAMP(4);

    if (tid < 128) {
        uint4 s; int it = 0;
        do { s = ld_rlx128(&g_st1[256 * q + 2 * tid]); } while ((s.y != epoch || s.w != epoch) && ++it < SPIN_LIMIT);
        sts32(sb + SM_M1 + tid * 4, __byte_perm(s.x, s.z, 0x5410));
        asm volatile("st.shared.v2.f32 [%0], {%1,%2};" :: "r"(sb + SM_RS1 + tid * 8), "f"(1.0f / bf_hi(s.x)), "f"(1.0f / bf_hi(s.z)) : "memory");
    }
    asm volatile("cp.async.wait_group 0;" ::: "memory");
    asm volatile("barrier.cluster.wait.aligned;" ::: "memory");
    __syncthreads();
    STAMP(5);

    for (int unit = warp; unit < 8 * nslot; unit += 20) {
        const int tg = unit & 7, kk = unit >> 3;
        const int r = lane & 7, mi = lane >> 3;
        uint32_t xv[4];
        ldsm4t(xv, sb + SM_XT + (4 * tg + (r >> 1)) * 672 + (2 * mi + (r & 1)) * 80 + kk * 16);
        const uint4 m2 = lds128(sb + SM_M1 + (32 * tg + 8 * cq) * 2);
        const float4 ra = lds128f(sb + SM_RS1 + (32 * tg + 8 * cq) * 4), rb = lds128f(sb + SM_RS1 + (32 * tg + 8 * cq) * 4 + 16);
        const uint32_t mm[4] = {m2.x, m2.y, m2.z, m2.w};
        const float rs[8] = {ra.x, ra.y, ra.z, ra.w, rb.x, rb.y, rb.z, rb.w};
        uint32_t o[4];
#pragma unroll
        for (int i = 0; i < 4; i++) {
            const uint32_t dd = bsub2(xv[i], mm[i]);
            const uint32_t n2 = pack_bf16(bf_lo(dd) * rs[2 * i], bf_hi(dd) * rs[2 * i + 1]);
            o[i] = pack_f16(bf_lo(n2), bf_hi(n2));
        }
        st_async4(mapa(sb + SM_U + kk * U_SZ + (q + 2) * U_PITCH + (32 * tg + 8 * cq) * 2, g), o[0], o[1], o[2], o[3], mapa(mb + (MB_X0 + kk) * 8, g));
    }
    STAMP(6);

    const int hb = tid >> 7, wi = tid & 127;
    int ta;
    if (wi < 32) ta = 16 * (wi & 3) + (wi >> 2);
    else if (wi < 48) ta = 16 * (4 + (wi & 1)) + ((wi - 32) >> 1);
    else if (wi < 80) ta = 16 * (6 + (wi & 3)) + ((wi - 48) >> 2);
    else if (wi < 88) ta = 160 + (wi - 80);
    else if (wi < 120) ta = 16 * (11 + (wi & 3)) + ((wi - 88) >> 2);
    else ta = 240 + (wi - 120);
    uint4 xa = make_uint4(0, 0, 0, 0), xb = xa, dk = xa, wk = xa;
    if (kact) {
        const int role = (wq + k) & 3;
        const uint32_t ub = sb + SM_U + k * U_SZ + 2 * U_PITCH;
        mbar_wait(mb + (MB_X0 + k) * 8);
        STAMP(7);
        if (role != 0) build_far(fb, ub, (3 - role) * 32 + lane, role != 1);
        else if (lane < 8) {
            float s = 0.f;
#pragma unroll
            for (int i = -2; i <= 2; i++) {
                const int t = 1528 + lane + i;
                unsigned short hv; asm volatile("ld.shared.u16 %0, [%1];" : "=h"(hv) : "r"(ub + t * 2 + (t >> 8) * 16) : "memory");
                s += __half2float(__ushort_as_half(hv));
            }
            sts16(fb + F_O5 + 96 * 16 + lane * 2, pack_f16(s, 0.f));
        }
        auto load_late = [&]() {
            const unsigned short* xr = xs + (size_t)(256 * q + ta) * D_ + d0 + 8 * hb;
            xa = __ldg((const uint4*)xr); xb = __ldg((const uint4*)(xr + 8 * D_));
            dk = __ldg((const uint4*)(prm.dskip + d0 + 8 * hb)); wk = __ldg((const uint4*)(prm.wr + d0 + 8 * hb));
        };
        if (role == 3) {
            bar_sync(1 + k, 128);
            far_conv(fb, pch, lane);
            bar_arrive(6 + k, 128);
            load_late();
            STAMP(8);
        } else {
            bar_arrive(1 + k, 128);
            float acc[6][4];
#pragma unroll
            for (int t = 0; t < 6; t++) acc[t][0] = acc[t][1] = acc[t][2] = acc[t][3] = 0.f;
            const uint32_t pbase = pch + P_NEAR + (g - 2 * cq) * 4;
            const int j0 = role == 0 ? 0 : (role == 1 ? 6 : 11);
            if (role == 0) near_conv<6>(acc, ub, pbase, 0, lane); else near_conv<5>(acc, ub, pbase, j0, lane);
            load_late();
            STAMP(8);
            for (int i = 0; i < nslot; i++) mbar_wait(mb + (MB_X0 + i) * 8);
            const float inv = ldsf(sb + SM_SC + k * 4);
            bar_sync(6 + k, 128);
            const uint32_t ydst = sb + SM_XT + (8 * k + q) * 512;
            if (role == 0) near_finish<6>(acc, fb, 0, 0, inv, ydst, mb + MB_Y * 8, lane);
            else near_finish<5>(acc, fb, j0, role == 1 ? 48 : 88, inv, ydst, mb + MB_Y * 8, lane);
        }
    }
    STAMP(9);

    uint32_t ha[4] = {0, 0, 0, 0}, hbv[4] = {0, 0, 0, 0};
    if (kact) {
        unsigned short ma, mbb;
        asm volatile("ld.shared.u16 %0, [%1];" : "=h"(ma) : "r"(sb + SM_M1 + ta * 2) : "memory");
        asm volatile("ld.shared.u16 %0, [%1];" : "=h"(mbb) : "r"(sb + SM_M1 + ta * 2 + 16) : "memory");
        const float rsa = ldsf(sb + SM_RS1 + ta * 4), rsb = ldsf(sb + SM_RS1 + ta * 4 + 32);
        const uint32_t ma2 = (uint32_t)ma * 0x10001u, mb2 = (uint32_t)mbb * 0x10001u;
        const uint32_t xav[4] = {xa.x, xa.y, xa.z, xa.w}, xbv[4] = {xb.x, xb.y, xb.z, xb.w};
        const uint32_t dkv[4] = {dk.x, dk.y, dk.z, dk.w}, wkv[4] = {wk.x, wk.y, wk.z, wk.w};
        uint32_t pa[4], pb[4];
#pragma unroll
        for (int i = 0; i < 4; i++) {
            uint32_t dd = bsub2(xav[i], ma2);
            pa[i] = bmul2(pack_bf16(bf_lo(dd) * rsa, bf_hi(dd) * rsa), dkv[i]);
            dd = bsub2(xbv[i], mb2);
            pb[i] = bmul2(pack_bf16(bf_lo(dd) * rsb, bf_hi(dd) * rsb), dkv[i]);
        }
        mbar_wait(mb + MB_Y * 8);
        STAMP(10);
        const float ca = bf_lo(ma2), cb = bf_lo(mb2);
        float a1 = 0.f, a2 = 0.f, a3 = 0.f, b1 = 0.f, b2 = 0.f, b3 = 0.f;
#pragma unroll
        for (int i = 0; i < 4; i++) {
            const uint32_t y0 = lds32(sb + SM_XT + (8 * hb + 2 * i) * 512 + wi * 4), y1 = lds32(sb + SM_XT + (8 * hb + 2 * i + 1) * 512 + wi * 4);
            ha[i]  = badd2(xav[i], badd2(__byte_perm(y0, y1, 0x5410), pa[i]));
            hbv[i] = badd2(xbv[i], badd2(__byte_perm(y0, y1, 0x7632), pb[i]));
            const float wl = bf_lo(wkv[i]), wh = bf_hi(wkv[i]);
            float u0 = bf_lo(ha[i]) - ca, u1 = bf_hi(ha[i]) - ca;
            a1 += u0 + u1; a2 = fmaf(u0, u0, fmaf(u1, u1, a2)); a3 = fmaf(u0, wl, fmaf(u1, wh, a3));
            u0 = bf_lo(hbv[i]) - cb; u1 = bf_hi(hbv[i]) - cb;
            b1 += u0 + u1; b2 = fmaf(u0, u0, fmaf(u1, u1, b2)); b3 = fmaf(u0, wl, fmaf(u1, wh, b3));
        }
        sts128f(sb + SM_SP + (hb * 256 + ta) * 16, a1, a2, a3, 0.f);
        sts128f(sb + SM_SP + (hb * 256 + ta + 8) * 16, b1, b2, b3, 0.f);
    }
    asm volatile("fence.proxy.async.shared::cta;" ::: "memory");
    __syncthreads();
    if (tid < 256) {
        float s1 = 0.f, s2 = 0.f, s3 = 0.f;
        for (int b = 0; b < nslot; b++) { float4 p = lds128f(sb + SM_SP + (b * 256 + tid) * 16); s1 += p.x; s2 += p.y; s3 += p.z; }
        asm volatile("red.relaxed.gpu.global.add.v4.f32 [%0], {%1,%2,%3,%4};" :: "l"(&g_acc[256 * q + tid]), "f"(s1), "f"(s2), "f"(s3), "f"(1.0f) : "memory");
    }
    if (tid == 256) {
        tma2d(sb + SM_W2, &tmD, 72 * q, 320 * c, mb + MB_W2 * 8);
        if (nslot == 5) tma2d(sb + SM_W2 + 23040, &tmD, 72 * q, 320 * c + 160, mb + MB_W2 * 8);
    }
    if (kact) {
        uint4* hp = (uint4*)(g_h + (size_t)(256 * q + ta) * D_ + d0 + 8 * hb);
        hp[0] = make_uint4(ha[0], ha[1], ha[2], ha[3]);
        hp[D_] = make_uint4(hbv[0], hbv[1], hbv[2], hbv[3]);
    }
    if (warp == 19) {
        bar_sync(11, NTHR);
        if (lane == 0) {
            __threadfence();
            asm volatile("red.relaxed.gpu.global.add.u32 [%0], 1;" :: "l"(&g_ctl.hcnt) : "memory");
            int it = 0;
            while ((int)(ld_acq(&g_ctl.hcnt) - epoch * NCTA) < 0 && ++it < SPIN_LIMIT) {}
        }
        __syncwarp();
    } else bar_arrive(11, NTHR);
    STAMP(11);

    if (tid < 256) {
        uint4 s; int it = 0;
        do { s = ld_rlx128(&g_acc[256 * q + tid]); } while (__uint_as_float(s.w) != (float)NCL && ++it < SPIN_LIMIT);
        unsigned short m1; asm volatile("ld.shared.u16 %0, [%1];" : "=h"(m1) : "r"(sb + SM_M1 + tid * 2) : "memory");
        const float cs = __uint_as_float((uint32_t)m1 << 16);
        const float dm = __uint_as_float(s.x) * (1.f / D_);
        const float var = fmaxf(__uint_as_float(s.y) * (1.f / D_) - dm * dm, 0.f);
        const uint32_t ms = pack_bf16(cs + dm, sqrtf(bfr(bfr(var) + 1e-5f)));
        const float rs = 1.0f / bf_hi(ms);
        const float r = (__uint_as_float(s.z) - (bf_lo(ms) - cs) * ldsf(sb + SM_SC + 24)) * rs;
        const uint32_t rb = pack_bf16(r, 0.f);
        const uint32_t key = ((rb ^ ((rb & 0x8000u) ? 0xFFFFu : 0x8000u)) << 16) | (uint32_t)(2047 - (256 * q + tid));
        sts32(sb + SM_M2 + tid * 4, ms); stsf(sb + SM_RS2 + tid * 4, rs);
        sts32(sb + SM_KEY + tid * 4, key);
        __syncwarp();
        int rank = 0;
#pragma unroll
        for (int i = 0; i < 8; i++) { uint4 o = lds128(sb + SM_KEY + warp * 128 + i * 16); rank += (o.x > key) + (o.y > key) + (o.z > key) + (o.w > key); }
        if (rank < 8) sts32(sb + SM_CAND + (warp * 8 + rank) * 4, key);
        bar_sync(12, 256);
        uint32_t mk = lds32(sb + SM_CAND + (tid >> 2) * 4);
        rank = 0;
#pragma unroll
        for (int i = 0; i < 4; i++) { uint4 o = lds128(sb + SM_CAND + cq * 64 + i * 16); rank += (o.x > mk) + (o.y > mk) + (o.z > mk) + (o.w > mk); }
        rank += __shfl_xor_sync(~0u, rank, 1); rank += __shfl_xor_sync(~0u, rank, 2);
        if (rank < 8) {
            const uint32_t msv = lds32(sb + SM_M2 + ((2047 - (mk & 0xFFFF)) & 255) * 4);
#pragma unroll
            for (int i = 0; i < 2; i++) {
                const uint32_t dst = mapa(sb + SM_RK + (q * 8 + rank) * 4, 2 * cq + i), mk_ = mapa(mb + MB_KEY * 8, 2 * cq + i);
                st_async1(dst, mk, mk_); st_async1(dst + 256, msv, mk_);
            }
        }
        mbar_wait(mb + MB_KEY * 8);
        mk = lds32(sb + SM_RK + (tid >> 2) * 4);
        rank = 0;
#pragma unroll
        for (int i = 0; i < 4; i++) { uint4 o = lds128(sb + SM_RK + cq * 64 + i * 16); rank += (o.x > mk) + (o.y > mk) + (o.z > mk) + (o.w > mk); }
        rank += __shfl_xor_sync(~0u, rank, 1); rank += __shfl_xor_sync(~0u, rank, 2);
        if (rank < 8 && cq == 0) { sts32(sb + SM_SEL + rank * 8, mk); sts32(sb + SM_SEL + rank * 8 + 4, lds32(sb + SM_RMS + (tid >> 2) * 4)); }
    }
    __syncthreads();
    STAMP(12);
    if (blockIdx.x == 0 && tid == 0) g_ctl.epoch = epoch;

    if (tid < 576) {
        const int tk = tid / 72, ck = tid - tk * 72;
        const uint32_t key = lds32(sb + SM_SEL + tk * 8), ms = lds32(sb + SM_SEL + tk * 8 + 4);
        const int t = 2047 - (int)(key & 0xFFFF);
        const uint4 hv = __ldcg((const uint4*)(g_h + (size_t)t * D_) + ck);
        const uint32_t m2 = __byte_perm(ms, ms, 0x1010);
        const float rs = 1.0f / bf_hi(ms);
        const uint32_t hh[4] = {hv.x, hv.y, hv.z, hv.w};
        uint32_t o[4];
#pragma unroll
        for (int i = 0; i < 4; i++) { const uint32_t dd = bsub2(hh[i], m2); o[i] = pack_bf16(bf_lo(dd) * rs, bf_hi(dd) * rs); }
        sts128(sb + SM_XS + tk * 1168 + ck * 16, o[0], o[1], o[2], o[3]);
        if (tk == q && ck >= 5 * c && ck < 5 * c + 5) sts128(sb + SM_HS + (ck - 5 * c) * 16, hv.x, hv.y, hv.z, hv.w);
    }
    const int mt = warp % 5, kq = warp / 5;
    const int mi = lane >> 3, mr = lane & 7;
    mbar_wait(mb + MB_W1 * 8);
    {
        uint32_t A[9][4];
        const uint32_t aa = sb + ((mi & 1) ? SM_WU : SM_WG) + (144 * kq + 8 * (mi >> 1) + mr) * 80 + mt * 16;
#pragma unroll
        for (int s = 0; s < 9; s++) ldsm4t(A[s], aa + s * 1280);
        __syncthreads();
        STAMP(13);
        float c0[4] = {0.f, 0.f, 0.f, 0.f}, c1[4] = {0.f, 0.f, 0.f, 0.f}, c2[4] = {0.f, 0.f, 0.f, 0.f};
        const uint32_t ba = sb + SM_XS + mr * 1168 + (144 * kq + 8 * mi) * 2;
        uint32_t b[4][4], b8, b9;
#pragma unroll
        for (int s = 0; s < 4; s++) ldsm4(b[s], ba + s * 64);
        ldsm2(b8, b9, sb + SM_XS + mr * 1168 + (144 * kq + 128 + 8 * (mi & 1)) * 2);
        mma_bf16(c0, A[0][0], A[0][1], A[0][2], A[0][3], b[0][0], b[0][1]);
        mma_bf16(c1, A[1][0], A[1][1], A[1][2], A[1][3], b[0][2], b[0][3]);
        mma_bf16(c2, A[2][0], A[2][1], A[2][2], A[2][3], b[1][0], b[1][1]);
        mma_bf16(c0, A[3][0], A[3][1], A[3][2], A[3][3], b[1][2], b[1][3]);
        mma_bf16(c1, A[4][0], A[4][1], A[4][2], A[4][3], b[2][0], b[2][1]);
        mma_bf16(c2, A[5][0], A[5][1], A[5][2], A[5][3], b[2][2], b[2][3]);
        mma_bf16(c0, A[6][0], A[6][1], A[6][2], A[6][3], b[3][0], b[3][1]);
        mma_bf16(c1, A[7][0], A[7][1], A[7][2], A[7][3], b[3][2], b[3][3]);
        mma_bf16(c2, A[8][0], A[8][1], A[8][2], A[8][3], b8, b9);
        sts128f(sb + SM_RED + warp * 512 + lane * 16, c0[0] + c1[0] + c2[0], c0[1] + c1[1] + c2[1], c0[2] + c1[2] + c2[2], c0[3] + c1[3] + c2[3]);
    }
    __syncthreads();
    if (mt < nslot) {
        float v[4] = {0.f, 0.f, 0.f, 0.f};
#pragma unroll
        for (int w = 0; w < 4; w++) { float4 p = lds128f(sb + SM_RED + (w * 5 + mt) * 512 + lane * 16); v[0] += p.x; v[1] += p.y; v[2] += p.z; v[3] += p.w; }
        const float g0 = bfr(v[0]), g1 = bfr(v[1]);
        const uint32_t sg = pack_bf16(g0 / (1.f + __expf(-g0)), g1 / (1.f + __expf(-g1)));
        const uint32_t gu = bmul2(sg, pack_bf16(v[2], v[3]));
#pragma unroll
        for (int i = 0; i < 2; i++)
            st_async1(mapa(sb + SM_GU + ((q * nslot + mt) * 8) * 16 + lane * 4, 2 * kq + i), gu, mapa(mb + MB_GU * 8, 2 * kq + i));
    }
    mbar_wait(mb + MB_W2 * 8);
    {
        uint32_t A[5][4];
        const uint32_t aa = sb + SM_W2 + (16 * nslot * kq + 8 * (mi >> 1) + mr) * 144 + mt * 32 + (mi & 1) * 16;
#pragma unroll
        for (int s = 0; s < 5; s++) if (s < nslot) ldsm4t(A[s], aa + s * 2304);
        mbar_wait(mb + MB_GU * 8);
        float c0[4] = {0.f, 0.f, 0.f, 0.f}, c1[4] = {0.f, 0.f, 0.f, 0.f};
        const uint32_t ba = sb + SM_GU + (16 * nslot * kq + (lane & 15)) * 16;
#pragma unroll
        for (int s = 0; s < 5; s++) if (s < nslot) {
            uint32_t b0, b1;
            ldsm2t(b0, b1, ba + s * 256);
            if (s & 1) mma_bf16(c1, A[s][0], A[s][1], A[s][2], A[s][3], b0, b1);
            else       mma_bf16(c0, A[s][0], A[s][1], A[s][2], A[s][3], b0, b1);
        }
        sts128f(sb + SM_SP + warp * 512 + lane * 16, c0[0] + c1[0], c0[1] + c1[1], c0[2] + c1[2], c0[3] + c1[3]);
    }
    __syncthreads();
    STAMP(14);
    if (tid < 576) {
        const int tk = tid / 72, dd = tid - tk * 72;
        const uint32_t a = sb + SM_SP + (dd >> 4) * 512 + ((dd & 7) * 4 + (tk >> 1)) * 16 + (((dd >> 3) & 1) * 2 + (tk & 1)) * 4;
        const float s = (ldsf(a) + ldsf(a + 2560)) + (ldsf(a + 5120) + ldsf(a + 7680));
        st_rlx64(&g_part[(tk * NCL + c) * D_ + 72 * q + dd], __float_as_uint(s), epoch);
    }
    if (kact) {
        bool sa = false, sbb = false;
#pragma unroll
        for (int i = 0; i < 8; i++) {
            const int t = 2047 - (int)(lds32(sb + SM_SEL + i * 8) & 0xFFFF);
            sa |= (t == 256 * q + ta); sbb |= (t == 256 * q + ta + 8);
        }
        const uint32_t msa = lds32(sb + SM_M2 + ta * 4), msb = lds32(sb + SM_M2 + ta * 4 + 32);
        const float rsa = ldsf(sb + SM_RS2 + ta * 4), rsb = ldsf(sb + SM_RS2 + ta * 4 + 32);
        const uint32_t ma2 = __byte_perm(msa, msa, 0x1010), mb2 = __byte_perm(msb, msb, 0x1010);
        uint32_t oa[4], ob[4];
#pragma unroll
        for (int i = 0; i < 4; i++) {
            uint32_t dd = bsub2(ha[i], ma2);
            oa[i] = badd2(ha[i], pack_bf16(bf_lo(dd) * rsa, bf_hi(dd) * rsa));
            dd = bsub2(hbv[i], mb2);
            ob[i] = badd2(hbv[i], pack_bf16(bf_lo(dd) * rsb, bf_hi(dd) * rsb));
        }
        uint4* op = (uint4*)(prm.out + (size_t)(256 * q + ta) * D_ + d0 + 8 * hb);
        if (!sa) op[0] = make_uint4(oa[0], oa[1], oa[2], oa[3]);
        if (!sbb) op[D_] = make_uint4(ob[0], ob[1], ob[2], ob[3]);
    }
    const int cc = 8 * nslot;
    if (tid < NCL * cc) {
        const int cp = tid / cc, i = tid - cp * cc;
        uint2 v; int it = 0;
        do { v = ld_rlx64(&g_part[(q * NCL + cp) * D_ + d0 + i]); } while (v.y != epoch && ++it < SPIN_LIMIT);
        sts32(sb + SM_FIN + tid * 4, v.x);
    }
    __syncthreads();
    if (tid < cc) {
        float s = 0.f;
#pragma unroll
        for (int cp = 0; cp < NCL; cp++) s += ldsf(sb + SM_FIN + (cp * cc + tid) * 4);
        const uint32_t key = lds32(sb + SM_SEL + q * 8);
        const uint32_t kb16 = key >> 16;
        const float r = __uint_as_float((kb16 ^ ((kb16 & 0x8000u) ? 0x8000u : 0xFFFFu)) << 16);
        const float sig = bfr(1.f / (1.f + __expf(-r)));
        const float y = bfr(bfr(s) * sig);
        unsigned short hn16, h16;
        asm volatile("ld.shared.u16 %0, [%1];" : "=h"(hn16) : "r"(sb + SM_XS + q * 1168 + (d0 + tid) * 2) : "memory");
        asm volatile("ld.shared.u16 %0, [%1];" : "=h"(h16) : "r"(sb + SM_HS + tid * 2) : "memory");
        const float o = bfr(__uint_as_float((uint32_t)hn16 << 16) + y);
        prm.out[(size_t)(2047 - (int)(key & 0xFFFF)) * D_ + d0 + tid] = __float2bfloat16_rn(__uint_as_float((uint32_t)h16 << 16) + o);
    }
    STAMP(15);
}

typedef CUresult (*EncodeFn)(CUtensorMap*, CUtensorMapDataType, cuuint32_t, void*, const cuuint64_t*, const cuuint64_t*,
                             const cuuint32_t*, const cuuint32_t*, CUtensorMapInterleave, CUtensorMapSwizzle,
                             CUtensorMapL2promotion, CUtensorMapFloatOOBfill);

void make_map(EncodeFn fn, CUtensorMap* tm, const void* p, int cols, int rows, int bc, int br) {
    cuuint64_t dims[2] = {(cuuint64_t)cols, (cuuint64_t)rows};
    cuuint64_t strides[1] = {(cuuint64_t)cols * 2};
    cuuint32_t box[2] = {(cuuint32_t)bc, (cuuint32_t)br};
    cuuint32_t es[2] = {1, 1};
    fn(tm, CU_TENSOR_MAP_DATA_TYPE_BFLOAT16, 2, const_cast<void*>(p), dims, strides, box, es, CU_TENSOR_MAP_INTERLEAVE_NONE,
       CU_TENSOR_MAP_SWIZZLE_NONE, CU_TENSOR_MAP_L2_PROMOTION_NONE, CU_TENSOR_MAP_FLOAT_OOB_FILL_NONE);
}

}

extern "C" void kernel_launch(void* const* d_in, const int* in_sizes, int n_in, void* d_out, int out_size) {
    (void)in_sizes; (void)n_in; (void)out_size;
    void* fp = nullptr;
    cudaDriverEntryPointQueryResult qr;
    cudaGetDriverEntryPoint("cuTensorMapEncodeTiled", &fp, cudaEnableDefault, &qr);
    EncodeFn fn = (EncodeFn)fp;
    CUtensorMap tmG, tmU, tmD;
    make_map(fn, &tmG, d_in[11], F_, D_, 40, 192);
    make_map(fn, &tmU, d_in[12], F_, D_, 40, 192);
    make_map(fn, &tmD, d_in[13], D_, F_, 72, 160);
    Params p;
    p.x = (const __nv_bfloat16*)d_in[0];
    p.Are = (const __nv_bfloat16*)d_in[1]; p.Aim = (const __nv_bfloat16*)d_in[2];
    p.Bre = (const __nv_bfloat16*)d_in[3]; p.Bim = (const __nv_bfloat16*)d_in[4];
    p.Cre = (const __nv_bfloat16*)d_in[5]; p.Cim = (const __nv_bfloat16*)d_in[6];
    p.logdt = (const __nv_bfloat16*)d_in[7]; p.dskip = (const __nv_bfloat16*)d_in[8];
    p.wr = (const __nv_bfloat16*)d_in[10]; p.wd = (const __nv_bfloat16*)d_in[13];
    p.out = (__nv_bfloat16*)d_out;
    cudaFuncSetAttribute(fused_kernel, cudaFuncAttributeMaxDynamicSharedMemorySize, SM_TOTAL);
    fused_kernel<<<NCTA, NTHR, SM_TOTAL>>>(p, tmG, tmU, tmD);
}
```

```cpp
#include <cuda_runtime.h>
#include <cuda_bf16.h>
#include <cuda_fp16.h>
#include <cuda.h>
#include <stdint.h>

namespace {

constexpr int L_ = 2048, D_ = 576, F_ = 4608;
constexpr int NCL = 15, CS = 8, NCTA = NCL * CS, NTHR = 672;
constexpr int SPIN_LIMIT = 1 << 22;

constexpr int SM_WG   = 0;
constexpr int SM_WU   = 46080;
constexpr int SM_XT   = 92160;
constexpr int Y_SLOT  = 4128;
constexpr int SM_FAR  = SM_XT + 21504;
constexpr int FAR_SZ  = 12352;
constexpr int F_E5 = 0, F_O5 = 1536, F_E3 = 3088, F_O3 = 4624, F_E7 = 6176, F_E2 = F_E7 + 1024, F_E9 = F_E7 + 2048,
              F_H = 3088, F_O7 = F_E7 + F_H, F_O2 = F_E2 + F_H, F_O9 = F_E9 + F_H;
constexpr int SM_CH   = SM_FAR + 5 * FAR_SZ;
constexpr int P_NEAR = 8 * 4;
constexpr int P_G0 = (528 + 8) * 4, P_GS = 48 * 4;
constexpr int P_H7 = (528 + 192 + 8) * 4, P_HS = 80 * 4;
constexpr int P_SZ = (528 + 192 + 240) * 4;
constexpr int U_PITCH = 528;
constexpr int CH_U0 = P_SZ + 2 * U_PITCH;
constexpr int CH_SZ = P_SZ + 10 * U_PITCH;
constexpr int SM_MISC = SM_CH + 5 * CH_SZ;
constexpr int SM_M1   = SM_MISC;
constexpr int SM_RH1  = SM_M1 + 512;
constexpr int SM_RL1  = SM_RH1 + 512;
constexpr int SM_ST2  = SM_RL1 + 512;
constexpr int SM_KEY  = SM_ST2 + 2048;
constexpr int SM_CAND = SM_KEY + 1024;
constexpr int SM_RK   = SM_CAND + 256;
constexpr int SM_SEL  = SM_RK + 256;
constexpr int SM_KG   = SM_SEL + 64;
constexpr int SM_SC   = SM_KG + 160;
constexpr int SM_MB   = SM_SC + 32;
constexpr int SM_TOTAL = SM_MB + 128;
constexpr int SM_W2   = SM_FAR;
constexpr int SM_RED  = SM_FAR + 46080 + 128;
constexpr int SM_RED2 = SM_WG;
constexpr int SM_HT   = SM_CH;
constexpr int SM_XS   = SM_CH + 20608;
constexpr int SM_GU   = SM_XS + 9344;
constexpr int SM_FIN  = SM_GU + 5120;
constexpr int SM_HS   = SM_FIN + 2400;
static_assert(F_O9 + 1024 <= FAR_SZ, "far overflow");
static_assert(4 * Y_SLOT + 4096 + 96 <= 21504, "y overflow");
static_assert(SM_RED + 10240 <= SM_CH, "alias overflow");
static_assert(SM_HS + 128 <= SM_MISC, "alias overflow");
static_assert(SM_TOTAL <= 232448, "smem overflow");
static_assert(SM_FAR % 128 == 0 && SM_XT % 128 == 0 && SM_CH % 16 == 0 && CH_SZ % 16 == 0 && SM_MB % 8 == 0 && SM_HS % 16 == 0, "align");

enum { MB_X0 = 0, MB_Y = 5, MB_W1 = 6, MB_W2 = 7, MB_KEY = 8, MB_GU = 9, MB_OUT = 10 };

struct __align__(128) Scratch {
    unsigned epoch, zcnt, pad[30];
    uint4  st1[L_ * 2];
    float4 acc[L_];
    uint4  cand[64 * NCL * 6];
    uint2  part[8 * NCL * D_];
};
__device__ Scratch g_s;
#define STAMP(i)

__device__ __forceinline__ uint32_t mapa(uint32_t a, uint32_t r) { uint32_t d; asm("mapa.shared::cluster.u32 %0, %1, %2;" : "=r"(d) : "r"(a), "r"(r)); return d; }
__device__ __forceinline__ void mbar_wait(uint32_t mb) {
    asm volatile("{ .reg .pred p, q; .reg .u32 n; mov.u32 n, 0;\n"
                 "W_%=: mbarrier.try_wait.parity.shared::cta.b64 p, [%0], 0; add.u32 n, n, 1; setp.lt.and.u32 q, n, 65536, !p; @q bra W_%=; }" :: "r"(mb) : "memory");
}
__device__ __forceinline__ void bar_sync(int id, int n) { asm volatile("bar.sync %0, %1;" :: "r"(id), "r"(n) : "memory"); }
__device__ __forceinline__ void bar_arrive(int id, int n) { asm volatile("bar.arrive %0, %1;" :: "r"(id), "r"(n) : "memory"); }
__device__ __forceinline__ uint32_t lds16(uint32_t a) { unsigned short v; asm volatile("ld.shared.u16 %0, [%1];" : "=h"(v) : "r"(a) : "memory"); return v; }
__device__ __forceinline__ uint32_t lds32(uint32_t a) { uint32_t v; asm volatile("ld.shared.u32 %0, [%1];" : "=r"(v) : "r"(a) : "memory"); return v; }
__device__ __forceinline__ uint2 lds64(uint32_t a) { uint2 v; asm volatile("ld.shared.v2.u32 {%0,%1}, [%2];" : "=r"(v.x), "=r"(v.y) : "r"(a) : "memory"); return v; }
__device__ __forceinline__ float ldsf(uint32_t a) { float v; asm volatile("ld.shared.f32 %0, [%1];" : "=f"(v) : "r"(a) : "memory"); return v; }
__device__ __forceinline__ uint4 lds128(uint32_t a) { uint4 v; asm volatile("ld.shared.v4.u32 {%0,%1,%2,%3}, [%4];" : "=r"(v.x), "=r"(v.y), "=r"(v.z), "=r"(v.w) : "r"(a) : "memory"); return v; }
__device__ __forceinline__ float4 lds128f(uint32_t a) { float4 v; asm volatile("ld.shared.v4.f32 {%0,%1,%2,%3}, [%4];" : "=f"(v.x), "=f"(v.y), "=f"(v.z), "=f"(v.w) : "r"(a) : "memory"); return v; }
__device__ __forceinline__ void sts16(uint32_t a, uint32_t v) { asm volatile("{ .reg .b16 l, h; mov.b32 {l, h}, %1; st.shared.b16 [%0], l; }" :: "r"(a), "r"(v) : "memory"); }
__device__ __forceinline__ void sts32(uint32_t a, uint32_t v) { asm volatile("st.shared.u32 [%0], %1;" :: "r"(a), "r"(v) : "memory"); }
__device__ __forceinline__ void sts64(uint32_t a, uint32_t x, uint32_t y) { asm volatile("st.shared.v2.u32 [%0], {%1,%2};" :: "r"(a), "r"(x), "r"(y) : "memory"); }
__device__ __forceinline__ void stsf(uint32_t a, float v) { asm volatile("st.shared.f32 [%0], %1;" :: "r"(a), "f"(v) : "memory"); }
__device__ __forceinline__ void sts128(uint32_t a, uint32_t x, uint32_t y, uint32_t z, uint32_t w) { asm volatile("st.shared.v4.u32 [%0], {%1,%2,%3,%4};" :: "r"(a), "r"(x), "r"(y), "r"(z), "r"(w) : "memory"); }
__device__ __forceinline__ void sts128f(uint32_t a, float x, float y, float z, float w) { asm volatile("st.shared.v4.f32 [%0], {%1,%2,%3,%4};" :: "r"(a), "f"(x), "f"(y), "f"(z), "f"(w) : "memory"); }
__device__ __forceinline__ void ldsm4(uint32_t (&r)[4], uint32_t a) { asm volatile("ldmatrix.sync.aligned.m8n8.x4.shared.b16 {%0,%1,%2,%3}, [%4];" : "=r"(r[0]), "=r"(r[1]), "=r"(r[2]), "=r"(r[3]) : "r"(a) : "memory"); }
__device__ __forceinline__ void ldsm4t(uint32_t (&r)[4], uint32_t a) { asm volatile("ldmatrix.sync.aligned.m8n8.x4.trans.shared.b16 {%0,%1,%2,%3}, [%4];" : "=r"(r[0]), "=r"(r[1]), "=r"(r[2]), "=r"(r[3]) : "r"(a) : "memory"); }
__device__ __forceinline__ void ldsm2t(uint32_t& r0, uint32_t& r1, uint32_t a) { asm volatile("ldmatrix.sync.aligned.m8n8.x2.trans.shared.b16 {%0,%1}, [%2];" : "=r"(r0), "=r"(r1) : "r"(a) : "memory"); }
__device__ __forceinline__ uint32_t opaque(uint32_t v) { uint32_t r; asm volatile("mov.b32 %0, %1;" : "=r"(r) : "r"(v)); return r; }
__device__ __forceinline__ void mma_f16(float (&d)[4], const uint32_t (&a)[4], uint32_t b0, uint32_t b1) {
    asm volatile("mma.sync.aligned.m16n8k16.row.col.f32.f16.f16.f32 {%0,%1,%2,%3}, {%4,%5,%6,%7}, {%8,%9}, {%0,%1,%2,%3};"
        : "+f"(d[0]), "+f"(d[1]), "+f"(d[2]), "+f"(d[3]) : "r"(a[0]), "r"(a[1]), "r"(a[2]), "r"(a[3]), "r"(b0), "r"(b1));
}
__device__ __forceinline__ void mma_bf16(float (&d)[4], uint32_t a0, uint32_t a1, uint32_t a2, uint32_t a3, uint32_t b0, uint32_t b1) {
    asm volatile("mma.sync.aligned.m16n8k16.row.col.f32.bf16.bf16.f32 {%0,%1,%2,%3}, {%4,%5,%6,%7}, {%8,%9}, {%0,%1,%2,%3};"
        : "+f"(d[0]), "+f"(d[1]), "+f"(d[2]), "+f"(d[3]) : "r"(a0), "r"(a1), "r"(a2), "r"(a3), "r"(b0), "r"(b1));
}
__device__ __forceinline__ void mma_bf16_k8(float (&d)[4], uint32_t a0, uint32_t a1, uint32_t b0) {
    asm volatile("mma.sync.aligned.m16n8k8.row.col.f32.bf16.bf16.f32 {%0,%1,%2,%3}, {%4,%5}, {%6}, {%0,%1,%2,%3};"
        : "+f"(d[0]), "+f"(d[1]), "+f"(d[2]), "+f"(d[3]) : "r"(a0), "r"(a1), "r"(b0));
}
__device__ __forceinline__ uint32_t pack_f16(float lo, float hi) { uint32_t r; asm("cvt.rn.f16x2.f32 %0, %1, %2;" : "=r"(r) : "f"(hi), "f"(lo)); return r; }
__device__ __forceinline__ uint32_t pack_bf16(float lo, float hi) { uint32_t r; asm("cvt.rn.bf16x2.f32 %0, %1, %2;" : "=r"(r) : "f"(hi), "f"(lo)); return r; }
__device__ __forceinline__ float bf_lo(uint32_t v) { return __uint_as_float(v << 16); }
__device__ __forceinline__ float bf_hi(uint32_t v) { return __uint_as_float(v & 0xFFFF0000u); }
__device__ __forceinline__ float bfr(float x) { return __uint_as_float(pack_bf16(0.f, x)); }
__device__ __forceinline__ uint32_t bsub2(uint32_t a, uint32_t b) { uint32_t r; asm("sub.rn.bf16x2 %0, %1, %2;" : "=r"(r) : "r"(a), "r"(b)); return r; }
__device__ __forceinline__ uint32_t badd2(uint32_t a, uint32_t b) { uint32_t r; asm("add.rn.bf16x2 %0, %1, %2;" : "=r"(r) : "r"(a), "r"(b)); return r; }
__device__ __forceinline__ uint32_t bmul2(uint32_t a, uint32_t b) { uint32_t r; asm("mul.rn.bf16x2 %0, %1, %2;" : "=r"(r) : "r"(a), "r"(b)); return r; }
__device__ __forceinline__ uint32_t bfma2(uint32_t a, uint32_t b, uint32_t c) { uint32_t r; asm("fma.rn.bf16x2 %0, %1, %2, %3;" : "=r"(r) : "r"(a), "r"(b), "r"(c)); return r; }
__device__ __forceinline__ uint32_t hadd2(uint32_t a, uint32_t b) { uint32_t r; asm("add.rn.f16x2 %0, %1, %2;" : "=r"(r) : "r"(a), "r"(b)); return r; }
__device__ __forceinline__ uint32_t hmul2(uint32_t a, uint32_t b) { uint32_t r; asm("mul.rn.f16x2 %0, %1, %2;" : "=r"(r) : "r"(a), "r"(b)); return r; }
__device__ __forceinline__ uint32_t hfma2(uint32_t a, uint32_t b, uint32_t c) { uint32_t r; asm("fma.rn.f16x2 %0, %1, %2, %3;" : "=r"(r) : "r"(a), "r"(b), "r"(c)); return r; }
__device__ __forceinline__ uint32_t hneg2(uint32_t a) { uint32_t r; asm("neg.f16x2 %0, %1;" : "=r"(r) : "r"(a)); return r; }
__device__ __forceinline__ float rcpf(float x) { float r; asm("rcp.approx.ftz.f32 %0, %1;" : "=f"(r) : "f"(x)); return r; }
__device__ __forceinline__ float sqrta(float x) { float r; asm("sqrt.approx.ftz.f32 %0, %1;" : "=f"(r) : "f"(x)); return r; }
__device__ __forceinline__ float ex2f(float x) { float r; asm("ex2.approx.ftz.f32 %0, %1;" : "=f"(r) : "f"(x)); return r; }
__device__ __forceinline__ void st_async4(uint32_t a, uint32_t x, uint32_t y, uint32_t z, uint32_t w, uint32_t mb) {
    asm volatile("st.async.shared::cluster.mbarrier::complete_tx::bytes.v4.u32 [%0], {%1,%2,%3,%4}, [%5];" :: "r"(a), "r"(x), "r"(y), "r"(z), "r"(w), "r"(mb) : "memory"); }
__device__ __forceinline__ void st_async1(uint32_t a, uint32_t x, uint32_t mb) {
    asm volatile("st.async.shared::cluster.mbarrier::complete_tx::bytes.u32 [%0], %1, [%2];" :: "r"(a), "r"(x), "r"(mb) : "memory"); }
__device__ __forceinline__ unsigned ld_rlx(const void* p) { unsigned v; asm volatile("ld.relaxed.gpu.global.u32 %0, [%1];" : "=r"(v) : "l"(p) : "memory"); return v; }
__device__ __forceinline__ unsigned ld_acq(const void* p) { unsigned v; asm volatile("ld.acquire.gpu.global.u32 %0, [%1];" : "=r"(v) : "l"(p) : "memory"); return v; }
__device__ __forceinline__ uint2 ld_rlx64(const void* p) { unsigned long long v; asm volatile("ld.relaxed.gpu.global.u64 %0, [%1];" : "=l"(v) : "l"(p) : "memory"); return make_uint2((unsigned)v, (unsigned)(v >> 32)); }
__device__ __forceinline__ void st_rlx64(void* p, unsigned lo, unsigned hi) { asm volatile("st.relaxed.gpu.global.u64 [%0], %1;" :: "l"(p), "l"((unsigned long long)lo | ((unsigned long long)hi << 32)) : "memory"); }
__device__ __forceinline__ void st_rlx128(void* p, uint32_t x, uint32_t y, uint32_t z, uint32_t w) {
    asm volatile("st.relaxed.gpu.global.v2.u64 [%0], {%1,%2};" :: "l"(p), "l"((unsigned long long)x | ((unsigned long long)y << 32)), "l"((unsigned long long)z | ((unsigned long long)w << 32)) : "memory"); }
__device__ __forceinline__ uint4 ld_rlx128(const void* p) { uint4 v; asm volatile("ld.relaxed.gpu.global.v4.u32 {%0,%1,%2,%3}, [%4];" : "=r"(v.x), "=r"(v.y), "=r"(v.z), "=r"(v.w) : "l"(p) : "memory"); return v; }
__device__ __forceinline__ void tma2d(uint32_t dst, const CUtensorMap* tm, int x, int y, uint32_t mb) {
    asm volatile("cp.async.bulk.tensor.2d.shared::cluster.global.mbarrier::complete_tx::bytes [%0], [%1, {%3, %4}], [%2];"
                 :: "r"(dst), "l"(tm), "r"(mb), "r"(x), "r"(y) : "memory");
}
__device__ __forceinline__ void cmul(float& xr, float& xi, float ar, float ai, float br, float bi) {
    const float r = fmaf(ar, br, -ai * bi), i = fmaf(ar, bi, ai * br); xr = r; xi = i;
}
__device__ __forceinline__ void csq(float& xr, float& xi, float ar, float ai) {
    const float r = fmaf(ar, ar, -ai * ai), i = (ar + ar) * ai; xr = r; xi = i;
}
__device__ __forceinline__ void cexp_s(float& zr, float& zi, float e2, float turns) {
    const float mag = ex2f(e2), r = (turns - rintf(turns)) * 6.283185307179586f;
    zr = mag * __cosf(r); zi = mag * __sinf(r);
}
__device__ __forceinline__ uint32_t ln_stats(float s1, float s2) {
    const float m = s1 * (1.f / D_);
    const float var = fmaxf(fmaf(s2, 1.f / D_, -m * m), 0.f);
    return pack_bf16(m, sqrta(bfr(bfr(var) + 1e-5f)));
}
__device__ __forceinline__ uint32_t rsplit(float rs) { const float h = bfr(rs); return pack_bf16(h, rs - h); }
__device__ __forceinline__ uint32_t norm2(uint32_t v, uint32_t m2, uint32_t rh2, uint32_t rl2) {
    const uint32_t dd = bsub2(v, m2);
    return bfma2(dd, rh2, bmul2(dd, rl2));
}
__device__ __noinline__ int rank16(uint32_t a, uint32_t key) {
    int r = 0;
#pragma unroll
    for (int i = 0; i < 4; i++) { const uint4 o = lds128(a + i * 16); r += (o.x > key) + (o.y > key) + (o.z > key) + (o.w > key); }
    return r;
}
struct H2C { uint32_t r, i; };
__device__ __forceinline__ H2C splat(float r, float i) { H2C h; h.r = pack_f16(r, r); h.i = pack_f16(i, i); return h; }
__device__ __forceinline__ void expand8(uint32_t are, uint32_t aim, float sr, float si, float m1r, float m1i, float m2r, float m2i, H2C m4) {
    float r1, i1, r2, i2, r3, i3;
    cmul(r1, i1, sr, si, m1r, m1i); cmul(r2, i2, sr, si, m2r, m2i); cmul(r3, i3, r1, i1, m2r, m2i);
    const uint32_t R0 = pack_f16(sr, r1), R1 = pack_f16(r2, r3), I0 = pack_f16(si, i1), I1 = pack_f16(i2, i3);
    sts128(are, R0, R1, hfma2(R0, m4.r, hneg2(hmul2(I0, m4.i))), hfma2(R1, m4.r, hneg2(hmul2(I1, m4.i))));
    sts128(aim, I0, I1, hfma2(R0, m4.i, hmul2(I0, m4.r)), hfma2(R1, m4.i, hmul2(I1, m4.r)));
}
__device__ __forceinline__ void put16(uint32_t a, uint32_t v) { sts16(a, v); sts16(a + 6, v); }

struct Params {
    const unsigned short *x, *prm6[6], *logdt, *dskip, *wr;
    const char* w3[3];
    __nv_bfloat16* out;
    unsigned zero;
};
__device__ __forceinline__ int word_token(int wi) {
    const int G = wi >> 5, l = (wi >> 3) & 3;
    return G < 3 ? 16 * ((G ? 1 + 5 * G : 0) + (wi & 3)) + ((wi & 31) >> 2) : 16 * (l ? 5 * l : 4) + (wi & 7);
}

__global__ void __cluster_dims__(CS, 1, 1) __launch_bounds__(NTHR, 1)
fused_kernel(const __grid_constant__ Params prm, const __grid_constant__ CUtensorMap tmG, const __grid_constant__ CUtensorMap tmU,
             const __grid_constant__ CUtensorMap tmD, const __grid_constant__ CUtensorMap tmO)
{
    extern __shared__ __align__(1024) unsigned char smem[];
    const int tid = threadIdx.x, lane = tid & 31, warp = __shfl_sync(~0u, tid >> 5, 0);
    const int c = blockIdx.x >> 3, q = blockIdx.x & 7;
    const int nslot = (c < NCL - 1) ? 5 : 2;
    const int d0 = 40 * c;
    const uint32_t sb = opaque((uint32_t)__cvta_generic_to_shared(smem));
    const uint32_t mb = sb + SM_MB;
    STAMP(0);

    if (warp == 20) {
        const unsigned epoch = ld_rlx(&g_s.epoch) + 1;
        uint4 wv = make_uint4(0, 0, 0, 0), wv2 = __ldg((const uint4*)prm.wr + lane), wv3 = __ldg((const uint4*)prm.wr + 32 + lane);
        if (lane < 8) wv = __ldg((const uint4*)prm.wr + 64 + lane);
        if (lane == 0) {
#pragma unroll
            for (int i = 0; i < 11; i++) asm volatile("mbarrier.init.shared::cta.b64 [%0], %1;" :: "r"(mb + i * 8), "r"(i == MB_OUT ? 8 : 1) : "memory");
            asm volatile("fence.mbarrier_init.release.cluster;" ::: "memory");
        }
        __syncwarp();
        asm volatile("barrier.cluster.arrive.relaxed.aligned;" ::: "memory");
        if (lane < 10 && lane != MB_Y) {
            const int bytes = lane < 5 ? 4096 : lane == MB_W1 ? 92160 : lane == MB_W2 ? (nslot == 5 ? 46080 : 23040) : lane == MB_KEY ? 256 : nslot * 1024;
            asm volatile("mbarrier.arrive.expect_tx.shared::cta.b64 _, [%0], %1;" :: "r"(mb + lane * 8), "r"(bytes) : "memory");
        }
        if (lane < 18 && 18 * c + lane < 256) g_s.acc[256 * q + 18 * c + lane] = make_float4(0.f, 0.f, 0.f, 0.f);
#pragma unroll 1
        for (int i = lane; i < 288; i += 32) { const int t = i / 36; ((uint4*)&g_s.part[(t * NCL + c) * D_ + 72 * q])[i - t * 36] = make_uint4(0, 0, 0, 0); }
        {
            const uint32_t old = (epoch & 1) ? 0u : 0x40004000u;
#pragma unroll 1
            for (int i = lane; i < 48; i += 32) { const int t = i / 6; g_s.cand[((q * 8 + t) * NCL + c) * 6 + i - t * 6] = make_uint4(old, old, old, old); }
        }
        if (lane < 2 * nslot) asm volatile("cp.async.bulk.prefetch.L2.global [%0], %1;" :: "l"(prm.w3[lane & 1] + (d0 + q + 8 * (lane >> 1)) * 9216), "r"(9216) : "memory");
        {
            float a[4] = {0.f, 0.f, 0.f, 0.f};
            const uint32_t one = 0x3F803F80u;
            mma_bf16(a, one, one, one, one, wv.x, wv.y);  mma_bf16(a, one, one, one, one, wv.z, wv.w);
            mma_bf16(a, one, one, one, one, wv2.x, wv2.y); mma_bf16(a, one, one, one, one, wv2.z, wv2.w);
            mma_bf16(a, one, one, one, one, wv3.x, wv3.y); mma_bf16(a, one, one, one, one, wv3.z, wv3.w);
            float s = a[0] + a[1];
            s += __shfl_xor_sync(~0u, s, 1); s += __shfl_xor_sync(~0u, s, 2);
            stsf(sb + SM_SC + 24, s);
        }
        asm volatile("fence.acq_rel.gpu;" ::: "memory");
        __syncwarp();
        if (lane == 0) asm volatile("red.relaxed.gpu.global.add.u32 [%0], 1;" :: "l"(&g_s.zcnt) : "memory");
        asm volatile("barrier.cluster.wait.aligned;" ::: "memory");
        STAMP(1);
        bar_sync(13, NTHR);
        if (lane < 6) tma2d(sb + SM_WG + lane * 15360, lane < 3 ? &tmG : &tmU, 320 * c + 8 * nslot * q, 192 * (lane % 3), mb + MB_W1 * 8);
        if (lane < nslot) asm volatile("cp.async.bulk.prefetch.L2.global [%0], %1;" :: "l"(prm.w3[2] + (d0 + q + 8 * lane) * 9216), "r"(9216) : "memory");
        if (lane == 0) {
            int n = 0;
            while ((int)(ld_acq(&g_s.zcnt) - epoch * NCTA) < 0 && ++n < SPIN_LIMIT) {}
            asm volatile("mbarrier.arrive.expect_tx.shared::cta.b64 _, [%0], %1;" :: "r"(mb + MB_Y * 8), "r"(4096 * nslot) : "memory");
            STAMP(2);
            mbar_wait(mb + MB_Y * 8);
            asm volatile("fence.proxy.async.shared::cta;" ::: "memory");
            tma2d(sb + SM_W2, &tmD, 72 * q, 320 * c, mb + MB_W2 * 8);
            if (nslot == 5) tma2d(sb + SM_W2 + 23040, &tmD, 72 * q, 320 * c + 160, mb + MB_W2 * 8);
        }
        __syncwarp();
        bar_sync(13, NTHR);
        if (lane == 0) {
            asm volatile("cp.async.bulk.tensor.2d.global.shared::cta.bulk_group [%0, {%2, %3}], [%1];" :: "l"(&tmO), "r"(sb + SM_XT), "r"(d0), "r"(256 * q) : "memory");
            asm volatile("cp.async.bulk.commit_group;" ::: "memory");
            if (blockIdx.x == 0) g_s.epoch = epoch;
            asm volatile("cp.async.bulk.wait_group 0;" ::: "memory");
            asm volatile("fence.proxy.async.global;" ::: "memory");
        }
        __syncwarp();
        if (lane < 8) asm volatile("mbarrier.arrive.release.cluster.shared::cluster.b64 _, [%0];" :: "r"(mapa(mb + MB_OUT * 8, lane)) : "memory");
        STAMP(3);
        return;
    }

    const int g = lane >> 2, cq = lane & 3;
    const int k = warp >> 2, wq = warp & 3;
    const unsigned short* xs = prm.x;
    const int lrow = 18 * c + warp;
    const bool rowact = warp < 18 && lrow < 256;
    const int trow = 256 * q + (rowact ? lrow : 0);
    uint32_t rx[9];
#pragma unroll
    for (int i = 0; i < 9; i++) rx[i] = __ldg((const uint32_t*)(xs + trow * D_) + lane + 32 * i);
    const int dch = min(d0 + 8 * k + q, D_ - 1);
    uint32_t pv[6];
#pragma unroll
    for (int i = 0; i < 6; i++) pv[i] = __ldg(prm.prm6[i] + dch * 128 + wq * 32 + lane);
    const uint32_t pLdt = __ldg(prm.logdt + dch);
    const unsigned epoch = ld_rlx(&g_s.epoch) + 1;
    {
        const unsigned t = (unsigned)tid / 5u, kk = tid - t * 5;
        if (kk < nslot) {
            const uint32_t dst = sb + SM_XT + t * 80 + (t >> 3) * 32 + kk * 16;
            const unsigned short* src = xs + (256 * q * D_ + d0) + (t * D_ + 8 * kk);
            asm volatile("cp.async.cg.shared.global [%0], [%1], 16;" :: "r"(dst), "l"(src) : "memory");
            asm volatile("cp.async.cg.shared.global [%0], [%1], 16;" :: "r"(dst + 16 * 672), "l"(src + 128 * D_) : "memory");
        }
    }
    asm volatile("barrier.cluster.arrive.relaxed.aligned;" ::: "memory");
    uint4* const st1p = &g_s.st1[trow * 2 + (lane >> 2)];
    const bool pub = rowact && (lane & 0x1B) == 0;
    if (pub) *st1p = make_uint4(0, 0, 0, 0);
    const uint32_t chb = sb + SM_CH + k * CH_SZ;
    {
        const uint32_t za = chb + (tid & 127) * 16;
        sts128(za, 0, 0, 0, 0); sts128(za + 2048, 0, 0, 0, 0);
        if ((tid & 127) < CH_U0 / 16 - 256) sts128(za + 4096, 0, 0, 0, 0);
    }
    STAMP(1);

    const uint32_t fb = sb + SM_FAR + k * FAR_SZ;
    const uint32_t kb = fb + wq * 3072;
    const uint32_t kl = kb + lane * 16;
    uint32_t Af[4][4];
    float sr, si, z1r, z1i, z2r, z2i, z4r, z4i, hr, hi_;
    {
        const float dt = bfr(ex2f(bf_lo(pLdt) * 1.4426950408889634f));
        const float e2 = dt * bf_lo(pv[0]) * 1.4426950408889634f, tn = dt * bf_lo(pv[1]) * 0.15915494309189535f;
        cmul(sr, si, bf_lo(pv[4]), bf_lo(pv[5]), dt * bf_lo(pv[2]), dt * bf_lo(pv[3]));
        const unsigned mx = __reduce_max_sync(~0u, __float_as_uint(fmaxf(fabsf(sr), fabsf(si))));
        float s0 = sr;
#pragma unroll
        for (int o = 16; o; o >>= 1) s0 += __shfl_xor_sync(~0u, s0, o);
        sts64(sb + SM_KG + warp * 8, mx, __float_as_uint(s0));
        float ar, ai, br, bi, cr, ci, dr, di;
        cexp_s(ar, ai, e2 * 8.f, tn * 8.f);
        csq(br, bi, ar, ai); csq(cr, ci, br, bi); csq(dr, di, cr, ci);
        const H2C m4 = splat(cr, ci);
        expand8(kl, kl + 1024, 1.f, 0.f, ar, ai, br, bi, m4);
        expand8(kl + 512, kl + 1536, dr, di, ar, ai, br, bi, m4);
        cexp_s(z1r, z1i, e2, -tn);
        cexp_s(hr, hi_, e2 * 128.f, -tn * 128.f);
        csq(z2r, z2i, z1r, z1i); csq(z4r, z4i, z2r, z2i);
        bar_sync(1 + k, 128);
#pragma unroll
        for (int ks = 0; ks < 4; ks++) ldsm4t(Af[ks], kb + (lane >> 3) * 512 + (lane & 7) * 16 + ks * 128);
    }
    STAMP(2);
    {
        float a[4] = {0.f, 0.f, 0.f, 0.f}, b[4] = {0.f, 0.f, 0.f, 0.f};
#pragma unroll
        for (int i = 0; i < 9; i++) { if (i & 1) mma_bf16_k8(b, rx[i], 0x3F803F80u, rx[i]); else mma_bf16_k8(a, rx[i], 0x3F803F80u, rx[i]); }
        float s2 = (g & 1) ? a[1] + b[1] : a[0] + b[0], s1 = (a[2] + b[2]) + (a[3] + b[3]);
        s2 += __shfl_xor_sync(~0u, s2, 4); s1 += __shfl_xor_sync(~0u, s1, 1);
        s2 += __shfl_xor_sync(~0u, s2, 9); s1 += __shfl_xor_sync(~0u, s1, 2);
        s2 += __shfl_xor_sync(~0u, s2, 18);
        const uint32_t ms = ln_stats(s1, s2);
        if (pub) st_rlx128(st1p, ms, epoch, ms, epoch);
    }
    STAMP(3);
    {
        const uint4 m01 = lds128(sb + SM_KG + k * 32), m23 = lds128(sb + SM_KG + k * 32 + 16);
        const unsigned E = min(max(max(max(m01.x, m01.z), max(m23.x, m23.z)) >> 23, 1u), 253u);
        const float sc = __uint_as_float((254u - E) << 23);
        if ((tid & 127) == 0) {
            sts32(sb + SM_SC + k * 4, E * 0x00800080u);
            put16(chb + P_NEAR, pack_f16(((__uint_as_float(m01.y) + __uint_as_float(m01.w)) + (__uint_as_float(m23.y) + __uint_as_float(m23.w))) * sc, 0.f));
        }
        const uint32_t la = kb + ((lane >> 3) & 1) * 512 + (lane >> 4) * 128 + (lane & 7) * 16;
        auto tile = [&](int off, float m1r, float m1i, float m2r, float m2i, H2C m4) {
            expand8(kl, kl + 512, sr, si, m1r, m1i, m2r, m2i, m4);
            __syncwarp();
            uint32_t b0[4], b1[4];
            ldsm4t(b0, la); ldsm4t(b1, la + 256);
            float a0[4] = {0.f, 0.f, 0.f, 0.f};
            mma_f16(a0, Af[0], b0[0], b0[1]); mma_f16(a0, Af[1], b0[2], b0[3]);
            mma_f16(a0, Af[2], b1[0], b1[1]); mma_f16(a0, Af[3], b1[2], b1[3]);
            sts128f(kl + off, a0[0], a0[1], a0[2], a0[3]);
        };
        cmul(sr, si, sr * sc, -si * sc, z1r, z1i);
        const H2C h4 = splat(z4r, z4i);
        tile(1024, z1r, z1i, z2r, z2i, h4);
        cmul(sr, si, sr, si, hr, hi_);
        tile(1536, z1r, z1i, z2r, z2i, h4);
        cmul(z1r, z1i, z1r, z1i, hr, hi_);
        cmul(sr, si, sr, si, z1r, z1i);

        if (tid < 256) {
            uint2 s; int n = 0;
            do { s = ld_rlx64(&g_s.st1[(256 * q + tid) * 2]); } while (s.y != epoch && ++n < SPIN_LIMIT);
            const uint32_t rr = rsplit(rcpf(bf_hi(s.x)));
            sts16(sb + SM_M1 + tid * 2, s.x); sts16(sb + SM_RH1 + tid * 2, rr); sts16(sb + SM_RL1 + tid * 2, rr >> 16);
        }
        asm volatile("cp.async.wait_all;" ::: "memory");
        asm volatile("barrier.cluster.wait.aligned;" ::: "memory");
        bar_sync(11, 640);
        STAMP(4);
        {
            const uint32_t xa = sb + SM_XT + ((lane & 7) >> 1) * 672 + (2 * (lane >> 3) + (lane & 1)) * 80;
            const uint32_t rb_ = mapa(sb, g);
#pragma unroll 1
            for (int unit = warp; unit < 8 * nslot; unit += 20) {
                const int tg = unit & 7, kk = unit >> 3;
                uint32_t xv[4];
                ldsm4t(xv, xa + tg * 2688 + kk * 16);
                const uint32_t sa = sb + cq * 16 + tg * 64;
                const uint4 m2 = lds128(sa + SM_M1), rh = lds128(sa + SM_RH1), rl = lds128(sa + SM_RL1);
                xv[0] = norm2(xv[0], m2.x, rh.x, rl.x); xv[1] = norm2(xv[1], m2.y, rh.y, rl.y);
                xv[2] = norm2(xv[2], m2.z, rh.z, rl.z); xv[3] = norm2(xv[3], m2.w, rh.w, rl.w);
#pragma unroll
                for (int i = 0; i < 4; i++) xv[i] = pack_f16(bf_lo(xv[i]), bf_hi(xv[i]));
                st_async4(rb_ + cq * 16 + (SM_CH + CH_U0 + kk * CH_SZ + q * U_PITCH + tg * 64), xv[0], xv[1], xv[2], xv[3], rb_ + (SM_MB + kk * 8));
            }
        }
        bar_arrive(13, NTHR);
        STAMP(5);
        tile(2048, z2r, z2i, z4r, z4i, splat(hr, hi_));
        csq(z1r, z1i, z1r, z1i);
        cmul(sr, si, sr, si, z1r, z1i);
        csq(z2r, z2i, hr, hi_);
        tile(2560, z4r, z4i, hr, hi_, splat(z2r, z2i));
        csq(z1r, z1i, z1r, z1i);
        cmul(sr, si, sr, si, z1r, z1i);
        csq(z4r, z4i, z2r, z2i);
        tile(0, hr, hi_, z2r, z2i, splat(z4r, z4i));
        bar_sync(1 + k, 128);
        const uint32_t ra = fb + lane * 16 + wq * 512 + 1024, rc = fb + lane * 16 + wq * 4;
        const float4 p0 = lds128f(ra), p1 = lds128f(ra + 3072), p2 = lds128f(ra + 6144), p3 = lds128f(ra + 9216);
        const float v4 = ((ldsf(rc) + ldsf(rc + 3072)) + (ldsf(rc + 6144) + ldsf(rc + 9216))) * (1.f / 512.f);
        const float fs = wq == 3 ? 1.f / 512.f : 1.f;
        const float v0 = ((p0.x + p1.x) + (p2.x + p3.x)) * fs, v1 = ((p0.y + p1.y) + (p2.y + p3.y)) * fs;
        float v2 = ((p0.z + p1.z) + (p2.z + p3.z)) * fs, v3 = ((p0.w + p1.w) + (p2.w + p3.w)) * fs;
        put16(chb + (P_H7 + 32 * (wq & 1) + 16 * (wq >> 1)) + (g & 1) * (2 * P_HS) + cq * 64 + (g >> 1) * 4, pack_f16(v4, 0.f));
        const bool last = lane == 31;
        if (wq < 2) {
            const uint32_t pa = chb + (P_NEAR + 4 + 512 * wq) + lane * 8;
            const uint32_t w0 = pack_f16(v1, v0), w1 = pack_f16(v3, v2);
            sts16(pa, w0 >> 16); sts32(pa + 4, w0); sts16(pa + 10, w0);
            sts16(pa + 256, w1 >> 16); sts32(pa + 260, w1); sts16(pa + 266, w1);
            if (last && wq) put16(pa + 264, w1);
        } else if (wq == 2) {
            const uint32_t pa = chb + (P_NEAR + 258 * 4) + (cq & 1) * 16 + (cq >> 1) * 512 + g * 32;
            if (last) { put16(chb + P_G0, pack_f16(v3 * (1.f / 512.f), 0.f)); v2 -= v3; v3 = 0.f; }
            const uint32_t w0 = pack_f16(v1, v0), w1 = pack_f16(v3, v2), b0 = __byte_perm(w0, w0, 0x1010), b1 = __byte_perm(w1, w1, 0x1010);
            sts16(pa, w0 >> 16); sts32(pa + 4, w0); sts64(pa + 8, b0, b0); sts16(pa + 18, w0);
            sts16(pa + 256, w1 >> 16); sts32(pa + 260, w1); sts64(pa + 264, b1, b1); sts16(pa + 274, w1);
        } else {
            const uint32_t pa = chb + P_G0 + ((g & 1) ? 3 * P_GS : P_GS) + cq * 32 + (g >> 1) * 4;
            const uint32_t pb = pa + ((g & 1) ? 4 - 3 * P_GS : P_GS);
            const uint32_t w0 = pack_f16(v0, v1), w1 = pack_f16(v2, v3);
            put16(pa, w0); put16(pb, w0 >> 16); put16(pa + 16, w1); put16(pb + 16, w1 >> 16);
            if (last) put16(chb + P_H7 + P_HS, w1 >> 16);
        }
        bar_sync(1 + k, 128);
    }
    STAMP(6);

    const int ta = word_token((warp * 8 + g) & 127);
#define CP(x) ((x) | prm.zero)
    if (k < nslot) {
        const int role = (wq + k) & 3;
        const uint32_t ub = chb + CH_U0;
        const uint32_t po = chb + (g - 2 * cq) * 4;
        mbar_wait(mb + k * 8);
        STAMP(7);
        if (role) {
            const int r = (3 - role) * 32 + lane;
            const uint32_t a1 = ub + r * 32 + (r & ~15), a0 = a1 - ((r & 15) ? 32 : 48);
            const uint4 q0 = lds128(a0), q1 = lds128(a0 + 16), q2 = lds128(a1), q3 = lds128(a1 + 16);
            const uint32_t U[16] = {q0.x, q0.y, q0.z, q0.w, q1.x, q1.y, q1.z, q1.w, q2.x, q2.y, q2.z, q2.w, q3.x, q3.y, q3.z, q3.w};
            uint32_t V[14], Q[14], R4[12], T[8];
#pragma unroll
            for (int i = 2; i < 14; i++) { V[i] = __byte_perm(U[i], U[i + 1], 0x5432); Q[i] = hadd2(U[i], V[i]); }
#pragma unroll
            for (int i = 2; i < 12; i++) R4[i] = hadd2(Q[i], Q[i + 1]);
            const uint32_t rb = fb + r * 16;
#pragma unroll
            for (int i = 0; i < 8; i++) T[i] = hadd2(V[5 + i], Q[6 + i]);
            sts128(rb + F_E3, T[0], T[1], T[2], T[3]); sts128(rb + F_O3 + 16, T[4], T[5], T[6], T[7]);
#pragma unroll
            for (int i = 0; i < 8; i++) T[i] = hadd2(R4[3 + i], U[5 + i]);
            sts128(rb + F_O5, T[0], T[1], T[2], T[3]); sts128(rb + F_E5, T[4], T[5], T[6], T[7]);
            if (role != 1) {
#pragma unroll
                for (int i = 0; i < 8; i++) T[i] = hadd2(T[i], hadd2(V[2 + i], V[5 + i]));
                sts128(rb + F_E7, T[0], T[1], T[2], T[3]); sts128(rb + F_O7, T[4], T[5], T[6], T[7]);
#pragma unroll
                for (int i = 0; i < 8; i++) T[i] = hadd2(R4[2 + i], hadd2(R4[4 + i], U[6 + i]));
                sts128(rb + F_O9, T[0], T[1], T[2], T[3]); sts128(rb + F_E9 + 16, T[4], T[5], T[6], T[7]);
                sts128(rb + F_E2, Q[6], Q[7], Q[8], Q[9]); sts128(rb + F_O2, Q[10], Q[11], Q[12], Q[13]);
            }
        } else if (lane < 8) {
            uint32_t s = 0;
#pragma unroll 1
            for (int t = 1526 + lane; t < 1531 + lane; t++) s = hadd2(s, lds16(ub + t * 2 + (t >> 8) * 16));
            sts16(fb + F_O5 + 96 * 16 + lane * 2, s);
            sts32(fb + (lane < 4 ? F_O3 : F_E9 - 16) + lane * 4, 0);
        }
        if (role == 3) {
            bar_sync(1 + k, 128);
            uint32_t Q[4][4];
            Q[0][2] = prm.zero;
#pragma unroll 1
            for (int h = 0; h < 2; h++) {
                float acc[7][4];
#pragma unroll
                for (int a = 0; a < 7; a++) acc[a][0] = acc[a][1] = acc[a][2] = acc[a][3] = 0.f;
                uint32_t B[3][4];
#pragma unroll 1
                for (int s = 0; s < 4; s++) {
#pragma unroll
                    for (int i = 0; i < 3; i++) { Q[i][0] = lds32(po + s * P_GS + (P_G0 + i * 64)); Q[i][1] = lds32(po + s * P_GS + (P_G0 + i * 64 + 32)); }
                    const uint32_t ba = fb + lane * 16 + ((s & 1) * F_E3 + ((s >> 1) == h ? 0 : F_O5 + h * 16));
#pragma unroll
                    for (int i = 0; i < 3; i++) ldsm4t(B[i], ba + i * 512);
#pragma unroll
                    for (int i = 0; i < 3; i++) { Q[i][3] = CP(Q[i][0]); if (i) Q[i][2] = CP(Q[i - 1][1]); }
#pragma unroll
                    for (int dl = 0; dl < 3; dl++)
#pragma unroll
                        for (int ap = 0; ap < 6 - dl; ap++) mma_f16(acc[ap + 1 + dl], Q[dl], B[ap >> 1][2 * (ap & 1)], B[ap >> 1][2 * (ap & 1) + 1]);
                    if (s < h) {
                        ldsm2t(B[0][0], B[0][1], fb + ((lane & 15) == 15 ? F_O5 : F_O3));
#pragma unroll
                        for (int dl = 0; dl < 3; dl++) mma_f16(acc[dl], Q[dl], B[0][0], B[0][1]);
                    }
                }
#pragma unroll 1
                for (int s = 0; s < 3; s++) {
#pragma unroll
                    for (int i = 0; i < 4; i++) { Q[i][0] = lds32(po + s * P_HS + (P_H7 + i * 64)); Q[i][1] = lds32(po + s * P_HS + (P_H7 + i * 64 + 32)); }
                    const uint32_t ba = fb + lane * 16 + (F_E7 + s * 1024 + h * F_H);
                    ldsm4t(B[0], ba); ldsm4t(B[1], ba + 512);
#pragma unroll
                    for (int i = 0; i < 4; i++) { Q[i][3] = CP(Q[i][0]); if (i) Q[i][2] = CP(Q[i - 1][1]); }
#pragma unroll
                    for (int dl = 0; dl < 4; dl++) {
#pragma unroll
                        for (int ap = 0; ap < 4 - dl; ap++) mma_f16(acc[ap + 3 + dl], Q[dl], B[ap >> 1][2 * (ap & 1)], B[ap >> 1][2 * (ap & 1) + 1]);
                        if (s == 1) break;
                    }
                }
                const uint32_t da = fb + lane * 32 + (F_E7 + h * F_H);
#pragma unroll
                for (int e = 0; e < 4; e++)
                    sts128(da + (((e ^ g) & 1) << 4) + (e >> 1) * 1024, pack_f16(0.f, acc[0][e]), pack_f16(acc[1][e], acc[2][e]),
                           pack_f16(acc[3][e], acc[4][e]), pack_f16(acc[5][e], acc[6][e]));
            }
            bar_arrive(6 + k, 128);
            STAMP(8);
        } else {
            bar_arrive(1 + k, 128);
            float acc[6][4];
#pragma unroll
            for (int t = 0; t < 6; t++) acc[t][0] = acc[t][1] = acc[t][2] = acc[t][3] = 0.f;
            const int j0 = role ? 1 + 5 * role : 0;
            const uint32_t lbase = ub + (lane & 7) * U_PITCH + ((lane >> 3) & 1) * 16;
            int m = j0 + 5 - (lane >> 4);
            uint32_t W[4][4], qa[4], qb[4];
#pragma unroll
            for (int i = 0; i < 3; i++) { ldsm4(W[i], lbase + m * 32 + (m & ~15)); m -= 2; }
            uint32_t pp = po + P_NEAR;
            qa[0] = lds32(pp); qa[1] = lds32(pp + 32); qa[2] = 0;
#define FR(i) W[(u + ((i) >> 1)) & 3][2 * ((i) & 1)], W[(u + ((i) >> 1)) & 3][2 * ((i) & 1) + 1]
#pragma unroll 1
            for (int it = 0;; it++) {
#pragma unroll
                for (int u = 0; u < 4; u++) {
                    ldsm4(W[(u + 3) & 3], lbase + m * 32 + (m & ~15)); m -= 2;
                    qb[0] = lds32(pp + u * 128 + 64); qb[1] = lds32(pp + u * 128 + 96);
                    qa[3] = CP(qa[0]); qb[2] = CP(qa[1]);
                    if (role == 0) mma_f16(acc[5], qa, FR(0));
                    mma_f16(acc[4], qa, FR(1)); mma_f16(acc[3], qa, FR(2)); mma_f16(acc[2], qa, FR(3)); mma_f16(acc[1], qa, FR(4)); mma_f16(acc[0], qa, FR(5));
                    if (u == 0 && it == 4) goto near_done;
                    qa[0] = lds32(pp + u * 128 + 128); qa[1] = lds32(pp + u * 128 + 160);
                    qb[3] = CP(qb[0]); qa[2] = CP(qb[1]);
                    if (role == 0) mma_f16(acc[5], qb, FR(1));
                    mma_f16(acc[4], qb, FR(2)); mma_f16(acc[3], qb, FR(3)); mma_f16(acc[2], qb, FR(4)); mma_f16(acc[1], qb, FR(5)); mma_f16(acc[0], qb, FR(6));
                }
                pp += 512;
            }
#undef FR
near_done:
            STAMP(8);
            if (lane < nslot) mbar_wait(mb + lane * 8);
            const uint32_t inv = lds32(sb + SM_SC + k * 4);
            qa[0] = (g == 2 * cq) ? 0x6000u : ((g == 2 * cq + 1) ? 0x60000000u : 0u);
            qa[1] = 0; qa[2] = prm.zero; qa[3] = CP(qa[0]);
            const int jl = j0 + (lane >> 4);
            const uint32_t fa = fb + F_E7 + jl * 128 + ((lane >> 3) & 1) * F_H + (((lane & 7) ^ (jl & 1)) << 4);
            bar_sync(6 + k, 128);
            uint32_t w0[6], w1[6];
#pragma unroll
            for (int t = 0; t < 3; t++) ldsm4t(W[t], fa + t * 256);
#pragma unroll
            for (int t = 0; t < 6; t++) {
                mma_f16(acc[t], qa, W[t >> 1][2 * (t & 1)], W[t >> 1][2 * (t & 1) + 1]);
                w0[t] = bmul2(pack_bf16(acc[t][0], acc[t][2]), inv); w1[t] = bmul2(pack_bf16(acc[t][1], acc[t][3]), inv);
            }
            const uint32_t r0 = mapa(sb, 2 * cq), r1 = mapa(sb, 2 * cq + 1);
            const uint32_t yo = SM_XT + k * Y_SLOT + q * 512 + (k == 4 ? (q >> 1) * 32 : 0);
            const uint32_t y4 = yo + role * 128 + g * 16, y1 = yo + 384 + (role ? role + 1 : 0) * 32 + g * 4;
            st_async4(r0 + y4, w0[0], w0[1], w0[2], w0[3], r0 + (SM_MB + MB_Y * 8));
            st_async4(r1 + y4, w1[0], w1[1], w1[2], w1[3], r1 + (SM_MB + MB_Y * 8));
            st_async1(r0 + y1, w0[4], r0 + (SM_MB + MB_Y * 8)); st_async1(r1 + y1, w1[4], r1 + (SM_MB + MB_Y * 8));
            if (role == 0) { st_async1(r0 + y1 + 32, w0[5], r0 + (SM_MB + MB_Y * 8)); st_async1(r1 + y1 + 32, w1[5], r1 + (SM_MB + MB_Y * 8)); }
        }
    }
    STAMP(9);
    uint32_t ha[5], hb[5];
    if (warp < 16) {
        const uint32_t o4 = d0 * 2 + (cq < nslot ? cq * 16 : 0), o1 = d0 * 2 + (nslot == 5 ? 64 + cq * 4 : 0);
        const char* xr = (const char*)xs + (uint32_t)((256 * q + ta) * (D_ * 2));
        const uint4 xa4 = __ldg((const uint4*)(xr + o4)), xb4 = __ldg((const uint4*)(xr + o4 + 16 * D_));
        const uint32_t xa1 = __ldg((const uint32_t*)(xr + o1)), xb1 = __ldg((const uint32_t*)(xr + o1 + 16 * D_));
        const uint4 dk = __ldg((const uint4*)((const char*)prm.dskip + o4)), wk = __ldg((const uint4*)((const char*)prm.wr + o4));
        const uint32_t d1 = __ldg((const uint32_t*)((const char*)prm.dskip + o1)), w1 = __ldg((const uint32_t*)((const char*)prm.wr + o1));
        const uint32_t sa = sb + ta * 2;
        const uint32_t ma = lds16(sa + SM_M1) * 0x10001u, mbb = lds16(sa + SM_M1 + 16) * 0x10001u;
        const uint32_t rha = lds16(sa + SM_RH1) * 0x10001u, rhb = lds16(sa + SM_RH1 + 16) * 0x10001u;
        const uint32_t rla = lds16(sa + SM_RL1) * 0x10001u, rlb = lds16(sa + SM_RL1 + 16) * 0x10001u;
        const uint32_t xav[5] = {xa4.x, xa4.y, xa4.z, xa4.w, xa1}, xbv[5] = {xb4.x, xb4.y, xb4.z, xb4.w, xb1};
        const uint32_t dkv[5] = {dk.x, dk.y, dk.z, dk.w, d1};
        uint32_t sel[5] = {wk.x, wk.y, wk.z, wk.w, w1};
#pragma unroll
        for (int i = 0; i < 5; i++) {
            ha[i] = bmul2(norm2(xav[i], ma, rha, rla), dkv[i]); hb[i] = bmul2(norm2(xbv[i], mbb, rhb, rlb), dkv[i]);
            if (!(g & 1)) sel[i] = 0x3F803F80u;
        }
        const uint32_t ya = sb + SM_XT + warp * 32 + g * 4;
        mbar_wait(mb + MB_Y * 8);
        STAMP(10);
        float ca[4] = {0.f, 0.f, 0.f, 0.f}, cb[4] = {0.f, 0.f, 0.f, 0.f};
#pragma unroll
        for (int i = 0; i < 5; i++) {
            const uint32_t yp = ya + (i < 4 ? cq * Y_SLOT + i * 1024 : 4 * Y_SLOT + cq * 1056);
            const uint32_t y0 = lds32(yp), y1 = lds32(yp + 512);
            ha[i] = badd2(xav[i], badd2(__byte_perm(y0, y1, 0x5410), ha[i]));
            hb[i] = badd2(xbv[i], badd2(__byte_perm(y0, y1, 0x7632), hb[i]));
        }
        if (nslot != 5) {
            ha[4] = hb[4] = 0;
            if (cq >= 2) ha[0] = ha[1] = ha[2] = ha[3] = hb[0] = hb[1] = hb[2] = hb[3] = 0;
        }
#pragma unroll
        for (int i = 0; i < 5; i++) { mma_bf16_k8(ca, ha[i], sel[i], ha[i]); mma_bf16_k8(cb, hb[i], sel[i], hb[i]); }
        const float oa = __shfl_xor_sync(~0u, (g & 1) ? ca[2] : ca[3], 4), ob = __shfl_xor_sync(~0u, (g & 1) ? cb[2] : cb[3], 4);
        if (cq == (g >> 1)) {
            float4* ap = &g_s.acc[256 * q + warp * 8 + g];
            const bool od = g & 1;
            asm volatile("red.relaxed.gpu.global.add.v4.f32 [%0], {%1,%2,%3,%4};" :: "l"(ap), "f"(od ? oa : ca[2]), "f"(od ? ca[1] : ca[0]), "f"(od ? ca[3] : oa), "f"(1.0f) : "memory");
            asm volatile("red.relaxed.gpu.global.add.v4.f32 [%0], {%1,%2,%3,%4};" :: "l"(ap + 128), "f"(od ? ob : cb[2]), "f"(od ? cb[1] : cb[0]), "f"(od ? cb[3] : ob), "f"(1.0f) : "memory");
        }
        const uint32_t hta = sb + SM_HT + ta * 80;
        sts128(hta + cq * 16, ha[0], ha[1], ha[2], ha[3]); sts32(hta + 64 + cq * 4, ha[4]);
        sts128(hta + cq * 16 + 640, hb[0], hb[1], hb[2], hb[3]); sts32(hta + 704 + cq * 4, hb[4]);
        STAMP(11);
    }
    const uint32_t par = (epoch & 1) ? 0x40004000u : 0u;
    if (warp < 8) {
        const int tok = word_token(tid & 127) + (tid >> 7) * 8;
        const float wsum = ldsf(sb + SM_SC + 24);
        uint4 s; int n = 0;
        do { s = ld_rlx128(&g_s.acc[256 * q + tid]); } while (__uint_as_float(s.w) != (float)NCL && ++n < SPIN_LIMIT);
        const uint32_t ms = ln_stats(__uint_as_float(s.x), __uint_as_float(s.y));
        const float rs = rcpf(bf_hi(ms));
        const uint32_t rb = pack_bf16(0.f, (__uint_as_float(s.z) - bf_lo(ms) * wsum) * rs);
        const uint32_t key = (rb ^ (((int)rb >> 31) | 0x80000000u) & 0xFFFF0000u) | (uint32_t)(2047 - 256 * q - tok);
        sts32(sb + SM_KEY + tid * 4, key);
        sts64(sb + SM_ST2 + tok * 8, __byte_perm(ms, ms, 0x1010), rsplit(rs));
        __syncwarp();
        int rank = rank16(sb + SM_KEY + warp * 128, key) + rank16(sb + SM_KEY + warp * 128 + 64, key);
        if (rank < 8) sts32(sb + SM_CAND + (warp * 8 + rank) * 4, key);
        bar_sync(12, 512);
        uint32_t mk = lds32(sb + SM_CAND + (tid >> 2) * 4);
        rank = rank16(sb + SM_CAND + cq * 64, mk);
        rank += __shfl_xor_sync(~0u, rank, 1); rank += __shfl_xor_sync(~0u, rank, 2);
        if (rank < 8) {
#pragma unroll
            for (int i = 0; i < 2; i++) {
                const uint32_t rb_ = mapa(sb, 2 * cq + i);
                st_async1(rb_ + SM_RK + (q * 8 + rank) * 4, mk, rb_ + (SM_MB + MB_KEY * 8));
            }
            const int t = ~mk & 255;
            const uint2 st = lds64(sb + SM_ST2 + t * 8);
            const uint32_t rr = bmul2(st.y, 0x3C803C80u), rh = __byte_perm(rr, rr, 0x1010), rl = __byte_perm(rr, rr, 0x3232);
            uint4* cp = &g_s.cand[((q * 8 + rank) * NCL + c) * 6];
#pragma unroll 1
            for (int i = cq; i < 6; i += 4) {
                const uint4 hv = lds128(sb + SM_HT + t * 80 + i * 16);
                st_rlx128(cp + i, (norm2(hv.x, st.x, rh, rl) & 0xBFFFBFFFu) | par, (norm2(hv.y, st.x, rh, rl) & 0xBFFFBFFFu) | par,
                          (norm2(hv.z, st.x, rh, rl) & 0xBFFFBFFFu) | par, (norm2(hv.w, st.x, rh, rl) & 0xBFFFBFFFu) | par);
            }
        }
        mbar_wait(mb + MB_KEY * 8);
        mk = lds32(sb + SM_RK + (tid >> 2) * 4);
        rank = rank16(sb + SM_RK + cq * 64, mk);
        rank += __shfl_xor_sync(~0u, rank, 1); rank += __shfl_xor_sync(~0u, rank, 2);
        if (rank < 8) sts64(sb + SM_SEL + rank * 8, mk, tid >> 2);
    } else if (warp < 16) bar_arrive(12, 512);
    const int kq = warp / 5, mt = warp - 5 * kq;
    const int mi = lane >> 3, mr = lane & 7;
    const unsigned tk = (unsigned)tid / 72u, ck = tid - tk * 72;
    uint32_t A[9][4];
    mbar_wait(mb + MB_W1 * 8);
    {
        const uint32_t aa = sb + (mi & 1) * SM_WU + (8 * (mi >> 1) + mr) * 80 + (144 * 80 * kq + mt * 16);
#pragma unroll
        for (int s = 0; s < 9; s++) ldsm4t(A[s], aa + s * 1280);
    }
    bar_sync(11, 640);
    STAMP(12);

    {
        const uint4* gp = &g_s.cand[lds32(sb + SM_SEL + 4 + (tk & 7) * 8) * 90 + ck / 5u + ck];
        uint4 hv;
        if (warp < 18) hv = ld_rlx128(gp);
        if (warp < 16) {
            const uint2 sa = lds64(sb + SM_ST2 + ta * 8), sbb = lds64(sb + SM_ST2 + ta * 8 + 64);
            const uint32_t rha = __byte_perm(sa.y, sa.y, 0x1010), rla = __byte_perm(sa.y, sa.y, 0x3232);
            const uint32_t rhb = __byte_perm(sbb.y, sbb.y, 0x1010), rlb = __byte_perm(sbb.y, sbb.y, 0x3232);
#pragma unroll
            for (int i = 0; i < 5; i++) { ha[i] = badd2(ha[i], norm2(ha[i], sa.x, rha, rla)); hb[i] = badd2(hb[i], norm2(hb[i], sbb.x, rhb, rlb)); }
            const uint32_t ota = sb + SM_XT + ta * 80;
            sts128(ota + cq * 16, ha[0], ha[1], ha[2], ha[3]); sts32(ota + 64 + cq * 4, ha[4]);
            sts128(ota + cq * 16 + 640, hb[0], hb[1], hb[2], hb[3]); sts32(ota + 704 + cq * 4, hb[4]);
            asm volatile("fence.proxy.async.shared::cta;" ::: "memory");
        } else if (warp == 19 && lane < 20) {
            const uint32_t t = ~lds32(sb + SM_SEL + q * 8) & 2047;
            uint32_t v; asm volatile("ld.shared::cluster.u32 %0, [%1];" : "=r"(v) : "r"(mapa(sb + SM_HT + (t & 255) * 80 + lane * 4, t >> 8)) : "memory");
            sts32(sb + SM_HS + lane * 4, v);
        }
        if (warp < 18) {
            int n = 0;
            while ((((hv.x ^ par) | (hv.y ^ par) | (hv.z ^ par) | (hv.w ^ par)) & 0x40004000u) && ++n < SPIN_LIMIT) hv = ld_rlx128(gp);
            sts128(sb + SM_XS + tk * 16 + tid * 16, hv.x ^ par, hv.y ^ par, hv.z ^ par, hv.w ^ par);
        }
    }
    bar_sync(13, NTHR);
    STAMP(13);
    {
        float c0[4] = {0.f, 0.f, 0.f, 0.f}, c1[4] = {0.f, 0.f, 0.f, 0.f}, c2[4] = {0.f, 0.f, 0.f, 0.f};
        const uint32_t ba = sb + SM_XS + mr * 1168 + mi * 16 + 288 * kq;
        uint32_t b[5][4];
#pragma unroll
        for (int s = 0; s < 5; s++) ldsm4(b[s], ba + s * 64);
        mma_bf16(c0, A[0][0], A[0][1], A[0][2], A[0][3], b[0][0], b[0][1]);
        mma_bf16(c1, A[1][0], A[1][1], A[1][2], A[1][3], b[0][2], b[0][3]);
        mma_bf16(c2, A[2][0], A[2][1], A[2][2], A[2][3], b[1][0], b[1][1]);
        mma_bf16(c0, A[3][0], A[3][1], A[3][2], A[3][3], b[1][2], b[1][3]);
        mma_bf16(c1, A[4][0], A[4][1], A[4][2], A[4][3], b[2][0], b[2][1]);
        mma_bf16(c2, A[5][0], A[5][1], A[5][2], A[5][3], b[2][2], b[2][3]);
        mma_bf16(c0, A[6][0], A[6][1], A[6][2], A[6][3], b[3][0], b[3][1]);
        mma_bf16(c1, A[7][0], A[7][1], A[7][2], A[7][3], b[3][2], b[3][3]);
        mma_bf16(c2, A[8][0], A[8][1], A[8][2], A[8][3], b[4][0], b[4][1]);
        sts128f(sb + SM_RED + tid * 16, c0[0] + c1[0] + c2[0], c0[1] + c1[1] + c2[1], c0[2] + c1[2] + c2[2], c0[3] + c1[3] + c2[3]);
    }
    mbar_wait(mb + MB_W2 * 8);
    {
        const uint32_t aa = sb + (8 * (mi >> 1) + mr) * 144 + (mi & 1) * 16 + (SM_W2 + 2304 * nslot * kq + mt * 32);
#pragma unroll
        for (int s = 0; s < 5; s++) ldsm4t(A[s], aa + s * 2304);
    }
    bar_sync(1 + mt, 128);
    if (mt < nslot) {
        const uint32_t ra = sb + SM_RED + mt * 512 + lane * 16;
        const float4 p0 = lds128f(ra), p1 = lds128f(ra + 2560), p2 = lds128f(ra + 5120), p3 = lds128f(ra + 7680);
        const float g0 = bfr(((p0.x + p1.x) + (p2.x + p3.x)) * 64.f), g1 = bfr(((p0.y + p1.y) + (p2.y + p3.y)) * 64.f);
        const uint32_t sg = pack_bf16(g0 * rcpf(1.f + ex2f(g0 * -1.4426950408889634f)), g1 * rcpf(1.f + ex2f(g1 * -1.4426950408889634f)));
        const uint32_t gu = bmul2(sg, pack_bf16(((p0.z + p1.z) + (p2.z + p3.z)) * 64.f, ((p0.w + p1.w) + (p2.w + p3.w)) * 64.f));
#pragma unroll
        for (int i = 0; i < 2; i++) {
            const uint32_t rb_ = mapa(sb, 2 * kq + i);
            st_async1(rb_ + (SM_GU + (q * nslot + mt) * 128) + lane * 4, gu, rb_ + (SM_MB + MB_GU * 8));
        }
    }
    {
        mbar_wait(mb + MB_GU * 8);
        float c0[4] = {0.f, 0.f, 0.f, 0.f}, c1[4] = {0.f, 0.f, 0.f, 0.f};
        const uint32_t ba = sb + (SM_GU + 256 * nslot * kq) + lane * 16;
        uint32_t b[3][4];
#pragma unroll
        for (int s = 0; s < 3; s++) ldsm4t(b[s], ba + s * 512);
        mma_bf16(c0, A[0][0], A[0][1], A[0][2], A[0][3], b[0][0], b[0][1]);
        mma_bf16(c1, A[1][0], A[1][1], A[1][2], A[1][3], b[0][2], b[0][3]);
        if (nslot == 5) {
            mma_bf16(c0, A[2][0], A[2][1], A[2][2], A[2][3], b[1][0], b[1][1]);
            mma_bf16(c1, A[3][0], A[3][1], A[3][2], A[3][3], b[1][2], b[1][3]);
            mma_bf16(c0, A[4][0], A[4][1], A[4][2], A[4][3], b[2][0], b[2][1]);
        }
        sts128f(sb + SM_RED2 + tid * 16, c0[0] + c1[0], c0[1] + c1[1], c0[2] + c1[2], c0[3] + c1[3]);
    }
    bar_sync(6 + mt, 128);
    STAMP(14);
    {
        const int col = lane & 15, tp = lane >> 4;
        const uint32_t a = sb + (SM_RED2 + mt * 512 + kq * 16) + (col & 7) * 64 + (col >> 3) * 8 + tp * 4;
        const float s = (ldsf(a) + ldsf(a + 2560)) + (ldsf(a + 5120) + ldsf(a + 7680));
        if (mt * 16 + col < 72) st_rlx64(&g_s.part[((2 * kq + tp) * NCL + c) * D_ + 72 * q + mt * 16 + col], __float_as_uint(s), epoch);
    }
    {
        const unsigned cp = (unsigned)tid / 40u, i = tid - cp * 40;
        if (tid < 600 && i < 8 * nslot) {
            uint2 v; int n = 0;
            do { v = ld_rlx64(&g_s.part[(q * NCL + cp) * D_ + d0 + i]); } while (v.y != epoch && ++n < SPIN_LIMIT);
            sts32(sb + SM_FIN + tid * 4, v.x);
        }
    }
    if (warp >= 2) { bar_arrive(11, 640); STAMP(15); return; }
    const uint32_t key = lds32(sb + SM_SEL + q * 8);
    const float r = __uint_as_float((key ^ (~((int)key >> 31) | 0x80000000u)) & 0xFFFF0000u);
    const float sig = bfr(rcpf(1.f + ex2f(r * -1.4426950408889634f)));
    const float hs = bf_lo(lds16(sb + SM_HS + tid * 2)), hn = bf_lo(lds16(sb + SM_XS + q * 1168 + (d0 + tid) * 2)) * 64.f;
    asm volatile("{ .reg .pred p, q; .reg .u32 n; mov.u32 n, 0;\n"
                 "W_%=: mbarrier.try_wait.parity.acquire.cluster.shared::cta.b64 p, [%0], 0; add.u32 n, n, 1; setp.lt.and.u32 q, n, 65536, !p; @q bra W_%=; }" :: "r"(mb + MB_OUT * 8) : "memory");
    bar_sync(11, 640);
    if (tid < 8 * nslot) {
        float s = 0.f;
#pragma unroll
        for (int cp = 0; cp < NCL; cp++) s += ldsf(sb + SM_FIN + (cp * 40 + tid) * 4);
        prm.out[(~key & 2047) * D_ + d0 + tid] = __float2bfloat16_rn(hs + bfr(hn + bfr(bfr(s) * sig)));
    }
    STAMP(15);
}

typedef CUresult (*EncodeFn)(CUtensorMap*, CUtensorMapDataType, cuuint32_t, void*, const cuuint64_t*, const cuuint64_t*,
                             const cuuint32_t*, const cuuint32_t*, CUtensorMapInterleave, CUtensorMapSwizzle,
                             CUtensorMapL2promotion, CUtensorMapFloatOOBfill);

void make_map(EncodeFn fn, CUtensorMap* tm, const void* p, int cols, int rows, int bc, int br) {
    cuuint64_t dims[2] = {(cuuint64_t)cols, (cuuint64_t)rows};
    cuuint64_t strides[1] = {(cuuint64_t)cols * 2};
    cuuint32_t box[2] = {(cuuint32_t)bc, (cuuint32_t)br};
    cuuint32_t es[2] = {1, 1};
    fn(tm, CU_TENSOR_MAP_DATA_TYPE_BFLOAT16, 2, const_cast<void*>(p), dims, strides, box, es, CU_TENSOR_MAP_INTERLEAVE_NONE,
       CU_TENSOR_MAP_SWIZZLE_NONE, CU_TENSOR_MAP_L2_PROMOTION_NONE, CU_TENSOR_MAP_FLOAT_OOB_FILL_NONE);
}

}

extern "C" void kernel_launch(void* const* d_in, const int* in_sizes, int n_in, void* d_out, int out_size) {
    (void)in_sizes; (void)n_in; (void)out_size;
    void* fp = nullptr;
    cudaDriverEntryPointQueryResult qr;
    cudaGetDriverEntryPoint("cuTensorMapEncodeTiled", &fp, cudaEnableDefault, &qr);
    EncodeFn fn = (EncodeFn)fp;
    CUtensorMap tmG, tmU, tmD, tmO;
    make_map(fn, &tmG, d_in[11], F_, D_, 40, 192);
    make_map(fn, &tmU, d_in[12], F_, D_, 40, 192);
    make_map(fn, &tmD, d_in[13], D_, F_, 72, 160);
    make_map(fn, &tmO, d_out, D_, L_, 40, 256);
    Params p;
    p.x = (const unsigned short*)d_in[0];
    for (int i = 0; i < 6; i++) p.prm6[i] = (const unsigned short*)d_in[1 + i];
    p.logdt = (const unsigned short*)d_in[7]; p.dskip = (const unsigned short*)d_in[8];
    p.wr = (const unsigned short*)d_in[10];
    for (int i = 0; i < 3; i++) p.w3[i] = (const char*)d_in[11 + i];
    p.out = (__nv_bfloat16*)d_out;
    p.zero = 0;
    cudaFuncSetAttribute(fused_kernel, cudaFuncAttributeMaxDynamicSharedMemorySize, SM_TOTAL);
    fused_kernel<<<NCTA, NTHR, SM_TOTAL>>>(p, tmG, tmU, tmD, tmO);
}
```

```cpp
#include <cuda_runtime.h>
#include <cuda_bf16.h>
#include <cuda_fp16.h>
#include <cuda.h>
#include <stdint.h>

namespace {

constexpr int L_ = 2048, D_ = 576, F_ = 4608;
constexpr int NCL = 15, CS = 8, NCTA = NCL * CS, NTHR = 768;
#define PACE_NS 100
#define PRE_N 0
#define PRE_NS 200
#define L2PROMO 2
#define GAP_NS 0
#define ROW_DELAY 0
constexpr int SPIN_LIMIT = 1 << 22;

constexpr int SM_WG   = 0;
constexpr int SM_WU   = 46080;
constexpr int YP = 2736, YS = 544;
constexpr int UP = 3376, US = 672;
constexpr int SM_XT   = 92160;
constexpr int SM_U    = SM_XT + 8 * YP;
constexpr int SM_FAR  = SM_U + 8 * UP;
constexpr int FAR_SZ  = 12416;
constexpr int F_E5 = 0, F_O5 = 1536, F_E3 = 3088, F_O3 = 4624, F_E7 = 6176, F_E2 = F_E7 + 1024, F_E9 = F_E7 + 2048,
              F_H = 3088, F_O7 = F_E7 + F_H, F_O2 = F_E2 + F_H, F_O9 = F_E9 + F_H;
constexpr int SM_P    = SM_FAR + 5 * FAR_SZ;
constexpr int PN_SZ = 584 * 4, SM_PN = SM_P + 64 * 4;
constexpr int P_GS = 48 * 4, P_H7 = 192 * 4, P_HS = 72 * 4;
constexpr int PF_SZ = (192 + 216) * 4, SM_PF = SM_PN + 5 * PN_SZ + 32;
constexpr int SM_MISC = SM_PF + 5 * PF_SZ;
constexpr int SM_ST   = SM_MISC;
constexpr int SM_RK   = SM_ST + 2048;
constexpr int SM_SEL  = SM_RK + 256;
constexpr int SM_KG   = SM_SEL + 64;
constexpr int SM_SC   = SM_KG + 160;
constexpr int SM_DW   = SM_SC + 32;
constexpr int SM_MB   = SM_DW + 160;
constexpr int SM_TOTAL = SM_MB + 128;
constexpr int SM_ROW  = SM_XT - 20736;
constexpr int SM_XTL  = SM_ROW - 20480;
constexpr int SM_RED2 = SM_WG;
constexpr int SM_HT   = SM_P - 512;
constexpr int SM_KEY  = SM_FAR + 9216 + 128;
constexpr int SM_CAND = SM_KEY + 1024;
constexpr int SM_FIN  = SM_FAR + FAR_SZ + 9216 + 128;
constexpr int SM_HS   = SM_FIN + 2400;
constexpr int SM_XS   = SM_U;
constexpr int SM_GU   = SM_XS + 9344;
constexpr int SM_RED  = SM_GU + 5632;
static_assert(F_O9 + 1024 <= FAR_SZ && FAR_SZ % 128 == 0, "far overflow");
static_assert(SM_RED + 10240 <= SM_FAR && SM_HS + 128 <= SM_FAR + 2 * FAR_SZ && SM_HT + 20496 <= SM_MISC, "alias overflow");
static_assert(SM_TOTAL <= 232448, "smem overflow");
static_assert(SM_FAR % 128 == 0 && SM_XT % 128 == 0 && SM_XTL % 128 == 0 && SM_P % 16 == 0 && SM_MISC % 16 == 0 && SM_MB % 8 == 0 && SM_HS % 16 == 0, "align");

enum { MB_X = 0, MB_W1 = 5, MB_W2 = 6, MB_KEY = 7, MB_GU = 8, MB_Y = 9, MB_OUT = 10, MB_T = 11, MB_R = 12 };

struct __align__(128) Scratch {
    unsigned epoch, zcnt, pad[30];
    uint4  st1[L_ * 2];
    float4 acc[L_];
    uint4  cand[64 * NCL * 6];
    uint2  part[8 * NCL * D_];
};
__device__ Scratch g_s;
#define STAMP(i)

__device__ __forceinline__ uint32_t mapa(uint32_t a, uint32_t r) { uint32_t d; asm("mapa.shared::cluster.u32 %0, %1, %2;" : "=r"(d) : "r"(a), "r"(r)); return d; }
__device__ __forceinline__ void mbar_wait(uint32_t mb) {
    asm volatile("{ .reg .pred p, q; .reg .u32 n; mov.u32 n, 0;\n"
                 "W_%=: mbarrier.try_wait.parity.shared::cta.b64 p, [%0], 0; add.u32 n, n, 1; setp.lt.and.u32 q, n, 65536, !p; @q bra W_%=; }" :: "r"(mb) : "memory");
}
__device__ __forceinline__ void arm(uint32_t mb, uint32_t bytes) { asm volatile("mbarrier.arrive.expect_tx.shared::cta.b64 _, [%0], %1;" :: "r"(mb), "r"(bytes) : "memory"); }
__device__ __forceinline__ void bar_sync(int id, int n) { asm volatile("bar.sync %0, %1;" :: "r"(id), "r"(n) : "memory"); }
__device__ __forceinline__ void bar_arrive(int id, int n) { asm volatile("bar.arrive %0, %1;" :: "r"(id), "r"(n) : "memory"); }
__device__ __forceinline__ uint32_t lds16(uint32_t a) { unsigned short v; asm volatile("ld.shared.u16 %0, [%1];" : "=h"(v) : "r"(a) : "memory"); return v; }
__device__ __forceinline__ uint32_t lds32(uint32_t a) { uint32_t v; asm volatile("ld.shared.u32 %0, [%1];" : "=r"(v) : "r"(a) : "memory"); return v; }
__device__ __forceinline__ uint2 lds64(uint32_t a) { uint2 v; asm volatile("ld.shared.v2.u32 {%0,%1}, [%2];" : "=r"(v.x), "=r"(v.y) : "r"(a) : "memory"); return v; }
__device__ __forceinline__ float ldsf(uint32_t a) { float v; asm volatile("ld.shared.f32 %0, [%1];" : "=f"(v) : "r"(a) : "memory"); return v; }
__device__ __forceinline__ uint4 lds128(uint32_t a) { uint4 v; asm volatile("ld.shared.v4.u32 {%0,%1,%2,%3}, [%4];" : "=r"(v.x), "=r"(v.y), "=r"(v.z), "=r"(v.w) : "r"(a) : "memory"); return v; }
__device__ __forceinline__ float4 lds128f(uint32_t a) { float4 v; asm volatile("ld.shared.v4.f32 {%0,%1,%2,%3}, [%4];" : "=f"(v.x), "=f"(v.y), "=f"(v.z), "=f"(v.w) : "r"(a) : "memory"); return v; }
__device__ __forceinline__ void sts16(uint32_t a, uint32_t v) { asm volatile("{ .reg .b16 l, h; mov.b32 {l, h}, %1; st.shared.b16 [%0], l; }" :: "r"(a), "r"(v) : "memory"); }
__device__ __forceinline__ void sts32(uint32_t a, uint32_t v) { asm volatile("st.shared.u32 [%0], %1;" :: "r"(a), "r"(v) : "memory"); }
__device__ __forceinline__ void sts64(uint32_t a, uint32_t x, uint32_t y) { asm volatile("st.shared.v2.u32 [%0], {%1,%2};" :: "r"(a), "r"(x), "r"(y) : "memory"); }
__device__ __forceinline__ void stsf(uint32_t a, float v) { asm volatile("st.shared.f32 [%0], %1;" :: "r"(a), "f"(v) : "memory"); }
__device__ __forceinline__ void sts128(uint32_t a, uint32_t x, uint32_t y, uint32_t z, uint32_t w) { asm volatile("st.shared.v4.u32 [%0], {%1,%2,%3,%4};" :: "r"(a), "r"(x), "r"(y), "r"(z), "r"(w) : "memory"); }
__device__ __forceinline__ void sts128f(uint32_t a, float x, float y, float z, float w) { asm volatile("st.shared.v4.f32 [%0], {%1,%2,%3,%4};" :: "r"(a), "f"(x), "f"(y), "f"(z), "f"(w) : "memory"); }
__device__ __forceinline__ void ldsm4(uint32_t (&r)[4], uint32_t a) { asm volatile("ldmatrix.sync.aligned.m8n8.x4.shared.b16 {%0,%1,%2,%3}, [%4];" : "=r"(r[0]), "=r"(r[1]), "=r"(r[2]), "=r"(r[3]) : "r"(a) : "memory"); }
__device__ __forceinline__ void ldsm4t(uint32_t (&r)[4], uint32_t a) { asm volatile("ldmatrix.sync.aligned.m8n8.x4.trans.shared.b16 {%0,%1,%2,%3}, [%4];" : "=r"(r[0]), "=r"(r[1]), "=r"(r[2]), "=r"(r[3]) : "r"(a) : "memory"); }
__device__ __forceinline__ void ldsm2t(uint32_t& r0, uint32_t& r1, uint32_t a) { asm volatile("ldmatrix.sync.aligned.m8n8.x2.trans.shared.b16 {%0,%1}, [%2];" : "=r"(r0), "=r"(r1) : "r"(a) : "memory"); }
__device__ __forceinline__ void stsm4t(uint32_t a, uint32_t r0, uint32_t r1, uint32_t r2, uint32_t r3) { asm volatile("stmatrix.sync.aligned.m8n8.x4.trans.shared.b16 [%0], {%1,%2,%3,%4};" :: "r"(a), "r"(r0), "r"(r1), "r"(r2), "r"(r3) : "memory"); }
__device__ __forceinline__ void stsm4(uint32_t a, uint32_t r0, uint32_t r1, uint32_t r2, uint32_t r3) { asm volatile("stmatrix.sync.aligned.m8n8.x4.shared.b16 [%0], {%1,%2,%3,%4};" :: "r"(a), "r"(r0), "r"(r1), "r"(r2), "r"(r3) : "memory"); }
__device__ __forceinline__ void stsm2t(uint32_t a, uint32_t r0, uint32_t r1) { asm volatile("stmatrix.sync.aligned.m8n8.x2.trans.shared.b16 [%0], {%1,%2};" :: "r"(a), "r"(r0), "r"(r1) : "memory"); }
__device__ __forceinline__ uint4 ldg128(const void* p) { uint4 v; asm volatile("ld.global.nc.v4.u32 {%0,%1,%2,%3}, [%4];" : "=r"(v.x), "=r"(v.y), "=r"(v.z), "=r"(v.w) : "l"(p)); return v; }
__device__ __forceinline__ uint32_t ldg32(const void* p) { uint32_t v; asm volatile("ld.global.nc.u32 %0, [%1];" : "=r"(v) : "l"(p)); return v; }
__device__ __forceinline__ uint32_t ldg16(const void* p) { unsigned short v; asm volatile("ld.global.nc.u16 %0, [%1];" : "=h"(v) : "l"(p)); return v; }
__device__ __forceinline__ uint32_t opaque(uint32_t v) { uint32_t r; asm volatile("mov.b32 %0, %1;" : "=r"(r) : "r"(v)); return r; }
__device__ __forceinline__ void mma_f16(float (&d)[4], const uint32_t (&a)[4], uint32_t b0, uint32_t b1) {
    asm volatile("mma.sync.aligned.m16n8k16.row.col.f32.f16.f16.f32 {%0,%1,%2,%3}, {%4,%5,%6,%7}, {%8,%9}, {%0,%1,%2,%3};"
        : "+f"(d[0]), "+f"(d[1]), "+f"(d[2]), "+f"(d[3]) : "r"(a[0]), "r"(a[1]), "r"(a[2]), "r"(a[3]), "r"(b0), "r"(b1));
}
__device__ __forceinline__ void mma_bf16(float (&d)[4], uint32_t a0, uint32_t a1, uint32_t a2, uint32_t a3, uint32_t b0, uint32_t b1) {
    asm volatile("mma.sync.aligned.m16n8k16.row.col.f32.bf16.bf16.f32 {%0,%1,%2,%3}, {%4,%5,%6,%7}, {%8,%9}, {%0,%1,%2,%3};"
        : "+f"(d[0]), "+f"(d[1]), "+f"(d[2]), "+f"(d[3]) : "r"(a0), "r"(a1), "r"(a2), "r"(a3), "r"(b0), "r"(b1));
}
__device__ __forceinline__ void mma_bf16_k8(float (&d)[4], uint32_t a0, uint32_t a1, uint32_t b0) {
    asm volatile("mma.sync.aligned.m16n8k8.row.col.f32.bf16.bf16.f32 {%0,%1,%2,%3}, {%4,%5}, {%6}, {%0,%1,%2,%3};"
        : "+f"(d[0]), "+f"(d[1]), "+f"(d[2]), "+f"(d[3]) : "r"(a0), "r"(a1), "r"(b0));
}
__device__ __forceinline__ uint32_t pack_f16(float lo, float hi) { uint32_t r; asm("cvt.rn.f16x2.f32 %0, %1, %2;" : "=r"(r) : "f"(hi), "f"(lo)); return r; }
__device__ __forceinline__ uint32_t pack_bf16(float lo, float hi) { uint32_t r; asm("cvt.rn.bf16x2.f32 %0, %1, %2;" : "=r"(r) : "f"(hi), "f"(lo)); return r; }
__device__ __forceinline__ float bf_lo(uint32_t v) { return __uint_as_float(v << 16); }
__device__ __forceinline__ float bf_hi(uint32_t v) { return __uint_as_float(v & 0xFFFF0000u); }
__device__ __forceinline__ float bfr(float x) { return __uint_as_float(pack_bf16(0.f, x)); }
__device__ __forceinline__ uint32_t bsub2(uint32_t a, uint32_t b) { uint32_t r; asm("sub.rn.bf16x2 %0, %1, %2;" : "=r"(r) : "r"(a), "r"(b)); return r; }
__device__ __forceinline__ uint32_t badd2(uint32_t a, uint32_t b) { uint32_t r; asm("add.rn.bf16x2 %0, %1, %2;" : "=r"(r) : "r"(a), "r"(b)); return r; }
__device__ __forceinline__ uint32_t bmul2(uint32_t a, uint32_t b) { uint32_t r; asm("mul.rn.bf16x2 %0, %1, %2;" : "=r"(r) : "r"(a), "r"(b)); return r; }
__device__ __forceinline__ uint32_t bfma2(uint32_t a, uint32_t b, uint32_t c) { uint32_t r; asm("fma.rn.bf16x2 %0, %1, %2, %3;" : "=r"(r) : "r"(a), "r"(b), "r"(c)); return r; }
__device__ __forceinline__ uint32_t hadd2(uint32_t a, uint32_t b) { uint32_t r; asm("add.rn.f16x2 %0, %1, %2;" : "=r"(r) : "r"(a), "r"(b)); return r; }
__device__ __forceinline__ uint32_t hmul2(uint32_t a, uint32_t b) { uint32_t r; asm("mul.rn.f16x2 %0, %1, %2;" : "=r"(r) : "r"(a), "r"(b)); return r; }
__device__ __forceinline__ uint32_t hfma2(uint32_t a, uint32_t b, uint32_t c) { uint32_t r; asm("fma.rn.f16x2 %0, %1, %2, %3;" : "=r"(r) : "r"(a), "r"(b), "r"(c)); return r; }
__device__ __forceinline__ uint32_t hneg2(uint32_t a) { uint32_t r; asm("neg.f16x2 %0, %1;" : "=r"(r) : "r"(a)); return r; }
__device__ __forceinline__ float rcpf(float x) { float r; asm("rcp.approx.ftz.f32 %0, %1;" : "=f"(r) : "f"(x)); return r; }
__device__ __forceinline__ float sqrta(float x) { float r; asm("sqrt.approx.ftz.f32 %0, %1;" : "=f"(r) : "f"(x)); return r; }
__device__ __forceinline__ float ex2f(float x) { float r; asm("ex2.approx.ftz.f32 %0, %1;" : "=f"(r) : "f"(x)); return r; }
__device__ __forceinline__ void st_async4(uint32_t a, uint32_t x, uint32_t y, uint32_t z, uint32_t w, uint32_t mb) {
    asm volatile("st.async.shared::cluster.mbarrier::complete_tx::bytes.v4.u32 [%0], {%1,%2,%3,%4}, [%5];" :: "r"(a), "r"(x), "r"(y), "r"(z), "r"(w), "r"(mb) : "memory"); }
__device__ __forceinline__ void st_async1(uint32_t a, uint32_t x, uint32_t mb) {
    asm volatile("st.async.shared::cluster.mbarrier::complete_tx::bytes.u32 [%0], %1, [%2];" :: "r"(a), "r"(x), "r"(mb) : "memory"); }
__device__ __forceinline__ unsigned ld_rlx(const void* p) { unsigned v; asm volatile("ld.relaxed.gpu.global.u32 %0, [%1];" : "=r"(v) : "l"(p) : "memory"); return v; }
__device__ __forceinline__ unsigned ld_acq(const void* p) { unsigned v; asm volatile("ld.acquire.gpu.global.u32 %0, [%1];" : "=r"(v) : "l"(p) : "memory"); return v; }
__device__ __forceinline__ uint2 ld_rlx64(const void* p) { unsigned long long v; asm volatile("ld.relaxed.gpu.global.u64 %0, [%1];" : "=l"(v) : "l"(p) : "memory"); return make_uint2((unsigned)v, (unsigned)(v >> 32)); }
__device__ __forceinline__ void st_rlx64(void* p, unsigned lo, unsigned hi) { asm volatile("st.relaxed.gpu.global.u64 [%0], %1;" :: "l"(p), "l"((unsigned long long)lo | ((unsigned long long)hi << 32)) : "memory"); }
__device__ __forceinline__ void st_rlx128(void* p, uint32_t x, uint32_t y, uint32_t z, uint32_t w) {
    asm volatile("st.relaxed.gpu.global.v2.u64 [%0], {%1,%2};" :: "l"(p), "l"((unsigned long long)x | ((unsigned long long)y << 32)), "l"((unsigned long long)z | ((unsigned long long)w << 32)) : "memory"); }
__device__ __forceinline__ uint4 ld_rlx128(const void* p) { unsigned long long a, b; asm volatile("ld.relaxed.gpu.global.v2.u64 {%0,%1}, [%2];" : "=l"(a), "=l"(b) : "l"(p) : "memory"); return make_uint4((unsigned)a, (unsigned)(a >> 32), (unsigned)b, (unsigned)(b >> 32)); }
__device__ __forceinline__ void tma2d(uint32_t dst, const CUtensorMap* tm, int x, int y, uint32_t mb) {
    asm volatile("cp.async.bulk.tensor.2d.shared::cluster.global.mbarrier::complete_tx::bytes [%0], [%1, {%3, %4}], [%2];"
                 :: "r"(dst), "l"(tm), "r"(mb), "r"(x), "r"(y) : "memory");
}
__device__ __forceinline__ void cmul(float& xr, float& xi, float ar, float ai, float br, float bi) {
    const float r = fmaf(ar, br, -ai * bi), i = fmaf(ar, bi, ai * br); xr = r; xi = i;
}
__device__ __forceinline__ void csq(float& xr, float& xi, float ar, float ai) {
    const float r = fmaf(ar, ar, -ai * ai), i = (ar + ar) * ai; xr = r; xi = i;
}
__device__ __forceinline__ void cexp_s(float& zr, float& zi, float e2, float turns) {
    const float mag = ex2f(e2), r = (turns - rintf(turns)) * 6.283185307179586f;
    zr = mag * __cosf(r); zi = mag * __sinf(r);
}
__device__ __forceinline__ uint32_t ln_stats(float s1, float s2) {
    const float m = s1 * (1.f / D_);
    const float var = fmaxf(fmaf(s2, 1.f / D_, -m * m), 0.f);
    return pack_bf16(m, sqrta(bfr(bfr(var) + 1e-5f)));
}
__device__ __forceinline__ uint32_t rsplit(float rs) { const float h = bfr(rs); return pack_bf16(h, rs - h); }
__device__ __forceinline__ uint32_t norm2(uint32_t v, uint32_t m2, uint32_t rh2, uint32_t rl2) {
    const uint32_t dd = bsub2(v, m2);
    return bfma2(dd, rh2, bmul2(dd, rl2));
}
template <int N>
__device__ __forceinline__ uint32_t rank4(uint32_t a, uint32_t key) {
    uint32_t r0 = 0, r1 = 0, r2 = 0, r3 = 0;
#pragma unroll
    for (int i = 0; i < N; i++) {
        const uint4 o = lds128(a + i * 16);
        r0 += (key - o.x) >> 31; r1 += (key - o.y) >> 31; r2 += (key - o.z) >> 31; r3 += (key - o.w) >> 31;
    }
    return (r0 + r1) + (r2 + r3);
}
struct H2C { uint32_t r, i; };
__device__ __forceinline__ H2C splat(float r, float i) { H2C h; h.r = pack_f16(r, r); h.i = pack_f16(i, i); return h; }
__device__ __forceinline__ void expand4(uint32_t are, uint32_t aim, uint32_t R0, uint32_t R1, uint32_t I0, uint32_t I1, H2C m4) {
    sts128(are, R0, R1, hfma2(R0, m4.r, hneg2(hmul2(I0, m4.i))), hfma2(R1, m4.r, hneg2(hmul2(I1, m4.i))));
    sts128(aim, I0, I1, hfma2(R0, m4.i, hmul2(I0, m4.r)), hfma2(R1, m4.i, hmul2(I1, m4.r)));
}
__device__ __forceinline__ void expand8(uint32_t are, uint32_t aim, float sr, float si, float m1r, float m1i, float m2r, float m2i, H2C m4) {
    float r1, i1, r2, i2, r3, i3;
    cmul(r1, i1, sr, si, m1r, m1i); cmul(r2, i2, sr, si, m2r, m2i); cmul(r3, i3, r1, i1, m2r, m2i);
    expand4(are, aim, pack_f16(sr, r1), pack_f16(r2, r3), pack_f16(si, i1), pack_f16(i2, i3), m4);
}
__device__ __forceinline__ void put16(uint32_t a, uint32_t v) { sts16(a, v); sts16(a + 6, v); }

struct Params {
    const unsigned short *x, *prm6[6], *logdt, *dskip, *wr;
    const char* w3[3];
    __nv_bfloat16* out;
    Scratch* gs;
    unsigned zero;
};
#define CP(x) ((x) | zero)
__device__ __forceinline__ void wgmma32(float (&d)[4][4], const uint32_t (&a)[4], uint32_t dlo) {
    asm volatile("{ .reg .b64 ds; mov.b64 ds, {%20, %21};\n"
                 "wgmma.mma_async.sync.aligned.m64n32k16.f32.f16.f16 {%0,%1,%2,%3,%4,%5,%6,%7,%8,%9,%10,%11,%12,%13,%14,%15}, {%16,%17,%18,%19}, ds, 1, 1, 1, 0; }"
        : "+f"(d[0][0]), "+f"(d[0][1]), "+f"(d[0][2]), "+f"(d[0][3]), "+f"(d[1][0]), "+f"(d[1][1]), "+f"(d[1][2]), "+f"(d[1][3]),
          "+f"(d[2][0]), "+f"(d[2][1]), "+f"(d[2][2]), "+f"(d[2][3]), "+f"(d[3][0]), "+f"(d[3][1]), "+f"(d[3][2]), "+f"(d[3][3])
        : "r"(a[0]), "r"(a[1]), "r"(a[2]), "r"(a[3]), "r"(dlo), "n"(128 >> 4));
}

__global__ void __cluster_dims__(CS, 1, 1) __launch_bounds__(NTHR, 1)
fused_kernel(const __grid_constant__ Params prm, const __grid_constant__ CUtensorMap tmG, const __grid_constant__ CUtensorMap tmU,
             const __grid_constant__ CUtensorMap tmD, const __grid_constant__ CUtensorMap tmO, const __grid_constant__ CUtensorMap tmX)
{
    extern __shared__ __align__(1024) unsigned char smem[];
    const int tid = threadIdx.x, lane = tid & 31, warp = __shfl_sync(~0u, tid >> 5, 0);
    const int c = blockIdx.x >> 3, q = blockIdx.x & 7;
    const int nslot = (c < NCL - 1) ? 5 : 2;
    const int d0 = 40 * c;
    const uint32_t sb = opaque((uint32_t)__cvta_generic_to_shared(smem));
    const uint32_t mb = sb + SM_MB;
    Scratch& g_s = *prm.gs;
    const unsigned& zero = prm.zero;
    STAMP(0);

    if (warp >= 20) {
        unsigned epoch = 0;
        if (warp == 20) {
            if (lane == 0) {
#pragma unroll
                for (int i = 0; i < 13; i++)
                    asm volatile("mbarrier.init.shared::cta.b64 [%0], %1;" :: "r"(mb + i * 8), "r"(i == MB_OUT ? 8 : (i == MB_R || i == MB_T) ? 2 : i == MB_Y ? 1 + 4 * nslot : 1) : "memory");
                asm volatile("fence.mbarrier_init.release.cluster;" ::: "memory");
                arm(mb + MB_W1 * 8, 92160); arm(mb + MB_W2 * 8, nslot * 9216); arm(mb + MB_KEY * 8, 256); arm(mb + MB_GU * 8, nslot * 1024); arm(mb + MB_T * 8, 20480);
                const int bytes = max(min(18, L_ - 18 * (int)blockIdx.x), 1) * (D_ * 2);
                arm(mb + MB_R * 8, bytes);
                asm volatile("cp.async.bulk.shared::cluster.global.mbarrier::complete_tx::bytes [%0], [%1], %2, [%3];"
                             :: "r"(sb + SM_ROW), "l"(prm.x + min(18 * (int)blockIdx.x, L_ - 1) * D_), "r"(bytes), "r"(mb + MB_R * 8) : "memory");
            }
            __syncwarp();
        } else if (warp == 22) {
            epoch = ld_rlx(&g_s.epoch);
            if (lane < 18 && 18 * c + lane < 256) g_s.acc[256 * q + 18 * c + lane] = make_float4(0.f, 0.f, 0.f, 0.f);
        } else if (warp == 23 && lane == 0) asm volatile("prefetch.tensormap [%0];" :: "l"(&tmX) : "memory");
        asm volatile("barrier.cluster.arrive.relaxed.aligned;" ::: "memory");
        bar_sync(12, NTHR);
        if (warp == 22) {
            if (lane == 0) { sts32(sb + SM_SC + 28, epoch); asm volatile("mbarrier.arrive.shared::cta.b64 _, [%0];" :: "r"(mb + MB_R * 8) : "memory"); }
            epoch++;
            asm volatile("fence.acq_rel.gpu;" ::: "memory");
            __syncwarp();
            if (lane == 0) asm volatile("red.relaxed.gpu.global.add.u32 [%0], 1;" :: "l"(&g_s.zcnt) : "memory");
            STAMP(1);
            uint4 wv = make_uint4(0, 0, 0, 0), wv2 = ldg128((const uint4*)prm.wr + lane), wv3 = ldg128((const uint4*)prm.wr + 32 + lane);
            if (lane < 8) wv = ldg128((const uint4*)prm.wr + 64 + lane);
            if (lane < 10) {
                const int j = lane < 5 ? lane : lane - 5;
                uint4 v = make_uint4(0, 0, 0, 0);
                if (j < nslot) v = ldg128((const uint4*)((lane < 5 ? prm.dskip : prm.wr) + d0) + j);
                sts128(sb + SM_DW + lane * 16, v.x, v.y, v.z, v.w);
            }
            __syncwarp();
            if (lane == 0) asm volatile("mbarrier.arrive.shared::cta.b64 _, [%0];" :: "r"(mb + MB_T * 8) : "memory");
            mbar_wait(mb + (MB_X + nslot - 1) * 8);
            const uint32_t old = (epoch & 1) ? 0u : 0x40004000u;
#pragma unroll 1
            for (int t = 0; t < 8; t++) {
                uint4* pp = (uint4*)&g_s.part[(t * NCL + c) * D_ + 72 * q] + lane;
                *pp = make_uint4(0, 0, 0, 0);
                if (lane < 4) pp[32] = make_uint4(0, 0, 0, 0);
                if (lane < 6) g_s.cand[((q * 8 + t) * NCL + c) * 6 + lane] = make_uint4(old, old, old, old);
            }
            float a[4] = {0.f, 0.f, 0.f, 0.f};
            const uint32_t one = 0x3F803F80u;
            mma_bf16(a, one, one, one, one, wv.x, wv.y);  mma_bf16(a, one, one, one, one, wv.z, wv.w);
            mma_bf16(a, one, one, one, one, wv2.x, wv2.y); mma_bf16(a, one, one, one, one, wv2.z, wv2.w);
            mma_bf16(a, one, one, one, one, wv3.x, wv3.y); mma_bf16(a, one, one, one, one, wv3.z, wv3.w);
            float s = a[0] + a[1];
            s += __shfl_xor_sync(~0u, s, 1); s += __shfl_xor_sync(~0u, s, 2);
            stsf(sb + SM_SC + 24, s);
            __syncwarp();
            if (lane == 0) {
                int n = 0;
                while ((int)(ld_acq(&g_s.zcnt) - epoch * NCTA) < 0 && ++n < SPIN_LIMIT) __nanosleep(200);
                arm(mb + MB_Y * 8, 7 * 512 * nslot);
                if (blockIdx.x == 0) g_s.epoch = epoch;
            }
            STAMP(2);
            return;
        }
        if (warp == 21) {
            bar_sync(13, 736);
            if (GAP_NS) __nanosleep(GAP_NS);
            asm volatile("fence.proxy.async.shared::cta;" ::: "memory");
#pragma unroll 1
            for (int i = 0; i < 24; i++) {
                if (lane == 0) tma2d(sb + SM_WG + i * 3840, i < 12 ? &tmG : &tmU, 320 * c + 8 * nslot * q, 48 * (i < 12 ? i : i - 12), mb + MB_W1 * 8);
                __nanosleep(PACE_NS);
            }
            STAMP(1);
            return;
        }
        if (warp == 20) {
            mbar_wait(mb + MB_R * 8);
            if (lane == 0) asm volatile("cp.async.bulk.tensor.3d.shared::cluster.global.mbarrier::complete_tx::bytes [%0], [%1, {%3, %4, %5}], [%2];"
                                        :: "r"(sb + SM_XTL), "l"(&tmX), "r"(mb + MB_T * 8), "r"(d0), "r"(8 * q), "r"(0) : "memory");
            STAMP(6);
        }
        if (PRE_N && warp == 23) {
            mbar_wait(mb + MB_R * 8);
            const char* wp = prm.w3[0] + blockIdx.x * (PRE_N * 4096) + lane * 128;
#pragma unroll 1
            for (int i = 0; i < PRE_N; i++) { asm volatile("prefetch.global.L2 [%0];" :: "l"(wp + i * 4096) : "memory"); __nanosleep(PRE_NS); }
        }
        asm volatile("barrier.cluster.wait.aligned;" ::: "memory");
        bar_sync(13, 736);
        {
            const int sl = nslot - 1 - (lane >> 2), pe = (lane & 3) * 2 + (warp & 1);
            if (sl >= 0) {
                if (pe == q) arm(mb + (MB_X + sl) * 8, 7 * 512);
                else {
                    const uint32_t rb_ = mapa(sb, pe);
                    asm volatile("cp.async.bulk.shared::cluster.shared::cta.mbarrier::complete_tx::bytes [%0], [%1], %2, [%3];"
                                 :: "r"(rb_ + SM_U + 128 + q * UP + sl * US), "r"(sb + SM_XT + pe * YP + sl * YS), "r"(512), "r"(rb_ + SM_MB + (MB_X + sl) * 8) : "memory");
                }
            }
        }
        STAMP(1);
        if (warp == 23) return;
        __syncwarp();
        bar_sync(14, 544);
        if (lane == 0) {
            asm volatile("cp.async.bulk.tensor.3d.global.shared::cta.bulk_group [%0, {%2, %3, %4}], [%1];" :: "l"(&tmO), "r"(sb + SM_XT), "r"(d0), "r"(8 * q), "r"(0) : "memory");
            asm volatile("cp.async.bulk.commit_group;" ::: "memory");
            asm volatile("cp.async.bulk.wait_group 0;" ::: "memory");
            asm volatile("fence.proxy.async.global;" ::: "memory");
        }
        __syncwarp();
        STAMP(2);
        if (lane < 8) asm volatile("mbarrier.arrive.release.cluster.shared::cluster.b64 _, [%0];" :: "r"(mapa(mb + MB_OUT * 8, lane)) : "memory");
        STAMP(3);
        return;
    }

    const int g = lane >> 2, cq = lane & 3;
    const int k = warp >> 2, wq = warp & 3;
    const int trow = 18 * blockIdx.x + warp;
    const bool rowact = warp < 18 && trow < L_;
    const int dch = min(d0 + 8 * k + q, D_ - 1);
    uint32_t pv[6];
#pragma unroll
    for (int i = 0; i < 6; i++) pv[i] = ldg16(prm.prm6[i] + (uint32_t)(dch * 128 + wq * 32 + lane));
    const uint32_t pLdt = ldg16(prm.logdt + dch);
    const int ta = 16 * (warp & 15) + g;
    uint32_t xa[5], xb[5];
    asm volatile("barrier.cluster.arrive.relaxed.aligned;" ::: "memory");
    uint4* const st1p = &g_s.st1[(((trow >> 3) & 7) * 256 + ((trow >> 6) & 31) * 8 + (trow & 7)) * 2 + (lane >> 2)];
    const bool pub = rowact && (lane & 0x1B) == 0;
    if (pub) st_rlx128(st1p, 0, 0, 0, 0);
    {
        const uint32_t za = sb + SM_P + tid * 16;
        sts128(za, 0, 0, 0, 0);
        if (tid < (SM_MISC - SM_P) / 16 - 640) sts128(za + 10240, 0, 0, 0, 0);
        sts64(sb + SM_U + ((tid >> 4) & 7) * UP + k * US + (lane & 15) * 8, 0, 0);
    }
    bar_sync(12, NTHR);
    const uint32_t dep = lds32(sb + SM_P);
#define PV(x) __uint_as_float(__byte_perm(dep, x, 0x5410))
    STAMP(1);
    const uint32_t fb = sb + SM_FAR + k * FAR_SZ;
    const uint32_t pn = sb + SM_PN + k * PN_SZ, pf = sb + SM_PF + k * PF_SZ;
    unsigned epoch;
    {
        const uint32_t kb = fb + wq * 3072;
        const uint32_t kl = kb + lane * 16;
        uint32_t Af[4][4];
        float sr, si, z1r, z1i, z2r, z2i, z4r, z4i, hr, hi_;
        {
            const float dt = bfr(ex2f(PV(pLdt) * 1.4426950408889634f));
            const float e2 = dt * PV(pv[0]) * 1.4426950408889634f, an = dt * PV(pv[1]);
            cmul(sr, si, PV(pv[4]), PV(pv[5]), dt * PV(pv[2]), dt * PV(pv[3]));
            const unsigned E = min(max(__reduce_max_sync(~0u, __float_as_uint(fmaxf(fabsf(sr), fabsf(si)))) >> 23, 1u), 253u);
            const float sc = __uint_as_float((254u - E) << 23);
            sr *= sc; si *= -sc;
            sts64(sb + SM_KG + warp * 8, E, __reduce_add_sync(~0u, __float2int_rn(sr * 16777216.f)));
            float ar, ai, br, bi, cr, ci, dr, di;
            { const float m = ex2f(e2 * 8.f); ar = m * __cosf(an * 8.f); ai = m * __sinf(an * 8.f); }
            csq(br, bi, ar, ai); csq(cr, ci, br, bi); csq(dr, di, cr, ci);
            const H2C m4 = splat(cr, ci);
            {
                float r3, i3;
                cmul(r3, i3, ar, ai, br, bi);
                expand4(kl, kl + 1024, pack_f16(1.f, ar), pack_f16(br, r3), pack_f16(0.f, ai), pack_f16(bi, i3), m4);
            }
            expand8(kl + 512, kl + 1536, dr, di, ar, ai, br, bi, m4);
            { const float m = ex2f(e2); z1r = m * __cosf(an); z1i = -m * __sinf(an); }
            cexp_s(hr, hi_, e2 * 128.f, an * (-128.f * 0.15915494309189535f));
            csq(z2r, z2i, z1r, z1i); csq(z4r, z4i, z2r, z2i);
        }
        __syncwarp();
#pragma unroll
        for (int ks = 0; ks < 4; ks++) ldsm4t(Af[ks], kb + (lane >> 3) * 512 + (lane & 7) * 16 + ks * 128);
        STAMP(2);
        mbar_wait(mb + MB_R * 8);
        epoch = lds32(sb + SM_SC + 28) + 1;
        {
            float a[4] = {0.f, 0.f, 0.f, 0.f}, b[4] = {0.f, 0.f, 0.f, 0.f};
            uint32_t rx[9];
#pragma unroll
            for (int i = 0; i < 9; i++) rx[i] = lds32(sb + SM_ROW + warp * (D_ * 2) + lane * 4 + i * 128);
#pragma unroll
            for (int i = 0; i < 9; i++) { if (i & 1) mma_bf16_k8(b, rx[i], 0x3F803F80u, rx[i]); else mma_bf16_k8(a, rx[i], 0x3F803F80u, rx[i]); }
            float s2 = (g & 1) ? a[1] + b[1] : a[0] + b[0], s1 = (a[2] + b[2]) + (a[3] + b[3]);
            s2 += __shfl_xor_sync(~0u, s2, 4); s1 += __shfl_xor_sync(~0u, s1, 1);
            s2 += __shfl_xor_sync(~0u, s2, 9); s1 += __shfl_xor_sync(~0u, s1, 2);
            s2 += __shfl_xor_sync(~0u, s2, 18);
            const uint32_t ms = ln_stats(s1, s2);
            if (pub) st_rlx128(st1p, ms, epoch, ms, epoch);
        }
        mbar_wait(mb + MB_R * 8);
        const uint32_t la = kb + ((lane >> 3) & 1) * 512 + (lane >> 4) * 128 + (lane & 7) * 16;
        uint32_t kp[5][2], b0[4], b1[4], b2[4], b3[4];
        auto mm2 = [&](int t) {
            float a0[4] = {0.f, 0.f, 0.f, 0.f}, a1[4] = {0.f, 0.f, 0.f, 0.f};
            mma_f16(a0, Af[0], b0[0], b0[1]); mma_f16(a1, Af[0], b2[0], b2[1]); mma_f16(a0, Af[1], b0[2], b0[3]); mma_f16(a1, Af[1], b2[2], b2[3]);
            mma_f16(a0, Af[2], b1[0], b1[1]); mma_f16(a1, Af[2], b3[0], b3[1]); mma_f16(a0, Af[3], b1[2], b1[3]); mma_f16(a1, Af[3], b3[2], b3[3]);
            kp[t][0] = pack_f16(a0[1], a0[0]); kp[t][1] = pack_f16(a0[3], a0[2]); kp[t + 1][0] = pack_f16(a1[1], a1[0]); kp[t + 1][1] = pack_f16(a1[3], a1[2]);
        };
        cmul(sr, si, sr, si, z1r, z1i);
        {
            const H2C h4 = splat(z4r, z4i);
            expand8(kl, kl + 512, sr, si, z1r, z1i, z2r, z2i, h4);
            cmul(sr, si, sr, si, hr, hi_);
            expand8(kl + 1024, kl + 1536, sr, si, z1r, z1i, z2r, z2i, h4);
        }
        __syncwarp();
        ldsm4t(b0, la); ldsm4t(b1, la + 256); ldsm4t(b2, la + 1024); ldsm4t(b3, la + 1280);
        cmul(z1r, z1i, z1r, z1i, hr, hi_);
        cmul(sr, si, sr, si, z1r, z1i);
        expand8(kl, kl + 512, sr, si, z2r, z2i, z4r, z4i, splat(hr, hi_));
        mm2(0);
        STAMP(3);
        if (warp < 16) {
            const uint4* sp = &g_s.st1[(256 * q + ta) * 2];
            mbar_wait(mb + MB_T * 8);
            {
                const uint32_t xt = sb + SM_XTL + ta * 80;
                const uint4 a4 = lds128(xt + cq * 16), b4 = lds128(xt + cq * 16 + 640);
                xa[0] = a4.x; xa[1] = a4.y; xa[2] = a4.z; xa[3] = a4.w; xa[4] = lds32(xt + 64 + cq * 4);
                xb[0] = b4.x; xb[1] = b4.y; xb[2] = b4.z; xb[3] = b4.w; xb[4] = lds32(xt + 704 + cq * 4);
            }
            uint2 sa, sc; int n = 0;
            do { sa = ld_rlx64(sp); sc = ld_rlx64(sp + 16); } while ((sa.y != epoch || sc.y != epoch) && ++n < SPIN_LIMIT);
            STAMP(4);
            const uint32_t ra = rsplit(rcpf(bf_hi(sa.x))), rc = rsplit(rcpf(bf_hi(sc.x)));
            const uint32_t ma = __byte_perm(sa.x, 0, 0x1010), mc = __byte_perm(sc.x, 0, 0x1010);
            if (cq < 2) sts64(sb + SM_ST + ta * 8 + cq * 64, cq ? mc : ma, cq ? rc : ra);
            const uint32_t rha = __byte_perm(ra, 0, 0x1010), rla = __byte_perm(ra, 0, 0x3232), rhc = __byte_perm(rc, 0, 0x1010), rlc = __byte_perm(rc, 0, 0x3232);
            uint32_t va[5], vc[5];
#pragma unroll
            for (int i = 0; i < 5; i++) {
                va[i] = norm2(xa[i], ma, rha, rla); va[i] = pack_f16(bf_lo(va[i]), bf_hi(va[i]));
                vc[i] = norm2(xb[i], mc, rhc, rlc); vc[i] = pack_f16(bf_lo(vc[i]), bf_hi(vc[i]));
            }
            const int d4 = 2 * (lane >> 3) + (lane & 1), d1_ = lane & 7;
            const uint32_t a4 = sb + warp * 32 + (d4 == q ? SM_U + 128 + q * UP + ((lane & 7) >> 1) * US : SM_XT + d4 * YP + ((lane & 7) >> 1) * YS);
            const uint32_t a1 = sb + warp * 32 + (d1_ == q ? SM_U + 128 + q * UP + 4 * US : SM_XT + d1_ * YP + 4 * YS) + (lane & 8) * 2;
            stsm4t(a4, va[0], va[1], va[2], va[3]); stsm4t(a4 + 16, vc[0], vc[1], vc[2], vc[3]); stsm2t(a1, va[4], vc[4]);
        }
        asm volatile("fence.proxy.async.shared::cta;" ::: "memory");
        bar_arrive(13, 736);
        STAMP(5);
        csq(z1r, z1i, z1r, z1i);
        cmul(sr, si, sr, si, z1r, z1i);
        csq(z2r, z2i, hr, hi_);
        expand8(kl + 1024, kl + 1536, sr, si, z4r, z4i, hr, hi_, splat(z2r, z2i));
        __syncwarp();
        ldsm4t(b0, la); ldsm4t(b1, la + 256); ldsm4t(b2, la + 1024); ldsm4t(b3, la + 1280);
        csq(z1r, z1i, z1r, z1i);
        cmul(sr, si, sr, si, z1r, z1i);
        csq(z4r, z4i, z2r, z2i);
        expand8(kl, kl + 512, sr, si, hr, hi_, z2r, z2i, splat(z4r, z4i));
        mm2(2);
        __syncwarp();
        ldsm4t(b0, la); ldsm4t(b1, la + 256);
#pragma unroll
        for (int t = 0; t < 4; t++) sts64(kb + lane * 8 + 1024 + t * 256, kp[t][0], kp[t][1]);
        {
            float a0[4] = {0.f, 0.f, 0.f, 0.f}, a1[4] = {0.f, 0.f, 0.f, 0.f};
            mma_f16(a0, Af[0], b0[0], b0[1]); mma_f16(a1, Af[1], b0[2], b0[3]); mma_f16(a0, Af[2], b1[0], b1[1]); mma_f16(a1, Af[3], b1[2], b1[3]);
            sts64(kb + lane * 8 + 2048, pack_f16(a0[1] + a1[1], a0[0] + a1[0]), pack_f16(a0[3] + a1[3], a0[2] + a1[2]));
        }
        bar_sync(1 + k, 128);
        const uint4 m01 = lds128(sb + SM_KG + k * 32), m23 = lds128(sb + SM_KG + k * 32 + 16);
        const unsigned Em = max(max(m01.x, m01.z), max(m23.x, m23.z));
        const float f0 = __uint_as_float(max((int)(127 + m01.x - Em), 0) << 23), f1 = __uint_as_float(max((int)(127 + m01.z - Em), 0) << 23),
                    f2 = __uint_as_float(max((int)(127 + m23.x - Em), 0) << 23), f3 = __uint_as_float(max((int)(127 + m23.z - Em), 0) << 23);
        const uint32_t r0 = pack_f16(f0, f0), r1 = pack_f16(f1, f1), r2 = pack_f16(f2, f2), r3 = pack_f16(f3, f3);
        const uint32_t ra = fb + lane * 8 + wq * 256 + 1024;
        const uint2 p0 = lds64(ra), p1 = lds64(ra + 3072), p2 = lds64(ra + 6144), p3 = lds64(ra + 9216);
        uint32_t w0 = hadd2(hfma2(p0.x, r0, hmul2(p1.x, r1)), hfma2(p2.x, r2, hmul2(p3.x, r3)));
        uint32_t w1 = hadd2(hfma2(p0.y, r0, hmul2(p1.y, r1)), hfma2(p2.y, r2, hmul2(p3.y, r3)));
        const bool last = lane == 31;
        if (wq < 2) {
            const uint32_t rc = fb + lane * 8 + wq * 4 + 2048;
            const uint32_t w4 = hmul2(hadd2(hfma2(lds32(rc), r0, hmul2(lds32(rc + 3072), r1)), hfma2(lds32(rc + 6144), r2, hmul2(lds32(rc + 9216), r3))), 0x18001800u);
            const uint32_t ph = pf + (P_H7 + 16 * wq) + (g & 1) * (2 * P_HS) + cq * 64 + (g >> 1) * 4;
            put16(ph, w4 >> 16); put16(ph + 32, w4);
            const uint32_t pa = pn + (4 + 512 * wq) + lane * 8;
            sts16(pa, w0 >> 16); sts32(pa + 4, w0); sts16(pa + 10, w0);
            sts16(pa + 256, w1 >> 16); sts32(pa + 260, w1); sts16(pa + 266, w1);
            if (last) {
                sts32(sb + SM_SC + k * 4, Em * 0x00800080u);
                put16(wq ? pa + 264 : pn,
                      wq ? w1 : pack_f16(((float)(int)m01.y * f0 + (float)(int)m01.w * f1 + (float)(int)m23.y * f2 + (float)(int)m23.w * f3) * (1.f / 16777216.f), 0.f));
            }
        } else if (wq == 2) {
            const uint32_t pa = pn + 258 * 4 + (cq & 1) * 16 + (cq >> 1) * 512 + g * 32;
            if (last) { put16(pf, hmul2(w1, 0x18001800u)); w1 = hadd2(w1, hneg2(__byte_perm(w1, 0, 0x1010))); }
            const uint32_t b0 = __byte_perm(w0, 0, 0x1010), b1 = __byte_perm(w1, 0, 0x1010);
            sts16(pa, w0 >> 16); sts32(pa + 4, w0); sts64(pa + 8, b0, b0); sts16(pa + 18, w0);
            sts16(pa + 256, w1 >> 16); sts32(pa + 260, w1); sts64(pa + 264, b1, b1); sts16(pa + 274, w1);
        } else {
            const uint32_t pa = pf + ((g & 1) ? 3 * P_GS : P_GS) + cq * 32 + (g >> 1) * 4;
            const uint32_t pb = pa + ((g & 1) ? 4 - 3 * P_GS : P_GS);
            w0 = hmul2(w0, 0x18001800u); w1 = hmul2(w1, 0x18001800u);
            put16(pa, w0 >> 16); put16(pb, w0); put16(pa + 16, w1 >> 16); put16(pb + 16, w1);
            if (last) put16(pf + P_H7 + P_HS, w1);
        }
        bar_sync(1 + k, 128);
    }
    STAMP(6);

    asm volatile("barrier.cluster.wait.aligned;" ::: "memory");
    mbar_wait(mb + (MB_X + min(k, nslot - 1)) * 8);
    STAMP(7);
    if (k < nslot) {
        const int role = (wq + k) & 3;
        const uint32_t ub = sb + SM_U + k * US + 128;
        if (role) {
            const int r = (3 - role) * 32 + lane;
            const uint32_t a1 = ub + (r & 3) * (2 * UP) + (r >> 2) * 16, a0 = a1 + ((r & 3) ? -2 * UP : 6 * UP - 16);
            const uint4 q0 = lds128(a0), q1 = lds128(a0 + UP), q2 = lds128(a1), q3 = lds128(a1 + UP);
            const uint32_t U[16] = {q0.x, q0.y, q0.z, q0.w, q1.x, q1.y, q1.z, q1.w, q2.x, q2.y, q2.z, q2.w, q3.x, q3.y, q3.z, q3.w};
            uint32_t V[14], Q[14], R4[12], T[8];
#pragma unroll
            for (int i = 2; i < 14; i++) { V[i] = __byte_perm(U[i], U[i + 1], 0x5432); Q[i] = hadd2(U[i], V[i]); }
#pragma unroll
            for (int i = 2; i < 12; i++) R4[i] = hadd2(Q[i], Q[i + 1]);
            const uint32_t rb = fb + r * 16;
#pragma unroll
            for (int i = 0; i < 8; i++) T[i] = hadd2(V[5 + i], Q[6 + i]);
            sts128(rb + F_E3, T[0], T[1], T[2], T[3]); sts128(rb + F_O3 + 16, T[4], T[5], T[6], T[7]);
#pragma unroll
            for (int i = 0; i < 8; i++) T[i] = hadd2(R4[3 + i], U[5 + i]);
            sts128(rb + F_O5, T[0], T[1], T[2], T[3]); sts128(rb + F_E5, T[4], T[5], T[6], T[7]);
            if (role != 1) {
#pragma unroll
                for (int i = 0; i < 8; i++) T[i] = hadd2(T[i], hadd2(V[2 + i], V[5 + i]));
                sts128(rb + F_E7, T[0], T[1], T[2], T[3]); sts128(rb + F_O7, T[4], T[5], T[6], T[7]);
#pragma unroll
                for (int i = 0; i < 8; i++) T[i] = hadd2(R4[2 + i], hadd2(R4[4 + i], U[6 + i]));
                sts128(rb + F_O9, T[0], T[1], T[2], T[3]); sts128(rb + F_E9 + 16, T[4], T[5], T[6], T[7]);
                sts128(rb + F_E2, Q[6], Q[7], Q[8], Q[9]); sts128(rb + F_O2, Q[10], Q[11], Q[12], Q[13]);
            }
        } else if (lane < 8) {
            uint32_t s = 0;
#pragma unroll 1
            for (int t = 1526 + lane; t < 1531 + lane; t++) s = hadd2(s, lds16(ub + ((t >> 3) & 7) * UP + (t >> 6) * 16 + (t & 7) * 2));
            sts16(fb + F_O5 + 96 * 16 + lane * 2, s);
            sts32(fb + (lane < 4 ? F_O3 : F_E9 - 16) + lane * 4, 0);
        }
        bar_sync(1 + k, 128);
        float acc[4][4];
        uint32_t Q[4][4];
        {
            const int h = role & 1, part = role >> 1;
            const uint32_t po = pf + (g - 2 * cq) * 4;
            float fa[7][4];
#pragma unroll
            for (int a = 0; a < 7; a++) fa[a][0] = fa[a][1] = fa[a][2] = fa[a][3] = 0.f;
            uint32_t B[3][4];
            Q[0][2] = zero;
#pragma unroll 1
            for (int s = 2 * part + 1; s >= 2 * part; s--) {
#pragma unroll
                for (int i = 0; i < 3; i++) { Q[i][0] = lds32(po + s * P_GS + i * 64); Q[i][1] = lds32(po + s * P_GS + (i * 64 + 32)); }
                const uint32_t ba = fb + lane * 16 + ((s & 1) * F_E3 + (part == h ? 0 : F_O5 + h * 16));
#pragma unroll
                for (int i = 0; i < 3; i++) ldsm4t(B[i], ba + i * 512);
#pragma unroll
                for (int i = 0; i < 3; i++) { Q[i][3] = CP(Q[i][0]); if (i) Q[i][2] = CP(Q[i - 1][1]); }
#pragma unroll
                for (int dl = 0; dl < 3; dl++)
#pragma unroll
                    for (int ap = 0; ap < 6 - dl; ap++) mma_f16(fa[ap + 1 + dl], Q[dl], B[ap >> 1][2 * (ap & 1)], B[ap >> 1][2 * (ap & 1) + 1]);
            }
#pragma unroll 1
            for (int s = role; s == 1; s++) {
                ldsm2t(B[0][0], B[0][1], fb + ((lane & 15) == 15 ? F_O5 : F_O3));
#pragma unroll
                for (int dl = 0; dl < 3; dl++) mma_f16(fa[dl], Q[dl], B[0][0], B[0][1]);
            }
#pragma unroll 1
            for (int s = part; s <= 2 * part; s++) {
#pragma unroll
                for (int i = 0; i < 4; i++) { Q[i][0] = lds32(po + s * P_HS + (P_H7 + i * 64)); Q[i][1] = lds32(po + s * P_HS + (P_H7 + i * 64 + 32)); }
                const uint32_t ba = fb + lane * 16 + (F_E7 + s * 1024 + h * F_H);
                ldsm4t(B[0], ba); ldsm4t(B[1], ba + 512);
#pragma unroll
                for (int i = 0; i < 4; i++) { Q[i][3] = CP(Q[i][0]); if (i) Q[i][2] = CP(Q[i - 1][1]); }
#pragma unroll
                for (int dl = 0; dl < 4; dl++) {
#pragma unroll
                    for (int ap = 0; ap < 4 - dl; ap++) mma_f16(fa[ap + 3 + dl], Q[dl], B[ap >> 1][2 * (ap & 1)], B[ap >> 1][2 * (ap & 1) + 1]);
                    if (s == 1) break;
                }
            }
            const uint32_t da = fb + role * 2048 + (lane & 3) * 512 + (((lane >> 2) ^ ((lane & 3) * 2)) << 4);
            bar_sync(1 + k, 128);
            stsm4(da, 0u, 0u, pack_f16(fa[0][0], fa[0][1]), pack_f16(fa[0][2], fa[0][3]));
#pragma unroll
            for (int i = 1; i < 4; i++)
                stsm4(da + i * 128, pack_f16(fa[2 * i - 1][0], fa[2 * i - 1][1]), pack_f16(fa[2 * i - 1][2], fa[2 * i - 1][3]),
                      pack_f16(fa[2 * i][0], fa[2 * i][1]), pack_f16(fa[2 * i][2], fa[2 * i][3]));
            Q[0][0] = (g == 2 * cq) ? 0x6000u : ((g == 2 * cq + 1) ? 0x60000000u : 0u);
            Q[0][1] = 0; Q[0][3] = CP(Q[0][0]);
            const uint32_t ra = fb + (lane >> 3) * 2048 + wq * 512 + (((lane & 7) ^ (wq * 2)) << 4);
            bar_sync(1 + k, 128);
#pragma unroll
            for (int i = 0; i < 4; i++) {
                ldsm4(B[0], ra + i * 128);
                acc[i][0] = acc[i][1] = acc[i][2] = acc[i][3] = 0.f;
                mma_f16(acc[i], Q[0], hadd2(B[0][0], B[0][2]), hadd2(B[0][1], B[0][3]));
            }
        }
        if (role) bar_arrive(6 + k, 128);
        else {
            bar_sync(6 + k, 128);
            if (lane == 0) { asm volatile("fence.proxy.async.shared::cta;" ::: "memory"); tma2d(fb, &tmD, 72 * q, 320 * c + 64 * k, mb + MB_W2 * 8); }
            __syncwarp();
        }
        STAMP(8);
        {
            uint32_t pp = pn + (16 * (wq - 3) + g - 2 * cq) * 4;
            uint32_t dlo = (((ub + 6 * UP) & 0x3FFFF) >> 4) | ((UP >> 4) << 16);
            Q[3][1] = 0;
#pragma unroll 1
            for (int dl = 0; dl < 9; dl++) {
                Q[0][2] = CP(Q[3][1]);
#pragma unroll
                for (int i = 0; i < 4; i++) { Q[i][0] = lds32(pp + i * 64); Q[i][1] = lds32(pp + i * 64 + 32); }
#pragma unroll
                for (int i = 0; i < 4; i++) { Q[i][3] = CP(Q[i][0]); if (i) Q[i][2] = CP(Q[i - 1][1]); }
                asm volatile("wgmma.fence.sync.aligned;" ::: "memory");
#pragma unroll
                for (int i = 0; i < 4; i++) wgmma32(acc, Q[i], dlo - i * (2 * UP >> 4));
                asm volatile("wgmma.commit_group.sync.aligned;" ::: "memory");
                pp += 256; dlo -= 1;
                asm volatile("wgmma.wait_group.sync.aligned 0;" ::: "memory");
            }
        }
        const uint32_t inv = lds32(sb + SM_SC + k * 4);
        const uint32_t yself = sb + SM_XT + q * YP + k * YS, ys = ub + 2 * wq * UP;
        bar_sync(1 + k, 128);
#pragma unroll
        for (int e = 0; e < 2; e++)
            stsm4t((2 * wq + e == q ? yself : ys + e * UP) + lane * 16,
                   bmul2(pack_bf16(acc[0][2 * e], acc[0][2 * e + 1]), inv), bmul2(pack_bf16(acc[1][2 * e], acc[1][2 * e + 1]), inv),
                   bmul2(pack_bf16(acc[2][2 * e], acc[2][2 * e + 1]), inv), bmul2(pack_bf16(acc[3][2 * e], acc[3][2 * e + 1]), inv));
        asm volatile("fence.proxy.async.shared::cta;" ::: "memory");
        __syncwarp();
        if (lane < 2 && 2 * wq + lane != q) {
            const uint32_t rb_ = mapa(sb, 2 * wq + lane);
            asm volatile("cp.async.bulk.shared::cluster.shared::cta.mbarrier::complete_tx::bytes [%0], [%1], %2, [%3];"
                         :: "r"(rb_ + SM_XT + q * YP + k * YS), "r"(ys + lane * UP), "r"(512), "r"(rb_ + SM_MB + MB_Y * 8) : "memory");
        }
        if (lane == 2) asm volatile("mbarrier.arrive.shared::cta.b64 _, [%0];" :: "r"(mb + MB_Y * 8) : "memory");
        __syncwarp();
    }
    STAMP(9);
    uint32_t ha[5], hb[5];
    if (warp < 16) {
        const uint2 sa = lds64(sb + SM_ST + ta * 8), sc = lds64(sb + SM_ST + ta * 8 + 64);
        const uint32_t ma = sa.x, mbb = sc.x;
        const uint32_t rha = __byte_perm(sa.y, 0, 0x1010), rla = __byte_perm(sa.y, 0, 0x3232), rhb = __byte_perm(sc.y, 0, 0x1010), rlb = __byte_perm(sc.y, 0, 0x3232);
        const uint4 dk = lds128(sb + SM_DW + cq * 16), wk = lds128(sb + SM_DW + 80 + cq * 16);
        const uint32_t d1 = lds32(sb + SM_DW + 64 + cq * 4), w1 = lds32(sb + SM_DW + 144 + cq * 4);
        const uint32_t dkv[5] = {dk.x, dk.y, dk.z, dk.w, d1};
        uint32_t sel[5] = {wk.x, wk.y, wk.z, wk.w, w1};
#pragma unroll
        for (int i = 0; i < 5; i++) {
            ha[i] = bmul2(norm2(xa[i], ma, rha, rla), dkv[i]); hb[i] = bmul2(norm2(xb[i], mbb, rhb, rlb), dkv[i]);
            if (!(g & 1)) sel[i] = 0x3F803F80u;
        }
        const uint32_t y4 = sb + SM_XT + warp * 32 + (2 * (lane >> 3) + (lane & 1)) * YP + ((lane & 7) >> 1) * YS;
        const uint32_t y1 = sb + SM_XT + warp * 32 + (lane & 7) * YP + 4 * YS + (lane & 8) * 2;
        mbar_wait(mb + MB_Y * 8);
        STAMP(10);
        float ca[4] = {0.f, 0.f, 0.f, 0.f}, cb[4] = {0.f, 0.f, 0.f, 0.f};
        {
            uint32_t ya[4], yb[4], yc, yd;
            ldsm4t(ya, y4); ldsm4t(yb, y4 + 16); ldsm2t(yc, yd, y1);
#pragma unroll
            for (int i = 0; i < 4; i++) { ha[i] = badd2(xa[i], badd2(ya[i], ha[i])); hb[i] = badd2(xb[i], badd2(yb[i], hb[i])); }
            ha[4] = badd2(xa[4], badd2(yc, ha[4])); hb[4] = badd2(xb[4], badd2(yd, hb[4]));
        }
        if (nslot != 5) {
            ha[4] = hb[4] = 0;
            if (cq >= 2) ha[0] = ha[1] = ha[2] = ha[3] = hb[0] = hb[1] = hb[2] = hb[3] = 0;
        }
#pragma unroll
        for (int i = 0; i < 5; i++) { mma_bf16_k8(ca, ha[i], sel[i], ha[i]); mma_bf16_k8(cb, hb[i], sel[i], hb[i]); }
        const float oa = __shfl_xor_sync(~0u, (g & 1) ? ca[2] : ca[3], 4), ob = __shfl_xor_sync(~0u, (g & 1) ? cb[2] : cb[3], 4);
        if (cq == (g >> 1)) {
            float4* ap = &g_s.acc[256 * q + ta];
            const bool od = g & 1;
            asm volatile("red.relaxed.gpu.global.add.v4.f32 [%0], {%1,%2,%3,%4};" :: "l"(ap), "f"(od ? oa : ca[2]), "f"(od ? ca[1] : ca[0]), "f"(od ? ca[3] : oa), "f"(1.0f) : "memory");
            asm volatile("red.relaxed.gpu.global.add.v4.f32 [%0], {%1,%2,%3,%4};" :: "l"(ap + 8), "f"(od ? ob : cb[2]), "f"(od ? cb[1] : cb[0]), "f"(od ? cb[3] : ob), "f"(1.0f) : "memory");
        }
        const uint32_t hta = sb + SM_HT + ta * 80;
        sts128(hta + cq * 16, ha[0], ha[1], ha[2], ha[3]); sts32(hta + 64 + cq * 4, ha[4]);
        sts128(hta + cq * 16 + 640, hb[0], hb[1], hb[2], hb[3]); sts32(hta + 704 + cq * 4, hb[4]);
        STAMP(11);
    }
    const int kq = warp / 5, mt = warp - 5 * kq;
    const int mi = lane >> 3, mr = lane & 7;
    const unsigned tk = (unsigned)tid / 72u, ck = tid - tk * 72;
    uint32_t A[9][4];
    const uint32_t par = (epoch & 1) ? 0x40004000u : 0u;
    if (warp < 8) {
        const float wsum = ldsf(sb + SM_SC + 24);
        const uint32_t idx = 2047 - (64 * (tid >> 3) + 8 * q + (tid & 7));
        uint4 s; int n = 0;
        do { s = ld_rlx128(&g_s.acc[256 * q + tid]); } while (__uint_as_float(s.w) != (float)NCL && ++n < SPIN_LIMIT);
        const uint32_t ms = ln_stats(__uint_as_float(s.x), __uint_as_float(s.y));
        const float rs = rcpf(bf_hi(ms));
        const uint32_t rb = pack_bf16(0.f, fmaf(-bf_lo(ms), wsum, __uint_as_float(s.z)) * rs);
        const uint32_t key = (((rb ^ (((int)rb >> 31) | 0x80000000u)) >> 16) << 11) | idx;
        sts32(sb + SM_KEY + tid * 4, key);
        __syncwarp();
        const uint32_t rank = rank4<8>(sb + SM_KEY + warp * 128, key);
        if (rank < 8) sts32(sb + SM_CAND + warp * 32 + rank * 4, key);
        sts64(sb + SM_ST + tid * 8, __byte_perm(ms, 0, 0x1010), rsplit(rs));
    }
    if (warp < 16) {
        bar_sync(12, 512);
        if (warp < 8) {
            const uint32_t mk = lds32(sb + SM_CAND + (tid >> 2) * 4);
            uint32_t rank = rank4<4>(sb + SM_CAND + cq * 64, mk);
            rank += __shfl_xor_sync(~0u, rank, 1); rank += __shfl_xor_sync(~0u, rank, 2);
            if (rank < 8) {
                const uint32_t pk0 = mapa(sb, 2 * cq), pk1 = mapa(sb, 2 * cq + 1);
                st_async1(pk0 + (SM_RK + q * 32) + rank * 4, mk, pk0 + (SM_MB + MB_KEY * 8));
                st_async1(pk1 + (SM_RK + q * 32) + rank * 4, mk, pk1 + (SM_MB + MB_KEY * 8));
                const int t = ((~mk >> 3) & 0xF8) | (~mk & 7);
                const uint2 sv = lds64(sb + SM_ST + t * 8);
                const uint4 hv = lds128(sb + SM_HT + t * 80 + cq * 16);
                const uint32_t h4 = lds32(sb + SM_HT + t * 80 + 64 + cq * 4);
                const uint32_t rr = bmul2(sv.y, 0x3C803C80u), rh = __byte_perm(rr, 0, 0x1010), rl = __byte_perm(rr, 0, 0x3232);
                uint4* const dp = &g_s.cand[(q * 8 * NCL + c) * 6 + cq] + rank * (NCL * 6);
                st_rlx128(dp, (norm2(hv.x, sv.x, rh, rl) & 0xBFFFBFFFu) | par, (norm2(hv.y, sv.x, rh, rl) & 0xBFFFBFFFu) | par,
                          (norm2(hv.z, sv.x, rh, rl) & 0xBFFFBFFFu) | par, (norm2(hv.w, sv.x, rh, rl) & 0xBFFFBFFFu) | par);
                asm volatile("st.relaxed.gpu.global.u32 [%0], %1;" :: "l"((char*)dp + 64 - cq * 12), "r"((norm2(h4, sv.x, rh, rl) & 0xBFFFBFFFu) | par) : "memory");
            }
            __syncwarp();
        }
        {
            const uint2 sa = lds64(sb + SM_ST + ta * 8), sbb = lds64(sb + SM_ST + ta * 8 + 64);
            const uint32_t rha = __byte_perm(sa.y, 0, 0x1010), rla = __byte_perm(sa.y, 0, 0x3232);
            const uint32_t rhb = __byte_perm(sbb.y, 0, 0x1010), rlb = __byte_perm(sbb.y, 0, 0x3232);
#pragma unroll
            for (int i = 0; i < 5; i++) { ha[i] = badd2(ha[i], norm2(ha[i], sa.x, rha, rla)); hb[i] = badd2(hb[i], norm2(hb[i], sbb.x, rhb, rlb)); }
            const uint32_t ota = sb + SM_XT + ta * 80;
            sts128(ota + cq * 16, ha[0], ha[1], ha[2], ha[3]); sts32(ota + 64 + cq * 4, ha[4]);
            sts128(ota + cq * 16 + 640, hb[0], hb[1], hb[2], hb[3]); sts32(ota + 704 + cq * 4, hb[4]);
            asm volatile("fence.proxy.async.shared::cta;" ::: "memory");
            bar_arrive(14, 544);
        }
        if (warp < 8) {
            mbar_wait(mb + MB_KEY * 8);
            const uint32_t mk = lds32(sb + SM_RK + (tid >> 2) * 4);
            uint32_t rank = rank4<4>(sb + SM_RK + cq * 64, mk);
            rank += __shfl_xor_sync(~0u, rank, 1); rank += __shfl_xor_sync(~0u, rank, 2);
            if (rank < 8) sts64(sb + SM_SEL + rank * 8, mk, (tid >> 2) * 90);
        }
    }
    const uint4* const gp0 = &g_s.cand[ck / 5u + ck];
    bar_sync(11, 640);
    STAMP(12);

    {
        const uint4* gp = gp0 + lds32(sb + SM_SEL + 4 + (tk & 7) * 8);
        uint4 hv = ld_rlx128(gp);
    mbar_wait(mb + MB_W1 * 8);
    {
        const uint32_t aa = sb + (mi & 1) * SM_WU + (8 * (mi >> 1) + mr) * 80 + (144 * 80 * kq + mt * 16);
#pragma unroll
        for (int s = 0; s < 9; s++) ldsm4t(A[s], aa + s * 1280);
    }
        if (warp < 18) {
            int n = 0;
            while ((((hv.x ^ par) | (hv.y ^ par) | (hv.z ^ par) | (hv.w ^ par)) & 0x40004000u) && ++n < SPIN_LIMIT) hv = ld_rlx128(gp);
            sts128(sb + SM_XS + tk * 16 + tid * 16, hv.x ^ par, hv.y ^ par, hv.z ^ par, hv.w ^ par);
        } else if (warp == 19 && lane < 20) {
            const uint32_t t = ~lds32(sb + SM_SEL + q * 8) & 2047;
            uint32_t v; asm volatile("ld.shared::cluster.u32 %0, [%1];" : "=r"(v) : "r"(mapa(sb + SM_HT + ((t >> 6) * 8 + (t & 7)) * 80 + lane * 4, (t >> 3) & 7)) : "memory");
            sts32(sb + SM_HS + lane * 4, v);
        }
    }
    bar_sync(11, 640);
    STAMP(13);
    {
        float c0[4] = {0.f, 0.f, 0.f, 0.f}, c1[4] = {0.f, 0.f, 0.f, 0.f}, c2[4] = {0.f, 0.f, 0.f, 0.f};
        const uint32_t ba = sb + SM_XS + mr * 1168 + mi * 16 + 288 * kq;
        uint32_t b[5][4];
#pragma unroll
        for (int s = 0; s < 5; s++) ldsm4(b[s], ba + s * 64);
        mma_bf16(c0, A[0][0], A[0][1], A[0][2], A[0][3], b[0][0], b[0][1]);
        mma_bf16(c1, A[1][0], A[1][1], A[1][2], A[1][3], b[0][2], b[0][3]);
        mma_bf16(c2, A[2][0], A[2][1], A[2][2], A[2][3], b[1][0], b[1][1]);
        mma_bf16(c0, A[3][0], A[3][1], A[3][2], A[3][3], b[1][2], b[1][3]);
        mma_bf16(c1, A[4][0], A[4][1], A[4][2], A[4][3], b[2][0], b[2][1]);
        mma_bf16(c2, A[5][0], A[5][1], A[5][2], A[5][3], b[2][2], b[2][3]);
        mma_bf16(c0, A[6][0], A[6][1], A[6][2], A[6][3], b[3][0], b[3][1]);
        mma_bf16(c1, A[7][0], A[7][1], A[7][2], A[7][3], b[3][2], b[3][3]);
        mma_bf16(c2, A[8][0], A[8][1], A[8][2], A[8][3], b[4][0], b[4][1]);
        sts128f(sb + SM_RED + tid * 16, c0[0] + c1[0] + c2[0], c0[1] + c1[1] + c2[1], c0[2] + c1[2] + c2[2], c0[3] + c1[3] + c2[3]);
    }
    bar_sync(1 + mt, 128);
    if (mt < nslot) {
        const uint32_t ra = sb + SM_RED + mt * 512 + lane * 16;
        const float4 p0 = lds128f(ra), p1 = lds128f(ra + 2560), p2 = lds128f(ra + 5120), p3 = lds128f(ra + 7680);
        const float g0 = bfr(((p0.x + p1.x) + (p2.x + p3.x)) * 64.f), g1 = bfr(((p0.y + p1.y) + (p2.y + p3.y)) * 64.f);
        const uint32_t sg = pack_bf16(g0 * rcpf(1.f + ex2f(g0 * -1.4426950408889634f)), g1 * rcpf(1.f + ex2f(g1 * -1.4426950408889634f)));
        const uint32_t gu = bmul2(sg, pack_bf16(((p0.z + p1.z) + (p2.z + p3.z)) * 64.f, ((p0.w + p1.w) + (p2.w + p3.w)) * 64.f));
#pragma unroll
        for (int i = 0; i < 2; i++) {
            const uint32_t rb_ = mapa(sb, 2 * kq + i);
            st_async1(rb_ + (SM_GU + (q * nslot + mt) * 128) + lane * 4, gu, rb_ + (SM_MB + MB_GU * 8));
        }
    }
    mbar_wait(mb + MB_W2 * 8);
    {
        const uint32_t aa = sb + (8 * (mi >> 1) + mr) * 144 + (mi & 1) * 16 + (SM_FAR + 2304 * kq + mt * 32);
#pragma unroll
        for (int s = 0; s < 5; s++) ldsm4t(A[s], aa + s * FAR_SZ);
    }
    {
        mbar_wait(mb + MB_GU * 8);
        float c0[4] = {0.f, 0.f, 0.f, 0.f}, c1[4] = {0.f, 0.f, 0.f, 0.f};
        const uint32_t ba = sb + (SM_GU + 256 * kq) + (lane & 15) * 16 + (lane >> 4) * 1024;
        uint32_t b[3][4];
#pragma unroll
        for (int s = 0; s < 3; s++) ldsm4t(b[s], ba + s * 2048);
        mma_bf16(c0, A[0][0], A[0][1], A[0][2], A[0][3], b[0][0], b[0][1]);
        mma_bf16(c1, A[1][0], A[1][1], A[1][2], A[1][3], b[0][2], b[0][3]);
        if (nslot == 5) {
            mma_bf16(c0, A[2][0], A[2][1], A[2][2], A[2][3], b[1][0], b[1][1]);
            mma_bf16(c1, A[3][0], A[3][1], A[3][2], A[3][3], b[1][2], b[1][3]);
            mma_bf16(c0, A[4][0], A[4][1], A[4][2], A[4][3], b[2][0], b[2][1]);
        }
        sts128f(sb + SM_RED2 + tid * 16, c0[0] + c1[0], c0[1] + c1[1], c0[2] + c1[2], c0[3] + c1[3]);
    }
    bar_sync(6 + mt, 128);
    STAMP(14);
    {
        const int col = lane & 15, tp = lane >> 4;
        const uint32_t a = sb + (SM_RED2 + mt * 512 + kq * 16) + (col & 7) * 64 + (col >> 3) * 8 + tp * 4;
        const float s = (ldsf(a) + ldsf(a + 2560)) + (ldsf(a + 5120) + ldsf(a + 7680));
        if (mt * 16 + col < 72) st_rlx64(&g_s.part[((2 * kq + tp) * NCL + c) * D_ + 72 * q + mt * 16 + col], __float_as_uint(s), epoch);
    }
    if (warp < 2 * nslot) {
        const int hf = lane & 1, cp = min(lane >> 1, NCL - 1), ch = 4 * warp + 2 * hf;
        const uint2* pp = &g_s.part[(q * NCL + cp) * D_ + d0 + ch];
        const uint32_t key = lds32(sb + SM_SEL + q * 8), k16 = key << 5;
        const float r = __uint_as_float((k16 ^ (~((int)k16 >> 31) | 0x80000000u)) & 0xFFFF0000u);
        const uint32_t sig = pack_bf16(rcpf(1.f + ex2f(r * -1.4426950408889634f)), rcpf(1.f + ex2f(r * -1.4426950408889634f)));
        const uint32_t hs = lds32(sb + SM_HS + ch * 2), hn = bmul2(lds32(sb + SM_XS + q * 1168 + (d0 + ch) * 2), 0x42804280u);
        uint32_t* const op = (uint32_t*)(prm.out + (~key & 2047) * D_ + d0 + ch);
        asm volatile("{ .reg .pred p, q; .reg .u32 n; mov.u32 n, 0;\n"
                     "W_%=: mbarrier.try_wait.parity.acquire.cluster.shared::cta.b64 p, [%0], 0; add.u32 n, n, 1; setp.lt.and.u32 q, n, 65536, !p; @q bra W_%=; }" :: "r"(mb + MB_OUT * 8) : "memory");
        uint4 v; int n = 0;
        do { v = ld_rlx128(pp); } while ((v.y != epoch || v.w != epoch) && ++n < SPIN_LIMIT);
        float s0 = lane < 30 ? __uint_as_float(v.x) : 0.f, s1 = lane < 30 ? __uint_as_float(v.z) : 0.f;
#pragma unroll
        for (int o = 2; o < 32; o <<= 1) { s0 += __shfl_xor_sync(~0u, s0, o); s1 += __shfl_xor_sync(~0u, s1, o); }
        if (lane < 2) *op = badd2(hs, badd2(hn, bmul2(pack_bf16(s0, s1), sig)));
    }
    STAMP(15);
}

typedef CUresult (*EncodeFn)(CUtensorMap*, CUtensorMapDataType, cuuint32_t, void*, const cuuint64_t*, const cuuint64_t*,
                             const cuuint32_t*, const cuuint32_t*, CUtensorMapInterleave, CUtensorMapSwizzle,
                             CUtensorMapL2promotion, CUtensorMapFloatOOBfill);

void make_map(EncodeFn fn, CUtensorMap* tm, const void* p, int cols, int rows, int bc, int br) {
    cuuint64_t dims[2] = {(cuuint64_t)cols, (cuuint64_t)rows};
    cuuint64_t strides[1] = {(cuuint64_t)cols * 2};
    cuuint32_t box[2] = {(cuuint32_t)bc, (cuuint32_t)br};
    cuuint32_t es[2] = {1, 1};
    fn(tm, CU_TENSOR_MAP_DATA_TYPE_BFLOAT16, 2, const_cast<void*>(p), dims, strides, box, es, CU_TENSOR_MAP_INTERLEAVE_NONE,
       CU_TENSOR_MAP_SWIZZLE_NONE, (CUtensorMapL2promotion)L2PROMO, CU_TENSOR_MAP_FLOAT_OOB_FILL_NONE);
}

void make_map3(EncodeFn fn, CUtensorMap* tm, const void* p) {
    cuuint64_t dims[3] = {(cuuint64_t)D_, 64, 32};
    cuuint64_t strides[2] = {(cuuint64_t)D_ * 2, (cuuint64_t)D_ * 128};
    cuuint32_t box[3] = {40, 8, 32};
    cuuint32_t es[3] = {1, 1, 1};
    fn(tm, CU_TENSOR_MAP_DATA_TYPE_BFLOAT16, 3, const_cast<void*>(p), dims, strides, box, es, CU_TENSOR_MAP_INTERLEAVE_NONE,
       CU_TENSOR_MAP_SWIZZLE_NONE, CU_TENSOR_MAP_L2_PROMOTION_NONE, CU_TENSOR_MAP_FLOAT_OOB_FILL_NONE);
}

}

extern "C" void kernel_launch(void* const* d_in, const int* in_sizes, int n_in, void* d_out, int out_size) {
    (void)in_sizes; (void)n_in; (void)out_size;
    void* fp = nullptr;
    cudaDriverEntryPointQueryResult qr;
    cudaGetDriverEntryPoint("cuTensorMapEncodeTiled", &fp, cudaEnableDefault, &qr);
    EncodeFn fn = (EncodeFn)fp;
    CUtensorMap tmG, tmU, tmD, tmO, tmX;
    make_map3(fn, &tmX, d_in[0]);
    make_map(fn, &tmG, d_in[11], F_, D_, 40, 48);
    make_map(fn, &tmU, d_in[12], F_, D_, 40, 48);
    make_map(fn, &tmD, d_in[13], D_, F_, 72, 64);
    make_map3(fn, &tmO, d_out);
    Params p;
    p.x = (const unsigned short*)d_in[0];
    for (int i = 0; i < 6; i++) p.prm6[i] = (const unsigned short*)d_in[1 + i];
    p.logdt = (const unsigned short*)d_in[7]; p.dskip = (const unsigned short*)d_in[8];
    p.wr = (const unsigned short*)d_in[10];
    for (int i = 0; i < 3; i++) p.w3[i] = (const char*)d_in[11 + i];
    p.out = (__nv_bfloat16*)d_out;
    p.zero = 0;
    cudaGetSymbolAddress((void**)&p.gs, g_s);
    cudaFuncSetAttribute(fused_kernel, cudaFuncAttributeMaxDynamicSharedMemorySize, SM_TOTAL);
    fused_kernel<<<NCTA, NTHR, SM_TOTAL>>>(p, tmG, tmU, tmD, tmO, tmX);
}
```

```cpp
#include <cuda_runtime.h>
#include <cuda_bf16.h>
#include <cuda_fp16.h>
#include <cuda.h>
#include <stdint.h>

namespace {

constexpr int L_ = 2048, D_ = 576, F_ = 4608;
constexpr int NCL = 15, CS = 8, NCTA = NCL * CS, NTHR = 768;
#define PACE_NS 100
#define PRE_N 0
#define PRE_NS 200
#define FIN_DELAY 0
#define RED_DELAY 0
#define NO_OUT 0
#define XSPLIT 3
#define NORM_EARLY 0
#define NEAR_DB 1
#define STREAM_T 0
#define L2PROMO 2
#define GAP_NS 0
#define ROW_DELAY 1
constexpr int SPIN_LIMIT = 1 << 22;

constexpr int SM_WG   = 0;
constexpr int SM_WU   = 46080;
constexpr int YP = 3376, YS = 672;
constexpr int UP = 3376, US = 672;
constexpr int SM_XT   = 92160;
constexpr int SM_U    = SM_XT + 8 * YP;
constexpr int SM_FAR  = SM_U + 8 * UP;
constexpr int FAR_SZ  = 12416;
constexpr int F_E5 = 0, F_O5 = 1536, F_E3 = 3088, F_O3 = 4624, F_E7 = 6176, F_E2 = F_E7 + 1024, F_E9 = F_E7 + 2048,
              F_H = 3088, F_O7 = F_E7 + F_H, F_O2 = F_E2 + F_H, F_O9 = F_E9 + F_H;
constexpr int SM_P    = SM_FAR + 5 * FAR_SZ;
constexpr int PN_SZ = 584 * 4, SM_PN = SM_P + 64 * 4;
constexpr int P_GS = 48 * 4, P_H7 = 192 * 4, P_HS = 72 * 4;
constexpr int PF_SZ = (192 + 216) * 4, SM_PF = SM_PN + 5 * PN_SZ + 32;
constexpr int SM_MISC = SM_PF + 5 * PF_SZ;
constexpr int SM_ST   = SM_MISC;
constexpr int SM_RK   = SM_ST + 2048;
constexpr int SM_SEL  = SM_RK + 256;
constexpr int SM_KG   = SM_SEL + 64;
constexpr int SM_SC   = SM_KG + 160;
constexpr int SM_DW   = SM_SC + 32;
constexpr int SM_MB   = SM_DW + 160;
constexpr int SM_TOTAL = SM_MB + 128;
constexpr int SM_ROW  = SM_XT - 20736;
constexpr int SM_XTL  = SM_ROW - 20480;
constexpr int SM_RED2 = SM_WG;
constexpr int SM_HT   = SM_P - 512;
constexpr int SM_KEY  = SM_FAR + 9216 + 128;
constexpr int SM_CAND = SM_KEY + 1024;
constexpr int SM_FIN  = SM_FAR + FAR_SZ + 9216 + 128;
constexpr int SM_HS   = SM_FIN + 2400;
constexpr int SM_XS   = SM_U;
constexpr int SM_GU   = SM_XS + 9344;
constexpr int SM_RED  = SM_GU + 5632;
static_assert(F_O9 + 1024 <= FAR_SZ && FAR_SZ % 128 == 0, "far overflow");
static_assert(SM_RED + 10240 <= SM_FAR && SM_HS + 128 <= SM_FAR + 2 * FAR_SZ && SM_HT + 20496 <= SM_MISC, "alias overflow");
static_assert(SM_TOTAL <= 232448, "smem overflow");
static_assert(SM_FAR % 128 == 0 && SM_XT % 128 == 0 && SM_XTL % 128 == 0 && SM_P % 16 == 0 && SM_MISC % 16 == 0 && SM_MB % 8 == 0 && SM_HS % 16 == 0, "align");

enum { MB_X = 0, MB_W1 = 5, MB_W2 = 6, MB_KEY = 7, MB_GU = 8, MB_Y = 9, MB_OUT = 10, MB_T = 11, MB_R = 12 };

struct __align__(128) Scratch {
    unsigned epoch, zcnt, pad[30];
    uint4  st1[L_ * 2];
    float4 acc[L_];
    uint4  cand[64 * NCL * 6];
    uint2  part[8 * NCL * D_];
};
__device__ Scratch g_s;
#define STAMP(i)

__device__ __forceinline__ uint32_t mapa(uint32_t a, uint32_t r) { uint32_t d; asm("mapa.shared::cluster.u32 %0, %1, %2;" : "=r"(d) : "r"(a), "r"(r)); return d; }
__device__ __forceinline__ void mbar_wait(uint32_t mb) {
    asm volatile("{ .reg .pred p, q; .reg .u32 n; mov.u32 n, 0;\n"
                 "W_%=: mbarrier.try_wait.parity.shared::cta.b64 p, [%0], 0; add.u32 n, n, 1; setp.lt.and.u32 q, n, 65536, !p; @q bra W_%=; }" :: "r"(mb) : "memory");
}
__device__ __forceinline__ void arm(uint32_t mb, uint32_t bytes) { asm volatile("mbarrier.arrive.expect_tx.shared::cta.b64 _, [%0], %1;" :: "r"(mb), "r"(bytes) : "memory"); }
__device__ __forceinline__ void bar_sync(int id, int n) { asm volatile("bar.sync %0, %1;" :: "r"(id), "r"(n) : "memory"); }
__device__ __forceinline__ void bar_arrive(int id, int n) { asm volatile("bar.arrive %0, %1;" :: "r"(id), "r"(n) : "memory"); }
__device__ __forceinline__ uint32_t lds16(uint32_t a) { unsigned short v; asm volatile("ld.shared.u16 %0, [%1];" : "=h"(v) : "r"(a) : "memory"); return v; }
__device__ __forceinline__ uint32_t lds32(uint32_t a) { uint32_t v; asm volatile("ld.shared.u32 %0, [%1];" : "=r"(v) : "r"(a) : "memory"); return v; }
__device__ __forceinline__ uint2 lds64(uint32_t a) { uint2 v; asm volatile("ld.shared.v2.u32 {%0,%1}, [%2];" : "=r"(v.x), "=r"(v.y) : "r"(a) : "memory"); return v; }
__device__ __forceinline__ float ldsf(uint32_t a) { float v; asm volatile("ld.shared.f32 %0, [%1];" : "=f"(v) : "r"(a) : "memory"); return v; }
__device__ __forceinline__ uint4 lds128(uint32_t a) { uint4 v; asm volatile("ld.shared.v4.u32 {%0,%1,%2,%3}, [%4];" : "=r"(v.x), "=r"(v.y), "=r"(v.z), "=r"(v.w) : "r"(a) : "memory"); return v; }
__device__ __forceinline__ float4 lds128f(uint32_t a) { float4 v; asm volatile("ld.shared.v4.f32 {%0,%1,%2,%3}, [%4];" : "=f"(v.x), "=f"(v.y), "=f"(v.z), "=f"(v.w) : "r"(a) : "memory"); return v; }
__device__ __forceinline__ void sts16(uint32_t a, uint32_t v) { asm volatile("{ .reg .b16 l, h; mov.b32 {l, h}, %1; st.shared.b16 [%0], l; }" :: "r"(a), "r"(v) : "memory"); }
__device__ __forceinline__ void sts32(uint32_t a, uint32_t v) { asm volatile("st.shared.u32 [%0], %1;" :: "r"(a), "r"(v) : "memory"); }
__device__ __forceinline__ void sts64(uint32_t a, uint32_t x, uint32_t y) { asm volatile("st.shared.v2.u32 [%0], {%1,%2};" :: "r"(a), "r"(x), "r"(y) : "memory"); }
__device__ __forceinline__ void stsf(uint32_t a, float v) { asm volatile("st.shared.f32 [%0], %1;" :: "r"(a), "f"(v) : "memory"); }
__device__ __forceinline__ void sts128(uint32_t a, uint32_t x, uint32_t y, uint32_t z, uint32_t w) { asm volatile("st.shared.v4.u32 [%0], {%1,%2,%3,%4};" :: "r"(a), "r"(x), "r"(y), "r"(z), "r"(w) : "memory"); }
__device__ __forceinline__ void sts128f(uint32_t a, float x, float y, float z, float w) { asm volatile("st.shared.v4.f32 [%0], {%1,%2,%3,%4};" :: "r"(a), "f"(x), "f"(y), "f"(z), "f"(w) : "memory"); }
__device__ __forceinline__ void ldsm4(uint32_t (&r)[4], uint32_t a) { asm volatile("ldmatrix.sync.aligned.m8n8.x4.shared.b16 {%0,%1,%2,%3}, [%4];" : "=r"(r[0]), "=r"(r[1]), "=r"(r[2]), "=r"(r[3]) : "r"(a) : "memory"); }
__device__ __forceinline__ void ldsm4t(uint32_t (&r)[4], uint32_t a) { asm volatile("ldmatrix.sync.aligned.m8n8.x4.trans.shared.b16 {%0,%1,%2,%3}, [%4];" : "=r"(r[0]), "=r"(r[1]), "=r"(r[2]), "=r"(r[3]) : "r"(a) : "memory"); }
__device__ __forceinline__ void ldsm2t(uint32_t& r0, uint32_t& r1, uint32_t a) { asm volatile("ldmatrix.sync.aligned.m8n8.x2.trans.shared.b16 {%0,%1}, [%2];" : "=r"(r0), "=r"(r1) : "r"(a) : "memory"); }
__device__ __forceinline__ void stsm4t(uint32_t a, uint32_t r0, uint32_t r1, uint32_t r2, uint32_t r3) { asm volatile("stmatrix.sync.aligned.m8n8.x4.trans.shared.b16 [%0], {%1,%2,%3,%4};" :: "r"(a), "r"(r0), "r"(r1), "r"(r2), "r"(r3) : "memory"); }
__device__ __forceinline__ void stsm4(uint32_t a, uint32_t r0, uint32_t r1, uint32_t r2, uint32_t r3) { asm volatile("stmatrix.sync.aligned.m8n8.x4.shared.b16 [%0], {%1,%2,%3,%4};" :: "r"(a), "r"(r0), "r"(r1), "r"(r2), "r"(r3) : "memory"); }
__device__ __forceinline__ void stsm2t(uint32_t a, uint32_t r0, uint32_t r1) { asm volatile("stmatrix.sync.aligned.m8n8.x2.trans.shared.b16 [%0], {%1,%2};" :: "r"(a), "r"(r0), "r"(r1) : "memory"); }
__device__ __forceinline__ uint4 ldg128(const void* p) { uint4 v; asm volatile("ld.global.nc.v4.u32 {%0,%1,%2,%3}, [%4];" : "=r"(v.x), "=r"(v.y), "=r"(v.z), "=r"(v.w) : "l"(p)); return v; }
__device__ __forceinline__ uint32_t ldg32(const void* p) { uint32_t v; asm volatile("ld.global.nc.u32 %0, [%1];" : "=r"(v) : "l"(p)); return v; }
__device__ __forceinline__ uint32_t ldg16(const void* p) { unsigned short v; asm volatile("ld.global.nc.u16 %0, [%1];" : "=h"(v) : "l"(p)); return v; }
__device__ __forceinline__ uint32_t opaque(uint32_t v) { uint32_t r; asm volatile("mov.b32 %0, %1;" : "=r"(r) : "r"(v)); return r; }
__device__ __forceinline__ void mma_f16(float (&d)[4], const uint32_t (&a)[4], uint32_t b0, uint32_t b1) {
    asm volatile("mma.sync.aligned.m16n8k16.row.col.f32.f16.f16.f32 {%0,%1,%2,%3}, {%4,%5,%6,%7}, {%8,%9}, {%0,%1,%2,%3};"
        : "+f"(d[0]), "+f"(d[1]), "+f"(d[2]), "+f"(d[3]) : "r"(a[0]), "r"(a[1]), "r"(a[2]), "r"(a[3]), "r"(b0), "r"(b1));
}
__device__ __forceinline__ void mma_bf16(float (&d)[4], uint32_t a0, uint32_t a1, uint32_t a2, uint32_t a3, uint32_t b0, uint32_t b1) {
    asm volatile("mma.sync.aligned.m16n8k16.row.col.f32.bf16.bf16.f32 {%0,%1,%2,%3}, {%4,%5,%6,%7}, {%8,%9}, {%0,%1,%2,%3};"
        : "+f"(d[0]), "+f"(d[1]), "+f"(d[2]), "+f"(d[3]) : "r"(a0), "r"(a1), "r"(a2), "r"(a3), "r"(b0), "r"(b1));
}
__device__ __forceinline__ void mma_bf16_k8(float (&d)[4], uint32_t a0, uint32_t a1, uint32_t b0) {
    asm volatile("mma.sync.aligned.m16n8k8.row.col.f32.bf16.bf16.f32 {%0,%1,%2,%3}, {%4,%5}, {%6}, {%0,%1,%2,%3};"
        : "+f"(d[0]), "+f"(d[1]), "+f"(d[2]), "+f"(d[3]) : "r"(a0), "r"(a1), "r"(b0));
}
__device__ __forceinline__ uint32_t pack_f16(float lo, float hi) { uint32_t r; asm("cvt.rn.f16x2.f32 %0, %1, %2;" : "=r"(r) : "f"(hi), "f"(lo)); return r; }
__device__ __forceinline__ uint32_t pack_bf16(float lo, float hi) { uint32_t r; asm("cvt.rn.bf16x2.f32 %0, %1, %2;" : "=r"(r) : "f"(hi), "f"(lo)); return r; }
__device__ __forceinline__ float bf_lo(uint32_t v) { return __uint_as_float(v << 16); }
__device__ __forceinline__ float bf_hi(uint32_t v) { return __uint_as_float(v & 0xFFFF0000u); }
__device__ __forceinline__ float bfr(float x) { return __uint_as_float(pack_bf16(0.f, x)); }
__device__ __forceinline__ uint32_t bsub2(uint32_t a, uint32_t b) { uint32_t r; asm("sub.rn.bf16x2 %0, %1, %2;" : "=r"(r) : "r"(a), "r"(b)); return r; }
__device__ __forceinline__ uint32_t badd2(uint32_t a, uint32_t b) { uint32_t r; asm("add.rn.bf16x2 %0, %1, %2;" : "=r"(r) : "r"(a), "r"(b)); return r; }
__device__ __forceinline__ uint32_t bmul2(uint32_t a, uint32_t b) { uint32_t r; asm("mul.rn.bf16x2 %0, %1, %2;" : "=r"(r) : "r"(a), "r"(b)); return r; }
__device__ __forceinline__ uint32_t bfma2(uint32_t a, uint32_t b, uint32_t c) { uint32_t r; asm("fma.rn.bf16x2 %0, %1, %2, %3;" : "=r"(r) : "r"(a), "r"(b), "r"(c)); return r; }
__device__ __forceinline__ uint32_t hadd2(uint32_t a, uint32_t b) { uint32_t r; asm("add.rn.f16x2 %0, %1, %2;" : "=r"(r) : "r"(a), "r"(b)); return r; }
__device__ __forceinline__ uint32_t hmul2(uint32_t a, uint32_t b) { uint32_t r; asm("mul.rn.f16x2 %0, %1, %2;" : "=r"(r) : "r"(a), "r"(b)); return r; }
__device__ __forceinline__ uint32_t hfma2(uint32_t a, uint32_t b, uint32_t c) { uint32_t r; asm("fma.rn.f16x2 %0, %1, %2, %3;" : "=r"(r) : "r"(a), "r"(b), "r"(c)); return r; }
__device__ __forceinline__ uint32_t hneg2(uint32_t a) { uint32_t r; asm("neg.f16x2 %0, %1;" : "=r"(r) : "r"(a)); return r; }
__device__ __forceinline__ float rcpf(float x) { float r; asm("rcp.approx.ftz.f32 %0, %1;" : "=f"(r) : "f"(x)); return r; }
__device__ __forceinline__ float sqrta(float x) { float r; asm("sqrt.approx.ftz.f32 %0, %1;" : "=f"(r) : "f"(x)); return r; }
__device__ __forceinline__ float ex2f(float x) { float r; asm("ex2.approx.ftz.f32 %0, %1;" : "=f"(r) : "f"(x)); return r; }
__device__ __forceinline__ void st_async4(uint32_t a, uint32_t x, uint32_t y, uint32_t z, uint32_t w, uint32_t mb) {
    asm volatile("st.async.shared::cluster.mbarrier::complete_tx::bytes.v4.u32 [%0], {%1,%2,%3,%4}, [%5];" :: "r"(a), "r"(x), "r"(y), "r"(z), "r"(w), "r"(mb) : "memory"); }
__device__ __forceinline__ void st_async1(uint32_t a, uint32_t x, uint32_t mb) {
    asm volatile("st.async.shared::cluster.mbarrier::complete_tx::bytes.u32 [%0], %1, [%2];" :: "r"(a), "r"(x), "r"(mb) : "memory"); }
__device__ __forceinline__ unsigned ld_rlx(const void* p) { unsigned v; asm volatile("ld.relaxed.gpu.global.u32 %0, [%1];" : "=r"(v) : "l"(p) : "memory"); return v; }
__device__ __forceinline__ unsigned ld_acq(const void* p) { unsigned v; asm volatile("ld.acquire.gpu.global.u32 %0, [%1];" : "=r"(v) : "l"(p) : "memory"); return v; }
__device__ __forceinline__ uint2 ld_rlx64(const void* p) { unsigned long long v; asm volatile("ld.relaxed.gpu.global.u64 %0, [%1];" : "=l"(v) : "l"(p) : "memory"); return make_uint2((unsigned)v, (unsigned)(v >> 32)); }
__device__ __forceinline__ void st_rlx64(void* p, unsigned lo, unsigned hi) { asm volatile("st.relaxed.gpu.global.u64 [%0], %1;" :: "l"(p), "l"((unsigned long long)lo | ((unsigned long long)hi << 32)) : "memory"); }
__device__ __forceinline__ void st_rlx128(void* p, uint32_t x, uint32_t y, uint32_t z, uint32_t w) {
    asm volatile("st.relaxed.gpu.global.v2.u64 [%0], {%1,%2};" :: "l"(p), "l"((unsigned long long)x | ((unsigned long long)y << 32)), "l"((unsigned long long)z | ((unsigned long long)w << 32)) : "memory"); }
__device__ __forceinline__ uint4 ld_rlx128(const void* p) { unsigned long long a, b; asm volatile("ld.relaxed.gpu.global.v2.u64 {%0,%1}, [%2];" : "=l"(a), "=l"(b) : "l"(p) : "memory"); return make_uint4((unsigned)a, (unsigned)(a >> 32), (unsigned)b, (unsigned)(b >> 32)); }
__device__ __forceinline__ void tma2d(uint32_t dst, const CUtensorMap* tm, int x, int y, uint32_t mb) {
    asm volatile("cp.async.bulk.tensor.2d.shared::cluster.global.mbarrier::complete_tx::bytes [%0], [%1, {%3, %4}], [%2];"
                 :: "r"(dst), "l"(tm), "r"(mb), "r"(x), "r"(y) : "memory");
}
__device__ __forceinline__ void cmul(float& xr, float& xi, float ar, float ai, float br, float bi) {
    const float r = fmaf(ar, br, -ai * bi), i = fmaf(ar, bi, ai * br); xr = r; xi = i;
}
__device__ __forceinline__ void csq(float& xr, float& xi, float ar, float ai) {
    const float r = fmaf(ar, ar, -ai * ai), i = (ar + ar) * ai; xr = r; xi = i;
}
__device__ __forceinline__ void cexp_s(float& zr, float& zi, float e2, float turns) {
    const float mag = ex2f(e2), r = (turns - rintf(turns)) * 6.283185307179586f;
    zr = mag * __cosf(r); zi = mag * __sinf(r);
}
__device__ __forceinline__ uint32_t ln_stats(float s1, float s2) {
    const float m = s1 * (1.f / D_);
    const float var = fmaxf(fmaf(s2, 1.f / D_, -m * m), 0.f);
    return pack_bf16(m, sqrta(bfr(bfr(var) + 1e-5f)));
}
__device__ __forceinline__ uint32_t rsplit(float rs) { const float h = bfr(rs); return pack_bf16(h, rs - h); }
__device__ __forceinline__ uint32_t norm2(uint32_t v, uint32_t m2, uint32_t rh2, uint32_t rl2) {
    const uint32_t dd = bsub2(v, m2);
    return bfma2(dd, rh2, bmul2(dd, rl2));
}
template <int N>
__device__ __forceinline__ uint32_t rank4(uint32_t a, uint32_t key) {
    uint32_t r0 = 0, r1 = 0, r2 = 0, r3 = 0;
#pragma unroll
    for (int i = 0; i < N; i++) {
        const uint4 o = lds128(a + i * 16);
        r0 += (key - o.x) >> 31; r1 += (key - o.y) >> 31; r2 += (key - o.z) >> 31; r3 += (key - o.w) >> 31;
    }
    return (r0 + r1) + (r2 + r3);
}
struct H2C { uint32_t r, i; };
__device__ __forceinline__ H2C splat(float r, float i) { H2C h; h.r = pack_f16(r, r); h.i = pack_f16(i, i); return h; }
__device__ __forceinline__ void expand4(uint32_t are, uint32_t aim, uint32_t R0, uint32_t R1, uint32_t I0, uint32_t I1, H2C m4) {
    sts128(are, R0, R1, hfma2(R0, m4.r, hneg2(hmul2(I0, m4.i))), hfma2(R1, m4.r, hneg2(hmul2(I1, m4.i))));
    sts128(aim, I0, I1, hfma2(R0, m4.i, hmul2(I0, m4.r)), hfma2(R1, m4.i, hmul2(I1, m4.r)));
}
__device__ __forceinline__ void expand8(uint32_t are, uint32_t aim, float sr, float si, float m1r, float m1i, float m2r, float m2i, H2C m4) {
    float r1, i1, r2, i2, r3, i3;
    cmul(r1, i1, sr, si, m1r, m1i); cmul(r2, i2, sr, si, m2r, m2i); cmul(r3, i3, r1, i1, m2r, m2i);
    expand4(are, aim, pack_f16(sr, r1), pack_f16(r2, r3), pack_f16(si, i1), pack_f16(i2, i3), m4);
}
__device__ __forceinline__ void put16(uint32_t a, uint32_t v) { sts16(a, v); sts16(a + 6, v); }

struct Params {
    const unsigned short *x, *prm6[6], *logdt, *dskip, *wr;
    const char* w3[3];
    __nv_bfloat16* out;
    Scratch* gs;
    unsigned zero;
};
__device__ __forceinline__ uint32_t tslot(uint32_t t) { return (t & 7) * 32 + ((t >> 4) & 24) + ((t >> 8) & 6) + ((t >> 6) & 1); }
#define CP(x) ((x) | zero)
#define PIN(x) asm volatile("or.b32 %0, %0, %1;" : "+r"(x) : "r"(zero))
__device__ __forceinline__ void wgmma32(float (&d)[4][4], const uint32_t (&a)[4], uint32_t dlo) {
    asm volatile("{ .reg .b64 ds; mov.b64 ds, {%20, %21};\n"
                 "wgmma.mma_async.sync.aligned.m64n32k16.f32.f16.f16 {%0,%1,%2,%3,%4,%5,%6,%7,%8,%9,%10,%11,%12,%13,%14,%15}, {%16,%17,%18,%19}, ds, 1, 1, 1, 0; }"
        : "+f"(d[0][0]), "+f"(d[0][1]), "+f"(d[0][2]), "+f"(d[0][3]), "+f"(d[1][0]), "+f"(d[1][1]), "+f"(d[1][2]), "+f"(d[1][3]),
          "+f"(d[2][0]), "+f"(d[2][1]), "+f"(d[2][2]), "+f"(d[2][3]), "+f"(d[3][0]), "+f"(d[3][1]), "+f"(d[3][2]), "+f"(d[3][3])
        : "r"(a[0]), "r"(a[1]), "r"(a[2]), "r"(a[3]), "r"(dlo), "n"(128 >> 4));
}

__global__ void __cluster_dims__(CS, 1, 1) __launch_bounds__(NTHR, 1)
fused_kernel(const __grid_constant__ Params prm, const __grid_constant__ CUtensorMap tmG, const __grid_constant__ CUtensorMap tmU,
             const __grid_constant__ CUtensorMap tmD, const __grid_constant__ CUtensorMap tmO, const __grid_constant__ CUtensorMap tmX)
{
    extern __shared__ __align__(1024) unsigned char smem[];
    const int tid = threadIdx.x, lane = tid & 31, warp = __shfl_sync(~0u, tid >> 5, 0);
    const int c = blockIdx.x >> 3, q = blockIdx.x & 7;
    const int nslot = (c < NCL - 1) ? 5 : 2;
    const int d0 = 40 * c;
    const uint32_t sb = opaque((uint32_t)__cvta_generic_to_shared(smem));
    const uint32_t mb = sb + SM_MB;
    Scratch& g_s = *prm.gs;
    const unsigned& zero = prm.zero;
    STAMP(0);

    if (warp >= 20) {
        unsigned epoch = 0;
        if (warp == 20) {
            if (lane == 0) {
#pragma unroll
                for (int i = 0; i < 13; i++)
                    asm volatile("mbarrier.init.shared::cta.b64 [%0], %1;" :: "r"(mb + i * 8), "r"(i == MB_OUT ? 8 : (i == MB_R || i == MB_T) ? 2 : i == MB_Y ? 1 + 4 * nslot : 1) : "memory");
                asm volatile("fence.mbarrier_init.release.cluster;" ::: "memory");
                arm(mb + MB_W1 * 8, 92160); arm(mb + MB_W2 * 8, nslot * 9216); arm(mb + MB_KEY * 8, 256); arm(mb + MB_GU * 8, nslot * 1024); arm(mb + MB_T * 8, 20480);
                const int bytes = max(min(18, L_ - 18 * (int)blockIdx.x), 1) * (D_ * 2);
                arm(mb + MB_R * 8, bytes);
                if (!ROW_DELAY) asm volatile("cp.async.bulk.shared::cluster.global.mbarrier::complete_tx::bytes [%0], [%1], %2, [%3];"
                             :: "r"(sb + SM_ROW), "l"(prm.x + min(18 * (int)blockIdx.x, L_ - 1) * D_), "r"(bytes), "r"(mb + MB_R * 8) : "memory");
            }
            __syncwarp();
        } else if (warp == 22) {
            epoch = ld_rlx(&g_s.epoch);
            if (lane < 18 && 18 * c + lane < 256) g_s.acc[256 * q + 18 * c + lane] = make_float4(0.f, 0.f, 0.f, 0.f);
        } else if (warp == 23 && lane == 0) asm volatile("prefetch.tensormap [%0];" :: "l"(&tmX) : "memory");
        asm volatile("barrier.cluster.arrive.relaxed.aligned;" ::: "memory");
        bar_sync(12, NTHR);
        if (warp == 22) {
            if (lane == 0) { sts32(sb + SM_SC + 28, epoch); asm volatile("mbarrier.arrive.shared::cta.b64 _, [%0];" :: "r"(mb + MB_R * 8) : "memory"); }
            epoch++;
            asm volatile("fence.acq_rel.gpu;" ::: "memory");
            __syncwarp();
            if (lane == 0) asm volatile("red.relaxed.gpu.global.add.u32 [%0], 1;" :: "l"(&g_s.zcnt) : "memory");
            STAMP(1);
            uint4 wv = make_uint4(0, 0, 0, 0), wv2 = ldg128((const uint4*)prm.wr + lane), wv3 = ldg128((const uint4*)prm.wr + 32 + lane);
            if (lane < 8) wv = ldg128((const uint4*)prm.wr + 64 + lane);
            if (lane < 10) {
                const int j = lane < 5 ? lane : lane - 5;
                uint4 v = make_uint4(0, 0, 0, 0);
                if (j < nslot) v = ldg128((const uint4*)((lane < 5 ? prm.dskip : prm.wr) + d0) + j);
                sts128(sb + SM_DW + lane * 16, v.x, v.y, v.z, v.w);
            }
            __syncwarp();
            if (lane == 0) asm volatile("mbarrier.arrive.shared::cta.b64 _, [%0];" :: "r"(mb + MB_T * 8) : "memory");
            mbar_wait(mb + (MB_X + 1) * 8);
            const uint32_t old = (epoch & 1) ? 0u : 0x40004000u;
#pragma unroll 1
            for (int t = 0; t < 8; t++) {
                uint4* pp = (uint4*)&g_s.part[(t * NCL + c) * D_ + 72 * q] + lane;
                *pp = make_uint4(0, 0, 0, 0);
                if (lane < 4) pp[32] = make_uint4(0, 0, 0, 0);
                if (lane < 6) g_s.cand[((q * 8 + t) * NCL + c) * 6 + lane] = make_uint4(old, old, old, old);
            }
            float a[4] = {0.f, 0.f, 0.f, 0.f};
            const uint32_t one = 0x3F803F80u;
            mma_bf16(a, one, one, one, one, wv.x, wv.y);  mma_bf16(a, one, one, one, one, wv.z, wv.w);
            mma_bf16(a, one, one, one, one, wv2.x, wv2.y); mma_bf16(a, one, one, one, one, wv2.z, wv2.w);
            mma_bf16(a, one, one, one, one, wv3.x, wv3.y); mma_bf16(a, one, one, one, one, wv3.z, wv3.w);
            float s = a[0] + a[1];
            s += __shfl_xor_sync(~0u, s, 1); s += __shfl_xor_sync(~0u, s, 2);
            stsf(sb + SM_SC + 24, s);
            __syncwarp();
            if (lane == 0) {
                int n = 0;
                while ((int)(ld_acq(&g_s.zcnt) - epoch * NCTA) < 0 && ++n < SPIN_LIMIT) __nanosleep(200);
                arm(mb + MB_Y * 8, 8 * 512 * nslot);
                if (blockIdx.x == 0) g_s.epoch = epoch;
            }
            STAMP(2);
            return;
        }
        if (warp == 21) {
            if (STREAM_T) { bar_arrive(13, 736); mbar_wait(mb + MB_T * 8); } else bar_sync(13, 736);
            if (GAP_NS) __nanosleep(GAP_NS);
#pragma unroll 1
            for (int i = 0; i < 24; i++) {
                if (i == 13) { bar_sync(15, 544); asm volatile("fence.proxy.async.shared::cta;" ::: "memory"); }
                if (lane == 0) tma2d(sb + SM_WG + i * 3840, i < 12 ? &tmG : &tmU, 320 * c + 8 * nslot * q, 48 * (i < 12 ? i : i - 12), mb + MB_W1 * 8);
                __nanosleep(PACE_NS);
            }
            STAMP(1);
            return;
        }
        if (warp == 20) {
            if (ROW_DELAY && lane == 0) {
                const long long t0 = clock64(); while (clock64() - t0 < ROW_DELAY) {}
                asm volatile("cp.async.bulk.shared::cluster.global.mbarrier::complete_tx::bytes [%0], [%1], %2, [%3];"
                             :: "r"(sb + SM_ROW), "l"(prm.x + min(18 * (int)blockIdx.x, L_ - 1) * D_), "r"(max(min(18, L_ - 18 * (int)blockIdx.x), 1) * (D_ * 2)), "r"(mb + MB_R * 8) : "memory");
            }
            __syncwarp();
            mbar_wait(mb + MB_R * 8);
            if (lane == 0) {
                asm volatile("cp.async.bulk.tensor.3d.shared::cluster.global.mbarrier::complete_tx::bytes [%0], [%1, {%3, %4, %5}], [%2];"
                             :: "r"(sb + SM_XTL), "l"(&tmX), "r"(mb + MB_T * 8), "r"(d0), "r"(8 * q), "r"(0) : "memory");
            }
            STAMP(6);
        }
        if (PRE_N && warp == 23) {
            mbar_wait(mb + MB_R * 8);
            const char* wp = prm.w3[0] + blockIdx.x * (PRE_N * 4096) + lane * 128;
#pragma unroll 1
            for (int i = 0; i < PRE_N; i++) { asm volatile("prefetch.global.L2 [%0];" :: "l"(wp + i * 4096) : "memory"); __nanosleep(PRE_NS); }
        }
        asm volatile("barrier.cluster.wait.aligned;" ::: "memory");
        bar_sync(13, 736);
        {
            const int gr = lane >> 2, pe = (lane & 3) * 2 + (warp & 1);
            const int s0 = gr ? 0 : XSPLIT, ns = gr ? min(XSPLIT, nslot) : nslot - XSPLIT;
            if (gr < 2 && ns > 0) {
                const int bytes = ns * YS - 160;
                if (pe == q) arm(mb + (MB_X + gr) * 8, 7 * bytes);
                else {
                    const uint32_t rb_ = mapa(sb, pe);
                    asm volatile("cp.async.bulk.shared::cluster.shared::cta.mbarrier::complete_tx::bytes [%0], [%1], %2, [%3];"
                                 :: "r"(rb_ + SM_U + 128 + q * UP + s0 * US), "r"(sb + SM_XT + 128 + pe * YP + s0 * YS), "r"(bytes), "r"(rb_ + SM_MB + (MB_X + gr) * 8) : "memory");
                }
            }
        }
        STAMP(1);
        if (warp == 23) {
#pragma unroll 1
            for (int kk = nslot - 1; kk >= 0; kk--) {
                __syncwarp();
                bar_sync(6 + kk, 160);
                if (lane == 0) { asm volatile("fence.proxy.async.shared::cta;" ::: "memory"); tma2d(sb + SM_FAR + kk * FAR_SZ, &tmD, 72 * q, 320 * c + 64 * kk, mb + MB_W2 * 8); }
            }
            return;
        }
        __syncwarp();
        bar_sync(14, 672);
        if (lane == 0) {
            if (!NO_OUT) asm volatile("cp.async.bulk.tensor.5d.global.shared::cta.bulk_group [%0, {%2, %4, %4, %4, %3}], [%1];" :: "l"(&tmO), "r"(sb + SM_XT), "r"(d0), "r"(8 * q), "r"(0) : "memory");
            asm volatile("cp.async.bulk.commit_group;" ::: "memory");
            asm volatile("cp.async.bulk.wait_group 0;" ::: "memory");
            asm volatile("fence.proxy.async.global;" ::: "memory");
        }
        __syncwarp();
        STAMP(2);
        if (lane < 8) asm volatile("mbarrier.arrive.release.cluster.shared::cluster.b64 _, [%0];" :: "r"(mapa(mb + MB_OUT * 8, lane)) : "memory");
        STAMP(3);
        return;
    }

    const int g = lane >> 2, cq = lane & 3;
    const int k = warp >> 2, wq = warp & 3;
    const int trow = 18 * blockIdx.x + warp;
    const bool rowact = warp < 18 && trow < L_;
    const int dch = min(d0 + 8 * k + q, D_ - 1);
    uint32_t pv[6];
#pragma unroll
    for (int i = 0; i < 6; i++) pv[i] = ldg16(prm.prm6[i] + (uint32_t)(dch * 128 + wq * 32 + lane));
    const uint32_t pLdt = ldg16(prm.logdt + dch);
    const int tn = 16 * (warp & 15) + g;
    uint32_t xa[5], xb[5];
    asm volatile("barrier.cluster.arrive.relaxed.aligned;" ::: "memory");
    uint4* const st1p = &g_s.st1[(((trow >> 3) & 7) * 256 + ((trow >> 6) & 31) * 8 + (trow & 7)) * 2 + (lane >> 2)];
    const bool pub = rowact && (lane & 0x1B) == 0;
    if (pub) st_rlx128(st1p, 0, 0, 0, 0);
    {
        const uint32_t za = sb + SM_P + tid * 16;
        sts128(za, 0, 0, 0, 0);
        if (tid < (SM_MISC - SM_P) / 16 - 640) sts128(za + 10240, 0, 0, 0, 0);
        sts128(sb + SM_XT + ((tid >> 3) & 15) * YP + k * YS + (lane & 7) * 16, 0, 0, 0, 0);
    }
    bar_sync(12, NTHR);
    const uint32_t dep = lds32(sb + SM_P);
#define PV(x) __uint_as_float(__byte_perm(dep, x, 0x5410))
    STAMP(1);
    const uint32_t fb = sb + SM_FAR + k * FAR_SZ;
    const uint32_t pn = sb + SM_PN + k * PN_SZ, pf = sb + SM_PF + k * PF_SZ;
    unsigned epoch;
    {
        const uint32_t kb = fb + wq * 3072;
        const uint32_t kl = kb + lane * 16;
        uint32_t Af[4][4];
        float sr, si, z1r, z1i, z2r, z2i, z4r, z4i, hr, hi_;
        {
            const float dt = bfr(ex2f(PV(pLdt) * 1.4426950408889634f));
            const float e2 = dt * PV(pv[0]) * 1.4426950408889634f, an = dt * PV(pv[1]);
            cmul(sr, si, PV(pv[4]), PV(pv[5]), dt * PV(pv[2]), dt * PV(pv[3]));
            const unsigned E = min(max(__reduce_max_sync(~0u, __float_as_uint(fmaxf(fabsf(sr), fabsf(si)))) >> 23, 1u), 253u);
            const float sc = __uint_as_float((254u - E) << 23);
            sr *= sc; si *= -sc;
            sts64(sb + SM_KG + warp * 8, E, __reduce_add_sync(~0u, __float2int_rn(sr * 16777216.f)));
            float ar, ai, br, bi, cr, ci, dr, di;
            { const float m = ex2f(e2 * 8.f); ar = m * __cosf(an * 8.f); ai = m * __sinf(an * 8.f); }
            csq(br, bi, ar, ai); csq(cr, ci, br, bi); csq(dr, di, cr, ci);
            const H2C m4 = splat(cr, ci);
            {
                float r3, i3;
                cmul(r3, i3, ar, ai, br, bi);
                expand4(kl, kl + 1024, pack_f16(1.f, ar), pack_f16(br, r3), pack_f16(0.f, ai), pack_f16(bi, i3), m4);
            }
            expand8(kl + 512, kl + 1536, dr, di, ar, ai, br, bi, m4);
            { const float m = ex2f(e2); z1r = m * __cosf(an); z1i = -m * __sinf(an); }
            cexp_s(hr, hi_, e2 * 128.f, an * (-128.f * 0.15915494309189535f));
            csq(z2r, z2i, z1r, z1i); csq(z4r, z4i, z2r, z2i);
        }
        __syncwarp();
#pragma unroll
        for (int ks = 0; ks < 4; ks++) ldsm4t(Af[ks], kb + (lane >> 3) * 512 + (lane & 7) * 16 + ks * 128);
        STAMP(2);
        mbar_wait(mb + MB_R * 8);
        epoch = lds32(sb + SM_SC + 28) + 1;
        {
            float a[4] = {0.f, 0.f, 0.f, 0.f}, b[4] = {0.f, 0.f, 0.f, 0.f};
            uint32_t rx[9];
#pragma unroll
            for (int i = 0; i < 9; i++) rx[i] = lds32(sb + SM_ROW + warp * (D_ * 2) + lane * 4 + i * 128);
#pragma unroll
            for (int i = 0; i < 9; i++) { if (i & 1) mma_bf16_k8(b, rx[i], 0x3F803F80u, rx[i]); else mma_bf16_k8(a, rx[i], 0x3F803F80u, rx[i]); }
            float s2 = (g & 1) ? a[1] + b[1] : a[0] + b[0], s1 = (a[2] + b[2]) + (a[3] + b[3]);
            s2 += __shfl_xor_sync(~0u, s2, 4); s1 += __shfl_xor_sync(~0u, s1, 1);
            s2 += __shfl_xor_sync(~0u, s2, 9); s1 += __shfl_xor_sync(~0u, s1, 2);
            s2 += __shfl_xor_sync(~0u, s2, 18);
            const uint32_t ms = ln_stats(s1, s2);
            if (pub) st_rlx128(st1p, ms, epoch, ms, epoch);
        }
        mbar_wait(mb + MB_R * 8);
        const uint32_t la = kb + ((lane >> 3) & 1) * 512 + (lane >> 4) * 128 + (lane & 7) * 16;
        uint32_t kp[5][2], b0[4], b1[4], b2[4], b3[4];
        auto mm2 = [&](int t) {
            float a0[4] = {0.f, 0.f, 0.f, 0.f}, a1[4] = {0.f, 0.f, 0.f, 0.f};
            mma_f16(a0, Af[0], b0[0], b0[1]); mma_f16(a1, Af[0], b2[0], b2[1]); mma_f16(a0, Af[1], b0[2], b0[3]); mma_f16(a1, Af[1], b2[2], b2[3]);
            mma_f16(a0, Af[2], b1[0], b1[1]); mma_f16(a1, Af[2], b3[0], b3[1]); mma_f16(a0, Af[3], b1[2], b1[3]); mma_f16(a1, Af[3], b3[2], b3[3]);
            kp[t][0] = pack_f16(a0[1], a0[0]); kp[t][1] = pack_f16(a0[3], a0[2]); kp[t + 1][0] = pack_f16(a1[1], a1[0]); kp[t + 1][1] = pack_f16(a1[3], a1[2]);
        };
        cmul(sr, si, sr, si, z1r, z1i);
        {
            const H2C h4 = splat(z4r, z4i);
            expand8(kl, kl + 512, sr, si, z1r, z1i, z2r, z2i, h4);
            cmul(sr, si, sr, si, hr, hi_);
            expand8(kl + 1024, kl + 1536, sr, si, z1r, z1i, z2r, z2i, h4);
        }
        __syncwarp();
        ldsm4t(b0, la); ldsm4t(b1, la + 256); ldsm4t(b2, la + 1024); ldsm4t(b3, la + 1280);
        cmul(z1r, z1i, z1r, z1i, hr, hi_);
        cmul(sr, si, sr, si, z1r, z1i);
        expand8(kl, kl + 512, sr, si, z2r, z2i, z4r, z4i, splat(hr, hi_));
        mm2(0);
        STAMP(3);
        if (warp < 16) {
            const uint4* sp = &g_s.st1[(256 * q + tn) * 2];
            uint32_t va[5], vc[5];
            mbar_wait(mb + MB_T * 8);
            {
                const uint32_t xt = sb + SM_XTL + tn * 80;
                uint4 a4 = lds128(xt + cq * 16), b4 = lds128(xt + cq * 16 + 640);
                va[0] = a4.x; va[1] = a4.y; va[2] = a4.z; va[3] = a4.w; va[4] = lds32(xt + 64 + cq * 4);
                vc[0] = b4.x; vc[1] = b4.y; vc[2] = b4.z; vc[3] = b4.w; vc[4] = lds32(xt + 704 + cq * 4);
            }
            uint2 sa, sc; int n = 0;
            do { sa = ld_rlx64(sp); sc = ld_rlx64(sp + 16); } while ((sa.y != epoch || sc.y != epoch) && ++n < SPIN_LIMIT);
            STAMP(4);
            const uint32_t ra = rsplit(rcpf(bf_hi(sa.x))), rc = rsplit(rcpf(bf_hi(sc.x)));
            const uint32_t ma = __byte_perm(sa.x, 0, 0x1010), mc = __byte_perm(sc.x, 0, 0x1010);
            if (cq < 2) sts64(sb + SM_ST + (64 * (warp & 3) + 16 * (warp >> 2)) + g * 256 + cq * 8, cq ? mc : ma, cq ? rc : ra);
            const uint32_t rha = __byte_perm(ra, 0, 0x1010), rla = __byte_perm(ra, 0, 0x3232), rhc = __byte_perm(rc, 0, 0x1010), rlc = __byte_perm(rc, 0, 0x3232);
#pragma unroll
            for (int i = 0; i < 5; i++) {
                va[i] = norm2(va[i], ma, rha, rla); va[i] = pack_f16(bf_lo(va[i]), bf_hi(va[i]));
                vc[i] = norm2(vc[i], mc, rhc, rlc); vc[i] = pack_f16(bf_lo(vc[i]), bf_hi(vc[i]));
            }
            const int d4 = 2 * (lane >> 3) + (lane & 1), d1_ = lane & 7;
            const uint32_t a4 = sb + warp * 32 + d4 * YP + (d4 == q ? SM_U + 128 : SM_XT + 128) + ((lane & 7) >> 1) * YS;
            const uint32_t a1 = sb + warp * 32 + d1_ * YP + (d1_ == q ? SM_U + 128 : SM_XT + 128) + 4 * YS + (lane & 8) * 2;
            stsm4t(a4, va[0], va[1], va[2], va[3]); stsm4t(a4 + 16, vc[0], vc[1], vc[2], vc[3]); stsm2t(a1, va[4], vc[4]);
        }
        asm volatile("fence.proxy.async.shared::cta;" ::: "memory");
        bar_arrive(13, 736);
        if (warp < 16) {
            const uint32_t xh = sb + SM_XTL + (64 * (g >> 1) + 32 * (warp & 1) + 8 * (g & 1) + (warp >> 1)) * 80;
            const uint4 a4 = lds128(xh + cq * 16), b4 = lds128(xh + cq * 16 + 1280);
            xa[0] = a4.x; xa[1] = a4.y; xa[2] = a4.z; xa[3] = a4.w; xa[4] = lds32(xh + 64 + cq * 4);
            xb[0] = b4.x; xb[1] = b4.y; xb[2] = b4.z; xb[3] = b4.w; xb[4] = lds32(xh + 1344 + cq * 4);
            bar_arrive(15, 544);
        }
        STAMP(5);
        csq(z1r, z1i, z1r, z1i);
        cmul(sr, si, sr, si, z1r, z1i);
        csq(z2r, z2i, hr, hi_);
        expand8(kl + 1024, kl + 1536, sr, si, z4r, z4i, hr, hi_, splat(z2r, z2i));
        __syncwarp();
        ldsm4t(b0, la); ldsm4t(b1, la + 256); ldsm4t(b2, la + 1024); ldsm4t(b3, la + 1280);
        csq(z1r, z1i, z1r, z1i);
        cmul(sr, si, sr, si, z1r, z1i);
        csq(z4r, z4i, z2r, z2i);
        expand8(kl, kl + 512, sr, si, hr, hi_, z2r, z2i, splat(z4r, z4i));
        mm2(2);
        __syncwarp();
        ldsm4t(b0, la); ldsm4t(b1, la + 256);
#pragma unroll
        for (int t = 0; t < 4; t++) sts64(kb + lane * 8 + 1024 + t * 256, kp[t][0], kp[t][1]);
        {
            float a0[4] = {0.f, 0.f, 0.f, 0.f}, a1[4] = {0.f, 0.f, 0.f, 0.f};
            mma_f16(a0, Af[0], b0[0], b0[1]); mma_f16(a1, Af[1], b0[2], b0[3]); mma_f16(a0, Af[2], b1[0], b1[1]); mma_f16(a1, Af[3], b1[2], b1[3]);
            sts64(kb + lane * 8 + 2048, pack_f16(a0[1] + a1[1], a0[0] + a1[0]), pack_f16(a0[3] + a1[3], a0[2] + a1[2]));
        }
        bar_sync(1 + k, 128);
        const uint4 m01 = lds128(sb + SM_KG + k * 32), m23 = lds128(sb + SM_KG + k * 32 + 16);
        const unsigned Em = max(max(m01.x, m01.z), max(m23.x, m23.z));
        const float f0 = __uint_as_float(max((int)(127 + m01.x - Em), 0) << 23), f1 = __uint_as_float(max((int)(127 + m01.z - Em), 0) << 23),
                    f2 = __uint_as_float(max((int)(127 + m23.x - Em), 0) << 23), f3 = __uint_as_float(max((int)(127 + m23.z - Em), 0) << 23);
        const uint32_t r0 = pack_f16(f0, f0), r1 = pack_f16(f1, f1), r2 = pack_f16(f2, f2), r3 = pack_f16(f3, f3);
        const uint32_t ra = fb + lane * 8 + wq * 256 + 1024;
        const uint2 p0 = lds64(ra), p1 = lds64(ra + 3072), p2 = lds64(ra + 6144), p3 = lds64(ra + 9216);
        uint32_t w0 = hadd2(hfma2(p0.x, r0, hmul2(p1.x, r1)), hfma2(p2.x, r2, hmul2(p3.x, r3)));
        uint32_t w1 = hadd2(hfma2(p0.y, r0, hmul2(p1.y, r1)), hfma2(p2.y, r2, hmul2(p3.y, r3)));
        const bool last = lane == 31;
        if (wq < 2) {
            const uint32_t rc = fb + lane * 8 + wq * 4 + 2048;
            const uint32_t w4 = hmul2(hadd2(hfma2(lds32(rc), r0, hmul2(lds32(rc + 3072), r1)), hfma2(lds32(rc + 6144), r2, hmul2(lds32(rc + 9216), r3))), 0x18001800u);
            const uint32_t ph = pf + (P_H7 + 16 * wq) + (g & 1) * (2 * P_HS) + cq * 64 + (g >> 1) * 4;
            put16(ph, w4 >> 16); put16(ph + 32, w4);
            const uint32_t pa = pn + (4 + 512 * wq) + lane * 8;
            sts16(pa, w0 >> 16); sts32(pa + 4, w0); sts16(pa + 10, w0);
            sts16(pa + 256, w1 >> 16); sts32(pa + 260, w1); sts16(pa + 266, w1);
            if (last) {
                sts32(sb + SM_SC + k * 4, Em * 0x00800080u);
                put16(wq ? pa + 264 : pn,
                      wq ? w1 : pack_f16(((float)(int)m01.y * f0 + (float)(int)m01.w * f1 + (float)(int)m23.y * f2 + (float)(int)m23.w * f3) * (1.f / 16777216.f), 0.f));
            }
        } else if (wq == 2) {
            const uint32_t pa = pn + 258 * 4 + (cq & 1) * 16 + (cq >> 1) * 512 + g * 32;
            if (last) { put16(pf, hmul2(w1, 0x18001800u)); w1 = hadd2(w1, hneg2(__byte_perm(w1, 0, 0x1010))); }
            const uint32_t b0 = __byte_perm(w0, 0, 0x1010), b1 = __byte_perm(w1, 0, 0x1010);
            sts16(pa, w0 >> 16); sts32(pa + 4, w0); sts64(pa + 8, b0, b0); sts16(pa + 18, w0);
            sts16(pa + 256, w1 >> 16); sts32(pa + 260, w1); sts64(pa + 264, b1, b1); sts16(pa + 274, w1);
        } else {
            const uint32_t pa = pf + ((g & 1) ? 3 * P_GS : P_GS) + cq * 32 + (g >> 1) * 4;
            const uint32_t pb = pa + ((g & 1) ? 4 - 3 * P_GS : P_GS);
            w0 = hmul2(w0, 0x18001800u); w1 = hmul2(w1, 0x18001800u);
            put16(pa, w0 >> 16); put16(pb, w0); put16(pa + 16, w1 >> 16); put16(pb + 16, w1);
            if (last) put16(pf + P_H7 + P_HS, w1);
        }
        bar_sync(1 + k, 128);
    }
    STAMP(6);

    asm volatile("barrier.cluster.wait.aligned;" ::: "memory");
    mbar_wait(mb + (MB_X + (k < XSPLIT || k >= nslot)) * 8);
    STAMP(7);
    if (k < nslot) {
        const int role = (wq + k) & 3;
        const uint32_t ub = sb + SM_U + k * US + 128;
        if (role) {
            const int r = (3 - role) * 32 + lane;
            const uint32_t a1 = ub + (r & 3) * (2 * UP) + (r >> 2) * 16, a0 = a1 + ((r & 3) ? -2 * UP : 6 * UP - 16);
            const uint4 q0 = lds128(a0), q1 = lds128(a0 + UP), q2 = lds128(a1), q3 = lds128(a1 + UP);
            const uint32_t U[16] = {q0.x, q0.y, q0.z, q0.w, q1.x, q1.y, q1.z, q1.w, q2.x, q2.y, q2.z, q2.w, q3.x, q3.y, q3.z, q3.w};
            uint32_t V[14], Q[14], R4[12], T[8];
#pragma unroll
            for (int i = 2; i < 14; i++) { V[i] = __byte_perm(U[i], U[i + 1], 0x5432); Q[i] = hadd2(U[i], V[i]); }
#pragma unroll
            for (int i = 2; i < 12; i++) R4[i] = hadd2(Q[i], Q[i + 1]);
            const uint32_t rb = fb + r * 16;
#pragma unroll
            for (int i = 0; i < 8; i++) T[i] = hadd2(V[5 + i], Q[6 + i]);
            sts128(rb + F_E3, T[0], T[1], T[2], T[3]); sts128(rb + F_O3 + 16, T[4], T[5], T[6], T[7]);
#pragma unroll
            for (int i = 0; i < 8; i++) T[i] = hadd2(R4[3 + i], U[5 + i]);
            sts128(rb + F_O5, T[0], T[1], T[2], T[3]); sts128(rb + F_E5, T[4], T[5], T[6], T[7]);
            if (role != 1) {
#pragma unroll
                for (int i = 0; i < 8; i++) T[i] = hadd2(T[i], hadd2(V[2 + i], V[5 + i]));
                sts128(rb + F_E7, T[0], T[1], T[2], T[3]); sts128(rb + F_O7, T[4], T[5], T[6], T[7]);
#pragma unroll
                for (int i = 0; i < 8; i++) T[i] = hadd2(R4[2 + i], hadd2(R4[4 + i], U[6 + i]));
                sts128(rb + F_O9, T[0], T[1], T[2], T[3]); sts128(rb + F_E9 + 16, T[4], T[5], T[6], T[7]);
                sts128(rb + F_E2, Q[6], Q[7], Q[8], Q[9]); sts128(rb + F_O2, Q[10], Q[11], Q[12], Q[13]);
            }
        } else if (lane < 8) {
            uint32_t v[5];
#pragma unroll
            for (int i = 0; i < 5; i++) { const int t = 6 + lane + i; v[i] = lds16(ub + 23 * 16 + (t < 16 ? (6 + (t >> 3)) * UP : 16) + (t & 7) * 2); }
            const uint32_t s = hadd2(hadd2(hadd2(v[0], v[1]), hadd2(v[2], v[3])), v[4]);
            sts16(fb + F_O5 + 96 * 16 + lane * 2, s);
            sts32(fb + (lane < 4 ? F_O3 : F_E9 - 16) + lane * 4, 0);
        }
        bar_sync(1 + k, 128);
        float acc[4][4];
        uint32_t Q[4][4];
        {
            const int h = role & 1, part = role >> 1;
            const uint32_t po = pf + (g - 2 * cq) * 4;
            float fa[7][4];
#pragma unroll
            for (int a = 0; a < 7; a++) fa[a][0] = fa[a][1] = fa[a][2] = fa[a][3] = 0.f;
            uint32_t B[3][4];
            Q[0][2] = zero;
#pragma unroll 1
            for (int s = 2 * part + 1; s >= 2 * part; s--) {
#pragma unroll
                for (int i = 0; i < 3; i++) { Q[i][0] = lds32(po + s * P_GS + i * 64); Q[i][1] = lds32(po + s * P_GS + (i * 64 + 32)); }
                const uint32_t ba = fb + lane * 16 + ((s & 1) * F_E3 + (part == h ? 0 : F_O5 + h * 16));
#pragma unroll
                for (int i = 0; i < 3; i++) ldsm4t(B[i], ba + i * 512);
#pragma unroll
                for (int i = 0; i < 3; i++) { Q[i][3] = CP(Q[i][0]); if (i) Q[i][2] = CP(Q[i - 1][1]); }
#pragma unroll
                for (int dl = 0; dl < 3; dl++)
#pragma unroll
                    for (int ap = 0; ap < 6 - dl; ap++) mma_f16(fa[ap + 1 + dl], Q[dl], B[ap >> 1][2 * (ap & 1)], B[ap >> 1][2 * (ap & 1) + 1]);
            }
#pragma unroll 1
            for (int s = role; s == 1; s++) {
                ldsm2t(B[0][0], B[0][1], fb + ((lane & 15) == 15 ? F_O5 : F_O3));
#pragma unroll
                for (int dl = 0; dl < 3; dl++) mma_f16(fa[dl], Q[dl], B[0][0], B[0][1]);
            }
#pragma unroll 1
            for (int s = part; s <= 2 * part; s++) {
#pragma unroll
                for (int i = 0; i < 4; i++) { Q[i][0] = lds32(po + s * P_HS + (P_H7 + i * 64)); Q[i][1] = lds32(po + s * P_HS + (P_H7 + i * 64 + 32)); }
                const uint32_t ba = fb + lane * 16 + (F_E7 + s * 1024 + h * F_H);
                ldsm4t(B[0], ba); ldsm4t(B[1], ba + 512);
#pragma unroll
                for (int i = 0; i < 4; i++) { Q[i][3] = CP(Q[i][0]); if (i) Q[i][2] = CP(Q[i - 1][1]); }
#pragma unroll
                for (int dl = 0; dl < 4; dl++) {
#pragma unroll
                    for (int ap = 0; ap < 4 - dl; ap++) mma_f16(fa[ap + 3 + dl], Q[dl], B[ap >> 1][2 * (ap & 1)], B[ap >> 1][2 * (ap & 1) + 1]);
                    if (s == 1) break;
                }
            }
            const uint32_t da = fb + role * 2048 + (lane & 3) * 512 + (((lane >> 2) ^ ((lane & 3) * 2)) << 4);
            bar_sync(1 + k, 128);
            stsm4(da, 0u, 0u, pack_f16(fa[0][0], fa[0][1]), pack_f16(fa[0][2], fa[0][3]));
#pragma unroll
            for (int i = 1; i < 4; i++)
                stsm4(da + i * 128, pack_f16(fa[2 * i - 1][0], fa[2 * i - 1][1]), pack_f16(fa[2 * i - 1][2], fa[2 * i - 1][3]),
                      pack_f16(fa[2 * i][0], fa[2 * i][1]), pack_f16(fa[2 * i][2], fa[2 * i][3]));
            Q[0][0] = (g == 2 * cq) ? 0x6000u : ((g == 2 * cq + 1) ? 0x60000000u : 0u);
            Q[0][1] = 0; Q[0][3] = CP(Q[0][0]);
            const uint32_t ra = fb + (lane >> 3) * 2048 + wq * 512 + (((lane & 7) ^ (wq * 2)) << 4);
            bar_sync(1 + k, 128);
#pragma unroll
            for (int i = 0; i < 4; i++) {
                ldsm4(B[0], ra + i * 128);
                acc[i][0] = acc[i][1] = acc[i][2] = acc[i][3] = 0.f;
                mma_f16(acc[i], Q[0], hadd2(B[0][0], B[0][2]), hadd2(B[0][1], B[0][3]));
            }
        }
        bar_arrive(6 + k, 160);
        STAMP(8);
        const uint32_t inv = lds32(sb + SM_SC + k * 4);
        uint32_t yd = mapa(sb, 2 * wq) + (SM_XT + 128 + q * YP + k * YS) + lane * 16;
        PIN(yd);
        {
            uint32_t pp = pn + (16 * (wq - 3) + g - 2 * cq) * 4;
            uint32_t dlo = (((ub + 6 * UP) & 0x3FFFF) >> 4) | ((UP >> 4) << 16);
            uint32_t R[4][4];
            auto loadQ = [&](uint32_t (&X)[4][4], uint32_t prev) {
#pragma unroll
                for (int i = 0; i < 4; i++) { X[i][0] = lds32(pp + i * 64); X[i][1] = lds32(pp + i * 64 + 32); }
                X[0][2] = CP(prev);
#pragma unroll
                for (int i = 0; i < 4; i++) { X[i][3] = CP(X[i][0]); if (i) X[i][2] = CP(X[i - 1][1]); }
                pp += 256;
            };
            auto issue = [&](uint32_t (&X)[4][4]) {
                asm volatile("wgmma.fence.sync.aligned;" ::: "memory");
#pragma unroll
                for (int i = 0; i < 4; i++) wgmma32(acc, X[i], dlo - i * (2 * UP >> 4));
                asm volatile("wgmma.commit_group.sync.aligned;" ::: "memory");
                dlo -= 1;
            };
            loadQ(Q, 0);
#pragma unroll 1
            for (int dl = 0; dl < 4; dl++) {
                issue(Q);
                asm volatile("wgmma.wait_group.sync.aligned 1;" ::: "memory");
                loadQ(R, Q[3][1]);
                issue(R);
                asm volatile("wgmma.wait_group.sync.aligned 1;" ::: "memory");
                loadQ(Q, R[3][1]);
            }
            issue(Q);
            asm volatile("wgmma.wait_group.sync.aligned 0;" ::: "memory");
        }
        const uint32_t pstep = mapa(sb, 1) - mapa(sb, 0), ym = mapa(mb + MB_Y * 8, 2 * wq);
#pragma unroll
        for (int e = 0; e < 2; e++)
            st_async4(yd + e * pstep, bmul2(pack_bf16(acc[0][2 * e], acc[0][2 * e + 1]), inv), bmul2(pack_bf16(acc[1][2 * e], acc[1][2 * e + 1]), inv),
                      bmul2(pack_bf16(acc[2][2 * e], acc[2][2 * e + 1]), inv), bmul2(pack_bf16(acc[3][2 * e], acc[3][2 * e + 1]), inv), ym + e * pstep);
        if (lane == 0) asm volatile("mbarrier.arrive.shared::cta.b64 _, [%0];" :: "r"(mb + MB_Y * 8) : "memory");
    }
    STAMP(9);
    uint32_t ha[5], hb[5];
    if (warp < 16) {
        const uint2 sa = lds64(sb + SM_ST + tn * 8), sc = lds64(sb + SM_ST + tn * 8 + 64);
        const uint32_t ma = sa.x, mbb = sc.x;
        const uint32_t rha = __byte_perm(sa.y, 0, 0x1010), rla = __byte_perm(sa.y, 0, 0x3232), rhb = __byte_perm(sc.y, 0, 0x1010), rlb = __byte_perm(sc.y, 0, 0x3232);
        const uint4 dk = lds128(sb + SM_DW + cq * 16), wk = lds128(sb + SM_DW + 80 + cq * 16);
        const uint32_t d1 = lds32(sb + SM_DW + 64 + cq * 4), w1 = lds32(sb + SM_DW + 144 + cq * 4);
        const uint32_t dkv[5] = {dk.x, dk.y, dk.z, dk.w, d1};
        uint32_t sel[5] = {wk.x, wk.y, wk.z, wk.w, w1}, sel2[5];
#pragma unroll
        for (int i = 0; i < 5; i++) {
            ha[i] = bmul2(norm2(xa[i], ma, rha, rla), dkv[i]); hb[i] = bmul2(norm2(xb[i], mbb, rhb, rlb), dkv[i]);
            if (!(g & 1)) sel[i] = 0x3F803F80u;
            sel2[i] = sel[i]; PIN(sel2[i]);
        }
        const uint32_t y4 = sb + SM_XT + 128 + warp * 32 + (2 * (lane >> 3) + (lane & 1)) * YP + ((lane & 7) >> 1) * YS;
        const uint32_t y1 = sb + SM_XT + 128 + warp * 32 + (lane & 7) * YP + 4 * YS + (lane & 8) * 2;
        mbar_wait(mb + MB_Y * 8);
        STAMP(10);
        float ca[4] = {0.f, 0.f, 0.f, 0.f}, cb[4] = {0.f, 0.f, 0.f, 0.f};
        {
            uint32_t ya[4], yb[4], yc, yd;
            ldsm4t(ya, y4); ldsm4t(yb, y4 + 16); ldsm2t(yc, yd, y1);
#pragma unroll
            for (int i = 0; i < 4; i++) { ha[i] = badd2(xa[i], badd2(ya[i], ha[i])); hb[i] = badd2(xb[i], badd2(yb[i], hb[i])); }
            ha[4] = badd2(xa[4], badd2(yc, ha[4])); hb[4] = badd2(xb[4], badd2(yd, hb[4]));
        }
        if (nslot != 5) {
            ha[4] = hb[4] = 0;
            if (cq >= 2) ha[0] = ha[1] = ha[2] = ha[3] = hb[0] = hb[1] = hb[2] = hb[3] = 0;
        }
#pragma unroll
        for (int i = 0; i < 5; i++) { mma_bf16_k8(ca, ha[i], sel[i], ha[i]); mma_bf16_k8(cb, hb[i], sel2[i], hb[i]); }
        const float oa = __shfl_xor_sync(~0u, (g & 1) ? ca[2] : ca[3], 4), ob = __shfl_xor_sync(~0u, (g & 1) ? cb[2] : cb[3], 4);
        if (cq == (g >> 1)) {
            float4* ap = &g_s.acc[256 * q + tn];
            const bool od = g & 1;
            asm volatile("red.relaxed.gpu.global.add.v4.f32 [%0], {%1,%2,%3,%4};" :: "l"(ap), "f"(od ? oa : ca[2]), "f"(od ? ca[1] : ca[0]), "f"(od ? ca[3] : oa), "f"(1.0f) : "memory");
            asm volatile("red.relaxed.gpu.global.add.v4.f32 [%0], {%1,%2,%3,%4};" :: "l"(ap + 8), "f"(od ? ob : cb[2]), "f"(od ? cb[1] : cb[0]), "f"(od ? cb[3] : ob), "f"(1.0f) : "memory");
        }
        const uint32_t hta = sb + SM_HT + tn * 80;
        sts128(hta + cq * 16, ha[0], ha[1], ha[2], ha[3]); sts32(hta + 64 + cq * 4, ha[4]);
        sts128(hta + cq * 16 + 640, hb[0], hb[1], hb[2], hb[3]); sts32(hta + 704 + cq * 4, hb[4]);
        STAMP(11);
    }
    const int kq = warp / 5, mt = warp - 5 * kq;
    const int mi = lane >> 3, mr = lane & 7;
    const unsigned tk = (unsigned)tid / 72u, ck = tid - tk * 72;
    uint32_t A[9][4];
    auto loadA = [&]() {
        mbar_wait(mb + MB_W1 * 8);
        const uint32_t aa = sb + (mi & 1) * SM_WU + (8 * (mi >> 1) + mr) * 80 + (144 * 80 * kq + mt * 16);
#pragma unroll
        for (int s = 0; s < 9; s++) ldsm4t(A[s], aa + s * 1280);
    };
    const uint32_t par = (epoch & 1) ? 0x40004000u : 0u;
    uint32_t pk0 = mapa(sb, 2 * cq), go = (ck / 5u + ck) * 16, co = ((q * 8 * NCL + c) * 6 + cq) * 16;
    PIN(pk0); PIN(go); PIN(co);
    if (warp < 8) {
        const float wsum = ldsf(sb + SM_SC + 24);
        const uint32_t idx = 2047 - (512 * ((tid >> 1) & 3) + 128 * ((tid >> 3) & 3) + 64 * (tid & 1) + 8 * q + warp);
        if (RED_DELAY) { const long long t0 = clock64(); while (clock64() - t0 < RED_DELAY) {} }
        uint4 s; int n = 0;
        do { s = ld_rlx128(&g_s.acc[256 * q + tid]); } while (__uint_as_float(s.w) != (float)NCL && ++n < SPIN_LIMIT);
        const uint32_t ms = ln_stats(__uint_as_float(s.x), __uint_as_float(s.y));
        const float rs = rcpf(bf_hi(ms));
        const uint32_t rb = pack_bf16(0.f, fmaf(-bf_lo(ms), wsum, __uint_as_float(s.z)) * rs);
        const uint32_t key = (((rb ^ (((int)rb >> 31) | 0x80000000u)) >> 16) << 11) | idx;
        sts32(sb + SM_KEY + tid * 4, key);
        __syncwarp();
        const uint32_t rank = rank4<8>(sb + SM_KEY + warp * 128, key);
        if (rank < 8) sts32(sb + SM_CAND + warp * 32 + rank * 4, key);
        sts64(sb + SM_ST + tid * 8, __byte_perm(ms, 0, 0x1010), rsplit(rs));
    } else loadA();
    if (warp < 16) {
        bar_sync(12, 512);
        if (warp < 8) {
            const uint32_t mk = lds32(sb + SM_CAND + (tid >> 2) * 4);
            uint32_t rank = rank4<4>(sb + SM_CAND + cq * 64, mk);
            rank += __shfl_xor_sync(~0u, rank, 1); rank += __shfl_xor_sync(~0u, rank, 2);
            if (rank < 8) {
                const uint32_t pk1 = pk0 + (mapa(sb, 1) - mapa(sb, 0));
                st_async1(pk0 + (SM_RK + q * 32) + rank * 4, mk, pk0 + (SM_MB + MB_KEY * 8));
                st_async1(pk1 + (SM_RK + q * 32) + rank * 4, mk, pk1 + (SM_MB + MB_KEY * 8));
                const uint32_t t = tslot(~mk);
                const uint2 sv = lds64(sb + SM_ST + t * 8);
                const uint4 hv = lds128(sb + SM_HT + t * 80 + cq * 16);
                const uint32_t h4 = lds32(sb + SM_HT + t * 80 + 64 + cq * 4);
                const uint32_t rr = bmul2(sv.y, 0x3C803C80u), rh = __byte_perm(rr, 0, 0x1010), rl = __byte_perm(rr, 0, 0x3232);
                char* const dp = (char*)g_s.cand + (co + rank * 1440);
                st_rlx128(dp, (norm2(hv.x, sv.x, rh, rl) & 0xBFFFBFFFu) | par, (norm2(hv.y, sv.x, rh, rl) & 0xBFFFBFFFu) | par,
                          (norm2(hv.z, sv.x, rh, rl) & 0xBFFFBFFFu) | par, (norm2(hv.w, sv.x, rh, rl) & 0xBFFFBFFFu) | par);
                asm volatile("st.relaxed.gpu.global.u32 [%0], %1;" :: "l"((char*)g_s.cand + (co + rank * 1440 + 64 - cq * 12)), "r"((norm2(h4, sv.x, rh, rl) & 0xBFFFBFFFu) | par) : "memory");
            }
            __syncwarp();
        }
        {
            const uint2 sa = lds64(sb + SM_ST + tn * 8), sbb = lds64(sb + SM_ST + tn * 8 + 64);
            const uint32_t rha = __byte_perm(sa.y, 0, 0x1010), rla = __byte_perm(sa.y, 0, 0x3232);
            const uint32_t rhb = __byte_perm(sbb.y, 0, 0x1010), rlb = __byte_perm(sbb.y, 0, 0x3232);
#pragma unroll
            for (int i = 0; i < 5; i++) { ha[i] = badd2(ha[i], norm2(ha[i], sa.x, rha, rla)); hb[i] = badd2(hb[i], norm2(hb[i], sbb.x, rhb, rlb)); }
            const uint32_t ota = sb + SM_XT + tn * 80;
            sts128(ota + cq * 16, ha[0], ha[1], ha[2], ha[3]); sts32(ota + 64 + cq * 4, ha[4]);
            sts128(ota + cq * 16 + 640, hb[0], hb[1], hb[2], hb[3]); sts32(ota + 704 + cq * 4, hb[4]);
            asm volatile("fence.proxy.async.shared::cta;" ::: "memory");
        }
        if (warp >= 8) {
            mbar_wait(mb + MB_KEY * 8);
            const uint32_t mk = lds32(sb + SM_RK - 256 + (tid >> 2) * 4);
            uint32_t rank = rank4<4>(sb + SM_RK + cq * 64, mk);
            rank += __shfl_xor_sync(~0u, rank, 1); rank += __shfl_xor_sync(~0u, rank, 2);
            if (rank < 8) sts64(sb + SM_SEL + rank * 8, mk, ((tid >> 2) - 64) * 1440);
        }
    }
    bar_sync(11, 640);
    STAMP(12);

    {
        const char* gp = (const char*)g_s.cand + (go + lds32(sb + SM_SEL + 4 + (tk & 7) * 8));
        uint4 hv = ld_rlx128(gp);
        if (warp < 8) loadA();
        if (warp < 18) {
            int n = 0;
            while ((((hv.x ^ par) | (hv.y ^ par) | (hv.z ^ par) | (hv.w ^ par)) & 0x40004000u) && ++n < SPIN_LIMIT) hv = ld_rlx128(gp);
            sts128(sb + SM_XS + tk * 16 + tid * 16, hv.x ^ par, hv.y ^ par, hv.z ^ par, hv.w ^ par);
        } else if (warp == 19 && lane < 20) {
            const uint32_t t = ~lds32(sb + SM_SEL + q * 8) & 2047;
            uint32_t v; asm volatile("ld.shared::cluster.u32 %0, [%1];" : "=r"(v) : "r"(mapa(sb + SM_HT + tslot(t) * 80 + lane * 4, (t >> 3) & 7)) : "memory");
            sts32(sb + SM_HS + lane * 4, v);
        }
    }
    bar_sync(14, 672);
    STAMP(13);
    {
        float c0[4] = {0.f, 0.f, 0.f, 0.f}, c1[4] = {0.f, 0.f, 0.f, 0.f}, c2[4] = {0.f, 0.f, 0.f, 0.f};
        const uint32_t ba = sb + SM_XS + mr * 1168 + mi * 16 + 288 * kq;
        uint32_t b[5][4];
#pragma unroll
        for (int s = 0; s < 5; s++) ldsm4(b[s], ba + s * 64);
        mma_bf16(c0, A[0][0], A[0][1], A[0][2], A[0][3], b[0][0], b[0][1]);
        mma_bf16(c1, A[1][0], A[1][1], A[1][2], A[1][3], b[0][2], b[0][3]);
        mma_bf16(c2, A[2][0], A[2][1], A[2][2], A[2][3], b[1][0], b[1][1]);
        mma_bf16(c0, A[3][0], A[3][1], A[3][2], A[3][3], b[1][2], b[1][3]);
        mma_bf16(c1, A[4][0], A[4][1], A[4][2], A[4][3], b[2][0], b[2][1]);
        mma_bf16(c2, A[5][0], A[5][1], A[5][2], A[5][3], b[2][2], b[2][3]);
        mma_bf16(c0, A[6][0], A[6][1], A[6][2], A[6][3], b[3][0], b[3][1]);
        mma_bf16(c1, A[7][0], A[7][1], A[7][2], A[7][3], b[3][2], b[3][3]);
        mma_bf16(c2, A[8][0], A[8][1], A[8][2], A[8][3], b[4][0], b[4][1]);
        sts128f(sb + SM_RED + tid * 16, c0[0] + c1[0] + c2[0], c0[1] + c1[1] + c2[1], c0[2] + c1[2] + c2[2], c0[3] + c1[3] + c2[3]);
    }
    bar_sync(1 + mt, 128);
    if (mt < nslot) {
        const uint32_t ra = sb + SM_RED + mt * 512 + lane * 16;
        const float4 p0 = lds128f(ra), p1 = lds128f(ra + 2560), p2 = lds128f(ra + 5120), p3 = lds128f(ra + 7680);
        const float g0 = bfr(((p0.x + p1.x) + (p2.x + p3.x)) * 64.f), g1 = bfr(((p0.y + p1.y) + (p2.y + p3.y)) * 64.f);
        const uint32_t sg = pack_bf16(g0 * rcpf(1.f + ex2f(g0 * -1.4426950408889634f)), g1 * rcpf(1.f + ex2f(g1 * -1.4426950408889634f)));
        const uint32_t gu = bmul2(sg, pack_bf16(((p0.z + p1.z) + (p2.z + p3.z)) * 64.f, ((p0.w + p1.w) + (p2.w + p3.w)) * 64.f));
#pragma unroll
        for (int i = 0; i < 2; i++) {
            const uint32_t rb_ = mapa(sb, 2 * kq + i);
            st_async1(rb_ + (SM_GU + (q * nslot + mt) * 128) + lane * 4, gu, rb_ + (SM_MB + MB_GU * 8));
        }
    }
    mbar_wait(mb + MB_W2 * 8);
    {
        const uint32_t aa = sb + (8 * (mi >> 1) + mr) * 144 + (mi & 1) * 16 + (SM_FAR + 2304 * kq + mt * 32);
#pragma unroll
        for (int s = 0; s < 5; s++) ldsm4t(A[s], aa + s * FAR_SZ);
    }
    const int col = lane & 15, tp = lane >> 4, ch = 4 * warp + 2 * (lane & 1);
    uint32_t po = (((2 * kq + tp) * NCL + c) * D_ + 72 * q + mt * 16 + col) * 8, pi = ((q * NCL + min(lane >> 1, NCL - 1)) * D_ + d0 + ch) * 8;
    uint32_t ra2 = sb + (SM_RED2 + mt * 576 + kq * 16) + (col & 7) * 72 + (col >> 3) * 8 + tp * 4;
    const uint32_t key = lds32(sb + SM_SEL + q * 8), k16 = key << 5;
    const float sg1 = rcpf(1.f + ex2f(__uint_as_float((k16 ^ (~((int)k16 >> 31) | 0x80000000u)) & 0xFFFF0000u) * -1.4426950408889634f));
    uint32_t sig = pack_bf16(sg1, sg1), oo = ((~key & 2047) * D_ + d0 + ch) * 2;
    uint32_t hs = lds32(sb + SM_HS + ch * 2), hn = bmul2(lds32(sb + SM_XS + q * 1168 + (d0 + ch) * 2), 0x42804280u);
    PIN(po); PIN(pi); PIN(ra2); PIN(sig); PIN(oo); PIN(hn);
    {
        uint32_t ba = sb + (SM_GU + 256 * kq) + (lane & 15) * 16 + (lane >> 4) * 1024, wa = sb + SM_RED2 + warp * 576 + g * 72 + cq * 16;
        PIN(ba); PIN(wa);
        mbar_wait(mb + MB_GU * 8);
        float c0[4] = {0.f, 0.f, 0.f, 0.f}, c1[4] = {0.f, 0.f, 0.f, 0.f}, c2[4] = {0.f, 0.f, 0.f, 0.f};
        uint32_t b[2][4], b8, b9;
        ldsm4t(b[0], ba); ldsm4t(b[1], ba + 2048); ldsm2t(b8, b9, ba + 4096);
        mma_bf16(c0, A[0][0], A[0][1], A[0][2], A[0][3], b[0][0], b[0][1]);
        mma_bf16(c1, A[1][0], A[1][1], A[1][2], A[1][3], b[0][2], b[0][3]);
        if (nslot == 5) {
            mma_bf16(c2, A[4][0], A[4][1], A[4][2], A[4][3], b8, b9);
            mma_bf16(c0, A[2][0], A[2][1], A[2][2], A[2][3], b[1][0], b[1][1]);
            mma_bf16(c1, A[3][0], A[3][1], A[3][2], A[3][3], b[1][2], b[1][3]);
        }
        sts64(wa, __float_as_uint(c0[0] + c1[0] + c2[0]), __float_as_uint(c0[1] + c1[1] + c2[1]));
        sts64(wa + 8, __float_as_uint(c0[2] + c1[2] + c2[2]), __float_as_uint(c0[3] + c1[3] + c2[3]));
    }
    bar_sync(6 + mt, 128);
    STAMP(14);
    {
        const float s = (ldsf(ra2) + ldsf(ra2 + 2880)) + (ldsf(ra2 + 5760) + ldsf(ra2 + 8640));
        if (mt * 16 + col < 72) st_rlx64((char*)g_s.part + po, __float_as_uint(s), epoch);
    }
    if (warp < 2 * nslot) {
        asm volatile("{ .reg .pred p, q; .reg .u32 n; mov.u32 n, 0;\n"
                     "W_%=: mbarrier.try_wait.parity.acquire.cluster.shared::cta.b64 p, [%0], 0; add.u32 n, n, 1; setp.lt.and.u32 q, n, 65536, !p; @q bra W_%=; }" :: "r"(mb + MB_OUT * 8) : "memory");
        if (FIN_DELAY) { const long long t0 = clock64(); while (clock64() - t0 < FIN_DELAY) {} }
        uint4 v; int n = 0;
        do { v = ld_rlx128((const char*)g_s.part + pi); } while ((v.y != epoch || v.w != epoch) && ++n < SPIN_LIMIT);
        float s0 = lane < 30 ? __uint_as_float(v.x) : 0.f, s1 = lane < 30 ? __uint_as_float(v.z) : 0.f;
#pragma unroll
        for (int o = 2; o < 32; o <<= 1) { s0 += __shfl_xor_sync(~0u, s0, o); s1 += __shfl_xor_sync(~0u, s1, o); }
        if (lane < 2) *(uint32_t*)((char*)prm.out + oo) = badd2(hs, badd2(hn, bmul2(pack_bf16(s0, s1), sig)));
    }
    STAMP(15);
}

typedef CUresult (*EncodeFn)(CUtensorMap*, CUtensorMapDataType, cuuint32_t, void*, const cuuint64_t*, const cuuint64_t*,
                             const cuuint32_t*, const cuuint32_t*, CUtensorMapInterleave, CUtensorMapSwizzle,
                             CUtensorMapL2promotion, CUtensorMapFloatOOBfill);

void make_map(EncodeFn fn, CUtensorMap* tm, const void* p, int cols, int rows, int bc, int br) {
    cuuint64_t dims[2] = {(cuuint64_t)cols, (cuuint64_t)rows};
    cuuint64_t strides[1] = {(cuuint64_t)cols * 2};
    cuuint32_t box[2] = {(cuuint32_t)bc, (cuuint32_t)br};
    cuuint32_t es[2] = {1, 1};
    fn(tm, CU_TENSOR_MAP_DATA_TYPE_BFLOAT16, 2, const_cast<void*>(p), dims, strides, box, es, CU_TENSOR_MAP_INTERLEAVE_NONE,
       CU_TENSOR_MAP_SWIZZLE_NONE, (CUtensorMapL2promotion)L2PROMO, CU_TENSOR_MAP_FLOAT_OOB_FILL_NONE);
}

void make_map3(EncodeFn fn, CUtensorMap* tm, const void* p) {
    cuuint64_t dims[3] = {(cuuint64_t)D_, 64, 32};
    cuuint64_t strides[2] = {(cuuint64_t)D_ * 2, (cuuint64_t)D_ * 128};
    cuuint32_t box[3] = {40, 8, 32};
    cuuint32_t es[3] = {1, 1, 1};
    fn(tm, CU_TENSOR_MAP_DATA_TYPE_BFLOAT16, 3, const_cast<void*>(p), dims, strides, box, es, CU_TENSOR_MAP_INTERLEAVE_NONE,
       CU_TENSOR_MAP_SWIZZLE_NONE, CU_TENSOR_MAP_L2_PROMOTION_NONE, CU_TENSOR_MAP_FLOAT_OOB_FILL_NONE);
}

void make_map5(EncodeFn fn, CUtensorMap* tm, const void* p) {
    cuuint64_t dims[5] = {(cuuint64_t)D_, 2, 4, 4, 64};
    cuuint64_t strides[4] = {(cuuint64_t)D_ * 128, (cuuint64_t)D_ * 1024, (cuuint64_t)D_ * 256, (cuuint64_t)D_ * 2};
    cuuint32_t box[5] = {40, 2, 4, 4, 8};
    cuuint32_t es[5] = {1, 1, 1, 1, 1};
    fn(tm, CU_TENSOR_MAP_DATA_TYPE_BFLOAT16, 5, const_cast<void*>(p), dims, strides, box, es, CU_TENSOR_MAP_INTERLEAVE_NONE,
       CU_TENSOR_MAP_SWIZZLE_NONE, CU_TENSOR_MAP_L2_PROMOTION_NONE, CU_TENSOR_MAP_FLOAT_OOB_FILL_NONE);
}

}

extern "C" void kernel_launch(void* const* d_in, const int* in_sizes, int n_in, void* d_out, int out_size) {
    (void)in_sizes; (void)n_in; (void)out_size;
    void* fp = nullptr;
    cudaDriverEntryPointQueryResult qr;
    cudaGetDriverEntryPoint("cuTensorMapEncodeTiled", &fp, cudaEnableDefault, &qr);
    EncodeFn fn = (EncodeFn)fp;
    CUtensorMap tmG, tmU, tmD, tmO, tmX;
    make_map3(fn, &tmX, d_in[0]);
    make_map(fn, &tmG, d_in[11], F_, D_, 40, 48);
    make_map(fn, &tmU, d_in[12], F_, D_, 40, 48);
    make_map(fn, &tmD, d_in[13], D_, F_, 72, 64);
    make_map5(fn, &tmO, d_out);
    Params p;
    p.x = (const unsigned short*)d_in[0];
    for (int i = 0; i < 6; i++) p.prm6[i] = (const unsigned short*)d_in[1 + i];
    p.logdt = (const unsigned short*)d_in[7]; p.dskip = (const unsigned short*)d_in[8];
    p.wr = (const unsigned short*)d_in[10];
    for (int i = 0; i < 3; i++) p.w3[i] = (const char*)d_in[11 + i];
    p.out = (__nv_bfloat16*)d_out;
    p.zero = 0;
    cudaGetSymbolAddress((void**)&p.gs, g_s);
    cudaFuncSetAttribute(fused_kernel, cudaFuncAttributeMaxDynamicSharedMemorySize, SM_TOTAL);
    fused_kernel<<<NCTA, NTHR, SM_TOTAL>>>(p, tmG, tmU, tmD, tmO, tmX);
}
```

```cpp
#include <cuda_runtime.h>
#include <cuda_bf16.h>
#include <cuda_fp16.h>
#include <cuda.h>
#include <stdint.h>

namespace {

constexpr int L_ = 2048, D_ = 576, F_ = 4608;
constexpr int NCL = 15, CS = 8, NCTA = NCL * CS, NTHR = 768;
#define PACE_NS 100
#define PRE_N 0
#define PRE_NS 200
#define FIN_DELAY 0
#define RED_DELAY 0
#define NO_OUT 0
#define XSPLIT 3
#define NORM_EARLY 0
#define NEAR_DB 1
#define STREAM_T 0
#define L2PROMO 2
#define GAP_NS 0
#define ROW_DELAY 1
constexpr int SPIN_LIMIT = 1 << 22;

constexpr int SM_WG   = 0;
constexpr int SM_WU   = 46080;
constexpr int YP = 3376, YS = 672;
constexpr int UP = 3376, US = 672;
constexpr int SM_XT   = 92160;
constexpr int SM_U    = SM_XT + 8 * YP;
constexpr int SM_FAR  = SM_U + 8 * UP;
constexpr int FAR_SZ  = 12416;
constexpr int F_E5 = 0, F_O5 = 1536, F_E3 = 3088, F_O3 = 4624, F_E7 = 6176, F_E2 = F_E7 + 1024, F_E9 = F_E7 + 2048,
              F_H = 3088, F_O7 = F_E7 + F_H, F_O2 = F_E2 + F_H, F_O9 = F_E9 + F_H;
constexpr int SM_P    = SM_FAR + 5 * FAR_SZ;
constexpr int PN_SZ = 584 * 4, SM_PN = SM_P + 64 * 4;
constexpr int P_GS = 48 * 4, P_H7 = 192 * 4, P_HS = 72 * 4;
constexpr int PF_SZ = (192 + 216) * 4, SM_PF = SM_PN + 5 * PN_SZ + 32;
constexpr int SM_MISC = SM_PF + 5 * PF_SZ;
constexpr int SM_ST   = SM_MISC;
constexpr int SM_RK   = SM_ST + 2048;
constexpr int SM_SEL  = SM_RK + 256;
constexpr int SM_KG   = SM_SEL + 64;
constexpr int SM_SC   = SM_KG + 160;
constexpr int SM_DW   = SM_SC + 32;
constexpr int SM_MB   = SM_DW + 160;
constexpr int SM_TOTAL = SM_MB + 128;
constexpr int SM_ROW  = SM_XT - 20736;
constexpr int SM_XTL  = SM_ROW - 20480;
constexpr int SM_RED2 = SM_WG;
constexpr int SM_HT   = SM_P - 512;
constexpr int SM_KEY  = SM_FAR + 9216 + 128;
constexpr int SM_CAND = SM_KEY + 1024;
constexpr int SM_FIN  = SM_FAR + FAR_SZ + 9216 + 128;
constexpr int SM_HS   = SM_FIN + 2400;
constexpr int SM_XS   = SM_U;
constexpr int SM_GU   = SM_XS + 9344;
constexpr int SM_RED  = SM_GU + 5632;
static_assert(F_O9 + 1024 <= FAR_SZ && FAR_SZ % 128 == 0, "far overflow");
static_assert(SM_RED + 10240 <= SM_FAR && SM_HS + 128 <= SM_FAR + 2 * FAR_SZ && SM_HT + 20496 <= SM_MISC, "alias overflow");
static_assert(SM_TOTAL <= 232448, "smem overflow");
static_assert(SM_FAR % 128 == 0 && SM_XT % 128 == 0 && SM_XTL % 128 == 0 && SM_P % 16 == 0 && SM_MISC % 16 == 0 && SM_MB % 8 == 0 && SM_HS % 16 == 0, "align");

enum { MB_X = 0, MB_W1 = 5, MB_W2 = 6, MB_KEY = 7, MB_GU = 8, MB_Y = 9, MB_OUT = 10, MB_T = 11, MB_R = 12 };

struct __align__(128) Scratch {
    unsigned epoch, zcnt, pad[30];
    uint4  st1[L_ * 2];
    float4 acc[L_];
    uint4  cand[64 * NCL * 6];
    float4 fin[8 * 192 + 24];
};
__device__ Scratch g_s;
#define STAMP(i)

__device__ __forceinline__ uint32_t mapa(uint32_t a, uint32_t r) { uint32_t d; asm("mapa.shared::cluster.u32 %0, %1, %2;" : "=r"(d) : "r"(a), "r"(r)); return d; }
__device__ __forceinline__ void mbar_wait(uint32_t mb) {
    asm volatile("{ .reg .pred p, q; .reg .u32 n; mov.u32 n, 0;\n"
                 "W_%=: mbarrier.try_wait.parity.shared::cta.b64 p, [%0], 0; add.u32 n, n, 1; setp.lt.and.u32 q, n, 65536, !p; @q bra W_%=; }" :: "r"(mb) : "memory");
}
__device__ __forceinline__ void arm(uint32_t mb, uint32_t bytes) { asm volatile("mbarrier.arrive.expect_tx.shared::cta.b64 _, [%0], %1;" :: "r"(mb), "r"(bytes) : "memory"); }
__device__ __forceinline__ void bar_sync(int id, int n) { asm volatile("bar.sync %0, %1;" :: "r"(id), "r"(n) : "memory"); }
__device__ __forceinline__ void bar_arrive(int id, int n) { asm volatile("bar.arrive %0, %1;" :: "r"(id), "r"(n) : "memory"); }
__device__ __forceinline__ uint32_t lds16(uint32_t a) { unsigned short v; asm volatile("ld.shared.u16 %0, [%1];" : "=h"(v) : "r"(a) : "memory"); return v; }
__device__ __forceinline__ uint32_t lds32(uint32_t a) { uint32_t v; asm volatile("ld.shared.u32 %0, [%1];" : "=r"(v) : "r"(a) : "memory"); return v; }
__device__ __forceinline__ uint2 lds64(uint32_t a) { uint2 v; asm volatile("ld.shared.v2.u32 {%0,%1}, [%2];" : "=r"(v.x), "=r"(v.y) : "r"(a) : "memory"); return v; }
__device__ __forceinline__ float ldsf(uint32_t a) { float v; asm volatile("ld.shared.f32 %0, [%1];" : "=f"(v) : "r"(a) : "memory"); return v; }
__device__ __forceinline__ uint4 lds128(uint32_t a) { uint4 v; asm volatile("ld.shared.v4.u32 {%0,%1,%2,%3}, [%4];" : "=r"(v.x), "=r"(v.y), "=r"(v.z), "=r"(v.w) : "r"(a) : "memory"); return v; }
__device__ __forceinline__ float4 lds128f(uint32_t a) { float4 v; asm volatile("ld.shared.v4.f32 {%0,%1,%2,%3}, [%4];" : "=f"(v.x), "=f"(v.y), "=f"(v.z), "=f"(v.w) : "r"(a) : "memory"); return v; }
__device__ __forceinline__ void sts16(uint32_t a, uint32_t v) { asm volatile("{ .reg .b16 l, h; mov.b32 {l, h}, %1; st.shared.b16 [%0], l; }" :: "r"(a), "r"(v) : "memory"); }
__device__ __forceinline__ void sts32(uint32_t a, uint32_t v) { asm volatile("st.shared.u32 [%0], %1;" :: "r"(a), "r"(v) : "memory"); }
__device__ __forceinline__ void sts64(uint32_t a, uint32_t x, uint32_t y) { asm volatile("st.shared.v2.u32 [%0], {%1,%2};" :: "r"(a), "r"(x), "r"(y) : "memory"); }
__device__ __forceinline__ void stsf(uint32_t a, float v) { asm volatile("st.shared.f32 [%0], %1;" :: "r"(a), "f"(v) : "memory"); }
__device__ __forceinline__ void sts128(uint32_t a, uint32_t x, uint32_t y, uint32_t z, uint32_t w) { asm volatile("st.shared.v4.u32 [%0], {%1,%2,%3,%4};" :: "r"(a), "r"(x), "r"(y), "r"(z), "r"(w) : "memory"); }
__device__ __forceinline__ void sts128f(uint32_t a, float x, float y, float z, float w) { asm volatile("st.shared.v4.f32 [%0], {%1,%2,%3,%4};" :: "r"(a), "f"(x), "f"(y), "f"(z), "f"(w) : "memory"); }
__device__ __forceinline__ void ldsm4(uint32_t (&r)[4], uint32_t a) { asm volatile("ldmatrix.sync.aligned.m8n8.x4.shared.b16 {%0,%1,%2,%3}, [%4];" : "=r"(r[0]), "=r"(r[1]), "=r"(r[2]), "=r"(r[3]) : "r"(a) : "memory"); }
__device__ __forceinline__ void ldsm4t(uint32_t (&r)[4], uint32_t a) { asm volatile("ldmatrix.sync.aligned.m8n8.x4.trans.shared.b16 {%0,%1,%2,%3}, [%4];" : "=r"(r[0]), "=r"(r[1]), "=r"(r[2]), "=r"(r[3]) : "r"(a) : "memory"); }
__device__ __forceinline__ void ldsm2t(uint32_t& r0, uint32_t& r1, uint32_t a) { asm volatile("ldmatrix.sync.aligned.m8n8.x2.trans.shared.b16 {%0,%1}, [%2];" : "=r"(r0), "=r"(r1) : "r"(a) : "memory"); }
__device__ __forceinline__ void stsm4t(uint32_t a, uint32_t r0, uint32_t r1, uint32_t r2, uint32_t r3) { asm volatile("stmatrix.sync.aligned.m8n8.x4.trans.shared.b16 [%0], {%1,%2,%3,%4};" :: "r"(a), "r"(r0), "r"(r1), "r"(r2), "r"(r3) : "memory"); }
__device__ __forceinline__ void stsm4(uint32_t a, uint32_t r0, uint32_t r1, uint32_t r2, uint32_t r3) { asm volatile("stmatrix.sync.aligned.m8n8.x4.shared.b16 [%0], {%1,%2,%3,%4};" :: "r"(a), "r"(r0), "r"(r1), "r"(r2), "r"(r3) : "memory"); }
__device__ __forceinline__ void stsm2t(uint32_t a, uint32_t r0, uint32_t r1) { asm volatile("stmatrix.sync.aligned.m8n8.x2.trans.shared.b16 [%0], {%1,%2};" :: "r"(a), "r"(r0), "r"(r1) : "memory"); }
__device__ __forceinline__ uint4 ldg128(const void* p) { uint4 v; asm volatile("ld.global.nc.v4.u32 {%0,%1,%2,%3}, [%4];" : "=r"(v.x), "=r"(v.y), "=r"(v.z), "=r"(v.w) : "l"(p)); return v; }
__device__ __forceinline__ uint32_t ldg32(const void* p) { uint32_t v; asm volatile("ld.global.nc.u32 %0, [%1];" : "=r"(v) : "l"(p)); return v; }
__device__ __forceinline__ uint32_t ldg16(const void* p) { unsigned short v; asm volatile("ld.global.nc.u16 %0, [%1];" : "=h"(v) : "l"(p)); return v; }
__device__ __forceinline__ uint32_t opaque(uint32_t v) { uint32_t r; asm volatile("mov.b32 %0, %1;" : "=r"(r) : "r"(v)); return r; }
__device__ __forceinline__ void mma_f16(float (&d)[4], const uint32_t (&a)[4], uint32_t b0, uint32_t b1) {
    asm volatile("mma.sync.aligned.m16n8k16.row.col.f32.f16.f16.f32 {%0,%1,%2,%3}, {%4,%5,%6,%7}, {%8,%9}, {%0,%1,%2,%3};"
        : "+f"(d[0]), "+f"(d[1]), "+f"(d[2]), "+f"(d[3]) : "r"(a[0]), "r"(a[1]), "r"(a[2]), "r"(a[3]), "r"(b0), "r"(b1));
}
__device__ __forceinline__ void mma_bf16(float (&d)[4], uint32_t a0, uint32_t a1, uint32_t a2, uint32_t a3, uint32_t b0, uint32_t b1) {
    asm volatile("mma.sync.aligned.m16n8k16.row.col.f32.bf16.bf16.f32 {%0,%1,%2,%3}, {%4,%5,%6,%7}, {%8,%9}, {%0,%1,%2,%3};"
        : "+f"(d[0]), "+f"(d[1]), "+f"(d[2]), "+f"(d[3]) : "r"(a0), "r"(a1), "r"(a2), "r"(a3), "r"(b0), "r"(b1));
}
__device__ __forceinline__ void mma_bf16_k8(float (&d)[4], uint32_t a0, uint32_t a1, uint32_t b0) {
    asm volatile("mma.sync.aligned.m16n8k8.row.col.f32.bf16.bf16.f32 {%0,%1,%2,%3}, {%4,%5}, {%6}, {%0,%1,%2,%3};"
        : "+f"(d[0]), "+f"(d[1]), "+f"(d[2]), "+f"(d[3]) : "r"(a0), "r"(a1), "r"(b0));
}
__device__ __forceinline__ uint32_t pack_f16(float lo, float hi) { uint32_t r; asm("cvt.rn.f16x2.f32 %0, %1, %2;" : "=r"(r) : "f"(hi), "f"(lo)); return r; }
__device__ __forceinline__ uint32_t pack_bf16(float lo, float hi) { uint32_t r; asm("cvt.rn.bf16x2.f32 %0, %1, %2;" : "=r"(r) : "f"(hi), "f"(lo)); return r; }
__device__ __forceinline__ float bf_lo(uint32_t v) { return __uint_as_float(v << 16); }
__device__ __forceinline__ float bf_hi(uint32_t v) { return __uint_as_float(v & 0xFFFF0000u); }
__device__ __forceinline__ float bfr(float x) { return __uint_as_float(pack_bf16(0.f, x)); }
__device__ __forceinline__ uint32_t bsub2(uint32_t a, uint32_t b) { uint32_t r; asm("sub.rn.bf16x2 %0, %1, %2;" : "=r"(r) : "r"(a), "r"(b)); return r; }
__device__ __forceinline__ uint32_t badd2(uint32_t a, uint32_t b) { uint32_t r; asm("add.rn.bf16x2 %0, %1, %2;" : "=r"(r) : "r"(a), "r"(b)); return r; }
__device__ __forceinline__ uint32_t bmul2(uint32_t a, uint32_t b) { uint32_t r; asm("mul.rn.bf16x2 %0, %1, %2;" : "=r"(r) : "r"(a), "r"(b)); return r; }
__device__ __forceinline__ uint32_t bfma2(uint32_t a, uint32_t b, uint32_t c) { uint32_t r; asm("fma.rn.bf16x2 %0, %1, %2, %3;" : "=r"(r) : "r"(a), "r"(b), "r"(c)); return r; }
__device__ __forceinline__ uint32_t hadd2(uint32_t a, uint32_t b) { uint32_t r; asm("add.rn.f16x2 %0, %1, %2;" : "=r"(r) : "r"(a), "r"(b)); return r; }
__device__ __forceinline__ uint32_t hmul2(uint32_t a, uint32_t b) { uint32_t r; asm("mul.rn.f16x2 %0, %1, %2;" : "=r"(r) : "r"(a), "r"(b)); return r; }
__device__ __forceinline__ uint32_t hfma2(uint32_t a, uint32_t b, uint32_t c) { uint32_t r; asm("fma.rn.f16x2 %0, %1, %2, %3;" : "=r"(r) : "r"(a), "r"(b), "r"(c)); return r; }
__device__ __forceinline__ uint32_t hneg2(uint32_t a) { uint32_t r; asm("neg.f16x2 %0, %1;" : "=r"(r) : "r"(a)); return r; }
__device__ __forceinline__ float rcpf(float x) { float r; asm("rcp.approx.ftz.f32 %0, %1;" : "=f"(r) : "f"(x)); return r; }
__device__ __forceinline__ float sqrta(float x) { float r; asm("sqrt.approx.ftz.f32 %0, %1;" : "=f"(r) : "f"(x)); return r; }
__device__ __forceinline__ float ex2f(float x) { float r; asm("ex2.approx.ftz.f32 %0, %1;" : "=f"(r) : "f"(x)); return r; }
__device__ __forceinline__ void st_async4(uint32_t a, uint32_t x, uint32_t y, uint32_t z, uint32_t w, uint32_t mb) {
    asm volatile("st.async.shared::cluster.mbarrier::complete_tx::bytes.v4.u32 [%0], {%1,%2,%3,%4}, [%5];" :: "r"(a), "r"(x), "r"(y), "r"(z), "r"(w), "r"(mb) : "memory"); }
__device__ __forceinline__ void st_async1(uint32_t a, uint32_t x, uint32_t mb) {
    asm volatile("st.async.shared::cluster.mbarrier::complete_tx::bytes.u32 [%0], %1, [%2];" :: "r"(a), "r"(x), "r"(mb) : "memory"); }
__device__ __forceinline__ unsigned ld_rlx(const void* p) { unsigned v; asm volatile("ld.relaxed.gpu.global.u32 %0, [%1];" : "=r"(v) : "l"(p) : "memory"); return v; }
__device__ __forceinline__ unsigned ld_acq(const void* p) { unsigned v; asm volatile("ld.acquire.gpu.global.u32 %0, [%1];" : "=r"(v) : "l"(p) : "memory"); return v; }
__device__ __forceinline__ uint2 ld_rlx64(const void* p) { unsigned long long v; asm volatile("ld.relaxed.gpu.global.u64 %0, [%1];" : "=l"(v) : "l"(p) : "memory"); return make_uint2((unsigned)v, (unsigned)(v >> 32)); }
__device__ __forceinline__ void st_rlx64(void* p, unsigned lo, unsigned hi) { asm volatile("st.relaxed.gpu.global.u64 [%0], %1;" :: "l"(p), "l"((unsigned long long)lo | ((unsigned long long)hi << 32)) : "memory"); }
__device__ __forceinline__ void st_rlx128(void* p, uint32_t x, uint32_t y, uint32_t z, uint32_t w) {
    asm volatile("st.relaxed.gpu.global.v2.u64 [%0], {%1,%2};" :: "l"(p), "l"((unsigned long long)x | ((unsigned long long)y << 32)), "l"((unsigned long long)z | ((unsigned long long)w << 32)) : "memory"); }
__device__ __forceinline__ uint4 ld_rlx128(const void* p) { unsigned long long a, b; asm volatile("ld.relaxed.gpu.global.v2.u64 {%0,%1}, [%2];" : "=l"(a), "=l"(b) : "l"(p) : "memory"); return make_uint4((unsigned)a, (unsigned)(a >> 32), (unsigned)b, (unsigned)(b >> 32)); }
__device__ __forceinline__ void tma2d(uint32_t dst, const CUtensorMap* tm, int x, int y, uint32_t mb) {
    asm volatile("cp.async.bulk.tensor.2d.shared::cluster.global.mbarrier::complete_tx::bytes [%0], [%1, {%3, %4}], [%2];"
                 :: "r"(dst), "l"(tm), "r"(mb), "r"(x), "r"(y) : "memory");
}
__device__ __forceinline__ void cmul(float& xr, float& xi, float ar, float ai, float br, float bi) {
    const float r = fmaf(ar, br, -ai * bi), i = fmaf(ar, bi, ai * br); xr = r; xi = i;
}
__device__ __forceinline__ void csq(float& xr, float& xi, float ar, float ai) {
    const float r = fmaf(ar, ar, -ai * ai), i = (ar + ar) * ai; xr = r; xi = i;
}
__device__ __forceinline__ void cexp_s(float& zr, float& zi, float e2, float turns) {
    const float mag = ex2f(e2), r = (turns - rintf(turns)) * 6.283185307179586f;
    zr = mag * __cosf(r); zi = mag * __sinf(r);
}
__device__ __forceinline__ uint32_t ln_stats(float s1, float s2) {
    const float m = s1 * (1.f / D_);
    const float var = fmaxf(fmaf(s2, 1.f / D_, -m * m), 0.f);
    return pack_bf16(m, sqrta(bfr(bfr(var) + 1e-5f)));
}
__device__ __forceinline__ uint32_t rsplit(float rs) { const float h = bfr(rs); return pack_bf16(h, rs - h); }
__device__ __forceinline__ uint32_t norm2(uint32_t v, uint32_t m2, uint32_t rh2, uint32_t rl2) {
    const uint32_t dd = bsub2(v, m2);
    return bfma2(dd, rh2, bmul2(dd, rl2));
}
template <int N>
__device__ __forceinline__ uint32_t rank4(uint32_t a, uint32_t key) {
    uint32_t r0 = 0, r1 = 0, r2 = 0, r3 = 0;
#pragma unroll
    for (int i = 0; i < N; i++) {
        const uint4 o = lds128(a + i * 16);
        r0 += (key - o.x) >> 31; r1 += (key - o.y) >> 31; r2 += (key - o.z) >> 31; r3 += (key - o.w) >> 31;
    }
    return (r0 + r1) + (r2 + r3);
}
struct H2C { uint32_t r, i; };
__device__ __forceinline__ H2C splat(float r, float i) { H2C h; h.r = pack_f16(r, r); h.i = pack_f16(i, i); return h; }
__device__ __forceinline__ void expand4(uint32_t are, uint32_t aim, uint32_t R0, uint32_t R1, uint32_t I0, uint32_t I1, H2C m4) {
    sts128(are, R0, R1, hfma2(R0, m4.r, hneg2(hmul2(I0, m4.i))), hfma2(R1, m4.r, hneg2(hmul2(I1, m4.i))));
    sts128(aim, I0, I1, hfma2(R0, m4.i, hmul2(I0, m4.r)), hfma2(R1, m4.i, hmul2(I1, m4.r)));
}
__device__ __forceinline__ void expand8(uint32_t are, uint32_t aim, float sr, float si, float m1r, float m1i, float m2r, float m2i, H2C m4) {
    float r1, i1, r2, i2, r3, i3;
    cmul(r1, i1, sr, si, m1r, m1i); cmul(r2, i2, sr, si, m2r, m2i); cmul(r3, i3, r1, i1, m2r, m2i);
    expand4(are, aim, pack_f16(sr, r1), pack_f16(r2, r3), pack_f16(si, i1), pack_f16(i2, i3), m4);
}
__device__ __forceinline__ void put16(uint32_t a, uint32_t v) { sts16(a, v); sts16(a + 6, v); }

struct Params {
    const unsigned short *x, *prm6[6], *logdt, *dskip, *wr;
    const char* w3[3];
    __nv_bfloat16* out;
    Scratch* gs;
    unsigned zero;
};
__device__ __forceinline__ uint32_t tslot(uint32_t t) { return (t & 7) * 32 + ((t >> 4) & 24) + ((t >> 8) & 6) + ((t >> 6) & 1); }
#define CP(x) ((x) | zero)
#define PIN(x) asm volatile("or.b32 %0, %0, %1;" : "+r"(x) : "r"(zero))
__device__ __forceinline__ void wgmma32(float (&d)[4][4], const uint32_t (&a)[4], uint32_t dlo) {
    asm volatile("{ .reg .b64 ds; mov.b64 ds, {%20, %21};\n"
                 "wgmma.mma_async.sync.aligned.m64n32k16.f32.f16.f16 {%0,%1,%2,%3,%4,%5,%6,%7,%8,%9,%10,%11,%12,%13,%14,%15}, {%16,%17,%18,%19}, ds, 1, 1, 1, 0; }"
        : "+f"(d[0][0]), "+f"(d[0][1]), "+f"(d[0][2]), "+f"(d[0][3]), "+f"(d[1][0]), "+f"(d[1][1]), "+f"(d[1][2]), "+f"(d[1][3]),
          "+f"(d[2][0]), "+f"(d[2][1]), "+f"(d[2][2]), "+f"(d[2][3]), "+f"(d[3][0]), "+f"(d[3][1]), "+f"(d[3][2]), "+f"(d[3][3])
        : "r"(a[0]), "r"(a[1]), "r"(a[2]), "r"(a[3]), "r"(dlo), "n"(128 >> 4));
}

__global__ void __cluster_dims__(CS, 1, 1) __launch_bounds__(NTHR, 1)
fused_kernel(const __grid_constant__ Params prm, const __grid_constant__ CUtensorMap tmG, const __grid_constant__ CUtensorMap tmU,
             const __grid_constant__ CUtensorMap tmD, const __grid_constant__ CUtensorMap tmO, const __grid_constant__ CUtensorMap tmX)
{
    extern __shared__ __align__(1024) unsigned char smem[];
    const int tid = threadIdx.x, lane = tid & 31, warp = __shfl_sync(~0u, tid >> 5, 0);
    const int c = blockIdx.x >> 3, q = blockIdx.x & 7;
    const int nslot = (c < NCL - 1) ? 5 : 2;
    const int d0 = 40 * c;
    const uint32_t sb = opaque((uint32_t)__cvta_generic_to_shared(smem));
    const uint32_t mb = sb + SM_MB;
    Scratch& g_s = *prm.gs;
    const unsigned& zero = prm.zero;
    STAMP(0);

    if (warp >= 20) {
        unsigned epoch = 0;
        if (warp == 20) {
            if (lane == 0) {
#pragma unroll
                for (int i = 0; i < 13; i++)
                    asm volatile("mbarrier.init.shared::cta.b64 [%0], %1;" :: "r"(mb + i * 8), "r"((i == MB_R || i == MB_T) ? 2 : i == MB_Y ? 1 + 4 * nslot : 1) : "memory");
                asm volatile("fence.mbarrier_init.release.cluster;" ::: "memory");
                arm(mb + MB_W1 * 8, 92160); arm(mb + MB_W2 * 8, nslot * 9216); arm(mb + MB_KEY * 8, 256); arm(mb + MB_GU * 8, nslot * 1024); arm(mb + MB_T * 8, 20480);
                const int bytes = max(min(18, L_ - 18 * (int)blockIdx.x), 1) * (D_ * 2);
                arm(mb + MB_R * 8, bytes);
                if (!ROW_DELAY) asm volatile("cp.async.bulk.shared::cluster.global.mbarrier::complete_tx::bytes [%0], [%1], %2, [%3];"
                             :: "r"(sb + SM_ROW), "l"(prm.x + min(18 * (int)blockIdx.x, L_ - 1) * D_), "r"(bytes), "r"(mb + MB_R * 8) : "memory");
            }
            __syncwarp();
        } else if (warp == 22) {
            epoch = ld_rlx(&g_s.epoch);
            if (lane < 18 ? 18 * c + lane < 256 : lane < 31) (lane < 18 ? &g_s.acc[256 * q + 18 * c] : &g_s.fin[13 * (int)blockIdx.x - 18])[lane] = make_float4(0.f, 0.f, 0.f, 0.f);
        } else if (warp == 23 && lane == 0) asm volatile("prefetch.tensormap [%0];" :: "l"(&tmX) : "memory");
        asm volatile("barrier.cluster.arrive.relaxed.aligned;" ::: "memory");
        bar_sync(12, NTHR);
        if (warp == 22) {
            if (lane == 0) { sts32(sb + SM_SC + 28, epoch); asm volatile("mbarrier.arrive.shared::cta.b64 _, [%0];" :: "r"(mb + MB_R * 8) : "memory"); }
            epoch++;
            asm volatile("fence.acq_rel.gpu;" ::: "memory");
            __syncwarp();
            if (lane == 0) asm volatile("red.relaxed.gpu.global.add.u32 [%0], 1;" :: "l"(&g_s.zcnt) : "memory");
            STAMP(1);
            uint4 wv = make_uint4(0, 0, 0, 0), wv2 = ldg128((const uint4*)prm.wr + lane), wv3 = ldg128((const uint4*)prm.wr + 32 + lane);
            if (lane < 8) wv = ldg128((const uint4*)prm.wr + 64 + lane);
            if (lane < 10) {
                const int j = lane < 5 ? lane : lane - 5;
                uint4 v = make_uint4(0, 0, 0, 0);
                if (j < nslot) v = ldg128((const uint4*)((lane < 5 ? prm.dskip : prm.wr) + d0) + j);
                sts128(sb + SM_DW + lane * 16, v.x, v.y, v.z, v.w);
            }
            __syncwarp();
            if (lane == 0) asm volatile("mbarrier.arrive.shared::cta.b64 _, [%0];" :: "r"(mb + MB_T * 8) : "memory");
            mbar_wait(mb + (MB_X + 1) * 8);
            const uint32_t old = (epoch & 1) ? 0u : 0x40004000u;
#pragma unroll
            for (int t = 0; t < 2; t++)
                if ((lane & 7) < 6) g_s.cand[((q * 8 + 4 * t + (lane >> 3)) * NCL + c) * 6 + (lane & 7)] = make_uint4(old, old, old, old);
            float a[4] = {0.f, 0.f, 0.f, 0.f};
            const uint32_t one = 0x3F803F80u;
            mma_bf16(a, one, one, one, one, wv.x, wv.y);  mma_bf16(a, one, one, one, one, wv.z, wv.w);
            mma_bf16(a, one, one, one, one, wv2.x, wv2.y); mma_bf16(a, one, one, one, one, wv2.z, wv2.w);
            mma_bf16(a, one, one, one, one, wv3.x, wv3.y); mma_bf16(a, one, one, one, one, wv3.z, wv3.w);
            float s = a[0] + a[1];
            s += __shfl_xor_sync(~0u, s, 1); s += __shfl_xor_sync(~0u, s, 2);
            stsf(sb + SM_SC + 24, s);
            __syncwarp();
            if (lane == 0) {
                int n = 0;
                while ((int)(ld_acq(&g_s.zcnt) - epoch * NCTA) < 0 && ++n < SPIN_LIMIT) __nanosleep(200);
                arm(mb + MB_Y * 8, 8 * 512 * nslot);
                if (blockIdx.x == 0) g_s.epoch = epoch;
            }
            STAMP(2);
            return;
        }
        if (warp == 21) {
            if (STREAM_T) { bar_arrive(13, 736); mbar_wait(mb + MB_T * 8); } else bar_sync(13, 736);
            if (GAP_NS) __nanosleep(GAP_NS);
#pragma unroll 1
            for (int i = 0; i < 24; i++) {
                if (i == 13) { bar_sync(15, 544); asm volatile("fence.proxy.async.shared::cta;" ::: "memory"); }
                if (lane == 0) tma2d(sb + SM_WG + i * 3840, i < 12 ? &tmG : &tmU, 320 * c + 8 * nslot * q, 48 * (i < 12 ? i : i - 12), mb + MB_W1 * 8);
                __nanosleep(PACE_NS);
            }
            STAMP(1);
            return;
        }
        if (warp == 20) {
            if (ROW_DELAY && lane == 0) {
                const long long t0 = clock64(); while (clock64() - t0 < ROW_DELAY) {}
                asm volatile("cp.async.bulk.shared::cluster.global.mbarrier::complete_tx::bytes [%0], [%1], %2, [%3];"
                             :: "r"(sb + SM_ROW), "l"(prm.x + min(18 * (int)blockIdx.x, L_ - 1) * D_), "r"(max(min(18, L_ - 18 * (int)blockIdx.x), 1) * (D_ * 2)), "r"(mb + MB_R * 8) : "memory");
            }
            __syncwarp();
            mbar_wait(mb + MB_R * 8);
            if (lane == 0) {
                asm volatile("cp.async.bulk.tensor.3d.shared::cluster.global.mbarrier::complete_tx::bytes [%0], [%1, {%3, %4, %5}], [%2];"
                             :: "r"(sb + SM_XTL), "l"(&tmX), "r"(mb + MB_T * 8), "r"(d0), "r"(8 * q), "r"(0) : "memory");
            }
            STAMP(6);
        }
        if (PRE_N && warp == 23) {
            mbar_wait(mb + MB_R * 8);
            const char* wp = prm.w3[0] + blockIdx.x * (PRE_N * 4096) + lane * 128;
#pragma unroll 1
            for (int i = 0; i < PRE_N; i++) { asm volatile("prefetch.global.L2 [%0];" :: "l"(wp + i * 4096) : "memory"); __nanosleep(PRE_NS); }
        }
        asm volatile("barrier.cluster.wait.aligned;" ::: "memory");
        bar_sync(13, 736);
        {
            const int gr = lane >> 2, pe = (lane & 3) * 2 + (warp & 1);
            const int s0 = gr ? 0 : XSPLIT, ns = gr ? min(XSPLIT, nslot) : nslot - XSPLIT;
            if (gr < 2 && ns > 0) {
                const int bytes = ns * YS - 160;
                if (pe == q) arm(mb + (MB_X + gr) * 8, 7 * bytes);
                else {
                    const uint32_t rb_ = mapa(sb, pe);
                    asm volatile("cp.async.bulk.shared::cluster.shared::cta.mbarrier::complete_tx::bytes [%0], [%1], %2, [%3];"
                                 :: "r"(rb_ + SM_U + 128 + q * UP + s0 * US), "r"(sb + SM_XT + 128 + pe * YP + s0 * YS), "r"(bytes), "r"(rb_ + SM_MB + (MB_X + gr) * 8) : "memory");
                }
            }
        }
        STAMP(1);
        if (warp == 23) {
#pragma unroll 1
            for (int kk = nslot - 1; kk >= 0; kk--) {
                __syncwarp();
                bar_sync(6 + kk, 160);
                if (lane == 0) { asm volatile("fence.proxy.async.shared::cta;" ::: "memory"); tma2d(sb + SM_FAR + kk * FAR_SZ, &tmD, 72 * q, 320 * c + 64 * kk, mb + MB_W2 * 8); }
            }
            return;
        }
        __syncwarp();
        bar_sync(14, 672);
        if (lane == 0) {
            if (!NO_OUT) asm volatile("cp.async.bulk.tensor.5d.global.shared::cta.bulk_group [%0, {%2, %4, %4, %4, %3}], [%1];" :: "l"(&tmO), "r"(sb + SM_XT), "r"(d0), "r"(8 * q), "r"(0) : "memory");
            asm volatile("cp.async.bulk.commit_group;" ::: "memory");
            asm volatile("cp.async.bulk.wait_group 0;" ::: "memory");
            asm volatile("fence.proxy.async.global;" ::: "memory");
            asm volatile("mbarrier.arrive.shared::cta.b64 _, [%0];" :: "r"(mb + MB_OUT * 8) : "memory");
        }
        STAMP(2);
        return;
    }

    const int g = lane >> 2, cq = lane & 3;
    const int k = warp >> 2, wq = warp & 3;
    const int trow = 18 * blockIdx.x + warp;
    const bool rowact = warp < 18 && trow < L_;
    const int dch = min(d0 + 8 * k + q, D_ - 1);
    uint32_t pv[6];
#pragma unroll
    for (int i = 0; i < 6; i++) pv[i] = ldg16(prm.prm6[i] + (uint32_t)(dch * 128 + wq * 32 + lane));
    const uint32_t pLdt = ldg16(prm.logdt + dch);
    const int tn = 16 * (warp & 15) + g;
    uint32_t xa[5], xb[5];
    asm volatile("barrier.cluster.arrive.relaxed.aligned;" ::: "memory");
    uint4* const st1p = &g_s.st1[(((trow >> 3) & 7) * 256 + ((trow >> 6) & 31) * 8 + (trow & 7)) * 2 + (lane >> 2)];
    const bool pub = rowact && (lane & 0x1B) == 0;
    if (pub) st_rlx128(st1p, 0, 0, 0, 0);
    {
        const uint32_t za = sb + SM_P + tid * 16;
        sts128(za, 0, 0, 0, 0);
        if (tid < (SM_MISC - SM_P) / 16 - 640) sts128(za + 10240, 0, 0, 0, 0);
        sts128(sb + SM_XT + ((tid >> 3) & 15) * YP + k * YS + (lane & 7) * 16, 0, 0, 0, 0);
    }
    bar_sync(12, NTHR);
    const uint32_t dep = lds32(sb + SM_P);
#define PV(x) __uint_as_float(__byte_perm(dep, x, 0x5410))
    STAMP(1);
    const uint32_t fb = sb + SM_FAR + k * FAR_SZ;
    const uint32_t pn = sb + SM_PN + k * PN_SZ, pf = sb + SM_PF + k * PF_SZ;
    unsigned epoch;
    {
        const uint32_t kb = fb + wq * 3072;
        const uint32_t kl = kb + lane * 16;
        uint32_t Af[4][4];
        float sr, si, z1r, z1i, z2r, z2i, z4r, z4i, hr, hi_;
        {
            const float dt = bfr(ex2f(PV(pLdt) * 1.4426950408889634f));
            const float e2 = dt * PV(pv[0]) * 1.4426950408889634f, an = dt * PV(pv[1]);
            cmul(sr, si, PV(pv[4]), PV(pv[5]), dt * PV(pv[2]), dt * PV(pv[3]));
            const unsigned E = min(max(__reduce_max_sync(~0u, __float_as_uint(fmaxf(fabsf(sr), fabsf(si)))) >> 23, 1u), 253u);
            const float sc = __uint_as_float((254u - E) << 23);
            sr *= sc; si *= -sc;
            sts64(sb + SM_KG + warp * 8, E, __reduce_add_sync(~0u, __float2int_rn(sr * 16777216.f)));
            float ar, ai, br, bi, cr, ci, dr, di;
            { const float m = ex2f(e2 * 8.f); ar = m * __cosf(an * 8.f); ai = m * __sinf(an * 8.f); }
            csq(br, bi, ar, ai); csq(cr, ci, br, bi); csq(dr, di, cr, ci);
            const H2C m4 = splat(cr, ci);
            {
                float r3, i3;
                cmul(r3, i3, ar, ai, br, bi);
                expand4(kl, kl + 1024, pack_f16(1.f, ar), pack_f16(br, r3), pack_f16(0.f, ai), pack_f16(bi, i3), m4);
            }
            expand8(kl + 512, kl + 1536, dr, di, ar, ai, br, bi, m4);
            { const float m = ex2f(e2); z1r = m * __cosf(an); z1i = -m * __sinf(an); }
            cexp_s(hr, hi_, e2 * 128.f, an * (-128.f * 0.15915494309189535f));
            csq(z2r, z2i, z1r, z1i); csq(z4r, z4i, z2r, z2i);
        }
        __syncwarp();
#pragma unroll
        for (int ks = 0; ks < 4; ks++) ldsm4t(Af[ks], kb + (lane >> 3) * 512 + (lane & 7) * 16 + ks * 128);
        STAMP(2);
        mbar_wait(mb + MB_R * 8);
        epoch = lds32(sb + SM_SC + 28) + 1;
        {
            float a[4] = {0.f, 0.f, 0.f, 0.f}, b[4] = {0.f, 0.f, 0.f, 0.f};
            uint32_t rx[9];
#pragma unroll
            for (int i = 0; i < 9; i++) rx[i] = lds32(sb + SM_ROW + warp * (D_ * 2) + lane * 4 + i * 128);
#pragma unroll
            for (int i = 0; i < 9; i++) { if (i & 1) mma_bf16_k8(b, rx[i], 0x3F803F80u, rx[i]); else mma_bf16_k8(a, rx[i], 0x3F803F80u, rx[i]); }
            float s2 = (g & 1) ? a[1] + b[1] : a[0] + b[0], s1 = (a[2] + b[2]) + (a[3] + b[3]);
            s2 += __shfl_xor_sync(~0u, s2, 4); s1 += __shfl_xor_sync(~0u, s1, 1);
            s2 += __shfl_xor_sync(~0u, s2, 9); s1 += __shfl_xor_sync(~0u, s1, 2);
            s2 += __shfl_xor_sync(~0u, s2, 18);
            const uint32_t ms = ln_stats(s1, s2);
            if (pub) st_rlx128(st1p, ms, epoch, ms, epoch);
        }
        mbar_wait(mb + MB_R * 8);
        const uint32_t la = kb + ((lane >> 3) & 1) * 512 + (lane >> 4) * 128 + (lane & 7) * 16;
        uint32_t kp[5][2], b0[4], b1[4], b2[4], b3[4];
        auto mm2 = [&](int t) {
            float a0[4] = {0.f, 0.f, 0.f, 0.f}, a1[4] = {0.f, 0.f, 0.f, 0.f};
            mma_f16(a0, Af[0], b0[0], b0[1]); mma_f16(a1, Af[0], b2[0], b2[1]); mma_f16(a0, Af[1], b0[2], b0[3]); mma_f16(a1, Af[1], b2[2], b2[3]);
            mma_f16(a0, Af[2], b1[0], b1[1]); mma_f16(a1, Af[2], b3[0], b3[1]); mma_f16(a0, Af[3], b1[2], b1[3]); mma_f16(a1, Af[3], b3[2], b3[3]);
            kp[t][0] = pack_f16(a0[1], a0[0]); kp[t][1] = pack_f16(a0[3], a0[2]); kp[t + 1][0] = pack_f16(a1[1], a1[0]); kp[t + 1][1] = pack_f16(a1[3], a1[2]);
        };
        cmul(sr, si, sr, si, z1r, z1i);
        {
            const H2C h4 = splat(z4r, z4i);
            expand8(kl, kl + 512, sr, si, z1r, z1i, z2r, z2i, h4);
            cmul(sr, si, sr, si, hr, hi_);
            expand8(kl + 1024, kl + 1536, sr, si, z1r, z1i, z2r, z2i, h4);
        }
        __syncwarp();
        ldsm4t(b0, la); ldsm4t(b1, la + 256); ldsm4t(b2, la + 1024); ldsm4t(b3, la + 1280);
        cmul(z1r, z1i, z1r, z1i, hr, hi_);
        cmul(sr, si, sr, si, z1r, z1i);
        expand8(kl, kl + 512, sr, si, z2r, z2i, z4r, z4i, splat(hr, hi_));
        mm2(0);
        STAMP(3);
        if (warp < 16) {
            const uint4* sp = &g_s.st1[(256 * q + tn) * 2];
            uint32_t va[5], vc[5];
            mbar_wait(mb + MB_T * 8);
            {
                const uint32_t xt = sb + SM_XTL + tn * 80;
                uint4 a4 = lds128(xt + cq * 16), b4 = lds128(xt + cq * 16 + 640);
                va[0] = a4.x; va[1] = a4.y; va[2] = a4.z; va[3] = a4.w; va[4] = lds32(xt + 64 + cq * 4);
                vc[0] = b4.x; vc[1] = b4.y; vc[2] = b4.z; vc[3] = b4.w; vc[4] = lds32(xt + 704 + cq * 4);
            }
            uint2 sa, sc; int n = 0;
            do { sa = ld_rlx64(sp); sc = ld_rlx64(sp + 16); } while ((sa.y != epoch || sc.y != epoch) && ++n < SPIN_LIMIT);
            STAMP(4);
            const uint32_t ra = rsplit(rcpf(bf_hi(sa.x))), rc = rsplit(rcpf(bf_hi(sc.x)));
            const uint32_t ma = __byte_perm(sa.x, 0, 0x1010), mc = __byte_perm(sc.x, 0, 0x1010);
            if (cq < 2) sts64(sb + SM_ST + (64 * (warp & 3) + 16 * (warp >> 2)) + g * 256 + cq * 8, cq ? mc : ma, cq ? rc : ra);
            const uint32_t rha = __byte_perm(ra, 0, 0x1010), rla = __byte_perm(ra, 0, 0x3232), rhc = __byte_perm(rc, 0, 0x1010), rlc = __byte_perm(rc, 0, 0x3232);
#pragma unroll
            for (int i = 0; i < 5; i++) {
                va[i] = norm2(va[i], ma, rha, rla); va[i] = pack_f16(bf_lo(va[i]), bf_hi(va[i]));
                vc[i] = norm2(vc[i], mc, rhc, rlc); vc[i] = pack_f16(bf_lo(vc[i]), bf_hi(vc[i]));
            }
            const int d4 = 2 * (lane >> 3) + (lane & 1), d1_ = lane & 7;
            const uint32_t a4 = sb + warp * 32 + d4 * YP + (d4 == q ? SM_U + 128 : SM_XT + 128) + ((lane & 7) >> 1) * YS;
            const uint32_t a1 = sb + warp * 32 + d1_ * YP + (d1_ == q ? SM_U + 128 : SM_XT + 128) + 4 * YS + (lane & 8) * 2;
            stsm4t(a4, va[0], va[1], va[2], va[3]); stsm4t(a4 + 16, vc[0], vc[1], vc[2], vc[3]); stsm2t(a1, va[4], vc[4]);
        }
        asm volatile("fence.proxy.async.shared::cta;" ::: "memory");
        bar_arrive(13, 736);
        if (warp < 16) {
            const uint32_t xh = sb + SM_XTL + (64 * (g >> 1) + 32 * (warp & 1) + 8 * (g & 1) + (warp >> 1)) * 80;
            const uint4 a4 = lds128(xh + cq * 16), b4 = lds128(xh + cq * 16 + 1280);
            xa[0] = a4.x; xa[1] = a4.y; xa[2] = a4.z; xa[3] = a4.w; xa[4] = lds32(xh + 64 + cq * 4);
            xb[0] = b4.x; xb[1] = b4.y; xb[2] = b4.z; xb[3] = b4.w; xb[4] = lds32(xh + 1344 + cq * 4);
            bar_arrive(15, 544);
        }
        STAMP(5);
        csq(z1r, z1i, z1r, z1i);
        cmul(sr, si, sr, si, z1r, z1i);
        csq(z2r, z2i, hr, hi_);
        expand8(kl + 1024, kl + 1536, sr, si, z4r, z4i, hr, hi_, splat(z2r, z2i));
        __syncwarp();
        ldsm4t(b0, la); ldsm4t(b1, la + 256); ldsm4t(b2, la + 1024); ldsm4t(b3, la + 1280);
        csq(z1r, z1i, z1r, z1i);
        cmul(sr, si, sr, si, z1r, z1i);
        csq(z4r, z4i, z2r, z2i);
        expand8(kl, kl + 512, sr, si, hr, hi_, z2r, z2i, splat(z4r, z4i));
        mm2(2);
        __syncwarp();
        ldsm4t(b0, la); ldsm4t(b1, la + 256);
#pragma unroll
        for (int t = 0; t < 4; t++) sts64(kb + lane * 8 + 1024 + t * 256, kp[t][0], kp[t][1]);
        {
            float a0[4] = {0.f, 0.f, 0.f, 0.f}, a1[4] = {0.f, 0.f, 0.f, 0.f};
            mma_f16(a0, Af[0], b0[0], b0[1]); mma_f16(a1, Af[1], b0[2], b0[3]); mma_f16(a0, Af[2], b1[0], b1[1]); mma_f16(a1, Af[3], b1[2], b1[3]);
            sts64(kb + lane * 8 + 2048, pack_f16(a0[1] + a1[1], a0[0] + a1[0]), pack_f16(a0[3] + a1[3], a0[2] + a1[2]));
        }
        bar_sync(1 + k, 128);
        const uint4 m01 = lds128(sb + SM_KG + k * 32), m23 = lds128(sb + SM_KG + k * 32 + 16);
        const unsigned Em = max(max(m01.x, m01.z), max(m23.x, m23.z));
        const float f0 = __uint_as_float(max((int)(127 + m01.x - Em), 0) << 23), f1 = __uint_as_float(max((int)(127 + m01.z - Em), 0) << 23),
                    f2 = __uint_as_float(max((int)(127 + m23.x - Em), 0) << 23), f3 = __uint_as_float(max((int)(127 + m23.z - Em), 0) << 23);
        const uint32_t r0 = pack_f16(f0, f0), r1 = pack_f16(f1, f1), r2 = pack_f16(f2, f2), r3 = pack_f16(f3, f3);
        const uint32_t ra = fb + lane * 8 + wq * 256 + 1024;
        const uint2 p0 = lds64(ra), p1 = lds64(ra + 3072), p2 = lds64(ra + 6144), p3 = lds64(ra + 9216);
        uint32_t w0 = hadd2(hfma2(p0.x, r0, hmul2(p1.x, r1)), hfma2(p2.x, r2, hmul2(p3.x, r3)));
        uint32_t w1 = hadd2(hfma2(p0.y, r0, hmul2(p1.y, r1)), hfma2(p2.y, r2, hmul2(p3.y, r3)));
        const bool last = lane == 31;
        if (wq < 2) {
            const uint32_t rc = fb + lane * 8 + wq * 4 + 2048;
            const uint32_t w4 = hmul2(hadd2(hfma2(lds32(rc), r0, hmul2(lds32(rc + 3072), r1)), hfma2(lds32(rc + 6144), r2, hmul2(lds32(rc + 9216), r3))), 0x18001800u);
            const uint32_t ph = pf + (P_H7 + 16 * wq) + (g & 1) * (2 * P_HS) + cq * 64 + (g >> 1) * 4;
            put16(ph, w4 >> 16); put16(ph + 32, w4);
            const uint32_t pa = pn + (4 + 512 * wq) + lane * 8;
            sts16(pa, w0 >> 16); sts32(pa + 4, w0); sts16(pa + 10, w0);
            sts16(pa + 256, w1 >> 16); sts32(pa + 260, w1); sts16(pa + 266, w1);
            if (last) {
                sts32(sb + SM_SC + k * 4, Em * 0x00800080u);
                put16(wq ? pa + 264 : pn,
                      wq ? w1 : pack_f16(((float)(int)m01.y * f0 + (float)(int)m01.w * f1 + (float)(int)m23.y * f2 + (float)(int)m23.w * f3) * (1.f / 16777216.f), 0.f));
            }
        } else if (wq == 2) {
            const uint32_t pa = pn + 258 * 4 + (cq & 1) * 16 + (cq >> 1) * 512 + g * 32;
            if (last) { put16(pf, hmul2(w1, 0x18001800u)); w1 = hadd2(w1, hneg2(__byte_perm(w1, 0, 0x1010))); }
            const uint32_t b0 = __byte_perm(w0, 0, 0x1010), b1 = __byte_perm(w1, 0, 0x1010);
            sts16(pa, w0 >> 16); sts32(pa + 4, w0); sts64(pa + 8, b0, b0); sts16(pa + 18, w0);
            sts16(pa + 256, w1 >> 16); sts32(pa + 260, w1); sts64(pa + 264, b1, b1); sts16(pa + 274, w1);
        } else {
            const uint32_t pa = pf + ((g & 1) ? 3 * P_GS : P_GS) + cq * 32 + (g >> 1) * 4;
            const uint32_t pb = pa + ((g & 1) ? 4 - 3 * P_GS : P_GS);
            w0 = hmul2(w0, 0x18001800u); w1 = hmul2(w1, 0x18001800u);
            put16(pa, w0 >> 16); put16(pb, w0); put16(pa + 16, w1 >> 16); put16(pb + 16, w1);
            if (last) put16(pf + P_H7 + P_HS, w1);
        }
        bar_sync(1 + k, 128);
    }
    STAMP(6);

    asm volatile("barrier.cluster.wait.aligned;" ::: "memory");
    mbar_wait(mb + (MB_X + (k < XSPLIT || k >= nslot)) * 8);
    STAMP(7);
    if (k < nslot) {
        const int role = (wq + k) & 3;
        const uint32_t ub = sb + SM_U + k * US + 128;
        if (role) {
            const int r = (3 - role) * 32 + lane;
            const uint32_t a1 = ub + (r & 3) * (2 * UP) + (r >> 2) * 16, a0 = a1 + ((r & 3) ? -2 * UP : 6 * UP - 16);
            const uint4 q0 = lds128(a0), q1 = lds128(a0 + UP), q2 = lds128(a1), q3 = lds128(a1 + UP);
            const uint32_t U[16] = {q0.x, q0.y, q0.z, q0.w, q1.x, q1.y, q1.z, q1.w, q2.x, q2.y, q2.z, q2.w, q3.x, q3.y, q3.z, q3.w};
            uint32_t V[14], Q[14], R4[12], T[8];
#pragma unroll
            for (int i = 2; i < 14; i++) { V[i] = __byte_perm(U[i], U[i + 1], 0x5432); Q[i] = hadd2(U[i], V[i]); }
#pragma unroll
            for (int i = 2; i < 12; i++) R4[i] = hadd2(Q[i], Q[i + 1]);
            const uint32_t rb = fb + r * 16;
#pragma unroll
            for (int i = 0; i < 8; i++) T[i] = hadd2(V[5 + i], Q[6 + i]);
            sts128(rb + F_E3, T[0], T[1], T[2], T[3]); sts128(rb + F_O3 + 16, T[4], T[5], T[6], T[7]);
#pragma unroll
            for (int i = 0; i < 8; i++) T[i] = hadd2(R4[3 + i], U[5 + i]);
            sts128(rb + F_O5, T[0], T[1], T[2], T[3]); sts128(rb + F_E5, T[4], T[5], T[6], T[7]);
            if (role != 1) {
#pragma unroll
                for (int i = 0; i < 8; i++) T[i] = hadd2(T[i], hadd2(V[2 + i], V[5 + i]));
                sts128(rb + F_E7, T[0], T[1], T[2], T[3]); sts128(rb + F_O7, T[4], T[5], T[6], T[7]);
#pragma unroll
                for (int i = 0; i < 8; i++) T[i] = hadd2(R4[2 + i], hadd2(R4[4 + i], U[6 + i]));
                sts128(rb + F_O9, T[0], T[1], T[2], T[3]); sts128(rb + F_E9 + 16, T[4], T[5], T[6], T[7]);
                sts128(rb + F_E2, Q[6], Q[7], Q[8], Q[9]); sts128(rb + F_O2, Q[10], Q[11], Q[12], Q[13]);
            }
        } else if (lane < 8) {
            uint32_t v[5];
#pragma unroll
            for (int i = 0; i < 5; i++) { const int t = 6 + lane + i; v[i] = lds16(ub + 23 * 16 + (t < 16 ? (6 + (t >> 3)) * UP : 16) + (t & 7) * 2); }
            const uint32_t s = hadd2(hadd2(hadd2(v[0], v[1]), hadd2(v[2], v[3])), v[4]);
            sts16(fb + F_O5 + 96 * 16 + lane * 2, s);
            sts32(fb + (lane < 4 ? F_O3 : F_E9 - 16) + lane * 4, 0);
        }
        bar_sync(1 + k, 128);
        float acc[4][4];
        uint32_t Q[4][4];
        {
            const int h = role & 1, part = role >> 1;
            const uint32_t po = pf + (g - 2 * cq) * 4;
            float fa[7][4];
#pragma unroll
            for (int a = 0; a < 7; a++) fa[a][0] = fa[a][1] = fa[a][2] = fa[a][3] = 0.f;
            uint32_t B[3][4];
            Q[0][2] = zero;
#pragma unroll 1
            for (int s = 2 * part + 1; s >= 2 * part; s--) {
#pragma unroll
                for (int i = 0; i < 3; i++) { Q[i][0] = lds32(po + s * P_GS + i * 64); Q[i][1] = lds32(po + s * P_GS + (i * 64 + 32)); }
                const uint32_t ba = fb + lane * 16 + ((s & 1) * F_E3 + (part == h ? 0 : F_O5 + h * 16));
#pragma unroll
                for (int i = 0; i < 3; i++) ldsm4t(B[i], ba + i * 512);
#pragma unroll
                for (int i = 0; i < 3; i++) { Q[i][3] = CP(Q[i][0]); if (i) Q[i][2] = CP(Q[i - 1][1]); }
#pragma unroll
                for (int dl = 0; dl < 3; dl++)
#pragma unroll
                    for (int ap = 0; ap < 6 - dl; ap++) mma_f16(fa[ap + 1 + dl], Q[dl], B[ap >> 1][2 * (ap & 1)], B[ap >> 1][2 * (ap & 1) + 1]);
            }
#pragma unroll 1
            for (int s = role; s == 1; s++) {
                ldsm2t(B[0][0], B[0][1], fb + ((lane & 15) == 15 ? F_O5 : F_O3));
#pragma unroll
                for (int dl = 0; dl < 3; dl++) mma_f16(fa[dl], Q[dl], B[0][0], B[0][1]);
            }
#pragma unroll 1
            for (int s = part; s <= 2 * part; s++) {
#pragma unroll
                for (int i = 0; i < 4; i++) { Q[i][0] = lds32(po + s * P_HS + (P_H7 + i * 64)); Q[i][1] = lds32(po + s * P_HS + (P_H7 + i * 64 + 32)); }
                const uint32_t ba = fb + lane * 16 + (F_E7 + s * 1024 + h * F_H);
                ldsm4t(B[0], ba); ldsm4t(B[1], ba + 512);
#pragma unroll
                for (int i = 0; i < 4; i++) { Q[i][3] = CP(Q[i][0]); if (i) Q[i][2] = CP(Q[i - 1][1]); }
#pragma unroll
                for (int dl = 0; dl < 4; dl++) {
#pragma unroll
                    for (int ap = 0; ap < 4 - dl; ap++) mma_f16(fa[ap + 3 + dl], Q[dl], B[ap >> 1][2 * (ap & 1)], B[ap >> 1][2 * (ap & 1) + 1]);
                    if (s == 1) break;
                }
            }
            const uint32_t da = fb + role * 2048 + (lane & 3) * 512 + (((lane >> 2) ^ ((lane & 3) * 2)) << 4);
            bar_sync(1 + k, 128);
            stsm4(da, 0u, 0u, pack_f16(fa[0][0], fa[0][1]), pack_f16(fa[0][2], fa[0][3]));
#pragma unroll
            for (int i = 1; i < 4; i++)
                stsm4(da + i * 128, pack_f16(fa[2 * i - 1][0], fa[2 * i - 1][1]), pack_f16(fa[2 * i - 1][2], fa[2 * i - 1][3]),
                      pack_f16(fa[2 * i][0], fa[2 * i][1]), pack_f16(fa[2 * i][2], fa[2 * i][3]));
            Q[0][0] = (g == 2 * cq) ? 0x6000u : ((g == 2 * cq + 1) ? 0x60000000u : 0u);
            Q[0][1] = 0; Q[0][3] = CP(Q[0][0]);
            const uint32_t ra = fb + (lane >> 3) * 2048 + wq * 512 + (((lane & 7) ^ (wq * 2)) << 4);
            bar_sync(1 + k, 128);
#pragma unroll
            for (int i = 0; i < 4; i++) {
                ldsm4(B[0], ra + i * 128);
                acc[i][0] = acc[i][1] = acc[i][2] = acc[i][3] = 0.f;
                mma_f16(acc[i], Q[0], hadd2(B[0][0], B[0][2]), hadd2(B[0][1], B[0][3]));
            }
        }
        bar_arrive(6 + k, 160);
        STAMP(8);
        const uint32_t inv = lds32(sb + SM_SC + k * 4);
        uint32_t yd = mapa(sb, 2 * wq) + (SM_XT + 128 + q * YP + k * YS) + lane * 16;
        PIN(yd);
        {
            uint32_t pp = pn + (16 * (wq - 3) + g - 2 * cq) * 4;
            uint32_t dlo = (((ub + 6 * UP) & 0x3FFFF) >> 4) | ((UP >> 4) << 16);
            uint32_t R[4][4];
            auto loadQ = [&](uint32_t (&X)[4][4], uint32_t prev) {
#pragma unroll
                for (int i = 0; i < 4; i++) { X[i][0] = lds32(pp + i * 64); X[i][1] = lds32(pp + i * 64 + 32); }
                X[0][2] = CP(prev);
#pragma unroll
                for (int i = 0; i < 4; i++) { X[i][3] = CP(X[i][0]); if (i) X[i][2] = CP(X[i - 1][1]); }
                pp += 256;
            };
            auto issue = [&](uint32_t (&X)[4][4]) {
                asm volatile("wgmma.fence.sync.aligned;" ::: "memory");
#pragma unroll
                for (int i = 0; i < 4; i++) wgmma32(acc, X[i], dlo - i * (2 * UP >> 4));
                asm volatile("wgmma.commit_group.sync.aligned;" ::: "memory");
                dlo -= 1;
            };
            loadQ(Q, 0);
#pragma unroll 1
            for (int dl = 0; dl < 4; dl++) {
                issue(Q);
                asm volatile("wgmma.wait_group.sync.aligned 1;" ::: "memory");
                loadQ(R, Q[3][1]);
                issue(R);
                asm volatile("wgmma.wait_group.sync.aligned 1;" ::: "memory");
                loadQ(Q, R[3][1]);
            }
            issue(Q);
            asm volatile("wgmma.wait_group.sync.aligned 0;" ::: "memory");
        }
        const uint32_t pstep = mapa(sb, 1) - mapa(sb, 0), ym = mapa(mb + MB_Y * 8, 2 * wq);
#pragma unroll
        for (int e = 0; e < 2; e++)
            st_async4(yd + e * pstep, bmul2(pack_bf16(acc[0][2 * e], acc[0][2 * e + 1]), inv), bmul2(pack_bf16(acc[1][2 * e], acc[1][2 * e + 1]), inv),
                      bmul2(pack_bf16(acc[2][2 * e], acc[2][2 * e + 1]), inv), bmul2(pack_bf16(acc[3][2 * e], acc[3][2 * e + 1]), inv), ym + e * pstep);
        if (lane == 0) asm volatile("mbarrier.arrive.shared::cta.b64 _, [%0];" :: "r"(mb + MB_Y * 8) : "memory");
    }
    STAMP(9);
    uint32_t ha[5], hb[5];
    if (warp < 16) {
        const uint2 sa = lds64(sb + SM_ST + tn * 8), sc = lds64(sb + SM_ST + tn * 8 + 64);
        const uint32_t ma = sa.x, mbb = sc.x;
        const uint32_t rha = __byte_perm(sa.y, 0, 0x1010), rla = __byte_perm(sa.y, 0, 0x3232), rhb = __byte_perm(sc.y, 0, 0x1010), rlb = __byte_perm(sc.y, 0, 0x3232);
        const uint4 dk = lds128(sb + SM_DW + cq * 16), wk = lds128(sb + SM_DW + 80 + cq * 16);
        const uint32_t d1 = lds32(sb + SM_DW + 64 + cq * 4), w1 = lds32(sb + SM_DW + 144 + cq * 4);
        const uint32_t dkv[5] = {dk.x, dk.y, dk.z, dk.w, d1};
        uint32_t sel[5] = {wk.x, wk.y, wk.z, wk.w, w1}, sel2[5];
#pragma unroll
        for (int i = 0; i < 5; i++) {
            ha[i] = bmul2(norm2(xa[i], ma, rha, rla), dkv[i]); hb[i] = bmul2(norm2(xb[i], mbb, rhb, rlb), dkv[i]);
            if (!(g & 1)) sel[i] = 0x3F803F80u;
            sel2[i] = sel[i]; PIN(sel2[i]);
        }
        const uint32_t y4 = sb + SM_XT + 128 + warp * 32 + (2 * (lane >> 3) + (lane & 1)) * YP + ((lane & 7) >> 1) * YS;
        const uint32_t y1 = sb + SM_XT + 128 + warp * 32 + (lane & 7) * YP + 4 * YS + (lane & 8) * 2;
        mbar_wait(mb + MB_Y * 8);
        STAMP(10);
        float ca[4] = {0.f, 0.f, 0.f, 0.f}, cb[4] = {0.f, 0.f, 0.f, 0.f};
        {
            uint32_t ya[4], yb[4], yc, yd;
            ldsm4t(ya, y4); ldsm4t(yb, y4 + 16); ldsm2t(yc, yd, y1);
#pragma unroll
            for (int i = 0; i < 4; i++) { ha[i] = badd2(xa[i], badd2(ya[i], ha[i])); hb[i] = badd2(xb[i], badd2(yb[i], hb[i])); }
            ha[4] = badd2(xa[4], badd2(yc, ha[4])); hb[4] = badd2(xb[4], badd2(yd, hb[4]));
        }
        if (nslot != 5) {
            ha[4] = hb[4] = 0;
            if (cq >= 2) ha[0] = ha[1] = ha[2] = ha[3] = hb[0] = hb[1] = hb[2] = hb[3] = 0;
        }
#pragma unroll
        for (int i = 0; i < 5; i++) { mma_bf16_k8(ca, ha[i], sel[i], ha[i]); mma_bf16_k8(cb, hb[i], sel2[i], hb[i]); }
        const float oa = __shfl_xor_sync(~0u, (g & 1) ? ca[2] : ca[3], 4), ob = __shfl_xor_sync(~0u, (g & 1) ? cb[2] : cb[3], 4);
        if (cq == (g >> 1)) {
            float4* ap = &g_s.acc[256 * q + tn];
            const bool od = g & 1;
            asm volatile("red.relaxed.gpu.global.add.v4.f32 [%0], {%1,%2,%3,%4};" :: "l"(ap), "f"(od ? oa : ca[2]), "f"(od ? ca[1] : ca[0]), "f"(od ? ca[3] : oa), "f"(1.0f) : "memory");
            asm volatile("red.relaxed.gpu.global.add.v4.f32 [%0], {%1,%2,%3,%4};" :: "l"(ap + 8), "f"(od ? ob : cb[2]), "f"(od ? cb[1] : cb[0]), "f"(od ? cb[3] : ob), "f"(1.0f) : "memory");
        }
        const uint32_t hta = sb + SM_HT + tn * 80;
        sts128(hta + cq * 16, ha[0], ha[1], ha[2], ha[3]); sts32(hta + 64 + cq * 4, ha[4]);
        sts128(hta + cq * 16 + 640, hb[0], hb[1], hb[2], hb[3]); sts32(hta + 704 + cq * 4, hb[4]);
        STAMP(11);
    }
    const int kq = warp / 5, mt = warp - 5 * kq;
    const int mi = lane >> 3, mr = lane & 7;
    const unsigned tk = (unsigned)tid / 72u, ck = tid - tk * 72;
    uint32_t A[9][4];
    auto loadA = [&]() {
        mbar_wait(mb + MB_W1 * 8);
        const uint32_t aa = sb + (mi & 1) * SM_WU + (8 * (mi >> 1) + mr) * 80 + (144 * 80 * kq + mt * 16);
#pragma unroll
        for (int s = 0; s < 9; s++) ldsm4t(A[s], aa + s * 1280);
    };
    const uint32_t par = (epoch & 1) ? 0x40004000u : 0u;
    uint32_t pk0 = mapa(sb, 2 * cq), go = (ck / 5u + ck) * 16, co = ((q * 8 * NCL + c) * 6 + cq) * 16;
    PIN(pk0); PIN(go); PIN(co);
    if (warp < 8) {
        const float wsum = ldsf(sb + SM_SC + 24);
        const uint32_t idx = 2047 - (512 * ((tid >> 1) & 3) + 128 * ((tid >> 3) & 3) + 64 * (tid & 1) + 8 * q + warp);
        if (RED_DELAY) { const long long t0 = clock64(); while (clock64() - t0 < RED_DELAY) {} }
        uint4 s; int n = 0;
        do { s = ld_rlx128(&g_s.acc[256 * q + tid]); } while (__uint_as_float(s.w) != (float)NCL && ++n < SPIN_LIMIT);
        const uint32_t ms = ln_stats(__uint_as_float(s.x), __uint_as_float(s.y));
        const float rs = rcpf(bf_hi(ms));
        const uint32_t rb = pack_bf16(0.f, fmaf(-bf_lo(ms), wsum, __uint_as_float(s.z)) * rs);
        const uint32_t key = (((rb ^ (((int)rb >> 31) | 0x80000000u)) >> 16) << 11) | idx;
        sts32(sb + SM_KEY + tid * 4, key);
        __syncwarp();
        const uint32_t rank = rank4<8>(sb + SM_KEY + warp * 128, key);
        if (rank < 8) sts32(sb + SM_CAND + warp * 32 + rank * 4, key);
        sts64(sb + SM_ST + tid * 8, __byte_perm(ms, 0, 0x1010), rsplit(rs));
    } else loadA();
    if (warp < 16) {
        bar_sync(12, 512);
        if (warp < 8) {
            const uint32_t mk = lds32(sb + SM_CAND + (tid >> 2) * 4);
            uint32_t rank = rank4<4>(sb + SM_CAND + cq * 64, mk);
            rank += __shfl_xor_sync(~0u, rank, 1); rank += __shfl_xor_sync(~0u, rank, 2);
            if (rank < 8) {
                const uint32_t pk1 = pk0 + (mapa(sb, 1) - mapa(sb, 0));
                st_async1(pk0 + (SM_RK + q * 32) + rank * 4, mk, pk0 + (SM_MB + MB_KEY * 8));
                st_async1(pk1 + (SM_RK + q * 32) + rank * 4, mk, pk1 + (SM_MB + MB_KEY * 8));
                const uint32_t t = tslot(~mk);
                const uint2 sv = lds64(sb + SM_ST + t * 8);
                const uint4 hv = lds128(sb + SM_HT + t * 80 + cq * 16);
                const uint32_t h4 = lds32(sb + SM_HT + t * 80 + 64 + cq * 4);
                const uint32_t rr = bmul2(sv.y, 0x3C803C80u), rh = __byte_perm(rr, 0, 0x1010), rl = __byte_perm(rr, 0, 0x3232);
                char* const dp = (char*)g_s.cand + (co + rank * 1440);
                st_rlx128(dp, (norm2(hv.x, sv.x, rh, rl) & 0xBFFFBFFFu) | par, (norm2(hv.y, sv.x, rh, rl) & 0xBFFFBFFFu) | par,
                          (norm2(hv.z, sv.x, rh, rl) & 0xBFFFBFFFu) | par, (norm2(hv.w, sv.x, rh, rl) & 0xBFFFBFFFu) | par);
                asm volatile("st.relaxed.gpu.global.u32 [%0], %1;" :: "l"((char*)g_s.cand + (co + rank * 1440 + 64 - cq * 12)), "r"((norm2(h4, sv.x, rh, rl) & 0xBFFFBFFFu) | par) : "memory");
            }
            __syncwarp();
        }
        {
            const uint2 sa = lds64(sb + SM_ST + tn * 8), sbb = lds64(sb + SM_ST + tn * 8 + 64);
            const uint32_t rha = __byte_perm(sa.y, 0, 0x1010), rla = __byte_perm(sa.y, 0, 0x3232);
            const uint32_t rhb = __byte_perm(sbb.y, 0, 0x1010), rlb = __byte_perm(sbb.y, 0, 0x3232);
#pragma unroll
            for (int i = 0; i < 5; i++) { ha[i] = badd2(ha[i], norm2(ha[i], sa.x, rha, rla)); hb[i] = badd2(hb[i], norm2(hb[i], sbb.x, rhb, rlb)); }
            const uint32_t ota = sb + SM_XT + tn * 80;
            sts128(ota + cq * 16, ha[0], ha[1], ha[2], ha[3]); sts32(ota + 64 + cq * 4, ha[4]);
            sts128(ota + cq * 16 + 640, hb[0], hb[1], hb[2], hb[3]); sts32(ota + 704 + cq * 4, hb[4]);
            asm volatile("fence.proxy.async.shared::cta;" ::: "memory");
        }
        if (warp >= 8) {
            mbar_wait(mb + MB_KEY * 8);
            const uint32_t mk = lds32(sb + SM_RK - 256 + (tid >> 2) * 4);
            uint32_t rank = rank4<4>(sb + SM_RK + cq * 64, mk);
            rank += __shfl_xor_sync(~0u, rank, 1); rank += __shfl_xor_sync(~0u, rank, 2);
            if (rank < 8) sts64(sb + SM_SEL + rank * 8, mk, ((tid >> 2) - 64) * 1440);
        }
    }
    bar_sync(11, 640);
    STAMP(12);

    {
        const char* gp = (const char*)g_s.cand + (go + lds32(sb + SM_SEL + 4 + (tk & 7) * 8));
        uint4 hv = ld_rlx128(gp);
        if (warp < 8) loadA();
        if (warp < 18) {
            int n = 0;
            while ((((hv.x ^ par) | (hv.y ^ par) | (hv.z ^ par) | (hv.w ^ par)) & 0x40004000u) && ++n < SPIN_LIMIT) hv = ld_rlx128(gp);
            sts128(sb + SM_XS + tk * 16 + tid * 16, hv.x ^ par, hv.y ^ par, hv.z ^ par, hv.w ^ par);
        }
    }
    bar_sync(14, 672);
    STAMP(13);
    {
        float c0[4] = {0.f, 0.f, 0.f, 0.f}, c1[4] = {0.f, 0.f, 0.f, 0.f}, c2[4] = {0.f, 0.f, 0.f, 0.f};
        const uint32_t ba = sb + SM_XS + mr * 1168 + mi * 16 + 288 * kq;
        uint32_t b[5][4];
#pragma unroll
        for (int s = 0; s < 5; s++) ldsm4(b[s], ba + s * 64);
        mma_bf16(c0, A[0][0], A[0][1], A[0][2], A[0][3], b[0][0], b[0][1]);
        mma_bf16(c1, A[1][0], A[1][1], A[1][2], A[1][3], b[0][2], b[0][3]);
        mma_bf16(c2, A[2][0], A[2][1], A[2][2], A[2][3], b[1][0], b[1][1]);
        mma_bf16(c0, A[3][0], A[3][1], A[3][2], A[3][3], b[1][2], b[1][3]);
        mma_bf16(c1, A[4][0], A[4][1], A[4][2], A[4][3], b[2][0], b[2][1]);
        mma_bf16(c2, A[5][0], A[5][1], A[5][2], A[5][3], b[2][2], b[2][3]);
        mma_bf16(c0, A[6][0], A[6][1], A[6][2], A[6][3], b[3][0], b[3][1]);
        mma_bf16(c1, A[7][0], A[7][1], A[7][2], A[7][3], b[3][2], b[3][3]);
        mma_bf16(c2, A[8][0], A[8][1], A[8][2], A[8][3], b[4][0], b[4][1]);
        sts128f(sb + SM_RED + tid * 16, c0[0] + c1[0] + c2[0], c0[1] + c1[1] + c2[1], c0[2] + c1[2] + c2[2], c0[3] + c1[3] + c2[3]);
    }
    bar_sync(1 + mt, 128);
    if (mt < nslot) {
        const uint32_t ra = sb + SM_RED + mt * 512 + lane * 16;
        const float4 p0 = lds128f(ra), p1 = lds128f(ra + 2560), p2 = lds128f(ra + 5120), p3 = lds128f(ra + 7680);
        const float g0 = bfr(((p0.x + p1.x) + (p2.x + p3.x)) * 64.f), g1 = bfr(((p0.y + p1.y) + (p2.y + p3.y)) * 64.f);
        const uint32_t sg = pack_bf16(g0 * rcpf(1.f + ex2f(g0 * -1.4426950408889634f)), g1 * rcpf(1.f + ex2f(g1 * -1.4426950408889634f)));
        const uint32_t gu = bmul2(sg, pack_bf16(((p0.z + p1.z) + (p2.z + p3.z)) * 64.f, ((p0.w + p1.w) + (p2.w + p3.w)) * 64.f));
#pragma unroll
        for (int i = 0; i < 2; i++) {
            const uint32_t rb_ = mapa(sb, 2 * kq + i);
            st_async1(rb_ + (SM_GU + (q * nslot + mt) * 128) + lane * 4, gu, rb_ + (SM_MB + MB_GU * 8));
        }
    }
    mbar_wait(mb + MB_W2 * 8);
    {
        const uint32_t aa = sb + (8 * (mi >> 1) + mr) * 144 + (mi & 1) * 16 + (SM_FAR + 2304 * kq + mt * 32);
#pragma unroll
        for (int s = 0; s < 5; s++) ldsm4t(A[s], aa + s * FAR_SZ);
    }
    const bool red = warp < 6;
    const uint32_t ft = red ? (unsigned)tid / 24u : (unsigned)(tid >> 4) & 7u, fj = red ? 24 * q + tid - ft * 24 : d0 / 3 + (lane & 15);
    const uint32_t key = lds32(sb + SM_SEL + ft * 8), k16 = key << 5;
    float sig = bfr(rcpf(1.f + ex2f(__uint_as_float((k16 ^ (~((int)k16 >> 31) | 0x80000000u)) & 0xFFFF0000u) * -1.4426950408889634f)));
    uint32_t ra2 = sb + SM_RED2 + tid * 12 + ft * 16, fo = (ft * 192 + fj) * 16, oo = ((~key & 2047) * D_ + 3 * fj) * 2;
    PIN(ra2); PIN(fo); PIN(oo);
    {
        uint32_t ba = sb + (SM_GU + 256 * kq) + (lane & 15) * 16 + (lane >> 4) * 1024, wa = sb + (SM_RED2 + kq * 2432 + mt * 64) + g * 4 + cq * 608;
        PIN(ba); PIN(wa);
        mbar_wait(mb + MB_GU * 8);
        float c0[4] = {0.f, 0.f, 0.f, 0.f}, c1[4] = {0.f, 0.f, 0.f, 0.f}, c2[4] = {0.f, 0.f, 0.f, 0.f};
        uint32_t b[2][4], b8, b9;
        ldsm4t(b[0], ba); ldsm4t(b[1], ba + 2048); ldsm2t(b8, b9, ba + 4096);
        mma_bf16(c0, A[0][0], A[0][1], A[0][2], A[0][3], b[0][0], b[0][1]);
        mma_bf16(c1, A[1][0], A[1][1], A[1][2], A[1][3], b[0][2], b[0][3]);
        if (nslot == 5) {
            mma_bf16(c2, A[4][0], A[4][1], A[4][2], A[4][3], b8, b9);
            mma_bf16(c0, A[2][0], A[2][1], A[2][2], A[2][3], b[1][0], b[1][1]);
            mma_bf16(c1, A[3][0], A[3][1], A[3][2], A[3][3], b[1][2], b[1][3]);
        }
        stsf(wa, c0[0] + c1[0] + c2[0]); stsf(wa + 304, c0[1] + c1[1] + c2[1]);
        if (mt < 4) { stsf(wa + 32, c0[2] + c1[2] + c2[2]); stsf(wa + 336, c0[3] + c1[3] + c2[3]); }
    }
    if (warp < 10) {
        float v[3], cnt = 3.f;
        if (red) {
            bar_sync(6, 640);
            STAMP(14);
#pragma unroll
            for (int i = 0; i < 3; i++) v[i] = ((ldsf(ra2 + i * 4) + ldsf(ra2 + i * 4 + 2432)) + (ldsf(ra2 + i * 4 + 4864) + ldsf(ra2 + i * 4 + 7296))) * sig;
        } else {
            bar_arrive(6, 640);
            cnt = 0.f;
#pragma unroll
            for (int i = 0; i < 3; i++) {
                const uint32_t cl = 3 * fj + i - d0;
                const bool ok = cl < 8 * nslot && ((~key >> 3) & 7) == q;
                v[i] = ok ? __uint_as_float(lds16(sb + SM_XT + tslot(~key) * 80 + (cl & 63) * 2) << 16) : 0.f;
                if (ok) cnt += 1.f;
            }
            mbar_wait(mb + MB_OUT * 8);
        }
        if (cnt != 0.f) {
            float x, y, z, w;
            asm volatile("atom.relaxed.gpu.global.add.v4.f32 {%0,%1,%2,%3}, [%4], {%5,%6,%7,%8};" : "=f"(x), "=f"(y), "=f"(z), "=f"(w)
                         : "l"((char*)g_s.fin + fo), "f"(v[0]), "f"(v[1]), "f"(v[2]), "f"(cnt) : "memory");
            if (w + cnt == 3.f * (NCL + 1)) {
                __nv_bfloat16* op = (__nv_bfloat16*)((char*)prm.out + oo);
                op[0] = __float2bfloat16(x + v[0]); op[1] = __float2bfloat16(y + v[1]); op[2] = __float2bfloat16(z + v[2]);
            }
        }
    } else bar_arrive(6, 640);
    STAMP(15);
}

typedef CUresult (*EncodeFn)(CUtensorMap*, CUtensorMapDataType, cuuint32_t, void*, const cuuint64_t*, const cuuint64_t*,
                             const cuuint32_t*, const cuuint32_t*, CUtensorMapInterleave, CUtensorMapSwizzle,
                             CUtensorMapL2promotion, CUtensorMapFloatOOBfill);

void make_map(EncodeFn fn, CUtensorMap* tm, const void* p, int cols, int rows, int bc, int br) {
    cuuint64_t dims[2] = {(cuuint64_t)cols, (cuuint64_t)rows};
    cuuint64_t strides[1] = {(cuuint64_t)cols * 2};
    cuuint32_t box[2] = {(cuuint32_t)bc, (cuuint32_t)br};
    cuuint32_t es[2] = {1, 1};
    fn(tm, CU_TENSOR_MAP_DATA_TYPE_BFLOAT16, 2, const_cast<void*>(p), dims, strides, box, es, CU_TENSOR_MAP_INTERLEAVE_NONE,
       CU_TENSOR_MAP_SWIZZLE_NONE, (CUtensorMapL2promotion)L2PROMO, CU_TENSOR_MAP_FLOAT_OOB_FILL_NONE);
}

void make_map3(EncodeFn fn, CUtensorMap* tm, const void* p) {
    cuuint64_t dims[3] = {(cuuint64_t)D_, 64, 32};
    cuuint64_t strides[2] = {(cuuint64_t)D_ * 2, (cuuint64_t)D_ * 128};
    cuuint32_t box[3] = {40, 8, 32};
    cuuint32_t es[3] = {1, 1, 1};
    fn(tm, CU_TENSOR_MAP_DATA_TYPE_BFLOAT16, 3, const_cast<void*>(p), dims, strides, box, es, CU_TENSOR_MAP_INTERLEAVE_NONE,
       CU_TENSOR_MAP_SWIZZLE_NONE, CU_TENSOR_MAP_L2_PROMOTION_NONE, CU_TENSOR_MAP_FLOAT_OOB_FILL_NONE);
}

void make_map5(EncodeFn fn, CUtensorMap* tm, const void* p) {
    cuuint64_t dims[5] = {(cuuint64_t)D_, 2, 4, 4, 64};
    cuuint64_t strides[4] = {(cuuint64_t)D_ * 128, (cuuint64_t)D_ * 1024, (cuuint64_t)D_ * 256, (cuuint64_t)D_ * 2};
    cuuint32_t box[5] = {40, 2, 4, 4, 8};
    cuuint32_t es[5] = {1, 1, 1, 1, 1};
    fn(tm, CU_TENSOR_MAP_DATA_TYPE_BFLOAT16, 5, const_cast<void*>(p), dims, strides, box, es, CU_TENSOR_MAP_INTERLEAVE_NONE,
       CU_TENSOR_MAP_SWIZZLE_NONE, CU_TENSOR_MAP_L2_PROMOTION_NONE, CU_TENSOR_MAP_FLOAT_OOB_FILL_NONE);
}

}

extern "C" void kernel_launch(void* const* d_in, const int* in_sizes, int n_in, void* d_out, int out_size) {
    (void)in_sizes; (void)n_in; (void)out_size;
    void* fp = nullptr;
    cudaDriverEntryPointQueryResult qr;
    cudaGetDriverEntryPoint("cuTensorMapEncodeTiled", &fp, cudaEnableDefault, &qr);
    EncodeFn fn = (EncodeFn)fp;
    CUtensorMap tmG, tmU, tmD, tmO, tmX;
    make_map3(fn, &tmX, d_in[0]);
    make_map(fn, &tmG, d_in[11], F_, D_, 40, 48);
    make_map(fn, &tmU, d_in[12], F_, D_, 40, 48);
    make_map(fn, &tmD, d_in[13], D_, F_, 72, 64);
    make_map5(fn, &tmO, d_out);
    Params p;
    p.x = (const unsigned short*)d_in[0];
    for (int i = 0; i < 6; i++) p.prm6[i] = (const unsigned short*)d_in[1 + i];
    p.logdt = (const unsigned short*)d_in[7]; p.dskip = (const unsigned short*)d_in[8];
    p.wr = (const unsigned short*)d_in[10];
    for (int i = 0; i < 3; i++) p.w3[i] = (const char*)d_in[11 + i];
    p.out = (__nv_bfloat16*)d_out;
    p.zero = 0;
    cudaGetSymbolAddress((void**)&p.gs, g_s);
    cudaFuncSetAttribute(fused_kernel, cudaFuncAttributeMaxDynamicSharedMemorySize, SM_TOTAL);
    fused_kernel<<<NCTA, NTHR, SM_TOTAL>>>(p, tmG, tmU, tmD, tmO, tmX);
}
```

```cpp
#include <cuda_runtime.h>
#include <cuda_bf16.h>
#include <cuda_fp16.h>
#include <cuda.h>
#include <stdint.h>

namespace {

constexpr int L_ = 2048, D_ = 576, F_ = 4608;
constexpr int NCL = 15, CS = 8, NCTA = NCL * CS, NTHR = 768;
#define PACE_NS 100
#define PRE_N 0
#define PRE_NS 200
#define FIN_DELAY 0
#define RED_DELAY 0
#define NO_OUT 0
#define XSPLIT 3
#define NORM_EARLY 0
#define NEAR_DB 1
#define STREAM_T 0
#define L2PROMO 2
#define GAP_NS 0
#define ROW_DELAY 1
constexpr int SPIN_LIMIT = 1 << 22;

constexpr int SM_WG   = 0;
constexpr int SM_WU   = 46080;
constexpr int YP = 3376, YS = 672;
constexpr int UP = 3376, US = 672;
constexpr int SM_XT   = 92160;
constexpr int SM_U    = SM_XT + 8 * YP;
constexpr int SM_FAR  = SM_U + 8 * UP;
constexpr int FAR_SZ  = 12416;
constexpr int F_E5 = 0, F_O5 = 1536, F_E3 = 3088, F_O3 = 4624, F_E7 = 6176, F_E2 = F_E7 + 1024, F_E9 = F_E7 + 2048,
              F_H = 3088, F_O7 = F_E7 + F_H, F_O2 = F_E2 + F_H, F_O9 = F_E9 + F_H;
constexpr int SM_P    = SM_FAR + 5 * FAR_SZ;
constexpr int PN_SZ = 584 * 4, SM_PN = SM_P + 64 * 4;
constexpr int P_GS = 48 * 4, P_H7 = 192 * 4, P_HS = 72 * 4;
constexpr int PF_SZ = (192 + 216) * 4, SM_PF = SM_PN + 5 * PN_SZ + 32;
constexpr int SM_MISC = SM_PF + 5 * PF_SZ;
constexpr int SM_ST   = SM_MISC;
constexpr int SM_RK   = SM_ST + 2048;
constexpr int SM_SEL  = SM_RK + 256;
constexpr int SM_KG   = SM_SEL + 64;
constexpr int SM_SC   = SM_KG + 160;
constexpr int SM_DW   = SM_SC + 32;
constexpr int SM_MB   = SM_DW + 160;
constexpr int SM_TOTAL = SM_MB + 128;
constexpr int SM_ROW  = SM_XT - 20736;
constexpr int SM_XTL  = SM_ROW - 20480;
constexpr int SM_RED2 = SM_WG;
constexpr int SM_HT   = SM_P - 512;
constexpr int SM_KEY  = SM_FAR + 9216 + 128;
constexpr int SM_CAND = SM_KEY + 1024;
constexpr int SM_FIN  = SM_FAR + FAR_SZ + 9216 + 128;
constexpr int SM_HS   = SM_FIN + 2400;
constexpr int SM_XS   = SM_U;
constexpr int SM_GU   = SM_XS + 9344;
constexpr int SM_RED  = SM_GU + 5632;
static_assert(F_O9 + 1024 <= FAR_SZ && FAR_SZ % 128 == 0, "far overflow");
static_assert(SM_RED + 10240 <= SM_FAR && SM_HS + 128 <= SM_FAR + 2 * FAR_SZ && SM_HT + 20496 <= SM_MISC, "alias overflow");
static_assert(SM_TOTAL <= 232448, "smem overflow");
static_assert(SM_FAR % 128 == 0 && SM_XT % 128 == 0 && SM_XTL % 128 == 0 && SM_P % 16 == 0 && SM_MISC % 16 == 0 && SM_MB % 8 == 0 && SM_HS % 16 == 0, "align");

enum { MB_X = 0, MB_W1 = 5, MB_W2 = 6, MB_KEY = 7, MB_GU = 8, MB_Y = 9, MB_OUT = 10, MB_T = 11, MB_R = 12 };

struct __align__(128) Scratch {
    unsigned epoch, zcnt, pad[30];
    uint4  st1[L_ * 2];
    float4 acc[L_];
    uint4  cand[64 * NCL * 6];
    float4 fin[8 * 192 + 24];
};
__device__ Scratch g_s;
#define STAMP(i)

__device__ __forceinline__ uint32_t mapa(uint32_t a, uint32_t r) { uint32_t d; asm("mapa.shared::cluster.u32 %0, %1, %2;" : "=r"(d) : "r"(a), "r"(r)); return d; }
__device__ __forceinline__ void mbar_wait(uint32_t mb) {
    asm volatile("{ .reg .pred p, q; .reg .u32 n; mov.u32 n, 0;\n"
                 "W_%=: mbarrier.try_wait.parity.shared::cta.b64 p, [%0], 0; add.u32 n, n, 1; setp.lt.and.u32 q, n, 65536, !p; @q bra W_%=; }" :: "r"(mb) : "memory");
}
__device__ __forceinline__ void arm(uint32_t mb, uint32_t bytes) { asm volatile("mbarrier.arrive.expect_tx.shared::cta.b64 _, [%0], %1;" :: "r"(mb), "r"(bytes) : "memory"); }
__device__ __forceinline__ void bar_sync(int id, int n) { asm volatile("bar.sync %0, %1;" :: "r"(id), "r"(n) : "memory"); }
__device__ __forceinline__ void bar_arrive(int id, int n) { asm volatile("bar.arrive %0, %1;" :: "r"(id), "r"(n) : "memory"); }
__device__ __forceinline__ uint32_t lds16(uint32_t a) { unsigned short v; asm volatile("ld.shared.u16 %0, [%1];" : "=h"(v) : "r"(a) : "memory"); return v; }
__device__ __forceinline__ uint32_t lds32(uint32_t a) { uint32_t v; asm volatile("ld.shared.u32 %0, [%1];" : "=r"(v) : "r"(a) : "memory"); return v; }
__device__ __forceinline__ uint2 lds64(uint32_t a) { uint2 v; asm volatile("ld.shared.v2.u32 {%0,%1}, [%2];" : "=r"(v.x), "=r"(v.y) : "r"(a) : "memory"); return v; }
__device__ __forceinline__ float ldsf(uint32_t a) { float v; asm volatile("ld.shared.f32 %0, [%1];" : "=f"(v) : "r"(a) : "memory"); return v; }
__device__ __forceinline__ uint4 lds128(uint32_t a) { uint4 v; asm volatile("ld.shared.v4.u32 {%0,%1,%2,%3}, [%4];" : "=r"(v.x), "=r"(v.y), "=r"(v.z), "=r"(v.w) : "r"(a) : "memory"); return v; }
__device__ __forceinline__ float4 lds128f(uint32_t a) { float4 v; asm volatile("ld.shared.v4.f32 {%0,%1,%2,%3}, [%4];" : "=f"(v.x), "=f"(v.y), "=f"(v.z), "=f"(v.w) : "r"(a) : "memory"); return v; }
__device__ __forceinline__ void sts16(uint32_t a, uint32_t v) { asm volatile("{ .reg .b16 l, h; mov.b32 {l, h}, %1; st.shared.b16 [%0], l; }" :: "r"(a), "r"(v) : "memory"); }
__device__ __forceinline__ void sts32(uint32_t a, uint32_t v) { asm volatile("st.shared.u32 [%0], %1;" :: "r"(a), "r"(v) : "memory"); }
__device__ __forceinline__ void sts64(uint32_t a, uint32_t x, uint32_t y) { asm volatile("st.shared.v2.u32 [%0], {%1,%2};" :: "r"(a), "r"(x), "r"(y) : "memory"); }
__device__ __forceinline__ void stsf(uint32_t a, float v) { asm volatile("st.shared.f32 [%0], %1;" :: "r"(a), "f"(v) : "memory"); }
__device__ __forceinline__ void sts128(uint32_t a, uint32_t x, uint32_t y, uint32_t z, uint32_t w) { asm volatile("st.shared.v4.u32 [%0], {%1,%2,%3,%4};" :: "r"(a), "r"(x), "r"(y), "r"(z), "r"(w) : "memory"); }
__device__ __forceinline__ void sts128f(uint32_t a, float x, float y, float z, float w) { asm volatile("st.shared.v4.f32 [%0], {%1,%2,%3,%4};" :: "r"(a), "f"(x), "f"(y), "f"(z), "f"(w) : "memory"); }
__device__ __forceinline__ void ldsm4(uint32_t (&r)[4], uint32_t a) { asm volatile("ldmatrix.sync.aligned.m8n8.x4.shared.b16 {%0,%1,%2,%3}, [%4];" : "=r"(r[0]), "=r"(r[1]), "=r"(r[2]), "=r"(r[3]) : "r"(a) : "memory"); }
__device__ __forceinline__ void ldsm4t(uint32_t (&r)[4], uint32_t a) { asm volatile("ldmatrix.sync.aligned.m8n8.x4.trans.shared.b16 {%0,%1,%2,%3}, [%4];" : "=r"(r[0]), "=r"(r[1]), "=r"(r[2]), "=r"(r[3]) : "r"(a) : "memory"); }
__device__ __forceinline__ void ldsm2t(uint32_t& r0, uint32_t& r1, uint32_t a) { asm volatile("ldmatrix.sync.aligned.m8n8.x2.trans.shared.b16 {%0,%1}, [%2];" : "=r"(r0), "=r"(r1) : "r"(a) : "memory"); }
__device__ __forceinline__ void stsm4t(uint32_t a, uint32_t r0, uint32_t r1, uint32_t r2, uint32_t r3) { asm volatile("stmatrix.sync.aligned.m8n8.x4.trans.shared.b16 [%0], {%1,%2,%3,%4};" :: "r"(a), "r"(r0), "r"(r1), "r"(r2), "r"(r3) : "memory"); }
__device__ __forceinline__ void stsm4(uint32_t a, uint32_t r0, uint32_t r1, uint32_t r2, uint32_t r3) { asm volatile("stmatrix.sync.aligned.m8n8.x4.shared.b16 [%0], {%1,%2,%3,%4};" :: "r"(a), "r"(r0), "r"(r1), "r"(r2), "r"(r3) : "memory"); }
__device__ __forceinline__ void stsm2t(uint32_t a, uint32_t r0, uint32_t r1) { asm volatile("stmatrix.sync.aligned.m8n8.x2.trans.shared.b16 [%0], {%1,%2};" :: "r"(a), "r"(r0), "r"(r1) : "memory"); }
__device__ __forceinline__ uint4 ldg128(const void* p) { uint4 v; asm volatile("ld.global.nc.v4.u32 {%0,%1,%2,%3}, [%4];" : "=r"(v.x), "=r"(v.y), "=r"(v.z), "=r"(v.w) : "l"(p)); return v; }
__device__ __forceinline__ uint32_t ldg32(const void* p) { uint32_t v; asm volatile("ld.global.nc.u32 %0, [%1];" : "=r"(v) : "l"(p)); return v; }
__device__ __forceinline__ uint32_t ldg16(const void* p) { unsigned short v; asm volatile("ld.global.nc.u16 %0, [%1];" : "=h"(v) : "l"(p)); return v; }
__device__ __forceinline__ uint32_t opaque(uint32_t v) { uint32_t r; asm volatile("mov.b32 %0, %1;" : "=r"(r) : "r"(v)); return r; }
__device__ __forceinline__ void mma_f16(float (&d)[4], const uint32_t (&a)[4], uint32_t b0, uint32_t b1) {
    asm volatile("mma.sync.aligned.m16n8k16.row.col.f32.f16.f16.f32 {%0,%1,%2,%3}, {%4,%5,%6,%7}, {%8,%9}, {%0,%1,%2,%3};"
        : "+f"(d[0]), "+f"(d[1]), "+f"(d[2]), "+f"(d[3]) : "r"(a[0]), "r"(a[1]), "r"(a[2]), "r"(a[3]), "r"(b0), "r"(b1));
}
__device__ __forceinline__ void mma_bf16(float (&d)[4], uint32_t a0, uint32_t a1, uint32_t a2, uint32_t a3, uint32_t b0, uint32_t b1) {
    asm volatile("mma.sync.aligned.m16n8k16.row.col.f32.bf16.bf16.f32 {%0,%1,%2,%3}, {%4,%5,%6,%7}, {%8,%9}, {%0,%1,%2,%3};"
        : "+f"(d[0]), "+f"(d[1]), "+f"(d[2]), "+f"(d[3]) : "r"(a0), "r"(a1), "r"(a2), "r"(a3), "r"(b0), "r"(b1));
}
__device__ __forceinline__ void mma_bf16_k8(float (&d)[4], uint32_t a0, uint32_t a1, uint32_t b0) {
    asm volatile("mma.sync.aligned.m16n8k8.row.col.f32.bf16.bf16.f32 {%0,%1,%2,%3}, {%4,%5}, {%6}, {%0,%1,%2,%3};"
        : "+f"(d[0]), "+f"(d[1]), "+f"(d[2]), "+f"(d[3]) : "r"(a0), "r"(a1), "r"(b0));
}
__device__ __forceinline__ uint32_t pack_f16(float lo, float hi) { uint32_t r; asm("cvt.rn.f16x2.f32 %0, %1, %2;" : "=r"(r) : "f"(hi), "f"(lo)); return r; }
__device__ __forceinline__ uint32_t pack_bf16(float lo, float hi) { uint32_t r; asm("cvt.rn.bf16x2.f32 %0, %1, %2;" : "=r"(r) : "f"(hi), "f"(lo)); return r; }
__device__ __forceinline__ float bf_lo(uint32_t v) { return __uint_as_float(v << 16); }
__device__ __forceinline__ float bf_hi(uint32_t v) { return __uint_as_float(v & 0xFFFF0000u); }
__device__ __forceinline__ float bfr(float x) { return __uint_as_float(pack_bf16(0.f, x)); }
__device__ __forceinline__ uint32_t bsub2(uint32_t a, uint32_t b) { uint32_t r; asm("sub.rn.bf16x2 %0, %1, %2;" : "=r"(r) : "r"(a), "r"(b)); return r; }
__device__ __forceinline__ uint32_t badd2(uint32_t a, uint32_t b) { uint32_t r; asm("add.rn.bf16x2 %0, %1, %2;" : "=r"(r) : "r"(a), "r"(b)); return r; }
__device__ __forceinline__ uint32_t bmul2(uint32_t a, uint32_t b) { uint32_t r; asm("mul.rn.bf16x2 %0, %1, %2;" : "=r"(r) : "r"(a), "r"(b)); return r; }
__device__ __forceinline__ uint32_t bfma2(uint32_t a, uint32_t b, uint32_t c) { uint32_t r; asm("fma.rn.bf16x2 %0, %1, %2, %3;" : "=r"(r) : "r"(a), "r"(b), "r"(c)); return r; }
__device__ __forceinline__ uint32_t hadd2(uint32_t a, uint32_t b) { uint32_t r; asm("add.rn.f16x2 %0, %1, %2;" : "=r"(r) : "r"(a), "r"(b)); return r; }
__device__ __forceinline__ uint32_t hmul2(uint32_t a, uint32_t b) { uint32_t r; asm("mul.rn.f16x2 %0, %1, %2;" : "=r"(r) : "r"(a), "r"(b)); return r; }
__device__ __forceinline__ uint32_t hfma2(uint32_t a, uint32_t b, uint32_t c) { uint32_t r; asm("fma.rn.f16x2 %0, %1, %2, %3;" : "=r"(r) : "r"(a), "r"(b), "r"(c)); return r; }
__device__ __forceinline__ uint32_t hneg2(uint32_t a) { uint32_t r; asm("neg.f16x2 %0, %1;" : "=r"(r) : "r"(a)); return r; }
__device__ __forceinline__ float rcpf(float x) { float r; asm("rcp.approx.ftz.f32 %0, %1;" : "=f"(r) : "f"(x)); return r; }
__device__ __forceinline__ float sqrta(float x) { float r; asm("sqrt.approx.ftz.f32 %0, %1;" : "=f"(r) : "f"(x)); return r; }
__device__ __forceinline__ float ex2f(float x) { float r; asm("ex2.approx.ftz.f32 %0, %1;" : "=f"(r) : "f"(x)); return r; }
__device__ __forceinline__ void st_async4(uint32_t a, uint32_t x, uint32_t y, uint32_t z, uint32_t w, uint32_t mb) {
    asm volatile("st.async.shared::cluster.mbarrier::complete_tx::bytes.v4.u32 [%0], {%1,%2,%3,%4}, [%5];" :: "r"(a), "r"(x), "r"(y), "r"(z), "r"(w), "r"(mb) : "memory"); }
__device__ __forceinline__ void st_async1(uint32_t a, uint32_t x, uint32_t mb) {
    asm volatile("st.async.shared::cluster.mbarrier::complete_tx::bytes.u32 [%0], %1, [%2];" :: "r"(a), "r"(x), "r"(mb) : "memory"); }
__device__ __forceinline__ unsigned ld_rlx(const void* p) { unsigned v; asm volatile("ld.relaxed.gpu.global.u32 %0, [%1];" : "=r"(v) : "l"(p) : "memory"); return v; }
__device__ __forceinline__ unsigned ld_acq(const void* p) { unsigned v; asm volatile("ld.acquire.gpu.global.u32 %0, [%1];" : "=r"(v) : "l"(p) : "memory"); return v; }
__device__ __forceinline__ uint2 ld_rlx64(const void* p) { unsigned long long v; asm volatile("ld.relaxed.gpu.global.u64 %0, [%1];" : "=l"(v) : "l"(p) : "memory"); return make_uint2((unsigned)v, (unsigned)(v >> 32)); }
__device__ __forceinline__ void st_rlx64(void* p, unsigned lo, unsigned hi) { asm volatile("st.relaxed.gpu.global.u64 [%0], %1;" :: "l"(p), "l"((unsigned long long)lo | ((unsigned long long)hi << 32)) : "memory"); }
__device__ __forceinline__ void st_rlx128(void* p, uint32_t x, uint32_t y, uint32_t z, uint32_t w) {
    asm volatile("st.relaxed.gpu.global.v2.u64 [%0], {%1,%2};" :: "l"(p), "l"((unsigned long long)x | ((unsigned long long)y << 32)), "l"((unsigned long long)z | ((unsigned long long)w << 32)) : "memory"); }
__device__ __forceinline__ uint4 ld_rlx128(const void* p) { unsigned long long a, b; asm volatile("ld.relaxed.gpu.global.v2.u64 {%0,%1}, [%2];" : "=l"(a), "=l"(b) : "l"(p) : "memory"); return make_uint4((unsigned)a, (unsigned)(a >> 32), (unsigned)b, (unsigned)(b >> 32)); }
__device__ __forceinline__ void tma2d(uint32_t dst, const CUtensorMap* tm, int x, int y, uint32_t mb) {
    asm volatile("cp.async.bulk.tensor.2d.shared::cluster.global.mbarrier::complete_tx::bytes [%0], [%1, {%3, %4}], [%2];"
                 :: "r"(dst), "l"(tm), "r"(mb), "r"(x), "r"(y) : "memory");
}
__device__ __forceinline__ void cmul(float& xr, float& xi, float ar, float ai, float br, float bi) {
    const float r = fmaf(ar, br, -ai * bi), i = fmaf(ar, bi, ai * br); xr = r; xi = i;
}
__device__ __forceinline__ void csq(float& xr, float& xi, float ar, float ai) {
    const float r = fmaf(ar, ar, -ai * ai), i = (ar + ar) * ai; xr = r; xi = i;
}
__device__ __forceinline__ void cexp_s(float& zr, float& zi, float e2, float turns) {
    const float mag = ex2f(e2), r = (turns - rintf(turns)) * 6.283185307179586f;
    zr = mag * __cosf(r); zi = mag * __sinf(r);
}
__device__ __forceinline__ uint32_t ln_stats(float s1, float s2) {
    const float m = s1 * (1.f / D_);
    const float var = fmaxf(fmaf(s2, 1.f / D_, -m * m), 0.f);
    return pack_bf16(m, sqrta(bfr(bfr(var) + 1e-5f)));
}
__device__ __forceinline__ uint32_t rsplit(float rs) { const float h = bfr(rs); return pack_bf16(h, rs - h); }
__device__ __forceinline__ uint32_t norm2(uint32_t v, uint32_t m2, uint32_t rh2, uint32_t rl2) {
    const uint32_t dd = bsub2(v, m2);
    return bfma2(dd, rh2, bmul2(dd, rl2));
}
template <int N>
__device__ __forceinline__ uint32_t rank4(uint32_t a, uint32_t key) {
    uint32_t r0 = 0, r1 = 0, r2 = 0, r3 = 0;
#pragma unroll
    for (int i = 0; i < N; i++) {
        const uint4 o = lds128(a + i * 16);
        r0 += (key - o.x) >> 31; r1 += (key - o.y) >> 31; r2 += (key - o.z) >> 31; r3 += (key - o.w) >> 31;
    }
    return (r0 + r1) + (r2 + r3);
}
struct H2C { uint32_t r, i; };
__device__ __forceinline__ H2C splat(float r, float i) { H2C h; h.r = pack_f16(r, r); h.i = pack_f16(i, i); return h; }
__device__ __forceinline__ void expand4(uint32_t are, uint32_t aim, uint32_t R0, uint32_t R1, uint32_t I0, uint32_t I1, H2C m4) {
    sts128(are, R0, R1, hfma2(R0, m4.r, hneg2(hmul2(I0, m4.i))), hfma2(R1, m4.r, hneg2(hmul2(I1, m4.i))));
    sts128(aim, I0, I1, hfma2(R0, m4.i, hmul2(I0, m4.r)), hfma2(R1, m4.i, hmul2(I1, m4.r)));
}
__device__ __forceinline__ void expand8(uint32_t are, uint32_t aim, float sr, float si, float m1r, float m1i, float m2r, float m2i, H2C m4) {
    float r1, i1, r2, i2, r3, i3;
    cmul(r1, i1, sr, si, m1r, m1i); cmul(r2, i2, sr, si, m2r, m2i); cmul(r3, i3, r1, i1, m2r, m2i);
    expand4(are, aim, pack_f16(sr, r1), pack_f16(r2, r3), pack_f16(si, i1), pack_f16(i2, i3), m4);
}
__device__ __forceinline__ void put16(uint32_t a, uint32_t v) { sts16(a, v); sts16(a + 6, v); }

struct Params {
    const unsigned short *x, *prm6[6], *logdt, *dskip, *wr;
    const char* w3[3];
    __nv_bfloat16* out;
    Scratch* gs;
    unsigned zero;
};
__device__ __forceinline__ uint32_t tslot(uint32_t t) { return (t & 7) * 32 + ((t >> 4) & 24) + ((t >> 8) & 6) + ((t >> 6) & 1); }
#define CP(x) ((x) | zero)
#define PIN(x) asm volatile("or.b32 %0, %0, %1;" : "+r"(x) : "r"(zero))
__device__ __forceinline__ void wgmma32(float (&d)[4][4], const uint32_t (&a)[4], uint32_t dlo) {
    asm volatile("{ .reg .b64 ds; mov.b64 ds, {%20, %21};\n"
                 "wgmma.mma_async.sync.aligned.m64n32k16.f32.f16.f16 {%0,%1,%2,%3,%4,%5,%6,%7,%8,%9,%10,%11,%12,%13,%14,%15}, {%16,%17,%18,%19}, ds, 1, 1, 1, 0; }"
        : "+f"(d[0][0]), "+f"(d[0][1]), "+f"(d[0][2]), "+f"(d[0][3]), "+f"(d[1][0]), "+f"(d[1][1]), "+f"(d[1][2]), "+f"(d[1][3]),
          "+f"(d[2][0]), "+f"(d[2][1]), "+f"(d[2][2]), "+f"(d[2][3]), "+f"(d[3][0]), "+f"(d[3][1]), "+f"(d[3][2]), "+f"(d[3][3])
        : "r"(a[0]), "r"(a[1]), "r"(a[2]), "r"(a[3]), "r"(dlo), "n"(128 >> 4));
}

__global__ void __cluster_dims__(CS, 1, 1) __launch_bounds__(NTHR, 1)
fused_kernel(const __grid_constant__ Params prm, const __grid_constant__ CUtensorMap tmG, const __grid_constant__ CUtensorMap tmU,
             const __grid_constant__ CUtensorMap tmD, const __grid_constant__ CUtensorMap tmO, const __grid_constant__ CUtensorMap tmX)
{
    extern __shared__ __align__(1024) unsigned char smem[];
    const int tid = threadIdx.x, lane = tid & 31, warp = __shfl_sync(~0u, tid >> 5, 0);
    const int c = blockIdx.x >> 3, q = blockIdx.x & 7;
    const int nslot = (c < NCL - 1) ? 5 : 2;
    const int d0 = 40 * c;
    const uint32_t sb = opaque((uint32_t)__cvta_generic_to_shared(smem));
    const uint32_t mb = sb + SM_MB;
    Scratch& g_s = *prm.gs;
    const unsigned& zero = prm.zero;
    STAMP(0);

    if (warp >= 20) {
        unsigned epoch = 0;
        if (warp == 20) {
            if (lane == 0) {
#pragma unroll
                for (int i = 0; i < 13; i++)
                    asm volatile("mbarrier.init.shared::cta.b64 [%0], %1;" :: "r"(mb + i * 8), "r"((i == MB_R || i == MB_T) ? 2 : i == MB_Y ? 1 + 4 * nslot : 1) : "memory");
                asm volatile("fence.mbarrier_init.release.cluster;" ::: "memory");
                arm(mb + MB_W1 * 8, 92160); arm(mb + MB_W2 * 8, nslot * 9216); arm(mb + MB_KEY * 8, 256); arm(mb + MB_GU * 8, nslot * 1024); arm(mb + MB_T * 8, 20480);
                const int bytes = max(min(18, L_ - 18 * (int)blockIdx.x), 1) * (D_ * 2);
                arm(mb + MB_R * 8, bytes);
                if (!ROW_DELAY) asm volatile("cp.async.bulk.shared::cluster.global.mbarrier::complete_tx::bytes [%0], [%1], %2, [%3];"
                             :: "r"(sb + SM_ROW), "l"(prm.x + min(18 * (int)blockIdx.x, L_ - 1) * D_), "r"(bytes), "r"(mb + MB_R * 8) : "memory");
            }
            __syncwarp();
        } else if (warp == 22) {
            epoch = ld_rlx(&g_s.epoch);
            if (lane < 18 ? 18 * c + lane < 256 : lane < 31) (lane < 18 ? &g_s.acc[256 * q + 18 * c] : &g_s.fin[13 * (int)blockIdx.x - 18])[lane] = make_float4(0.f, 0.f, 0.f, 0.f);
        } else if (warp == 23 && lane == 0) asm volatile("prefetch.tensormap [%0];" :: "l"(&tmX) : "memory");
        asm volatile("barrier.cluster.arrive.relaxed.aligned;" ::: "memory");
        bar_sync(12, NTHR);
        if (warp == 22) {
            if (lane == 0) { sts32(sb + SM_SC + 28, epoch); asm volatile("mbarrier.arrive.shared::cta.b64 _, [%0];" :: "r"(mb + MB_R * 8) : "memory"); }
            epoch++;
            asm volatile("fence.acq_rel.gpu;" ::: "memory");
            __syncwarp();
            if (lane == 0) asm volatile("red.relaxed.gpu.global.add.u32 [%0], 1;" :: "l"(&g_s.zcnt) : "memory");
            STAMP(1);
            uint4 wv = make_uint4(0, 0, 0, 0), wv2 = ldg128((const uint4*)prm.wr + lane), wv3 = ldg128((const uint4*)prm.wr + 32 + lane);
            if (lane < 8) wv = ldg128((const uint4*)prm.wr + 64 + lane);
            if (lane < 5) {
                uint4 v = make_uint4(0, 0, 0, 0);
                if (lane < nslot) v = ldg128((const uint4*)(prm.wr + d0) + lane);
                sts128(sb + SM_DW + lane * 16, v.x, v.y, v.z, v.w);
            }
            __syncwarp();
            if (lane == 0) asm volatile("mbarrier.arrive.shared::cta.b64 _, [%0];" :: "r"(mb + MB_T * 8) : "memory");
            mbar_wait(mb + (MB_X + 1) * 8);
            const uint32_t old = (epoch & 1) ? 0u : 0x40004000u;
#pragma unroll
            for (int t = 0; t < 2; t++)
                if ((lane & 7) < 6) g_s.cand[((q * 8 + 4 * t + (lane >> 3)) * NCL + c) * 6 + (lane & 7)] = make_uint4(old, old, old, old);
            float a[4] = {0.f, 0.f, 0.f, 0.f};
            const uint32_t one = 0x3F803F80u;
            mma_bf16(a, one, one, one, one, wv.x, wv.y);  mma_bf16(a, one, one, one, one, wv.z, wv.w);
            mma_bf16(a, one, one, one, one, wv2.x, wv2.y); mma_bf16(a, one, one, one, one, wv2.z, wv2.w);
            mma_bf16(a, one, one, one, one, wv3.x, wv3.y); mma_bf16(a, one, one, one, one, wv3.z, wv3.w);
            float s = a[0] + a[1];
            s += __shfl_xor_sync(~0u, s, 1); s += __shfl_xor_sync(~0u, s, 2);
            stsf(sb + SM_SC + 24, s);
            __syncwarp();
            if (lane == 0) {
                int n = 0;
                while ((int)(ld_acq(&g_s.zcnt) - epoch * NCTA) < 0 && ++n < SPIN_LIMIT) __nanosleep(200);
                arm(mb + MB_Y * 8, 8 * 512 * nslot);
                if (blockIdx.x == 0) g_s.epoch = epoch;
            }
            STAMP(2);
            return;
        }
        if (warp == 21) {
            if (STREAM_T) { bar_arrive(13, 736); mbar_wait(mb + MB_T * 8); } else bar_sync(13, 736);
            if (GAP_NS) __nanosleep(GAP_NS);
#pragma unroll 1
            for (int i = 0; i < 24; i++) {
                if (i == 13) { bar_sync(15, 544); asm volatile("fence.proxy.async.shared::cta;" ::: "memory"); }
                if (lane == 0) tma2d(sb + SM_WG + i * 3840, i < 12 ? &tmG : &tmU, 320 * c + 8 * nslot * q, 48 * (i < 12 ? i : i - 12), mb + MB_W1 * 8);
                __nanosleep(PACE_NS);
            }
            STAMP(1);
            return;
        }
        if (warp == 20) {
            if (ROW_DELAY && lane == 0) {
                const long long t0 = clock64(); while (clock64() - t0 < ROW_DELAY) {}
                asm volatile("cp.async.bulk.shared::cluster.global.mbarrier::complete_tx::bytes [%0], [%1], %2, [%3];"
                             :: "r"(sb + SM_ROW), "l"(prm.x + min(18 * (int)blockIdx.x, L_ - 1) * D_), "r"(max(min(18, L_ - 18 * (int)blockIdx.x), 1) * (D_ * 2)), "r"(mb + MB_R * 8) : "memory");
            }
            __syncwarp();
            mbar_wait(mb + MB_R * 8);
            if (lane == 0) {
                asm volatile("cp.async.bulk.tensor.3d.shared::cluster.global.mbarrier::complete_tx::bytes [%0], [%1, {%3, %4, %5}], [%2];"
                             :: "r"(sb + SM_XTL), "l"(&tmX), "r"(mb + MB_T * 8), "r"(d0), "r"(8 * q), "r"(0) : "memory");
            }
            STAMP(6);
        }
        if (PRE_N && warp == 23) {
            mbar_wait(mb + MB_R * 8);
            const char* wp = prm.w3[0] + blockIdx.x * (PRE_N * 4096) + lane * 128;
#pragma unroll 1
            for (int i = 0; i < PRE_N; i++) { asm volatile("prefetch.global.L2 [%0];" :: "l"(wp + i * 4096) : "memory"); __nanosleep(PRE_NS); }
        }
        asm volatile("barrier.cluster.wait.aligned;" ::: "memory");
        bar_sync(13, 736);
        {
            const int gr = lane >> 2, pe = (lane & 3) * 2 + (warp & 1);
            const int s0 = gr ? 0 : XSPLIT, ns = gr ? min(XSPLIT, nslot) : nslot - XSPLIT;
            if (gr < 2 && ns > 0) {
                const int bytes = ns * YS - 160;
                if (pe == q) arm(mb + (MB_X + gr) * 8, 7 * bytes);
                else {
                    const uint32_t rb_ = mapa(sb, pe);
                    asm volatile("cp.async.bulk.shared::cluster.shared::cta.mbarrier::complete_tx::bytes [%0], [%1], %2, [%3];"
                                 :: "r"(rb_ + SM_U + 128 + q * UP + s0 * US), "r"(sb + SM_XT + 128 + pe * YP + s0 * YS), "r"(bytes), "r"(rb_ + SM_MB + (MB_X + gr) * 8) : "memory");
                }
            }
        }
        STAMP(1);
        if (warp == 23) {
#pragma unroll 1
            for (int kk = nslot - 1; kk >= 0; kk--) {
                __syncwarp();
                bar_sync(6 + kk, 160);
                if (lane == 0) { asm volatile("fence.proxy.async.shared::cta;" ::: "memory"); tma2d(sb + SM_FAR + kk * FAR_SZ, &tmD, 72 * q, 320 * c + 64 * kk, mb + MB_W2 * 8); }
            }
            return;
        }
        __syncwarp();
        bar_sync(14, 672);
        if (lane == 0) {
            if (!NO_OUT) asm volatile("cp.async.bulk.tensor.5d.global.shared::cta.bulk_group [%0, {%2, %4, %4, %4, %3}], [%1];" :: "l"(&tmO), "r"(sb + SM_XT), "r"(d0), "r"(8 * q), "r"(0) : "memory");
            asm volatile("cp.async.bulk.commit_group;" ::: "memory");
            asm volatile("cp.async.bulk.wait_group 0;" ::: "memory");
            asm volatile("fence.proxy.async.global;" ::: "memory");
            asm volatile("mbarrier.arrive.shared::cta.b64 _, [%0];" :: "r"(mb + MB_OUT * 8) : "memory");
        }
        STAMP(2);
        return;
    }

    const int g = lane >> 2, cq = lane & 3;
    const int k = warp >> 2, wq = warp & 3;
    const int trow = 18 * blockIdx.x + warp;
    const bool rowact = warp < 18 && trow < L_;
    const int dch = min(d0 + 8 * k + q, D_ - 1);
    uint32_t pv[6];
#pragma unroll
    for (int i = 0; i < 6; i++) pv[i] = ldg16(prm.prm6[i] + (uint32_t)(dch * 128 + wq * 32 + lane));
    const uint32_t pLdt = ldg16(prm.logdt + dch), pD = ldg16(prm.dskip + dch);
    const int tn = 16 * (warp & 15) + g;
    uint32_t xa[5], xb[5];
    asm volatile("barrier.cluster.arrive.relaxed.aligned;" ::: "memory");
    uint4* const st1p = &g_s.st1[(((trow >> 3) & 7) * 256 + ((trow >> 6) & 31) * 8 + (trow & 7)) * 2 + (lane >> 2)];
    const bool pub = rowact && (lane & 0x1B) == 0;
    if (pub) st_rlx128(st1p, 0, 0, 0, 0);
    {
        const uint32_t za = sb + SM_P + tid * 16;
        sts128(za, 0, 0, 0, 0);
        if (tid < (SM_MISC - SM_P) / 16 - 640) sts128(za + 10240, 0, 0, 0, 0);
        sts128(sb + SM_XT + ((tid >> 3) & 15) * YP + k * YS + (lane & 7) * 16, 0, 0, 0, 0);
    }
    bar_sync(12, NTHR);
    const uint32_t dep = lds32(sb + SM_P);
#define PV(x) __uint_as_float(__byte_perm(dep, x, 0x5410))
    STAMP(1);
    const uint32_t fb = sb + SM_FAR + k * FAR_SZ;
    const uint32_t pn = sb + SM_PN + k * PN_SZ, pf = sb + SM_PF + k * PF_SZ;
    unsigned epoch;
    {
        const uint32_t kb = fb + wq * 3072;
        const uint32_t kl = kb + lane * 16;
        uint32_t Af[4][4];
        float sr, si, z1r, z1i, z2r, z2i, z4r, z4i, hr, hi_;
        {
            const float dt = bfr(ex2f(PV(pLdt) * 1.4426950408889634f));
            const float e2 = dt * PV(pv[0]) * 1.4426950408889634f, an = dt * PV(pv[1]);
            cmul(sr, si, PV(pv[4]), PV(pv[5]), dt * PV(pv[2]), dt * PV(pv[3]));
            const unsigned E = min(max(__reduce_max_sync(~0u, __float_as_uint(fmaxf(fmaxf(fabsf(sr), fabsf(si)), fabsf(PV(pD)) * (1.f / 8192.f)))) >> 23, 1u), 253u);
            const float sc = __uint_as_float((254u - E) << 23);
            sr *= sc; si *= -sc;
            sts64(sb + SM_KG + warp * 8, E, __reduce_add_sync(~0u, __float2int_rn(sr * 16777216.f)));
            float ar, ai, br, bi, cr, ci, dr, di;
            { const float m = ex2f(e2 * 8.f); ar = m * __cosf(an * 8.f); ai = m * __sinf(an * 8.f); }
            csq(br, bi, ar, ai); csq(cr, ci, br, bi); csq(dr, di, cr, ci);
            const H2C m4 = splat(cr, ci);
            {
                float r3, i3;
                cmul(r3, i3, ar, ai, br, bi);
                expand4(kl, kl + 1024, pack_f16(1.f, ar), pack_f16(br, r3), pack_f16(0.f, ai), pack_f16(bi, i3), m4);
            }
            expand8(kl + 512, kl + 1536, dr, di, ar, ai, br, bi, m4);
            { const float m = ex2f(e2); z1r = m * __cosf(an); z1i = -m * __sinf(an); }
            cexp_s(hr, hi_, e2 * 128.f, an * (-128.f * 0.15915494309189535f));
            csq(z2r, z2i, z1r, z1i); csq(z4r, z4i, z2r, z2i);
        }
        __syncwarp();
#pragma unroll
        for (int ks = 0; ks < 4; ks++) ldsm4t(Af[ks], kb + (lane >> 3) * 512 + (lane & 7) * 16 + ks * 128);
        STAMP(2);
        mbar_wait(mb + MB_R * 8);
        epoch = lds32(sb + SM_SC + 28) + 1;
        {
            float a[4] = {0.f, 0.f, 0.f, 0.f}, b[4] = {0.f, 0.f, 0.f, 0.f};
            uint32_t rx[9];
#pragma unroll
            for (int i = 0; i < 9; i++) rx[i] = lds32(sb + SM_ROW + warp * (D_ * 2) + lane * 4 + i * 128);
#pragma unroll
            for (int i = 0; i < 9; i++) { if (i & 1) mma_bf16_k8(b, rx[i], 0x3F803F80u, rx[i]); else mma_bf16_k8(a, rx[i], 0x3F803F80u, rx[i]); }
            float s2 = (g & 1) ? a[1] + b[1] : a[0] + b[0], s1 = (a[2] + b[2]) + (a[3] + b[3]);
            s2 += __shfl_xor_sync(~0u, s2, 4); s1 += __shfl_xor_sync(~0u, s1, 1);
            s2 += __shfl_xor_sync(~0u, s2, 9); s1 += __shfl_xor_sync(~0u, s1, 2);
            s2 += __shfl_xor_sync(~0u, s2, 18);
            const uint32_t ms = ln_stats(s1, s2);
            if (pub) st_rlx128(st1p, ms, epoch, ms, epoch);
        }
        mbar_wait(mb + MB_R * 8);
        const uint32_t la = kb + ((lane >> 3) & 1) * 512 + (lane >> 4) * 128 + (lane & 7) * 16;
        uint32_t kp[5][2], b0[4], b1[4], b2[4], b3[4];
        auto mm2 = [&](int t) {
            float a0[4] = {0.f, 0.f, 0.f, 0.f}, a1[4] = {0.f, 0.f, 0.f, 0.f};
            mma_f16(a0, Af[0], b0[0], b0[1]); mma_f16(a1, Af[0], b2[0], b2[1]); mma_f16(a0, Af[1], b0[2], b0[3]); mma_f16(a1, Af[1], b2[2], b2[3]);
            mma_f16(a0, Af[2], b1[0], b1[1]); mma_f16(a1, Af[2], b3[0], b3[1]); mma_f16(a0, Af[3], b1[2], b1[3]); mma_f16(a1, Af[3], b3[2], b3[3]);
            kp[t][0] = pack_f16(a0[1], a0[0]); kp[t][1] = pack_f16(a0[3], a0[2]); kp[t + 1][0] = pack_f16(a1[1], a1[0]); kp[t + 1][1] = pack_f16(a1[3], a1[2]);
        };
        cmul(sr, si, sr, si, z1r, z1i);
        {
            const H2C h4 = splat(z4r, z4i);
            expand8(kl, kl + 512, sr, si, z1r, z1i, z2r, z2i, h4);
            cmul(sr, si, sr, si, hr, hi_);
            expand8(kl + 1024, kl + 1536, sr, si, z1r, z1i, z2r, z2i, h4);
        }
        __syncwarp();
        ldsm4t(b0, la); ldsm4t(b1, la + 256); ldsm4t(b2, la + 1024); ldsm4t(b3, la + 1280);
        cmul(z1r, z1i, z1r, z1i, hr, hi_);
        cmul(sr, si, sr, si, z1r, z1i);
        expand8(kl, kl + 512, sr, si, z2r, z2i, z4r, z4i, splat(hr, hi_));
        mm2(0);
        STAMP(3);
        if (warp < 16) {
            const uint4* sp = &g_s.st1[(256 * q + tn) * 2];
            uint32_t va[5], vc[5];
            mbar_wait(mb + MB_T * 8);
            {
                const uint32_t xt = sb + SM_XTL + tn * 80;
                uint4 a4 = lds128(xt + cq * 16), b4 = lds128(xt + cq * 16 + 640);
                va[0] = a4.x; va[1] = a4.y; va[2] = a4.z; va[3] = a4.w; va[4] = lds32(xt + 64 + cq * 4);
                vc[0] = b4.x; vc[1] = b4.y; vc[2] = b4.z; vc[3] = b4.w; vc[4] = lds32(xt + 704 + cq * 4);
            }
            uint2 sa, sc; int n = 0;
            do { sa = ld_rlx64(sp); sc = ld_rlx64(sp + 16); } while ((sa.y != epoch || sc.y != epoch) && ++n < SPIN_LIMIT);
            STAMP(4);
            const uint32_t ra = rsplit(rcpf(bf_hi(sa.x))), rc = rsplit(rcpf(bf_hi(sc.x)));
            const uint32_t ma = __byte_perm(sa.x, 0, 0x1010), mc = __byte_perm(sc.x, 0, 0x1010);
            const uint32_t rha = __byte_perm(ra, 0, 0x1010), rla = __byte_perm(ra, 0, 0x3232), rhc = __byte_perm(rc, 0, 0x1010), rlc = __byte_perm(rc, 0, 0x3232);
#pragma unroll
            for (int i = 0; i < 5; i++) {
                va[i] = norm2(va[i], ma, rha, rla); va[i] = pack_f16(bf_lo(va[i]), bf_hi(va[i]));
                vc[i] = norm2(vc[i], mc, rhc, rlc); vc[i] = pack_f16(bf_lo(vc[i]), bf_hi(vc[i]));
            }
            const int d4 = 2 * (lane >> 3) + (lane & 1), d1_ = lane & 7;
            const uint32_t a4 = sb + warp * 32 + d4 * YP + (d4 == q ? SM_U + 128 : SM_XT + 128) + ((lane & 7) >> 1) * YS;
            const uint32_t a1 = sb + warp * 32 + d1_ * YP + (d1_ == q ? SM_U + 128 : SM_XT + 128) + 4 * YS + (lane & 8) * 2;
            stsm4t(a4, va[0], va[1], va[2], va[3]); stsm4t(a4 + 16, vc[0], vc[1], vc[2], vc[3]); stsm2t(a1, va[4], vc[4]);
        }
        asm volatile("fence.proxy.async.shared::cta;" ::: "memory");
        bar_arrive(13, 736);
        if (warp < 16) {
            const uint32_t xh = sb + SM_XTL + (64 * (g >> 1) + 32 * (warp & 1) + 8 * (g & 1) + (warp >> 1)) * 80;
            const uint4 a4 = lds128(xh + cq * 16), b4 = lds128(xh + cq * 16 + 1280);
            xa[0] = a4.x; xa[1] = a4.y; xa[2] = a4.z; xa[3] = a4.w; xa[4] = lds32(xh + 64 + cq * 4);
            xb[0] = b4.x; xb[1] = b4.y; xb[2] = b4.z; xb[3] = b4.w; xb[4] = lds32(xh + 1344 + cq * 4);
            bar_arrive(15, 544);
        }
        STAMP(5);
        csq(z1r, z1i, z1r, z1i);
        cmul(sr, si, sr, si, z1r, z1i);
        csq(z2r, z2i, hr, hi_);
        expand8(kl + 1024, kl + 1536, sr, si, z4r, z4i, hr, hi_, splat(z2r, z2i));
        __syncwarp();
        ldsm4t(b0, la); ldsm4t(b1, la + 256); ldsm4t(b2, la + 1024); ldsm4t(b3, la + 1280);
        csq(z1r, z1i, z1r, z1i);
        cmul(sr, si, sr, si, z1r, z1i);
        csq(z4r, z4i, z2r, z2i);
        expand8(kl, kl + 512, sr, si, hr, hi_, z2r, z2i, splat(z4r, z4i));
        mm2(2);
        __syncwarp();
        ldsm4t(b0, la); ldsm4t(b1, la + 256);
#pragma unroll
        for (int t = 0; t < 4; t++) sts64(kb + lane * 8 + 1024 + t * 256, kp[t][0], kp[t][1]);
        {
            float a0[4] = {0.f, 0.f, 0.f, 0.f}, a1[4] = {0.f, 0.f, 0.f, 0.f};
            mma_f16(a0, Af[0], b0[0], b0[1]); mma_f16(a1, Af[1], b0[2], b0[3]); mma_f16(a0, Af[2], b1[0], b1[1]); mma_f16(a1, Af[3], b1[2], b1[3]);
            sts64(kb + lane * 8 + 2048, pack_f16(a0[1] + a1[1], a0[0] + a1[0]), pack_f16(a0[3] + a1[3], a0[2] + a1[2]));
        }
        bar_sync(1 + k, 128);
        const uint4 m01 = lds128(sb + SM_KG + k * 32), m23 = lds128(sb + SM_KG + k * 32 + 16);
        const unsigned Em = max(max(m01.x, m01.z), max(m23.x, m23.z));
        const float f0 = __uint_as_float(max((int)(127 + m01.x - Em), 0) << 23), f1 = __uint_as_float(max((int)(127 + m01.z - Em), 0) << 23),
                    f2 = __uint_as_float(max((int)(127 + m23.x - Em), 0) << 23), f3 = __uint_as_float(max((int)(127 + m23.z - Em), 0) << 23);
        const uint32_t r0 = pack_f16(f0, f0), r1 = pack_f16(f1, f1), r2 = pack_f16(f2, f2), r3 = pack_f16(f3, f3);
        const uint32_t ra = fb + lane * 8 + wq * 256 + 1024;
        const uint2 p0 = lds64(ra), p1 = lds64(ra + 3072), p2 = lds64(ra + 6144), p3 = lds64(ra + 9216);
        uint32_t w0 = hadd2(hfma2(p0.x, r0, hmul2(p1.x, r1)), hfma2(p2.x, r2, hmul2(p3.x, r3)));
        uint32_t w1 = hadd2(hfma2(p0.y, r0, hmul2(p1.y, r1)), hfma2(p2.y, r2, hmul2(p3.y, r3)));
        const bool last = lane == 31;
        if (wq < 2) {
            const uint32_t rc = fb + lane * 8 + wq * 4 + 2048;
            const uint32_t w4 = hmul2(hadd2(hfma2(lds32(rc), r0, hmul2(lds32(rc + 3072), r1)), hfma2(lds32(rc + 6144), r2, hmul2(lds32(rc + 9216), r3))), 0x18001800u);
            const uint32_t ph = pf + (P_H7 + 16 * wq) + (g & 1) * (2 * P_HS) + cq * 64 + (g >> 1) * 4;
            put16(ph, w4 >> 16); put16(ph + 32, w4);
            const uint32_t pa = pn + (4 + 512 * wq) + lane * 8;
            sts16(pa, w0 >> 16); sts32(pa + 4, w0); sts16(pa + 10, w0);
            sts16(pa + 256, w1 >> 16); sts32(pa + 260, w1); sts16(pa + 266, w1);
            if (last) {
                sts32(sb + SM_SC + k * 4, Em * 0x00800080u);
                put16(wq ? pa + 264 : pn,
                      wq ? w1 : pack_f16(((float)(int)m01.y * f0 + (float)(int)m01.w * f1 + (float)(int)m23.y * f2 + (float)(int)m23.w * f3) * (1.f / 16777216.f)
                                         + __uint_as_float(pD << 16) * __uint_as_float((254u - Em) << 23), 0.f));
            }
        } else if (wq == 2) {
            const uint32_t pa = pn + 258 * 4 + (cq & 1) * 16 + (cq >> 1) * 512 + g * 32;
            if (last) { put16(pf, hmul2(w1, 0x18001800u)); w1 = hadd2(w1, hneg2(__byte_perm(w1, 0, 0x1010))); }
            const uint32_t b0 = __byte_perm(w0, 0, 0x1010), b1 = __byte_perm(w1, 0, 0x1010);
            sts16(pa, w0 >> 16); sts32(pa + 4, w0); sts64(pa + 8, b0, b0); sts16(pa + 18, w0);
            sts16(pa + 256, w1 >> 16); sts32(pa + 260, w1); sts64(pa + 264, b1, b1); sts16(pa + 274, w1);
        } else {
            const uint32_t pa = pf + ((g & 1) ? 3 * P_GS : P_GS) + cq * 32 + (g >> 1) * 4;
            const uint32_t pb = pa + ((g & 1) ? 4 - 3 * P_GS : P_GS);
            w0 = hmul2(w0, 0x18001800u); w1 = hmul2(w1, 0x18001800u);
            put16(pa, w0 >> 16); put16(pb, w0); put16(pa + 16, w1 >> 16); put16(pb + 16, w1);
            if (last) put16(pf + P_H7 + P_HS, w1);
        }
        bar_sync(1 + k, 128);
    }
    STAMP(6);

    asm volatile("barrier.cluster.wait.aligned;" ::: "memory");
    mbar_wait(mb + (MB_X + (k < XSPLIT || k >= nslot)) * 8);
    STAMP(7);
    if (k < nslot) {
        const int role = (wq + k) & 3;
        const uint32_t ub = sb + SM_U + k * US + 128;
        if (role) {
            const int r = (3 - role) * 32 + lane;
            const uint32_t a1 = ub + (r & 3) * (2 * UP) + (r >> 2) * 16, a0 = a1 + ((r & 3) ? -2 * UP : 6 * UP - 16);
            const uint4 q0 = lds128(a0), q1 = lds128(a0 + UP), q2 = lds128(a1), q3 = lds128(a1 + UP);
            const uint32_t U[16] = {q0.x, q0.y, q0.z, q0.w, q1.x, q1.y, q1.z, q1.w, q2.x, q2.y, q2.z, q2.w, q3.x, q3.y, q3.z, q3.w};
            uint32_t V[14], Q[14], R4[12], T[8];
#pragma unroll
            for (int i = 2; i < 14; i++) { V[i] = __byte_perm(U[i], U[i + 1], 0x5432); Q[i] = hadd2(U[i], V[i]); }
#pragma unroll
            for (int i = 2; i < 12; i++) R4[i] = hadd2(Q[i], Q[i + 1]);
            const uint32_t rb = fb + r * 16;
#pragma unroll
            for (int i = 0; i < 8; i++) T[i] = hadd2(V[5 + i], Q[6 + i]);
            sts128(rb + F_E3, T[0], T[1], T[2], T[3]); sts128(rb + F_O3 + 16, T[4], T[5], T[6], T[7]);
#pragma unroll
            for (int i = 0; i < 8; i++) T[i] = hadd2(R4[3 + i], U[5 + i]);
            sts128(rb + F_O5, T[0], T[1], T[2], T[3]); sts128(rb + F_E5, T[4], T[5], T[6], T[7]);
            if (role != 1) {
#pragma unroll
                for (int i = 0; i < 8; i++) T[i] = hadd2(T[i], hadd2(V[2 + i], V[5 + i]));
                sts128(rb + F_E7, T[0], T[1], T[2], T[3]); sts128(rb + F_O7, T[4], T[5], T[6], T[7]);
#pragma unroll
                for (int i = 0; i < 8; i++) T[i] = hadd2(R4[2 + i], hadd2(R4[4 + i], U[6 + i]));
                sts128(rb + F_O9, T[0], T[1], T[2], T[3]); sts128(rb + F_E9 + 16, T[4], T[5], T[6], T[7]);
                sts128(rb + F_E2, Q[6], Q[7], Q[8], Q[9]); sts128(rb + F_O2, Q[10], Q[11], Q[12], Q[13]);
            }
        } else if (lane < 8) {
            uint32_t v[5];
#pragma unroll
            for (int i = 0; i < 5; i++) { const int t = 6 + lane + i; v[i] = lds16(ub + 23 * 16 + (t < 16 ? (6 + (t >> 3)) * UP : 16) + (t & 7) * 2); }
            const uint32_t s = hadd2(hadd2(hadd2(v[0], v[1]), hadd2(v[2], v[3])), v[4]);
            sts16(fb + F_O5 + 96 * 16 + lane * 2, s);
            sts32(fb + (lane < 4 ? F_O3 : F_E9 - 16) + lane * 4, 0);
        }
        bar_sync(1 + k, 128);
        float acc[4][4];
        uint32_t Q[4][4];
        {
            const int h = role & 1, part = role >> 1;
            const uint32_t po = pf + (g - 2 * cq) * 4;
            float fa[7][4];
#pragma unroll
            for (int a = 0; a < 7; a++) fa[a][0] = fa[a][1] = fa[a][2] = fa[a][3] = 0.f;
            uint32_t B[3][4];
            Q[0][2] = zero;
#pragma unroll 1
            for (int s = 2 * part + 1; s >= 2 * part; s--) {
#pragma unroll
                for (int i = 0; i < 3; i++) { Q[i][0] = lds32(po + s * P_GS + i * 64); Q[i][1] = lds32(po + s * P_GS + (i * 64 + 32)); }
                const uint32_t ba = fb + lane * 16 + ((s & 1) * F_E3 + (part == h ? 0 : F_O5 + h * 16));
#pragma unroll
                for (int i = 0; i < 3; i++) ldsm4t(B[i], ba + i * 512);
#pragma unroll
                for (int i = 0; i < 3; i++) { Q[i][3] = CP(Q[i][0]); if (i) Q[i][2] = CP(Q[i - 1][1]); }
#pragma unroll
                for (int dl = 0; dl < 3; dl++)
#pragma unroll
                    for (int ap = 0; ap < 6 - dl; ap++) mma_f16(fa[ap + 1 + dl], Q[dl], B[ap >> 1][2 * (ap & 1)], B[ap >> 1][2 * (ap & 1) + 1]);
            }
#pragma unroll 1
            for (int s = role; s == 1; s++) {
                ldsm2t(B[0][0], B[0][1], fb + ((lane & 15) == 15 ? F_O5 : F_O3));
#pragma unroll
                for (int dl = 0; dl < 3; dl++) mma_f16(fa[dl], Q[dl], B[0][0], B[0][1]);
            }
#pragma unroll 1
            for (int s = part; s <= 2 * part; s++) {
#pragma unroll
                for (int i = 0; i < 4; i++) { Q[i][0] = lds32(po + s * P_HS + (P_H7 + i * 64)); Q[i][1] = lds32(po + s * P_HS + (P_H7 + i * 64 + 32)); }
                const uint32_t ba = fb + lane * 16 + (F_E7 + s * 1024 + h * F_H);
                ldsm4t(B[0], ba); ldsm4t(B[1], ba + 512);
#pragma unroll
                for (int i = 0; i < 4; i++) { Q[i][3] = CP(Q[i][0]); if (i) Q[i][2] = CP(Q[i - 1][1]); }
#pragma unroll
                for (int dl = 0; dl < 4; dl++) {
#pragma unroll
                    for (int ap = 0; ap < 4 - dl; ap++) mma_f16(fa[ap + 3 + dl], Q[dl], B[ap >> 1][2 * (ap & 1)], B[ap >> 1][2 * (ap & 1) + 1]);
                    if (s == 1) break;
                }
            }
            const uint32_t da = fb + role * 2048 + (lane & 3) * 512 + (((lane >> 2) ^ ((lane & 3) * 2)) << 4);
            bar_sync(1 + k, 128);
            stsm4(da, 0u, 0u, pack_f16(fa[0][0], fa[0][1]), pack_f16(fa[0][2], fa[0][3]));
#pragma unroll
            for (int i = 1; i < 4; i++)
                stsm4(da + i * 128, pack_f16(fa[2 * i - 1][0], fa[2 * i - 1][1]), pack_f16(fa[2 * i - 1][2], fa[2 * i - 1][3]),
                      pack_f16(fa[2 * i][0], fa[2 * i][1]), pack_f16(fa[2 * i][2], fa[2 * i][3]));
            Q[0][0] = (g == 2 * cq) ? 0x6000u : ((g == 2 * cq + 1) ? 0x60000000u : 0u);
            Q[0][1] = 0; Q[0][3] = CP(Q[0][0]);
            const uint32_t ra = fb + (lane >> 3) * 2048 + wq * 512 + (((lane & 7) ^ (wq * 2)) << 4);
            bar_sync(1 + k, 128);
#pragma unroll
            for (int i = 0; i < 4; i++) {
                ldsm4(B[0], ra + i * 128);
                acc[i][0] = acc[i][1] = acc[i][2] = acc[i][3] = 0.f;
                mma_f16(acc[i], Q[0], hadd2(B[0][0], B[0][2]), hadd2(B[0][1], B[0][3]));
            }
        }
        bar_arrive(6 + k, 160);
        STAMP(8);
        const uint32_t inv = lds32(sb + SM_SC + k * 4);
        uint32_t yd = mapa(sb, 2 * wq) + (SM_XT + 128 + q * YP + k * YS) + lane * 16;
        PIN(yd);
        {
            uint32_t pp = pn + (16 * (wq - 3) + g - 2 * cq) * 4;
            uint32_t dlo = (((ub + 6 * UP) & 0x3FFFF) >> 4) | ((UP >> 4) << 16);
            uint32_t R[4][4];
            auto loadQ = [&](uint32_t (&X)[4][4], uint32_t prev) {
#pragma unroll
                for (int i = 0; i < 4; i++) { X[i][0] = lds32(pp + i * 64); X[i][1] = lds32(pp + i * 64 + 32); }
                X[0][2] = CP(prev);
#pragma unroll
                for (int i = 0; i < 4; i++) { X[i][3] = CP(X[i][0]); if (i) X[i][2] = CP(X[i - 1][1]); }
                pp += 256;
            };
            auto issue = [&](uint32_t (&X)[4][4]) {
                asm volatile("wgmma.fence.sync.aligned;" ::: "memory");
#pragma unroll
                for (int i = 0; i < 4; i++) wgmma32(acc, X[i], dlo - i * (2 * UP >> 4));
                asm volatile("wgmma.commit_group.sync.aligned;" ::: "memory");
                dlo -= 1;
            };
            loadQ(Q, 0);
#pragma unroll 1
            for (int dl = 0; dl < 4; dl++) {
                issue(Q);
                asm volatile("wgmma.wait_group.sync.aligned 1;" ::: "memory");
                loadQ(R, Q[3][1]);
                issue(R);
                asm volatile("wgmma.wait_group.sync.aligned 1;" ::: "memory");
                loadQ(Q, R[3][1]);
            }
            issue(Q);
            asm volatile("wgmma.wait_group.sync.aligned 0;" ::: "memory");
        }
        const uint32_t pstep = mapa(sb, 1) - mapa(sb, 0), ym = mapa(mb + MB_Y * 8, 2 * wq);
#pragma unroll
        for (int e = 0; e < 2; e++)
            st_async4(yd + e * pstep, bmul2(pack_bf16(acc[0][2 * e], acc[0][2 * e + 1]), inv), bmul2(pack_bf16(acc[1][2 * e], acc[1][2 * e + 1]), inv),
                      bmul2(pack_bf16(acc[2][2 * e], acc[2][2 * e + 1]), inv), bmul2(pack_bf16(acc[3][2 * e], acc[3][2 * e + 1]), inv), ym + e * pstep);
        if (lane == 0) asm volatile("mbarrier.arrive.shared::cta.b64 _, [%0];" :: "r"(mb + MB_Y * 8) : "memory");
    }
    STAMP(9);
    uint32_t ha[5], hb[5];
    if (warp < 16) {
        const uint4 wk = lds128(sb + SM_DW + cq * 16);
        uint32_t sel[5] = {wk.x, wk.y, wk.z, wk.w, lds32(sb + SM_DW + 64 + cq * 4)}, sel2[5];
#pragma unroll
        for (int i = 0; i < 5; i++) {
            if (!(g & 1)) sel[i] = 0x3F803F80u;
            sel2[i] = sel[i]; PIN(sel2[i]);
        }
        const uint32_t y4 = sb + SM_XT + 128 + warp * 32 + (2 * (lane >> 3) + (lane & 1)) * YP + ((lane & 7) >> 1) * YS;
        const uint32_t y1 = sb + SM_XT + 128 + warp * 32 + (lane & 7) * YP + 4 * YS + (lane & 8) * 2;
        mbar_wait(mb + MB_Y * 8);
        STAMP(10);
        float ca[4] = {0.f, 0.f, 0.f, 0.f}, cb[4] = {0.f, 0.f, 0.f, 0.f};
        {
            uint32_t ya[4], yb[4], yc, yd;
            ldsm4t(ya, y4); ldsm4t(yb, y4 + 16); ldsm2t(yc, yd, y1);
#pragma unroll
            for (int i = 0; i < 4; i++) { ha[i] = badd2(xa[i], ya[i]); hb[i] = badd2(xb[i], yb[i]); }
            ha[4] = badd2(xa[4], yc); hb[4] = badd2(xb[4], yd);
        }
        if (nslot != 5) {
            ha[4] = hb[4] = 0;
            if (cq >= 2) ha[0] = ha[1] = ha[2] = ha[3] = hb[0] = hb[1] = hb[2] = hb[3] = 0;
        }
#pragma unroll
        for (int i = 0; i < 5; i++) { mma_bf16_k8(ca, ha[i], sel[i], ha[i]); mma_bf16_k8(cb, hb[i], sel2[i], hb[i]); }
        const float oa = __shfl_xor_sync(~0u, (g & 1) ? ca[2] : ca[3], 4), ob = __shfl_xor_sync(~0u, (g & 1) ? cb[2] : cb[3], 4);
        if (cq == (g >> 1)) {
            float4* ap = &g_s.acc[256 * q + tn];
            const bool od = g & 1;
            asm volatile("red.relaxed.gpu.global.add.v4.f32 [%0], {%1,%2,%3,%4};" :: "l"(ap), "f"(od ? oa : ca[2]), "f"(od ? ca[1] : ca[0]), "f"(od ? ca[3] : oa), "f"(1.0f) : "memory");
            asm volatile("red.relaxed.gpu.global.add.v4.f32 [%0], {%1,%2,%3,%4};" :: "l"(ap + 8), "f"(od ? ob : cb[2]), "f"(od ? cb[1] : cb[0]), "f"(od ? cb[3] : ob), "f"(1.0f) : "memory");
        }
        const uint32_t hta = sb + SM_HT + tn * 80;
        sts128(hta + cq * 16, ha[0], ha[1], ha[2], ha[3]); sts32(hta + 64 + cq * 4, ha[4]);
        sts128(hta + cq * 16 + 640, hb[0], hb[1], hb[2], hb[3]); sts32(hta + 704 + cq * 4, hb[4]);
        STAMP(11);
    }
    const int kq = warp / 5, mt = warp - 5 * kq;
    const int mi = lane >> 3, mr = lane & 7;
    const unsigned tk = (unsigned)tid / 72u, ck = tid - tk * 72;
    uint32_t A[9][4];
    auto loadA = [&]() {
        mbar_wait(mb + MB_W1 * 8);
        const uint32_t aa = sb + (mi & 1) * SM_WU + (8 * (mi >> 1) + mr) * 80 + (144 * 80 * kq + mt * 16);
#pragma unroll
        for (int s = 0; s < 9; s++) ldsm4t(A[s], aa + s * 1280);
    };
    const uint32_t par = (epoch & 1) ? 0x40004000u : 0u;
    uint32_t pk0 = mapa(sb, 2 * cq), go = (ck / 5u + ck) * 16, co = ((q * 8 * NCL + c) * 6 + cq) * 16;
    PIN(pk0); PIN(go); PIN(co);
    if (warp < 8) {
        const float wsum = ldsf(sb + SM_SC + 24);
        const uint32_t idx = 2047 - (512 * ((tid >> 1) & 3) + 128 * ((tid >> 3) & 3) + 64 * (tid & 1) + 8 * q + warp);
        if (RED_DELAY) { const long long t0 = clock64(); while (clock64() - t0 < RED_DELAY) {} }
        uint4 s; int n = 0;
        do { s = ld_rlx128(&g_s.acc[256 * q + tid]); } while (__uint_as_float(s.w) != (float)NCL && ++n < SPIN_LIMIT);
        STAMP(16);
        const uint32_t ms = ln_stats(__uint_as_float(s.x), __uint_as_float(s.y));
        const float rs = rcpf(bf_hi(ms));
        const uint32_t rb = pack_bf16(0.f, fmaf(-bf_lo(ms), wsum, __uint_as_float(s.z)) * rs);
        const uint32_t key = (((rb ^ (((int)rb >> 31) | 0x80000000u)) >> 16) << 11) | idx;
        sts32(sb + SM_KEY + tid * 4, key);
        __syncwarp();
        const uint32_t rank = rank4<8>(sb + SM_KEY + warp * 128, key);
        if (rank < 8) sts32(sb + SM_CAND + warp * 32 + rank * 4, key);
        sts64(sb + SM_ST + tid * 8, __byte_perm(ms, 0, 0x1010), rsplit(rs));
    } else loadA();
    if (warp < 16) {
        STAMP(17);
        bar_sync(12, 512);
        STAMP(18);
        if (warp < 8) {
            const uint32_t mk = lds32(sb + SM_CAND + (tid >> 2) * 4);
            uint32_t rank = rank4<4>(sb + SM_CAND + cq * 64, mk);
            rank += __shfl_xor_sync(~0u, rank, 1); rank += __shfl_xor_sync(~0u, rank, 2);
            if (rank < 8) {
                const uint32_t pk1 = pk0 + (mapa(sb, 1) - mapa(sb, 0));
                st_async1(pk0 + (SM_RK + q * 32) + rank * 4, mk, pk0 + (SM_MB + MB_KEY * 8));
                st_async1(pk1 + (SM_RK + q * 32) + rank * 4, mk, pk1 + (SM_MB + MB_KEY * 8));
                const uint32_t t = tslot(~mk);
                const uint2 sv = lds64(sb + SM_ST + t * 8);
                const uint4 hv = lds128(sb + SM_HT + t * 80 + cq * 16);
                const uint32_t h4 = lds32(sb + SM_HT + t * 80 + 64 + cq * 4);
                const uint32_t rr = bmul2(sv.y, 0x3C803C80u), rh = __byte_perm(rr, 0, 0x1010), rl = __byte_perm(rr, 0, 0x3232);
                char* const dp = (char*)g_s.cand + (co + rank * 1440);
                st_rlx128(dp, (norm2(hv.x, sv.x, rh, rl) & 0xBFFFBFFFu) | par, (norm2(hv.y, sv.x, rh, rl) & 0xBFFFBFFFu) | par,
                          (norm2(hv.z, sv.x, rh, rl) & 0xBFFFBFFFu) | par, (norm2(hv.w, sv.x, rh, rl) & 0xBFFFBFFFu) | par);
                asm volatile("st.relaxed.gpu.global.u32 [%0], %1;" :: "l"((char*)g_s.cand + (co + rank * 1440 + 64 - cq * 12)), "r"((norm2(h4, sv.x, rh, rl) & 0xBFFFBFFFu) | par) : "memory");
            }
            __syncwarp();
        }
        {
            const uint2 sa = lds64(sb + SM_ST + tn * 8), sbb = lds64(sb + SM_ST + tn * 8 + 64);
            const uint32_t rha = __byte_perm(sa.y, 0, 0x1010), rla = __byte_perm(sa.y, 0, 0x3232);
            const uint32_t rhb = __byte_perm(sbb.y, 0, 0x1010), rlb = __byte_perm(sbb.y, 0, 0x3232);
#pragma unroll
            for (int i = 0; i < 5; i++) { ha[i] = badd2(ha[i], norm2(ha[i], sa.x, rha, rla)); hb[i] = badd2(hb[i], norm2(hb[i], sbb.x, rhb, rlb)); }
            const uint32_t ota = sb + SM_XT + tn * 80;
            sts128(ota + cq * 16, ha[0], ha[1], ha[2], ha[3]); sts32(ota + 64 + cq * 4, ha[4]);
            sts128(ota + cq * 16 + 640, hb[0], hb[1], hb[2], hb[3]); sts32(ota + 704 + cq * 4, hb[4]);
            asm volatile("fence.proxy.async.shared::cta;" ::: "memory");
        }
        if (warp >= 8) {
            STAMP(19);
            mbar_wait(mb + MB_KEY * 8);
            STAMP(20);
            const uint32_t mk = lds32(sb + SM_RK - 256 + (tid >> 2) * 4);
            uint32_t rank = rank4<4>(sb + SM_RK + cq * 64, mk);
            rank += __shfl_xor_sync(~0u, rank, 1); rank += __shfl_xor_sync(~0u, rank, 2);
            if (rank < 8) sts64(sb + SM_SEL + rank * 8, mk, ((tid >> 2) - 64) * 1440);
        }
    }
    bar_sync(11, 640);
    STAMP(12);

    {
        const char* gp = (const char*)g_s.cand + (go + lds32(sb + SM_SEL + 4 + (tk & 7) * 8));
        uint4 hv = ld_rlx128(gp);
        if (warp < 8) loadA();
        if (warp < 18) {
            int n = 0;
            while ((((hv.x ^ par) | (hv.y ^ par) | (hv.z ^ par) | (hv.w ^ par)) & 0x40004000u) && ++n < SPIN_LIMIT) hv = ld_rlx128(gp);
            sts128(sb + SM_XS + tk * 16 + tid * 16, hv.x ^ par, hv.y ^ par, hv.z ^ par, hv.w ^ par);
        }
    }
    bar_sync(14, 672);
    STAMP(13);
    {
        float c0[4] = {0.f, 0.f, 0.f, 0.f}, c1[4] = {0.f, 0.f, 0.f, 0.f}, c2[4] = {0.f, 0.f, 0.f, 0.f};
        const uint32_t ba = sb + SM_XS + mr * 1168 + mi * 16 + 288 * kq;
        uint32_t b[5][4];
#pragma unroll
        for (int s = 0; s < 5; s++) ldsm4(b[s], ba + s * 64);
        mma_bf16(c0, A[0][0], A[0][1], A[0][2], A[0][3], b[0][0], b[0][1]);
        mma_bf16(c1, A[1][0], A[1][1], A[1][2], A[1][3], b[0][2], b[0][3]);
        mma_bf16(c2, A[2][0], A[2][1], A[2][2], A[2][3], b[1][0], b[1][1]);
        mma_bf16(c0, A[3][0], A[3][1], A[3][2], A[3][3], b[1][2], b[1][3]);
        mma_bf16(c1, A[4][0], A[4][1], A[4][2], A[4][3], b[2][0], b[2][1]);
        mma_bf16(c2, A[5][0], A[5][1], A[5][2], A[5][3], b[2][2], b[2][3]);
        mma_bf16(c0, A[6][0], A[6][1], A[6][2], A[6][3], b[3][0], b[3][1]);
        mma_bf16(c1, A[7][0], A[7][1], A[7][2], A[7][3], b[3][2], b[3][3]);
        mma_bf16(c2, A[8][0], A[8][1], A[8][2], A[8][3], b[4][0], b[4][1]);
        sts128f(sb + SM_RED + tid * 16, c0[0] + c1[0] + c2[0], c0[1] + c1[1] + c2[1], c0[2] + c1[2] + c2[2], c0[3] + c1[3] + c2[3]);
    }
    bar_sync(1 + mt, 128);
    STAMP(21);
    if (mt < nslot) {
        const uint32_t ra = sb + SM_RED + mt * 512 + lane * 16;
        const float4 p0 = lds128f(ra), p1 = lds128f(ra + 2560), p2 = lds128f(ra + 5120), p3 = lds128f(ra + 7680);
        const float g0 = bfr(((p0.x + p1.x) + (p2.x + p3.x)) * 64.f), g1 = bfr(((p0.y + p1.y) + (p2.y + p3.y)) * 64.f);
        const uint32_t sg = pack_bf16(g0 * rcpf(1.f + ex2f(g0 * -1.4426950408889634f)), g1 * rcpf(1.f + ex2f(g1 * -1.4426950408889634f)));
        const uint32_t gu = bmul2(sg, pack_bf16(((p0.z + p1.z) + (p2.z + p3.z)) * 64.f, ((p0.w + p1.w) + (p2.w + p3.w)) * 64.f));
#pragma unroll
        for (int i = 0; i < 2; i++) {
            const uint32_t rb_ = mapa(sb, 2 * kq + i);
            st_async1(rb_ + (SM_GU + (q * nslot + mt) * 128) + lane * 4, gu, rb_ + (SM_MB + MB_GU * 8));
        }
    }
    mbar_wait(mb + MB_W2 * 8);
    {
        const uint32_t aa = sb + (8 * (mi >> 1) + mr) * 144 + (mi & 1) * 16 + (SM_FAR + 2304 * kq + mt * 32);
#pragma unroll
        for (int s = 0; s < 5; s++) ldsm4t(A[s], aa + s * FAR_SZ);
    }
    const bool red = warp < 6;
    const uint32_t ft = red ? (unsigned)tid / 24u : (unsigned)(tid >> 4) & 7u, fj = red ? 24 * q + tid - ft * 24 : d0 / 3 + (lane & 15);
    const uint32_t key = lds32(sb + SM_SEL + ft * 8), k16 = key << 5;
    float sig = bfr(rcpf(1.f + ex2f(__uint_as_float((k16 ^ (~((int)k16 >> 31) | 0x80000000u)) & 0xFFFF0000u) * -1.4426950408889634f)));
    uint32_t ra2 = sb + SM_RED2 + tid * 12 + ft * 16, fo = (ft * 192 + fj) * 16, oo = ((~key & 2047) * D_ + 3 * fj) * 2;
    PIN(ra2); PIN(fo); PIN(oo);
    {
        uint32_t ba = sb + (SM_GU + 256 * kq) + (lane & 15) * 16 + (lane >> 4) * 1024, wa = sb + (SM_RED2 + kq * 2432 + mt * 64) + g * 4 + cq * 608;
        PIN(ba); PIN(wa);
        STAMP(22);
        mbar_wait(mb + MB_GU * 8);
        STAMP(23);
        float c0[4] = {0.f, 0.f, 0.f, 0.f}, c1[4] = {0.f, 0.f, 0.f, 0.f}, c2[4] = {0.f, 0.f, 0.f, 0.f};
        uint32_t b[2][4], b8, b9;
        ldsm4t(b[0], ba); ldsm4t(b[1], ba + 2048); ldsm2t(b8, b9, ba + 4096);
        mma_bf16(c0, A[0][0], A[0][1], A[0][2], A[0][3], b[0][0], b[0][1]);
        mma_bf16(c1, A[1][0], A[1][1], A[1][2], A[1][3], b[0][2], b[0][3]);
        if (nslot == 5) {
            mma_bf16(c2, A[4][0], A[4][1], A[4][2], A[4][3], b8, b9);
            mma_bf16(c0, A[2][0], A[2][1], A[2][2], A[2][3], b[1][0], b[1][1]);
            mma_bf16(c1, A[3][0], A[3][1], A[3][2], A[3][3], b[1][2], b[1][3]);
        }
        stsf(wa, c0[0] + c1[0] + c2[0]); stsf(wa + 304, c0[1] + c1[1] + c2[1]);
        if (mt < 4) { stsf(wa + 32, c0[2] + c1[2] + c2[2]); stsf(wa + 336, c0[3] + c1[3] + c2[3]); }
    }
    if (warp < 10) {
        float v[3], cnt = 3.f;
        if (red) {
            bar_sync(6, 640);
            STAMP(14);
#pragma unroll
            for (int i = 0; i < 3; i++) v[i] = ((ldsf(ra2 + i * 4) + ldsf(ra2 + i * 4 + 2432)) + (ldsf(ra2 + i * 4 + 4864) + ldsf(ra2 + i * 4 + 7296))) * sig;
        } else {
            bar_arrive(6, 640);
            cnt = 0.f;
#pragma unroll
            for (int i = 0; i < 3; i++) {
                const uint32_t cl = 3 * fj + i - d0;
                const bool ok = cl < 8 * nslot && ((~key >> 3) & 7) == q;
                v[i] = ok ? __uint_as_float(lds16(sb + SM_XT + tslot(~key) * 80 + (cl & 63) * 2) << 16) : 0.f;
                if (ok) cnt += 1.f;
            }
            mbar_wait(mb + MB_OUT * 8);
        }
        if (cnt != 0.f) {
            float x, y, z, w;
            asm volatile("atom.relaxed.gpu.global.add.v4.f32 {%0,%1,%2,%3}, [%4], {%5,%6,%7,%8};" : "=f"(x), "=f"(y), "=f"(z), "=f"(w)
                         : "l"((char*)g_s.fin + fo), "f"(v[0]), "f"(v[1]), "f"(v[2]), "f"(cnt) : "memory");
            if (w + cnt == 3.f * (NCL + 1)) {
                __nv_bfloat16* op = (__nv_bfloat16*)((char*)prm.out + oo);
                op[0] = __float2bfloat16(x + v[0]); op[1] = __float2bfloat16(y + v[1]); op[2] = __float2bfloat16(z + v[2]);
            }
        }
    } else bar_arrive(6, 640);
    STAMP(15);
}

typedef CUresult (*EncodeFn)(CUtensorMap*, CUtensorMapDataType, cuuint32_t, void*, const cuuint64_t*, const cuuint64_t*,
                             const cuuint32_t*, const cuuint32_t*, CUtensorMapInterleave, CUtensorMapSwizzle,
                             CUtensorMapL2promotion, CUtensorMapFloatOOBfill);

void make_map(EncodeFn fn, CUtensorMap* tm, const void* p, int cols, int rows, int bc, int br) {
    cuuint64_t dims[2] = {(cuuint64_t)cols, (cuuint64_t)rows};
    cuuint64_t strides[1] = {(cuuint64_t)cols * 2};
    cuuint32_t box[2] = {(cuuint32_t)bc, (cuuint32_t)br};
    cuuint32_t es[2] = {1, 1};
    fn(tm, CU_TENSOR_MAP_DATA_TYPE_BFLOAT16, 2, const_cast<void*>(p), dims, strides, box, es, CU_TENSOR_MAP_INTERLEAVE_NONE,
       CU_TENSOR_MAP_SWIZZLE_NONE, (CUtensorMapL2promotion)L2PROMO, CU_TENSOR_MAP_FLOAT_OOB_FILL_NONE);
}

void make_map3(EncodeFn fn, CUtensorMap* tm, const void* p) {
    cuuint64_t dims[3] = {(cuuint64_t)D_, 64, 32};
    cuuint64_t strides[2] = {(cuuint64_t)D_ * 2, (cuuint64_t)D_ * 128};
    cuuint32_t box[3] = {40, 8, 32};
    cuuint32_t es[3] = {1, 1, 1};
    fn(tm, CU_TENSOR_MAP_DATA_TYPE_BFLOAT16, 3, const_cast<void*>(p), dims, strides, box, es, CU_TENSOR_MAP_INTERLEAVE_NONE,
       CU_TENSOR_MAP_SWIZZLE_NONE, CU_TENSOR_MAP_L2_PROMOTION_NONE, CU_TENSOR_MAP_FLOAT_OOB_FILL_NONE);
}

void make_map5(EncodeFn fn, CUtensorMap* tm, const void* p) {
    cuuint64_t dims[5] = {(cuuint64_t)D_, 2, 4, 4, 64};
    cuuint64_t strides[4] = {(cuuint64_t)D_ * 128, (cuuint64_t)D_ * 1024, (cuuint64_t)D_ * 256, (cuuint64_t)D_ * 2};
    cuuint32_t box[5] = {40, 2, 4, 4, 8};
    cuuint32_t es[5] = {1, 1, 1, 1, 1};
    fn(tm, CU_TENSOR_MAP_DATA_TYPE_BFLOAT16, 5, const_cast<void*>(p), dims, strides, box, es, CU_TENSOR_MAP_INTERLEAVE_NONE,
       CU_TENSOR_MAP_SWIZZLE_NONE, CU_TENSOR_MAP_L2_PROMOTION_NONE, CU_TENSOR_MAP_FLOAT_OOB_FILL_NONE);
}

}

extern "C" void kernel_launch(void* const* d_in, const int* in_sizes, int n_in, void* d_out, int out_size) {
    (void)in_sizes; (void)n_in; (void)out_size;
    void* fp = nullptr;
    cudaDriverEntryPointQueryResult qr;
    cudaGetDriverEntryPoint("cuTensorMapEncodeTiled", &fp, cudaEnableDefault, &qr);
    EncodeFn fn = (EncodeFn)fp;
    CUtensorMap tmG, tmU, tmD, tmO, tmX;
    make_map3(fn, &tmX, d_in[0]);
    make_map(fn, &tmG, d_in[11], F_, D_, 40, 48);
    make_map(fn, &tmU, d_in[12], F_, D_, 40, 48);
    make_map(fn, &tmD, d_in[13], D_, F_, 72, 64);
    make_map5(fn, &tmO, d_out);
    Params p;
    p.x = (const unsigned short*)d_in[0];
    for (int i = 0; i < 6; i++) p.prm6[i] = (const unsigned short*)d_in[1 + i];
    p.logdt = (const unsigned short*)d_in[7]; p.dskip = (const unsigned short*)d_in[8];
    p.wr = (const unsigned short*)d_in[10];
    for (int i = 0; i < 3; i++) p.w3[i] = (const char*)d_in[11 + i];
    p.out = (__nv_bfloat16*)d_out;
    p.zero = 0;
    cudaGetSymbolAddress((void**)&p.gs, g_s);
    cudaFuncSetAttribute(fused_kernel, cudaFuncAttributeMaxDynamicSharedMemorySize, SM_TOTAL);
    fused_kernel<<<NCTA, NTHR, SM_TOTAL>>>(p, tmG, tmU, tmD, tmO, tmX);
}
```

```cpp
#include <cuda_runtime.h>
#include <cuda_bf16.h>
#include <cuda_fp16.h>
#include <cuda.h>
#include <stdint.h>

namespace {

constexpr int L_ = 2048, D_ = 576, F_ = 4608;
constexpr int NCL = 15, CS = 8, NCTA = NCL * CS, NTHR = 768;
#define PACE_NS 100
#define PRE_N 0
#define PRE_NS 200
#define FIN_DELAY 0
#define RED_DELAY 0
#define NO_OUT 0
#define XSPLIT 3
#define LNPOS 2
#define NMPOS 3
#define CFENCE 1
#define NEAR_DB 1
#define STREAM_T 0
#define L2PROMO 2
#define GAP_NS 0
#define ROW_DELAY 1
constexpr int SPIN_LIMIT = 1 << 22;

constexpr int SM_WG   = 0;
constexpr int SM_WU   = 46080;
constexpr int YP = 3376, YS = 672;
constexpr int UP = 3376, US = 672;
constexpr int SM_XT   = 92160;
constexpr int SM_U    = SM_XT + 8 * YP;
constexpr int SM_FAR  = SM_U + 8 * UP;
constexpr int FAR_SZ  = 12416;
constexpr int F_E5 = 0, F_O5 = 1536, F_E3 = 3088, F_O3 = 4624, F_E7 = 6176, F_E2 = F_E7 + 1024, F_E9 = F_E7 + 2048,
              F_H = 3088, F_O7 = F_E7 + F_H, F_O2 = F_E2 + F_H, F_O9 = F_E9 + F_H;
constexpr int SM_P    = SM_FAR + 5 * FAR_SZ;
constexpr int PN_SZ = 584 * 4, SM_PN = SM_P + 64 * 4;
constexpr int P_GS = 48 * 4, P_H7 = 192 * 4, P_HS = 72 * 4;
constexpr int PF_SZ = (192 + 216) * 4, SM_PF = SM_PN + 5 * PN_SZ + 32;
constexpr int SM_MISC = SM_PF + 5 * PF_SZ;
constexpr int SM_ST   = SM_MISC;
constexpr int SM_RK   = SM_ST + 2048;
constexpr int SM_SEL  = SM_RK + 256;
constexpr int SM_KG   = SM_SEL + 64;
constexpr int SM_SC   = SM_KG + 160;
constexpr int SM_DW   = SM_SC + 32;
constexpr int SM_MB   = SM_DW + 160;
constexpr int SM_TOTAL = SM_MB + 128;
constexpr int SM_ROW  = SM_XT - 20736;
constexpr int SM_XTL  = SM_ROW - 20480;
constexpr int SM_RED2 = SM_WG;
constexpr int SM_HT   = SM_P - 512;
constexpr int SM_KEY  = SM_FAR + 9216 + 128;
constexpr int SM_CAND = SM_KEY + 1024;
constexpr int SM_FIN  = SM_FAR + FAR_SZ + 9216 + 128;
constexpr int SM_HS   = SM_FIN + 2400;
constexpr int SM_XS   = SM_U;
constexpr int SM_GU   = SM_XS + 9344;
constexpr int SM_RED  = SM_GU + 5632;
static_assert(F_O9 + 1024 <= FAR_SZ && FAR_SZ % 128 == 0, "far overflow");
static_assert(SM_RED + 10240 <= SM_FAR && SM_HS + 128 <= SM_FAR + 2 * FAR_SZ && SM_HT + 20496 <= SM_MISC, "alias overflow");
static_assert(SM_TOTAL <= 232448, "smem overflow");
static_assert(SM_FAR % 128 == 0 && SM_XT % 128 == 0 && SM_XTL % 128 == 0 && SM_P % 16 == 0 && SM_MISC % 16 == 0 && SM_MB % 8 == 0 && SM_HS % 16 == 0, "align");

enum { MB_X = 0, MB_W1 = 5, MB_W2 = 6, MB_KEY = 7, MB_GU = 8, MB_Y = 9, MB_OUT = 10, MB_T = 11, MB_R = 12 };

struct __align__(128) Scratch {
    unsigned epoch, zcnt, pad[30];
    uint4  st1[L_ * 2];
    float4 acc[L_];
    uint4  cand[64 * NCL * 6];
    float4 fin[8 * 192 + 24];
};
__device__ Scratch g_s;
#define STAMP(i)

__device__ __forceinline__ uint32_t mapa(uint32_t a, uint32_t r) { uint32_t d; asm("mapa.shared::cluster.u32 %0, %1, %2;" : "=r"(d) : "r"(a), "r"(r)); return d; }
__device__ __forceinline__ void mbar_wait(uint32_t mb) {
    asm volatile("{ .reg .pred p, q; .reg .u32 n; mov.u32 n, 0;\n"
                 "W_%=: mbarrier.try_wait.parity.shared::cta.b64 p, [%0], 0; add.u32 n, n, 1; setp.lt.and.u32 q, n, 65536, !p; @q bra W_%=; }" :: "r"(mb) : "memory");
}
__device__ __forceinline__ void arm(uint32_t mb, uint32_t bytes) { asm volatile("mbarrier.arrive.expect_tx.shared::cta.b64 _, [%0], %1;" :: "r"(mb), "r"(bytes) : "memory"); }
__device__ __forceinline__ void bar_sync(int id, int n) { asm volatile("bar.sync %0, %1;" :: "r"(id), "r"(n) : "memory"); }
__device__ __forceinline__ void bar_arrive(int id, int n) { asm volatile("bar.arrive %0, %1;" :: "r"(id), "r"(n) : "memory"); }
__device__ __forceinline__ uint32_t lds16(uint32_t a) { unsigned short v; asm volatile("ld.shared.u16 %0, [%1];" : "=h"(v) : "r"(a) : "memory"); return v; }
__device__ __forceinline__ uint32_t lds32(uint32_t a) { uint32_t v; asm volatile("ld.shared.u32 %0, [%1];" : "=r"(v) : "r"(a) : "memory"); return v; }
__device__ __forceinline__ uint2 lds64(uint32_t a) { uint2 v; asm volatile("ld.shared.v2.u32 {%0,%1}, [%2];" : "=r"(v.x), "=r"(v.y) : "r"(a) : "memory"); return v; }
__device__ __forceinline__ float ldsf(uint32_t a) { float v; asm volatile("ld.shared.f32 %0, [%1];" : "=f"(v) : "r"(a) : "memory"); return v; }
__device__ __forceinline__ uint4 lds128(uint32_t a) { uint4 v; asm volatile("ld.shared.v4.u32 {%0,%1,%2,%3}, [%4];" : "=r"(v.x), "=r"(v.y), "=r"(v.z), "=r"(v.w) : "r"(a) : "memory"); return v; }
__device__ __forceinline__ float4 lds128f(uint32_t a) { float4 v; asm volatile("ld.shared.v4.f32 {%0,%1,%2,%3}, [%4];" : "=f"(v.x), "=f"(v.y), "=f"(v.z), "=f"(v.w) : "r"(a) : "memory"); return v; }
__device__ __forceinline__ void sts16(uint32_t a, uint32_t v) { asm volatile("{ .reg .b16 l, h; mov.b32 {l, h}, %1; st.shared.b16 [%0], l; }" :: "r"(a), "r"(v) : "memory"); }
__device__ __forceinline__ void sts32(uint32_t a, uint32_t v) { asm volatile("st.shared.u32 [%0], %1;" :: "r"(a), "r"(v) : "memory"); }
__device__ __forceinline__ void sts64(uint32_t a, uint32_t x, uint32_t y) { asm volatile("st.shared.v2.u32 [%0], {%1,%2};" :: "r"(a), "r"(x), "r"(y) : "memory"); }
__device__ __forceinline__ void stsf(uint32_t a, float v) { asm volatile("st.shared.f32 [%0], %1;" :: "r"(a), "f"(v) : "memory"); }
__device__ __forceinline__ void sts128(uint32_t a, uint32_t x, uint32_t y, uint32_t z, uint32_t w) { asm volatile("st.shared.v4.u32 [%0], {%1,%2,%3,%4};" :: "r"(a), "r"(x), "r"(y), "r"(z), "r"(w) : "memory"); }
__device__ __forceinline__ void sts128f(uint32_t a, float x, float y, float z, float w) { asm volatile("st.shared.v4.f32 [%0], {%1,%2,%3,%4};" :: "r"(a), "f"(x), "f"(y), "f"(z), "f"(w) : "memory"); }
__device__ __forceinline__ void ldsm4(uint32_t (&r)[4], uint32_t a) { asm volatile("ldmatrix.sync.aligned.m8n8.x4.shared.b16 {%0,%1,%2,%3}, [%4];" : "=r"(r[0]), "=r"(r[1]), "=r"(r[2]), "=r"(r[3]) : "r"(a) : "memory"); }
__device__ __forceinline__ void ldsm4t(uint32_t (&r)[4], uint32_t a) { asm volatile("ldmatrix.sync.aligned.m8n8.x4.trans.shared.b16 {%0,%1,%2,%3}, [%4];" : "=r"(r[0]), "=r"(r[1]), "=r"(r[2]), "=r"(r[3]) : "r"(a) : "memory"); }
__device__ __forceinline__ void ldsm2t(uint32_t& r0, uint32_t& r1, uint32_t a) { asm volatile("ldmatrix.sync.aligned.m8n8.x2.trans.shared.b16 {%0,%1}, [%2];" : "=r"(r0), "=r"(r1) : "r"(a) : "memory"); }
__device__ __forceinline__ void stsm4t(uint32_t a, uint32_t r0, uint32_t r1, uint32_t r2, uint32_t r3) { asm volatile("stmatrix.sync.aligned.m8n8.x4.trans.shared.b16 [%0], {%1,%2,%3,%4};" :: "r"(a), "r"(r0), "r"(r1), "r"(r2), "r"(r3) : "memory"); }
__device__ __forceinline__ void stsm4(uint32_t a, uint32_t r0, uint32_t r1, uint32_t r2, uint32_t r3) { asm volatile("stmatrix.sync.aligned.m8n8.x4.shared.b16 [%0], {%1,%2,%3,%4};" :: "r"(a), "r"(r0), "r"(r1), "r"(r2), "r"(r3) : "memory"); }
__device__ __forceinline__ void stsm2t(uint32_t a, uint32_t r0, uint32_t r1) { asm volatile("stmatrix.sync.aligned.m8n8.x2.trans.shared.b16 [%0], {%1,%2};" :: "r"(a), "r"(r0), "r"(r1) : "memory"); }
__device__ __forceinline__ uint4 ldg128(const void* p) { uint4 v; asm volatile("ld.global.nc.v4.u32 {%0,%1,%2,%3}, [%4];" : "=r"(v.x), "=r"(v.y), "=r"(v.z), "=r"(v.w) : "l"(p)); return v; }
__device__ __forceinline__ uint32_t ldg32(const void* p) { uint32_t v; asm volatile("ld.global.nc.u32 %0, [%1];" : "=r"(v) : "l"(p)); return v; }
__device__ __forceinline__ uint32_t ldg16(const void* p) { unsigned short v; asm volatile("ld.global.nc.u16 %0, [%1];" : "=h"(v) : "l"(p)); return v; }
__device__ __forceinline__ uint32_t opaque(uint32_t v) { uint32_t r; asm volatile("mov.b32 %0, %1;" : "=r"(r) : "r"(v)); return r; }
__device__ __forceinline__ void mma_f16(float (&d)[4], const uint32_t (&a)[4], uint32_t b0, uint32_t b1) {
    asm volatile("mma.sync.aligned.m16n8k16.row.col.f32.f16.f16.f32 {%0,%1,%2,%3}, {%4,%5,%6,%7}, {%8,%9}, {%0,%1,%2,%3};"
        : "+f"(d[0]), "+f"(d[1]), "+f"(d[2]), "+f"(d[3]) : "r"(a[0]), "r"(a[1]), "r"(a[2]), "r"(a[3]), "r"(b0), "r"(b1));
}
__device__ __forceinline__ void mma_bf16(float (&d)[4], uint32_t a0, uint32_t a1, uint32_t a2, uint32_t a3, uint32_t b0, uint32_t b1) {
    asm volatile("mma.sync.aligned.m16n8k16.row.col.f32.bf16.bf16.f32 {%0,%1,%2,%3}, {%4,%5,%6,%7}, {%8,%9}, {%0,%1,%2,%3};"
        : "+f"(d[0]), "+f"(d[1]), "+f"(d[2]), "+f"(d[3]) : "r"(a0), "r"(a1), "r"(a2), "r"(a3), "r"(b0), "r"(b1));
}
__device__ __forceinline__ void mma_bf16_k8(float (&d)[4], uint32_t a0, uint32_t a1, uint32_t b0) {
    asm volatile("mma.sync.aligned.m16n8k8.row.col.f32.bf16.bf16.f32 {%0,%1,%2,%3}, {%4,%5}, {%6}, {%0,%1,%2,%3};"
        : "+f"(d[0]), "+f"(d[1]), "+f"(d[2]), "+f"(d[3]) : "r"(a0), "r"(a1), "r"(b0));
}
__device__ __forceinline__ uint32_t pack_f16(float lo, float hi) { uint32_t r; asm("cvt.rn.f16x2.f32 %0, %1, %2;" : "=r"(r) : "f"(hi), "f"(lo)); return r; }
__device__ __forceinline__ uint32_t pack_bf16(float lo, float hi) { uint32_t r; asm("cvt.rn.bf16x2.f32 %0, %1, %2;" : "=r"(r) : "f"(hi), "f"(lo)); return r; }
__device__ __forceinline__ float bf_lo(uint32_t v) { return __uint_as_float(v << 16); }
__device__ __forceinline__ float bf_hi(uint32_t v) { return __uint_as_float(v & 0xFFFF0000u); }
__device__ __forceinline__ float bfr(float x) { return __uint_as_float(pack_bf16(0.f, x)); }
__device__ __forceinline__ uint32_t bsub2(uint32_t a, uint32_t b) { uint32_t r; asm("sub.rn.bf16x2 %0, %1, %2;" : "=r"(r) : "r"(a), "r"(b)); return r; }
__device__ __forceinline__ uint32_t badd2(uint32_t a, uint32_t b) { uint32_t r; asm("add.rn.bf16x2 %0, %1, %2;" : "=r"(r) : "r"(a), "r"(b)); return r; }
__device__ __forceinline__ uint32_t bmul2(uint32_t a, uint32_t b) { uint32_t r; asm("mul.rn.bf16x2 %0, %1, %2;" : "=r"(r) : "r"(a), "r"(b)); return r; }
__device__ __forceinline__ uint32_t bfma2(uint32_t a, uint32_t b, uint32_t c) { uint32_t r; asm("fma.rn.bf16x2 %0, %1, %2, %3;" : "=r"(r) : "r"(a), "r"(b), "r"(c)); return r; }
__device__ __forceinline__ uint32_t hadd2(uint32_t a, uint32_t b) { uint32_t r; asm("add.rn.f16x2 %0, %1, %2;" : "=r"(r) : "r"(a), "r"(b)); return r; }
__device__ __forceinline__ uint32_t hmul2(uint32_t a, uint32_t b) { uint32_t r; asm("mul.rn.f16x2 %0, %1, %2;" : "=r"(r) : "r"(a), "r"(b)); return r; }
__device__ __forceinline__ uint32_t hfma2(uint32_t a, uint32_t b, uint32_t c) { uint32_t r; asm("fma.rn.f16x2 %0, %1, %2, %3;" : "=r"(r) : "r"(a), "r"(b), "r"(c)); return r; }
__device__ __forceinline__ uint32_t hneg2(uint32_t a) { uint32_t r; asm("neg.f16x2 %0, %1;" : "=r"(r) : "r"(a)); return r; }
__device__ __forceinline__ float rcpf(float x) { float r; asm("rcp.approx.ftz.f32 %0, %1;" : "=f"(r) : "f"(x)); return r; }
__device__ __forceinline__ float sqrta(float x) { float r; asm("sqrt.approx.ftz.f32 %0, %1;" : "=f"(r) : "f"(x)); return r; }
__device__ __forceinline__ float ex2f(float x) { float r; asm("ex2.approx.ftz.f32 %0, %1;" : "=f"(r) : "f"(x)); return r; }
__device__ __forceinline__ void st_async4(uint32_t a, uint32_t x, uint32_t y, uint32_t z, uint32_t w, uint32_t mb) {
    asm volatile("st.async.shared::cluster.mbarrier::complete_tx::bytes.v4.u32 [%0], {%1,%2,%3,%4}, [%5];" :: "r"(a), "r"(x), "r"(y), "r"(z), "r"(w), "r"(mb) : "memory"); }
__device__ __forceinline__ void st_async1(uint32_t a, uint32_t x, uint32_t mb) {
    asm volatile("st.async.shared::cluster.mbarrier::complete_tx::bytes.u32 [%0], %1, [%2];" :: "r"(a), "r"(x), "r"(mb) : "memory"); }
__device__ __forceinline__ unsigned ld_rlx(const void* p) { unsigned v; asm volatile("ld.relaxed.gpu.global.u32 %0, [%1];" : "=r"(v) : "l"(p) : "memory"); return v; }
__device__ __forceinline__ unsigned ld_acq(const void* p) { unsigned v; asm volatile("ld.acquire.gpu.global.u32 %0, [%1];" : "=r"(v) : "l"(p) : "memory"); return v; }
__device__ __forceinline__ uint2 ld_rlx64(const void* p) { unsigned long long v; asm volatile("ld.relaxed.gpu.global.u64 %0, [%1];" : "=l"(v) : "l"(p) : "memory"); return make_uint2((unsigned)v, (unsigned)(v >> 32)); }
__device__ __forceinline__ void st_rlx64(void* p, unsigned lo, unsigned hi) { asm volatile("st.relaxed.gpu.global.u64 [%0], %1;" :: "l"(p), "l"((unsigned long long)lo | ((unsigned long long)hi << 32)) : "memory"); }
__device__ __forceinline__ void st_rlx128(void* p, uint32_t x, uint32_t y, uint32_t z, uint32_t w) {
    asm volatile("st.relaxed.gpu.global.v2.u64 [%0], {%1,%2};" :: "l"(p), "l"((unsigned long long)x | ((unsigned long long)y << 32)), "l"((unsigned long long)z | ((unsigned long long)w << 32)) : "memory"); }
__device__ __forceinline__ uint4 ld_rlx128(const void* p) { unsigned long long a, b; asm volatile("ld.relaxed.gpu.global.v2.u64 {%0,%1}, [%2];" : "=l"(a), "=l"(b) : "l"(p) : "memory"); return make_uint4((unsigned)a, (unsigned)(a >> 32), (unsigned)b, (unsigned)(b >> 32)); }
__device__ __forceinline__ void tma2d(uint32_t dst, const CUtensorMap* tm, int x, int y, uint32_t mb) {
    asm volatile("cp.async.bulk.tensor.2d.shared::cluster.global.mbarrier::complete_tx::bytes [%0], [%1, {%3, %4}], [%2];"
                 :: "r"(dst), "l"(tm), "r"(mb), "r"(x), "r"(y) : "memory");
}
__device__ __forceinline__ void cmul(float& xr, float& xi, float ar, float ai, float br, float bi) {
    const float r = fmaf(ar, br, -ai * bi), i = fmaf(ar, bi, ai * br); xr = r; xi = i;
}
__device__ __forceinline__ void csq(float& xr, float& xi, float ar, float ai) {
    const float r = fmaf(ar, ar, -ai * ai), i = (ar + ar) * ai; xr = r; xi = i;
}
__device__ __forceinline__ void cexp_s(float& zr, float& zi, float e2, float turns) {
    const float mag = ex2f(e2), r = (turns - rintf(turns)) * 6.283185307179586f;
    zr = mag * __cosf(r); zi = mag * __sinf(r);
}
__device__ __forceinline__ uint32_t ln_stats(float s1, float s2) {
    const float m = s1 * (1.f / D_);
    const float var = fmaxf(fmaf(s2, 1.f / D_, -m * m), 0.f);
    return pack_bf16(m, sqrta(bfr(bfr(var) + 1e-5f)));
}
__device__ __forceinline__ uint32_t rsplit(float rs) { const float h = bfr(rs); return pack_bf16(h, rs - h); }
__device__ __forceinline__ uint32_t norm2(uint32_t v, uint32_t m2, uint32_t rh2, uint32_t rl2) {
    const uint32_t dd = bsub2(v, m2);
    return bfma2(dd, rh2, bmul2(dd, rl2));
}
template <int N>
__device__ __forceinline__ uint32_t rank4(uint32_t a, uint32_t key) {
    uint32_t r0 = 0, r1 = 0, r2 = 0, r3 = 0;
#pragma unroll
    for (int i = 0; i < N; i++) {
        const uint4 o = lds128(a + i * 16);
        r0 += (key - o.x) >> 31; r1 += (key - o.y) >> 31; r2 += (key - o.z) >> 31; r3 += (key - o.w) >> 31;
    }
    return (r0 + r1) + (r2 + r3);
}
struct H2C { uint32_t r, i; };
__device__ __forceinline__ H2C splat(float r, float i) { H2C h; h.r = pack_f16(r, r); h.i = pack_f16(i, i); return h; }
__device__ __forceinline__ void expand4(uint32_t are, uint32_t aim, uint32_t R0, uint32_t R1, uint32_t I0, uint32_t I1, H2C m4) {
    sts128(are, R0, R1, hfma2(R0, m4.r, hneg2(hmul2(I0, m4.i))), hfma2(R1, m4.r, hneg2(hmul2(I1, m4.i))));
    sts128(aim, I0, I1, hfma2(R0, m4.i, hmul2(I0, m4.r)), hfma2(R1, m4.i, hmul2(I1, m4.r)));
}
__device__ __forceinline__ void expand8(uint32_t are, uint32_t aim, float sr, float si, float m1r, float m1i, float m2r, float m2i, H2C m4) {
    float r1, i1, r2, i2, r3, i3;
    cmul(r1, i1, sr, si, m1r, m1i); cmul(r2, i2, sr, si, m2r, m2i); cmul(r3, i3, r1, i1, m2r, m2i);
    expand4(are, aim, pack_f16(sr, r1), pack_f16(r2, r3), pack_f16(si, i1), pack_f16(i2, i3), m4);
}
__device__ __forceinline__ void put16(uint32_t a, uint32_t v) { sts16(a, v); sts16(a + 6, v); }

struct Params {
    const unsigned short *x, *prm6[6], *logdt, *dskip, *wr;
    const char* w3[3];
    __nv_bfloat16* out;
    Scratch* gs;
    unsigned zero;
};
__device__ __forceinline__ uint32_t tslot(uint32_t t) { return (t & 7) * 32 + ((t >> 4) & 24) + ((t >> 8) & 6) + ((t >> 6) & 1); }
#define CP(x) ((x) | zero)
#define PIN(x) asm volatile("or.b32 %0, %0, %1;" : "+r"(x) : "r"(zero))
__device__ __forceinline__ void wgmma32(float (&d)[4][4], const uint32_t (&a)[4], uint32_t dlo) {
    asm volatile("{ .reg .b64 ds; mov.b64 ds, {%20, %21};\n"
                 "wgmma.mma_async.sync.aligned.m64n32k16.f32.f16.f16 {%0,%1,%2,%3,%4,%5,%6,%7,%8,%9,%10,%11,%12,%13,%14,%15}, {%16,%17,%18,%19}, ds, 1, 1, 1, 0; }"
        : "+f"(d[0][0]), "+f"(d[0][1]), "+f"(d[0][2]), "+f"(d[0][3]), "+f"(d[1][0]), "+f"(d[1][1]), "+f"(d[1][2]), "+f"(d[1][3]),
          "+f"(d[2][0]), "+f"(d[2][1]), "+f"(d[2][2]), "+f"(d[2][3]), "+f"(d[3][0]), "+f"(d[3][1]), "+f"(d[3][2]), "+f"(d[3][3])
        : "r"(a[0]), "r"(a[1]), "r"(a[2]), "r"(a[3]), "r"(dlo), "n"(128 >> 4));
}

__global__ void __cluster_dims__(CS, 1, 1) __launch_bounds__(NTHR, 1)
fused_kernel(const __grid_constant__ Params prm, const __grid_constant__ CUtensorMap tmG, const __grid_constant__ CUtensorMap tmU,
             const __grid_constant__ CUtensorMap tmD, const __grid_constant__ CUtensorMap tmO, const __grid_constant__ CUtensorMap tmX)
{
    extern __shared__ __align__(1024) unsigned char smem[];
    const int tid = threadIdx.x, lane = tid & 31, warp = __shfl_sync(~0u, tid >> 5, 0);
    const int c = blockIdx.x >> 3, q = blockIdx.x & 7;
    const int nslot = (c < NCL - 1) ? 5 : 2;
    const int d0 = 40 * c;
    const uint32_t sb = opaque((uint32_t)__cvta_generic_to_shared(smem));
    const uint32_t mb = sb + SM_MB;
    Scratch& g_s = *prm.gs;
    const unsigned& zero = prm.zero;
    STAMP(0);

    if (warp >= 20) {
        unsigned epoch = 0;
        if (warp == 20) {
            if (lane == 0) {
#pragma unroll
                for (int i = 0; i < 13; i++)
                    asm volatile("mbarrier.init.shared::cta.b64 [%0], %1;" :: "r"(mb + i * 8), "r"((i == MB_R || i == MB_T) ? 2 : i == MB_Y ? 1 + 4 * nslot : 1) : "memory");
                asm volatile("fence.mbarrier_init.release.cluster;" ::: "memory");
                arm(mb + MB_W1 * 8, 92160); arm(mb + MB_W2 * 8, nslot * 9216); arm(mb + MB_KEY * 8, 256); arm(mb + MB_GU * 8, nslot * 1024); arm(mb + MB_T * 8, 20480);
                const int bytes = max(min(18, L_ - 18 * (int)blockIdx.x), 1) * (D_ * 2);
                arm(mb + MB_R * 8, bytes);
                if (!ROW_DELAY) asm volatile("cp.async.bulk.shared::cluster.global.mbarrier::complete_tx::bytes [%0], [%1], %2, [%3];"
                             :: "r"(sb + SM_ROW), "l"(prm.x + min(18 * (int)blockIdx.x, L_ - 1) * D_), "r"(bytes), "r"(mb + MB_R * 8) : "memory");
            }
            __syncwarp();
        } else if (warp == 22) {
            epoch = ld_rlx(&g_s.epoch);
            if (lane < 18 ? 18 * c + lane < 256 : lane < 31) (lane < 18 ? &g_s.acc[256 * q + 18 * c] : &g_s.fin[13 * (int)blockIdx.x - 18])[lane] = make_float4(0.f, 0.f, 0.f, 0.f);
        } else if (warp == 23 && lane == 0) asm volatile("prefetch.tensormap [%0];" :: "l"(&tmX) : "memory");
        asm volatile("barrier.cluster.arrive.relaxed.aligned;" ::: "memory");
        bar_sync(12, NTHR);
        if (warp == 22) {
            if (lane == 0) { sts32(sb + SM_SC + 28, epoch); asm volatile("mbarrier.arrive.shared::cta.b64 _, [%0];" :: "r"(mb + MB_R * 8) : "memory"); }
            epoch++;
            asm volatile("fence.acq_rel.gpu;" ::: "memory");
            __syncwarp();
            if (lane == 0) asm volatile("red.relaxed.gpu.global.add.u32 [%0], 1;" :: "l"(&g_s.zcnt) : "memory");
            STAMP(1);
            uint4 wv = make_uint4(0, 0, 0, 0), wv2 = ldg128((const uint4*)prm.wr + lane), wv3 = ldg128((const uint4*)prm.wr + 32 + lane);
            if (lane < 8) wv = ldg128((const uint4*)prm.wr + 64 + lane);
            if (lane < 5) {
                uint4 v = make_uint4(0, 0, 0, 0);
                if (lane < nslot) v = ldg128((const uint4*)(prm.wr + d0) + lane);
                sts128(sb + SM_DW + lane * 16, v.x, v.y, v.z, v.w);
            }
            __syncwarp();
            if (lane == 0) asm volatile("mbarrier.arrive.shared::cta.b64 _, [%0];" :: "r"(mb + MB_T * 8) : "memory");
            mbar_wait(mb + (MB_X + 1) * 8);
            const uint32_t old = (epoch & 1) ? 0u : 0x40004000u;
#pragma unroll
            for (int t = 0; t < 2; t++)
                if ((lane & 7) < 6) g_s.cand[((q * 8 + 4 * t + (lane >> 3)) * NCL + c) * 6 + (lane & 7)] = make_uint4(old, old, old, old);
            float a[4] = {0.f, 0.f, 0.f, 0.f};
            const uint32_t one = 0x3F803F80u;
            mma_bf16(a, one, one, one, one, wv.x, wv.y);  mma_bf16(a, one, one, one, one, wv.z, wv.w);
            mma_bf16(a, one, one, one, one, wv2.x, wv2.y); mma_bf16(a, one, one, one, one, wv2.z, wv2.w);
            mma_bf16(a, one, one, one, one, wv3.x, wv3.y); mma_bf16(a, one, one, one, one, wv3.z, wv3.w);
            float s = a[0] + a[1];
            s += __shfl_xor_sync(~0u, s, 1); s += __shfl_xor_sync(~0u, s, 2);
            stsf(sb + SM_SC + 24, s);
            __syncwarp();
            if (lane == 0) {
                int n = 0;
                while ((int)(ld_acq(&g_s.zcnt) - epoch * NCTA) < 0 && ++n < SPIN_LIMIT) __nanosleep(200);
                arm(mb + MB_Y * 8, 8 * 512 * nslot);
                if (blockIdx.x == 0) g_s.epoch = epoch;
            }
            STAMP(2);
            return;
        }
        if (warp == 21) {
            if (STREAM_T) { bar_arrive(13, 736); mbar_wait(mb + MB_T * 8); } else bar_sync(13, 736);
            if (GAP_NS) __nanosleep(GAP_NS);
#pragma unroll 1
            for (int i = 0; i < 24; i++) {
                if (i == 13) { bar_sync(15, 544); asm volatile("fence.proxy.async.shared::cta;" ::: "memory"); }
                if (lane == 0) tma2d(sb + SM_WG + i * 3840, i < 12 ? &tmG : &tmU, 320 * c + 8 * nslot * q, 48 * (i < 12 ? i : i - 12), mb + MB_W1 * 8);
                __nanosleep(PACE_NS);
            }
            STAMP(1);
            return;
        }
        if (warp == 20) {
            if (ROW_DELAY && lane == 0) {
                const long long t0 = clock64(); while (clock64() - t0 < ROW_DELAY) {}
                asm volatile("cp.async.bulk.shared::cluster.global.mbarrier::complete_tx::bytes [%0], [%1], %2, [%3];"
                             :: "r"(sb + SM_ROW), "l"(prm.x + min(18 * (int)blockIdx.x, L_ - 1) * D_), "r"(max(min(18, L_ - 18 * (int)blockIdx.x), 1) * (D_ * 2)), "r"(mb + MB_R * 8) : "memory");
            }
            __syncwarp();
            mbar_wait(mb + MB_R * 8);
            if (lane == 0) {
                asm volatile("cp.async.bulk.tensor.3d.shared::cluster.global.mbarrier::complete_tx::bytes [%0], [%1, {%3, %4, %5}], [%2];"
                             :: "r"(sb + SM_XTL), "l"(&tmX), "r"(mb + MB_T * 8), "r"(d0), "r"(8 * q), "r"(0) : "memory");
            }
            STAMP(6);
        }
        if (PRE_N && warp == 23) {
            mbar_wait(mb + MB_R * 8);
            const char* wp = prm.w3[0] + blockIdx.x * (PRE_N * 4096) + lane * 128;
#pragma unroll 1
            for (int i = 0; i < PRE_N; i++) { asm volatile("prefetch.global.L2 [%0];" :: "l"(wp + i * 4096) : "memory"); __nanosleep(PRE_NS); }
        }
        asm volatile("barrier.cluster.wait.aligned;" ::: "memory");
        bar_sync(13, 736);
        if (CFENCE) asm volatile("fence.proxy.async.shared::cta;" ::: "memory");
        {
            const int gr = lane >> 2, pe = (lane & 3) * 2 + (warp & 1);
            const int s0 = gr ? 0 : XSPLIT, ns = gr ? min(XSPLIT, nslot) : nslot - XSPLIT;
            if (gr < 2 && ns > 0) {
                const int bytes = ns * YS - 160;
                if (pe == q) arm(mb + (MB_X + gr) * 8, 7 * bytes);
                else {
                    const uint32_t rb_ = mapa(sb, pe);
                    asm volatile("cp.async.bulk.shared::cluster.shared::cta.mbarrier::complete_tx::bytes [%0], [%1], %2, [%3];"
                                 :: "r"(rb_ + SM_U + 128 + q * UP + s0 * US), "r"(sb + SM_XT + 128 + pe * YP + s0 * YS), "r"(bytes), "r"(rb_ + SM_MB + (MB_X + gr) * 8) : "memory");
                }
            }
        }
        STAMP(1);
        if (warp == 23) {
#pragma unroll 1
            for (int kk = nslot - 1; kk >= 0; kk--) {
                __syncwarp();
                bar_sync(6 + kk, 160);
                if (lane == 0) { asm volatile("fence.proxy.async.shared::cta;" ::: "memory"); tma2d(sb + SM_FAR + kk * FAR_SZ, &tmD, 72 * q, 320 * c + 64 * kk, mb + MB_W2 * 8); }
            }
            return;
        }
        __syncwarp();
        bar_sync(14, 672);
        if (lane == 0) {
            if (CFENCE) asm volatile("fence.proxy.async.shared::cta;" ::: "memory");
            if (!NO_OUT) asm volatile("cp.async.bulk.tensor.5d.global.shared::cta.bulk_group [%0, {%2, %4, %4, %4, %3}], [%1];" :: "l"(&tmO), "r"(sb + SM_XT), "r"(d0), "r"(8 * q), "r"(0) : "memory");
            asm volatile("cp.async.bulk.commit_group;" ::: "memory");
            asm volatile("cp.async.bulk.wait_group 0;" ::: "memory");
            asm volatile("fence.proxy.async.global;" ::: "memory");
            asm volatile("mbarrier.arrive.shared::cta.b64 _, [%0];" :: "r"(mb + MB_OUT * 8) : "memory");
        }
        STAMP(2);
        return;
    }

    const int g = lane >> 2, cq = lane & 3;
    const int k = warp >> 2, wq = warp & 3;
    const int trow = 18 * blockIdx.x + warp;
    const bool rowact = warp < 18 && trow < L_;
    const int dch = min(d0 + 8 * k + q, D_ - 1);
    uint32_t pv[6];
#pragma unroll
    for (int i = 0; i < 6; i++) pv[i] = ldg16(prm.prm6[i] + (uint32_t)(dch * 128 + wq * 32 + lane));
    const uint32_t pLdt = ldg16(prm.logdt + dch), pD = ldg16(prm.dskip + dch);
    const int tn = 16 * (warp & 15) + g;
    uint32_t xa[5], xb[5];
    asm volatile("barrier.cluster.arrive.relaxed.aligned;" ::: "memory");
    uint4* const st1p = &g_s.st1[(((trow >> 3) & 7) * 256 + ((trow >> 6) & 31) * 8 + (trow & 7)) * 2 + (lane >> 2)];
    const bool pub = rowact && (lane & 0x1B) == 0;
    if (pub) st_rlx128(st1p, 0, 0, 0, 0);
    {
        const uint32_t za = sb + SM_P + tid * 16;
        sts128(za, 0, 0, 0, 0);
        if (tid < (SM_MISC - SM_P) / 16 - 640) sts128(za + 10240, 0, 0, 0, 0);
        sts128(sb + SM_XT + ((tid >> 3) & 15) * YP + k * YS + (lane & 7) * 16, 0, 0, 0, 0);
    }
    bar_sync(12, NTHR);
    const uint32_t dep = lds32(sb + SM_P);
#define PV(x) __uint_as_float(__byte_perm(dep, x, 0x5410))
    STAMP(1);
    const uint32_t fb = sb + SM_FAR + k * FAR_SZ;
    const uint32_t pn = sb + SM_PN + k * PN_SZ, pf = sb + SM_PF + k * PF_SZ;
    unsigned epoch;
    {
        const uint32_t kb = fb + wq * 3072;
        const uint32_t kl = kb + lane * 16;
        uint32_t Af[4][4];
        float sr, si, z1r, z1i, z2r, z2i, z4r, z4i, hr, hi_;
        {
            const float dt = bfr(ex2f(PV(pLdt) * 1.4426950408889634f));
            const float e2 = dt * PV(pv[0]) * 1.4426950408889634f, an = dt * PV(pv[1]);
            cmul(sr, si, PV(pv[4]), PV(pv[5]), dt * PV(pv[2]), dt * PV(pv[3]));
            const unsigned E = min(max(__reduce_max_sync(~0u, __float_as_uint(fmaxf(fmaxf(fabsf(sr), fabsf(si)), fabsf(PV(pD)) * (1.f / 8192.f)))) >> 23, 1u), 253u);
            const float sc = __uint_as_float((254u - E) << 23);
            sr *= sc; si *= -sc;
            sts64(sb + SM_KG + warp * 8, E, __reduce_add_sync(~0u, __float2int_rn(sr * 16777216.f)));
            float ar, ai, br, bi, cr, ci, dr, di;
            { const float m = ex2f(e2 * 8.f); ar = m * __cosf(an * 8.f); ai = m * __sinf(an * 8.f); }
            csq(br, bi, ar, ai); csq(cr, ci, br, bi); csq(dr, di, cr, ci);
            const H2C m4 = splat(cr, ci);
            {
                float r3, i3;
                cmul(r3, i3, ar, ai, br, bi);
                expand4(kl, kl + 1024, pack_f16(1.f, ar), pack_f16(br, r3), pack_f16(0.f, ai), pack_f16(bi, i3), m4);
            }
            expand8(kl + 512, kl + 1536, dr, di, ar, ai, br, bi, m4);
            { const float m = ex2f(e2); z1r = m * __cosf(an); z1i = -m * __sinf(an); }
            cexp_s(hr, hi_, e2 * 128.f, an * (-128.f * 0.15915494309189535f));
            csq(z2r, z2i, z1r, z1i); csq(z4r, z4i, z2r, z2i);
        }
        __syncwarp();
#pragma unroll
        for (int ks = 0; ks < 4; ks++) ldsm4t(Af[ks], kb + (lane >> 3) * 512 + (lane & 7) * 16 + ks * 128);
        STAMP(2);
        const uint32_t la = kb + ((lane >> 3) & 1) * 512 + (lane >> 4) * 128 + (lane & 7) * 16;
        uint32_t kp[5][2], b0[4], b1[4], b2[4], b3[4];
        auto mm2 = [&](int t) {
            float a0[4] = {0.f, 0.f, 0.f, 0.f}, a1[4] = {0.f, 0.f, 0.f, 0.f};
            mma_f16(a0, Af[0], b0[0], b0[1]); mma_f16(a1, Af[0], b2[0], b2[1]); mma_f16(a0, Af[1], b0[2], b0[3]); mma_f16(a1, Af[1], b2[2], b2[3]);
            mma_f16(a0, Af[2], b1[0], b1[1]); mma_f16(a1, Af[2], b3[0], b3[1]); mma_f16(a0, Af[3], b1[2], b1[3]); mma_f16(a1, Af[3], b3[2], b3[3]);
            kp[t][0] = pack_f16(a0[1], a0[0]); kp[t][1] = pack_f16(a0[3], a0[2]); kp[t + 1][0] = pack_f16(a1[1], a1[0]); kp[t + 1][1] = pack_f16(a1[3], a1[2]);
        };
        auto ln1 = [&]() {
        mbar_wait(mb + MB_R * 8);
        epoch = lds32(sb + SM_SC + 28) + 1;
        {
            float a[4] = {0.f, 0.f, 0.f, 0.f}, b[4] = {0.f, 0.f, 0.f, 0.f};
            uint32_t rx[9];
#pragma unroll
            for (int i = 0; i < 9; i++) rx[i] = lds32(sb + SM_ROW + warp * (D_ * 2) + lane * 4 + i * 128);
#pragma unroll
            for (int i = 0; i < 9; i++) { if (i & 1) mma_bf16_k8(b, rx[i], 0x3F803F80u, rx[i]); else mma_bf16_k8(a, rx[i], 0x3F803F80u, rx[i]); }
            float s2 = (g & 1) ? a[1] + b[1] : a[0] + b[0], s1 = (a[2] + b[2]) + (a[3] + b[3]);
            s2 += __shfl_xor_sync(~0u, s2, 4); s1 += __shfl_xor_sync(~0u, s1, 1);
            s2 += __shfl_xor_sync(~0u, s2, 9); s1 += __shfl_xor_sync(~0u, s1, 2);
            s2 += __shfl_xor_sync(~0u, s2, 18);
            const uint32_t ms = ln_stats(s1, s2);
            if (pub) st_rlx128(st1p, ms, epoch, ms, epoch);
        }
        mbar_wait(mb + MB_R * 8);
        };
        auto norm = [&]() {
        STAMP(3);
        if (warp < 16) {
            const uint4* sp = &g_s.st1[(256 * q + tn) * 2];
            uint32_t va[5], vc[5];
            mbar_wait(mb + MB_T * 8);
            {
                const uint32_t xt = sb + SM_XTL + tn * 80;
                uint4 a4 = lds128(xt + cq * 16), b4 = lds128(xt + cq * 16 + 640);
                va[0] = a4.x; va[1] = a4.y; va[2] = a4.z; va[3] = a4.w; va[4] = lds32(xt + 64 + cq * 4);
                vc[0] = b4.x; vc[1] = b4.y; vc[2] = b4.z; vc[3] = b4.w; vc[4] = lds32(xt + 704 + cq * 4);
            }
            uint2 sa, sc; int n = 0;
            do { sa = ld_rlx64(sp); sc = ld_rlx64(sp + 16); } while ((sa.y != epoch || sc.y != epoch) && ++n < SPIN_LIMIT);
            STAMP(4);
            const uint32_t ra = rsplit(rcpf(bf_hi(sa.x))), rc = rsplit(rcpf(bf_hi(sc.x)));
            const uint32_t ma = __byte_perm(sa.x, 0, 0x1010), mc = __byte_perm(sc.x, 0, 0x1010);
            const uint32_t rha = __byte_perm(ra, 0, 0x1010), rla = __byte_perm(ra, 0, 0x3232), rhc = __byte_perm(rc, 0, 0x1010), rlc = __byte_perm(rc, 0, 0x3232);
#pragma unroll
            for (int i = 0; i < 5; i++) {
                va[i] = norm2(va[i], ma, rha, rla); va[i] = pack_f16(bf_lo(va[i]), bf_hi(va[i]));
                vc[i] = norm2(vc[i], mc, rhc, rlc); vc[i] = pack_f16(bf_lo(vc[i]), bf_hi(vc[i]));
            }
            const int d4 = 2 * (lane >> 3) + (lane & 1), d1_ = lane & 7;
            const uint32_t a4 = sb + warp * 32 + d4 * YP + (d4 == q ? SM_U + 128 : SM_XT + 128) + ((lane & 7) >> 1) * YS;
            const uint32_t a1 = sb + warp * 32 + d1_ * YP + (d1_ == q ? SM_U + 128 : SM_XT + 128) + 4 * YS + (lane & 8) * 2;
            stsm4t(a4, va[0], va[1], va[2], va[3]); stsm4t(a4 + 16, vc[0], vc[1], vc[2], vc[3]); stsm2t(a1, va[4], vc[4]);
        }
        if (!CFENCE) asm volatile("fence.proxy.async.shared::cta;" ::: "memory");
        bar_arrive(13, 736);
        if (warp < 16) {
            const uint32_t xh = sb + SM_XTL + (64 * (g >> 1) + 32 * (warp & 1) + 8 * (g & 1) + (warp >> 1)) * 80;
            const uint4 a4 = lds128(xh + cq * 16), b4 = lds128(xh + cq * 16 + 1280);
            xa[0] = a4.x; xa[1] = a4.y; xa[2] = a4.z; xa[3] = a4.w; xa[4] = lds32(xh + 64 + cq * 4);
            xb[0] = b4.x; xb[1] = b4.y; xb[2] = b4.z; xb[3] = b4.w; xb[4] = lds32(xh + 1344 + cq * 4);
            bar_arrive(15, 544);
        }
        STAMP(5);
        };
        if (LNPOS == 0) ln1();
        cmul(sr, si, sr, si, z1r, z1i);
        {
            const H2C h4 = splat(z4r, z4i);
            expand8(kl, kl + 512, sr, si, z1r, z1i, z2r, z2i, h4);
            cmul(sr, si, sr, si, hr, hi_);
            expand8(kl + 1024, kl + 1536, sr, si, z1r, z1i, z2r, z2i, h4);
        }
        __syncwarp();
        ldsm4t(b0, la); ldsm4t(b1, la + 256); ldsm4t(b2, la + 1024); ldsm4t(b3, la + 1280);
        cmul(z1r, z1i, z1r, z1i, hr, hi_);
        cmul(sr, si, sr, si, z1r, z1i);
        if (LNPOS == 1) ln1();
        expand8(kl, kl + 512, sr, si, z2r, z2i, z4r, z4i, splat(hr, hi_));
        mm2(0);
        if (LNPOS == 2) ln1();
        if (NMPOS == 2) norm();
        csq(z1r, z1i, z1r, z1i);
        cmul(sr, si, sr, si, z1r, z1i);
        csq(z2r, z2i, hr, hi_);
        expand8(kl + 1024, kl + 1536, sr, si, z4r, z4i, hr, hi_, splat(z2r, z2i));
        __syncwarp();
        ldsm4t(b0, la); ldsm4t(b1, la + 256); ldsm4t(b2, la + 1024); ldsm4t(b3, la + 1280);
        csq(z1r, z1i, z1r, z1i);
        cmul(sr, si, sr, si, z1r, z1i);
        csq(z4r, z4i, z2r, z2i);
        expand8(kl, kl + 512, sr, si, hr, hi_, z2r, z2i, splat(z4r, z4i));
        mm2(2);
        if (LNPOS == 3) ln1();
        if (NMPOS == 3) norm();
        __syncwarp();
        ldsm4t(b0, la); ldsm4t(b1, la + 256);
#pragma unroll
        for (int t = 0; t < 4; t++) sts64(kb + lane * 8 + 1024 + t * 256, kp[t][0], kp[t][1]);
        {
            float a0[4] = {0.f, 0.f, 0.f, 0.f}, a1[4] = {0.f, 0.f, 0.f, 0.f};
            mma_f16(a0, Af[0], b0[0], b0[1]); mma_f16(a1, Af[1], b0[2], b0[3]); mma_f16(a0, Af[2], b1[0], b1[1]); mma_f16(a1, Af[3], b1[2], b1[3]);
            sts64(kb + lane * 8 + 2048, pack_f16(a0[1] + a1[1], a0[0] + a1[0]), pack_f16(a0[3] + a1[3], a0[2] + a1[2]));
        }
        if (NMPOS == 4) norm();
        bar_sync(1 + k, 128);
        const uint4 m01 = lds128(sb + SM_KG + k * 32), m23 = lds128(sb + SM_KG + k * 32 + 16);
        const unsigned Em = max(max(m01.x, m01.z), max(m23.x, m23.z));
        const float f0 = __uint_as_float(max((int)(127 + m01.x - Em), 0) << 23), f1 = __uint_as_float(max((int)(127 + m01.z - Em), 0) << 23),
                    f2 = __uint_as_float(max((int)(127 + m23.x - Em), 0) << 23), f3 = __uint_as_float(max((int)(127 + m23.z - Em), 0) << 23);
        const uint32_t r0 = pack_f16(f0, f0), r1 = pack_f16(f1, f1), r2 = pack_f16(f2, f2), r3 = pack_f16(f3, f3);
        const uint32_t ra = fb + lane * 8 + wq * 256 + 1024;
        const uint2 p0 = lds64(ra), p1 = lds64(ra + 3072), p2 = lds64(ra + 6144), p3 = lds64(ra + 9216);
        uint32_t w0 = hadd2(hfma2(p0.x, r0, hmul2(p1.x, r1)), hfma2(p2.x, r2, hmul2(p3.x, r3)));
        uint32_t w1 = hadd2(hfma2(p0.y, r0, hmul2(p1.y, r1)), hfma2(p2.y, r2, hmul2(p3.y, r3)));
        const bool last = lane == 31;
        if (wq < 2) {
            const uint32_t rc = fb + lane * 8 + wq * 4 + 2048;
            const uint32_t w4 = hmul2(hadd2(hfma2(lds32(rc), r0, hmul2(lds32(rc + 3072), r1)), hfma2(lds32(rc + 6144), r2, hmul2(lds32(rc + 9216), r3))), 0x18001800u);
            const uint32_t ph = pf + (P_H7 + 16 * wq) + (g & 1) * (2 * P_HS) + cq * 64 + (g >> 1) * 4;
            put16(ph, w4 >> 16); put16(ph + 32, w4);
            const uint32_t pa = pn + (4 + 512 * wq) + lane * 8;
            sts16(pa, w0 >> 16); sts32(pa + 4, w0); sts16(pa + 10, w0);
            sts16(pa + 256, w1 >> 16); sts32(pa + 260, w1); sts16(pa + 266, w1);
            if (last) {
                sts32(sb + SM_SC + k * 4, Em * 0x00800080u);
                put16(wq ? pa + 264 : pn,
                      wq ? w1 : pack_f16(((float)(int)m01.y * f0 + (float)(int)m01.w * f1 + (float)(int)m23.y * f2 + (float)(int)m23.w * f3) * (1.f / 16777216.f)
                                         + __uint_as_float(pD << 16) * __uint_as_float((254u - Em) << 23), 0.f));
            }
        } else if (wq == 2) {
            const uint32_t pa = pn + 258 * 4 + (cq & 1) * 16 + (cq >> 1) * 512 + g * 32;
            if (last) { put16(pf, hmul2(w1, 0x18001800u)); w1 = hadd2(w1, hneg2(__byte_perm(w1, 0, 0x1010))); }
            const uint32_t b0 = __byte_perm(w0, 0, 0x1010), b1 = __byte_perm(w1, 0, 0x1010);
            sts16(pa, w0 >> 16); sts32(pa + 4, w0); sts64(pa + 8, b0, b0); sts16(pa + 18, w0);
            sts16(pa + 256, w1 >> 16); sts32(pa + 260, w1); sts64(pa + 264, b1, b1); sts16(pa + 274, w1);
        } else {
            const uint32_t pa = pf + ((g & 1) ? 3 * P_GS : P_GS) + cq * 32 + (g >> 1) * 4;
            const uint32_t pb = pa + ((g & 1) ? 4 - 3 * P_GS : P_GS);
            w0 = hmul2(w0, 0x18001800u); w1 = hmul2(w1, 0x18001800u);
            put16(pa, w0 >> 16); put16(pb, w0); put16(pa + 16, w1 >> 16); put16(pb + 16, w1);
            if (last) put16(pf + P_H7 + P_HS, w1);
        }
        bar_sync(1 + k, 128);
    }
    STAMP(6);

    asm volatile("barrier.cluster.wait.aligned;" ::: "memory");
    mbar_wait(mb + (MB_X + (k < XSPLIT || k >= nslot)) * 8);
    STAMP(7);
    if (k < nslot) {
        const int role = (wq + k) & 3;
        const uint32_t ub = sb + SM_U + k * US + 128;
        if (role) {
            const int r = (3 - role) * 32 + lane;
            const uint32_t a1 = ub + (r & 3) * (2 * UP) + (r >> 2) * 16, a0 = a1 + ((r & 3) ? -2 * UP : 6 * UP - 16);
            const uint4 q0 = lds128(a0), q1 = lds128(a0 + UP), q2 = lds128(a1), q3 = lds128(a1 + UP);
            const uint32_t U[16] = {q0.x, q0.y, q0.z, q0.w, q1.x, q1.y, q1.z, q1.w, q2.x, q2.y, q2.z, q2.w, q3.x, q3.y, q3.z, q3.w};
            uint32_t V[14], Q[14], R4[12], T[8];
#pragma unroll
            for (int i = 2; i < 14; i++) { V[i] = __byte_perm(U[i], U[i + 1], 0x5432); Q[i] = hadd2(U[i], V[i]); }
#pragma unroll
            for (int i = 2; i < 12; i++) R4[i] = hadd2(Q[i], Q[i + 1]);
            const uint32_t rb = fb + r * 16;
#pragma unroll
            for (int i = 0; i < 8; i++) T[i] = hadd2(V[5 + i], Q[6 + i]);
            sts128(rb + F_E3, T[0], T[1], T[2], T[3]); sts128(rb + F_O3 + 16, T[4], T[5], T[6], T[7]);
#pragma unroll
            for (int i = 0; i < 8; i++) T[i] = hadd2(R4[3 + i], U[5 + i]);
            sts128(rb + F_O5, T[0], T[1], T[2], T[3]); sts128(rb + F_E5, T[4], T[5], T[6], T[7]);
            if (role != 1) {
#pragma unroll
                for (int i = 0; i < 8; i++) T[i] = hadd2(T[i], hadd2(V[2 + i], V[5 + i]));
                sts128(rb + F_E7, T[0], T[1], T[2], T[3]); sts128(rb + F_O7, T[4], T[5], T[6], T[7]);
#pragma unroll
                for (int i = 0; i < 8; i++) T[i] = hadd2(R4[2 + i], hadd2(R4[4 + i], U[6 + i]));
                sts128(rb + F_O9, T[0], T[1], T[2], T[3]); sts128(rb + F_E9 + 16, T[4], T[5], T[6], T[7]);
                sts128(rb + F_E2, Q[6], Q[7], Q[8], Q[9]); sts128(rb + F_O2, Q[10], Q[11], Q[12], Q[13]);
            }
        } else if (lane < 8) {
            uint32_t v[5];
#pragma unroll
            for (int i = 0; i < 5; i++) { const int t = 6 + lane + i; v[i] = lds16(ub + 23 * 16 + (t < 16 ? (6 + (t >> 3)) * UP : 16) + (t & 7) * 2); }
            const uint32_t s = hadd2(hadd2(hadd2(v[0], v[1]), hadd2(v[2], v[3])), v[4]);
            sts16(fb + F_O5 + 96 * 16 + lane * 2, s);
            sts32(fb + (lane < 4 ? F_O3 : F_E9 - 16) + lane * 4, 0);
        }
        bar_sync(1 + k, 128);
        float acc[4][4];
        uint32_t Q[4][4];
        {
            const int h = role & 1, part = role >> 1;
            const uint32_t po = pf + (g - 2 * cq) * 4;
            float fa[7][4];
#pragma unroll
            for (int a = 0; a < 7; a++) fa[a][0] = fa[a][1] = fa[a][2] = fa[a][3] = 0.f;
            uint32_t B[3][4];
            Q[0][2] = zero;
#pragma unroll 1
            for (int s = 2 * part + 1; s >= 2 * part; s--) {
#pragma unroll
                for (int i = 0; i < 3; i++) { Q[i][0] = lds32(po + s * P_GS + i * 64); Q[i][1] = lds32(po + s * P_GS + (i * 64 + 32)); }
                const uint32_t ba = fb + lane * 16 + ((s & 1) * F_E3 + (part == h ? 0 : F_O5 + h * 16));
#pragma unroll
                for (int i = 0; i < 3; i++) ldsm4t(B[i], ba + i * 512);
#pragma unroll
                for (int i = 0; i < 3; i++) { Q[i][3] = CP(Q[i][0]); if (i) Q[i][2] = CP(Q[i - 1][1]); }
#pragma unroll
                for (int dl = 0; dl < 3; dl++)
#pragma unroll
                    for (int ap = 0; ap < 6 - dl; ap++) mma_f16(fa[ap + 1 + dl], Q[dl], B[ap >> 1][2 * (ap & 1)], B[ap >> 1][2 * (ap & 1) + 1]);
            }
#pragma unroll 1
            for (int s = role; s == 1; s++) {
                ldsm2t(B[0][0], B[0][1], fb + ((lane & 15) == 15 ? F_O5 : F_O3));
#pragma unroll
                for (int dl = 0; dl < 3; dl++) mma_f16(fa[dl], Q[dl], B[0][0], B[0][1]);
            }
#pragma unroll 1
            for (int s = part; s <= 2 * part; s++) {
#pragma unroll
                for (int i = 0; i < 4; i++) { Q[i][0] = lds32(po + s * P_HS + (P_H7 + i * 64)); Q[i][1] = lds32(po + s * P_HS + (P_H7 + i * 64 + 32)); }
                const uint32_t ba = fb + lane * 16 + (F_E7 + s * 1024 + h * F_H);
                ldsm4t(B[0], ba); ldsm4t(B[1], ba + 512);
#pragma unroll
                for (int i = 0; i < 4; i++) { Q[i][3] = CP(Q[i][0]); if (i) Q[i][2] = CP(Q[i - 1][1]); }
#pragma unroll
                for (int dl = 0; dl < 4; dl++) {
#pragma unroll
                    for (int ap = 0; ap < 4 - dl; ap++) mma_f16(fa[ap + 3 + dl], Q[dl], B[ap >> 1][2 * (ap & 1)], B[ap >> 1][2 * (ap & 1) + 1]);
                    if (s == 1) break;
                }
            }
            const uint32_t da = fb + role * 2048 + (lane & 3) * 512 + (((lane >> 2) ^ ((lane & 3) * 2)) << 4);
            bar_sync(1 + k, 128);
            stsm4(da, 0u, 0u, pack_f16(fa[0][0], fa[0][1]), pack_f16(fa[0][2], fa[0][3]));
#pragma unroll
            for (int i = 1; i < 4; i++)
                stsm4(da + i * 128, pack_f16(fa[2 * i - 1][0], fa[2 * i - 1][1]), pack_f16(fa[2 * i - 1][2], fa[2 * i - 1][3]),
                      pack_f16(fa[2 * i][0], fa[2 * i][1]), pack_f16(fa[2 * i][2], fa[2 * i][3]));
            Q[0][0] = (g == 2 * cq) ? 0x6000u : ((g == 2 * cq + 1) ? 0x60000000u : 0u);
            Q[0][1] = 0; Q[0][3] = CP(Q[0][0]);
            const uint32_t ra = fb + (lane >> 3) * 2048 + wq * 512 + (((lane & 7) ^ (wq * 2)) << 4);
            bar_sync(1 + k, 128);
#pragma unroll
            for (int i = 0; i < 4; i++) {
                ldsm4(B[0], ra + i * 128);
                acc[i][0] = acc[i][1] = acc[i][2] = acc[i][3] = 0.f;
                mma_f16(acc[i], Q[0], hadd2(B[0][0], B[0][2]), hadd2(B[0][1], B[0][3]));
            }
        }
        bar_arrive(6 + k, 160);
        STAMP(8);
        const uint32_t inv = lds32(sb + SM_SC + k * 4);
        uint32_t yd = mapa(sb, 2 * wq) + (SM_XT + 128 + q * YP + k * YS) + lane * 16;
        PIN(yd);
        {
            uint32_t pp = pn + (16 * (wq - 3) + g - 2 * cq) * 4;
            uint32_t dlo = (((ub + 6 * UP) & 0x3FFFF) >> 4) | ((UP >> 4) << 16);
            uint32_t R[4][4];
            auto loadQ = [&](uint32_t (&X)[4][4], uint32_t prev) {
#pragma unroll
                for (int i = 0; i < 4; i++) { X[i][0] = lds32(pp + i * 64); X[i][1] = lds32(pp + i * 64 + 32); }
                X[0][2] = CP(prev);
#pragma unroll
                for (int i = 0; i < 4; i++) { X[i][3] = CP(X[i][0]); if (i) X[i][2] = CP(X[i - 1][1]); }
                pp += 256;
            };
            auto issue = [&](uint32_t (&X)[4][4]) {
                asm volatile("wgmma.fence.sync.aligned;" ::: "memory");
#pragma unroll
                for (int i = 0; i < 4; i++) wgmma32(acc, X[i], dlo - i * (2 * UP >> 4));
                asm volatile("wgmma.commit_group.sync.aligned;" ::: "memory");
                dlo -= 1;
            };
            loadQ(Q, 0);
#pragma unroll 1
            for (int dl = 0; dl < 4; dl++) {
                issue(Q);
                asm volatile("wgmma.wait_group.sync.aligned 1;" ::: "memory");
                loadQ(R, Q[3][1]);
                issue(R);
                asm volatile("wgmma.wait_group.sync.aligned 1;" ::: "memory");
                loadQ(Q, R[3][1]);
            }
            issue(Q);
            asm volatile("wgmma.wait_group.sync.aligned 0;" ::: "memory");
        }
        const uint32_t pstep = mapa(sb, 1) - mapa(sb, 0), ym = mapa(mb + MB_Y * 8, 2 * wq);
#pragma unroll
        for (int e = 0; e < 2; e++)
            st_async4(yd + e * pstep, bmul2(pack_bf16(acc[0][2 * e], acc[0][2 * e + 1]), inv), bmul2(pack_bf16(acc[1][2 * e], acc[1][2 * e + 1]), inv),
                      bmul2(pack_bf16(acc[2][2 * e], acc[2][2 * e + 1]), inv), bmul2(pack_bf16(acc[3][2 * e], acc[3][2 * e + 1]), inv), ym + e * pstep);
        if (lane == 0) asm volatile("mbarrier.arrive.shared::cta.b64 _, [%0];" :: "r"(mb + MB_Y * 8) : "memory");
    }
    STAMP(9);
    uint32_t ha[5], hb[5];
    if (warp < 16) {
        const uint4 wk = lds128(sb + SM_DW + cq * 16);
        uint32_t sel[5] = {wk.x, wk.y, wk.z, wk.w, lds32(sb + SM_DW + 64 + cq * 4)}, sel2[5];
#pragma unroll
        for (int i = 0; i < 5; i++) {
            if (!(g & 1)) sel[i] = 0x3F803F80u;
            sel2[i] = sel[i]; PIN(sel2[i]);
        }
        const uint32_t y4 = sb + SM_XT + 128 + warp * 32 + (2 * (lane >> 3) + (lane & 1)) * YP + ((lane & 7) >> 1) * YS;
        const uint32_t y1 = sb + SM_XT + 128 + warp * 32 + (lane & 7) * YP + 4 * YS + (lane & 8) * 2;
        mbar_wait(mb + MB_Y * 8);
        STAMP(10);
        float ca[4] = {0.f, 0.f, 0.f, 0.f}, cb[4] = {0.f, 0.f, 0.f, 0.f};
        {
            uint32_t ya[4], yb[4], yc, yd;
            ldsm4t(ya, y4); ldsm4t(yb, y4 + 16); ldsm2t(yc, yd, y1);
#pragma unroll
            for (int i = 0; i < 4; i++) { ha[i] = badd2(xa[i], ya[i]); hb[i] = badd2(xb[i], yb[i]); }
            ha[4] = badd2(xa[4], yc); hb[4] = badd2(xb[4], yd);
        }
        if (nslot != 5) {
            ha[4] = hb[4] = 0;
            if (cq >= 2) ha[0] = ha[1] = ha[2] = ha[3] = hb[0] = hb[1] = hb[2] = hb[3] = 0;
        }
#pragma unroll
        for (int i = 0; i < 5; i++) { mma_bf16_k8(ca, ha[i], sel[i], ha[i]); mma_bf16_k8(cb, hb[i], sel2[i], hb[i]); }
        const float oa = __shfl_xor_sync(~0u, (g & 1) ? ca[2] : ca[3], 4), ob = __shfl_xor_sync(~0u, (g & 1) ? cb[2] : cb[3], 4);
        if (cq == (g >> 1)) {
            float4* ap = &g_s.acc[256 * q + tn];
            const bool od = g & 1;
            asm volatile("red.relaxed.gpu.global.add.v4.f32 [%0], {%1,%2,%3,%4};" :: "l"(ap), "f"(od ? oa : ca[2]), "f"(od ? ca[1] : ca[0]), "f"(od ? ca[3] : oa), "f"(1.0f) : "memory");
            asm volatile("red.relaxed.gpu.global.add.v4.f32 [%0], {%1,%2,%3,%4};" :: "l"(ap + 8), "f"(od ? ob : cb[2]), "f"(od ? cb[1] : cb[0]), "f"(od ? cb[3] : ob), "f"(1.0f) : "memory");
        }
        const uint32_t hta = sb + SM_HT + tn * 80;
        sts128(hta + cq * 16, ha[0], ha[1], ha[2], ha[3]); sts32(hta + 64 + cq * 4, ha[4]);
        sts128(hta + cq * 16 + 640, hb[0], hb[1], hb[2], hb[3]); sts32(hta + 704 + cq * 4, hb[4]);
        STAMP(11);
    }
    const int kq = warp / 5, mt = warp - 5 * kq;
    const int mi = lane >> 3, mr = lane & 7;
    const unsigned tk = (unsigned)tid / 72u, ck = tid - tk * 72;
    uint32_t A[9][4];
    auto loadA = [&]() {
        mbar_wait(mb + MB_W1 * 8);
        const uint32_t aa = sb + (mi & 1) * SM_WU + (8 * (mi >> 1) + mr) * 80 + (144 * 80 * kq + mt * 16);
#pragma unroll
        for (int s = 0; s < 9; s++) ldsm4t(A[s], aa + s * 1280);
    };
    const uint32_t par = (epoch & 1) ? 0x40004000u : 0u;
    uint32_t pk0 = mapa(sb, 2 * cq), go = (ck / 5u + ck) * 16, co = ((q * 8 * NCL + c) * 6 + cq) * 16;
    PIN(pk0); PIN(go); PIN(co);
    if (warp < 8) {
        const float wsum = ldsf(sb + SM_SC + 24);
        const uint32_t idx = 2047 - (512 * ((tid >> 1) & 3) + 128 * ((tid >> 3) & 3) + 64 * (tid & 1) + 8 * q + warp);
        if (RED_DELAY) { const long long t0 = clock64(); while (clock64() - t0 < RED_DELAY) {} }
        uint4 s; int n = 0;
        do { s = ld_rlx128(&g_s.acc[256 * q + tid]); } while (__uint_as_float(s.w) != (float)NCL && ++n < SPIN_LIMIT);
        STAMP(16);
        const uint32_t ms = ln_stats(__uint_as_float(s.x), __uint_as_float(s.y));
        const float rs = rcpf(bf_hi(ms));
        const uint32_t rb = pack_bf16(0.f, fmaf(-bf_lo(ms), wsum, __uint_as_float(s.z)) * rs);
        const uint32_t key = (((rb ^ (((int)rb >> 31) | 0x80000000u)) >> 16) << 11) | idx;
        sts32(sb + SM_KEY + tid * 4, key);
        __syncwarp();
        const uint32_t rank = rank4<8>(sb + SM_KEY + warp * 128, key);
        if (rank < 8) sts32(sb + SM_CAND + warp * 32 + rank * 4, key);
        sts64(sb + SM_ST + tid * 8, __byte_perm(ms, 0, 0x1010), rsplit(rs));
    } else loadA();
    if (warp < 16) {
        STAMP(17);
        bar_sync(12, 512);
        STAMP(18);
        if (warp < 8) {
            const uint32_t mk = lds32(sb + SM_CAND + (tid >> 2) * 4);
            uint32_t rank = rank4<4>(sb + SM_CAND + cq * 64, mk);
            rank += __shfl_xor_sync(~0u, rank, 1); rank += __shfl_xor_sync(~0u, rank, 2);
            if (rank < 8) {
                const uint32_t pk1 = pk0 + (mapa(sb, 1) - mapa(sb, 0));
                st_async1(pk0 + (SM_RK + q * 32) + rank * 4, mk, pk0 + (SM_MB + MB_KEY * 8));
                st_async1(pk1 + (SM_RK + q * 32) + rank * 4, mk, pk1 + (SM_MB + MB_KEY * 8));
                const uint32_t t = tslot(~mk);
                const uint2 sv = lds64(sb + SM_ST + t * 8);
                const uint4 hv = lds128(sb + SM_HT + t * 80 + cq * 16);
                const uint32_t h4 = lds32(sb + SM_HT + t * 80 + 64 + cq * 4);
                const uint32_t rr = bmul2(sv.y, 0x3C803C80u), rh = __byte_perm(rr, 0, 0x1010), rl = __byte_perm(rr, 0, 0x3232);
                char* const dp = (char*)g_s.cand + (co + rank * 1440);
                st_rlx128(dp, (norm2(hv.x, sv.x, rh, rl) & 0xBFFFBFFFu) | par, (norm2(hv.y, sv.x, rh, rl) & 0xBFFFBFFFu) | par,
                          (norm2(hv.z, sv.x, rh, rl) & 0xBFFFBFFFu) | par, (norm2(hv.w, sv.x, rh, rl) & 0xBFFFBFFFu) | par);
                asm volatile("st.relaxed.gpu.global.u32 [%0], %1;" :: "l"((char*)g_s.cand + (co + rank * 1440 + 64 - cq * 12)), "r"((norm2(h4, sv.x, rh, rl) & 0xBFFFBFFFu) | par) : "memory");
            }
            __syncwarp();
        }
        {
            const uint2 sa = lds64(sb + SM_ST + tn * 8), sbb = lds64(sb + SM_ST + tn * 8 + 64);
            const uint32_t rha = __byte_perm(sa.y, 0, 0x1010), rla = __byte_perm(sa.y, 0, 0x3232);
            const uint32_t rhb = __byte_perm(sbb.y, 0, 0x1010), rlb = __byte_perm(sbb.y, 0, 0x3232);
#pragma unroll
            for (int i = 0; i < 5; i++) { ha[i] = badd2(ha[i], norm2(ha[i], sa.x, rha, rla)); hb[i] = badd2(hb[i], norm2(hb[i], sbb.x, rhb, rlb)); }
            const uint32_t ota = sb + SM_XT + tn * 80;
            sts128(ota + cq * 16, ha[0], ha[1], ha[2], ha[3]); sts32(ota + 64 + cq * 4, ha[4]);
            sts128(ota + cq * 16 + 640, hb[0], hb[1], hb[2], hb[3]); sts32(ota + 704 + cq * 4, hb[4]);
            if (!CFENCE) asm volatile("fence.proxy.async.shared::cta;" ::: "memory");
        }
        if (warp >= 8) {
            STAMP(19);
            mbar_wait(mb + MB_KEY * 8);
            STAMP(20);
            const uint32_t mk = lds32(sb + SM_RK - 256 + (tid >> 2) * 4);
            uint32_t rank = rank4<4>(sb + SM_RK + cq * 64, mk);
            rank += __shfl_xor_sync(~0u, rank, 1); rank += __shfl_xor_sync(~0u, rank, 2);
            if (rank < 8) sts64(sb + SM_SEL + rank * 8, mk, ((tid >> 2) - 64) * 1440);
        }
    }
    bar_sync(11, 640);
    STAMP(12);

    {
        const char* gp = (const char*)g_s.cand + (go + lds32(sb + SM_SEL + 4 + (tk & 7) * 8));
        uint4 hv = ld_rlx128(gp);
        if (warp < 8) loadA();
        if (warp < 18) {
            int n = 0;
            while ((((hv.x ^ par) | (hv.y ^ par) | (hv.z ^ par) | (hv.w ^ par)) & 0x40004000u) && ++n < SPIN_LIMIT) hv = ld_rlx128(gp);
            sts128(sb + SM_XS + tk * 16 + tid * 16, hv.x ^ par, hv.y ^ par, hv.z ^ par, hv.w ^ par);
        }
    }
    bar_sync(14, 672);
    STAMP(13);
    {
        float c0[4] = {0.f, 0.f, 0.f, 0.f}, c1[4] = {0.f, 0.f, 0.f, 0.f}, c2[4] = {0.f, 0.f, 0.f, 0.f};
        const uint32_t ba = sb + SM_XS + mr * 1168 + mi * 16 + 288 * kq;
        uint32_t b[5][4];
#pragma unroll
        for (int s = 0; s < 5; s++) ldsm4(b[s], ba + s * 64);
        mma_bf16(c0, A[0][0], A[0][1], A[0][2], A[0][3], b[0][0], b[0][1]);
        mma_bf16(c1, A[1][0], A[1][1], A[1][2], A[1][3], b[0][2], b[0][3]);
        mma_bf16(c2, A[2][0], A[2][1], A[2][2], A[2][3], b[1][0], b[1][1]);
        mma_bf16(c0, A[3][0], A[3][1], A[3][2], A[3][3], b[1][2], b[1][3]);
        mma_bf16(c1, A[4][0], A[4][1], A[4][2], A[4][3], b[2][0], b[2][1]);
        mma_bf16(c2, A[5][0], A[5][1], A[5][2], A[5][3], b[2][2], b[2][3]);
        mma_bf16(c0, A[6][0], A[6][1], A[6][2], A[6][3], b[3][0], b[3][1]);
        mma_bf16(c1, A[7][0], A[7][1], A[7][2], A[7][3], b[3][2], b[3][3]);
        mma_bf16(c2, A[8][0], A[8][1], A[8][2], A[8][3], b[4][0], b[4][1]);
        sts128f(sb + SM_RED + tid * 16, c0[0] + c1[0] + c2[0], c0[1] + c1[1] + c2[1], c0[2] + c1[2] + c2[2], c0[3] + c1[3] + c2[3]);
    }
    bar_sync(1 + mt, 128);
    STAMP(21);
    if (mt < nslot) {
        const uint32_t ra = sb + SM_RED + mt * 512 + lane * 16;
        const float4 p0 = lds128f(ra), p1 = lds128f(ra + 2560), p2 = lds128f(ra + 5120), p3 = lds128f(ra + 7680);
        const float g0 = bfr(((p0.x + p1.x) + (p2.x + p3.x)) * 64.f), g1 = bfr(((p0.y + p1.y) + (p2.y + p3.y)) * 64.f);
        const uint32_t sg = pack_bf16(g0 * rcpf(1.f + ex2f(g0 * -1.4426950408889634f)), g1 * rcpf(1.f + ex2f(g1 * -1.4426950408889634f)));
        const uint32_t gu = bmul2(sg, pack_bf16(((p0.z + p1.z) + (p2.z + p3.z)) * 64.f, ((p0.w + p1.w) + (p2.w + p3.w)) * 64.f));
#pragma unroll
        for (int i = 0; i < 2; i++) {
            const uint32_t rb_ = mapa(sb, 2 * kq + i);
            st_async1(rb_ + (SM_GU + (q * nslot + mt) * 128) + lane * 4, gu, rb_ + (SM_MB + MB_GU * 8));
        }
    }
    mbar_wait(mb + MB_W2 * 8);
    {
        const uint32_t aa = sb + (8 * (mi >> 1) + mr) * 144 + (mi & 1) * 16 + (SM_FAR + 2304 * kq + mt * 32);
#pragma unroll
        for (int s = 0; s < 5; s++) ldsm4t(A[s], aa + s * FAR_SZ);
    }
    const bool red = warp < 6;
    const uint32_t ft = red ? (unsigned)tid / 24u : (unsigned)(tid >> 4) & 7u, fj = red ? 24 * q + tid - ft * 24 : d0 / 3 + (lane & 15);
    const uint32_t key = lds32(sb + SM_SEL + ft * 8), k16 = key << 5;
    float sig = bfr(rcpf(1.f + ex2f(__uint_as_float((k16 ^ (~((int)k16 >> 31) | 0x80000000u)) & 0xFFFF0000u) * -1.4426950408889634f)));
    uint32_t ra2 = sb + SM_RED2 + tid * 12 + ft * 16, fo = (ft * 192 + fj) * 16, oo = ((~key & 2047) * D_ + 3 * fj) * 2;
    PIN(ra2); PIN(fo); PIN(oo);
    {
        uint32_t ba = sb + (SM_GU + 256 * kq) + (lane & 15) * 16 + (lane >> 4) * 1024, wa = sb + (SM_RED2 + kq * 2432 + mt * 64) + g * 4 + cq * 608;
        PIN(ba); PIN(wa);
        STAMP(22);
        mbar_wait(mb + MB_GU * 8);
        STAMP(23);
        float c0[4] = {0.f, 0.f, 0.f, 0.f}, c1[4] = {0.f, 0.f, 0.f, 0.f}, c2[4] = {0.f, 0.f, 0.f, 0.f};
        uint32_t b[2][4], b8, b9;
        ldsm4t(b[0], ba); ldsm4t(b[1], ba + 2048); ldsm2t(b8, b9, ba + 4096);
        mma_bf16(c0, A[0][0], A[0][1], A[0][2], A[0][3], b[0][0], b[0][1]);
        mma_bf16(c1, A[1][0], A[1][1], A[1][2], A[1][3], b[0][2], b[0][3]);
        if (nslot == 5) {
            mma_bf16(c2, A[4][0], A[4][1], A[4][2], A[4][3], b8, b9);
            mma_bf16(c0, A[2][0], A[2][1], A[2][2], A[2][3], b[1][0], b[1][1]);
            mma_bf16(c1, A[3][0], A[3][1], A[3][2], A[3][3], b[1][2], b[1][3]);
        }
        stsf(wa, c0[0] + c1[0] + c2[0]); stsf(wa + 304, c0[1] + c1[1] + c2[1]);
        if (mt < 4) { stsf(wa + 32, c0[2] + c1[2] + c2[2]); stsf(wa + 336, c0[3] + c1[3] + c2[3]); }
    }
    if (warp < 10) {
        float v[3], cnt = 3.f;
        if (red) {
            bar_sync(6, 640);
            STAMP(14);
#pragma unroll
            for (int i = 0; i < 3; i++) v[i] = ((ldsf(ra2 + i * 4) + ldsf(ra2 + i * 4 + 2432)) + (ldsf(ra2 + i * 4 + 4864) + ldsf(ra2 + i * 4 + 7296))) * sig;
        } else {
            bar_arrive(6, 640);
            cnt = 0.f;
#pragma unroll
            for (int i = 0; i < 3; i++) {
                const uint32_t cl = 3 * fj + i - d0;
                const bool ok = cl < 8 * nslot && ((~key >> 3) & 7) == q;
                v[i] = ok ? __uint_as_float(lds16(sb + SM_XT + tslot(~key) * 80 + (cl & 63) * 2) << 16) : 0.f;
                if (ok) cnt += 1.f;
            }
            mbar_wait(mb + MB_OUT * 8);
        }
        if (cnt != 0.f) {
            float x, y, z, w;
            asm volatile("atom.relaxed.gpu.global.add.v4.f32 {%0,%1,%2,%3}, [%4], {%5,%6,%7,%8};" : "=f"(x), "=f"(y), "=f"(z), "=f"(w)
                         : "l"((char*)g_s.fin + fo), "f"(v[0]), "f"(v[1]), "f"(v[2]), "f"(cnt) : "memory");
            if (w + cnt == 3.f * (NCL + 1)) {
                __nv_bfloat16* op = (__nv_bfloat16*)((char*)prm.out + oo);
                op[0] = __float2bfloat16(x + v[0]); op[1] = __float2bfloat16(y + v[1]); op[2] = __float2bfloat16(z + v[2]);
            }
        }
    } else bar_arrive(6, 640);
    STAMP(15);
}

typedef CUresult (*EncodeFn)(CUtensorMap*, CUtensorMapDataType, cuuint32_t, void*, const cuuint64_t*, const cuuint64_t*,
                             const cuuint32_t*, const cuuint32_t*, CUtensorMapInterleave, CUtensorMapSwizzle,
                             CUtensorMapL2promotion, CUtensorMapFloatOOBfill);

void make_map(EncodeFn fn, CUtensorMap* tm, const void* p, int cols, int rows, int bc, int br) {
    cuuint64_t dims[2] = {(cuuint64_t)cols, (cuuint64_t)rows};
    cuuint64_t strides[1] = {(cuuint64_t)cols * 2};
    cuuint32_t box[2] = {(cuuint32_t)bc, (cuuint32_t)br};
    cuuint32_t es[2] = {1, 1};
    fn(tm, CU_TENSOR_MAP_DATA_TYPE_BFLOAT16, 2, const_cast<void*>(p), dims, strides, box, es, CU_TENSOR_MAP_INTERLEAVE_NONE,
       CU_TENSOR_MAP_SWIZZLE_NONE, (CUtensorMapL2promotion)L2PROMO, CU_TENSOR_MAP_FLOAT_OOB_FILL_NONE);
}

void make_map3(EncodeFn fn, CUtensorMap* tm, const void* p) {
    cuuint64_t dims[3] = {(cuuint64_t)D_, 64, 32};
    cuuint64_t strides[2] = {(cuuint64_t)D_ * 2, (cuuint64_t)D_ * 128};
    cuuint32_t box[3] = {40, 8, 32};
    cuuint32_t es[3] = {1, 1, 1};
    fn(tm, CU_TENSOR_MAP_DATA_TYPE_BFLOAT16, 3, const_cast<void*>(p), dims, strides, box, es, CU_TENSOR_MAP_INTERLEAVE_NONE,
       CU_TENSOR_MAP_SWIZZLE_NONE, CU_TENSOR_MAP_L2_PROMOTION_NONE, CU_TENSOR_MAP_FLOAT_OOB_FILL_NONE);
}

void make_map5(EncodeFn fn, CUtensorMap* tm, const void* p) {
    cuuint64_t dims[5] = {(cuuint64_t)D_, 2, 4, 4, 64};
    cuuint64_t strides[4] = {(cuuint64_t)D_ * 128, (cuuint64_t)D_ * 1024, (cuuint64_t)D_ * 256, (cuuint64_t)D_ * 2};
    cuuint32_t box[5] = {40, 2, 4, 4, 8};
    cuuint32_t es[5] = {1, 1, 1, 1, 1};
    fn(tm, CU_TENSOR_MAP_DATA_TYPE_BFLOAT16, 5, const_cast<void*>(p), dims, strides, box, es, CU_TENSOR_MAP_INTERLEAVE_NONE,
       CU_TENSOR_MAP_SWIZZLE_NONE, CU_TENSOR_MAP_L2_PROMOTION_NONE, CU_TENSOR_MAP_FLOAT_OOB_FILL_NONE);
}

}

extern "C" void kernel_launch(void* const* d_in, const int* in_sizes, int n_in, void* d_out, int out_size) {
    (void)in_sizes; (void)n_in; (void)out_size;
    void* fp = nullptr;
    cudaDriverEntryPointQueryResult qr;
    cudaGetDriverEntryPoint("cuTensorMapEncodeTiled", &fp, cudaEnableDefault, &qr);
    EncodeFn fn = (EncodeFn)fp;
    CUtensorMap tmG, tmU, tmD, tmO, tmX;
    make_map3(fn, &tmX, d_in[0]);
    make_map(fn, &tmG, d_in[11], F_, D_, 40, 48);
    make_map(fn, &tmU, d_in[12], F_, D_, 40, 48);
    make_map(fn, &tmD, d_in[13], D_, F_, 72, 64);
    make_map5(fn, &tmO, d_out);
    Params p;
    p.x = (const unsigned short*)d_in[0];
    for (int i = 0; i < 6; i++) p.prm6[i] = (const unsigned short*)d_in[1 + i];
    p.logdt = (const unsigned short*)d_in[7]; p.dskip = (const unsigned short*)d_in[8];
    p.wr = (const unsigned short*)d_in[10];
    for (int i = 0; i < 3; i++) p.w3[i] = (const char*)d_in[11 + i];
    p.out = (__nv_bfloat16*)d_out;
    p.zero = 0;
    cudaGetSymbolAddress((void**)&p.gs, g_s);
    cudaFuncSetAttribute(fused_kernel, cudaFuncAttributeMaxDynamicSharedMemorySize, SM_TOTAL);
    fused_kernel<<<NCTA, NTHR, SM_TOTAL>>>(p, tmG, tmU, tmD, tmO, tmX);
}
```

```cpp
#include <cuda_runtime.h>
#include <cuda_bf16.h>
#include <cuda_fp16.h>
#include <cuda.h>
#include <stdint.h>

namespace {

constexpr int L_ = 2048, D_ = 576, F_ = 4608;
constexpr int NCL = 15, CS = 8, NCTA = NCL * CS, NTHR = 768;
#define PACE_NS 100
#define PRE_N 0
#define PRE_NS 200
#define FIN_DELAY 0
#define RED_DELAY 0
#define NO_OUT 0
#define XSPLIT 3
#define LNPOS 2
#define NMPOS 3
#define XWAIT -1
#define XWB 1
#define XROT 0
#define NBOX 24
#define NRED 2
#define HALF_AT 1
#define OUT_NS 0
#define PFMAP 2
#define CFENCE 1
#define NEAR_DB 1
#define STREAM_T 0
#define L2PROMO 2
#define GAP_NS 0
#define ROW_DELAY 1
constexpr int SPIN_LIMIT = 1 << 22;

constexpr int SM_WG   = 0;
constexpr int SM_WU   = 46080;
constexpr int YP = 3376, YS = 672;
constexpr int UP = 3376, US = 672;
constexpr int SM_XT   = 92160;
constexpr int SM_U    = SM_XT + 8 * YP;
constexpr int SM_FAR  = SM_U + 8 * UP;
constexpr int FAR_SZ  = 12416;
constexpr int F_E5 = 0, F_O5 = 1536, F_E3 = 3088, F_O3 = 4624, F_E7 = 6176, F_E2 = F_E7 + 1024, F_E9 = F_E7 + 2048,
              F_H = 3088, F_O7 = F_E7 + F_H, F_O2 = F_E2 + F_H, F_O9 = F_E9 + F_H;
constexpr int SM_P    = SM_FAR + 5 * FAR_SZ;
constexpr int PN_SZ = 584 * 4, SM_PN = SM_P + 64 * 4;
constexpr int P_GS = 48 * 4, P_H7 = 192 * 4, P_HS = 72 * 4;
constexpr int PF_SZ = (192 + 216) * 4, SM_PF = SM_PN + 5 * PN_SZ + 32;
constexpr int SM_MISC = SM_PF + 5 * PF_SZ;
constexpr int SM_ST   = SM_MISC;
constexpr int SM_RK   = SM_ST + 2048;
constexpr int SM_SEL  = SM_RK + 256;
constexpr int SM_KG   = SM_SEL + 64;
constexpr int SM_SC   = SM_KG + 160;
constexpr int SM_DW   = SM_SC + 32;
constexpr int SM_MB   = SM_DW + 160;
constexpr int SM_TOTAL = SM_MB + 128;
constexpr int SM_ROW  = SM_XT - 20736;
constexpr int SM_XTL  = SM_ROW - 20480;
constexpr int SM_RED2 = SM_WG;
constexpr int SM_HT   = SM_P - 512;
constexpr int SM_KEY  = SM_FAR + 9216 + 128;
constexpr int SM_CAND = SM_KEY + 1024;
constexpr int SM_FIN  = SM_FAR + FAR_SZ + 9216 + 128;
constexpr int SM_HS   = SM_FIN + 2400;
constexpr int SM_XS   = SM_U;
constexpr int SM_GU   = SM_XS + 9344;
constexpr int SM_RED  = SM_GU + 5632;
static_assert(F_O9 + 1024 <= FAR_SZ && FAR_SZ % 128 == 0, "far overflow");
static_assert(SM_RED + 10240 <= SM_FAR && SM_HS + 128 <= SM_FAR + 2 * FAR_SZ && SM_HT + 20496 <= SM_MISC, "alias overflow");
static_assert(SM_TOTAL <= 232448, "smem overflow");
static_assert(SM_FAR % 128 == 0 && SM_XT % 128 == 0 && SM_XTL % 128 == 0 && SM_P % 16 == 0 && SM_MISC % 16 == 0 && SM_MB % 8 == 0 && SM_HS % 16 == 0, "align");

enum { MB_X = 0, MB_W1 = 5, MB_W2 = 6, MB_KEY = 7, MB_GU = 8, MB_Y = 9, MB_OUT = 10, MB_T = 11, MB_R = 12 };

struct __align__(128) Scratch {
    unsigned epoch, zcnt, pad[30];
    uint4  st1[L_ * 2];
    float4 acc[L_];
    uint4  cand[64 * NCL * 6];
    float4 fin[8 * 192 + 24];
};
__device__ Scratch g_s;
#define STAMP(i)

__device__ __forceinline__ uint32_t mapa(uint32_t a, uint32_t r) { uint32_t d; asm("mapa.shared::cluster.u32 %0, %1, %2;" : "=r"(d) : "r"(a), "r"(r)); return d; }
__device__ __forceinline__ void mbar_wait(uint32_t mb) {
    asm volatile("{ .reg .pred p, q; .reg .u32 n; mov.u32 n, 0;\n"
                 "W_%=: mbarrier.try_wait.parity.shared::cta.b64 p, [%0], 0; add.u32 n, n, 1; setp.lt.and.u32 q, n, 65536, !p; @q bra W_%=; }" :: "r"(mb) : "memory");
}
__device__ __forceinline__ void arm(uint32_t mb, uint32_t bytes) { asm volatile("mbarrier.arrive.expect_tx.shared::cta.b64 _, [%0], %1;" :: "r"(mb), "r"(bytes) : "memory"); }
__device__ __forceinline__ void bar_sync(int id, int n) { asm volatile("bar.sync %0, %1;" :: "r"(id), "r"(n) : "memory"); }
__device__ __forceinline__ void bar_arrive(int id, int n) { asm volatile("bar.arrive %0, %1;" :: "r"(id), "r"(n) : "memory"); }
__device__ __forceinline__ uint32_t lds16(uint32_t a) { unsigned short v; asm volatile("ld.shared.u16 %0, [%1];" : "=h"(v) : "r"(a) : "memory"); return v; }
__device__ __forceinline__ uint32_t lds32(uint32_t a) { uint32_t v; asm volatile("ld.shared.u32 %0, [%1];" : "=r"(v) : "r"(a) : "memory"); return v; }
__device__ __forceinline__ uint2 lds64(uint32_t a) { uint2 v; asm volatile("ld.shared.v2.u32 {%0,%1}, [%2];" : "=r"(v.x), "=r"(v.y) : "r"(a) : "memory"); return v; }
__device__ __forceinline__ float ldsf(uint32_t a) { float v; asm volatile("ld.shared.f32 %0, [%1];" : "=f"(v) : "r"(a) : "memory"); return v; }
__device__ __forceinline__ uint4 lds128(uint32_t a) { uint4 v; asm volatile("ld.shared.v4.u32 {%0,%1,%2,%3}, [%4];" : "=r"(v.x), "=r"(v.y), "=r"(v.z), "=r"(v.w) : "r"(a) : "memory"); return v; }
__device__ __forceinline__ float4 lds128f(uint32_t a) { float4 v; asm volatile("ld.shared.v4.f32 {%0,%1,%2,%3}, [%4];" : "=f"(v.x), "=f"(v.y), "=f"(v.z), "=f"(v.w) : "r"(a) : "memory"); return v; }
__device__ __forceinline__ void sts16(uint32_t a, uint32_t v) { asm volatile("{ .reg .b16 l, h; mov.b32 {l, h}, %1; st.shared.b16 [%0], l; }" :: "r"(a), "r"(v) : "memory"); }
__device__ __forceinline__ void sts32(uint32_t a, uint32_t v) { asm volatile("st.shared.u32 [%0], %1;" :: "r"(a), "r"(v) : "memory"); }
__device__ __forceinline__ void sts64(uint32_t a, uint32_t x, uint32_t y) { asm volatile("st.shared.v2.u32 [%0], {%1,%2};" :: "r"(a), "r"(x), "r"(y) : "memory"); }
__device__ __forceinline__ void stsf(uint32_t a, float v) { asm volatile("st.shared.f32 [%0], %1;" :: "r"(a), "f"(v) : "memory"); }
__device__ __forceinline__ void sts128(uint32_t a, uint32_t x, uint32_t y, uint32_t z, uint32_t w) { asm volatile("st.shared.v4.u32 [%0], {%1,%2,%3,%4};" :: "r"(a), "r"(x), "r"(y), "r"(z), "r"(w) : "memory"); }
__device__ __forceinline__ void sts128f(uint32_t a, float x, float y, float z, float w) { asm volatile("st.shared.v4.f32 [%0], {%1,%2,%3,%4};" :: "r"(a), "f"(x), "f"(y), "f"(z), "f"(w) : "memory"); }
__device__ __forceinline__ void ldsm4(uint32_t (&r)[4], uint32_t a) { asm volatile("ldmatrix.sync.aligned.m8n8.x4.shared.b16 {%0,%1,%2,%3}, [%4];" : "=r"(r[0]), "=r"(r[1]), "=r"(r[2]), "=r"(r[3]) : "r"(a) : "memory"); }
__device__ __forceinline__ void ldsm4t(uint32_t (&r)[4], uint32_t a) { asm volatile("ldmatrix.sync.aligned.m8n8.x4.trans.shared.b16 {%0,%1,%2,%3}, [%4];" : "=r"(r[0]), "=r"(r[1]), "=r"(r[2]), "=r"(r[3]) : "r"(a) : "memory"); }
__device__ __forceinline__ void ldsm2t(uint32_t& r0, uint32_t& r1, uint32_t a) { asm volatile("ldmatrix.sync.aligned.m8n8.x2.trans.shared.b16 {%0,%1}, [%2];" : "=r"(r0), "=r"(r1) : "r"(a) : "memory"); }
__device__ __forceinline__ void stsm4t(uint32_t a, uint32_t r0, uint32_t r1, uint32_t r2, uint32_t r3) { asm volatile("stmatrix.sync.aligned.m8n8.x4.trans.shared.b16 [%0], {%1,%2,%3,%4};" :: "r"(a), "r"(r0), "r"(r1), "r"(r2), "r"(r3) : "memory"); }
__device__ __forceinline__ void stsm4(uint32_t a, uint32_t r0, uint32_t r1, uint32_t r2, uint32_t r3) { asm volatile("stmatrix.sync.aligned.m8n8.x4.shared.b16 [%0], {%1,%2,%3,%4};" :: "r"(a), "r"(r0), "r"(r1), "r"(r2), "r"(r3) : "memory"); }
__device__ __forceinline__ void stsm2t(uint32_t a, uint32_t r0, uint32_t r1) { asm volatile("stmatrix.sync.aligned.m8n8.x2.trans.shared.b16 [%0], {%1,%2};" :: "r"(a), "r"(r0), "r"(r1) : "memory"); }
__device__ __forceinline__ uint4 ldg128(const void* p) { uint4 v; asm volatile("ld.global.nc.v4.u32 {%0,%1,%2,%3}, [%4];" : "=r"(v.x), "=r"(v.y), "=r"(v.z), "=r"(v.w) : "l"(p)); return v; }
__device__ __forceinline__ uint32_t ldg32(const void* p) { uint32_t v; asm volatile("ld.global.nc.u32 %0, [%1];" : "=r"(v) : "l"(p)); return v; }
__device__ __forceinline__ uint32_t ldg16(const void* p) { unsigned short v; asm volatile("ld.global.nc.u16 %0, [%1];" : "=h"(v) : "l"(p)); return v; }
__device__ __forceinline__ uint32_t opaque(uint32_t v) { uint32_t r; asm volatile("mov.b32 %0, %1;" : "=r"(r) : "r"(v)); return r; }
__device__ __forceinline__ void mma_f16(float (&d)[4], const uint32_t (&a)[4], uint32_t b0, uint32_t b1) {
    asm volatile("mma.sync.aligned.m16n8k16.row.col.f32.f16.f16.f32 {%0,%1,%2,%3}, {%4,%5,%6,%7}, {%8,%9}, {%0,%1,%2,%3};"
        : "+f"(d[0]), "+f"(d[1]), "+f"(d[2]), "+f"(d[3]) : "r"(a[0]), "r"(a[1]), "r"(a[2]), "r"(a[3]), "r"(b0), "r"(b1));
}
__device__ __forceinline__ void mma_bf16(float (&d)[4], uint32_t a0, uint32_t a1, uint32_t a2, uint32_t a3, uint32_t b0, uint32_t b1) {
    asm volatile("mma.sync.aligned.m16n8k16.row.col.f32.bf16.bf16.f32 {%0,%1,%2,%3}, {%4,%5,%6,%7}, {%8,%9}, {%0,%1,%2,%3};"
        : "+f"(d[0]), "+f"(d[1]), "+f"(d[2]), "+f"(d[3]) : "r"(a0), "r"(a1), "r"(a2), "r"(a3), "r"(b0), "r"(b1));
}
__device__ __forceinline__ void mma_bf16_k8(float (&d)[4], uint32_t a0, uint32_t a1, uint32_t b0) {
    asm volatile("mma.sync.aligned.m16n8k8.row.col.f32.bf16.bf16.f32 {%0,%1,%2,%3}, {%4,%5}, {%6}, {%0,%1,%2,%3};"
        : "+f"(d[0]), "+f"(d[1]), "+f"(d[2]), "+f"(d[3]) : "r"(a0), "r"(a1), "r"(b0));
}
__device__ __forceinline__ uint32_t pack_f16(float lo, float hi) { uint32_t r; asm("cvt.rn.f16x2.f32 %0, %1, %2;" : "=r"(r) : "f"(hi), "f"(lo)); return r; }
__device__ __forceinline__ uint32_t pack_bf16(float lo, float hi) { uint32_t r; asm("cvt.rn.bf16x2.f32 %0, %1, %2;" : "=r"(r) : "f"(hi), "f"(lo)); return r; }
__device__ __forceinline__ float bf_lo(uint32_t v) { return __uint_as_float(v << 16); }
__device__ __forceinline__ float bf_hi(uint32_t v) { return __uint_as_float(v & 0xFFFF0000u); }
__device__ __forceinline__ float bfr(float x) { return __uint_as_float(pack_bf16(0.f, x)); }
__device__ __forceinline__ uint32_t bsub2(uint32_t a, uint32_t b) { uint32_t r; asm("sub.rn.bf16x2 %0, %1, %2;" : "=r"(r) : "r"(a), "r"(b)); return r; }
__device__ __forceinline__ uint32_t badd2(uint32_t a, uint32_t b) { uint32_t r; asm("add.rn.bf16x2 %0, %1, %2;" : "=r"(r) : "r"(a), "r"(b)); return r; }
__device__ __forceinline__ uint32_t bmul2(uint32_t a, uint32_t b) { uint32_t r; asm("mul.rn.bf16x2 %0, %1, %2;" : "=r"(r) : "r"(a), "r"(b)); return r; }
__device__ __forceinline__ uint32_t bfma2(uint32_t a, uint32_t b, uint32_t c) { uint32_t r; asm("fma.rn.bf16x2 %0, %1, %2, %3;" : "=r"(r) : "r"(a), "r"(b), "r"(c)); return r; }
__device__ __forceinline__ uint32_t hadd2(uint32_t a, uint32_t b) { uint32_t r; asm("add.rn.f16x2 %0, %1, %2;" : "=r"(r) : "r"(a), "r"(b)); return r; }
__device__ __forceinline__ uint32_t hmul2(uint32_t a, uint32_t b) { uint32_t r; asm("mul.rn.f16x2 %0, %1, %2;" : "=r"(r) : "r"(a), "r"(b)); return r; }
__device__ __forceinline__ uint32_t hfma2(uint32_t a, uint32_t b, uint32_t c) { uint32_t r; asm("fma.rn.f16x2 %0, %1, %2, %3;" : "=r"(r) : "r"(a), "r"(b), "r"(c)); return r; }
__device__ __forceinline__ uint32_t hneg2(uint32_t a) { uint32_t r; asm("neg.f16x2 %0, %1;" : "=r"(r) : "r"(a)); return r; }
__device__ __forceinline__ float rcpf(float x) { float r; asm("rcp.approx.ftz.f32 %0, %1;" : "=f"(r) : "f"(x)); return r; }
__device__ __forceinline__ float sqrta(float x) { float r; asm("sqrt.approx.ftz.f32 %0, %1;" : "=f"(r) : "f"(x)); return r; }
__device__ __forceinline__ float ex2f(float x) { float r; asm("ex2.approx.ftz.f32 %0, %1;" : "=f"(r) : "f"(x)); return r; }
__device__ __forceinline__ void st_async4(uint32_t a, uint32_t x, uint32_t y, uint32_t z, uint32_t w, uint32_t mb) {
    asm volatile("st.async.shared::cluster.mbarrier::complete_tx::bytes.v4.u32 [%0], {%1,%2,%3,%4}, [%5];" :: "r"(a), "r"(x), "r"(y), "r"(z), "r"(w), "r"(mb) : "memory"); }
__device__ __forceinline__ void st_async1(uint32_t a, uint32_t x, uint32_t mb) {
    asm volatile("st.async.shared::cluster.mbarrier::complete_tx::bytes.u32 [%0], %1, [%2];" :: "r"(a), "r"(x), "r"(mb) : "memory"); }
__device__ __forceinline__ unsigned ld_rlx(const void* p) { unsigned v; asm volatile("ld.relaxed.gpu.global.u32 %0, [%1];" : "=r"(v) : "l"(p) : "memory"); return v; }
__device__ __forceinline__ unsigned ld_acq(const void* p) { unsigned v; asm volatile("ld.acquire.gpu.global.u32 %0, [%1];" : "=r"(v) : "l"(p) : "memory"); return v; }
__device__ __forceinline__ uint2 ld_rlx64(const void* p) { unsigned long long v; asm volatile("ld.relaxed.gpu.global.u64 %0, [%1];" : "=l"(v) : "l"(p) : "memory"); return make_uint2((unsigned)v, (unsigned)(v >> 32)); }
__device__ __forceinline__ void st_rlx64(void* p, unsigned lo, unsigned hi) { asm volatile("st.relaxed.gpu.global.u64 [%0], %1;" :: "l"(p), "l"((unsigned long long)lo | ((unsigned long long)hi << 32)) : "memory"); }
__device__ __forceinline__ void st_rlx128(void* p, uint32_t x, uint32_t y, uint32_t z, uint32_t w) {
    asm volatile("st.relaxed.gpu.global.v2.u64 [%0], {%1,%2};" :: "l"(p), "l"((unsigned long long)x | ((unsigned long long)y << 32)), "l"((unsigned long long)z | ((unsigned long long)w << 32)) : "memory"); }
__device__ __forceinline__ uint4 ld_rlx128(const void* p) { unsigned long long a, b; asm volatile("ld.relaxed.gpu.global.v2.u64 {%0,%1}, [%2];" : "=l"(a), "=l"(b) : "l"(p) : "memory"); return make_uint4((unsigned)a, (unsigned)(a >> 32), (unsigned)b, (unsigned)(b >> 32)); }
__device__ __forceinline__ void tma2d(uint32_t dst, const CUtensorMap* tm, int x, int y, uint32_t mb) {
    asm volatile("cp.async.bulk.tensor.2d.shared::cluster.global.mbarrier::complete_tx::bytes [%0], [%1, {%3, %4}], [%2];"
                 :: "r"(dst), "l"(tm), "r"(mb), "r"(x), "r"(y) : "memory");
}
__device__ __forceinline__ void cmul(float& xr, float& xi, float ar, float ai, float br, float bi) {
    const float r = fmaf(ar, br, -ai * bi), i = fmaf(ar, bi, ai * br); xr = r; xi = i;
}
__device__ __forceinline__ void csq(float& xr, float& xi, float ar, float ai) {
    const float r = fmaf(ar, ar, -ai * ai), i = (ar + ar) * ai; xr = r; xi = i;
}
__device__ __forceinline__ void cexp_s(float& zr, float& zi, float e2, float turns) {
    const float mag = ex2f(e2), r = (turns - rintf(turns)) * 6.283185307179586f;
    zr = mag * __cosf(r); zi = mag * __sinf(r);
}
__device__ __forceinline__ uint32_t ln_stats(float s1, float s2) {
    const float m = s1 * (1.f / D_);
    const float var = fmaxf(fmaf(s2, 1.f / D_, -m * m), 0.f);
    return pack_bf16(m, sqrta(bfr(bfr(var) + 1e-5f)));
}
__device__ __forceinline__ uint32_t rsplit(float rs) { const float h = bfr(rs); return pack_bf16(h, rs - h); }
__device__ __forceinline__ uint32_t norm2(uint32_t v, uint32_t m2, uint32_t rh2, uint32_t rl2) {
    const uint32_t dd = bsub2(v, m2);
    return bfma2(dd, rh2, bmul2(dd, rl2));
}
template <int N>
__device__ __forceinline__ uint32_t rank4(uint32_t a, uint32_t key) {
    uint32_t r0 = 0, r1 = 0, r2 = 0, r3 = 0;
#pragma unroll
    for (int i = 0; i < N; i++) {
        const uint4 o = lds128(a + i * 16);
        r0 += (key - o.x) >> 31; r1 += (key - o.y) >> 31; r2 += (key - o.z) >> 31; r3 += (key - o.w) >> 31;
    }
    return (r0 + r1) + (r2 + r3);
}
struct H2C { uint32_t r, i; };
__device__ __forceinline__ H2C splat(float r, float i) { H2C h; h.r = pack_f16(r, r); h.i = pack_f16(i, i); return h; }
__device__ __forceinline__ void expand4(uint32_t are, uint32_t aim, uint32_t R0, uint32_t R1, uint32_t I0, uint32_t I1, H2C m4) {
    sts128(are, R0, R1, hfma2(R0, m4.r, hneg2(hmul2(I0, m4.i))), hfma2(R1, m4.r, hneg2(hmul2(I1, m4.i))));
    sts128(aim, I0, I1, hfma2(R0, m4.i, hmul2(I0, m4.r)), hfma2(R1, m4.i, hmul2(I1, m4.r)));
}
__device__ __forceinline__ void expand8(uint32_t are, uint32_t aim, float sr, float si, float m1r, float m1i, float m2r, float m2i, H2C m4) {
    float r1, i1, r2, i2, r3, i3;
    cmul(r1, i1, sr, si, m1r, m1i); cmul(r2, i2, sr, si, m2r, m2i); cmul(r3, i3, r1, i1, m2r, m2i);
    expand4(are, aim, pack_f16(sr, r1), pack_f16(r2, r3), pack_f16(si, i1), pack_f16(i2, i3), m4);
}
__device__ __forceinline__ void put16(uint32_t a, uint32_t v) { sts16(a, v); sts16(a + 6, v); }

struct Params {
    const unsigned short *x, *prm6[6], *logdt, *dskip, *wr;
    const char* w3[3];
    __nv_bfloat16* out;
    Scratch* gs;
    unsigned zero;
};
__device__ __forceinline__ uint32_t tslot(uint32_t t) { return (t & 7) * 32 + ((t >> 4) & 24) + ((t >> 8) & 6) + ((t >> 6) & 1); }
#define CP(x) ((x) | zero)
#define PIN(x) asm volatile("or.b32 %0, %0, %1;" : "+r"(x) : "r"(zero))
__device__ __forceinline__ void wgmma32(float (&d)[4][4], const uint32_t (&a)[4], uint32_t dlo) {
    asm volatile("{ .reg .b64 ds; mov.b64 ds, {%20, %21};\n"
                 "wgmma.mma_async.sync.aligned.m64n32k16.f32.f16.f16 {%0,%1,%2,%3,%4,%5,%6,%7,%8,%9,%10,%11,%12,%13,%14,%15}, {%16,%17,%18,%19}, ds, 1, 1, 1, 0; }"
        : "+f"(d[0][0]), "+f"(d[0][1]), "+f"(d[0][2]), "+f"(d[0][3]), "+f"(d[1][0]), "+f"(d[1][1]), "+f"(d[1][2]), "+f"(d[1][3]),
          "+f"(d[2][0]), "+f"(d[2][1]), "+f"(d[2][2]), "+f"(d[2][3]), "+f"(d[3][0]), "+f"(d[3][1]), "+f"(d[3][2]), "+f"(d[3][3])
        : "r"(a[0]), "r"(a[1]), "r"(a[2]), "r"(a[3]), "r"(dlo), "n"(128 >> 4));
}

__global__ void __cluster_dims__(CS, 1, 1) __launch_bounds__(NTHR, 1)
fused_kernel(const __grid_constant__ Params prm, const __grid_constant__ CUtensorMap tmG, const __grid_constant__ CUtensorMap tmU,
             const __grid_constant__ CUtensorMap tmD, const __grid_constant__ CUtensorMap tmO, const __grid_constant__ CUtensorMap tmX, const __grid_constant__ CUtensorMap tmH)
{
    extern __shared__ __align__(1024) unsigned char smem[];
    const int tid = threadIdx.x, lane = tid & 31, warp = __shfl_sync(~0u, tid >> 5, 0);
    const int c = blockIdx.x >> 3, q = blockIdx.x & 7;
    const int nslot = (c < NCL - 1) ? 5 : 2;
    const int d0 = 40 * c;
    const uint32_t sb = opaque((uint32_t)__cvta_generic_to_shared(smem));
    const uint32_t mb = sb + SM_MB;
    Scratch& g_s = *prm.gs;
    const unsigned& zero = prm.zero;
    STAMP(0);

    if (warp >= 20) {
        unsigned epoch = 0;
        if (warp == 20) {
            if (lane == 0) {
#pragma unroll
                for (int i = 0; i < 13; i++)
                    asm volatile("mbarrier.init.shared::cta.b64 [%0], %1;" :: "r"(mb + i * 8), "r"((i == MB_R || i == MB_T) ? 2 : i == MB_Y ? 1 + 4 * nslot : 1) : "memory");
                asm volatile("fence.mbarrier_init.release.cluster;" ::: "memory");
                arm(mb + MB_W1 * 8, NBOX * 3840); arm(mb + MB_W2 * 8, nslot * 9216); arm(mb + MB_KEY * 8, 256); arm(mb + MB_GU * 8, nslot * 1024); arm(mb + MB_T * 8, 20480);
                const int bytes = max(min(18, L_ - 18 * (int)blockIdx.x), 1) * (D_ * 2);
                arm(mb + MB_R * 8, bytes);
                if (!ROW_DELAY) asm volatile("cp.async.bulk.shared::cluster.global.mbarrier::complete_tx::bytes [%0], [%1], %2, [%3];"
                             :: "r"(sb + SM_ROW), "l"(prm.x + min(18 * (int)blockIdx.x, L_ - 1) * D_), "r"(bytes), "r"(mb + MB_R * 8) : "memory");
            }
            __syncwarp();
        } else if (warp == 22) {
            epoch = ld_rlx(&g_s.epoch);
            if (lane < 18 ? 18 * c + lane < 256 : lane < 31) (lane < 18 ? &g_s.acc[256 * q + 18 * c] : &g_s.fin[13 * (int)blockIdx.x - 18])[lane] = make_float4(0.f, 0.f, 0.f, 0.f);
        } else if (warp == 23 && lane == 0) asm volatile("prefetch.tensormap [%0];" :: "l"(&tmX) : "memory");
        asm volatile("barrier.cluster.arrive.relaxed.aligned;" ::: "memory");
        bar_sync(12, NTHR);
        if (warp == 22) {
            if (lane == 0) { sts32(sb + SM_SC + 28, epoch); asm volatile("mbarrier.arrive.shared::cta.b64 _, [%0];" :: "r"(mb + MB_R * 8) : "memory"); }
            epoch++;
            asm volatile("fence.acq_rel.gpu;" ::: "memory");
            __syncwarp();
            if (lane == 0) asm volatile("red.relaxed.gpu.global.add.u32 [%0], 1;" :: "l"(&g_s.zcnt) : "memory");
            STAMP(1);
            uint4 wv = make_uint4(0, 0, 0, 0), wv2 = ldg128((const uint4*)prm.wr + lane), wv3 = ldg128((const uint4*)prm.wr + 32 + lane);
            if (lane < 8) wv = ldg128((const uint4*)prm.wr + 64 + lane);
            if (lane < 5) {
                uint4 v = make_uint4(0, 0, 0, 0);
                if (lane < nslot) v = ldg128((const uint4*)(prm.wr + d0) + lane);
                sts128(sb + SM_DW + lane * 16, v.x, v.y, v.z, v.w);
            }
            __syncwarp();
            if (lane == 0) asm volatile("mbarrier.arrive.shared::cta.b64 _, [%0];" :: "r"(mb + MB_T * 8) : "memory");
            mbar_wait(mb + (MB_X + 1) * 8);
            const uint32_t old = (epoch & 1) ? 0u : 0x40004000u;
#pragma unroll
            for (int t = 0; t < 2; t++)
                if ((lane & 7) < 6) g_s.cand[((q * 8 + 4 * t + (lane >> 3)) * NCL + c) * 6 + (lane & 7)] = make_uint4(old, old, old, old);
            float a[4] = {0.f, 0.f, 0.f, 0.f};
            const uint32_t one = 0x3F803F80u;
            mma_bf16(a, one, one, one, one, wv.x, wv.y);  mma_bf16(a, one, one, one, one, wv.z, wv.w);
            mma_bf16(a, one, one, one, one, wv2.x, wv2.y); mma_bf16(a, one, one, one, one, wv2.z, wv2.w);
            mma_bf16(a, one, one, one, one, wv3.x, wv3.y); mma_bf16(a, one, one, one, one, wv3.z, wv3.w);
            float s = a[0] + a[1];
            s += __shfl_xor_sync(~0u, s, 1); s += __shfl_xor_sync(~0u, s, 2);
            stsf(sb + SM_SC + 24, s);
            __syncwarp();
            if (lane == 0) {
                int n = 0;
                while ((int)(ld_acq(&g_s.zcnt) - epoch * NCTA) < 0 && ++n < SPIN_LIMIT) __nanosleep(200);
                arm(mb + MB_Y * 8, 8 * 512 * nslot);
                if (blockIdx.x == 0) g_s.epoch = epoch;
            }
            STAMP(2);
            return;
        }
        if (warp == 21) {
            if (PFMAP > 1 && lane == 0) { asm volatile("prefetch.tensormap [%0];" :: "l"(&tmG) : "memory"); asm volatile("prefetch.tensormap [%0];" :: "l"(&tmU) : "memory"); asm volatile("prefetch.tensormap [%0];" :: "l"(&tmD) : "memory"); }
            __syncwarp();
            if (STREAM_T) { bar_arrive(13, 736); mbar_wait(mb + MB_T * 8); } else bar_sync(13, 736);
            if (GAP_NS) __nanosleep(GAP_NS);
#pragma unroll 1
            for (int i = 24 - NBOX; i < 24; i++) {
                if (i == XWAIT) mbar_wait(mb + (MB_X + XWB) * 8);
                if (i == 13) { bar_sync(15, 544); asm volatile("fence.proxy.async.shared::cta;" ::: "memory"); }
                if (lane == 0) tma2d(sb + SM_WG + i * 3840, i < 12 ? &tmG : &tmU, 320 * c + 8 * nslot * q, 48 * (i < 12 ? i : i - 12), mb + MB_W1 * 8);
                __nanosleep(PACE_NS);
            }
            STAMP(1);
            return;
        }
        if (warp == 20) {
            if (ROW_DELAY && lane == 0) {
                const long long t0 = clock64(); while (clock64() - t0 < ROW_DELAY) {}
                asm volatile("cp.async.bulk.shared::cluster.global.mbarrier::complete_tx::bytes [%0], [%1], %2, [%3];"
                             :: "r"(sb + SM_ROW), "l"(prm.x + min(18 * (int)blockIdx.x, L_ - 1) * D_), "r"(max(min(18, L_ - 18 * (int)blockIdx.x), 1) * (D_ * 2)), "r"(mb + MB_R * 8) : "memory");
            }
            __syncwarp();
            mbar_wait(mb + MB_R * 8);
            if (lane == 0) {
                asm volatile("cp.async.bulk.tensor.3d.shared::cluster.global.mbarrier::complete_tx::bytes [%0], [%1, {%3, %4, %5}], [%2];"
                             :: "r"(sb + SM_XTL), "l"(&tmX), "r"(mb + MB_T * 8), "r"(d0), "r"(8 * q), "r"(0) : "memory");
            }
            STAMP(6);
        }
        if (PRE_N && warp == 23) {
            mbar_wait(mb + MB_R * 8);
            const char* wp = prm.w3[0] + blockIdx.x * (PRE_N * 4096) + lane * 128;
#pragma unroll 1
            for (int i = 0; i < PRE_N; i++) { asm volatile("prefetch.global.L2 [%0];" :: "l"(wp + i * 4096) : "memory"); __nanosleep(PRE_NS); }
        }
        asm volatile("barrier.cluster.wait.aligned;" ::: "memory");
        bar_sync(13, 736);
        if (CFENCE) asm volatile("fence.proxy.async.shared::cta;" ::: "memory");
        {
            const int gr = lane >> 2, pe = ((lane & 3) * 2 + (warp & 1) + XROT * (q + 1)) & 7;
            const int s0 = gr ? 0 : XSPLIT, ns = gr ? min(XSPLIT, nslot) : nslot - XSPLIT;
            if (gr < 2 && ns > 0) {
                const int bytes = ns * YS - 160;
                if (pe == q) arm(mb + (MB_X + gr) * 8, 7 * bytes);
                else {
                    const uint32_t rb_ = mapa(sb, pe);
                    asm volatile("cp.async.bulk.shared::cluster.shared::cta.mbarrier::complete_tx::bytes [%0], [%1], %2, [%3];"
                                 :: "r"(rb_ + SM_U + 128 + q * UP + s0 * US), "r"(sb + SM_XT + 128 + pe * YP + s0 * YS), "r"(bytes), "r"(rb_ + SM_MB + (MB_X + gr) * 8) : "memory");
                }
            }
        }
        STAMP(1);
        if (PFMAP && warp == 20 && lane == 0) { asm volatile("prefetch.tensormap [%0];" :: "l"(&tmO) : "memory"); asm volatile("prefetch.tensormap [%0];" :: "l"(&tmH) : "memory"); }
        if (warp == 23) {
#pragma unroll 1
            for (int kk = nslot - 1; kk >= 0; kk--) {
                __syncwarp();
                bar_sync(6 + kk, 160);
                if (lane == 0) { asm volatile("fence.proxy.async.shared::cta;" ::: "memory"); tma2d(sb + SM_FAR + kk * FAR_SZ, &tmD, 72 * q, 320 * c + 64 * kk, mb + MB_W2 * 8); }
            }
            return;
        }
        __syncwarp();
        if (HALF_AT == 0) bar_sync(13, 544);
        if (HALF_AT == 1) bar_sync(14, 672);
        if (HALF_AT == 2) { bar_sync(11, 672); if (OUT_NS) __nanosleep(OUT_NS); }
        if (lane == 0) {
            asm volatile("fence.proxy.async.shared::cta;" ::: "memory");
            asm volatile("cp.async.bulk.tensor.5d.global.shared::cta.bulk_group [%0, {%2, %4, %4, %4, %3}], [%1];" :: "l"(&tmH), "r"(sb + SM_XT + 16384), "r"(d0 + ((c & 1) ? 0 : 32)), "r"(8 * q), "r"(0) : "memory");
        }
        __syncwarp();
        if (HALF_AT != 1) bar_sync(14, 672);
        if (lane == 0) {
            asm volatile("cp.async.bulk.tensor.5d.global.shared::cta.bulk_group [%0, {%2, %4, %4, %4, %3}], [%1];" :: "l"(&tmO), "r"(sb + SM_XT), "r"(d0 + (c & 1) * 8), "r"(8 * q), "r"(0) : "memory");
            asm volatile("cp.async.bulk.commit_group;" ::: "memory");
            asm volatile("cp.async.bulk.wait_group 0;" ::: "memory");
            asm volatile("fence.proxy.async.global;" ::: "memory");
            asm volatile("mbarrier.arrive.shared::cta.b64 _, [%0];" :: "r"(mb + MB_OUT * 8) : "memory");
        }
        STAMP(2);
        return;
    }

    const int g = lane >> 2, cq = lane & 3;
    const int k = warp >> 2, wq = warp & 3;
    const int trow = 18 * blockIdx.x + warp;
    const bool rowact = warp < 18 && trow < L_;
    const int dch = min(d0 + 8 * k + q, D_ - 1);
    uint32_t pv[6];
#pragma unroll
    for (int i = 0; i < 6; i++) pv[i] = ldg16(prm.prm6[i] + (uint32_t)(dch * 128 + wq * 32 + lane));
    const uint32_t pLdt = ldg16(prm.logdt + dch), pD = ldg16(prm.dskip + dch);
    const int tn = 16 * (warp & 15) + g;
    uint32_t xa[5], xb[5];
    asm volatile("barrier.cluster.arrive.relaxed.aligned;" ::: "memory");
    uint4* const st1p = &g_s.st1[(((trow >> 3) & 7) * 256 + ((trow >> 6) & 31) * 8 + (trow & 7)) * 2 + (lane >> 2)];
    const bool pub = rowact && (lane & 0x1B) == 0;
    if (pub) st_rlx128(st1p, 0, 0, 0, 0);
    {
        const uint32_t za = sb + SM_P + tid * 16;
        sts128(za, 0, 0, 0, 0);
        if (tid < (SM_MISC - SM_P) / 16 - 640) sts128(za + 10240, 0, 0, 0, 0);
        sts128(sb + SM_XT + ((tid >> 3) & 15) * YP + k * YS + (lane & 7) * 16, 0, 0, 0, 0);
    }
    bar_sync(12, NTHR);
    const uint32_t dep = lds32(sb + SM_P);
#define PV(x) __uint_as_float(__byte_perm(dep, x, 0x5410))
    STAMP(1);
    const uint32_t fb = sb + SM_FAR + k * FAR_SZ;
    const uint32_t pn = sb + SM_PN + k * PN_SZ, pf = sb + SM_PF + k * PF_SZ;
    unsigned epoch;
    {
        const uint32_t kb = fb + wq * 3072;
        const uint32_t kl = kb + lane * 16;
        uint32_t Af[4][4];
        float sr, si, z1r, z1i, z2r, z2i, z4r, z4i, hr, hi_;
        {
            const float dt = bfr(ex2f(PV(pLdt) * 1.4426950408889634f));
            const float e2 = dt * PV(pv[0]) * 1.4426950408889634f, an = dt * PV(pv[1]);
            cmul(sr, si, PV(pv[4]), PV(pv[5]), dt * PV(pv[2]), dt * PV(pv[3]));
            const unsigned E = min(max(__reduce_max_sync(~0u, __float_as_uint(fmaxf(fmaxf(fabsf(sr), fabsf(si)), fabsf(PV(pD)) * (1.f / 8192.f)))) >> 23, 1u), 253u);
            const float sc = __uint_as_float((254u - E) << 23);
            sr *= sc; si *= -sc;
            sts64(sb + SM_KG + warp * 8, E, __reduce_add_sync(~0u, __float2int_rn(sr * 16777216.f)));
            float ar, ai, br, bi, cr, ci, dr, di;
            { const float m = ex2f(e2 * 8.f); ar = m * __cosf(an * 8.f); ai = m * __sinf(an * 8.f); }
            csq(br, bi, ar, ai); csq(cr, ci, br, bi); csq(dr, di, cr, ci);
            const H2C m4 = splat(cr, ci);
            {
                float r3, i3;
                cmul(r3, i3, ar, ai, br, bi);
                expand4(kl, kl + 1024, pack_f16(1.f, ar), pack_f16(br, r3), pack_f16(0.f, ai), pack_f16(bi, i3), m4);
            }
            expand8(kl + 512, kl + 1536, dr, di, ar, ai, br, bi, m4);
            { const float m = ex2f(e2); z1r = m * __cosf(an); z1i = -m * __sinf(an); }
            cexp_s(hr, hi_, e2 * 128.f, an * (-128.f * 0.15915494309189535f));
            csq(z2r, z2i, z1r, z1i); csq(z4r, z4i, z2r, z2i);
        }
        __syncwarp();
#pragma unroll
        for (int ks = 0; ks < 4; ks++) ldsm4t(Af[ks], kb + (lane >> 3) * 512 + (lane & 7) * 16 + ks * 128);
        STAMP(2);
        const uint32_t la = kb + ((lane >> 3) & 1) * 512 + (lane >> 4) * 128 + (lane & 7) * 16;
        uint32_t kp[5][2], b0[4], b1[4], b2[4], b3[4];
        auto mm2 = [&](int t) {
            float a0[4] = {0.f, 0.f, 0.f, 0.f}, a1[4] = {0.f, 0.f, 0.f, 0.f};
            mma_f16(a0, Af[0], b0[0], b0[1]); mma_f16(a1, Af[0], b2[0], b2[1]); mma_f16(a0, Af[1], b0[2], b0[3]); mma_f16(a1, Af[1], b2[2], b2[3]);
            mma_f16(a0, Af[2], b1[0], b1[1]); mma_f16(a1, Af[2], b3[0], b3[1]); mma_f16(a0, Af[3], b1[2], b1[3]); mma_f16(a1, Af[3], b3[2], b3[3]);
            kp[t][0] = pack_f16(a0[1], a0[0]); kp[t][1] = pack_f16(a0[3], a0[2]); kp[t + 1][0] = pack_f16(a1[1], a1[0]); kp[t + 1][1] = pack_f16(a1[3], a1[2]);
        };
        auto ln1 = [&]() {
        mbar_wait(mb + MB_R * 8);
        epoch = lds32(sb + SM_SC + 28) + 1;
        {
            float a[4] = {0.f, 0.f, 0.f, 0.f}, b[4] = {0.f, 0.f, 0.f, 0.f};
            uint32_t rx[9];
#pragma unroll
            for (int i = 0; i < 9; i++) rx[i] = lds32(sb + SM_ROW + warp * (D_ * 2) + lane * 4 + i * 128);
#pragma unroll
            for (int i = 0; i < 9; i++) { if (i & 1) mma_bf16_k8(b, rx[i], 0x3F803F80u, rx[i]); else mma_bf16_k8(a, rx[i], 0x3F803F80u, rx[i]); }
            float s2 = (g & 1) ? a[1] + b[1] : a[0] + b[0], s1 = (a[2] + b[2]) + (a[3] + b[3]);
            s2 += __shfl_xor_sync(~0u, s2, 4); s1 += __shfl_xor_sync(~0u, s1, 1);
            s2 += __shfl_xor_sync(~0u, s2, 9); s1 += __shfl_xor_sync(~0u, s1, 2);
            s2 += __shfl_xor_sync(~0u, s2, 18);
            const uint32_t ms = ln_stats(s1, s2);
            if (pub) st_rlx128(st1p, ms, epoch, ms, epoch);
        }
        mbar_wait(mb + MB_R * 8);
        };
        auto norm = [&]() {
        STAMP(3);
        if (warp < 16) {
            const uint4* sp = &g_s.st1[(256 * q + tn) * 2];
            uint32_t va[5], vc[5];
            mbar_wait(mb + MB_T * 8);
            {
                const uint32_t xt = sb + SM_XTL + tn * 80;
                uint4 a4 = lds128(xt + cq * 16), b4 = lds128(xt + cq * 16 + 640);
                va[0] = a4.x; va[1] = a4.y; va[2] = a4.z; va[3] = a4.w; va[4] = lds32(xt + 64 + cq * 4);
                vc[0] = b4.x; vc[1] = b4.y; vc[2] = b4.z; vc[3] = b4.w; vc[4] = lds32(xt + 704 + cq * 4);
            }
            uint2 sa, sc; int n = 0;
            do { sa = ld_rlx64(sp); sc = ld_rlx64(sp + 16); } while ((sa.y != epoch || sc.y != epoch) && ++n < SPIN_LIMIT);
            STAMP(4);
            const uint32_t ra = rsplit(rcpf(bf_hi(sa.x))), rc = rsplit(rcpf(bf_hi(sc.x)));
            const uint32_t ma = __byte_perm(sa.x, 0, 0x1010), mc = __byte_perm(sc.x, 0, 0x1010);
            const uint32_t rha = __byte_perm(ra, 0, 0x1010), rla = __byte_perm(ra, 0, 0x3232), rhc = __byte_perm(rc, 0, 0x1010), rlc = __byte_perm(rc, 0, 0x3232);
#pragma unroll
            for (int i = 0; i < 5; i++) {
                va[i] = norm2(va[i], ma, rha, rla); va[i] = pack_f16(bf_lo(va[i]), bf_hi(va[i]));
                vc[i] = norm2(vc[i], mc, rhc, rlc); vc[i] = pack_f16(bf_lo(vc[i]), bf_hi(vc[i]));
            }
            const int d4 = 2 * (lane >> 3) + (lane & 1), d1_ = lane & 7;
            const uint32_t a4 = sb + warp * 32 + d4 * YP + (d4 == q ? SM_U + 128 : SM_XT + 128) + ((lane & 7) >> 1) * YS;
            const uint32_t a1 = sb + warp * 32 + d1_ * YP + (d1_ == q ? SM_U + 128 : SM_XT + 128) + 4 * YS + (lane & 8) * 2;
            stsm4t(a4, va[0], va[1], va[2], va[3]); stsm4t(a4 + 16, vc[0], vc[1], vc[2], vc[3]); stsm2t(a1, va[4], vc[4]);
        }
        if (!CFENCE) asm volatile("fence.proxy.async.shared::cta;" ::: "memory");
        bar_arrive(13, 736);
        if (warp < 16) {
            const uint32_t xh = sb + SM_XTL + (64 * (g >> 1) + 32 * (warp & 1) + 8 * (g & 1) + (warp >> 1)) * 80;
            const uint4 a4 = lds128(xh + cq * 16), b4 = lds128(xh + cq * 16 + 1280);
            xa[0] = a4.x; xa[1] = a4.y; xa[2] = a4.z; xa[3] = a4.w; xa[4] = lds32(xh + 64 + cq * 4);
            xb[0] = b4.x; xb[1] = b4.y; xb[2] = b4.z; xb[3] = b4.w; xb[4] = lds32(xh + 1344 + cq * 4);
            bar_arrive(15, 544);
        }
        STAMP(5);
        };
        if (LNPOS == 0) ln1();
        cmul(sr, si, sr, si, z1r, z1i);
        {
            const H2C h4 = splat(z4r, z4i);
            expand8(kl, kl + 512, sr, si, z1r, z1i, z2r, z2i, h4);
            cmul(sr, si, sr, si, hr, hi_);
            expand8(kl + 1024, kl + 1536, sr, si, z1r, z1i, z2r, z2i, h4);
        }
        __syncwarp();
        ldsm4t(b0, la); ldsm4t(b1, la + 256); ldsm4t(b2, la + 1024); ldsm4t(b3, la + 1280);
        cmul(z1r, z1i, z1r, z1i, hr, hi_);
        cmul(sr, si, sr, si, z1r, z1i);
        if (LNPOS == 1) ln1();
        expand8(kl, kl + 512, sr, si, z2r, z2i, z4r, z4i, splat(hr, hi_));
        mm2(0);
        if (LNPOS == 2) ln1();
        if (NMPOS == 2) norm();
        csq(z1r, z1i, z1r, z1i);
        cmul(sr, si, sr, si, z1r, z1i);
        csq(z2r, z2i, hr, hi_);
        expand8(kl + 1024, kl + 1536, sr, si, z4r, z4i, hr, hi_, splat(z2r, z2i));
        __syncwarp();
        ldsm4t(b0, la); ldsm4t(b1, la + 256); ldsm4t(b2, la + 1024); ldsm4t(b3, la + 1280);
        csq(z1r, z1i, z1r, z1i);
        cmul(sr, si, sr, si, z1r, z1i);
        csq(z4r, z4i, z2r, z2i);
        expand8(kl, kl + 512, sr, si, hr, hi_, z2r, z2i, splat(z4r, z4i));
        mm2(2);
        if (LNPOS == 3) ln1();
        if (NMPOS == 3) norm();
        __syncwarp();
        ldsm4t(b0, la); ldsm4t(b1, la + 256);
#pragma unroll
        for (int t = 0; t < 4; t++) sts64(kb + lane * 8 + 1024 + t * 256, kp[t][0], kp[t][1]);
        {
            float a0[4] = {0.f, 0.f, 0.f, 0.f}, a1[4] = {0.f, 0.f, 0.f, 0.f};
            mma_f16(a0, Af[0], b0[0], b0[1]); mma_f16(a1, Af[1], b0[2], b0[3]); mma_f16(a0, Af[2], b1[0], b1[1]); mma_f16(a1, Af[3], b1[2], b1[3]);
            sts64(kb + lane * 8 + 2048, pack_f16(a0[1] + a1[1], a0[0] + a1[0]), pack_f16(a0[3] + a1[3], a0[2] + a1[2]));
        }
        if (NMPOS == 4) norm();
        bar_sync(1 + k, 128);
        const uint4 m01 = lds128(sb + SM_KG + k * 32), m23 = lds128(sb + SM_KG + k * 32 + 16);
        const unsigned Em = max(max(m01.x, m01.z), max(m23.x, m23.z));
        const float f0 = __uint_as_float(max((int)(127 + m01.x - Em), 0) << 23), f1 = __uint_as_float(max((int)(127 + m01.z - Em), 0) << 23),
                    f2 = __uint_as_float(max((int)(127 + m23.x - Em), 0) << 23), f3 = __uint_as_float(max((int)(127 + m23.z - Em), 0) << 23);
        const uint32_t r0 = pack_f16(f0, f0), r1 = pack_f16(f1, f1), r2 = pack_f16(f2, f2), r3 = pack_f16(f3, f3);
        const uint32_t ra = fb + lane * 8 + wq * 256 + 1024;
        const uint2 p0 = lds64(ra), p1 = lds64(ra + 3072), p2 = lds64(ra + 6144), p3 = lds64(ra + 9216);
        uint32_t w0 = hadd2(hfma2(p0.x, r0, hmul2(p1.x, r1)), hfma2(p2.x, r2, hmul2(p3.x, r3)));
        uint32_t w1 = hadd2(hfma2(p0.y, r0, hmul2(p1.y, r1)), hfma2(p2.y, r2, hmul2(p3.y, r3)));
        const bool last = lane == 31;
        if (wq < 2) {
            const uint32_t rc = fb + lane * 8 + wq * 4 + 2048;
            const uint32_t w4 = hmul2(hadd2(hfma2(lds32(rc), r0, hmul2(lds32(rc + 3072), r1)), hfma2(lds32(rc + 6144), r2, hmul2(lds32(rc + 9216), r3))), 0x18001800u);
            const uint32_t ph = pf + (P_H7 + 16 * wq) + (g & 1) * (2 * P_HS) + cq * 64 + (g >> 1) * 4;
            put16(ph, w4 >> 16); put16(ph + 32, w4);
            const uint32_t pa = pn + (4 + 512 * wq) + lane * 8;
            sts16(pa, w0 >> 16); sts32(pa + 4, w0); sts16(pa + 10, w0);
            sts16(pa + 256, w1 >> 16); sts32(pa + 260, w1); sts16(pa + 266, w1);
            if (last) {
                sts32(sb + SM_SC + k * 4, Em * 0x00800080u);
                put16(wq ? pa + 264 : pn,
                      wq ? w1 : pack_f16(((float)(int)m01.y * f0 + (float)(int)m01.w * f1 + (float)(int)m23.y * f2 + (float)(int)m23.w * f3) * (1.f / 16777216.f)
                                         + __uint_as_float(pD << 16) * __uint_as_float((254u - Em) << 23), 0.f));
            }
        } else if (wq == 2) {
            const uint32_t pa = pn + 258 * 4 + (cq & 1) * 16 + (cq >> 1) * 512 + g * 32;
            if (last) { put16(pf, hmul2(w1, 0x18001800u)); w1 = hadd2(w1, hneg2(__byte_perm(w1, 0, 0x1010))); }
            const uint32_t b0 = __byte_perm(w0, 0, 0x1010), b1 = __byte_perm(w1, 0, 0x1010);
            sts16(pa, w0 >> 16); sts32(pa + 4, w0); sts64(pa + 8, b0, b0); sts16(pa + 18, w0);
            sts16(pa + 256, w1 >> 16); sts32(pa + 260, w1); sts64(pa + 264, b1, b1); sts16(pa + 274, w1);
        } else {
            const uint32_t pa = pf + ((g & 1) ? 3 * P_GS : P_GS) + cq * 32 + (g >> 1) * 4;
            const uint32_t pb = pa + ((g & 1) ? 4 - 3 * P_GS : P_GS);
            w0 = hmul2(w0, 0x18001800u); w1 = hmul2(w1, 0x18001800u);
            put16(pa, w0 >> 16); put16(pb, w0); put16(pa + 16, w1 >> 16); put16(pb + 16, w1);
            if (last) put16(pf + P_H7 + P_HS, w1);
        }
        bar_sync(1 + k, 128);
    }
    STAMP(6);

    asm volatile("barrier.cluster.wait.aligned;" ::: "memory");
    mbar_wait(mb + (MB_X + (k < XSPLIT || k >= nslot)) * 8);
    STAMP(7);
    if (k < nslot) {
        const int role = (wq + k) & 3;
        const uint32_t ub = sb + SM_U + k * US + 128;
        if (role) {
            const int r = (3 - role) * 32 + lane;
            const uint32_t a1 = ub + (r & 3) * (2 * UP) + (r >> 2) * 16, a0 = a1 + ((r & 3) ? -2 * UP : 6 * UP - 16);
            const uint4 q0 = lds128(a0), q1 = lds128(a0 + UP), q2 = lds128(a1), q3 = lds128(a1 + UP);
            const uint32_t U[16] = {q0.x, q0.y, q0.z, q0.w, q1.x, q1.y, q1.z, q1.w, q2.x, q2.y, q2.z, q2.w, q3.x, q3.y, q3.z, q3.w};
            uint32_t V[14], Q[14], R4[12], T[8];
#pragma unroll
            for (int i = 2; i < 14; i++) { V[i] = __byte_perm(U[i], U[i + 1], 0x5432); Q[i] = hadd2(U[i], V[i]); }
#pragma unroll
            for (int i = 2; i < 12; i++) R4[i] = hadd2(Q[i], Q[i + 1]);
            const uint32_t rb = fb + r * 16;
#pragma unroll
            for (int i = 0; i < 8; i++) T[i] = hadd2(V[5 + i], Q[6 + i]);
            sts128(rb + F_E3, T[0], T[1], T[2], T[3]); sts128(rb + F_O3 + 16, T[4], T[5], T[6], T[7]);
#pragma unroll
            for (int i = 0; i < 8; i++) T[i] = hadd2(R4[3 + i], U[5 + i]);
            sts128(rb + F_O5, T[0], T[1], T[2], T[3]); sts128(rb + F_E5, T[4], T[5], T[6], T[7]);
            if (role != 1) {
#pragma unroll
                for (int i = 0; i < 8; i++) T[i] = hadd2(T[i], hadd2(V[2 + i], V[5 + i]));
                sts128(rb + F_E7, T[0], T[1], T[2], T[3]); sts128(rb + F_O7, T[4], T[5], T[6], T[7]);
#pragma unroll
                for (int i = 0; i < 8; i++) T[i] = hadd2(R4[2 + i], hadd2(R4[4 + i], U[6 + i]));
                sts128(rb + F_O9, T[0], T[1], T[2], T[3]); sts128(rb + F_E9 + 16, T[4], T[5], T[6], T[7]);
                sts128(rb + F_E2, Q[6], Q[7], Q[8], Q[9]); sts128(rb + F_O2, Q[10], Q[11], Q[12], Q[13]);
            }
        } else if (lane < 8) {
            uint32_t v[5];
#pragma unroll
            for (int i = 0; i < 5; i++) { const int t = 6 + lane + i; v[i] = lds16(ub + 23 * 16 + (t < 16 ? (6 + (t >> 3)) * UP : 16) + (t & 7) * 2); }
            const uint32_t s = hadd2(hadd2(hadd2(v[0], v[1]), hadd2(v[2], v[3])), v[4]);
            sts16(fb + F_O5 + 96 * 16 + lane * 2, s);
            sts32(fb + (lane < 4 ? F_O3 : F_E9 - 16) + lane * 4, 0);
        }
        bar_sync(1 + k, 128);
        float acc[4][4];
        uint32_t Q[4][4];
        {
            const int h = role & 1, part = role >> 1;
            const uint32_t po = pf + (g - 2 * cq) * 4;
            float fa[7][4];
#pragma unroll
            for (int a = 0; a < 7; a++) fa[a][0] = fa[a][1] = fa[a][2] = fa[a][3] = 0.f;
            uint32_t B[3][4];
            Q[0][2] = zero;
#pragma unroll 1
            for (int s = 2 * part + 1; s >= 2 * part; s--) {
#pragma unroll
                for (int i = 0; i < 3; i++) { Q[i][0] = lds32(po + s * P_GS + i * 64); Q[i][1] = lds32(po + s * P_GS + (i * 64 + 32)); }
                const uint32_t ba = fb + lane * 16 + ((s & 1) * F_E3 + (part == h ? 0 : F_O5 + h * 16));
#pragma unroll
                for (int i = 0; i < 3; i++) ldsm4t(B[i], ba + i * 512);
#pragma unroll
                for (int i = 0; i < 3; i++) { Q[i][3] = CP(Q[i][0]); if (i) Q[i][2] = CP(Q[i - 1][1]); }
#pragma unroll
                for (int dl = 0; dl < 3; dl++)
#pragma unroll
                    for (int ap = 0; ap < 6 - dl; ap++) mma_f16(fa[ap + 1 + dl], Q[dl], B[ap >> 1][2 * (ap & 1)], B[ap >> 1][2 * (ap & 1) + 1]);
            }
#pragma unroll 1
            for (int s = role; s == 1; s++) {
                ldsm2t(B[0][0], B[0][1], fb + ((lane & 15) == 15 ? F_O5 : F_O3));
#pragma unroll
                for (int dl = 0; dl < 3; dl++) mma_f16(fa[dl], Q[dl], B[0][0], B[0][1]);
            }
#pragma unroll 1
            for (int s = part; s <= 2 * part; s++) {
#pragma unroll
                for (int i = 0; i < 4; i++) { Q[i][0] = lds32(po + s * P_HS + (P_H7 + i * 64)); Q[i][1] = lds32(po + s * P_HS + (P_H7 + i * 64 + 32)); }
                const uint32_t ba = fb + lane * 16 + (F_E7 + s * 1024 + h * F_H);
                ldsm4t(B[0], ba); ldsm4t(B[1], ba + 512);
#pragma unroll
                for (int i = 0; i < 4; i++) { Q[i][3] = CP(Q[i][0]); if (i) Q[i][2] = CP(Q[i - 1][1]); }
#pragma unroll
                for (int dl = 0; dl < 4; dl++) {
#pragma unroll
                    for (int ap = 0; ap < 4 - dl; ap++) mma_f16(fa[ap + 3 + dl], Q[dl], B[ap >> 1][2 * (ap & 1)], B[ap >> 1][2 * (ap & 1) + 1]);
                    if (s == 1) break;
                }
            }
            const uint32_t da = fb + role * 2048 + (lane & 3) * 512 + (((lane >> 2) ^ ((lane & 3) * 2)) << 4);
            bar_sync(1 + k, 128);
            stsm4(da, 0u, 0u, pack_f16(fa[0][0], fa[0][1]), pack_f16(fa[0][2], fa[0][3]));
#pragma unroll
            for (int i = 1; i < 4; i++)
                stsm4(da + i * 128, pack_f16(fa[2 * i - 1][0], fa[2 * i - 1][1]), pack_f16(fa[2 * i - 1][2], fa[2 * i - 1][3]),
                      pack_f16(fa[2 * i][0], fa[2 * i][1]), pack_f16(fa[2 * i][2], fa[2 * i][3]));
            Q[0][0] = (g == 2 * cq) ? 0x6000u : ((g == 2 * cq + 1) ? 0x60000000u : 0u);
            Q[0][1] = 0; Q[0][3] = CP(Q[0][0]);
            const uint32_t ra = fb + (lane >> 3) * 2048 + wq * 512 + (((lane & 7) ^ (wq * 2)) << 4);
            bar_sync(1 + k, 128);
#pragma unroll
            for (int i = 0; i < 4; i++) {
                ldsm4(B[0], ra + i * 128);
                acc[i][0] = acc[i][1] = acc[i][2] = acc[i][3] = 0.f;
                mma_f16(acc[i], Q[0], hadd2(B[0][0], B[0][2]), hadd2(B[0][1], B[0][3]));
            }
        }
        bar_arrive(6 + k, 160);
        STAMP(8);
        const uint32_t inv = lds32(sb + SM_SC + k * 4);
        uint32_t yd = mapa(sb, 2 * wq) + (SM_XT + 128 + q * YP + k * YS) + lane * 16;
        PIN(yd);
        {
            uint32_t pp = pn + (16 * (wq - 3) + g - 2 * cq) * 4;
            uint32_t dlo = (((ub + 6 * UP) & 0x3FFFF) >> 4) | ((UP >> 4) << 16);
            uint32_t R[4][4];
            auto loadQ = [&](uint32_t (&X)[4][4], uint32_t prev) {
#pragma unroll
                for (int i = 0; i < 4; i++) { X[i][0] = lds32(pp + i * 64); X[i][1] = lds32(pp + i * 64 + 32); }
                X[0][2] = CP(prev);
#pragma unroll
                for (int i = 0; i < 4; i++) { X[i][3] = CP(X[i][0]); if (i) X[i][2] = CP(X[i - 1][1]); }
                pp += 256;
            };
            auto issue = [&](uint32_t (&X)[4][4]) {
                asm volatile("wgmma.fence.sync.aligned;" ::: "memory");
#pragma unroll
                for (int i = 0; i < 4; i++) wgmma32(acc, X[i], dlo - i * (2 * UP >> 4));
                asm volatile("wgmma.commit_group.sync.aligned;" ::: "memory");
                dlo -= 1;
            };
            loadQ(Q, 0);
#pragma unroll 1
            for (int dl = 0; dl < 4; dl++) {
                issue(Q);
                asm volatile("wgmma.wait_group.sync.aligned 1;" ::: "memory");
                loadQ(R, Q[3][1]);
                issue(R);
                asm volatile("wgmma.wait_group.sync.aligned 1;" ::: "memory");
                loadQ(Q, R[3][1]);
            }
            issue(Q);
            asm volatile("wgmma.wait_group.sync.aligned 0;" ::: "memory");
        }
        const uint32_t pstep = mapa(sb, 1) - mapa(sb, 0), ym = mapa(mb + MB_Y * 8, 2 * wq);
#pragma unroll
        for (int e = 0; e < 2; e++)
            st_async4(yd + e * pstep, bmul2(pack_bf16(acc[0][2 * e], acc[0][2 * e + 1]), inv), bmul2(pack_bf16(acc[1][2 * e], acc[1][2 * e + 1]), inv),
                      bmul2(pack_bf16(acc[2][2 * e], acc[2][2 * e + 1]), inv), bmul2(pack_bf16(acc[3][2 * e], acc[3][2 * e + 1]), inv), ym + e * pstep);
        if (lane == 0) asm volatile("mbarrier.arrive.shared::cta.b64 _, [%0];" :: "r"(mb + MB_Y * 8) : "memory");
    }
    STAMP(9);
    uint32_t ha[5], hb[5];
    if (warp < 16) {
        const uint4 wk = lds128(sb + SM_DW + cq * 16);
        uint32_t sel[5] = {wk.x, wk.y, wk.z, wk.w, lds32(sb + SM_DW + 64 + cq * 4)}, sel2[5];
#pragma unroll
        for (int i = 0; i < 5; i++) {
            if (!(g & 1)) sel[i] = 0x3F803F80u;
            sel2[i] = sel[i]; PIN(sel2[i]);
        }
        const uint32_t y4 = sb + SM_XT + 128 + warp * 32 + (2 * (lane >> 3) + (lane & 1)) * YP + ((lane & 7) >> 1) * YS;
        const uint32_t y1 = sb + SM_XT + 128 + warp * 32 + (lane & 7) * YP + 4 * YS + (lane & 8) * 2;
        mbar_wait(mb + MB_Y * 8);
        STAMP(10);
        float ca[4] = {0.f, 0.f, 0.f, 0.f}, cb[4] = {0.f, 0.f, 0.f, 0.f};
        {
            uint32_t ya[4], yb[4], yc, yd;
            ldsm4t(ya, y4); ldsm4t(yb, y4 + 16); ldsm2t(yc, yd, y1);
#pragma unroll
            for (int i = 0; i < 4; i++) { ha[i] = badd2(xa[i], ya[i]); hb[i] = badd2(xb[i], yb[i]); }
            ha[4] = badd2(xa[4], yc); hb[4] = badd2(xb[4], yd);
        }
        if (nslot != 5) {
            ha[4] = hb[4] = 0;
            if (cq >= 2) ha[0] = ha[1] = ha[2] = ha[3] = hb[0] = hb[1] = hb[2] = hb[3] = 0;
        }
#pragma unroll
        for (int i = 0; i < 5; i++) { mma_bf16_k8(ca, ha[i], sel[i], ha[i]); mma_bf16_k8(cb, hb[i], sel2[i], hb[i]); }
        const float oa = __shfl_xor_sync(~0u, (g & 1) ? ca[2] : ca[3], 4), ob = __shfl_xor_sync(~0u, (g & 1) ? cb[2] : cb[3], 4);
        if (cq == (g >> 1)) {
            float4* ap = &g_s.acc[256 * q + tn];
            const bool od = g & 1;
            asm volatile("red.relaxed.gpu.global.add.v4.f32 [%0], {%1,%2,%3,%4};" :: "l"(ap), "f"(od ? oa : ca[2]), "f"(od ? ca[1] : ca[0]), "f"(od ? ca[3] : oa), "f"(1.0f) : "memory");
            asm volatile("red.relaxed.gpu.global.add.v4.f32 [%0], {%1,%2,%3,%4};" :: "l"(ap + 8), "f"(od ? ob : cb[2]), "f"(od ? cb[1] : cb[0]), "f"(od ? cb[3] : ob), "f"(1.0f) : "memory");
        }
        const uint32_t hta = sb + SM_HT + tn * 80;
        sts128(hta + cq * 16, ha[0], ha[1], ha[2], ha[3]); sts32(hta + 64 + cq * 4, ha[4]);
        sts128(hta + cq * 16 + 640, hb[0], hb[1], hb[2], hb[3]); sts32(hta + 704 + cq * 4, hb[4]);
        STAMP(11);
    }
    const int kq = warp / 5, mt = warp - 5 * kq;
    const int mi = lane >> 3, mr = lane & 7;
    const unsigned tk = (unsigned)tid / 72u, ck = tid - tk * 72;
    uint32_t A[9][4];
    auto loadA = [&]() {
        mbar_wait(mb + MB_W1 * 8);
        const uint32_t aa = sb + (mi & 1) * SM_WU + (8 * (mi >> 1) + mr) * 80 + (144 * 80 * kq + mt * 16);
#pragma unroll
        for (int s = 0; s < 9; s++) ldsm4t(A[s], aa + s * 1280);
    };
    const uint32_t par = (epoch & 1) ? 0x40004000u : 0u;
    uint32_t pk0 = mapa(sb, 2 * cq), go = (ck / 5u + ck) * 16, co = ((q * 8 * NCL + c) * 6 + cq) * 16;
    PIN(pk0); PIN(go); PIN(co);
    if (warp < 8) {
        const float wsum = ldsf(sb + SM_SC + 24);
        const uint32_t idx = 2047 - (512 * ((tid >> 1) & 3) + 128 * ((tid >> 3) & 3) + 64 * (tid & 1) + 8 * q + warp);
        if (RED_DELAY) { const long long t0 = clock64(); while (clock64() - t0 < RED_DELAY) {} }
        uint4 s; int n = 0;
        do { s = ld_rlx128(&g_s.acc[256 * q + tid]); } while (__uint_as_float(s.w) != (float)NCL && ++n < SPIN_LIMIT);
        STAMP(16);
        const uint32_t ms = ln_stats(__uint_as_float(s.x), __uint_as_float(s.y));
        const float rs = rcpf(bf_hi(ms));
        const uint32_t rb = pack_bf16(0.f, fmaf(-bf_lo(ms), wsum, __uint_as_float(s.z)) * rs);
        const uint32_t key = (((rb ^ (((int)rb >> 31) | 0x80000000u)) >> 16) << 11) | idx;
        sts32(sb + SM_KEY + tid * 4, key);
        __syncwarp();
        const uint32_t rank = rank4<8>(sb + SM_KEY + warp * 128, key);
        if (rank < 8) sts32(sb + SM_CAND + warp * 32 + rank * 4, key);
        sts64(sb + SM_ST + tid * 8, __byte_perm(ms, 0, 0x1010), rsplit(rs));
    } else loadA();
    if (warp < 16) {
        STAMP(17);
        bar_sync(12, 512);
        STAMP(18);
        if (warp < 8) {
            const uint32_t mk = lds32(sb + SM_CAND + (tid >> 2) * 4);
            uint32_t rank = rank4<4>(sb + SM_CAND + cq * 64, mk);
            rank += __shfl_xor_sync(~0u, rank, 1); rank += __shfl_xor_sync(~0u, rank, 2);
            if (rank < 8) {
                const uint32_t pk1 = pk0 + (mapa(sb, 1) - mapa(sb, 0));
                st_async1(pk0 + (SM_RK + q * 32) + rank * 4, mk, pk0 + (SM_MB + MB_KEY * 8));
                st_async1(pk1 + (SM_RK + q * 32) + rank * 4, mk, pk1 + (SM_MB + MB_KEY * 8));
                const uint32_t t = tslot(~mk);
                const uint2 sv = lds64(sb + SM_ST + t * 8);
                const uint4 hv = lds128(sb + SM_HT + t * 80 + cq * 16);
                const uint32_t h4 = lds32(sb + SM_HT + t * 80 + 64 + cq * 4);
                const uint32_t rr = bmul2(sv.y, 0x3C803C80u), rh = __byte_perm(rr, 0, 0x1010), rl = __byte_perm(rr, 0, 0x3232);
                char* const dp = (char*)g_s.cand + (co + rank * 1440);
                st_rlx128(dp, (norm2(hv.x, sv.x, rh, rl) & 0xBFFFBFFFu) | par, (norm2(hv.y, sv.x, rh, rl) & 0xBFFFBFFFu) | par,
                          (norm2(hv.z, sv.x, rh, rl) & 0xBFFFBFFFu) | par, (norm2(hv.w, sv.x, rh, rl) & 0xBFFFBFFFu) | par);
                asm volatile("st.relaxed.gpu.global.u32 [%0], %1;" :: "l"((char*)g_s.cand + (co + rank * 1440 + 64 - cq * 12)), "r"((norm2(h4, sv.x, rh, rl) & 0xBFFFBFFFu) | par) : "memory");
            }
            __syncwarp();
        }
        {
            const uint2 sa = lds64(sb + SM_ST + tn * 8), sbb = lds64(sb + SM_ST + tn * 8 + 64);
            const uint32_t rha = __byte_perm(sa.y, 0, 0x1010), rla = __byte_perm(sa.y, 0, 0x3232);
            const uint32_t rhb = __byte_perm(sbb.y, 0, 0x1010), rlb = __byte_perm(sbb.y, 0, 0x3232);
#pragma unroll
            for (int i = 0; i < 5; i++) { ha[i] = badd2(ha[i], norm2(ha[i], sa.x, rha, rla)); hb[i] = badd2(hb[i], norm2(hb[i], sbb.x, rhb, rlb)); }
            const bool hf = (c & 1) && cq == 0;
            const uint32_t o16 = sb + SM_XT + (hf ? 16384 + tn * 16 : tn * 64 + (cq - (c & 1)) * 16), o4 = sb + SM_XT + ((c & 1) ? tn * 64 + 48 : 16384 + tn * 16) + cq * 4;
            sts128(o16, ha[0], ha[1], ha[2], ha[3]); sts32(o4, ha[4]);
            sts128(o16 + (hf ? 128 : 512), hb[0], hb[1], hb[2], hb[3]); sts32(o4 + ((c & 1) ? 512 : 128), hb[4]);
            if (HALF_AT == 0) bar_arrive(13, 544);
        }
        if (warp >= 8) {
            STAMP(19);
            mbar_wait(mb + MB_KEY * 8);
            STAMP(20);
            const uint32_t mk = lds32(sb + SM_RK - 256 + (tid >> 2) * 4);
            uint32_t rank = rank4<4>(sb + SM_RK + cq * 64, mk);
            rank += __shfl_xor_sync(~0u, rank, 1); rank += __shfl_xor_sync(~0u, rank, 2);
            if (rank < 8) sts64(sb + SM_SEL + rank * 8, mk, ((tid >> 2) - 64) * 1440);
        }
    }
    bar_sync(11, HALF_AT == 2 ? 672 : 640);
    STAMP(12);

    const char* gp = (const char*)g_s.cand + (go + lds32(sb + SM_SEL + 4 + (tk & 7) * 8));
    uint4 hv = ld_rlx128(gp);
    if (warp < 8) loadA();
    const bool red = warp < 6;
    const uint32_t ft = red ? (unsigned)tid / 24u : (unsigned)(tid >> 4) & 7u, fj = red ? 24 * q + tid - ft * 24 : d0 / 3 + (lane & 15);
    const uint32_t key = lds32(sb + SM_SEL + ft * 8), k16 = key << 5;
    float sig = bfr(rcpf(1.f + ex2f(__uint_as_float((k16 ^ (~((int)k16 >> 31) | 0x80000000u)) & 0xFFFF0000u) * -1.4426950408889634f)));
    uint32_t ra2 = sb + SM_RED2 + tid * 12 + ft * 16, fo = (ft * 192 + fj) * 16, oo = ((~key & 2047) * D_ + 3 * fj) * 2;
    uint32_t bx = sb + SM_XS + mr * 1168 + mi * 16 + 288 * kq, gd = mapa(sb, kq * (8 / NRED)) + (SM_GU + (q * nslot + mt) * 128) + lane * 4;
    PIN(ra2); PIN(fo); PIN(oo); PIN(bx); PIN(gd);
    asm volatile("" : "+f"(sig));
    {
        if (warp < 18) {
            int n = 0;
            while ((((hv.x ^ par) | (hv.y ^ par) | (hv.z ^ par) | (hv.w ^ par)) & 0x40004000u) && ++n < SPIN_LIMIT) hv = ld_rlx128(gp);
            sts128(sb + SM_XS + tk * 16 + tid * 16, hv.x ^ par, hv.y ^ par, hv.z ^ par, hv.w ^ par);
        }
    }
    bar_sync(14, 672);
    STAMP(13);
    {
        float c0[4] = {0.f, 0.f, 0.f, 0.f}, c1[4] = {0.f, 0.f, 0.f, 0.f}, c2[4] = {0.f, 0.f, 0.f, 0.f};
        uint32_t b[5][4];
#pragma unroll
        for (int s = 0; s < 4; s++) ldsm4(b[s], bx + s * 64);
        asm volatile("ldmatrix.sync.aligned.m8n8.x2.shared.b16 {%0,%1}, [%2];" : "=r"(b[4][0]), "=r"(b[4][1]) : "r"(bx + 256) : "memory");
        mma_bf16(c0, A[0][0], A[0][1], A[0][2], A[0][3], b[0][0], b[0][1]);
        mma_bf16(c1, A[1][0], A[1][1], A[1][2], A[1][3], b[0][2], b[0][3]);
        mma_bf16(c2, A[2][0], A[2][1], A[2][2], A[2][3], b[1][0], b[1][1]);
        mma_bf16(c0, A[3][0], A[3][1], A[3][2], A[3][3], b[1][2], b[1][3]);
        mma_bf16(c1, A[4][0], A[4][1], A[4][2], A[4][3], b[2][0], b[2][1]);
        mma_bf16(c2, A[5][0], A[5][1], A[5][2], A[5][3], b[2][2], b[2][3]);
        mma_bf16(c0, A[6][0], A[6][1], A[6][2], A[6][3], b[3][0], b[3][1]);
        mma_bf16(c1, A[7][0], A[7][1], A[7][2], A[7][3], b[3][2], b[3][3]);
        mma_bf16(c2, A[8][0], A[8][1], A[8][2], A[8][3], b[4][0], b[4][1]);
        sts128f(sb + SM_RED + tid * 16, c0[0] + c1[0] + c2[0], c0[1] + c1[1] + c2[1], c0[2] + c1[2] + c2[2], c0[3] + c1[3] + c2[3]);
    }
    bar_sync(1 + mt, 128);
    STAMP(21);
    if (mt < nslot && kq < NRED) {
        const uint32_t ra = sb + SM_RED + mt * 512 + lane * 16;
        const float4 p0 = lds128f(ra), p1 = lds128f(ra + 2560), p2 = lds128f(ra + 5120), p3 = lds128f(ra + 7680);
        const float g0 = bfr(((p0.x + p1.x) + (p2.x + p3.x)) * 64.f), g1 = bfr(((p0.y + p1.y) + (p2.y + p3.y)) * 64.f);
        const uint32_t sg = pack_bf16(g0 * rcpf(1.f + ex2f(g0 * -1.4426950408889634f)), g1 * rcpf(1.f + ex2f(g1 * -1.4426950408889634f)));
        const uint32_t gu = bmul2(sg, pack_bf16(((p0.z + p1.z) + (p2.z + p3.z)) * 64.f, ((p0.w + p1.w) + (p2.w + p3.w)) * 64.f));
        const uint32_t pstep = mapa(sb, 1) - mapa(sb, 0), gm = mapa(mb + MB_GU * 8, kq * (8 / NRED));
#pragma unroll
        for (int i = 0; i < 8 / NRED; i++) st_async1(gd + i * pstep, gu, gm + i * pstep);
    }
    mbar_wait(mb + MB_W2 * 8);
    {
        const uint32_t aa = sb + (8 * (mi >> 1) + mr) * 144 + (mi & 1) * 16 + (SM_FAR + 2304 * kq + mt * 32);
#pragma unroll
        for (int s = 0; s < 5; s++) ldsm4t(A[s], aa + s * FAR_SZ);
    }
    {
        uint32_t ba = sb + (SM_GU + 256 * kq) + (lane & 15) * 16 + (lane >> 4) * 1024, wa = sb + (SM_RED2 + kq * 2432 + mt * 64) + g * 4 + cq * 608;
        PIN(ba); PIN(wa);
        STAMP(22);
        mbar_wait(mb + MB_GU * 8);
        STAMP(23);
        float c0[4] = {0.f, 0.f, 0.f, 0.f}, c1[4] = {0.f, 0.f, 0.f, 0.f}, c2[4] = {0.f, 0.f, 0.f, 0.f};
        uint32_t b[2][4], b8, b9;
        ldsm4t(b[0], ba); ldsm4t(b[1], ba + 2048); ldsm2t(b8, b9, ba + 4096);
        mma_bf16(c0, A[0][0], A[0][1], A[0][2], A[0][3], b[0][0], b[0][1]);
        mma_bf16(c1, A[1][0], A[1][1], A[1][2], A[1][3], b[0][2], b[0][3]);
        if (nslot == 5) {
            mma_bf16(c2, A[4][0], A[4][1], A[4][2], A[4][3], b8, b9);
            mma_bf16(c0, A[2][0], A[2][1], A[2][2], A[2][3], b[1][0], b[1][1]);
            mma_bf16(c1, A[3][0], A[3][1], A[3][2], A[3][3], b[1][2], b[1][3]);
        }
        stsf(wa, c0[0] + c1[0] + c2[0]); stsf(wa + 304, c0[1] + c1[1] + c2[1]);
        if (mt < 4) { stsf(wa + 32, c0[2] + c1[2] + c2[2]); stsf(wa + 336, c0[3] + c1[3] + c2[3]); }
    }
    if (warp < 10) {
        float v[3], cnt = 3.f;
        if (red) {
            bar_sync(6, 640);
            STAMP(14);
#pragma unroll
            for (int i = 0; i < 3; i++) v[i] = ((ldsf(ra2 + i * 4) + ldsf(ra2 + i * 4 + 2432)) + (ldsf(ra2 + i * 4 + 4864) + ldsf(ra2 + i * 4 + 7296))) * sig;
        } else {
            bar_arrive(6, 640);
            cnt = 0.f;
#pragma unroll
            for (int i = 0; i < 3; i++) {
                const uint32_t cl = 3 * fj + i - d0;
                const bool ok = cl < 8 * nslot && ((~key >> 3) & 7) == q;
                const uint32_t cf = cl - (c & 1) * 8;
                v[i] = ok ? __uint_as_float(lds16(sb + SM_XT + (cf < 32 ? tslot(~key) * 64 + cf * 2 : 16384 + tslot(~key) * 16 + (cl & 7) * 2)) << 16) : 0.f;
                if (ok) cnt += 1.f;
            }
            mbar_wait(mb + MB_OUT * 8);
        }
        if (cnt != 0.f) {
            float x, y, z, w;
            asm volatile("atom.relaxed.gpu.global.add.v4.f32 {%0,%1,%2,%3}, [%4], {%5,%6,%7,%8};" : "=f"(x), "=f"(y), "=f"(z), "=f"(w)
                         : "l"((char*)g_s.fin + fo), "f"(v[0]), "f"(v[1]), "f"(v[2]), "f"(cnt) : "memory");
            if (w + cnt == 3.f * (NCL + 1)) {
                __nv_bfloat16* op = (__nv_bfloat16*)((char*)prm.out + oo);
                op[0] = __float2bfloat16(x + v[0]); op[1] = __float2bfloat16(y + v[1]); op[2] = __float2bfloat16(z + v[2]);
            }
        }
    } else bar_arrive(6, 640);
    STAMP(15);
}

typedef CUresult (*EncodeFn)(CUtensorMap*, CUtensorMapDataType, cuuint32_t, void*, const cuuint64_t*, const cuuint64_t*,
                             const cuuint32_t*, const cuuint32_t*, CUtensorMapInterleave, CUtensorMapSwizzle,
                             CUtensorMapL2promotion, CUtensorMapFloatOOBfill);

void make_map(EncodeFn fn, CUtensorMap* tm, const void* p, int cols, int rows, int bc, int br) {
    cuuint64_t dims[2] = {(cuuint64_t)cols, (cuuint64_t)rows};
    cuuint64_t strides[1] = {(cuuint64_t)cols * 2};
    cuuint32_t box[2] = {(cuuint32_t)bc, (cuuint32_t)br};
    cuuint32_t es[2] = {1, 1};
    fn(tm, CU_TENSOR_MAP_DATA_TYPE_BFLOAT16, 2, const_cast<void*>(p), dims, strides, box, es, CU_TENSOR_MAP_INTERLEAVE_NONE,
       CU_TENSOR_MAP_SWIZZLE_NONE, (CUtensorMapL2promotion)L2PROMO, CU_TENSOR_MAP_FLOAT_OOB_FILL_NONE);
}

void make_map3(EncodeFn fn, CUtensorMap* tm, const void* p) {
    cuuint64_t dims[3] = {(cuuint64_t)D_, 64, 32};
    cuuint64_t strides[2] = {(cuuint64_t)D_ * 2, (cuuint64_t)D_ * 128};
    cuuint32_t box[3] = {40, 8, 32};
    cuuint32_t es[3] = {1, 1, 1};
    fn(tm, CU_TENSOR_MAP_DATA_TYPE_BFLOAT16, 3, const_cast<void*>(p), dims, strides, box, es, CU_TENSOR_MAP_INTERLEAVE_NONE,
       CU_TENSOR_MAP_SWIZZLE_NONE, CU_TENSOR_MAP_L2_PROMOTION_NONE, CU_TENSOR_MAP_FLOAT_OOB_FILL_NONE);
}

void make_map5(EncodeFn fn, CUtensorMap* tm, const void* p, int bc) {
    cuuint64_t dims[5] = {(cuuint64_t)D_, 2, 4, 4, 64};
    cuuint64_t strides[4] = {(cuuint64_t)D_ * 128, (cuuint64_t)D_ * 1024, (cuuint64_t)D_ * 256, (cuuint64_t)D_ * 2};
    cuuint32_t box[5] = {(cuuint32_t)bc, 2, 4, 4, 8};
    cuuint32_t es[5] = {1, 1, 1, 1, 1};
    fn(tm, CU_TENSOR_MAP_DATA_TYPE_BFLOAT16, 5, const_cast<void*>(p), dims, strides, box, es, CU_TENSOR_MAP_INTERLEAVE_NONE,
       CU_TENSOR_MAP_SWIZZLE_NONE, CU_TENSOR_MAP_L2_PROMOTION_NONE, CU_TENSOR_MAP_FLOAT_OOB_FILL_NONE);
}

}

extern "C" void kernel_launch(void* const* d_in, const int* in_sizes, int n_in, void* d_out, int out_size) {
    (void)in_sizes; (void)n_in; (void)out_size;
    void* fp = nullptr;
    cudaDriverEntryPointQueryResult qr;
    cudaGetDriverEntryPoint("cuTensorMapEncodeTiled", &fp, cudaEnableDefault, &qr);
    EncodeFn fn = (EncodeFn)fp;
    CUtensorMap tmG, tmU, tmD, tmO, tmX, tmH;
    make_map3(fn, &tmX, d_in[0]);
    make_map(fn, &tmG, d_in[11], F_, D_, 40, 48);
    make_map(fn, &tmU, d_in[12], F_, D_, 40, 48);
    make_map(fn, &tmD, d_in[13], D_, F_, 72, 64);
    make_map5(fn, &tmO, d_out, 32);
    make_map5(fn, &tmH, d_out, 8);
    Params p;
    p.x = (const unsigned short*)d_in[0];
    for (int i = 0; i < 6; i++) p.prm6[i] = (const unsigned short*)d_in[1 + i];
    p.logdt = (const unsigned short*)d_in[7]; p.dskip = (const unsigned short*)d_in[8];
    p.wr = (const unsigned short*)d_in[10];
    for (int i = 0; i < 3; i++) p.w3[i] = (const char*)d_in[11 + i];
    p.out = (__nv_bfloat16*)d_out;
    p.zero = 0;
    cudaGetSymbolAddress((void**)&p.gs, g_s);
    cudaFuncSetAttribute(fused_kernel, cudaFuncAttributeMaxDynamicSharedMemorySize, SM_TOTAL);
    fused_kernel<<<NCTA, NTHR, SM_TOTAL>>>(p, tmG, tmU, tmD, tmO, tmX, tmH);
}
```

```cpp
#include <cuda_runtime.h>
#include <cuda_bf16.h>
#include <cuda_fp16.h>
#include <cuda.h>
#include <stdint.h>

namespace {

constexpr int L_ = 2048, D_ = 576, F_ = 4608;
constexpr int NCL = 15, CS = 8, NCTA = NCL * CS, NTHR = 768;
#define PACE_NS 100
#define PRE_N 0
#define PRE_NS 200
#define FIN_DELAY 0
#define RED_DELAY 0
#define NO_OUT 0
#define XSPLIT 3
#define LNPOS 2
#define NMPOS 3
#define XWAIT -1
#define XWB 1
#define XROT 0
#define NBOX 24
#define NRED 2
#define HALF_AT 1
#define OUT_NS 0
#define PFMAP 2
#define PPOS 0
#define LNDYN 1
#define CFENCE 1
#define NEAR_DB 1
#define STREAM_T 0
#define L2PROMO 2
#define GAP_NS 0
#define ROW_DELAY 1
constexpr int SPIN_LIMIT = 1 << 22;

constexpr int SM_WG   = 0;
constexpr int SM_WU   = 46080;
constexpr int YP = 3376, YS = 672;
constexpr int UP = 3376, US = 672;
constexpr int SM_XT   = 92160;
constexpr int SM_U    = SM_XT + 8 * YP;
constexpr int SM_FAR  = SM_U + 8 * UP;
constexpr int FAR_SZ  = 12416;
constexpr int F_E5 = 0, F_O5 = 1536, F_E3 = 3088, F_O3 = 4624, F_E7 = 6176, F_E2 = F_E7 + 1024, F_E9 = F_E7 + 2048,
              F_H = 3088, F_O7 = F_E7 + F_H, F_O2 = F_E2 + F_H, F_O9 = F_E9 + F_H;
constexpr int SM_P    = SM_FAR + 5 * FAR_SZ;
constexpr int PN_SZ = 584 * 4, SM_PN = SM_P + 64 * 4;
constexpr int P_GS = 48 * 4, P_H7 = 192 * 4, P_HS = 72 * 4;
constexpr int PF_SZ = (192 + 216) * 4, SM_PF = SM_PN + 5 * PN_SZ + 32;
constexpr int SM_MISC = SM_PF + 5 * PF_SZ;
constexpr int SM_ST   = SM_MISC;
constexpr int SM_RK   = SM_ST + 2048;
constexpr int SM_SEL  = SM_RK + 256;
constexpr int SM_KG   = SM_SEL + 64;
constexpr int SM_SC   = SM_KG + 160;
constexpr int SM_DW   = SM_SC + 32;
constexpr int SM_MB   = SM_DW + 160;
constexpr int SM_TOTAL = SM_MB + 128;
constexpr int SM_ROW  = SM_XT - 20736;
constexpr int SM_XTL  = SM_ROW - 20480;
constexpr int SM_RED2 = SM_WG;
constexpr int SM_HT   = SM_P - 512;
constexpr int SM_KEY  = SM_FAR + 9216 + 128;
constexpr int SM_CAND = SM_KEY + 1024;
constexpr int SM_FIN  = SM_FAR + FAR_SZ + 9216 + 128;
constexpr int SM_HS   = SM_FIN + 2400;
constexpr int SM_XS   = SM_U;
constexpr int SM_GU   = SM_XS + 9344;
constexpr int SM_RED  = SM_GU + 5632;
static_assert(F_O9 + 1024 <= FAR_SZ && FAR_SZ % 128 == 0, "far overflow");
static_assert(SM_RED + 10240 <= SM_FAR && SM_HS + 128 <= SM_FAR + 2 * FAR_SZ && SM_HT + 20496 <= SM_MISC, "alias overflow");
static_assert(SM_TOTAL <= 232448, "smem overflow");
static_assert(SM_FAR % 128 == 0 && SM_XT % 128 == 0 && SM_XTL % 128 == 0 && SM_P % 16 == 0 && SM_MISC % 16 == 0 && SM_MB % 8 == 0 && SM_HS % 16 == 0, "align");

enum { MB_X = 0, MB_W1 = 5, MB_W2 = 6, MB_KEY = 7, MB_GU = 8, MB_Y = 9, MB_OUT = 10, MB_T = 11, MB_R = 12 };

struct __align__(128) Scratch {
    unsigned epoch, zcnt, pad[30];
    uint4  st1[L_ * 2];
    float4 acc[L_];
    uint4  cand[64 * NCL * 6];
    float4 fin[8 * 192 + 24];
};
__device__ Scratch g_s;
#define STAMP(i)

__device__ __forceinline__ uint32_t mapa(uint32_t a, uint32_t r) { uint32_t d; asm("mapa.shared::cluster.u32 %0, %1, %2;" : "=r"(d) : "r"(a), "r"(r)); return d; }
__device__ __forceinline__ void mbar_wait(uint32_t mb) {
    asm volatile("{ .reg .pred p, q; .reg .u32 n; mov.u32 n, 0;\n"
                 "W_%=: mbarrier.try_wait.parity.shared::cta.b64 p, [%0], 0; add.u32 n, n, 1; setp.lt.and.u32 q, n, 65536, !p; @q bra W_%=; }" :: "r"(mb) : "memory");
}
__device__ __forceinline__ void arm(uint32_t mb, uint32_t bytes) { asm volatile("mbarrier.arrive.expect_tx.shared::cta.b64 _, [%0], %1;" :: "r"(mb), "r"(bytes) : "memory"); }
__device__ __forceinline__ void bar_sync(int id, int n) { asm volatile("bar.sync %0, %1;" :: "r"(id), "r"(n) : "memory"); }
__device__ __forceinline__ void bar_arrive(int id, int n) { asm volatile("bar.arrive %0, %1;" :: "r"(id), "r"(n) : "memory"); }
__device__ __forceinline__ uint32_t lds16(uint32_t a) { unsigned short v; asm volatile("ld.shared.u16 %0, [%1];" : "=h"(v) : "r"(a) : "memory"); return v; }
__device__ __forceinline__ uint32_t lds32(uint32_t a) { uint32_t v; asm volatile("ld.shared.u32 %0, [%1];" : "=r"(v) : "r"(a) : "memory"); return v; }
__device__ __forceinline__ uint2 lds64(uint32_t a) { uint2 v; asm volatile("ld.shared.v2.u32 {%0,%1}, [%2];" : "=r"(v.x), "=r"(v.y) : "r"(a) : "memory"); return v; }
__device__ __forceinline__ float ldsf(uint32_t a) { float v; asm volatile("ld.shared.f32 %0, [%1];" : "=f"(v) : "r"(a) : "memory"); return v; }
__device__ __forceinline__ uint4 lds128(uint32_t a) { uint4 v; asm volatile("ld.shared.v4.u32 {%0,%1,%2,%3}, [%4];" : "=r"(v.x), "=r"(v.y), "=r"(v.z), "=r"(v.w) : "r"(a) : "memory"); return v; }
__device__ __forceinline__ float4 lds128f(uint32_t a) { float4 v; asm volatile("ld.shared.v4.f32 {%0,%1,%2,%3}, [%4];" : "=f"(v.x), "=f"(v.y), "=f"(v.z), "=f"(v.w) : "r"(a) : "memory"); return v; }
__device__ __forceinline__ void sts16(uint32_t a, uint32_t v) { asm volatile("{ .reg .b16 l, h; mov.b32 {l, h}, %1; st.shared.b16 [%0], l; }" :: "r"(a), "r"(v) : "memory"); }
__device__ __forceinline__ void sts32(uint32_t a, uint32_t v) { asm volatile("st.shared.u32 [%0], %1;" :: "r"(a), "r"(v) : "memory"); }
__device__ __forceinline__ void sts64(uint32_t a, uint32_t x, uint32_t y) { asm volatile("st.shared.v2.u32 [%0], {%1,%2};" :: "r"(a), "r"(x), "r"(y) : "memory"); }
__device__ __forceinline__ void stsf(uint32_t a, float v) { asm volatile("st.shared.f32 [%0], %1;" :: "r"(a), "f"(v) : "memory"); }
__device__ __forceinline__ void sts128(uint32_t a, uint32_t x, uint32_t y, uint32_t z, uint32_t w) { asm volatile("st.shared.v4.u32 [%0], {%1,%2,%3,%4};" :: "r"(a), "r"(x), "r"(y), "r"(z), "r"(w) : "memory"); }
__device__ __forceinline__ void sts128f(uint32_t a, float x, float y, float z, float w) { asm volatile("st.shared.v4.f32 [%0], {%1,%2,%3,%4};" :: "r"(a), "f"(x), "f"(y), "f"(z), "f"(w) : "memory"); }
__device__ __forceinline__ void ldsm4(uint32_t (&r)[4], uint32_t a) { asm volatile("ldmatrix.sync.aligned.m8n8.x4.shared.b16 {%0,%1,%2,%3}, [%4];" : "=r"(r[0]), "=r"(r[1]), "=r"(r[2]), "=r"(r[3]) : "r"(a) : "memory"); }
__device__ __forceinline__ void ldsm4t(uint32_t (&r)[4], uint32_t a) { asm volatile("ldmatrix.sync.aligned.m8n8.x4.trans.shared.b16 {%0,%1,%2,%3}, [%4];" : "=r"(r[0]), "=r"(r[1]), "=r"(r[2]), "=r"(r[3]) : "r"(a) : "memory"); }
__device__ __forceinline__ void ldsm2t(uint32_t& r0, uint32_t& r1, uint32_t a) { asm volatile("ldmatrix.sync.aligned.m8n8.x2.trans.shared.b16 {%0,%1}, [%2];" : "=r"(r0), "=r"(r1) : "r"(a) : "memory"); }
__device__ __forceinline__ void stsm4t(uint32_t a, uint32_t r0, uint32_t r1, uint32_t r2, uint32_t r3) { asm volatile("stmatrix.sync.aligned.m8n8.x4.trans.shared.b16 [%0], {%1,%2,%3,%4};" :: "r"(a), "r"(r0), "r"(r1), "r"(r2), "r"(r3) : "memory"); }
__device__ __forceinline__ void stsm4(uint32_t a, uint32_t r0, uint32_t r1, uint32_t r2, uint32_t r3) { asm volatile("stmatrix.sync.aligned.m8n8.x4.shared.b16 [%0], {%1,%2,%3,%4};" :: "r"(a), "r"(r0), "r"(r1), "r"(r2), "r"(r3) : "memory"); }
__device__ __forceinline__ void stsm2t(uint32_t a, uint32_t r0, uint32_t r1) { asm volatile("stmatrix.sync.aligned.m8n8.x2.trans.shared.b16 [%0], {%1,%2};" :: "r"(a), "r"(r0), "r"(r1) : "memory"); }
__device__ __forceinline__ uint4 ldg128(const void* p) { uint4 v; asm volatile("ld.global.nc.v4.u32 {%0,%1,%2,%3}, [%4];" : "=r"(v.x), "=r"(v.y), "=r"(v.z), "=r"(v.w) : "l"(p)); return v; }
__device__ __forceinline__ uint32_t ldg32(const void* p) { uint32_t v; asm volatile("ld.global.nc.u32 %0, [%1];" : "=r"(v) : "l"(p)); return v; }
__device__ __forceinline__ uint32_t ldg16(const void* p) { unsigned short v; asm volatile("ld.global.nc.u16 %0, [%1];" : "=h"(v) : "l"(p)); return v; }
__device__ __forceinline__ uint32_t opaque(uint32_t v) { uint32_t r; asm volatile("mov.b32 %0, %1;" : "=r"(r) : "r"(v)); return r; }
__device__ __forceinline__ void mma_f16(float (&d)[4], const uint32_t (&a)[4], uint32_t b0, uint32_t b1) {
    asm volatile("mma.sync.aligned.m16n8k16.row.col.f32.f16.f16.f32 {%0,%1,%2,%3}, {%4,%5,%6,%7}, {%8,%9}, {%0,%1,%2,%3};"
        : "+f"(d[0]), "+f"(d[1]), "+f"(d[2]), "+f"(d[3]) : "r"(a[0]), "r"(a[1]), "r"(a[2]), "r"(a[3]), "r"(b0), "r"(b1));
}
__device__ __forceinline__ void mma_bf16(float (&d)[4], uint32_t a0, uint32_t a1, uint32_t a2, uint32_t a3, uint32_t b0, uint32_t b1) {
    asm volatile("mma.sync.aligned.m16n8k16.row.col.f32.bf16.bf16.f32 {%0,%1,%2,%3}, {%4,%5,%6,%7}, {%8,%9}, {%0,%1,%2,%3};"
        : "+f"(d[0]), "+f"(d[1]), "+f"(d[2]), "+f"(d[3]) : "r"(a0), "r"(a1), "r"(a2), "r"(a3), "r"(b0), "r"(b1));
}
__device__ __forceinline__ void mma_bf16_k8(float (&d)[4], uint32_t a0, uint32_t a1, uint32_t b0) {
    asm volatile("mma.sync.aligned.m16n8k8.row.col.f32.bf16.bf16.f32 {%0,%1,%2,%3}, {%4,%5}, {%6}, {%0,%1,%2,%3};"
        : "+f"(d[0]), "+f"(d[1]), "+f"(d[2]), "+f"(d[3]) : "r"(a0), "r"(a1), "r"(b0));
}
__device__ __forceinline__ uint32_t pack_f16(float lo, float hi) { uint32_t r; asm("cvt.rn.f16x2.f32 %0, %1, %2;" : "=r"(r) : "f"(hi), "f"(lo)); return r; }
__device__ __forceinline__ uint32_t pack_bf16(float lo, float hi) { uint32_t r; asm("cvt.rn.bf16x2.f32 %0, %1, %2;" : "=r"(r) : "f"(hi), "f"(lo)); return r; }
__device__ __forceinline__ float bf_lo(uint32_t v) { return __uint_as_float(v << 16); }
__device__ __forceinline__ float bf_hi(uint32_t v) { return __uint_as_float(v & 0xFFFF0000u); }
__device__ __forceinline__ float bfr(float x) { return __uint_as_float(pack_bf16(0.f, x)); }
__device__ __forceinline__ uint32_t bsub2(uint32_t a, uint32_t b) { uint32_t r; asm("sub.rn.bf16x2 %0, %1, %2;" : "=r"(r) : "r"(a), "r"(b)); return r; }
__device__ __forceinline__ uint32_t badd2(uint32_t a, uint32_t b) { uint32_t r; asm("add.rn.bf16x2 %0, %1, %2;" : "=r"(r) : "r"(a), "r"(b)); return r; }
__device__ __forceinline__ uint32_t bmul2(uint32_t a, uint32_t b) { uint32_t r; asm("mul.rn.bf16x2 %0, %1, %2;" : "=r"(r) : "r"(a), "r"(b)); return r; }
__device__ __forceinline__ uint32_t bfma2(uint32_t a, uint32_t b, uint32_t c) { uint32_t r; asm("fma.rn.bf16x2 %0, %1, %2, %3;" : "=r"(r) : "r"(a), "r"(b), "r"(c)); return r; }
__device__ __forceinline__ uint32_t hadd2(uint32_t a, uint32_t b) { uint32_t r; asm("add.rn.f16x2 %0, %1, %2;" : "=r"(r) : "r"(a), "r"(b)); return r; }
__device__ __forceinline__ uint32_t hmul2(uint32_t a, uint32_t b) { uint32_t r; asm("mul.rn.f16x2 %0, %1, %2;" : "=r"(r) : "r"(a), "r"(b)); return r; }
__device__ __forceinline__ uint32_t hfma2(uint32_t a, uint32_t b, uint32_t c) { uint32_t r; asm("fma.rn.f16x2 %0, %1, %2, %3;" : "=r"(r) : "r"(a), "r"(b), "r"(c)); return r; }
__device__ __forceinline__ uint32_t hneg2(uint32_t a) { uint32_t r; asm("neg.f16x2 %0, %1;" : "=r"(r) : "r"(a)); return r; }
__device__ __forceinline__ float rcpf(float x) { float r; asm("rcp.approx.ftz.f32 %0, %1;" : "=f"(r) : "f"(x)); return r; }
__device__ __forceinline__ float sqrta(float x) { float r; asm("sqrt.approx.ftz.f32 %0, %1;" : "=f"(r) : "f"(x)); return r; }
__device__ __forceinline__ float ex2f(float x) { float r; asm("ex2.approx.ftz.f32 %0, %1;" : "=f"(r) : "f"(x)); return r; }
__device__ __forceinline__ void st_async4(uint32_t a, uint32_t x, uint32_t y, uint32_t z, uint32_t w, uint32_t mb) {
    asm volatile("st.async.shared::cluster.mbarrier::complete_tx::bytes.v4.u32 [%0], {%1,%2,%3,%4}, [%5];" :: "r"(a), "r"(x), "r"(y), "r"(z), "r"(w), "r"(mb) : "memory"); }
__device__ __forceinline__ void st_async1(uint32_t a, uint32_t x, uint32_t mb) {
    asm volatile("st.async.shared::cluster.mbarrier::complete_tx::bytes.u32 [%0], %1, [%2];" :: "r"(a), "r"(x), "r"(mb) : "memory"); }
__device__ __forceinline__ unsigned ld_rlx(const void* p) { unsigned v; asm volatile("ld.relaxed.gpu.global.u32 %0, [%1];" : "=r"(v) : "l"(p) : "memory"); return v; }
__device__ __forceinline__ unsigned ld_acq(const void* p) { unsigned v; asm volatile("ld.acquire.gpu.global.u32 %0, [%1];" : "=r"(v) : "l"(p) : "memory"); return v; }
__device__ __forceinline__ uint2 ld_rlx64(const void* p) { unsigned long long v; asm volatile("ld.relaxed.gpu.global.u64 %0, [%1];" : "=l"(v) : "l"(p) : "memory"); return make_uint2((unsigned)v, (unsigned)(v >> 32)); }
__device__ __forceinline__ void st_rlx64(void* p, unsigned lo, unsigned hi) { asm volatile("st.relaxed.gpu.global.u64 [%0], %1;" :: "l"(p), "l"((unsigned long long)lo | ((unsigned long long)hi << 32)) : "memory"); }
__device__ __forceinline__ void st_rlx128(void* p, uint32_t x, uint32_t y, uint32_t z, uint32_t w) {
    asm volatile("st.relaxed.gpu.global.v2.u64 [%0], {%1,%2};" :: "l"(p), "l"((unsigned long long)x | ((unsigned long long)y << 32)), "l"((unsigned long long)z | ((unsigned long long)w << 32)) : "memory"); }
__device__ __forceinline__ uint4 ld_rlx128(const void* p) { unsigned long long a, b; asm volatile("ld.relaxed.gpu.global.v2.u64 {%0,%1}, [%2];" : "=l"(a), "=l"(b) : "l"(p) : "memory"); return make_uint4((unsigned)a, (unsigned)(a >> 32), (unsigned)b, (unsigned)(b >> 32)); }
__device__ __forceinline__ void tma2d(uint32_t dst, const CUtensorMap* tm, int x, int y, uint32_t mb) {
    asm volatile("cp.async.bulk.tensor.2d.shared::cluster.global.mbarrier::complete_tx::bytes [%0], [%1, {%3, %4}], [%2];"
                 :: "r"(dst), "l"(tm), "r"(mb), "r"(x), "r"(y) : "memory");
}
__device__ __forceinline__ void cmul(float& xr, float& xi, float ar, float ai, float br, float bi) {
    const float r = fmaf(ar, br, -ai * bi), i = fmaf(ar, bi, ai * br); xr = r; xi = i;
}
__device__ __forceinline__ void csq(float& xr, float& xi, float ar, float ai) {
    const float r = fmaf(ar, ar, -ai * ai), i = (ar + ar) * ai; xr = r; xi = i;
}
__device__ __forceinline__ void cexp_s(float& zr, float& zi, float e2, float turns) {
    const float mag = ex2f(e2), r = (turns - rintf(turns)) * 6.283185307179586f;
    zr = mag * __cosf(r); zi = mag * __sinf(r);
}
__device__ __forceinline__ uint32_t ln_stats(float s1, float s2) {
    const float m = s1 * (1.f / D_);
    const float var = fmaxf(fmaf(s2, 1.f / D_, -m * m), 0.f);
    return pack_bf16(m, sqrta(bfr(bfr(var) + 1e-5f)));
}
__device__ __forceinline__ uint32_t rsplit(float rs) { const float h = bfr(rs); return pack_bf16(h, rs - h); }
__device__ __forceinline__ uint32_t norm2(uint32_t v, uint32_t m2, uint32_t rh2, uint32_t rl2) {
    const uint32_t dd = bsub2(v, m2);
    return bfma2(dd, rh2, bmul2(dd, rl2));
}
template <int N>
__device__ __forceinline__ uint32_t rank4(uint32_t a, uint32_t key) {
    uint32_t r0 = 0, r1 = 0, r2 = 0, r3 = 0;
#pragma unroll
    for (int i = 0; i < N; i++) {
        const uint4 o = lds128(a + i * 16);
        r0 += (key - o.x) >> 31; r1 += (key - o.y) >> 31; r2 += (key - o.z) >> 31; r3 += (key - o.w) >> 31;
    }
    return (r0 + r1) + (r2 + r3);
}
struct H2C { uint32_t r, i; };
__device__ __forceinline__ H2C splat(float r, float i) { H2C h; h.r = pack_f16(r, r); h.i = pack_f16(i, i); return h; }
__device__ __forceinline__ void expand4(uint32_t are, uint32_t aim, uint32_t R0, uint32_t R1, uint32_t I0, uint32_t I1, H2C m4) {
    sts128(are, R0, R1, hfma2(R0, m4.r, hneg2(hmul2(I0, m4.i))), hfma2(R1, m4.r, hneg2(hmul2(I1, m4.i))));
    sts128(aim, I0, I1, hfma2(R0, m4.i, hmul2(I0, m4.r)), hfma2(R1, m4.i, hmul2(I1, m4.r)));
}
__device__ __forceinline__ void expand8(uint32_t are, uint32_t aim, float sr, float si, float m1r, float m1i, float m2r, float m2i, H2C m4) {
    float r1, i1, r2, i2, r3, i3;
    cmul(r1, i1, sr, si, m1r, m1i); cmul(r2, i2, sr, si, m2r, m2i); cmul(r3, i3, r1, i1, m2r, m2i);
    expand4(are, aim, pack_f16(sr, r1), pack_f16(r2, r3), pack_f16(si, i1), pack_f16(i2, i3), m4);
}
__device__ __forceinline__ void put16(uint32_t a, uint32_t v) { sts16(a, v); sts16(a + 6, v); }

struct Params {
    const unsigned short *x, *prm6[6], *logdt, *dskip, *wr;
    const char* w3[3];
    __nv_bfloat16* out;
    Scratch* gs;
    unsigned zero;
};
__device__ __forceinline__ uint32_t tslot(uint32_t t) { return (t & 7) * 32 + ((t >> 4) & 24) + ((t >> 8) & 6) + ((t >> 6) & 1); }
#define CP(x) ((x) | zero)
#define PIN(x) asm volatile("or.b32 %0, %0, %1;" : "+r"(x) : "r"(zero))
__device__ __forceinline__ void wgmma32(float (&d)[4][4], const uint32_t (&a)[4], uint32_t dlo) {
    asm volatile("{ .reg .b64 ds; mov.b64 ds, {%20, %21};\n"
                 "wgmma.mma_async.sync.aligned.m64n32k16.f32.f16.f16 {%0,%1,%2,%3,%4,%5,%6,%7,%8,%9,%10,%11,%12,%13,%14,%15}, {%16,%17,%18,%19}, ds, 1, 1, 1, 0; }"
        : "+f"(d[0][0]), "+f"(d[0][1]), "+f"(d[0][2]), "+f"(d[0][3]), "+f"(d[1][0]), "+f"(d[1][1]), "+f"(d[1][2]), "+f"(d[1][3]),
          "+f"(d[2][0]), "+f"(d[2][1]), "+f"(d[2][2]), "+f"(d[2][3]), "+f"(d[3][0]), "+f"(d[3][1]), "+f"(d[3][2]), "+f"(d[3][3])
        : "r"(a[0]), "r"(a[1]), "r"(a[2]), "r"(a[3]), "r"(dlo), "n"(128 >> 4));
}

__global__ void __cluster_dims__(CS, 1, 1) __launch_bounds__(NTHR, 1)
fused_kernel(const __grid_constant__ Params prm, const __grid_constant__ CUtensorMap tmG, const __grid_constant__ CUtensorMap tmU,
             const __grid_constant__ CUtensorMap tmD, const __grid_constant__ CUtensorMap tmO, const __grid_constant__ CUtensorMap tmX, const __grid_constant__ CUtensorMap tmH)
{
    extern __shared__ __align__(1024) unsigned char smem[];
    const int tid = threadIdx.x, lane = tid & 31, warp = __shfl_sync(~0u, tid >> 5, 0);
    const int c = blockIdx.x >> 3, q = blockIdx.x & 7;
    const int nslot = (c < NCL - 1) ? 5 : 2;
    const int d0 = 40 * c;
    const uint32_t sb = opaque((uint32_t)__cvta_generic_to_shared(smem));
    const uint32_t mb = sb + SM_MB;
    Scratch& g_s = *prm.gs;
    const unsigned& zero = prm.zero;
    STAMP(0);

    if (warp >= 20) {
        unsigned epoch = 0;
        if (warp == 20) {
            if (lane == 0) {
#pragma unroll
                for (int i = 0; i < 13; i++)
                    asm volatile("mbarrier.init.shared::cta.b64 [%0], %1;" :: "r"(mb + i * 8), "r"((i == MB_R || i == MB_T) ? 2 : i == MB_Y ? 1 + 4 * nslot : 1) : "memory");
                asm volatile("fence.mbarrier_init.release.cluster;" ::: "memory");
                arm(mb + MB_W1 * 8, NBOX * 3840); arm(mb + MB_W2 * 8, nslot * 9216); arm(mb + MB_KEY * 8, 256); arm(mb + MB_GU * 8, nslot * 1024); arm(mb + MB_T * 8, 20480);
                const int bytes = max(min(18, L_ - 18 * (int)blockIdx.x), 1) * (D_ * 2);
                arm(mb + MB_R * 8, bytes);
                if (!ROW_DELAY) asm volatile("cp.async.bulk.shared::cluster.global.mbarrier::complete_tx::bytes [%0], [%1], %2, [%3];"
                             :: "r"(sb + SM_ROW), "l"(prm.x + min(18 * (int)blockIdx.x, L_ - 1) * D_), "r"(bytes), "r"(mb + MB_R * 8) : "memory");
            }
            __syncwarp();
        } else if (warp == 22) {
            epoch = ld_rlx(&g_s.epoch);
            if (lane < 18 ? 18 * c + lane < 256 : lane < 31) (lane < 18 ? &g_s.acc[256 * q + 18 * c] : &g_s.fin[13 * (int)blockIdx.x - 18])[lane] = make_float4(0.f, 0.f, 0.f, 0.f);
        } else if (warp == 23 && lane == 0) asm volatile("prefetch.tensormap [%0];" :: "l"(&tmX) : "memory");
        asm volatile("barrier.cluster.arrive.relaxed.aligned;" ::: "memory");
        bar_sync(12, NTHR);
        if (warp == 22) {
            if (lane == 0) { sts32(sb + SM_SC + 28, epoch); asm volatile("mbarrier.arrive.shared::cta.b64 _, [%0];" :: "r"(mb + MB_R * 8) : "memory"); }
            epoch++;
            asm volatile("fence.acq_rel.gpu;" ::: "memory");
            __syncwarp();
            if (lane == 0) asm volatile("red.relaxed.gpu.global.add.u32 [%0], 1;" :: "l"(&g_s.zcnt) : "memory");
            STAMP(1);
            uint4 wv = make_uint4(0, 0, 0, 0), wv2 = ldg128((const uint4*)prm.wr + lane), wv3 = ldg128((const uint4*)prm.wr + 32 + lane);
            if (lane < 8) wv = ldg128((const uint4*)prm.wr + 64 + lane);
            if (lane < 5) {
                uint4 v = make_uint4(0, 0, 0, 0);
                if (lane < nslot) v = ldg128((const uint4*)(prm.wr + d0) + lane);
                sts128(sb + SM_DW + lane * 16, v.x, v.y, v.z, v.w);
            }
            __syncwarp();
            if (lane == 0) asm volatile("mbarrier.arrive.shared::cta.b64 _, [%0];" :: "r"(mb + MB_T * 8) : "memory");
            mbar_wait(mb + (MB_X + 1) * 8);
            const uint32_t old = (epoch & 1) ? 0u : 0x40004000u;
#pragma unroll
            for (int t = 0; t < 2; t++)
                if ((lane & 7) < 6) g_s.cand[((q * 8 + 4 * t + (lane >> 3)) * NCL + c) * 6 + (lane & 7)] = make_uint4(old, old, old, old);
            float a[4] = {0.f, 0.f, 0.f, 0.f};
            const uint32_t one = 0x3F803F80u;
            mma_bf16(a, one, one, one, one, wv.x, wv.y);  mma_bf16(a, one, one, one, one, wv.z, wv.w);
            mma_bf16(a, one, one, one, one, wv2.x, wv2.y); mma_bf16(a, one, one, one, one, wv2.z, wv2.w);
            mma_bf16(a, one, one, one, one, wv3.x, wv3.y); mma_bf16(a, one, one, one, one, wv3.z, wv3.w);
            float s = a[0] + a[1];
            s += __shfl_xor_sync(~0u, s, 1); s += __shfl_xor_sync(~0u, s, 2);
            stsf(sb + SM_SC + 24, s);
            __syncwarp();
            if (lane == 0) {
                int n = 0;
                while ((int)(ld_acq(&g_s.zcnt) - epoch * NCTA) < 0 && ++n < SPIN_LIMIT) __nanosleep(200);
                arm(mb + MB_Y * 8, 8 * 512 * nslot);
                if (blockIdx.x == 0) g_s.epoch = epoch;
            }
            STAMP(2);
            return;
        }
        if (warp == 21) {
            if (PFMAP > 1 && lane == 0) { asm volatile("prefetch.tensormap [%0];" :: "l"(&tmG) : "memory"); asm volatile("prefetch.tensormap [%0];" :: "l"(&tmU) : "memory"); asm volatile("prefetch.tensormap [%0];" :: "l"(&tmD) : "memory"); }
            __syncwarp();
            if (STREAM_T) { bar_arrive(13, 736); mbar_wait(mb + MB_T * 8); } else bar_sync(13, 736);
            if (GAP_NS) __nanosleep(GAP_NS);
#pragma unroll 1
            for (int i = 24 - NBOX; i < 24; i++) {
                if (i == XWAIT) mbar_wait(mb + (MB_X + XWB) * 8);
                if (i == 13) { bar_sync(15, 544); asm volatile("fence.proxy.async.shared::cta;" ::: "memory"); }
                if (lane == 0) tma2d(sb + SM_WG + i * 3840, i < 12 ? &tmG : &tmU, 320 * c + 8 * nslot * q, 48 * (i < 12 ? i : i - 12), mb + MB_W1 * 8);
                __nanosleep(PACE_NS);
            }
            STAMP(1);
            return;
        }
        if (warp == 20) {
            if (ROW_DELAY && lane == 0) {
                const long long t0 = clock64(); while (clock64() - t0 < ROW_DELAY) {}
                asm volatile("cp.async.bulk.shared::cluster.global.mbarrier::complete_tx::bytes [%0], [%1], %2, [%3];"
                             :: "r"(sb + SM_ROW), "l"(prm.x + min(18 * (int)blockIdx.x, L_ - 1) * D_), "r"(max(min(18, L_ - 18 * (int)blockIdx.x), 1) * (D_ * 2)), "r"(mb + MB_R * 8) : "memory");
            }
            __syncwarp();
            mbar_wait(mb + MB_R * 8);
            if (lane == 0) {
                asm volatile("cp.async.bulk.tensor.3d.shared::cluster.global.mbarrier::complete_tx::bytes [%0], [%1, {%3, %4, %5}], [%2];"
                             :: "r"(sb + SM_XTL), "l"(&tmX), "r"(mb + MB_T * 8), "r"(d0), "r"(8 * q), "r"(0) : "memory");
            }
            STAMP(6);
        }
        if (PRE_N && warp == 23) {
            mbar_wait(mb + MB_R * 8);
            const char* wp = prm.w3[0] + blockIdx.x * (PRE_N * 4096) + lane * 128;
#pragma unroll 1
            for (int i = 0; i < PRE_N; i++) { asm volatile("prefetch.global.L2 [%0];" :: "l"(wp + i * 4096) : "memory"); __nanosleep(PRE_NS); }
        }
        asm volatile("barrier.cluster.wait.aligned;" ::: "memory");
        bar_sync(13, 736);
        if (CFENCE) asm volatile("fence.proxy.async.shared::cta;" ::: "memory");
        {
            const int gr = lane >> 2, pe = ((lane & 3) * 2 + (warp & 1) + XROT * (q + 1)) & 7;
            const int s0 = gr ? 0 : XSPLIT, ns = gr ? min(XSPLIT, nslot) : nslot - XSPLIT;
            if (gr < 2 && ns > 0) {
                const int bytes = ns * YS - 160;
                if (pe == q) arm(mb + (MB_X + gr) * 8, 7 * bytes);
                else {
                    const uint32_t rb_ = mapa(sb, pe);
                    asm volatile("cp.async.bulk.shared::cluster.shared::cta.mbarrier::complete_tx::bytes [%0], [%1], %2, [%3];"
                                 :: "r"(rb_ + SM_U + 128 + q * UP + s0 * US), "r"(sb + SM_XT + 128 + pe * YP + s0 * YS), "r"(bytes), "r"(rb_ + SM_MB + (MB_X + gr) * 8) : "memory");
                }
            }
        }
        STAMP(1);
        if (PFMAP && warp == 20 && lane == 0) { asm volatile("prefetch.tensormap [%0];" :: "l"(&tmO) : "memory"); asm volatile("prefetch.tensormap [%0];" :: "l"(&tmH) : "memory"); }
        if (warp == 23) {
#pragma unroll 1
            for (int kk = nslot - 1; kk >= 0; kk--) {
                __syncwarp();
                bar_sync(6 + kk, 160);
                if (lane == 0) { asm volatile("fence.proxy.async.shared::cta;" ::: "memory"); tma2d(sb + SM_FAR + kk * FAR_SZ, &tmD, 72 * q, 320 * c + 64 * kk, mb + MB_W2 * 8); }
            }
            return;
        }
        __syncwarp();
        if (HALF_AT == 0) bar_sync(13, 544);
        if (HALF_AT == 1) bar_sync(14, 672);
        if (HALF_AT == 2) { bar_sync(11, 672); if (OUT_NS) __nanosleep(OUT_NS); }
        if (lane == 0) {
            asm volatile("fence.proxy.async.shared::cta;" ::: "memory");
            asm volatile("cp.async.bulk.tensor.5d.global.shared::cta.bulk_group [%0, {%2, %4, %4, %4, %3}], [%1];" :: "l"(&tmH), "r"(sb + SM_XT + 16384), "r"(d0 + ((c & 1) ? 0 : 32)), "r"(8 * q), "r"(0) : "memory");
        }
        __syncwarp();
        if (HALF_AT != 1) bar_sync(14, 672);
        if (lane == 0) {
            asm volatile("cp.async.bulk.tensor.5d.global.shared::cta.bulk_group [%0, {%2, %4, %4, %4, %3}], [%1];" :: "l"(&tmO), "r"(sb + SM_XT), "r"(d0 + (c & 1) * 8), "r"(8 * q), "r"(0) : "memory");
            asm volatile("cp.async.bulk.commit_group;" ::: "memory");
            asm volatile("cp.async.bulk.wait_group 0;" ::: "memory");
            asm volatile("fence.proxy.async.global;" ::: "memory");
            asm volatile("mbarrier.arrive.shared::cta.b64 _, [%0];" :: "r"(mb + MB_OUT * 8) : "memory");
        }
        STAMP(2);
        return;
    }

    const int g = lane >> 2, cq = lane & 3;
    const int k = warp >> 2, wq = warp & 3;
    const int trow = 18 * blockIdx.x + warp;
    const bool rowact = warp < 18 && trow < L_;
    const int dch = min(d0 + 8 * k + q, D_ - 1);
    uint32_t pv[6];
#pragma unroll
    for (int i = 0; i < 6; i++) pv[i] = ldg16(prm.prm6[i] + (uint32_t)(dch * 128 + wq * 32 + lane));
    const uint32_t pLdt = ldg16(prm.logdt + dch), pD = ldg16(prm.dskip + dch);
    const int tn = 16 * (warp & 15) + g;
    uint32_t xa[5], xb[5];
    asm volatile("barrier.cluster.arrive.relaxed.aligned;" ::: "memory");
    uint4* const st1p = &g_s.st1[(((trow >> 3) & 7) * 256 + ((trow >> 6) & 31) * 8 + (trow & 7)) * 2 + (lane >> 2)];
    const bool pub = rowact && (lane & 0x1B) == 0;
    if (pub) st_rlx128(st1p, 0, 0, 0, 0);
    {
        const uint32_t za = sb + SM_P + tid * 16;
        sts128(za, 0, 0, 0, 0);
        if (tid < (SM_MISC - SM_P) / 16 - 640) sts128(za + 10240, 0, 0, 0, 0);
        sts128(sb + SM_XT + ((tid >> 3) & 15) * YP + k * YS + (lane & 7) * 16, 0, 0, 0, 0);
    }
    bar_sync(12, NTHR);
    const uint32_t dep = lds32(sb + SM_P);
#define PV(x) __uint_as_float(__byte_perm(dep, x, 0x5410))
    STAMP(1);
    const uint32_t fb = sb + SM_FAR + k * FAR_SZ;
    const uint32_t pn = sb + SM_PN + k * PN_SZ, pf = sb + SM_PF + k * PF_SZ;
    unsigned epoch;
    {
        const uint32_t kb = fb + wq * 3072;
        const uint32_t kl = kb + lane * 16;
        uint32_t Af[4][4];
        float sr, si, z1r, z1i, z2r, z2i, z4r, z4i, hr, hi_;
        {
            const float dt = bfr(ex2f(PV(pLdt) * 1.4426950408889634f));
            const float e2 = dt * PV(pv[0]) * 1.4426950408889634f, an = dt * PV(pv[1]);
            cmul(sr, si, PV(pv[4]), PV(pv[5]), dt * PV(pv[2]), dt * PV(pv[3]));
            const unsigned E = min(max(__reduce_max_sync(~0u, __float_as_uint(fmaxf(fmaxf(fabsf(sr), fabsf(si)), fabsf(PV(pD)) * (1.f / 8192.f)))) >> 23, 1u), 253u);
            const float sc = __uint_as_float((254u - E) << 23);
            sr *= sc; si *= -sc;
            sts64(sb + SM_KG + warp * 8, E, __reduce_add_sync(~0u, __float2int_rn(sr * 16777216.f)));
            float ar, ai, br, bi, cr, ci, dr, di;
            { const float m = ex2f(e2 * 8.f); ar = m * __cosf(an * 8.f); ai = m * __sinf(an * 8.f); }
            csq(br, bi, ar, ai); csq(cr, ci, br, bi); csq(dr, di, cr, ci);
            const H2C m4 = splat(cr, ci);
            {
                float r3, i3;
                cmul(r3, i3, ar, ai, br, bi);
                expand4(kl, kl + 1024, pack_f16(1.f, ar), pack_f16(br, r3), pack_f16(0.f, ai), pack_f16(bi, i3), m4);
            }
            expand8(kl + 512, kl + 1536, dr, di, ar, ai, br, bi, m4);
            { const float m = ex2f(e2); z1r = m * __cosf(an); z1i = -m * __sinf(an); }
            cexp_s(hr, hi_, e2 * 128.f, an * (-128.f * 0.15915494309189535f));
            csq(z2r, z2i, z1r, z1i); csq(z4r, z4i, z2r, z2i);
        }
        __syncwarp();
#pragma unroll
        for (int ks = 0; ks < 4; ks++) ldsm4t(Af[ks], kb + (lane >> 3) * 512 + (lane & 7) * 16 + ks * 128);
        STAMP(2);
        const uint32_t la = kb + ((lane >> 3) & 1) * 512 + (lane >> 4) * 128 + (lane & 7) * 16;
        uint32_t kp[5][2], b0[4], b1[4], b2[4], b3[4];
        auto mm2 = [&](int t) {
            float a0[4] = {0.f, 0.f, 0.f, 0.f}, a1[4] = {0.f, 0.f, 0.f, 0.f};
            mma_f16(a0, Af[0], b0[0], b0[1]); mma_f16(a1, Af[0], b2[0], b2[1]); mma_f16(a0, Af[1], b0[2], b0[3]); mma_f16(a1, Af[1], b2[2], b2[3]);
            mma_f16(a0, Af[2], b1[0], b1[1]); mma_f16(a1, Af[2], b3[0], b3[1]); mma_f16(a0, Af[3], b1[2], b1[3]); mma_f16(a1, Af[3], b3[2], b3[3]);
            kp[t][0] = pack_f16(a0[1], a0[0]); kp[t][1] = pack_f16(a0[3], a0[2]); kp[t + 1][0] = pack_f16(a1[1], a1[0]); kp[t + 1][1] = pack_f16(a1[3], a1[2]);
        };
        auto ln1 = [&]() {
        mbar_wait(mb + MB_R * 8);
        epoch = lds32(sb + SM_SC + 28) + 1;
        {
            float a[4] = {0.f, 0.f, 0.f, 0.f}, b[4] = {0.f, 0.f, 0.f, 0.f};
            uint32_t rx[9];
#pragma unroll
            for (int i = 0; i < 9; i++) rx[i] = lds32(sb + SM_ROW + warp * (D_ * 2) + lane * 4 + i * 128);
#pragma unroll
            for (int i = 0; i < 9; i++) { if (i & 1) mma_bf16_k8(b, rx[i], 0x3F803F80u, rx[i]); else mma_bf16_k8(a, rx[i], 0x3F803F80u, rx[i]); }
            float s2 = (g & 1) ? a[1] + b[1] : a[0] + b[0], s1 = (a[2] + b[2]) + (a[3] + b[3]);
            s2 += __shfl_xor_sync(~0u, s2, 4); s1 += __shfl_xor_sync(~0u, s1, 1);
            s2 += __shfl_xor_sync(~0u, s2, 9); s1 += __shfl_xor_sync(~0u, s1, 2);
            s2 += __shfl_xor_sync(~0u, s2, 18);
            const uint32_t ms = ln_stats(s1, s2);
            if (pub) st_rlx128(st1p, ms, epoch, ms, epoch);
        }
        mbar_wait(mb + MB_R * 8);
        };
        const uint4* sp = &g_s.st1[(256 * q + tn) * 2];
        uint2 sa, sc;
        auto poll = [&]() { if (warp < 16) { sa = ld_rlx64(sp); sc = ld_rlx64(sp + 16); } };
        auto norm = [&]() {
        STAMP(3);
        if (warp < 16) {
            uint32_t va[5], vc[5];
            if (PPOS == 0) poll();
            mbar_wait(mb + MB_T * 8);
            {
                const uint32_t xt = sb + SM_XTL + tn * 80;
                uint4 a4 = lds128(xt + cq * 16), b4 = lds128(xt + cq * 16 + 640);
                va[0] = a4.x; va[1] = a4.y; va[2] = a4.z; va[3] = a4.w; va[4] = lds32(xt + 64 + cq * 4);
                vc[0] = b4.x; vc[1] = b4.y; vc[2] = b4.z; vc[3] = b4.w; vc[4] = lds32(xt + 704 + cq * 4);
            }
            int n = 0;
            while ((sa.y != epoch || sc.y != epoch) && ++n < SPIN_LIMIT) poll();
            STAMP(4);
            const uint32_t ra = rsplit(rcpf(bf_hi(sa.x))), rc = rsplit(rcpf(bf_hi(sc.x)));
            const uint32_t ma = __byte_perm(sa.x, 0, 0x1010), mc = __byte_perm(sc.x, 0, 0x1010);
            const uint32_t rha = __byte_perm(ra, 0, 0x1010), rla = __byte_perm(ra, 0, 0x3232), rhc = __byte_perm(rc, 0, 0x1010), rlc = __byte_perm(rc, 0, 0x3232);
#pragma unroll
            for (int i = 0; i < 5; i++) {
                va[i] = norm2(va[i], ma, rha, rla); va[i] = pack_f16(bf_lo(va[i]), bf_hi(va[i]));
                vc[i] = norm2(vc[i], mc, rhc, rlc); vc[i] = pack_f16(bf_lo(vc[i]), bf_hi(vc[i]));
            }
            const int d4 = 2 * (lane >> 3) + (lane & 1), d1_ = lane & 7;
            const uint32_t a4 = sb + warp * 32 + d4 * YP + (d4 == q ? SM_U + 128 : SM_XT + 128) + ((lane & 7) >> 1) * YS;
            const uint32_t a1 = sb + warp * 32 + d1_ * YP + (d1_ == q ? SM_U + 128 : SM_XT + 128) + 4 * YS + (lane & 8) * 2;
            stsm4t(a4, va[0], va[1], va[2], va[3]); stsm4t(a4 + 16, vc[0], vc[1], vc[2], vc[3]); stsm2t(a1, va[4], vc[4]);
        }
        if (!CFENCE) asm volatile("fence.proxy.async.shared::cta;" ::: "memory");
        bar_arrive(13, 736);
        if (warp < 16) {
            const uint32_t xh = sb + SM_XTL + (64 * (g >> 1) + 32 * (warp & 1) + 8 * (g & 1) + (warp >> 1)) * 80;
            const uint4 a4 = lds128(xh + cq * 16), b4 = lds128(xh + cq * 16 + 1280);
            xa[0] = a4.x; xa[1] = a4.y; xa[2] = a4.z; xa[3] = a4.w; xa[4] = lds32(xh + 64 + cq * 4);
            xb[0] = b4.x; xb[1] = b4.y; xb[2] = b4.z; xb[3] = b4.w; xb[4] = lds32(xh + 1344 + cq * 4);
            bar_arrive(15, 544);
        }
        STAMP(5);
        };
        uint32_t rdy = 0;
        if (LNDYN == 1) {
            asm volatile("{ .reg .pred p; mbarrier.test_wait.parity.shared::cta.b64 p, [%1], 0; selp.u32 %0, 1, 0, p; }" : "=r"(rdy) : "r"(mb + MB_R * 8) : "memory");
            rdy = __all_sync(~0u, rdy);
            if (rdy) ln1();
        }
        if (LNPOS == 0) ln1();
        cmul(sr, si, sr, si, z1r, z1i);
        {
            const H2C h4 = splat(z4r, z4i);
            expand8(kl, kl + 512, sr, si, z1r, z1i, z2r, z2i, h4);
            cmul(sr, si, sr, si, hr, hi_);
            expand8(kl + 1024, kl + 1536, sr, si, z1r, z1i, z2r, z2i, h4);
        }
        __syncwarp();
        ldsm4t(b0, la); ldsm4t(b1, la + 256); ldsm4t(b2, la + 1024); ldsm4t(b3, la + 1280);
        cmul(z1r, z1i, z1r, z1i, hr, hi_);
        cmul(sr, si, sr, si, z1r, z1i);
        if (LNDYN == 2) {
            asm volatile("{ .reg .pred p; mbarrier.test_wait.parity.shared::cta.b64 p, [%1], 0; selp.u32 %0, 1, 0, p; }" : "=r"(rdy) : "r"(mb + MB_R * 8) : "memory");
            rdy = __all_sync(~0u, rdy);
            if (rdy) ln1();
        }
        if (LNPOS == 1) ln1();
        expand8(kl, kl + 512, sr, si, z2r, z2i, z4r, z4i, splat(hr, hi_));
        mm2(0);
        if (LNPOS == 2 && !rdy) ln1();
        if (NMPOS == 2) norm();
        csq(z1r, z1i, z1r, z1i);
        cmul(sr, si, sr, si, z1r, z1i);
        csq(z2r, z2i, hr, hi_);
        expand8(kl + 1024, kl + 1536, sr, si, z4r, z4i, hr, hi_, splat(z2r, z2i));
        __syncwarp();
        ldsm4t(b0, la); ldsm4t(b1, la + 256); ldsm4t(b2, la + 1024); ldsm4t(b3, la + 1280);
        if (PPOS == 1) poll();
        csq(z1r, z1i, z1r, z1i);
        cmul(sr, si, sr, si, z1r, z1i);
        csq(z4r, z4i, z2r, z2i);
        expand8(kl, kl + 512, sr, si, hr, hi_, z2r, z2i, splat(z4r, z4i));
        if (PPOS == 2) poll();
        mm2(2);
        if (PPOS == 3) poll();
        if (LNPOS == 3) ln1();
        if (NMPOS == 3) norm();
        __syncwarp();
        ldsm4t(b0, la); ldsm4t(b1, la + 256);
#pragma unroll
        for (int t = 0; t < 4; t++) sts64(kb + lane * 8 + 1024 + t * 256, kp[t][0], kp[t][1]);
        {
            float a0[4] = {0.f, 0.f, 0.f, 0.f}, a1[4] = {0.f, 0.f, 0.f, 0.f};
            mma_f16(a0, Af[0], b0[0], b0[1]); mma_f16(a1, Af[1], b0[2], b0[3]); mma_f16(a0, Af[2], b1[0], b1[1]); mma_f16(a1, Af[3], b1[2], b1[3]);
            sts64(kb + lane * 8 + 2048, pack_f16(a0[1] + a1[1], a0[0] + a1[0]), pack_f16(a0[3] + a1[3], a0[2] + a1[2]));
        }
        if (NMPOS == 4) norm();
        bar_sync(1 + k, 128);
        const uint4 m01 = lds128(sb + SM_KG + k * 32), m23 = lds128(sb + SM_KG + k * 32 + 16);
        const unsigned Em = max(max(m01.x, m01.z), max(m23.x, m23.z));
        const float f0 = __uint_as_float(max((int)(127 + m01.x - Em), 0) << 23), f1 = __uint_as_float(max((int)(127 + m01.z - Em), 0) << 23),
                    f2 = __uint_as_float(max((int)(127 + m23.x - Em), 0) << 23), f3 = __uint_as_float(max((int)(127 + m23.z - Em), 0) << 23);
        const uint32_t r0 = pack_f16(f0, f0), r1 = pack_f16(f1, f1), r2 = pack_f16(f2, f2), r3 = pack_f16(f3, f3);
        const uint32_t ra = fb + lane * 8 + wq * 256 + 1024;
        const uint2 p0 = lds64(ra), p1 = lds64(ra + 3072), p2 = lds64(ra + 6144), p3 = lds64(ra + 9216);
        uint32_t w0 = hadd2(hfma2(p0.x, r0, hmul2(p1.x, r1)), hfma2(p2.x, r2, hmul2(p3.x, r3)));
        uint32_t w1 = hadd2(hfma2(p0.y, r0, hmul2(p1.y, r1)), hfma2(p2.y, r2, hmul2(p3.y, r3)));
        const bool last = lane == 31;
        if (wq < 2) {
            const uint32_t rc = fb + lane * 8 + wq * 4 + 2048;
            const uint32_t w4 = hmul2(hadd2(hfma2(lds32(rc), r0, hmul2(lds32(rc + 3072), r1)), hfma2(lds32(rc + 6144), r2, hmul2(lds32(rc + 9216), r3))), 0x18001800u);
            const uint32_t ph = pf + (P_H7 + 16 * wq) + (g & 1) * (2 * P_HS) + cq * 64 + (g >> 1) * 4;
            put16(ph, w4 >> 16); put16(ph + 32, w4);
            const uint32_t pa = pn + (4 + 512 * wq) + lane * 8;
            sts16(pa, w0 >> 16); sts32(pa + 4, w0); sts16(pa + 10, w0);
            sts16(pa + 256, w1 >> 16); sts32(pa + 260, w1); sts16(pa + 266, w1);
            if (last) {
                sts32(sb + SM_SC + k * 4, Em * 0x00800080u);
                put16(wq ? pa + 264 : pn,
                      wq ? w1 : pack_f16(((float)(int)m01.y * f0 + (float)(int)m01.w * f1 + (float)(int)m23.y * f2 + (float)(int)m23.w * f3) * (1.f / 16777216.f)
                                         + __uint_as_float(pD << 16) * __uint_as_float((254u - Em) << 23), 0.f));
            }
        } else if (wq == 2) {
            const uint32_t pa = pn + 258 * 4 + (cq & 1) * 16 + (cq >> 1) * 512 + g * 32;
            if (last) { put16(pf, hmul2(w1, 0x18001800u)); w1 = hadd2(w1, hneg2(__byte_perm(w1, 0, 0x1010))); }
            const uint32_t b0 = __byte_perm(w0, 0, 0x1010), b1 = __byte_perm(w1, 0, 0x1010);
            sts16(pa, w0 >> 16); sts32(pa + 4, w0); sts64(pa + 8, b0, b0); sts16(pa + 18, w0);
            sts16(pa + 256, w1 >> 16); sts32(pa + 260, w1); sts64(pa + 264, b1, b1); sts16(pa + 274, w1);
        } else {
            const uint32_t pa = pf + ((g & 1) ? 3 * P_GS : P_GS) + cq * 32 + (g >> 1) * 4;
            const uint32_t pb = pa + ((g & 1) ? 4 - 3 * P_GS : P_GS);
            w0 = hmul2(w0, 0x18001800u); w1 = hmul2(w1, 0x18001800u);
            put16(pa, w0 >> 16); put16(pb, w0); put16(pa + 16, w1 >> 16); put16(pb + 16, w1);
            if (last) put16(pf + P_H7 + P_HS, w1);
        }
        bar_sync(1 + k, 128);
    }
    STAMP(6);

    asm volatile("barrier.cluster.wait.aligned;" ::: "memory");
    mbar_wait(mb + (MB_X + (k < XSPLIT || k >= nslot)) * 8);
    STAMP(7);
    if (k < nslot) {
        const int role = (wq + k) & 3;
        const uint32_t ub = sb + SM_U + k * US + 128;
        if (role) {
            const int r = (3 - role) * 32 + lane;
            const uint32_t a1 = ub + (r & 3) * (2 * UP) + (r >> 2) * 16, a0 = a1 + ((r & 3) ? -2 * UP : 6 * UP - 16);
            const uint4 q0 = lds128(a0), q1 = lds128(a0 + UP), q2 = lds128(a1), q3 = lds128(a1 + UP);
            const uint32_t U[16] = {q0.x, q0.y, q0.z, q0.w, q1.x, q1.y, q1.z, q1.w, q2.x, q2.y, q2.z, q2.w, q3.x, q3.y, q3.z, q3.w};
            uint32_t V[14], Q[14], R4[12], T[8];
#pragma unroll
            for (int i = 2; i < 14; i++) { V[i] = __byte_perm(U[i], U[i + 1], 0x5432); Q[i] = hadd2(U[i], V[i]); }
#pragma unroll
            for (int i = 2; i < 12; i++) R4[i] = hadd2(Q[i], Q[i + 1]);
            const uint32_t rb = fb + r * 16;
#pragma unroll
            for (int i = 0; i < 8; i++) T[i] = hadd2(V[5 + i], Q[6 + i]);
            sts128(rb + F_E3, T[0], T[1], T[2], T[3]); sts128(rb + F_O3 + 16, T[4], T[5], T[6], T[7]);
#pragma unroll
            for (int i = 0; i < 8; i++) T[i] = hadd2(R4[3 + i], U[5 + i]);
            sts128(rb + F_O5, T[0], T[1], T[2], T[3]); sts128(rb + F_E5, T[4], T[5], T[6], T[7]);
            if (role != 1) {
#pragma unroll
                for (int i = 0; i < 8; i++) T[i] = hadd2(T[i], hadd2(V[2 + i], V[5 + i]));
                sts128(rb + F_E7, T[0], T[1], T[2], T[3]); sts128(rb + F_O7, T[4], T[5], T[6], T[7]);
#pragma unroll
                for (int i = 0; i < 8; i++) T[i] = hadd2(R4[2 + i], hadd2(R4[4 + i], U[6 + i]));
                sts128(rb + F_O9, T[0], T[1], T[2], T[3]); sts128(rb + F_E9 + 16, T[4], T[5], T[6], T[7]);
                sts128(rb + F_E2, Q[6], Q[7], Q[8], Q[9]); sts128(rb + F_O2, Q[10], Q[11], Q[12], Q[13]);
            }
        } else if (lane < 8) {
            uint32_t v[5];
#pragma unroll
            for (int i = 0; i < 5; i++) { const int t = 6 + lane + i; v[i] = lds16(ub + 23 * 16 + (t < 16 ? (6 + (t >> 3)) * UP : 16) + (t & 7) * 2); }
            const uint32_t s = hadd2(hadd2(hadd2(v[0], v[1]), hadd2(v[2], v[3])), v[4]);
            sts16(fb + F_O5 + 96 * 16 + lane * 2, s);
            sts32(fb + (lane < 4 ? F_O3 : F_E9 - 16) + lane * 4, 0);
        }
        bar_sync(1 + k, 128);
        float acc[4][4];
        uint32_t Q[4][4];
        {
            const int h = role & 1, part = role >> 1;
            const uint32_t po = pf + (g - 2 * cq) * 4;
            float fa[7][4];
#pragma unroll
            for (int a = 0; a < 7; a++) fa[a][0] = fa[a][1] = fa[a][2] = fa[a][3] = 0.f;
            uint32_t B[3][4];
            Q[0][2] = zero;
#pragma unroll 1
            for (int s = 2 * part + 1; s >= 2 * part; s--) {
#pragma unroll
                for (int i = 0; i < 3; i++) { Q[i][0] = lds32(po + s * P_GS + i * 64); Q[i][1] = lds32(po + s * P_GS + (i * 64 + 32)); }
                const uint32_t ba = fb + lane * 16 + ((s & 1) * F_E3 + (part == h ? 0 : F_O5 + h * 16));
#pragma unroll
                for (int i = 0; i < 3; i++) ldsm4t(B[i], ba + i * 512);
#pragma unroll
                for (int i = 0; i < 3; i++) { Q[i][3] = CP(Q[i][0]); if (i) Q[i][2] = CP(Q[i - 1][1]); }
#pragma unroll
                for (int dl = 0; dl < 3; dl++)
#pragma unroll
                    for (int ap = 0; ap < 6 - dl; ap++) mma_f16(fa[ap + 1 + dl], Q[dl], B[ap >> 1][2 * (ap & 1)], B[ap >> 1][2 * (ap & 1) + 1]);
            }
#pragma unroll 1
            for (int s = role; s == 1; s++) {
                ldsm2t(B[0][0], B[0][1], fb + ((lane & 15) == 15 ? F_O5 : F_O3));
#pragma unroll
                for (int dl = 0; dl < 3; dl++) mma_f16(fa[dl], Q[dl], B[0][0], B[0][1]);
            }
#pragma unroll 1
            for (int s = part; s <= 2 * part; s++) {
#pragma unroll
                for (int i = 0; i < 4; i++) { Q[i][0] = lds32(po + s * P_HS + (P_H7 + i * 64)); Q[i][1] = lds32(po + s * P_HS + (P_H7 + i * 64 + 32)); }
                const uint32_t ba = fb + lane * 16 + (F_E7 + s * 1024 + h * F_H);
                ldsm4t(B[0], ba); ldsm4t(B[1], ba + 512);
#pragma unroll
                for (int i = 0; i < 4; i++) { Q[i][3] = CP(Q[i][0]); if (i) Q[i][2] = CP(Q[i - 1][1]); }
#pragma unroll
                for (int dl = 0; dl < 4; dl++) {
#pragma unroll
                    for (int ap = 0; ap < 4 - dl; ap++) mma_f16(fa[ap + 3 + dl], Q[dl], B[ap >> 1][2 * (ap & 1)], B[ap >> 1][2 * (ap & 1) + 1]);
                    if (s == 1) break;
                }
            }
            const uint32_t da = fb + role * 2048 + (lane & 3) * 512 + (((lane >> 2) ^ ((lane & 3) * 2)) << 4);
            bar_sync(1 + k, 128);
            stsm4(da, 0u, 0u, pack_f16(fa[0][0], fa[0][1]), pack_f16(fa[0][2], fa[0][3]));
#pragma unroll
            for (int i = 1; i < 4; i++)
                stsm4(da + i * 128, pack_f16(fa[2 * i - 1][0], fa[2 * i - 1][1]), pack_f16(fa[2 * i - 1][2], fa[2 * i - 1][3]),
                      pack_f16(fa[2 * i][0], fa[2 * i][1]), pack_f16(fa[2 * i][2], fa[2 * i][3]));
            Q[0][0] = (g == 2 * cq) ? 0x6000u : ((g == 2 * cq + 1) ? 0x60000000u : 0u);
            Q[0][1] = 0; Q[0][3] = CP(Q[0][0]);
            const uint32_t ra = fb + (lane >> 3) * 2048 + wq * 512 + (((lane & 7) ^ (wq * 2)) << 4);
            bar_sync(1 + k, 128);
#pragma unroll
            for (int i = 0; i < 4; i++) {
                ldsm4(B[0], ra + i * 128);
                acc[i][0] = acc[i][1] = acc[i][2] = acc[i][3] = 0.f;
                mma_f16(acc[i], Q[0], hadd2(B[0][0], B[0][2]), hadd2(B[0][1], B[0][3]));
            }
        }
        bar_arrive(6 + k, 160);
        STAMP(8);
        const uint32_t inv = lds32(sb + SM_SC + k * 4);
        uint32_t yd = mapa(sb, 2 * wq) + (SM_XT + 128 + q * YP + k * YS) + lane * 16;
        PIN(yd);
        {
            uint32_t pp = pn + (16 * (wq - 3) + g - 2 * cq) * 4;
            uint32_t dlo = (((ub + 6 * UP) & 0x3FFFF) >> 4) | ((UP >> 4) << 16);
            uint32_t R[4][4];
            auto loadQ = [&](uint32_t (&X)[4][4], uint32_t prev) {
#pragma unroll
                for (int i = 0; i < 4; i++) { X[i][0] = lds32(pp + i * 64); X[i][1] = lds32(pp + i * 64 + 32); }
                X[0][2] = CP(prev);
#pragma unroll
                for (int i = 0; i < 4; i++) { X[i][3] = CP(X[i][0]); if (i) X[i][2] = CP(X[i - 1][1]); }
                pp += 256;
            };
            auto issue = [&](uint32_t (&X)[4][4]) {
                asm volatile("wgmma.fence.sync.aligned;" ::: "memory");
#pragma unroll
                for (int i = 0; i < 4; i++) wgmma32(acc, X[i], dlo - i * (2 * UP >> 4));
                asm volatile("wgmma.commit_group.sync.aligned;" ::: "memory");
                dlo -= 1;
            };
            loadQ(Q, 0);
#pragma unroll 1
            for (int dl = 0; dl < 4; dl++) {
                issue(Q);
                asm volatile("wgmma.wait_group.sync.aligned 1;" ::: "memory");
                loadQ(R, Q[3][1]);
                issue(R);
                asm volatile("wgmma.wait_group.sync.aligned 1;" ::: "memory");
                loadQ(Q, R[3][1]);
            }
            issue(Q);
            asm volatile("wgmma.wait_group.sync.aligned 0;" ::: "memory");
        }
        const uint32_t pstep = mapa(sb, 1) - mapa(sb, 0), ym = mapa(mb + MB_Y * 8, 2 * wq);
#pragma unroll
        for (int e = 0; e < 2; e++)
            st_async4(yd + e * pstep, bmul2(pack_bf16(acc[0][2 * e], acc[0][2 * e + 1]), inv), bmul2(pack_bf16(acc[1][2 * e], acc[1][2 * e + 1]), inv),
                      bmul2(pack_bf16(acc[2][2 * e], acc[2][2 * e + 1]), inv), bmul2(pack_bf16(acc[3][2 * e], acc[3][2 * e + 1]), inv), ym + e * pstep);
        if (lane == 0) asm volatile("mbarrier.arrive.shared::cta.b64 _, [%0];" :: "r"(mb + MB_Y * 8) : "memory");
    }
    STAMP(9);
    uint32_t ha[5], hb[5];
    if (warp < 16) {
        const uint4 wk = lds128(sb + SM_DW + cq * 16);
        uint32_t sel[5] = {wk.x, wk.y, wk.z, wk.w, lds32(sb + SM_DW + 64 + cq * 4)}, sel2[5];
#pragma unroll
        for (int i = 0; i < 5; i++) {
            if (!(g & 1)) sel[i] = 0x3F803F80u;
            sel2[i] = sel[i]; PIN(sel2[i]);
        }
        const uint32_t y4 = sb + SM_XT + 128 + warp * 32 + (2 * (lane >> 3) + (lane & 1)) * YP + ((lane & 7) >> 1) * YS;
        const uint32_t y1 = sb + SM_XT + 128 + warp * 32 + (lane & 7) * YP + 4 * YS + (lane & 8) * 2;
        mbar_wait(mb + MB_Y * 8);
        STAMP(10);
        float ca[4] = {0.f, 0.f, 0.f, 0.f}, cb[4] = {0.f, 0.f, 0.f, 0.f};
        {
            uint32_t ya[4], yb[4], yc, yd;
            ldsm4t(ya, y4); ldsm4t(yb, y4 + 16); ldsm2t(yc, yd, y1);
#pragma unroll
            for (int i = 0; i < 4; i++) { ha[i] = badd2(xa[i], ya[i]); hb[i] = badd2(xb[i], yb[i]); }
            ha[4] = badd2(xa[4], yc); hb[4] = badd2(xb[4], yd);
        }
        if (nslot != 5) {
            ha[4] = hb[4] = 0;
            if (cq >= 2) ha[0] = ha[1] = ha[2] = ha[3] = hb[0] = hb[1] = hb[2] = hb[3] = 0;
        }
#pragma unroll
        for (int i = 0; i < 5; i++) { mma_bf16_k8(ca, ha[i], sel[i], ha[i]); mma_bf16_k8(cb, hb[i], sel2[i], hb[i]); }
        const float oa = __shfl_xor_sync(~0u, (g & 1) ? ca[2] : ca[3], 4), ob = __shfl_xor_sync(~0u, (g & 1) ? cb[2] : cb[3], 4);
        if (cq == (g >> 1)) {
            float4* ap = &g_s.acc[256 * q + tn];
            const bool od = g & 1;
            asm volatile("red.relaxed.gpu.global.add.v4.f32 [%0], {%1,%2,%3,%4};" :: "l"(ap), "f"(od ? oa : ca[2]), "f"(od ? ca[1] : ca[0]), "f"(od ? ca[3] : oa), "f"(1.0f) : "memory");
            asm volatile("red.relaxed.gpu.global.add.v4.f32 [%0], {%1,%2,%3,%4};" :: "l"(ap + 8), "f"(od ? ob : cb[2]), "f"(od ? cb[1] : cb[0]), "f"(od ? cb[3] : ob), "f"(1.0f) : "memory");
        }
        const uint32_t hta = sb + SM_HT + tn * 80;
        sts128(hta + cq * 16, ha[0], ha[1], ha[2], ha[3]); sts32(hta + 64 + cq * 4, ha[4]);
        sts128(hta + cq * 16 + 640, hb[0], hb[1], hb[2], hb[3]); sts32(hta + 704 + cq * 4, hb[4]);
        STAMP(11);
    }
    const int kq = warp / 5, mt = warp - 5 * kq;
    const int mi = lane >> 3, mr = lane & 7;
    const unsigned tk = (unsigned)tid / 72u, ck = tid - tk * 72;
    uint32_t A[9][4];
    auto loadA = [&]() {
        mbar_wait(mb + MB_W1 * 8);
        const uint32_t aa = sb + (mi & 1) * SM_WU + (8 * (mi >> 1) + mr) * 80 + (144 * 80 * kq + mt * 16);
#pragma unroll
        for (int s = 0; s < 9; s++) ldsm4t(A[s], aa + s * 1280);
    };
    const uint32_t par = (epoch & 1) ? 0x40004000u : 0u;
    uint32_t pk0 = mapa(sb, 2 * cq), go = (ck / 5u + ck) * 16, co = ((q * 8 * NCL + c) * 6 + cq) * 16;
    PIN(pk0); PIN(go); PIN(co);
    if (warp < 8) {
        const float wsum = ldsf(sb + SM_SC + 24);
        const uint32_t idx = 2047 - (512 * ((tid >> 1) & 3) + 128 * ((tid >> 3) & 3) + 64 * (tid & 1) + 8 * q + warp);
        if (RED_DELAY) { const long long t0 = clock64(); while (clock64() - t0 < RED_DELAY) {} }
        uint4 s; int n = 0;
        do { s = ld_rlx128(&g_s.acc[256 * q + tid]); } while (__uint_as_float(s.w) != (float)NCL && ++n < SPIN_LIMIT);
        STAMP(16);
        const uint32_t ms = ln_stats(__uint_as_float(s.x), __uint_as_float(s.y));
        const float rs = rcpf(bf_hi(ms));
        const uint32_t rb = pack_bf16(0.f, fmaf(-bf_lo(ms), wsum, __uint_as_float(s.z)) * rs);
        const uint32_t key = (((rb ^ (((int)rb >> 31) | 0x80000000u)) >> 16) << 11) | idx;
        sts32(sb + SM_KEY + tid * 4, key);
        __syncwarp();
        const uint32_t rank = rank4<8>(sb + SM_KEY + warp * 128, key);
        if (rank < 8) sts32(sb + SM_CAND + warp * 32 + rank * 4, key);
        sts64(sb + SM_ST + tid * 8, __byte_perm(ms, 0, 0x1010), rsplit(rs));
    } else loadA();
    if (warp < 16) {
        STAMP(17);
        bar_sync(12, 512);
        STAMP(18);
        if (warp < 8) {
            const uint32_t mk = lds32(sb + SM_CAND + (tid >> 2) * 4);
            uint32_t rank = rank4<4>(sb + SM_CAND + cq * 64, mk);
            rank += __shfl_xor_sync(~0u, rank, 1); rank += __shfl_xor_sync(~0u, rank, 2);
            if (rank < 8) {
                const uint32_t pk1 = pk0 + (mapa(sb, 1) - mapa(sb, 0));
                st_async1(pk0 + (SM_RK + q * 32) + rank * 4, mk, pk0 + (SM_MB + MB_KEY * 8));
                st_async1(pk1 + (SM_RK + q * 32) + rank * 4, mk, pk1 + (SM_MB + MB_KEY * 8));
                const uint32_t t = tslot(~mk);
                const uint2 sv = lds64(sb + SM_ST + t * 8);
                const uint4 hv = lds128(sb + SM_HT + t * 80 + cq * 16);
                const uint32_t h4 = lds32(sb + SM_HT + t * 80 + 64 + cq * 4);
                const uint32_t rr = bmul2(sv.y, 0x3C803C80u), rh = __byte_perm(rr, 0, 0x1010), rl = __byte_perm(rr, 0, 0x3232);
                char* const dp = (char*)g_s.cand + (co + rank * 1440);
                st_rlx128(dp, (norm2(hv.x, sv.x, rh, rl) & 0xBFFFBFFFu) | par, (norm2(hv.y, sv.x, rh, rl) & 0xBFFFBFFFu) | par,
                          (norm2(hv.z, sv.x, rh, rl) & 0xBFFFBFFFu) | par, (norm2(hv.w, sv.x, rh, rl) & 0xBFFFBFFFu) | par);
                asm volatile("st.relaxed.gpu.global.u32 [%0], %1;" :: "l"((char*)g_s.cand + (co + rank * 1440 + 64 - cq * 12)), "r"((norm2(h4, sv.x, rh, rl) & 0xBFFFBFFFu) | par) : "memory");
            }
            __syncwarp();
        }
        {
            const uint2 sa = lds64(sb + SM_ST + tn * 8), sbb = lds64(sb + SM_ST + tn * 8 + 64);
            const uint32_t rha = __byte_perm(sa.y, 0, 0x1010), rla = __byte_perm(sa.y, 0, 0x3232);
            const uint32_t rhb = __byte_perm(sbb.y, 0, 0x1010), rlb = __byte_perm(sbb.y, 0, 0x3232);
#pragma unroll
            for (int i = 0; i < 5; i++) { ha[i] = badd2(ha[i], norm2(ha[i], sa.x, rha, rla)); hb[i] = badd2(hb[i], norm2(hb[i], sbb.x, rhb, rlb)); }
            const bool hf = (c & 1) && cq == 0;
            const uint32_t o16 = sb + SM_XT + (hf ? 16384 + tn * 16 : tn * 64 + (cq - (c & 1)) * 16), o4 = sb + SM_XT + ((c & 1) ? tn * 64 + 48 : 16384 + tn * 16) + cq * 4;
            sts128(o16, ha[0], ha[1], ha[2], ha[3]); sts32(o4, ha[4]);
            sts128(o16 + (hf ? 128 : 512), hb[0], hb[1], hb[2], hb[3]); sts32(o4 + ((c & 1) ? 512 : 128), hb[4]);
            if (HALF_AT == 0) bar_arrive(13, 544);
        }
        if (warp >= 8) {
            STAMP(19);
            mbar_wait(mb + MB_KEY * 8);
            STAMP(20);
            const uint32_t mk = lds32(sb + SM_RK - 256 + (tid >> 2) * 4);
            uint32_t rank = rank4<4>(sb + SM_RK + cq * 64, mk);
            rank += __shfl_xor_sync(~0u, rank, 1); rank += __shfl_xor_sync(~0u, rank, 2);
            if (rank < 8) sts64(sb + SM_SEL + rank * 8, mk, ((tid >> 2) - 64) * 1440);
        }
    }
    bar_sync(11, HALF_AT == 2 ? 672 : 640);
    STAMP(12);

    const char* gp = (const char*)g_s.cand + (go + lds32(sb + SM_SEL + 4 + (tk & 7) * 8));
    uint4 hv = ld_rlx128(gp);
    if (warp < 8) loadA();
    const bool red = warp < 6;
    const uint32_t ft = red ? (unsigned)tid / 24u : (unsigned)(tid >> 4) & 7u, fj = red ? 24 * q + tid - ft * 24 : d0 / 3 + (lane & 15);
    const uint32_t key = lds32(sb + SM_SEL + ft * 8), k16 = key << 5;
    float sig = bfr(rcpf(1.f + ex2f(__uint_as_float((k16 ^ (~((int)k16 >> 31) | 0x80000000u)) & 0xFFFF0000u) * -1.4426950408889634f)));
    uint32_t ra2 = sb + SM_RED2 + tid * 12 + ft * 16, fo = (ft * 192 + fj) * 16, oo = ((~key & 2047) * D_ + 3 * fj) * 2;
    uint32_t bx = sb + SM_XS + mr * 1168 + mi * 16 + 288 * kq, gd = mapa(sb, kq * (8 / NRED)) + (SM_GU + (q * nslot + mt) * 128) + lane * 4;
    PIN(ra2); PIN(fo); PIN(oo); PIN(bx); PIN(gd);
    asm volatile("" : "+f"(sig));
    {
        if (warp < 18) {
            int n = 0;
            while ((((hv.x ^ par) | (hv.y ^ par) | (hv.z ^ par) | (hv.w ^ par)) & 0x40004000u) && ++n < SPIN_LIMIT) hv = ld_rlx128(gp);
            sts128(sb + SM_XS + tk * 16 + tid * 16, hv.x ^ par, hv.y ^ par, hv.z ^ par, hv.w ^ par);
        }
    }
    bar_sync(14, 672);
    STAMP(13);
    {
        float c0[4] = {0.f, 0.f, 0.f, 0.f}, c1[4] = {0.f, 0.f, 0.f, 0.f}, c2[4] = {0.f, 0.f, 0.f, 0.f};
        uint32_t b[5][4];
#pragma unroll
        for (int s = 0; s < 4; s++) ldsm4(b[s], bx + s * 64);
        asm volatile("ldmatrix.sync.aligned.m8n8.x2.shared.b16 {%0,%1}, [%2];" : "=r"(b[4][0]), "=r"(b[4][1]) : "r"(bx + 256) : "memory");
        mma_bf16(c0, A[0][0], A[0][1], A[0][2], A[0][3], b[0][0], b[0][1]);
        mma_bf16(c1, A[1][0], A[1][1], A[1][2], A[1][3], b[0][2], b[0][3]);
        mma_bf16(c2, A[2][0], A[2][1], A[2][2], A[2][3], b[1][0], b[1][1]);
        mma_bf16(c0, A[3][0], A[3][1], A[3][2], A[3][3], b[1][2], b[1][3]);
        mma_bf16(c1, A[4][0], A[4][1], A[4][2], A[4][3], b[2][0], b[2][1]);
        mma_bf16(c2, A[5][0], A[5][1], A[5][2], A[5][3], b[2][2], b[2][3]);
        mma_bf16(c0, A[6][0], A[6][1], A[6][2], A[6][3], b[3][0], b[3][1]);
        mma_bf16(c1, A[7][0], A[7][1], A[7][2], A[7][3], b[3][2], b[3][3]);
        mma_bf16(c2, A[8][0], A[8][1], A[8][2], A[8][3], b[4][0], b[4][1]);
        sts128f(sb + SM_RED + tid * 16, c0[0] + c1[0] + c2[0], c0[1] + c1[1] + c2[1], c0[2] + c1[2] + c2[2], c0[3] + c1[3] + c2[3]);
    }
    bar_sync(1 + mt, 128);
    STAMP(21);
    if (mt < nslot && kq < NRED) {
        const uint32_t ra = sb + SM_RED + mt * 512 + lane * 16;
        const float4 p0 = lds128f(ra), p1 = lds128f(ra + 2560), p2 = lds128f(ra + 5120), p3 = lds128f(ra + 7680);
        const float g0 = bfr(((p0.x + p1.x) + (p2.x + p3.x)) * 64.f), g1 = bfr(((p0.y + p1.y) + (p2.y + p3.y)) * 64.f);
        const uint32_t sg = pack_bf16(g0 * rcpf(1.f + ex2f(g0 * -1.4426950408889634f)), g1 * rcpf(1.f + ex2f(g1 * -1.4426950408889634f)));
        const uint32_t gu = bmul2(sg, pack_bf16(((p0.z + p1.z) + (p2.z + p3.z)) * 64.f, ((p0.w + p1.w) + (p2.w + p3.w)) * 64.f));
        const uint32_t pstep = mapa(sb, 1) - mapa(sb, 0), gm = mapa(mb + MB_GU * 8, kq * (8 / NRED));
#pragma unroll
        for (int i = 0; i < 8 / NRED; i++) st_async1(gd + i * pstep, gu, gm + i * pstep);
    }
    mbar_wait(mb + MB_W2 * 8);
    {
        const uint32_t aa = sb + (8 * (mi >> 1) + mr) * 144 + (mi & 1) * 16 + (SM_FAR + 2304 * kq + mt * 32);
#pragma unroll
        for (int s = 0; s < 5; s++) ldsm4t(A[s], aa + s * FAR_SZ);
    }
    {
        uint32_t ba = sb + (SM_GU + 256 * kq) + (lane & 15) * 16 + (lane >> 4) * 1024, wa = sb + (SM_RED2 + kq * 2432 + mt * 64) + g * 4 + cq * 608;
        PIN(ba); PIN(wa);
        STAMP(22);
        mbar_wait(mb + MB_GU * 8);
        STAMP(23);
        float c0[4] = {0.f, 0.f, 0.f, 0.f}, c1[4] = {0.f, 0.f, 0.f, 0.f}, c2[4] = {0.f, 0.f, 0.f, 0.f};
        uint32_t b[2][4], b8, b9;
        ldsm4t(b[0], ba); ldsm4t(b[1], ba + 2048); ldsm2t(b8, b9, ba + 4096);
        mma_bf16(c0, A[0][0], A[0][1], A[0][2], A[0][3], b[0][0], b[0][1]);
        mma_bf16(c1, A[1][0], A[1][1], A[1][2], A[1][3], b[0][2], b[0][3]);
        if (nslot == 5) {
            mma_bf16(c2, A[4][0], A[4][1], A[4][2], A[4][3], b8, b9);
            mma_bf16(c0, A[2][0], A[2][1], A[2][2], A[2][3], b[1][0], b[1][1]);
            mma_bf16(c1, A[3][0], A[3][1], A[3][2], A[3][3], b[1][2], b[1][3]);
        }
        stsf(wa, c0[0] + c1[0] + c2[0]); stsf(wa + 304, c0[1] + c1[1] + c2[1]);
        if (mt < 4) { stsf(wa + 32, c0[2] + c1[2] + c2[2]); stsf(wa + 336, c0[3] + c1[3] + c2[3]); }
    }
    if (warp < 10) {
        float v[3], cnt = 3.f;
        if (red) {
            bar_sync(6, 640);
            STAMP(14);
#pragma unroll
            for (int i = 0; i < 3; i++) v[i] = ((ldsf(ra2 + i * 4) + ldsf(ra2 + i * 4 + 2432)) + (ldsf(ra2 + i * 4 + 4864) + ldsf(ra2 + i * 4 + 7296))) * sig;
        } else {
            bar_arrive(6, 640);
            cnt = 0.f;
#pragma unroll
            for (int i = 0; i < 3; i++) {
                const uint32_t cl = 3 * fj + i - d0;
                const bool ok = cl < 8 * nslot && ((~key >> 3) & 7) == q;
                const uint32_t cf = cl - (c & 1) * 8;
                v[i] = ok ? __uint_as_float(lds16(sb + SM_XT + (cf < 32 ? tslot(~key) * 64 + cf * 2 : 16384 + tslot(~key) * 16 + (cl & 7) * 2)) << 16) : 0.f;
                if (ok) cnt += 1.f;
            }
            mbar_wait(mb + MB_OUT * 8);
        }
        if (cnt != 0.f) {
            float x, y, z, w;
            asm volatile("atom.relaxed.gpu.global.add.v4.f32 {%0,%1,%2,%3}, [%4], {%5,%6,%7,%8};" : "=f"(x), "=f"(y), "=f"(z), "=f"(w)
                         : "l"((char*)g_s.fin + fo), "f"(v[0]), "f"(v[1]), "f"(v[2]), "f"(cnt) : "memory");
            if (w + cnt == 3.f * (NCL + 1)) {
                __nv_bfloat16* op = (__nv_bfloat16*)((char*)prm.out + oo);
                op[0] = __float2bfloat16(x + v[0]); op[1] = __float2bfloat16(y + v[1]); op[2] = __float2bfloat16(z + v[2]);
            }
        }
    } else bar_arrive(6, 640);
    STAMP(15);
}

typedef CUresult (*EncodeFn)(CUtensorMap*, CUtensorMapDataType, cuuint32_t, void*, const cuuint64_t*, const cuuint64_t*,
                             const cuuint32_t*, const cuuint32_t*, CUtensorMapInterleave, CUtensorMapSwizzle,
                             CUtensorMapL2promotion, CUtensorMapFloatOOBfill);

void make_map(EncodeFn fn, CUtensorMap* tm, const void* p, int cols, int rows, int bc, int br) {
    cuuint64_t dims[2] = {(cuuint64_t)cols, (cuuint64_t)rows};
    cuuint64_t strides[1] = {(cuuint64_t)cols * 2};
    cuuint32_t box[2] = {(cuuint32_t)bc, (cuuint32_t)br};
    cuuint32_t es[2] = {1, 1};
    fn(tm, CU_TENSOR_MAP_DATA_TYPE_BFLOAT16, 2, const_cast<void*>(p), dims, strides, box, es, CU_TENSOR_MAP_INTERLEAVE_NONE,
       CU_TENSOR_MAP_SWIZZLE_NONE, (CUtensorMapL2promotion)L2PROMO, CU_TENSOR_MAP_FLOAT_OOB_FILL_NONE);
}

void make_map3(EncodeFn fn, CUtensorMap* tm, const void* p) {
    cuuint64_t dims[3] = {(cuuint64_t)D_, 64, 32};
    cuuint64_t strides[2] = {(cuuint64_t)D_ * 2, (cuuint64_t)D_ * 128};
    cuuint32_t box[3] = {40, 8, 32};
    cuuint32_t es[3] = {1, 1, 1};
    fn(tm, CU_TENSOR_MAP_DATA_TYPE_BFLOAT16, 3, const_cast<void*>(p), dims, strides, box, es, CU_TENSOR_MAP_INTERLEAVE_NONE,
       CU_TENSOR_MAP_SWIZZLE_NONE, CU_TENSOR_MAP_L2_PROMOTION_NONE, CU_TENSOR_MAP_FLOAT_OOB_FILL_NONE);
}

void make_map5(EncodeFn fn, CUtensorMap* tm, const void* p, int bc) {
    cuuint64_t dims[5] = {(cuuint64_t)D_, 2, 4, 4, 64};
    cuuint64_t strides[4] = {(cuuint64_t)D_ * 128, (cuuint64_t)D_ * 1024, (cuuint64_t)D_ * 256, (cuuint64_t)D_ * 2};
    cuuint32_t box[5] = {(cuuint32_t)bc, 2, 4, 4, 8};
    cuuint32_t es[5] = {1, 1, 1, 1, 1};
    fn(tm, CU_TENSOR_MAP_DATA_TYPE_BFLOAT16, 5, const_cast<void*>(p), dims, strides, box, es, CU_TENSOR_MAP_INTERLEAVE_NONE,
       CU_TENSOR_MAP_SWIZZLE_NONE, CU_TENSOR_MAP_L2_PROMOTION_NONE, CU_TENSOR_MAP_FLOAT_OOB_FILL_NONE);
}

}

extern "C" void kernel_launch(void* const* d_in, const int* in_sizes, int n_in, void* d_out, int out_size) {
    (void)in_sizes; (void)n_in; (void)out_size;
    void* fp = nullptr;
    cudaDriverEntryPointQueryResult qr;
    cudaGetDriverEntryPoint("cuTensorMapEncodeTiled", &fp, cudaEnableDefault, &qr);
    EncodeFn fn = (EncodeFn)fp;
    CUtensorMap tmG, tmU, tmD, tmO, tmX, tmH;
    make_map3(fn, &tmX, d_in[0]);
    make_map(fn, &tmG, d_in[11], F_, D_, 40, 48);
    make_map(fn, &tmU, d_in[12], F_, D_, 40, 48);
    make_map(fn, &tmD, d_in[13], D_, F_, 72, 64);
    make_map5(fn, &tmO, d_out, 32);
    make_map5(fn, &tmH, d_out, 8);
    Params p;
    p.x = (const unsigned short*)d_in[0];
    for (int i = 0; i < 6; i++) p.prm6[i] = (const unsigned short*)d_in[1 + i];
    p.logdt = (const unsigned short*)d_in[7]; p.dskip = (const unsigned short*)d_in[8];
    p.wr = (const unsigned short*)d_in[10];
    for (int i = 0; i < 3; i++) p.w3[i] = (const char*)d_in[11 + i];
    p.out = (__nv_bfloat16*)d_out;
    p.zero = 0;
    cudaGetSymbolAddress((void**)&p.gs, g_s);
    cudaFuncSetAttribute(fused_kernel, cudaFuncAttributeMaxDynamicSharedMemorySize, SM_TOTAL);
    fused_kernel<<<NCTA, NTHR, SM_TOTAL>>>(p, tmG, tmU, tmD, tmO, tmX, tmH);
}
```

```cpp
#include <cuda_runtime.h>
#include <cuda_bf16.h>
#include <cuda_fp16.h>
#include <cuda.h>
#include <stdint.h>

namespace {

constexpr int L_ = 2048, D_ = 576, F_ = 4608;
constexpr int NCL = 15, CS = 8, NCTA = NCL * CS, NTHR = 768;
#define PACE_NS 100
#define LNPOS 2
#define MMPOS 1
constexpr int XSPLIT = 3, NRED = 2;
constexpr int SPIN_LIMIT = 1 << 22;

constexpr int SM_WG   = 0;
constexpr int SM_WU   = 46080;
constexpr int YP = 3376, YS = 672;
constexpr int UP = 3376, US = 672;
constexpr int SM_XT   = 92160;
constexpr int SM_U    = SM_XT + 8 * YP;
constexpr int SM_FAR  = SM_U + 8 * UP;
constexpr int FAR_SZ  = 12416;
constexpr int F_E5 = 0, F_O5 = 1536, F_E3 = 3088, F_O3 = 4624, F_E7 = 6176, F_E2 = F_E7 + 1024, F_E9 = F_E7 + 2048,
              F_H = 3088, F_O7 = F_E7 + F_H, F_O2 = F_E2 + F_H, F_O9 = F_E9 + F_H;
constexpr int SM_P    = SM_FAR + 5 * FAR_SZ;
constexpr int PN_SZ = 584 * 4, SM_PN = SM_P + 64 * 4;
constexpr int P_GS = 48 * 4, P_H7 = 192 * 4, P_HS = 72 * 4;
constexpr int PF_SZ = (192 + 216) * 4, SM_PF = SM_PN + 5 * PN_SZ + 32;
constexpr int SM_MISC = SM_PF + 5 * PF_SZ;
constexpr int SM_ST   = SM_MISC;
constexpr int SM_RK   = SM_ST + 2048;
constexpr int SM_SEL  = SM_RK + 256;
constexpr int SM_KG   = SM_SEL + 64;
constexpr int SM_SC   = SM_KG + 160;
constexpr int SM_DW   = SM_SC + 32;
constexpr int SM_MB   = SM_DW + 160;
constexpr int SM_TOTAL = SM_MB + 128;
constexpr int SM_ROW  = SM_XT - 20736;
constexpr int SM_XTL  = SM_ROW - 20480;
constexpr int SM_RED2 = SM_WG;
constexpr int SM_HT   = SM_P - 512;
constexpr int SM_KEY  = SM_FAR + 9216 + 128;
constexpr int SM_CAND = SM_KEY + 1024;
constexpr int SM_XS   = SM_U;
constexpr int SM_GU   = SM_XS + 9344;
constexpr int SM_RED  = SM_GU + 5632;
static_assert(F_O9 + 1024 <= FAR_SZ && FAR_SZ % 128 == 0, "far overflow");
static_assert(SM_RED + 10240 <= SM_FAR && SM_HT + 20496 <= SM_MISC, "alias overflow");
static_assert(SM_TOTAL <= 232448, "smem overflow");
static_assert(SM_FAR % 128 == 0 && SM_XT % 128 == 0 && SM_XTL % 128 == 0 && SM_P % 16 == 0 && SM_MISC % 16 == 0 && SM_MB % 8 == 0, "align");

enum { MB_X = 0, MB_W1 = 5, MB_W2 = 6, MB_KEY = 7, MB_GU = 8, MB_Y = 9, MB_OUT = 10, MB_T = 11, MB_R = 12 };

struct __align__(128) Scratch {
    unsigned epoch, zcnt, pad[30];
    uint4  st1[L_ * 2];
    float4 acc[L_];
    uint4  cand[64 * NCL * 6];
    float4 fin[8 * 192 + 24];
};
__device__ Scratch g_s;
#define STAMP(i)

__device__ __forceinline__ uint32_t mapa(uint32_t a, uint32_t r) { uint32_t d; asm("mapa.shared::cluster.u32 %0, %1, %2;" : "=r"(d) : "r"(a), "r"(r)); return d; }
__device__ __forceinline__ void mbar_wait(uint32_t mb) {
    asm volatile("{ .reg .pred p, q; .reg .u32 n; mov.u32 n, 0;\n"
                 "W_%=: mbarrier.try_wait.parity.shared::cta.b64 p, [%0], 0; add.u32 n, n, 1; setp.lt.and.u32 q, n, 65536, !p; @q bra W_%=; }" :: "r"(mb) : "memory");
}
__device__ __forceinline__ void arm(uint32_t mb, uint32_t bytes) { asm volatile("mbarrier.arrive.expect_tx.shared::cta.b64 _, [%0], %1;" :: "r"(mb), "r"(bytes) : "memory"); }
__device__ __forceinline__ void bar_sync(int id, int n) { asm volatile("bar.sync %0, %1;" :: "r"(id), "r"(n) : "memory"); }
__device__ __forceinline__ void bar_arrive(int id, int n) { asm volatile("bar.arrive %0, %1;" :: "r"(id), "r"(n) : "memory"); }
__device__ __forceinline__ uint32_t lds16(uint32_t a) { unsigned short v; asm volatile("ld.shared.u16 %0, [%1];" : "=h"(v) : "r"(a) : "memory"); return v; }
__device__ __forceinline__ uint32_t lds32(uint32_t a) { uint32_t v; asm volatile("ld.shared.u32 %0, [%1];" : "=r"(v) : "r"(a) : "memory"); return v; }
__device__ __forceinline__ uint2 lds64(uint32_t a) { uint2 v; asm volatile("ld.shared.v2.u32 {%0,%1}, [%2];" : "=r"(v.x), "=r"(v.y) : "r"(a) : "memory"); return v; }
__device__ __forceinline__ float ldsf(uint32_t a) { float v; asm volatile("ld.shared.f32 %0, [%1];" : "=f"(v) : "r"(a) : "memory"); return v; }
__device__ __forceinline__ uint4 lds128(uint32_t a) { uint4 v; asm volatile("ld.shared.v4.u32 {%0,%1,%2,%3}, [%4];" : "=r"(v.x), "=r"(v.y), "=r"(v.z), "=r"(v.w) : "r"(a) : "memory"); return v; }
__device__ __forceinline__ float4 lds128f(uint32_t a) { float4 v; asm volatile("ld.shared.v4.f32 {%0,%1,%2,%3}, [%4];" : "=f"(v.x), "=f"(v.y), "=f"(v.z), "=f"(v.w) : "r"(a) : "memory"); return v; }
__device__ __forceinline__ void sts16(uint32_t a, uint32_t v) { asm volatile("{ .reg .b16 l, h; mov.b32 {l, h}, %1; st.shared.b16 [%0], l; }" :: "r"(a), "r"(v) : "memory"); }
__device__ __forceinline__ void sts32(uint32_t a, uint32_t v) { asm volatile("st.shared.u32 [%0], %1;" :: "r"(a), "r"(v) : "memory"); }
__device__ __forceinline__ void sts64(uint32_t a, uint32_t x, uint32_t y) { asm volatile("st.shared.v2.u32 [%0], {%1,%2};" :: "r"(a), "r"(x), "r"(y) : "memory"); }
__device__ __forceinline__ void stsf(uint32_t a, float v) { asm volatile("st.shared.f32 [%0], %1;" :: "r"(a), "f"(v) : "memory"); }
__device__ __forceinline__ void sts128(uint32_t a, uint32_t x, uint32_t y, uint32_t z, uint32_t w) { asm volatile("st.shared.v4.u32 [%0], {%1,%2,%3,%4};" :: "r"(a), "r"(x), "r"(y), "r"(z), "r"(w) : "memory"); }
__device__ __forceinline__ void sts128f(uint32_t a, float x, float y, float z, float w) { asm volatile("st.shared.v4.f32 [%0], {%1,%2,%3,%4};" :: "r"(a), "f"(x), "f"(y), "f"(z), "f"(w) : "memory"); }
__device__ __forceinline__ void ldsm4(uint32_t (&r)[4], uint32_t a) { asm volatile("ldmatrix.sync.aligned.m8n8.x4.shared.b16 {%0,%1,%2,%3}, [%4];" : "=r"(r[0]), "=r"(r[1]), "=r"(r[2]), "=r"(r[3]) : "r"(a) : "memory"); }
__device__ __forceinline__ void ldsm4t(uint32_t (&r)[4], uint32_t a) { asm volatile("ldmatrix.sync.aligned.m8n8.x4.trans.shared.b16 {%0,%1,%2,%3}, [%4];" : "=r"(r[0]), "=r"(r[1]), "=r"(r[2]), "=r"(r[3]) : "r"(a) : "memory"); }
__device__ __forceinline__ void ldsm2t(uint32_t& r0, uint32_t& r1, uint32_t a) { asm volatile("ldmatrix.sync.aligned.m8n8.x2.trans.shared.b16 {%0,%1}, [%2];" : "=r"(r0), "=r"(r1) : "r"(a) : "memory"); }
__device__ __forceinline__ void stsm4t(uint32_t a, uint32_t r0, uint32_t r1, uint32_t r2, uint32_t r3) { asm volatile("stmatrix.sync.aligned.m8n8.x4.trans.shared.b16 [%0], {%1,%2,%3,%4};" :: "r"(a), "r"(r0), "r"(r1), "r"(r2), "r"(r3) : "memory"); }
__device__ __forceinline__ void stsm4(uint32_t a, uint32_t r0, uint32_t r1, uint32_t r2, uint32_t r3) { asm volatile("stmatrix.sync.aligned.m8n8.x4.shared.b16 [%0], {%1,%2,%3,%4};" :: "r"(a), "r"(r0), "r"(r1), "r"(r2), "r"(r3) : "memory"); }
__device__ __forceinline__ void stsm2t(uint32_t a, uint32_t r0, uint32_t r1) { asm volatile("stmatrix.sync.aligned.m8n8.x2.trans.shared.b16 [%0], {%1,%2};" :: "r"(a), "r"(r0), "r"(r1) : "memory"); }
__device__ __forceinline__ uint4 ldg128(const void* p) { uint4 v; asm volatile("ld.global.nc.v4.u32 {%0,%1,%2,%3}, [%4];" : "=r"(v.x), "=r"(v.y), "=r"(v.z), "=r"(v.w) : "l"(p)); return v; }
__device__ __forceinline__ uint32_t ldg16(const void* p) { unsigned short v; asm volatile("ld.global.nc.u16 %0, [%1];" : "=h"(v) : "l"(p)); return v; }
__device__ __forceinline__ uint32_t opaque(uint32_t v) { uint32_t r; asm volatile("mov.b32 %0, %1;" : "=r"(r) : "r"(v)); return r; }
__device__ __forceinline__ void mma_f16(float (&d)[4], const uint32_t (&a)[4], uint32_t b0, uint32_t b1) {
    asm volatile("mma.sync.aligned.m16n8k16.row.col.f32.f16.f16.f32 {%0,%1,%2,%3}, {%4,%5,%6,%7}, {%8,%9}, {%0,%1,%2,%3};"
        : "+f"(d[0]), "+f"(d[1]), "+f"(d[2]), "+f"(d[3]) : "r"(a[0]), "r"(a[1]), "r"(a[2]), "r"(a[3]), "r"(b0), "r"(b1));
}
__device__ __forceinline__ void mma_bf16(float (&d)[4], uint32_t a0, uint32_t a1, uint32_t a2, uint32_t a3, uint32_t b0, uint32_t b1) {
    asm volatile("mma.sync.aligned.m16n8k16.row.col.f32.bf16.bf16.f32 {%0,%1,%2,%3}, {%4,%5,%6,%7}, {%8,%9}, {%0,%1,%2,%3};"
        : "+f"(d[0]), "+f"(d[1]), "+f"(d[2]), "+f"(d[3]) : "r"(a0), "r"(a1), "r"(a2), "r"(a3), "r"(b0), "r"(b1));
}
__device__ __forceinline__ void mma_bf16_k8(float (&d)[4], uint32_t a0, uint32_t a1, uint32_t b0) {
    asm volatile("mma.sync.aligned.m16n8k8.row.col.f32.bf16.bf16.f32 {%0,%1,%2,%3}, {%4,%5}, {%6}, {%0,%1,%2,%3};"
        : "+f"(d[0]), "+f"(d[1]), "+f"(d[2]), "+f"(d[3]) : "r"(a0), "r"(a1), "r"(b0));
}
__device__ __forceinline__ uint32_t pack_f16(float lo, float hi) { uint32_t r; asm("cvt.rn.f16x2.f32 %0, %1, %2;" : "=r"(r) : "f"(hi), "f"(lo)); return r; }
__device__ __forceinline__ uint32_t pack_bf16(float lo, float hi) { uint32_t r; asm("cvt.rn.bf16x2.f32 %0, %1, %2;" : "=r"(r) : "f"(hi), "f"(lo)); return r; }
__device__ __forceinline__ float bf_lo(uint32_t v) { return __uint_as_float(v << 16); }
__device__ __forceinline__ float bf_hi(uint32_t v) { return __uint_as_float(v & 0xFFFF0000u); }
__device__ __forceinline__ float bfr(float x) { return __uint_as_float(pack_bf16(0.f, x)); }
__device__ __forceinline__ uint32_t bsub2(uint32_t a, uint32_t b) { uint32_t r; asm("sub.rn.bf16x2 %0, %1, %2;" : "=r"(r) : "r"(a), "r"(b)); return r; }
__device__ __forceinline__ uint32_t badd2(uint32_t a, uint32_t b) { uint32_t r; asm("add.rn.bf16x2 %0, %1, %2;" : "=r"(r) : "r"(a), "r"(b)); return r; }
__device__ __forceinline__ uint32_t bmul2(uint32_t a, uint32_t b) { uint32_t r; asm("mul.rn.bf16x2 %0, %1, %2;" : "=r"(r) : "r"(a), "r"(b)); return r; }
__device__ __forceinline__ uint32_t bfma2(uint32_t a, uint32_t b, uint32_t c) { uint32_t r; asm("fma.rn.bf16x2 %0, %1, %2, %3;" : "=r"(r) : "r"(a), "r"(b), "r"(c)); return r; }
__device__ __forceinline__ uint32_t hadd2(uint32_t a, uint32_t b) { uint32_t r; asm("add.rn.f16x2 %0, %1, %2;" : "=r"(r) : "r"(a), "r"(b)); return r; }
__device__ __forceinline__ uint32_t hmul2(uint32_t a, uint32_t b) { uint32_t r; asm("mul.rn.f16x2 %0, %1, %2;" : "=r"(r) : "r"(a), "r"(b)); return r; }
__device__ __forceinline__ uint32_t hfma2(uint32_t a, uint32_t b, uint32_t c) { uint32_t r; asm("fma.rn.f16x2 %0, %1, %2, %3;" : "=r"(r) : "r"(a), "r"(b), "r"(c)); return r; }
__device__ __forceinline__ uint32_t hneg2(uint32_t a) { uint32_t r; asm("neg.f16x2 %0, %1;" : "=r"(r) : "r"(a)); return r; }
__device__ __forceinline__ float rcpf(float x) { float r; asm("rcp.approx.ftz.f32 %0, %1;" : "=f"(r) : "f"(x)); return r; }
__device__ __forceinline__ float sqrta(float x) { float r; asm("sqrt.approx.ftz.f32 %0, %1;" : "=f"(r) : "f"(x)); return r; }
__device__ __forceinline__ float ex2f(float x) { float r; asm("ex2.approx.ftz.f32 %0, %1;" : "=f"(r) : "f"(x)); return r; }
__device__ __forceinline__ void st_async4(uint32_t a, uint32_t x, uint32_t y, uint32_t z, uint32_t w, uint32_t mb) {
    asm volatile("st.async.shared::cluster.mbarrier::complete_tx::bytes.v4.u32 [%0], {%1,%2,%3,%4}, [%5];" :: "r"(a), "r"(x), "r"(y), "r"(z), "r"(w), "r"(mb) : "memory"); }
__device__ __forceinline__ void st_async1(uint32_t a, uint32_t x, uint32_t mb) {
    asm volatile("st.async.shared::cluster.mbarrier::complete_tx::bytes.u32 [%0], %1, [%2];" :: "r"(a), "r"(x), "r"(mb) : "memory"); }
__device__ __forceinline__ unsigned ld_rlx(const void* p) { unsigned v; asm volatile("ld.relaxed.gpu.global.u32 %0, [%1];" : "=r"(v) : "l"(p) : "memory"); return v; }
__device__ __forceinline__ unsigned ld_acq(const void* p) { unsigned v; asm volatile("ld.acquire.gpu.global.u32 %0, [%1];" : "=r"(v) : "l"(p) : "memory"); return v; }
__device__ __forceinline__ uint2 ld_rlx64(const void* p) { unsigned long long v; asm volatile("ld.relaxed.gpu.global.u64 %0, [%1];" : "=l"(v) : "l"(p) : "memory"); return make_uint2((unsigned)v, (unsigned)(v >> 32)); }
__device__ __forceinline__ void st_rlx128(void* p, uint32_t x, uint32_t y, uint32_t z, uint32_t w) {
    asm volatile("st.relaxed.gpu.global.v2.u64 [%0], {%1,%2};" :: "l"(p), "l"((unsigned long long)x | ((unsigned long long)y << 32)), "l"((unsigned long long)z | ((unsigned long long)w << 32)) : "memory"); }
__device__ __forceinline__ uint4 ld_rlx128(const void* p) { unsigned long long a, b; asm volatile("ld.relaxed.gpu.global.v2.u64 {%0,%1}, [%2];" : "=l"(a), "=l"(b) : "l"(p) : "memory"); return make_uint4((unsigned)a, (unsigned)(a >> 32), (unsigned)b, (unsigned)(b >> 32)); }
__device__ __forceinline__ void tma2d(uint32_t dst, const CUtensorMap* tm, int x, int y, uint32_t mb) {
    asm volatile("cp.async.bulk.tensor.2d.shared::cluster.global.mbarrier::complete_tx::bytes [%0], [%1, {%3, %4}], [%2];"
                 :: "r"(dst), "l"(tm), "r"(mb), "r"(x), "r"(y) : "memory");
}
__device__ __forceinline__ void cmul(float& xr, float& xi, float ar, float ai, float br, float bi) {
    const float r = fmaf(ar, br, -ai * bi), i = fmaf(ar, bi, ai * br); xr = r; xi = i;
}
__device__ __forceinline__ void csq(float& xr, float& xi, float ar, float ai) {
    const float r = fmaf(ar, ar, -ai * ai), i = (ar + ar) * ai; xr = r; xi = i;
}
__device__ __forceinline__ void cexp_s(float& zr, float& zi, float e2, float turns) {
    const float mag = ex2f(e2), r = (turns - rintf(turns)) * 6.283185307179586f;
    zr = mag * __cosf(r); zi = mag * __sinf(r);
}
__device__ __forceinline__ uint32_t ln_stats(float s1, float s2) {
    const float m = s1 * (1.f / D_);
    const float var = fmaxf(fmaf(s2, 1.f / D_, -m * m), 0.f);
    return pack_bf16(m, sqrta(bfr(bfr(var) + 1e-5f)));
}
__device__ __forceinline__ uint32_t rsplit(float rs) { const float h = bfr(rs); return pack_bf16(h, rs - h); }
__device__ __forceinline__ uint32_t norm2(uint32_t v, uint32_t m2, uint32_t rh2, uint32_t rl2) {
    const uint32_t dd = bsub2(v, m2);
    return bfma2(dd, rh2, bmul2(dd, rl2));
}
__device__ __forceinline__ uint32_t norm2s(uint32_t v, uint32_t mh, uint32_t lx) {
    uint32_t r;
    asm("{ .reg .b16 m, h, l, x; .reg .b32 m2, h2, l2, d, t; mov.b32 {m, h}, %2; mov.b32 {l, x}, %3; mov.b32 m2, {m, m}; mov.b32 h2, {h, h}; mov.b32 l2, {l, l};\n"
        "sub.rn.bf16x2 d, %1, m2; mul.rn.bf16x2 t, d, l2; fma.rn.bf16x2 %0, d, h2, t; }" : "=r"(r) : "r"(v), "r"(mh), "r"(lx));
    return r;
}
template <int N>
__device__ __forceinline__ uint32_t rank4(uint32_t a, uint32_t key) {
    uint32_t r0 = 0, r1 = 0, r2 = 0, r3 = 0;
#pragma unroll
    for (int i = 0; i < N; i++) {
        const uint4 o = lds128(a + i * 16);
        r0 += (key - o.x) >> 31; r1 += (key - o.y) >> 31; r2 += (key - o.z) >> 31; r3 += (key - o.w) >> 31;
    }
    return (r0 + r1) + (r2 + r3);
}
struct H2C { uint32_t r, i; };
__device__ __forceinline__ H2C splat(float r, float i) { H2C h; h.r = pack_f16(r, r); h.i = pack_f16(i, i); return h; }
__device__ __forceinline__ void expand4(uint32_t are, uint32_t aim, uint32_t R0, uint32_t R1, uint32_t I0, uint32_t I1, H2C m4) {
    sts128(are, R0, R1, hfma2(R0, m4.r, hneg2(hmul2(I0, m4.i))), hfma2(R1, m4.r, hneg2(hmul2(I1, m4.i))));
    sts128(aim, I0, I1, hfma2(R0, m4.i, hmul2(I0, m4.r)), hfma2(R1, m4.i, hmul2(I1, m4.r)));
}
__device__ __forceinline__ void expand8(uint32_t are, uint32_t aim, float sr, float si, float m1r, float m1i, float m2r, float m2i, H2C m4) {
    float r1, i1, r2, i2, r3, i3;
    cmul(r1, i1, sr, si, m1r, m1i); cmul(r2, i2, sr, si, m2r, m2i); cmul(r3, i3, r1, i1, m2r, m2i);
    expand4(are, aim, pack_f16(sr, r1), pack_f16(r2, r3), pack_f16(si, i1), pack_f16(i2, i3), m4);
}
__device__ __forceinline__ void put16(uint32_t a, uint32_t v) { sts16(a, v); sts16(a + 6, v); }

struct Params {
    const unsigned short *x, *prm6[6], *logdt, *dskip, *wr;
    __nv_bfloat16* out;
    Scratch* gs;
    unsigned zero;
};
__device__ __forceinline__ uint32_t tslot(uint32_t t) { return (t & 7) * 32 + ((t >> 4) & 24) + ((t >> 8) & 6) + ((t >> 6) & 1); }
#define CP(x) ((x) | zero)
#define PIN(x) asm volatile("or.b32 %0, %0, %1;" : "+r"(x) : "r"(zero))
__device__ __forceinline__ void wgmma32(float (&d)[4][4], const uint32_t (&a)[4], uint32_t dlo) {
    asm volatile("{ .reg .b64 ds; mov.b64 ds, {%20, %21};\n"
                 "wgmma.mma_async.sync.aligned.m64n32k16.f32.f16.f16 {%0,%1,%2,%3,%4,%5,%6,%7,%8,%9,%10,%11,%12,%13,%14,%15}, {%16,%17,%18,%19}, ds, 1, 1, 1, 0; }"
        : "+f"(d[0][0]), "+f"(d[0][1]), "+f"(d[0][2]), "+f"(d[0][3]), "+f"(d[1][0]), "+f"(d[1][1]), "+f"(d[1][2]), "+f"(d[1][3]),
          "+f"(d[2][0]), "+f"(d[2][1]), "+f"(d[2][2]), "+f"(d[2][3]), "+f"(d[3][0]), "+f"(d[3][1]), "+f"(d[3][2]), "+f"(d[3][3])
        : "r"(a[0]), "r"(a[1]), "r"(a[2]), "r"(a[3]), "r"(dlo), "n"(128 >> 4));
}

__global__ void __cluster_dims__(CS, 1, 1) __launch_bounds__(NTHR, 1)
fused_kernel(const __grid_constant__ Params prm, const __grid_constant__ CUtensorMap tmG, const __grid_constant__ CUtensorMap tmU,
             const __grid_constant__ CUtensorMap tmD, const __grid_constant__ CUtensorMap tmO, const __grid_constant__ CUtensorMap tmX, const __grid_constant__ CUtensorMap tmH)
{
    extern __shared__ __align__(1024) unsigned char smem[];
    const int tid = threadIdx.x, lane = tid & 31, warp = __shfl_sync(~0u, tid >> 5, 0);
    const int c = blockIdx.x >> 3, q = blockIdx.x & 7;
    const int nslot = (c < NCL - 1) ? 5 : 2;
    const int d0 = 40 * c;
    const uint32_t sb = opaque((uint32_t)__cvta_generic_to_shared(smem));
    const uint32_t mb = sb + SM_MB;
    Scratch& g_s = *prm.gs;
    const unsigned& zero = prm.zero;
    STAMP(0);

    if (warp >= 20) {
        unsigned epoch = 0;
        if (warp == 20) {
            if (lane == 0) {
#pragma unroll
                for (int i = 0; i < 13; i++)
                    asm volatile("mbarrier.init.shared::cta.b64 [%0], %1;" :: "r"(mb + i * 8), "r"((i == MB_R || i < 2) ? 2 : i == MB_Y ? 1 + 4 * nslot : 1) : "memory");
                asm volatile("fence.mbarrier_init.release.cluster;" ::: "memory");
                arm(mb + MB_W1 * 8, 92160); arm(mb + MB_W2 * 8, nslot * 9216); arm(mb + MB_KEY * 8, 256); arm(mb + MB_GU * 8, nslot * 1024); arm(mb + MB_T * 8, 20480);
                const int bytes = max(min(18, L_ - 18 * (int)blockIdx.x), 1) * (D_ * 2);
                arm(mb + MB_R * 8, bytes);
            }
            __syncwarp();
        } else if (warp == 22) {
            epoch = ld_rlx(&g_s.epoch);
            if (lane < 18 ? 18 * c + lane < 256 : lane < 31) (lane < 18 ? &g_s.acc[256 * q + 18 * c] : &g_s.fin[13 * (int)blockIdx.x - 18])[lane] = make_float4(0.f, 0.f, 0.f, 0.f);
        } else if (warp == 23 && lane == 0) asm volatile("prefetch.tensormap [%0];" :: "l"(&tmX) : "memory");
        asm volatile("barrier.cluster.arrive.relaxed.aligned;" ::: "memory");
        bar_sync(12, NTHR);
        if (warp == 22) {
            if (lane == 0) { sts32(sb + SM_SC + 28, epoch); asm volatile("mbarrier.arrive.shared::cta.b64 _, [%0];" :: "r"(mb + MB_R * 8) : "memory"); }
            epoch++;
            asm volatile("fence.acq_rel.gpu;" ::: "memory");
            __syncwarp();
            if (lane == 0) asm volatile("red.relaxed.gpu.global.add.u32 [%0], 1;" :: "l"(&g_s.zcnt) : "memory");
            STAMP(1);
            uint4 wv = make_uint4(0, 0, 0, 0), wv2 = ldg128((const uint4*)prm.wr + lane), wv3 = ldg128((const uint4*)prm.wr + 32 + lane);
            if (lane < 8) wv = ldg128((const uint4*)prm.wr + 64 + lane);
            if (lane < 5) {
                uint4 v = make_uint4(0, 0, 0, 0);
                if (lane < nslot) v = ldg128((const uint4*)(prm.wr + d0) + lane);
                sts128(sb + SM_DW + lane * 16, v.x, v.y, v.z, v.w);
            }
            __syncwarp();
            if (lane < 2) asm volatile("mbarrier.arrive.shared::cta.b64 _, [%0];" :: "r"(mb + (MB_X + lane) * 8) : "memory");
            mbar_wait(mb + (MB_X + 1) * 8);
            const uint32_t old = (epoch & 1) ? 0u : 0x40004000u;
#pragma unroll
            for (int t = 0; t < 2; t++)
                if ((lane & 7) < 6) g_s.cand[((q * 8 + 4 * t + (lane >> 3)) * NCL + c) * 6 + (lane & 7)] = make_uint4(old, old, old, old);
            float a[4] = {0.f, 0.f, 0.f, 0.f};
            const uint32_t one = 0x3F803F80u;
            mma_bf16(a, one, one, one, one, wv.x, wv.y);  mma_bf16(a, one, one, one, one, wv.z, wv.w);
            mma_bf16(a, one, one, one, one, wv2.x, wv2.y); mma_bf16(a, one, one, one, one, wv2.z, wv2.w);
            mma_bf16(a, one, one, one, one, wv3.x, wv3.y); mma_bf16(a, one, one, one, one, wv3.z, wv3.w);
            float s = a[0] + a[1];
            s += __shfl_xor_sync(~0u, s, 1); s += __shfl_xor_sync(~0u, s, 2);
            stsf(sb + SM_SC + 24, s);
            __syncwarp();
            if (lane == 0) {
                int n = 0;
                while ((int)(ld_acq(&g_s.zcnt) - epoch * NCTA) < 0 && ++n < SPIN_LIMIT) __nanosleep(200);
                arm(mb + MB_Y * 8, 8 * 512 * nslot);
                if (blockIdx.x == 0) g_s.epoch = epoch;
            }
            STAMP(2);
            return;
        }
        if (warp == 21) {
            if (lane == 0) { asm volatile("prefetch.tensormap [%0];" :: "l"(&tmG) : "memory"); asm volatile("prefetch.tensormap [%0];" :: "l"(&tmU) : "memory"); asm volatile("prefetch.tensormap [%0];" :: "l"(&tmD) : "memory"); }
            __syncwarp();
            bar_sync(13, 736);
#pragma unroll 1
            for (int i = 0; i < 24; i++) {
                if (i == 13) { bar_sync(15, 544); asm volatile("fence.proxy.async.shared::cta;" ::: "memory"); }
                if (lane == 0) tma2d(sb + SM_WG + i * 3840, i < 12 ? &tmG : &tmU, 320 * c + 8 * nslot * q, 48 * (i < 12 ? i : i - 12), mb + MB_W1 * 8);
                __nanosleep(PACE_NS);
            }
            STAMP(1);
            return;
        }
        if (warp == 20) {
            if (lane == 0) {
                asm volatile("cp.async.bulk.shared::cluster.global.mbarrier::complete_tx::bytes [%0], [%1], %2, [%3];"
                             :: "r"(sb + SM_ROW), "l"(prm.x + min(18 * (int)blockIdx.x, L_ - 1) * D_), "r"(max(min(18, L_ - 18 * (int)blockIdx.x), 1) * (D_ * 2)), "r"(mb + MB_R * 8) : "memory");
            }
            __syncwarp();
            mbar_wait(mb + MB_R * 8);
            if (lane == 0) {
                asm volatile("cp.async.bulk.tensor.3d.shared::cluster.global.mbarrier::complete_tx::bytes [%0], [%1, {%3, %4, %5}], [%2];"
                             :: "r"(sb + SM_XTL), "l"(&tmX), "r"(mb + MB_T * 8), "r"(d0), "r"(8 * q), "r"(0) : "memory");
            }
            STAMP(6);
        }
        asm volatile("barrier.cluster.wait.aligned;" ::: "memory");
        bar_sync(13, 736);
        asm volatile("fence.proxy.async.shared::cta;" ::: "memory");
        {
            const int gr = lane >> 2, pe = (((lane & 3) ^ (gr * 3)) * 2 + (warp & 1)) & 7;
            const int s0 = gr ? 0 : XSPLIT, ns = gr ? min(XSPLIT, nslot) : nslot - XSPLIT;
            if (gr < 2 && ns > 0) {
                const int bytes = ns * YS - 160;
                if (pe == q) arm(mb + (MB_X + gr) * 8, 7 * bytes);
                else {
                    const uint32_t rb_ = mapa(sb, pe);
                    asm volatile("cp.async.bulk.shared::cluster.shared::cta.mbarrier::complete_tx::bytes [%0], [%1], %2, [%3];"
                                 :: "r"(rb_ + SM_U + 128 + q * UP + s0 * US), "r"(sb + SM_XT + 128 + pe * YP + s0 * YS), "r"(bytes), "r"(rb_ + SM_MB + (MB_X + gr) * 8) : "memory");
                }
            }
        }
        STAMP(1);
        if (warp == 20 && lane == 0) { asm volatile("prefetch.tensormap [%0];" :: "l"(&tmO) : "memory"); asm volatile("prefetch.tensormap [%0];" :: "l"(&tmH) : "memory"); }
        if (warp == 23) {
#pragma unroll 1
            for (int kk = nslot - 1; kk >= 0; kk--) {
                __syncwarp();
                bar_sync(6 + kk, 160);
                if (lane == 0) { asm volatile("fence.proxy.async.shared::cta;" ::: "memory"); tma2d(sb + SM_FAR + kk * FAR_SZ, &tmD, 72 * q, 320 * c + 64 * kk, mb + MB_W2 * 8); }
            }
            return;
        }
        __syncwarp();
        bar_sync(14, 672);
        if (lane == 0) {
            asm volatile("fence.proxy.async.shared::cta;" ::: "memory");
            asm volatile("cp.async.bulk.tensor.5d.global.shared::cta.bulk_group [%0, {%2, %4, %4, %4, %3}], [%1];" :: "l"(&tmH), "r"(sb + SM_XT + 16384), "r"(d0 + ((c & 1) ? 0 : 32)), "r"(8 * q), "r"(0) : "memory");
            asm volatile("cp.async.bulk.tensor.5d.global.shared::cta.bulk_group [%0, {%2, %4, %4, %4, %3}], [%1];" :: "l"(&tmO), "r"(sb + SM_XT), "r"(d0 + (c & 1) * 8), "r"(8 * q), "r"(0) : "memory");
            asm volatile("cp.async.bulk.commit_group;" ::: "memory");
            asm volatile("cp.async.bulk.wait_group 0;" ::: "memory");
            asm volatile("fence.proxy.async.global;" ::: "memory");
            asm volatile("mbarrier.arrive.shared::cta.b64 _, [%0];" :: "r"(mb + MB_OUT * 8) : "memory");
        }
        STAMP(2);
        return;
    }

    const int g = lane >> 2, cq = lane & 3;
    const int k = warp >> 2, wq = warp & 3;
    const int trow = 18 * blockIdx.x + warp;
    const bool rowact = warp < 18 && trow < L_;
    const int dch = min(d0 + 8 * k + q, D_ - 1);
    uint32_t pv[6];
#pragma unroll
    for (int i = 0; i < 6; i++) pv[i] = ldg16(prm.prm6[i] + (uint32_t)(dch * 128 + wq * 32 + lane));
    const uint32_t pLdt = ldg16(prm.logdt + dch), pD = ldg16(prm.dskip + dch);
    const int tn = 16 * (warp & 15) + g;
    uint32_t xa[5], xb[5];
    asm volatile("barrier.cluster.arrive.relaxed.aligned;" ::: "memory");
    uint4* const st1p = &g_s.st1[(((trow >> 3) & 7) * 256 + ((trow >> 6) & 31) * 8 + (trow & 7)) * 2 + (lane >> 2)];
    const bool pub = rowact && (lane & 0x1B) == 0;
    if (pub) st_rlx128(st1p, 0, 0, 0, 0);
    {
        const uint32_t za = sb + SM_P + tid * 16;
        sts128(za, 0, 0, 0, 0);
        if (tid < (SM_MISC - SM_P) / 16 - 640) sts128(za + 10240, 0, 0, 0, 0);
        sts128(sb + SM_XT + ((tid >> 3) & 15) * YP + k * YS + (lane & 7) * 16, 0, 0, 0, 0);
    }
    bar_sync(12, NTHR);
    const uint32_t dep = lds32(sb + SM_P);
#define PV(x) __uint_as_float(__byte_perm(dep, x, 0x5410))
    STAMP(1);
    const uint32_t fb = sb + SM_FAR + k * FAR_SZ;
    const uint32_t pn = sb + SM_PN + k * PN_SZ, pf = sb + SM_PF + k * PF_SZ;
    unsigned epoch;
    {
        const uint32_t kb = fb + wq * 3072;
        const uint32_t kl = kb + lane * 16;
        uint32_t Af[4][4];
        float sr, si, z1r, z1i, z2r, z2i, z4r, z4i, hr, hi_;
        {
            const float dt = bfr(ex2f(PV(pLdt) * 1.4426950408889634f));
            const float e2 = dt * PV(pv[0]) * 1.4426950408889634f, an = dt * PV(pv[1]);
            cmul(sr, si, PV(pv[4]), PV(pv[5]), dt * PV(pv[2]), dt * PV(pv[3]));
            const unsigned E = min(max(__reduce_max_sync(~0u, __float_as_uint(fmaxf(fmaxf(fabsf(sr), fabsf(si)), fabsf(PV(pD)) * (1.f / 8192.f)))) >> 23, 1u), 253u);
            const float sc = __uint_as_float((254u - E) << 23);
            sr *= sc; si *= -sc;
            sts64(sb + SM_KG + warp * 8, E, __reduce_add_sync(~0u, __float2int_rn(sr * 16777216.f)));
            float ar, ai, br, bi, cr, ci, dr, di;
            { const float m = ex2f(e2 * 8.f); ar = m * __cosf(an * 8.f); ai = m * __sinf(an * 8.f); }
            csq(br, bi, ar, ai); csq(cr, ci, br, bi); csq(dr, di, cr, ci);
            const H2C m4 = splat(cr, ci);
            {
                float r3, i3;
                cmul(r3, i3, ar, ai, br, bi);
                expand4(kl, kl + 1024, pack_f16(1.f, ar), pack_f16(br, r3), pack_f16(0.f, ai), pack_f16(bi, i3), m4);
            }
            expand8(kl + 512, kl + 1536, dr, di, ar, ai, br, bi, m4);
            { const float m = ex2f(e2); z1r = m * __cosf(an); z1i = -m * __sinf(an); }
            cexp_s(hr, hi_, e2 * 128.f, an * (-128.f * 0.15915494309189535f));
            csq(z2r, z2i, z1r, z1i); csq(z4r, z4i, z2r, z2i);
        }
        __syncwarp();
#pragma unroll
        for (int ks = 0; ks < 4; ks++) ldsm4t(Af[ks], kb + (lane >> 3) * 512 + (lane & 7) * 16 + ks * 128);
        STAMP(2);
        const uint32_t la = kb + ((lane >> 3) & 1) * 512 + (lane >> 4) * 128 + (lane & 7) * 16;
        uint32_t kp[5][2], b0[4], b1[4], b2[4], b3[4];
        auto mm2 = [&](int t) {
            float a0[4] = {0.f, 0.f, 0.f, 0.f}, a1[4] = {0.f, 0.f, 0.f, 0.f};
            mma_f16(a0, Af[0], b0[0], b0[1]); mma_f16(a1, Af[0], b2[0], b2[1]); mma_f16(a0, Af[1], b0[2], b0[3]); mma_f16(a1, Af[1], b2[2], b2[3]);
            mma_f16(a0, Af[2], b1[0], b1[1]); mma_f16(a1, Af[2], b3[0], b3[1]); mma_f16(a0, Af[3], b1[2], b1[3]); mma_f16(a1, Af[3], b3[2], b3[3]);
            kp[t][0] = pack_f16(a0[1], a0[0]); kp[t][1] = pack_f16(a0[3], a0[2]); kp[t + 1][0] = pack_f16(a1[1], a1[0]); kp[t + 1][1] = pack_f16(a1[3], a1[2]);
        };
        auto ln1 = [&]() {
        mbar_wait(mb + MB_R * 8);
        epoch = lds32(sb + SM_SC + 28) + 1;
        {
            const uint32_t ra = sb + SM_ROW + warp * (D_ * 2);
            const uint4 r0 = lds128(ra + lane * 16), r1 = lds128(ra + 512 + lane * 16);
            const uint32_t rx[9] = {r0.x, r0.y, r0.z, r0.w, r1.x, r1.y, r1.z, r1.w, lds32(ra + 1024 + lane * 4)};
            float a0 = bf_lo(rx[0]), a1 = bf_hi(rx[0]), c0 = a0 * a0, c1 = a1 * a1;
#pragma unroll
            for (int i = 1; i < 9; i++) { const float l = bf_lo(rx[i]), h = bf_hi(rx[i]); a0 += l; a1 += h; c0 = fmaf(l, l, c0); c1 = fmaf(h, h, c1); }
            a0 += a1; c0 += c1;
            float s1 = ((lane & 1) ? c0 : a0) + __shfl_xor_sync(~0u, (lane & 1) ? a0 : c0, 1);
#pragma unroll
            for (int o = 2; o < 32; o <<= 1) s1 += __shfl_xor_sync(~0u, s1, o);
            const float s2 = __shfl_xor_sync(~0u, s1, 1);
            const uint32_t ms = ln_stats(s1, s2);
            const uint32_t rs = rsplit(rcpf(bf_hi(ms))), p0 = __byte_perm(ms, rs, 0x5410), p1 = __byte_perm(rs, epoch | 0x8000u, 0x5432);
            if (pub) st_rlx128(st1p, p0, p1, p0, p1);
        }
        mbar_wait(mb + MB_R * 8);
        };
        const uint4* sp = &g_s.st1[(256 * q + tn) * 2];
        uint2 sa, sc;
        auto poll = [&]() { sa = ld_rlx64(sp); sc = ld_rlx64(sp + 16); };
        auto norm = [&]() {
        STAMP(3);
        if (warp < 16) {
            uint32_t va[5], vc[5];
            poll();
            mbar_wait(mb + MB_T * 8);
            {
                const uint32_t xt = sb + SM_XTL + tn * 80;
                uint4 a4 = lds128(xt + cq * 16), b4 = lds128(xt + cq * 16 + 640);
                va[0] = a4.x; va[1] = a4.y; va[2] = a4.z; va[3] = a4.w; va[4] = lds32(xt + 64 + cq * 4);
                vc[0] = b4.x; vc[1] = b4.y; vc[2] = b4.z; vc[3] = b4.w; vc[4] = lds32(xt + 704 + cq * 4);
            }
            const int d4 = 2 * (lane >> 3) + (lane & 1), d1_ = lane & 7;
            uint32_t a4 = sb + warp * 32 + d4 * YP + (d4 == q ? SM_U + 128 : SM_XT + 128) + ((lane & 7) >> 1) * YS;
            uint32_t a1 = sb + warp * 32 + d1_ * YP + (d1_ == q ? SM_U + 128 : SM_XT + 128) + 4 * YS + (lane & 8) * 2;
            PIN(a4); PIN(a1);
            const uint32_t tag = __byte_perm(epoch | 0x8000u, 0, 0x1010) | ((va[0] & va[4] & vc[0] & vc[4]) & zero);
            int n = 0;
            while (__byte_perm(sa.y, sc.y, 0x7632) != tag && ++n < SPIN_LIMIT) poll();
            STAMP(4);
#pragma unroll
            for (int i = 0; i < 5; i++) {
                va[i] = norm2s(va[i], sa.x, sa.y); va[i] = pack_f16(bf_lo(va[i]), bf_hi(va[i]));
                vc[i] = norm2s(vc[i], sc.x, sc.y); vc[i] = pack_f16(bf_lo(vc[i]), bf_hi(vc[i]));
            }
            stsm4t(a4, va[0], va[1], va[2], va[3]); stsm4t(a4 + 16, vc[0], vc[1], vc[2], vc[3]); stsm2t(a1, va[4], vc[4]);
        }
        bar_arrive(13, 736);
        if (warp < 16) {
            const uint32_t xh = sb + SM_XTL + (64 * (g >> 1) + 32 * (warp & 1) + 8 * (g & 1) + (warp >> 1)) * 80;
            const uint4 a4 = lds128(xh + cq * 16), b4 = lds128(xh + cq * 16 + 1280);
            xa[0] = a4.x; xa[1] = a4.y; xa[2] = a4.z; xa[3] = a4.w; xa[4] = lds32(xh + 64 + cq * 4);
            xb[0] = b4.x; xb[1] = b4.y; xb[2] = b4.z; xb[3] = b4.w; xb[4] = lds32(xh + 1344 + cq * 4);
            bar_arrive(15, 544);
        }
        STAMP(5);
        };
        if (LNPOS == 0) ln1();
        cmul(sr, si, sr, si, z1r, z1i);
        {
            const H2C h4 = splat(z4r, z4i);
            expand8(kl, kl + 512, sr, si, z1r, z1i, z2r, z2i, h4);
            cmul(sr, si, sr, si, hr, hi_);
            expand8(kl + 1024, kl + 1536, sr, si, z1r, z1i, z2r, z2i, h4);
        }
        __syncwarp();
        ldsm4t(b0, la); ldsm4t(b1, la + 256); ldsm4t(b2, la + 1024); ldsm4t(b3, la + 1280);
        cmul(z1r, z1i, z1r, z1i, hr, hi_);
        cmul(sr, si, sr, si, z1r, z1i);
        if (LNPOS == 1) ln1();
        expand8(kl, kl + 512, sr, si, z2r, z2i, z4r, z4i, splat(hr, hi_));
        if (LNPOS == 2) ln1();
        csq(z1r, z1i, z1r, z1i);
        cmul(sr, si, sr, si, z1r, z1i);
        csq(z2r, z2i, hr, hi_);
        expand8(kl + 1024, kl + 1536, sr, si, z4r, z4i, hr, hi_, splat(z2r, z2i));
        if (LNPOS == 3) ln1();
        csq(z1r, z1i, z1r, z1i);
        cmul(sr, si, sr, si, z1r, z1i);
        csq(z4r, z4i, z2r, z2i);
        expand8(kl + 2048, kl + 2560, sr, si, hr, hi_, z2r, z2i, splat(z4r, z4i));
        if (LNPOS == 4) ln1();
        if (MMPOS == 0) norm();
        mm2(0);
        __syncwarp();
        ldsm4t(b0, la); ldsm4t(b1, la + 256); ldsm4t(b2, la + 1024); ldsm4t(b3, la + 1280);
        if (MMPOS == 1) norm();
        mm2(2);
        if (MMPOS == 2) norm();
        ldsm4t(b0, la + 2048); ldsm4t(b1, la + 2304);
#pragma unroll
        for (int t = 0; t < 4; t++) sts64(kb + lane * 8 + 1024 + t * 256, kp[t][0], kp[t][1]);
        {
            float a0[4] = {0.f, 0.f, 0.f, 0.f}, a1[4] = {0.f, 0.f, 0.f, 0.f};
            mma_f16(a0, Af[0], b0[0], b0[1]); mma_f16(a1, Af[1], b0[2], b0[3]); mma_f16(a0, Af[2], b1[0], b1[1]); mma_f16(a1, Af[3], b1[2], b1[3]);
            sts64(kb + lane * 8 + 2048, pack_f16(a0[1] + a1[1], a0[0] + a1[0]), pack_f16(a0[3] + a1[3], a0[2] + a1[2]));
        }
        bar_sync(1 + k, 128);
        const uint4 m01 = lds128(sb + SM_KG + k * 32), m23 = lds128(sb + SM_KG + k * 32 + 16);
        const unsigned Em = max(max(m01.x, m01.z), max(m23.x, m23.z));
        const float f0 = __uint_as_float(max((int)(127 + m01.x - Em), 0) << 23), f1 = __uint_as_float(max((int)(127 + m01.z - Em), 0) << 23),
                    f2 = __uint_as_float(max((int)(127 + m23.x - Em), 0) << 23), f3 = __uint_as_float(max((int)(127 + m23.z - Em), 0) << 23);
        const uint32_t r0 = pack_f16(f0, f0), r1 = pack_f16(f1, f1), r2 = pack_f16(f2, f2), r3 = pack_f16(f3, f3);
        const uint32_t ra = fb + lane * 8 + wq * 256 + 1024;
        const uint2 p0 = lds64(ra), p1 = lds64(ra + 3072), p2 = lds64(ra + 6144), p3 = lds64(ra + 9216);
        uint32_t w0 = hadd2(hfma2(p0.x, r0, hmul2(p1.x, r1)), hfma2(p2.x, r2, hmul2(p3.x, r3)));
        uint32_t w1 = hadd2(hfma2(p0.y, r0, hmul2(p1.y, r1)), hfma2(p2.y, r2, hmul2(p3.y, r3)));
        const bool last = lane == 31;
        if (wq < 2) {
            const uint32_t rc = fb + lane * 8 + wq * 4 + 2048;
            const uint32_t w4 = hmul2(hadd2(hfma2(lds32(rc), r0, hmul2(lds32(rc + 3072), r1)), hfma2(lds32(rc + 6144), r2, hmul2(lds32(rc + 9216), r3))), 0x18001800u);
            const uint32_t ph = pf + (P_H7 + 16 * wq) + (g & 1) * (2 * P_HS) + cq * 64 + (g >> 1) * 4;
            put16(ph, w4 >> 16); put16(ph + 32, w4);
            const uint32_t pa = pn + (4 + 512 * wq) + lane * 8;
            sts16(pa, w0 >> 16); sts32(pa + 4, w0); sts16(pa + 10, w0);
            sts16(pa + 256, w1 >> 16); sts32(pa + 260, w1); sts16(pa + 266, w1);
            if (last) {
                sts32(sb + SM_SC + k * 4, Em * 0x00800080u);
                put16(wq ? pa + 264 : pn,
                      wq ? w1 : pack_f16(((float)(int)m01.y * f0 + (float)(int)m01.w * f1 + (float)(int)m23.y * f2 + (float)(int)m23.w * f3) * (1.f / 16777216.f)
                                         + __uint_as_float(pD << 16) * __uint_as_float((254u - Em) << 23), 0.f));
            }
        } else if (wq == 2) {
            const uint32_t pa = pn + 258 * 4 + (cq & 1) * 16 + (cq >> 1) * 512 + g * 32;
            if (last) { put16(pf, hmul2(w1, 0x18001800u)); w1 = hadd2(w1, hneg2(__byte_perm(w1, 0, 0x1010))); }
            const uint32_t b0 = __byte_perm(w0, 0, 0x1010), b1 = __byte_perm(w1, 0, 0x1010);
            sts16(pa, w0 >> 16); sts32(pa + 4, w0); sts64(pa + 8, b0, b0); sts16(pa + 18, w0);
            sts16(pa + 256, w1 >> 16); sts32(pa + 260, w1); sts64(pa + 264, b1, b1); sts16(pa + 274, w1);
        } else {
            const uint32_t pa = pf + ((g & 1) ? 3 * P_GS : P_GS) + cq * 32 + (g >> 1) * 4;
            const uint32_t pb = pa + ((g & 1) ? 4 - 3 * P_GS : P_GS);
            w0 = hmul2(w0, 0x18001800u); w1 = hmul2(w1, 0x18001800u);
            put16(pa, w0 >> 16); put16(pb, w0); put16(pa + 16, w1 >> 16); put16(pb + 16, w1);
            if (last) put16(pf + P_H7 + P_HS, w1);
        }
        bar_sync(1 + k, 128);
    }
    STAMP(6);

    asm volatile("barrier.cluster.wait.aligned;" ::: "memory");
    mbar_wait(mb + (MB_X + (k < XSPLIT || k >= nslot)) * 8);
    STAMP(7);
    if (k < nslot) {
        const int role = (wq + k) & 3;
        const uint32_t ub = sb + SM_U + k * US + 128;
        if (role) {
            const int r = (3 - role) * 32 + lane;
            const uint32_t a1 = ub + (r & 3) * (2 * UP) + (r >> 2) * 16, a0 = a1 + ((r & 3) ? -2 * UP : 6 * UP - 16);
            const uint4 q0 = lds128(a0), q1 = lds128(a0 + UP), q2 = lds128(a1), q3 = lds128(a1 + UP);
            const uint32_t U[16] = {q0.x, q0.y, q0.z, q0.w, q1.x, q1.y, q1.z, q1.w, q2.x, q2.y, q2.z, q2.w, q3.x, q3.y, q3.z, q3.w};
            uint32_t V[14], Q[14], R4[12], T[8];
#pragma unroll
            for (int i = 2; i < 14; i++) { V[i] = __byte_perm(U[i], U[i + 1], 0x5432); Q[i] = hadd2(U[i], V[i]); }
#pragma unroll
            for (int i = 2; i < 12; i++) R4[i] = hadd2(Q[i], Q[i + 1]);
            const uint32_t rb = fb + r * 16;
#pragma unroll
            for (int i = 0; i < 8; i++) T[i] = hadd2(V[5 + i], Q[6 + i]);
            sts128(rb + F_E3, T[0], T[1], T[2], T[3]); sts128(rb + F_O3 + 16, T[4], T[5], T[6], T[7]);
#pragma unroll
            for (int i = 0; i < 8; i++) T[i] = hadd2(R4[3 + i], U[5 + i]);
            sts128(rb + F_O5, T[0], T[1], T[2], T[3]); sts128(rb + F_E5, T[4], T[5], T[6], T[7]);
            if (role != 1) {
#pragma unroll
                for (int i = 0; i < 8; i++) T[i] = hadd2(T[i], hadd2(V[2 + i], V[5 + i]));
                sts128(rb + F_E7, T[0], T[1], T[2], T[3]); sts128(rb + F_O7, T[4], T[5], T[6], T[7]);
#pragma unroll
                for (int i = 0; i < 8; i++) T[i] = hadd2(R4[2 + i], hadd2(R4[4 + i], U[6 + i]));
                sts128(rb + F_O9, T[0], T[1], T[2], T[3]); sts128(rb + F_E9 + 16, T[4], T[5], T[6], T[7]);
                sts128(rb + F_E2, Q[6], Q[7], Q[8], Q[9]); sts128(rb + F_O2, Q[10], Q[11], Q[12], Q[13]);
            }
        } else if (lane < 8) {
            uint32_t v[5];
#pragma unroll
            for (int i = 0; i < 5; i++) { const int t = 6 + lane + i; v[i] = lds16(ub + 23 * 16 + (t < 16 ? (6 + (t >> 3)) * UP : 16) + (t & 7) * 2); }
            const uint32_t s = hadd2(hadd2(hadd2(v[0], v[1]), hadd2(v[2], v[3])), v[4]);
            sts16(fb + F_O5 + 96 * 16 + lane * 2, s);
            sts32(fb + (lane < 4 ? F_O3 : F_E9 - 16) + lane * 4, 0);
        }
        bar_sync(1 + k, 128);
        float acc[4][4];
        uint32_t Q[4][4];
        {
            const int h = role & 1, part = role >> 1;
            const uint32_t po = pf + (g - 2 * cq) * 4;
            float fa[7][4];
#pragma unroll
            for (int a = 0; a < 7; a++) fa[a][0] = fa[a][1] = fa[a][2] = fa[a][3] = 0.f;
            uint32_t B[3][4];
            Q[0][2] = zero;
#pragma unroll 1
            for (int s = 2 * part + 1; s >= 2 * part; s--) {
#pragma unroll
                for (int i = 0; i < 3; i++) { Q[i][0] = lds32(po + s * P_GS + i * 64); Q[i][1] = lds32(po + s * P_GS + (i * 64 + 32)); }
                const uint32_t ba = fb + lane * 16 + ((s & 1) * F_E3 + (part == h ? 0 : F_O5 + h * 16));
#pragma unroll
                for (int i = 0; i < 3; i++) ldsm4t(B[i], ba + i * 512);
#pragma unroll
                for (int i = 0; i < 3; i++) { Q[i][3] = CP(Q[i][0]); if (i) Q[i][2] = CP(Q[i - 1][1]); }
#pragma unroll
                for (int dl = 0; dl < 3; dl++)
#pragma unroll
                    for (int ap = 0; ap < 6 - dl; ap++) mma_f16(fa[ap + 1 + dl], Q[dl], B[ap >> 1][2 * (ap & 1)], B[ap >> 1][2 * (ap & 1) + 1]);
            }
#pragma unroll 1
            for (int s = role; s == 1; s++) {
                ldsm2t(B[0][0], B[0][1], fb + ((lane & 15) == 15 ? F_O5 : F_O3));
#pragma unroll
                for (int dl = 0; dl < 3; dl++) mma_f16(fa[dl], Q[dl], B[0][0], B[0][1]);
            }
#pragma unroll 1
            for (int s = part; s <= 2 * part; s++) {
#pragma unroll
                for (int i = 0; i < 4; i++) { Q[i][0] = lds32(po + s * P_HS + (P_H7 + i * 64)); Q[i][1] = lds32(po + s * P_HS + (P_H7 + i * 64 + 32)); }
                const uint32_t ba = fb + lane * 16 + (F_E7 + s * 1024 + h * F_H);
                ldsm4t(B[0], ba); ldsm4t(B[1], ba + 512);
#pragma unroll
                for (int i = 0; i < 4; i++) { Q[i][3] = CP(Q[i][0]); if (i) Q[i][2] = CP(Q[i - 1][1]); }
#pragma unroll
                for (int dl = 0; dl < 4; dl++) {
#pragma unroll
                    for (int ap = 0; ap < 4 - dl; ap++) mma_f16(fa[ap + 3 + dl], Q[dl], B[ap >> 1][2 * (ap & 1)], B[ap >> 1][2 * (ap & 1) + 1]);
                    if (s == 1) break;
                }
            }
            const uint32_t da = fb + role * 2048 + (lane & 3) * 512 + (((lane >> 2) ^ ((lane & 3) * 2)) << 4);
            bar_sync(1 + k, 128);
            stsm4(da, 0u, 0u, pack_f16(fa[0][0], fa[0][1]), pack_f16(fa[0][2], fa[0][3]));
#pragma unroll
            for (int i = 1; i < 4; i++)
                stsm4(da + i * 128, pack_f16(fa[2 * i - 1][0], fa[2 * i - 1][1]), pack_f16(fa[2 * i - 1][2], fa[2 * i - 1][3]),
                      pack_f16(fa[2 * i][0], fa[2 * i][1]), pack_f16(fa[2 * i][2], fa[2 * i][3]));
            Q[0][0] = (g == 2 * cq) ? 0x6000u : ((g == 2 * cq + 1) ? 0x60000000u : 0u);
            Q[0][1] = 0; Q[0][3] = CP(Q[0][0]);
            const uint32_t ra = fb + (lane >> 3) * 2048 + wq * 512 + (((lane & 7) ^ (wq * 2)) << 4);
            bar_sync(1 + k, 128);
#pragma unroll
            for (int i = 0; i < 4; i++) {
                ldsm4(B[0], ra + i * 128);
                acc[i][0] = acc[i][1] = acc[i][2] = acc[i][3] = 0.f;
                mma_f16(acc[i], Q[0], hadd2(B[0][0], B[0][2]), hadd2(B[0][1], B[0][3]));
            }
        }
        bar_arrive(6 + k, 160);
        STAMP(8);
        const uint32_t inv = lds32(sb + SM_SC + k * 4);
        uint32_t yd = mapa(sb, 2 * wq) + (SM_XT + 128 + q * YP + k * YS) + lane * 16;
        PIN(yd);
        {
            uint32_t pp = pn + (16 * (wq - 3) + g - 2 * cq) * 4;
            uint32_t dlo = (((ub + 6 * UP) & 0x3FFFF) >> 4) | ((UP >> 4) << 16);
            uint32_t R[4][4];
            auto loadQ = [&](uint32_t (&X)[4][4], uint32_t prev) {
#pragma unroll
                for (int i = 0; i < 4; i++) { X[i][0] = lds32(pp + i * 64); X[i][1] = lds32(pp + i * 64 + 32); }
                X[0][2] = CP(prev);
#pragma unroll
                for (int i = 0; i < 4; i++) { X[i][3] = CP(X[i][0]); if (i) X[i][2] = CP(X[i - 1][1]); }
                pp += 256;
            };
            auto issue = [&](uint32_t (&X)[4][4]) {
                asm volatile("wgmma.fence.sync.aligned;" ::: "memory");
#pragma unroll
                for (int i = 0; i < 4; i++) wgmma32(acc, X[i], dlo - i * (2 * UP >> 4));
                asm volatile("wgmma.commit_group.sync.aligned;" ::: "memory");
                dlo -= 1;
            };
            loadQ(Q, 0);
#pragma unroll 1
            for (int dl = 0; dl < 4; dl++) {
                issue(Q);
                asm volatile("wgmma.wait_group.sync.aligned 1;" ::: "memory");
                loadQ(R, Q[3][1]);
                issue(R);
                asm volatile("wgmma.wait_group.sync.aligned 1;" ::: "memory");
                loadQ(Q, R[3][1]);
            }
            issue(Q);
            asm volatile("wgmma.wait_group.sync.aligned 0;" ::: "memory");
        }
        const uint32_t pstep = mapa(sb, 1) - mapa(sb, 0), ym = mapa(mb + MB_Y * 8, 2 * wq);
#pragma unroll
        for (int e = 0; e < 2; e++)
            st_async4(yd + e * pstep, bmul2(pack_bf16(acc[0][2 * e], acc[0][2 * e + 1]), inv), bmul2(pack_bf16(acc[1][2 * e], acc[1][2 * e + 1]), inv),
                      bmul2(pack_bf16(acc[2][2 * e], acc[2][2 * e + 1]), inv), bmul2(pack_bf16(acc[3][2 * e], acc[3][2 * e + 1]), inv), ym + e * pstep);
        if (lane == 0) asm volatile("mbarrier.arrive.shared::cta.b64 _, [%0];" :: "r"(mb + MB_Y * 8) : "memory");
    }
    STAMP(9);
    uint32_t ha[5], hb[5];
    if (warp < 16) {
        const uint4 wk = lds128(sb + SM_DW + cq * 16);
        uint32_t sel[5] = {wk.x, wk.y, wk.z, wk.w, lds32(sb + SM_DW + 64 + cq * 4)}, sel2[5];
#pragma unroll
        for (int i = 0; i < 5; i++) {
            if (!(g & 1)) sel[i] = 0x3F803F80u;
            sel2[i] = sel[i]; PIN(sel2[i]);
        }
        const uint32_t y4 = sb + SM_XT + 128 + warp * 32 + (2 * (lane >> 3) + (lane & 1)) * YP + ((lane & 7) >> 1) * YS;
        const uint32_t y1 = sb + SM_XT + 128 + warp * 32 + (lane & 7) * YP + 4 * YS + (lane & 8) * 2;
        mbar_wait(mb + MB_Y * 8);
        STAMP(10);
        float ca[4] = {0.f, 0.f, 0.f, 0.f}, cb[4] = {0.f, 0.f, 0.f, 0.f};
        {
            uint32_t ya[4], yb[4], yc, yd;
            ldsm4t(ya, y4); ldsm4t(yb, y4 + 16); ldsm2t(yc, yd, y1);
#pragma unroll
            for (int i = 0; i < 4; i++) { ha[i] = badd2(xa[i], ya[i]); hb[i] = badd2(xb[i], yb[i]); }
            ha[4] = badd2(xa[4], yc); hb[4] = badd2(xb[4], yd);
        }
        if (nslot != 5) {
            ha[4] = hb[4] = 0;
            if (cq >= 2) ha[0] = ha[1] = ha[2] = ha[3] = hb[0] = hb[1] = hb[2] = hb[3] = 0;
        }
#pragma unroll
        for (int i = 0; i < 5; i++) { mma_bf16_k8(ca, ha[i], sel[i], ha[i]); mma_bf16_k8(cb, hb[i], sel2[i], hb[i]); }
        const float oa = __shfl_xor_sync(~0u, (g & 1) ? ca[2] : ca[3], 4), ob = __shfl_xor_sync(~0u, (g & 1) ? cb[2] : cb[3], 4);
        if (cq == (g >> 1)) {
            float4* ap = &g_s.acc[256 * q + tn];
            const bool od = g & 1;
            asm volatile("red.relaxed.gpu.global.add.v4.f32 [%0], {%1,%2,%3,%4};" :: "l"(ap), "f"(od ? oa : ca[2]), "f"(od ? ca[1] : ca[0]), "f"(od ? ca[3] : oa), "f"(1.0f) : "memory");
            asm volatile("red.relaxed.gpu.global.add.v4.f32 [%0], {%1,%2,%3,%4};" :: "l"(ap + 8), "f"(od ? ob : cb[2]), "f"(od ? cb[1] : cb[0]), "f"(od ? cb[3] : ob), "f"(1.0f) : "memory");
        }
        const uint32_t hta = sb + SM_HT + tn * 80;
        sts128(hta + cq * 16, ha[0], ha[1], ha[2], ha[3]); sts32(hta + 64 + cq * 4, ha[4]);
        sts128(hta + cq * 16 + 640, hb[0], hb[1], hb[2], hb[3]); sts32(hta + 704 + cq * 4, hb[4]);
        STAMP(11);
    }
    const int kq = warp / 5, mt = warp - 5 * kq;
    const int mi = lane >> 3, mr = lane & 7;
    const unsigned tk = (unsigned)tid / 72u, ck = tid - tk * 72;
    uint32_t A[9][4];
    auto loadA = [&]() {
        mbar_wait(mb + MB_W1 * 8);
        const uint32_t aa = sb + (mi & 1) * SM_WU + (8 * (mi >> 1) + mr) * 80 + (144 * 80 * kq + mt * 16);
#pragma unroll
        for (int s = 0; s < 9; s++) ldsm4t(A[s], aa + s * 1280);
    };
    const uint32_t par = (epoch & 1) ? 0x40004000u : 0u;
    uint32_t pk0 = mapa(sb, 2 * cq), go = (ck / 5u + ck) * 16, co = ((q * 8 * NCL + c) * 6 + cq) * 16;
    PIN(pk0); PIN(go); PIN(co);
    if (warp < 8) {
        const float wsum = ldsf(sb + SM_SC + 24);
        const uint32_t idx = 2047 - (512 * ((tid >> 1) & 3) + 128 * ((tid >> 3) & 3) + 64 * (tid & 1) + 8 * q + warp);
        uint4 s; int n = 0;
        do { s = ld_rlx128(&g_s.acc[256 * q + tid]); } while (__uint_as_float(s.w) != (float)NCL && ++n < SPIN_LIMIT);
        STAMP(16);
        const uint32_t ms = ln_stats(__uint_as_float(s.x), __uint_as_float(s.y));
        const float rs = rcpf(bf_hi(ms));
        const uint32_t rb = pack_bf16(0.f, fmaf(-bf_lo(ms), wsum, __uint_as_float(s.z)) * rs);
        const uint32_t key = (((rb ^ (((int)rb >> 31) | 0x80000000u)) >> 16) << 11) | idx;
        sts32(sb + SM_KEY + tid * 4, key);
        __syncwarp();
        const uint32_t rank = rank4<8>(sb + SM_KEY + warp * 128, key);
        if (rank < 8) sts32(sb + SM_CAND + warp * 32 + rank * 4, key);
        sts64(sb + SM_ST + tid * 8, __byte_perm(ms, 0, 0x1010), rsplit(rs));
    } else loadA();
    if (warp < 16) {
        STAMP(17);
        bar_sync(12, 512);
        STAMP(18);
        if (warp < 8) {
            const uint32_t mk = lds32(sb + SM_CAND + (tid >> 2) * 4);
            uint32_t rank = rank4<4>(sb + SM_CAND + cq * 64, mk);
            rank += __shfl_xor_sync(~0u, rank, 1); rank += __shfl_xor_sync(~0u, rank, 2);
            if (rank < 8) {
                const uint32_t pk1 = pk0 + (mapa(sb, 1) - mapa(sb, 0));
                st_async1(pk0 + (SM_RK + q * 32) + rank * 4, mk, pk0 + (SM_MB + MB_KEY * 8));
                st_async1(pk1 + (SM_RK + q * 32) + rank * 4, mk, pk1 + (SM_MB + MB_KEY * 8));
                const uint32_t t = tslot(~mk);
                const uint2 sv = lds64(sb + SM_ST + t * 8);
                const uint4 hv = lds128(sb + SM_HT + t * 80 + cq * 16);
                const uint32_t h4 = lds32(sb + SM_HT + t * 80 + 64 + cq * 4);
                const uint32_t rr = bmul2(sv.y, 0x3C803C80u), rh = __byte_perm(rr, 0, 0x1010), rl = __byte_perm(rr, 0, 0x3232);
                char* const dp = (char*)g_s.cand + (co + rank * 1440);
                st_rlx128(dp, (norm2(hv.x, sv.x, rh, rl) & 0xBFFFBFFFu) | par, (norm2(hv.y, sv.x, rh, rl) & 0xBFFFBFFFu) | par,
                          (norm2(hv.z, sv.x, rh, rl) & 0xBFFFBFFFu) | par, (norm2(hv.w, sv.x, rh, rl) & 0xBFFFBFFFu) | par);
                asm volatile("st.relaxed.gpu.global.u32 [%0], %1;" :: "l"((char*)g_s.cand + (co + rank * 1440 + 64 - cq * 12)), "r"((norm2(h4, sv.x, rh, rl) & 0xBFFFBFFFu) | par) : "memory");
            }
            __syncwarp();
        }
        {
            const uint2 sa = lds64(sb + SM_ST + tn * 8), sbb = lds64(sb + SM_ST + tn * 8 + 64);
            const uint32_t rha = __byte_perm(sa.y, 0, 0x1010), rla = __byte_perm(sa.y, 0, 0x3232);
            const uint32_t rhb = __byte_perm(sbb.y, 0, 0x1010), rlb = __byte_perm(sbb.y, 0, 0x3232);
#pragma unroll
            for (int i = 0; i < 5; i++) { ha[i] = badd2(ha[i], norm2(ha[i], sa.x, rha, rla)); hb[i] = badd2(hb[i], norm2(hb[i], sbb.x, rhb, rlb)); }
            const bool hf = (c & 1) && cq == 0;
            const uint32_t o16 = sb + SM_XT + (hf ? 16384 + tn * 16 : tn * 64 + (cq - (c & 1)) * 16), o4 = sb + SM_XT + ((c & 1) ? tn * 64 + 48 : 16384 + tn * 16) + cq * 4;
            sts128(o16, ha[0], ha[1], ha[2], ha[3]); sts32(o4, ha[4]);
            sts128(o16 + (hf ? 128 : 512), hb[0], hb[1], hb[2], hb[3]); sts32(o4 + ((c & 1) ? 512 : 128), hb[4]);
        }
        if (warp >= 8) {
            STAMP(19);
            mbar_wait(mb + MB_KEY * 8);
            STAMP(20);
            const uint32_t mk = lds32(sb + SM_RK - 256 + (tid >> 2) * 4);
            uint32_t rank = rank4<4>(sb + SM_RK + cq * 64, mk);
            rank += __shfl_xor_sync(~0u, rank, 1); rank += __shfl_xor_sync(~0u, rank, 2);
            if (rank < 8) sts64(sb + SM_SEL + rank * 8, mk, ((tid >> 2) - 64) * 1440);
        }
    }
    bar_sync(11, 640);
    STAMP(12);

    const char* gp = (const char*)g_s.cand + (go + lds32(sb + SM_SEL + 4 + (tk & 7) * 8));
    uint4 hv = ld_rlx128(gp);
    if (warp < 8) loadA();
    const bool red = warp < 6;
    const uint32_t ft = red ? (unsigned)tid / 24u : (unsigned)(tid >> 4) & 7u, fj = red ? 24 * q + tid - ft * 24 : d0 / 3 + (lane & 15);
    const uint32_t key = lds32(sb + SM_SEL + ft * 8), k16 = key << 5;
    float sig = bfr(rcpf(1.f + ex2f(__uint_as_float((k16 ^ (~((int)k16 >> 31) | 0x80000000u)) & 0xFFFF0000u) * -1.4426950408889634f)));
    uint32_t ra2 = sb + SM_RED2 + tid * 12 + ft * 16, fo = (ft * 192 + fj) * 16, oo = ((~key & 2047) * D_ + 3 * fj) * 2;
    uint32_t bx = sb + SM_XS + mr * 1168 + mi * 16 + 288 * kq, gd = mapa(sb, kq * (8 / NRED)) + (SM_GU + (q * nslot + mt) * 128) + lane * 4;
    PIN(ra2); PIN(fo); PIN(oo); PIN(bx); PIN(gd);
    asm volatile("" : "+f"(sig));
    {
        if (warp < 18) {
            int n = 0;
            while ((((hv.x ^ par) | (hv.y ^ par) | (hv.z ^ par) | (hv.w ^ par)) & 0x40004000u) && ++n < SPIN_LIMIT) hv = ld_rlx128(gp);
            sts128(sb + SM_XS + tk * 16 + tid * 16, hv.x ^ par, hv.y ^ par, hv.z ^ par, hv.w ^ par);
        }
    }
    bar_sync(14, 672);
    STAMP(13);
    {
        float c0[4] = {0.f, 0.f, 0.f, 0.f}, c1[4] = {0.f, 0.f, 0.f, 0.f}, c2[4] = {0.f, 0.f, 0.f, 0.f};
        uint32_t b[5][4];
#pragma unroll
        for (int s = 0; s < 4; s++) ldsm4(b[s], bx + s * 64);
        asm volatile("ldmatrix.sync.aligned.m8n8.x2.shared.b16 {%0,%1}, [%2];" : "=r"(b[4][0]), "=r"(b[4][1]) : "r"(bx + 256) : "memory");
        mma_bf16(c0, A[0][0], A[0][1], A[0][2], A[0][3], b[0][0], b[0][1]);
        mma_bf16(c1, A[1][0], A[1][1], A[1][2], A[1][3], b[0][2], b[0][3]);
        mma_bf16(c2, A[2][0], A[2][1], A[2][2], A[2][3], b[1][0], b[1][1]);
        mma_bf16(c0, A[3][0], A[3][1], A[3][2], A[3][3], b[1][2], b[1][3]);
        mma_bf16(c1, A[4][0], A[4][1], A[4][2], A[4][3], b[2][0], b[2][1]);
        mma_bf16(c2, A[5][0], A[5][1], A[5][2], A[5][3], b[2][2], b[2][3]);
        mma_bf16(c0, A[6][0], A[6][1], A[6][2], A[6][3], b[3][0], b[3][1]);
        mma_bf16(c1, A[7][0], A[7][1], A[7][2], A[7][3], b[3][2], b[3][3]);
        mma_bf16(c2, A[8][0], A[8][1], A[8][2], A[8][3], b[4][0], b[4][1]);
        sts128f(sb + SM_RED + tid * 16, c0[0] + c1[0] + c2[0], c0[1] + c1[1] + c2[1], c0[2] + c1[2] + c2[2], c0[3] + c1[3] + c2[3]);
    }
    bar_sync(1 + mt, 128);
    STAMP(21);
    if (mt < nslot && kq < NRED) {
        const uint32_t ra = sb + SM_RED + mt * 512 + lane * 16;
        const float4 p0 = lds128f(ra), p1 = lds128f(ra + 2560), p2 = lds128f(ra + 5120), p3 = lds128f(ra + 7680);
        const float g0 = bfr(((p0.x + p1.x) + (p2.x + p3.x)) * 64.f), g1 = bfr(((p0.y + p1.y) + (p2.y + p3.y)) * 64.f);
        const uint32_t sg = pack_bf16(g0 * rcpf(1.f + ex2f(g0 * -1.4426950408889634f)), g1 * rcpf(1.f + ex2f(g1 * -1.4426950408889634f)));
        const uint32_t gu = bmul2(sg, pack_bf16(((p0.z + p1.z) + (p2.z + p3.z)) * 64.f, ((p0.w + p1.w) + (p2.w + p3.w)) * 64.f));
        const uint32_t pstep = mapa(sb, 1) - mapa(sb, 0), gm = mapa(mb + MB_GU * 8, kq * (8 / NRED));
#pragma unroll
        for (int i = 0; i < 8 / NRED; i++) st_async1(gd + i * pstep, gu, gm + i * pstep);
    }
    mbar_wait(mb + MB_W2 * 8);
    {
        const uint32_t aa = sb + (8 * (mi >> 1) + mr) * 144 + (mi & 1) * 16 + (SM_FAR + 2304 * kq + mt * 32);
#pragma unroll
        for (int s = 0; s < 5; s++) ldsm4t(A[s], aa + s * FAR_SZ);
    }
    {
        uint32_t ba = sb + (SM_GU + 256 * kq) + (lane & 15) * 16 + (lane >> 4) * 1024, wa = sb + (SM_RED2 + kq * 2432 + mt * 64) + g * 4 + cq * 608;
        PIN(ba); PIN(wa);
        STAMP(22);
        mbar_wait(mb + MB_GU * 8);
        STAMP(23);
        float c0[4] = {0.f, 0.f, 0.f, 0.f}, c1[4] = {0.f, 0.f, 0.f, 0.f}, c2[4] = {0.f, 0.f, 0.f, 0.f};
        uint32_t b[2][4], b8, b9;
        ldsm4t(b[0], ba); ldsm4t(b[1], ba + 2048); ldsm2t(b8, b9, ba + 4096);
        mma_bf16(c0, A[0][0], A[0][1], A[0][2], A[0][3], b[0][0], b[0][1]);
        mma_bf16(c1, A[1][0], A[1][1], A[1][2], A[1][3], b[0][2], b[0][3]);
        if (nslot == 5) {
            mma_bf16(c2, A[4][0], A[4][1], A[4][2], A[4][3], b8, b9);
            mma_bf16(c0, A[2][0], A[2][1], A[2][2], A[2][3], b[1][0], b[1][1]);
            mma_bf16(c1, A[3][0], A[3][1], A[3][2], A[3][3], b[1][2], b[1][3]);
        }
        stsf(wa, c0[0] + c1[0] + c2[0]); stsf(wa + 304, c0[1] + c1[1] + c2[1]);
        if (mt < 4) { stsf(wa + 32, c0[2] + c1[2] + c2[2]); stsf(wa + 336, c0[3] + c1[3] + c2[3]); }
    }
    if (warp < 10) {
        float v[3], cnt = 3.f;
        if (red) {
            bar_sync(6, 640);
            STAMP(14);
#pragma unroll
            for (int i = 0; i < 3; i++) v[i] = ((ldsf(ra2 + i * 4) + ldsf(ra2 + i * 4 + 2432)) + (ldsf(ra2 + i * 4 + 4864) + ldsf(ra2 + i * 4 + 7296))) * sig;
        } else {
            bar_arrive(6, 640);
            cnt = 0.f;
#pragma unroll
            for (int i = 0; i < 3; i++) {
                const uint32_t cl = 3 * fj + i - d0;
                const bool ok = cl < 8 * nslot && ((~key >> 3) & 7) == q;
                const uint32_t cf = cl - (c & 1) * 8;
                v[i] = ok ? __uint_as_float(lds16(sb + SM_XT + (cf < 32 ? tslot(~key) * 64 + cf * 2 : 16384 + tslot(~key) * 16 + (cl & 7) * 2)) << 16) : 0.f;
                if (ok) cnt += 1.f;
            }
            mbar_wait(mb + MB_OUT * 8);
        }
        if (cnt != 0.f) {
            float x, y, z, w;
            asm volatile("atom.relaxed.gpu.global.add.v4.f32 {%0,%1,%2,%3}, [%4], {%5,%6,%7,%8};" : "=f"(x), "=f"(y), "=f"(z), "=f"(w)
                         : "l"((char*)g_s.fin + fo), "f"(v[0]), "f"(v[1]), "f"(v[2]), "f"(cnt) : "memory");
            if (w + cnt == 3.f * (NCL + 1)) {
                __nv_bfloat16* op = (__nv_bfloat16*)((char*)prm.out + oo);
                op[0] = __float2bfloat16(x + v[0]); op[1] = __float2bfloat16(y + v[1]); op[2] = __float2bfloat16(z + v[2]);
            }
        }
    } else bar_arrive(6, 640);
    STAMP(15);
}

typedef CUresult (*EncodeFn)(CUtensorMap*, CUtensorMapDataType, cuuint32_t, void*, const cuuint64_t*, const cuuint64_t*,
                             const cuuint32_t*, const cuuint32_t*, CUtensorMapInterleave, CUtensorMapSwizzle,
                             CUtensorMapL2promotion, CUtensorMapFloatOOBfill);

void make_map(EncodeFn fn, CUtensorMap* tm, const void* p, int cols, int rows, int bc, int br) {
    cuuint64_t dims[2] = {(cuuint64_t)cols, (cuuint64_t)rows};
    cuuint64_t strides[1] = {(cuuint64_t)cols * 2};
    cuuint32_t box[2] = {(cuuint32_t)bc, (cuuint32_t)br};
    cuuint32_t es[2] = {1, 1};
    fn(tm, CU_TENSOR_MAP_DATA_TYPE_BFLOAT16, 2, const_cast<void*>(p), dims, strides, box, es, CU_TENSOR_MAP_INTERLEAVE_NONE,
       CU_TENSOR_MAP_SWIZZLE_NONE, CU_TENSOR_MAP_L2_PROMOTION_L2_128B, CU_TENSOR_MAP_FLOAT_OOB_FILL_NONE);
}

void make_map3(EncodeFn fn, CUtensorMap* tm, const void* p) {
    cuuint64_t dims[3] = {(cuuint64_t)D_, 64, 32};
    cuuint64_t strides[2] = {(cuuint64_t)D_ * 2, (cuuint64_t)D_ * 128};
    cuuint32_t box[3] = {40, 8, 32};
    cuuint32_t es[3] = {1, 1, 1};
    fn(tm, CU_TENSOR_MAP_DATA_TYPE_BFLOAT16, 3, const_cast<void*>(p), dims, strides, box, es, CU_TENSOR_MAP_INTERLEAVE_NONE,
       CU_TENSOR_MAP_SWIZZLE_NONE, CU_TENSOR_MAP_L2_PROMOTION_NONE, CU_TENSOR_MAP_FLOAT_OOB_FILL_NONE);
}

void make_map5(EncodeFn fn, CUtensorMap* tm, const void* p, int bc) {
    cuuint64_t dims[5] = {(cuuint64_t)D_, 2, 4, 4, 64};
    cuuint64_t strides[4] = {(cuuint64_t)D_ * 128, (cuuint64_t)D_ * 1024, (cuuint64_t)D_ * 256, (cuuint64_t)D_ * 2};
    cuuint32_t box[5] = {(cuuint32_t)bc, 2, 4, 4, 8};
    cuuint32_t es[5] = {1, 1, 1, 1, 1};
    fn(tm, CU_TENSOR_MAP_DATA_TYPE_BFLOAT16, 5, const_cast<void*>(p), dims, strides, box, es, CU_TENSOR_MAP_INTERLEAVE_NONE,
       CU_TENSOR_MAP_SWIZZLE_NONE, CU_TENSOR_MAP_L2_PROMOTION_NONE, CU_TENSOR_MAP_FLOAT_OOB_FILL_NONE);
}

}

extern "C" void kernel_launch(void* const* d_in, const int* in_sizes, int n_in, void* d_out, int out_size) {
    (void)in_sizes; (void)n_in; (void)out_size;
    void* fp = nullptr;
    cudaDriverEntryPointQueryResult qr;
    cudaGetDriverEntryPoint("cuTensorMapEncodeTiled", &fp, cudaEnableDefault, &qr);
    EncodeFn fn = (EncodeFn)fp;
    CUtensorMap tmG, tmU, tmD, tmO, tmX, tmH;
    make_map3(fn, &tmX, d_in[0]);
    make_map(fn, &tmG, d_in[11], F_, D_, 40, 48);
    make_map(fn, &tmU, d_in[12], F_, D_, 40, 48);
    make_map(fn, &tmD, d_in[13], D_, F_, 72, 64);
    make_map5(fn, &tmO, d_out, 32);
    make_map5(fn, &tmH, d_out, 8);
    Params p;
    p.x = (const unsigned short*)d_in[0];
    for (int i = 0; i < 6; i++) p.prm6[i] = (const unsigned short*)d_in[1 + i];
    p.logdt = (const unsigned short*)d_in[7]; p.dskip = (const unsigned short*)d_in[8];
    p.wr = (const unsigned short*)d_in[10];
    p.out = (__nv_bfloat16*)d_out;
    p.zero = 0;
    cudaGetSymbolAddress((void**)&p.gs, g_s);
    cudaFuncSetAttribute(fused_kernel, cudaFuncAttributeMaxDynamicSharedMemorySize, SM_TOTAL);
    fused_kernel<<<NCTA, NTHR, SM_TOTAL>>>(p, tmG, tmU, tmD, tmO, tmX, tmH);
}
```

```cpp
#include <cuda_runtime.h>
#include <cuda_bf16.h>
#include <cuda_fp16.h>
#include <cuda.h>
#include <stdint.h>

namespace {

constexpr int L_ = 2048, D_ = 576, F_ = 4608;
constexpr int NCL = 15, CS = 8, NCTA = NCL * CS, NTHR = 768;
#define PACE_NS 0
#define AFTERX 0
#define EARLYB 0
#define GAP_NS 0
#define PACE0 200
#define W2W 72
#define ROWE 0
#define LNPOS 1
#define MMPOS 0
constexpr int XSPLIT = 3, NRED = 2;
constexpr int SPIN_LIMIT = 1 << 22;

constexpr int SM_WG   = 0;
constexpr int SM_WU   = 46080;
constexpr int YP = 3376, YS = 672;
constexpr int UP = 3376, US = 672;
constexpr int SM_XT   = 92160;
constexpr int SM_U    = SM_XT + 8 * YP;
constexpr int SM_FAR  = SM_U + 8 * UP;
constexpr int FAR_SZ  = 12416;
constexpr int F_E5 = 0, F_O5 = 1536, F_E3 = 3088, F_O3 = 4624, F_E7 = 6176, F_E2 = F_E7 + 1024, F_E9 = F_E7 + 2048,
              F_H = 3088, F_O7 = F_E7 + F_H, F_O2 = F_E2 + F_H, F_O9 = F_E9 + F_H;
constexpr int SM_P    = SM_FAR + 5 * FAR_SZ;
constexpr int PN_SZ = 584 * 4, SM_PN = SM_P + 64 * 4;
constexpr int P_GS = 48 * 4, P_H7 = 192 * 4, P_HS = 72 * 4;
constexpr int PF_SZ = (192 + 216) * 4, SM_PF = SM_PN + 5 * PN_SZ + 32;
constexpr int SM_MISC = SM_PF + 5 * PF_SZ;
constexpr int SM_ST   = SM_MISC;
constexpr int SM_RK   = SM_ST + 2048;
constexpr int SM_SEL  = SM_RK + 256;
constexpr int SM_KG   = SM_SEL + 64;
constexpr int SM_SC   = SM_KG + 160;
constexpr int SM_DW   = SM_SC + 32;
constexpr int SM_MB   = SM_DW + 160;
constexpr int SM_TOTAL = SM_MB + 128;
constexpr int SM_ROW  = SM_XT - 20736;
constexpr int SM_XTL  = SM_ROW - 20480;
constexpr int SM_RED2 = SM_WG;
constexpr int SM_HT   = SM_P - 512;
constexpr int SM_KEY  = SM_FAR + 10240 + 128;
constexpr int SM_CAND = SM_KEY + 1024;
constexpr int SM_XS   = SM_U;
constexpr int SM_GU   = SM_XS + 9344;
constexpr int SM_RED  = SM_GU + 5632;
static_assert(F_O9 + 1024 <= FAR_SZ && FAR_SZ % 128 == 0, "far overflow");
static_assert(SM_RED + 10240 <= SM_FAR && SM_HT + 20496 <= SM_MISC, "alias overflow");
static_assert(SM_TOTAL <= 232448, "smem overflow");
static_assert(SM_FAR % 128 == 0 && SM_XT % 128 == 0 && SM_XTL % 128 == 0 && SM_P % 16 == 0 && SM_MISC % 16 == 0 && SM_MB % 8 == 0, "align");

enum { MB_X = 0, MB_W1 = 5, MB_W2 = 6, MB_KEY = 7, MB_GU = 8, MB_Y = 9, MB_OUT = 10, MB_T = 11, MB_R = 12 };

struct __align__(128) Scratch {
    unsigned epoch, zcnt, pad[30];
    uint4  st1[L_ * 2];
    float4 acc[L_];
    uint4  cand[64 * NCL * 6];
    float4 fin[8 * 192 + 24];
};
__device__ Scratch g_s;
#define STAMP(i)

__device__ __forceinline__ uint32_t mapa(uint32_t a, uint32_t r) { uint32_t d; asm("mapa.shared::cluster.u32 %0, %1, %2;" : "=r"(d) : "r"(a), "r"(r)); return d; }
__device__ __forceinline__ void mbar_wait(uint32_t mb) {
    asm volatile("{ .reg .pred p, q; .reg .u32 n; mov.u32 n, 0;\n"
                 "W_%=: mbarrier.try_wait.parity.shared::cta.b64 p, [%0], 0; add.u32 n, n, 1; setp.lt.and.u32 q, n, 65536, !p; @q bra W_%=; }" :: "r"(mb) : "memory");
}
__device__ __forceinline__ void arm(uint32_t mb, uint32_t bytes) { asm volatile("mbarrier.arrive.expect_tx.shared::cta.b64 _, [%0], %1;" :: "r"(mb), "r"(bytes) : "memory"); }
__device__ __forceinline__ void bar_sync(int id, int n) { asm volatile("bar.sync %0, %1;" :: "r"(id), "r"(n) : "memory"); }
__device__ __forceinline__ void bar_arrive(int id, int n) { asm volatile("bar.arrive %0, %1;" :: "r"(id), "r"(n) : "memory"); }
__device__ __forceinline__ uint32_t lds16(uint32_t a) { unsigned short v; asm volatile("ld.shared.u16 %0, [%1];" : "=h"(v) : "r"(a) : "memory"); return v; }
__device__ __forceinline__ uint32_t lds32(uint32_t a) { uint32_t v; asm volatile("ld.shared.u32 %0, [%1];" : "=r"(v) : "r"(a) : "memory"); return v; }
__device__ __forceinline__ uint2 lds64(uint32_t a) { uint2 v; asm volatile("ld.shared.v2.u32 {%0,%1}, [%2];" : "=r"(v.x), "=r"(v.y) : "r"(a) : "memory"); return v; }
__device__ __forceinline__ float ldsf(uint32_t a) { float v; asm volatile("ld.shared.f32 %0, [%1];" : "=f"(v) : "r"(a) : "memory"); return v; }
__device__ __forceinline__ uint4 lds128(uint32_t a) { uint4 v; asm volatile("ld.shared.v4.u32 {%0,%1,%2,%3}, [%4];" : "=r"(v.x), "=r"(v.y), "=r"(v.z), "=r"(v.w) : "r"(a) : "memory"); return v; }
__device__ __forceinline__ float4 lds128f(uint32_t a) { float4 v; asm volatile("ld.shared.v4.f32 {%0,%1,%2,%3}, [%4];" : "=f"(v.x), "=f"(v.y), "=f"(v.z), "=f"(v.w) : "r"(a) : "memory"); return v; }
__device__ __forceinline__ void sts16(uint32_t a, uint32_t v) { asm volatile("{ .reg .b16 l, h; mov.b32 {l, h}, %1; st.shared.b16 [%0], l; }" :: "r"(a), "r"(v) : "memory"); }
__device__ __forceinline__ void sts32(uint32_t a, uint32_t v) { asm volatile("st.shared.u32 [%0], %1;" :: "r"(a), "r"(v) : "memory"); }
__device__ __forceinline__ void sts64(uint32_t a, uint32_t x, uint32_t y) { asm volatile("st.shared.v2.u32 [%0], {%1,%2};" :: "r"(a), "r"(x), "r"(y) : "memory"); }
__device__ __forceinline__ void stsf(uint32_t a, float v) { asm volatile("st.shared.f32 [%0], %1;" :: "r"(a), "f"(v) : "memory"); }
__device__ __forceinline__ void sts128(uint32_t a, uint32_t x, uint32_t y, uint32_t z, uint32_t w) { asm volatile("st.shared.v4.u32 [%0], {%1,%2,%3,%4};" :: "r"(a), "r"(x), "r"(y), "r"(z), "r"(w) : "memory"); }
__device__ __forceinline__ void sts128f(uint32_t a, float x, float y, float z, float w) { asm volatile("st.shared.v4.f32 [%0], {%1,%2,%3,%4};" :: "r"(a), "f"(x), "f"(y), "f"(z), "f"(w) : "memory"); }
__device__ __forceinline__ void ldsm4(uint32_t (&r)[4], uint32_t a) { asm volatile("ldmatrix.sync.aligned.m8n8.x4.shared.b16 {%0,%1,%2,%3}, [%4];" : "=r"(r[0]), "=r"(r[1]), "=r"(r[2]), "=r"(r[3]) : "r"(a) : "memory"); }
__device__ __forceinline__ void ldsm4t(uint32_t (&r)[4], uint32_t a) { asm volatile("ldmatrix.sync.aligned.m8n8.x4.trans.shared.b16 {%0,%1,%2,%3}, [%4];" : "=r"(r[0]), "=r"(r[1]), "=r"(r[2]), "=r"(r[3]) : "r"(a) : "memory"); }
__device__ __forceinline__ void ldsm2t(uint32_t& r0, uint32_t& r1, uint32_t a) { asm volatile("ldmatrix.sync.aligned.m8n8.x2.trans.shared.b16 {%0,%1}, [%2];" : "=r"(r0), "=r"(r1) : "r"(a) : "memory"); }
__device__ __forceinline__ void stsm4t(uint32_t a, uint32_t r0, uint32_t r1, uint32_t r2, uint32_t r3) { asm volatile("stmatrix.sync.aligned.m8n8.x4.trans.shared.b16 [%0], {%1,%2,%3,%4};" :: "r"(a), "r"(r0), "r"(r1), "r"(r2), "r"(r3) : "memory"); }
__device__ __forceinline__ void stsm4(uint32_t a, uint32_t r0, uint32_t r1, uint32_t r2, uint32_t r3) { asm volatile("stmatrix.sync.aligned.m8n8.x4.shared.b16 [%0], {%1,%2,%3,%4};" :: "r"(a), "r"(r0), "r"(r1), "r"(r2), "r"(r3) : "memory"); }
__device__ __forceinline__ void stsm2t(uint32_t a, uint32_t r0, uint32_t r1) { asm volatile("stmatrix.sync.aligned.m8n8.x2.trans.shared.b16 [%0], {%1,%2};" :: "r"(a), "r"(r0), "r"(r1) : "memory"); }
__device__ __forceinline__ uint4 ldg128(const void* p) { uint4 v; asm volatile("ld.global.nc.v4.u32 {%0,%1,%2,%3}, [%4];" : "=r"(v.x), "=r"(v.y), "=r"(v.z), "=r"(v.w) : "l"(p)); return v; }
__device__ __forceinline__ uint32_t ldg16(const void* p) { unsigned short v; asm volatile("ld.global.nc.u16 %0, [%1];" : "=h"(v) : "l"(p)); return v; }
__device__ __forceinline__ uint32_t opaque(uint32_t v) { uint32_t r; asm volatile("mov.b32 %0, %1;" : "=r"(r) : "r"(v)); return r; }
__device__ __forceinline__ void mma_f16(float (&d)[4], const uint32_t (&a)[4], uint32_t b0, uint32_t b1) {
    asm volatile("mma.sync.aligned.m16n8k16.row.col.f32.f16.f16.f32 {%0,%1,%2,%3}, {%4,%5,%6,%7}, {%8,%9}, {%0,%1,%2,%3};"
        : "+f"(d[0]), "+f"(d[1]), "+f"(d[2]), "+f"(d[3]) : "r"(a[0]), "r"(a[1]), "r"(a[2]), "r"(a[3]), "r"(b0), "r"(b1));
}
__device__ __forceinline__ void mma_bf16(float (&d)[4], uint32_t a0, uint32_t a1, uint32_t a2, uint32_t a3, uint32_t b0, uint32_t b1) {
    asm volatile("mma.sync.aligned.m16n8k16.row.col.f32.bf16.bf16.f32 {%0,%1,%2,%3}, {%4,%5,%6,%7}, {%8,%9}, {%0,%1,%2,%3};"
        : "+f"(d[0]), "+f"(d[1]), "+f"(d[2]), "+f"(d[3]) : "r"(a0), "r"(a1), "r"(a2), "r"(a3), "r"(b0), "r"(b1));
}
__device__ __forceinline__ void mma_bf16_k8(float (&d)[4], uint32_t a0, uint32_t a1, uint32_t b0) {
    asm volatile("mma.sync.aligned.m16n8k8.row.col.f32.bf16.bf16.f32 {%0,%1,%2,%3}, {%4,%5}, {%6}, {%0,%1,%2,%3};"
        : "+f"(d[0]), "+f"(d[1]), "+f"(d[2]), "+f"(d[3]) : "r"(a0), "r"(a1), "r"(b0));
}
__device__ __forceinline__ uint32_t pack_f16(float lo, float hi) { uint32_t r; asm("cvt.rn.f16x2.f32 %0, %1, %2;" : "=r"(r) : "f"(hi), "f"(lo)); return r; }
__device__ __forceinline__ uint32_t pack_bf16(float lo, float hi) { uint32_t r; asm("cvt.rn.bf16x2.f32 %0, %1, %2;" : "=r"(r) : "f"(hi), "f"(lo)); return r; }
__device__ __forceinline__ float bf_lo(uint32_t v) { return __uint_as_float(v << 16); }
__device__ __forceinline__ float bf_hi(uint32_t v) { return __uint_as_float(v & 0xFFFF0000u); }
__device__ __forceinline__ float bfr(float x) { return __uint_as_float(pack_bf16(0.f, x)); }
__device__ __forceinline__ uint32_t badd2(uint32_t a, uint32_t b) { uint32_t r; asm("add.rn.bf16x2 %0, %1, %2;" : "=r"(r) : "r"(a), "r"(b)); return r; }
__device__ __forceinline__ uint32_t bmul2(uint32_t a, uint32_t b) { uint32_t r; asm("mul.rn.bf16x2 %0, %1, %2;" : "=r"(r) : "r"(a), "r"(b)); return r; }
__device__ __forceinline__ uint32_t hadd2(uint32_t a, uint32_t b) { uint32_t r; asm("add.rn.f16x2 %0, %1, %2;" : "=r"(r) : "r"(a), "r"(b)); return r; }
__device__ __forceinline__ uint32_t hmul2(uint32_t a, uint32_t b) { uint32_t r; asm("mul.rn.f16x2 %0, %1, %2;" : "=r"(r) : "r"(a), "r"(b)); return r; }
__device__ __forceinline__ uint32_t hfma2(uint32_t a, uint32_t b, uint32_t c) { uint32_t r; asm("fma.rn.f16x2 %0, %1, %2, %3;" : "=r"(r) : "r"(a), "r"(b), "r"(c)); return r; }
__device__ __forceinline__ uint32_t hneg2(uint32_t a) { uint32_t r; asm("neg.f16x2 %0, %1;" : "=r"(r) : "r"(a)); return r; }
__device__ __forceinline__ float rcpf(float x) { float r; asm("rcp.approx.ftz.f32 %0, %1;" : "=f"(r) : "f"(x)); return r; }
__device__ __forceinline__ float sqrta(float x) { float r; asm("sqrt.approx.ftz.f32 %0, %1;" : "=f"(r) : "f"(x)); return r; }
__device__ __forceinline__ float ex2f(float x) { float r; asm("ex2.approx.ftz.f32 %0, %1;" : "=f"(r) : "f"(x)); return r; }
__device__ __forceinline__ void st_async4(uint32_t a, uint32_t x, uint32_t y, uint32_t z, uint32_t w, uint32_t mb) {
    asm volatile("st.async.shared::cluster.mbarrier::complete_tx::bytes.v4.u32 [%0], {%1,%2,%3,%4}, [%5];" :: "r"(a), "r"(x), "r"(y), "r"(z), "r"(w), "r"(mb) : "memory"); }
__device__ __forceinline__ void st_async1(uint32_t a, uint32_t x, uint32_t mb) {
    asm volatile("st.async.shared::cluster.mbarrier::complete_tx::bytes.u32 [%0], %1, [%2];" :: "r"(a), "r"(x), "r"(mb) : "memory"); }
__device__ __forceinline__ unsigned ld_rlx(const void* p) { unsigned v; asm volatile("ld.relaxed.gpu.global.u32 %0, [%1];" : "=r"(v) : "l"(p) : "memory"); return v; }
__device__ __forceinline__ unsigned ld_acq(const void* p) { unsigned v; asm volatile("ld.acquire.gpu.global.u32 %0, [%1];" : "=r"(v) : "l"(p) : "memory"); return v; }
__device__ __forceinline__ uint2 ld_rlx64(const void* p) { unsigned long long v; asm volatile("ld.relaxed.gpu.global.u64 %0, [%1];" : "=l"(v) : "l"(p) : "memory"); return make_uint2((unsigned)v, (unsigned)(v >> 32)); }
__device__ __forceinline__ void st_rlx128(void* p, uint32_t x, uint32_t y, uint32_t z, uint32_t w) {
    asm volatile("st.relaxed.gpu.global.v2.u64 [%0], {%1,%2};" :: "l"(p), "l"((unsigned long long)x | ((unsigned long long)y << 32)), "l"((unsigned long long)z | ((unsigned long long)w << 32)) : "memory"); }
__device__ __forceinline__ uint4 ld_rlx128(const void* p) { unsigned long long a, b; asm volatile("ld.relaxed.gpu.global.v2.u64 {%0,%1}, [%2];" : "=l"(a), "=l"(b) : "l"(p) : "memory"); return make_uint4((unsigned)a, (unsigned)(a >> 32), (unsigned)b, (unsigned)(b >> 32)); }
__device__ __forceinline__ void tma2d(uint32_t dst, const CUtensorMap* tm, int x, int y, uint32_t mb) {
    asm volatile("cp.async.bulk.tensor.2d.shared::cluster.global.mbarrier::complete_tx::bytes [%0], [%1, {%3, %4}], [%2];"
                 :: "r"(dst), "l"(tm), "r"(mb), "r"(x), "r"(y) : "memory");
}
__device__ __forceinline__ void cmul(float& xr, float& xi, float ar, float ai, float br, float bi) {
    const float r = fmaf(ar, br, -ai * bi), i = fmaf(ar, bi, ai * br); xr = r; xi = i;
}
__device__ __forceinline__ void csq(float& xr, float& xi, float ar, float ai) {
    const float r = fmaf(ar, ar, -ai * ai), i = (ar + ar) * ai; xr = r; xi = i;
}
__device__ __forceinline__ void cexp_s(float& zr, float& zi, float e2, float turns) {
    const float mag = ex2f(e2), r = (turns - rintf(turns)) * 6.283185307179586f;
    zr = mag * __cosf(r); zi = mag * __sinf(r);
}
__device__ __forceinline__ uint32_t ln_stats(float s1, float s2) {
    const float m = s1 * (1.f / D_);
    const float var = fmaxf(fmaf(s2, 1.f / D_, -m * m), 0.f);
    return pack_bf16(m, sqrta(bfr(bfr(var) + 1e-5f)));
}
__device__ __forceinline__ uint32_t rsplit(float rs) { const float h = bfr(rs); return pack_bf16(h, rs - h); }
__device__ __forceinline__ uint32_t norm2(uint32_t v, uint32_t mx, uint32_t hl) {
    uint32_t r;
    asm("{ .reg .b16 m, h, l, x; .reg .b32 m2, h2, l2, d, t; mov.b32 {m, x}, %2; mov.b32 {h, l}, %3; mov.b32 m2, {m, m}; mov.b32 h2, {h, h}; mov.b32 l2, {l, l};\n"
        "sub.rn.bf16x2 d, %1, m2; mul.rn.bf16x2 t, d, l2; fma.rn.bf16x2 %0, d, h2, t; }" : "=r"(r) : "r"(v), "r"(mx), "r"(hl));
    return r;
}
template <int N, int S>
__device__ __forceinline__ uint32_t rank4(uint32_t a, uint32_t key) {
    uint32_t r0 = 0, r1 = 0, r2 = 0, r3 = 0;
#pragma unroll
    for (int i = 0; i < N; i++) {
        const uint4 o = lds128(a + i * S);
        r0 += (key - o.x) >> 31; r1 += (key - o.y) >> 31; r2 += (key - o.z) >> 31; r3 += (key - o.w) >> 31;
    }
    return (r0 + r1) + (r2 + r3);
}
typedef uint32_t H2C;
__device__ __forceinline__ H2C splat(float r, float i) { return pack_f16(r, i); }
__device__ __forceinline__ void hcmul(uint32_t& xr, uint32_t& xi, uint32_t R, uint32_t I, H2C m) {
    asm("{ .reg .b16 a, b; .reg .b32 a2, b2, t; mov.b32 {a, b}, %4; mov.b32 a2, {a, a}; mov.b32 b2, {b, b};\n"
        "mul.rn.f16x2 t, %3, b2; neg.f16x2 t, t; fma.rn.f16x2 %0, %2, a2, t; mul.rn.f16x2 t, %3, a2; fma.rn.f16x2 %1, %2, b2, t; }"
        : "=&r"(xr), "=r"(xi) : "r"(R), "r"(I), "r"(m));
}
__device__ __forceinline__ void expand4(uint32_t are, uint32_t aim, uint32_t R0, uint32_t R1, uint32_t I0, uint32_t I1, H2C m4) {
    uint32_t R2, I2, R3, I3;
    hcmul(R2, I2, R0, I0, m4); hcmul(R3, I3, R1, I1, m4);
    sts128(are, R0, R1, R2, R3);
    sts128(aim, I0, I1, I2, I3);
}
__device__ __forceinline__ void expand8(uint32_t are, uint32_t aim, float sr, float si, float m1r, float m1i, float m2r, float m2i, H2C m4) {
    float r1, i1, r2, i2, r3, i3;
    cmul(r1, i1, sr, si, m1r, m1i); cmul(r2, i2, sr, si, m2r, m2i); cmul(r3, i3, r1, i1, m2r, m2i);
    expand4(are, aim, pack_f16(sr, r1), pack_f16(r2, r3), pack_f16(si, i1), pack_f16(i2, i3), m4);
}
__device__ __forceinline__ void put16(uint32_t a, uint32_t v) { sts16(a, v); sts16(a + 6, v); }

struct Params {
    const unsigned short *x, *prm6[6], *logdt, *dskip, *wr;
    __nv_bfloat16* out;
    Scratch* gs;
    unsigned zero;
};
__device__ __forceinline__ uint32_t tslot(uint32_t t) { return (t & 7) * 32 + ((t >> 4) & 24) + ((t >> 8) & 6) + ((t >> 6) & 1); }
#define CP(x) ((x) | zero)
#define PIN(x) asm volatile("or.b32 %0, %0, %1;" : "+r"(x) : "r"(zero))
__device__ __forceinline__ void wgmma32(float (&d)[4][4], const uint32_t (&a)[4], uint32_t dlo) {
    asm volatile("{ .reg .b64 ds; mov.b64 ds, {%20, %21};\n"
                 "wgmma.mma_async.sync.aligned.m64n32k16.f32.f16.f16 {%0,%1,%2,%3,%4,%5,%6,%7,%8,%9,%10,%11,%12,%13,%14,%15}, {%16,%17,%18,%19}, ds, 1, 1, 1, 0; }"
        : "+f"(d[0][0]), "+f"(d[0][1]), "+f"(d[0][2]), "+f"(d[0][3]), "+f"(d[1][0]), "+f"(d[1][1]), "+f"(d[1][2]), "+f"(d[1][3]),
          "+f"(d[2][0]), "+f"(d[2][1]), "+f"(d[2][2]), "+f"(d[2][3]), "+f"(d[3][0]), "+f"(d[3][1]), "+f"(d[3][2]), "+f"(d[3][3])
        : "r"(a[0]), "r"(a[1]), "r"(a[2]), "r"(a[3]), "r"(dlo), "n"(128 >> 4));
}

__global__ void __cluster_dims__(CS, 1, 1) __launch_bounds__(NTHR, 1)
fused_kernel(const __grid_constant__ Params prm, const __grid_constant__ CUtensorMap tmG, const __grid_constant__ CUtensorMap tmU,
             const __grid_constant__ CUtensorMap tmD, const __grid_constant__ CUtensorMap tmO, const __grid_constant__ CUtensorMap tmX, const __grid_constant__ CUtensorMap tmH)
{
    extern __shared__ __align__(1024) unsigned char smem[];
    const int tid = threadIdx.x, lane = tid & 31, warp = __shfl_sync(~0u, tid >> 5, 0);
    const int c = blockIdx.x >> 3, q = blockIdx.x & 7;
    const int nslot = (c < NCL - 1) ? 5 : 2;
    const int d0 = 40 * c;
    const uint32_t sb = opaque((uint32_t)__cvta_generic_to_shared(smem));
    const uint32_t mb = sb + SM_MB;
    Scratch& g_s = *prm.gs;
    const unsigned& zero = prm.zero;
    STAMP(0);

    if (warp >= 20) {
        unsigned epoch = 0;
        if (warp == 20) {
            if (lane == 0) {
#pragma unroll
                for (int i = 0; i < 13; i++)
                    asm volatile("mbarrier.init.shared::cta.b64 [%0], %1;" :: "r"(mb + i * 8), "r"((i == MB_R || i < 2) ? 2 : i == MB_Y ? 1 + 4 * nslot : 1) : "memory");
                asm volatile("fence.mbarrier_init.release.cluster;" ::: "memory");
                arm(mb + MB_W1 * 8, 92160); arm(mb + MB_W2 * 8, nslot * (128 * W2W)); arm(mb + MB_KEY * 8, 256); arm(mb + MB_GU * 8, nslot * 1024); arm(mb + MB_T * 8, 20480);
                const int bytes = max(min(18, L_ - 18 * (int)blockIdx.x), 1) * (D_ * 2);
                arm(mb + MB_R * 8, bytes);
                if (ROWE) asm volatile("cp.async.bulk.shared::cluster.global.mbarrier::complete_tx::bytes [%0], [%1], %2, [%3];"
                             :: "r"(sb + SM_ROW), "l"(prm.x + min(18 * (int)blockIdx.x, L_ - 1) * D_), "r"(max(min(18, L_ - 18 * (int)blockIdx.x), 1) * (D_ * 2)), "r"(mb + MB_R * 8) : "memory");
            }
            __syncwarp();
        } else if (warp == 22) {
            epoch = ld_rlx(&g_s.epoch);
            if (lane < 18 ? 18 * c + lane < 256 : lane < 31) (lane < 18 ? &g_s.acc[256 * q + 18 * c] : &g_s.fin[13 * (int)blockIdx.x - 18])[lane] = make_float4(0.f, 0.f, 0.f, 0.f);
        } else if (warp == 23 && lane == 0) asm volatile("prefetch.tensormap [%0];" :: "l"(&tmX) : "memory");
        asm volatile("barrier.cluster.arrive.relaxed.aligned;" ::: "memory");
        bar_sync(12, NTHR);
        if (warp == 22) {
            if (lane == 0) { sts32(sb + SM_SC + 28, epoch); asm volatile("mbarrier.arrive.shared::cta.b64 _, [%0];" :: "r"(mb + MB_R * 8) : "memory"); }
            epoch++;
            asm volatile("fence.acq_rel.gpu;" ::: "memory");
            __syncwarp();
            if (lane == 0) asm volatile("red.relaxed.gpu.global.add.u32 [%0], 1;" :: "l"(&g_s.zcnt) : "memory");
            STAMP(1);
            uint4 wv = make_uint4(0, 0, 0, 0), wv2 = ldg128((const uint4*)prm.wr + lane), wv3 = ldg128((const uint4*)prm.wr + 32 + lane);
            if (lane < 8) wv = ldg128((const uint4*)prm.wr + 64 + lane);
            if (lane < 5) {
                uint4 v = make_uint4(0, 0, 0, 0);
                if (lane < nslot) v = ldg128((const uint4*)(prm.wr + d0) + lane);
                sts128(sb + SM_DW + lane * 16, v.x, v.y, v.z, v.w);
            }
            __syncwarp();
            if (lane < 2) asm volatile("mbarrier.arrive.shared::cta.b64 _, [%0];" :: "r"(mb + (MB_X + lane) * 8) : "memory");
            mbar_wait(mb + (MB_X + 1) * 8);
            const uint32_t old = (epoch & 1) ? 0u : 0x40004000u;
#pragma unroll
            for (int t = 0; t < 2; t++)
                if ((lane & 7) < 6) g_s.cand[((q * 8 + 4 * t + (lane >> 3)) * NCL + c) * 6 + (lane & 7)] = make_uint4(old, old, old, old);
            float a[4] = {0.f, 0.f, 0.f, 0.f};
            const uint32_t one = 0x3F803F80u;
            mma_bf16(a, one, one, one, one, wv.x, wv.y);  mma_bf16(a, one, one, one, one, wv.z, wv.w);
            mma_bf16(a, one, one, one, one, wv2.x, wv2.y); mma_bf16(a, one, one, one, one, wv2.z, wv2.w);
            mma_bf16(a, one, one, one, one, wv3.x, wv3.y); mma_bf16(a, one, one, one, one, wv3.z, wv3.w);
            float s = a[0] + a[1];
            s += __shfl_xor_sync(~0u, s, 1); s += __shfl_xor_sync(~0u, s, 2);
            stsf(sb + SM_SC + 24, s);
            __syncwarp();
            if (lane == 0) {
                int n = 0;
                while ((int)(ld_acq(&g_s.zcnt) - epoch * NCTA) < 0 && ++n < SPIN_LIMIT) __nanosleep(200);
                arm(mb + MB_Y * 8, 8 * 512 * nslot);
                if (blockIdx.x == 0) g_s.epoch = epoch;
            }
            STAMP(2);
            return;
        }
        if (warp == 21) {
            if (lane == 0) { asm volatile("prefetch.tensormap [%0];" :: "l"(&tmG) : "memory"); asm volatile("prefetch.tensormap [%0];" :: "l"(&tmU) : "memory"); asm volatile("prefetch.tensormap [%0];" :: "l"(&tmD) : "memory"); }
            __syncwarp();
            if (EARLYB) { bar_arrive(13, 736); mbar_wait(mb + MB_T * 8); if (GAP_NS) __nanosleep(GAP_NS); } else bar_sync(13, 736);
#pragma unroll 1
            for (int i = 0; i < 24; i++) {
                if (AFTERX && i == EARLYB) bar_sync(0, 96);
                if (i == 13) { bar_sync(15, 544); asm volatile("fence.proxy.async.shared::cta;" ::: "memory"); }
                if (lane == 0) tma2d(sb + SM_WG + i * 3840, i < 12 ? &tmG : &tmU, 320 * c + 8 * nslot * q, 48 * (i < 12 ? i : i - 12), mb + MB_W1 * 8);
                if (PACE_NS >= 0) __nanosleep(i < EARLYB ? PACE0 : PACE_NS);
            }
            STAMP(1);
            return;
        }
        if (warp == 20) {
            if (!ROWE && lane == 0) {
                asm volatile("cp.async.bulk.shared::cluster.global.mbarrier::complete_tx::bytes [%0], [%1], %2, [%3];"
                             :: "r"(sb + SM_ROW), "l"(prm.x + min(18 * (int)blockIdx.x, L_ - 1) * D_), "r"(max(min(18, L_ - 18 * (int)blockIdx.x), 1) * (D_ * 2)), "r"(mb + MB_R * 8) : "memory");
            }
            __syncwarp();
            mbar_wait(mb + MB_R * 8);
            if (lane == 0) {
                asm volatile("cp.async.bulk.tensor.3d.shared::cluster.global.mbarrier::complete_tx::bytes [%0], [%1, {%3, %4, %5}], [%2];"
                             :: "r"(sb + SM_XTL), "l"(&tmX), "r"(mb + MB_T * 8), "r"(d0), "r"(8 * q), "r"(0) : "memory");
            }
            STAMP(6);
        }
        asm volatile("barrier.cluster.wait.aligned;" ::: "memory");
        bar_sync(13, 736);
        asm volatile("fence.proxy.async.shared::cta;" ::: "memory");
        {
            const int gr = lane >> 2, pe = (((lane & 3) ^ (gr * 3)) * 2 + (warp & 1)) & 7;
            const int s0 = gr ? 0 : XSPLIT, ns = gr ? min(XSPLIT, nslot) : nslot - XSPLIT;
            if (gr < 2 && ns > 0) {
                const int bytes = ns * YS - 160;
                if (pe == q) arm(mb + (MB_X + gr) * 8, 7 * bytes);
                else {
                    const uint32_t rb_ = mapa(sb, pe);
                    asm volatile("cp.async.bulk.shared::cluster.shared::cta.mbarrier::complete_tx::bytes [%0], [%1], %2, [%3];"
                                 :: "r"(rb_ + SM_U + 128 + q * UP + s0 * US), "r"(sb + SM_XT + 128 + pe * YP + s0 * YS), "r"(bytes), "r"(rb_ + SM_MB + (MB_X + gr) * 8) : "memory");
                }
            }
        }
        __syncwarp();
        if (AFTERX) bar_arrive(0, 96);
        STAMP(1);
        if (warp == 20 && lane == 0) { asm volatile("prefetch.tensormap [%0];" :: "l"(&tmO) : "memory"); asm volatile("prefetch.tensormap [%0];" :: "l"(&tmH) : "memory"); }
        if (warp == 23) {
#pragma unroll 1
            for (int kk = nslot - 1; kk >= 0; kk--) {
                __syncwarp();
                bar_sync(6 + kk, 160);
                if (lane == 0) { asm volatile("fence.proxy.async.shared::cta;" ::: "memory"); tma2d(sb + SM_FAR + kk * FAR_SZ, &tmD, W2W == 72 ? 72 * q : (72 * q) & ~15, 320 * c + 64 * kk, mb + MB_W2 * 8); }
            }
            return;
        }
        __syncwarp();
        bar_sync(14, 672);
        if (lane == 0) {
            asm volatile("fence.proxy.async.shared::cta;" ::: "memory");
            asm volatile("cp.async.bulk.tensor.5d.global.shared::cta.bulk_group [%0, {%2, %4, %4, %4, %3}], [%1];" :: "l"(&tmH), "r"(sb + SM_XT + 16384), "r"(d0 + ((c & 1) ? 0 : 32)), "r"(8 * q), "r"(0) : "memory");
            asm volatile("cp.async.bulk.tensor.5d.global.shared::cta.bulk_group [%0, {%2, %4, %4, %4, %3}], [%1];" :: "l"(&tmO), "r"(sb + SM_XT), "r"(d0 + (c & 1) * 8), "r"(8 * q), "r"(0) : "memory");
            asm volatile("cp.async.bulk.commit_group;" ::: "memory");
            asm volatile("cp.async.bulk.wait_group 0;" ::: "memory");
            asm volatile("fence.proxy.async.global;" ::: "memory");
            asm volatile("mbarrier.arrive.shared::cta.b64 _, [%0];" :: "r"(mb + MB_OUT * 8) : "memory");
        }
        STAMP(2);
        return;
    }

    const int g = lane >> 2, cq = lane & 3;
    const int k = warp >> 2, wq = warp & 3;
    const int trow = 18 * blockIdx.x + warp;
    const bool rowact = warp < 18 && trow < L_;
    const int dch = min(d0 + 8 * k + q, D_ - 1);
    uint32_t pv[6];
#pragma unroll
    for (int i = 0; i < 6; i++) pv[i] = ldg16(prm.prm6[i] + (uint32_t)(dch * 128 + wq * 32 + lane));
    const uint32_t pLdt = ldg16(prm.logdt + dch), pD = ldg16(prm.dskip + dch);
    const int tn = 16 * (warp & 15) + g;
    uint32_t xa[5], xb[5];
    asm volatile("barrier.cluster.arrive.relaxed.aligned;" ::: "memory");
    uint4* const st1p = &g_s.st1[(((trow >> 3) & 7) * 256 + ((trow >> 6) & 31) * 8 + (trow & 7)) * 2 + (lane >> 2)];
    const bool pub = rowact && (lane & 0x1B) == 0;
    if (pub) st_rlx128(st1p, 0, 0, 0, 0);
    {
        const uint32_t za = sb + SM_P + tid * 16;
        sts128(za, 0, 0, 0, 0);
        if (tid < (SM_MISC - SM_P) / 16 - 640) sts128(za + 10240, 0, 0, 0, 0);
        sts128(sb + SM_XT + ((tid >> 3) & 15) * YP + k * YS + (lane & 7) * 16, 0, 0, 0, 0);
    }
    bar_sync(12, NTHR);
    const uint32_t dep = lds32(sb + SM_P);
#define PV(x) __uint_as_float(__byte_perm(dep, x, 0x5410))
    STAMP(1);
    const uint32_t fb = sb + SM_FAR + k * FAR_SZ;
    const uint32_t pn = sb + SM_PN + k * PN_SZ, pf = sb + SM_PF + k * PF_SZ;
    unsigned epoch;
    {
        const uint32_t kb = fb + wq * 3072;
        const uint32_t kl = kb + lane * 16;
        uint32_t Af[4][4];
        float sr, si, z1r, z1i, z2r, z2i, z4r, z4i, hr, hi_;
        {
            const float dt = bfr(ex2f(PV(pLdt) * 1.4426950408889634f));
            const float e2 = dt * PV(pv[0]) * 1.4426950408889634f, an = dt * PV(pv[1]);
            cmul(sr, si, PV(pv[4]), PV(pv[5]), dt * PV(pv[2]), dt * PV(pv[3]));
            const unsigned E = min(max(__reduce_max_sync(~0u, __float_as_uint(fmaxf(fmaxf(fabsf(sr), fabsf(si)), fabsf(PV(pD)) * (1.f / 8192.f)))) >> 23, 1u), 253u);
            const float sc = __uint_as_float((254u - E) << 23);
            sr *= sc; si *= -sc;
            sts64(sb + SM_KG + warp * 8, E, __reduce_add_sync(~0u, __float2int_rn(sr * 16777216.f)));
            float ar, ai, br, bi, cr, ci, dr, di;
            { const float m = ex2f(e2 * 8.f); ar = m * __cosf(an * 8.f); ai = m * __sinf(an * 8.f); }
            csq(br, bi, ar, ai); csq(cr, ci, br, bi); csq(dr, di, cr, ci);
            const H2C m4 = splat(cr, ci);
            {
                float r3, i3;
                cmul(r3, i3, ar, ai, br, bi);
                expand4(kl, kl + 1024, pack_f16(1.f, ar), pack_f16(br, r3), pack_f16(0.f, ai), pack_f16(bi, i3), m4);
            }
            expand8(kl + 512, kl + 1536, dr, di, ar, ai, br, bi, m4);
            { const float m = ex2f(e2); z1r = m * __cosf(an); z1i = -m * __sinf(an); }
            cexp_s(hr, hi_, e2 * 128.f, an * (-128.f * 0.15915494309189535f));
            csq(z2r, z2i, z1r, z1i); csq(z4r, z4i, z2r, z2i);
        }
        __syncwarp();
#pragma unroll
        for (int ks = 0; ks < 4; ks++) ldsm4t(Af[ks], kb + (lane >> 3) * 512 + (lane & 7) * 16 + ks * 128);
        STAMP(2);
        const uint32_t la = kb + ((lane >> 3) & 1) * 512 + (lane >> 4) * 128 + (lane & 7) * 16;
        uint32_t kp[5][2], b0[4], b1[4], b2[4], b3[4];
        auto mm2 = [&](int t) {
            float a0[4] = {0.f, 0.f, 0.f, 0.f}, a1[4] = {0.f, 0.f, 0.f, 0.f};
            mma_f16(a0, Af[0], b0[0], b0[1]); mma_f16(a1, Af[0], b2[0], b2[1]); mma_f16(a0, Af[1], b0[2], b0[3]); mma_f16(a1, Af[1], b2[2], b2[3]);
            mma_f16(a0, Af[2], b1[0], b1[1]); mma_f16(a1, Af[2], b3[0], b3[1]); mma_f16(a0, Af[3], b1[2], b1[3]); mma_f16(a1, Af[3], b3[2], b3[3]);
            kp[t][0] = pack_f16(a0[1], a0[0]); kp[t][1] = pack_f16(a0[3], a0[2]); kp[t + 1][0] = pack_f16(a1[1], a1[0]); kp[t + 1][1] = pack_f16(a1[3], a1[2]);
        };
        auto ln1 = [&]() {
        mbar_wait(mb + MB_R * 8);
        epoch = lds32(sb + SM_SC + 28) + 1;
        {
            const uint32_t ra = sb + SM_ROW + warp * (D_ * 2);
            const uint4 r0 = lds128(ra + lane * 16), r1 = lds128(ra + 512 + lane * 16);
            const uint32_t rx[9] = {r0.x, r0.y, r0.z, r0.w, r1.x, r1.y, r1.z, r1.w, lds32(ra + 1024 + lane * 4)};
            float a0 = bf_lo(rx[0]), a1 = bf_hi(rx[0]), c0 = a0 * a0, c1 = a1 * a1;
#pragma unroll
            for (int i = 1; i < 9; i++) { const float l = bf_lo(rx[i]), h = bf_hi(rx[i]); a0 += l; a1 += h; c0 = fmaf(l, l, c0); c1 = fmaf(h, h, c1); }
            a0 += a1; c0 += c1;
            float s1 = ((lane & 1) ? c0 : a0) + __shfl_xor_sync(~0u, (lane & 1) ? a0 : c0, 1);
#pragma unroll
            for (int o = 2; o < 32; o <<= 1) s1 += __shfl_xor_sync(~0u, s1, o);
            const float s2 = __shfl_xor_sync(~0u, s1, 1);
            const uint32_t ms = ln_stats(s1, s2);
            const uint32_t p0 = __byte_perm(ms, epoch | 0x8000u, 0x5410), p1 = rsplit(rcpf(bf_hi(ms)));
            if (pub) st_rlx128(st1p, p0, p1, p0, p1);
        }
        mbar_wait(mb + MB_R * 8);
        STAMP(1);
        };
        const uint4* sp = &g_s.st1[(256 * q + tn) * 2];
        uint2 sa, sc;
        auto poll = [&]() { sa = ld_rlx64(sp); sc = ld_rlx64(sp + 16); };
        auto norm = [&]() {
        STAMP(3);
        if (warp < 16) {
            uint32_t va[5], vc[5];
            poll();
            mbar_wait(mb + MB_T * 8);
            {
                const uint32_t xt = sb + SM_XTL + tn * 80;
                uint4 a4 = lds128(xt + cq * 16), b4 = lds128(xt + cq * 16 + 640);
                va[0] = a4.x; va[1] = a4.y; va[2] = a4.z; va[3] = a4.w; va[4] = lds32(xt + 64 + cq * 4);
                vc[0] = b4.x; vc[1] = b4.y; vc[2] = b4.z; vc[3] = b4.w; vc[4] = lds32(xt + 704 + cq * 4);
            }
            const int d4 = 2 * (lane >> 3) + (lane & 1), d1_ = lane & 7;
            uint32_t a4 = sb + warp * 32 + d4 * YP + (d4 == q ? SM_U + 128 : SM_XT + 128) + ((lane & 7) >> 1) * YS;
            uint32_t a1 = sb + warp * 32 + d1_ * YP + (d1_ == q ? SM_U + 128 : SM_XT + 128) + 4 * YS + (lane & 8) * 2;
            PIN(a4); PIN(a1);
            const uint32_t tag = __byte_perm(epoch | 0x8000u, 0, 0x1010) | ((va[0] & va[4] & vc[0] & vc[4]) & zero);
            int n = 0;
            while (__byte_perm(sa.x, sc.x, 0x7632) != tag && ++n < SPIN_LIMIT) poll();
            STAMP(4);
#pragma unroll
            for (int i = 0; i < 5; i++) {
                va[i] = norm2(va[i], sa.x, sa.y); va[i] = pack_f16(bf_lo(va[i]), bf_hi(va[i]));
                vc[i] = norm2(vc[i], sc.x, sc.y); vc[i] = pack_f16(bf_lo(vc[i]), bf_hi(vc[i]));
            }
            stsm4t(a4, va[0], va[1], va[2], va[3]); stsm4t(a4 + 16, vc[0], vc[1], vc[2], vc[3]); stsm2t(a1, va[4], vc[4]);
        }
        bar_arrive(13, 736);
        if (warp < 16) {
            const uint32_t xh = sb + SM_XTL + (64 * (g >> 1) + 32 * (warp & 1) + 8 * (g & 1) + (warp >> 1)) * 80;
            const uint4 a4 = lds128(xh + cq * 16), b4 = lds128(xh + cq * 16 + 1280);
            xa[0] = a4.x; xa[1] = a4.y; xa[2] = a4.z; xa[3] = a4.w; xa[4] = lds32(xh + 64 + cq * 4);
            xb[0] = b4.x; xb[1] = b4.y; xb[2] = b4.z; xb[3] = b4.w; xb[4] = lds32(xh + 1344 + cq * 4);
            bar_arrive(15, 544);
        }
        STAMP(5);
        };
        if (LNPOS == 0) ln1();
        cmul(sr, si, sr, si, z1r, z1i);
        {
            const H2C h4 = splat(z4r, z4i);
            expand8(kl, kl + 512, sr, si, z1r, z1i, z2r, z2i, h4);
            cmul(sr, si, sr, si, hr, hi_);
            expand8(kl + 1024, kl + 1536, sr, si, z1r, z1i, z2r, z2i, h4);
        }
        __syncwarp();
        ldsm4t(b0, la); ldsm4t(b1, la + 256); ldsm4t(b2, la + 1024); ldsm4t(b3, la + 1280);
        cmul(z1r, z1i, z1r, z1i, hr, hi_);
        cmul(sr, si, sr, si, z1r, z1i);
        if (LNPOS == 1) ln1();
        expand8(kl, kl + 512, sr, si, z2r, z2i, z4r, z4i, splat(hr, hi_));
        if (LNPOS == 2) ln1();
        csq(z1r, z1i, z1r, z1i);
        cmul(sr, si, sr, si, z1r, z1i);
        csq(z2r, z2i, hr, hi_);
        expand8(kl + 1024, kl + 1536, sr, si, z4r, z4i, hr, hi_, splat(z2r, z2i));
        if (LNPOS == 3) ln1();
        csq(z1r, z1i, z1r, z1i);
        cmul(sr, si, sr, si, z1r, z1i);
        csq(z4r, z4i, z2r, z2i);
        expand8(kl + 2048, kl + 2560, sr, si, hr, hi_, z2r, z2i, splat(z4r, z4i));
        if (LNPOS == 4) ln1();
        if (MMPOS == 0) norm();
        mm2(0);
        __syncwarp();
        ldsm4t(b0, la); ldsm4t(b1, la + 256); ldsm4t(b2, la + 1024); ldsm4t(b3, la + 1280);
        if (MMPOS == 1) norm();
        mm2(2);
        if (MMPOS == 2) norm();
        ldsm4t(b0, la + 2048); ldsm4t(b1, la + 2304);
#pragma unroll
        for (int t = 0; t < 4; t++) sts64(kb + lane * 8 + 1024 + t * 256, kp[t][0], kp[t][1]);
        {
            float a0[4] = {0.f, 0.f, 0.f, 0.f}, a1[4] = {0.f, 0.f, 0.f, 0.f};
            mma_f16(a0, Af[0], b0[0], b0[1]); mma_f16(a1, Af[1], b0[2], b0[3]); mma_f16(a0, Af[2], b1[0], b1[1]); mma_f16(a1, Af[3], b1[2], b1[3]);
            sts64(kb + lane * 8 + 2048, pack_f16(a0[1] + a1[1], a0[0] + a1[0]), pack_f16(a0[3] + a1[3], a0[2] + a1[2]));
        }
        bar_sync(1 + k, 128);
        const uint4 m01 = lds128(sb + SM_KG + k * 32), m23 = lds128(sb + SM_KG + k * 32 + 16);
        const unsigned Em = max(max(m01.x, m01.z), max(m23.x, m23.z));
        const float f0 = __uint_as_float(max((int)(127 + m01.x - Em), 0) << 23), f1 = __uint_as_float(max((int)(127 + m01.z - Em), 0) << 23),
                    f2 = __uint_as_float(max((int)(127 + m23.x - Em), 0) << 23), f3 = __uint_as_float(max((int)(127 + m23.z - Em), 0) << 23);
        const uint32_t r0 = pack_f16(f0, f0), r1 = pack_f16(f1, f1), r2 = pack_f16(f2, f2), r3 = pack_f16(f3, f3);
        const uint32_t ra = fb + lane * 8 + wq * 256 + 1024;
        const uint2 p0 = lds64(ra), p1 = lds64(ra + 3072), p2 = lds64(ra + 6144), p3 = lds64(ra + 9216);
        uint32_t w0 = hadd2(hfma2(p0.x, r0, hmul2(p1.x, r1)), hfma2(p2.x, r2, hmul2(p3.x, r3)));
        uint32_t w1 = hadd2(hfma2(p0.y, r0, hmul2(p1.y, r1)), hfma2(p2.y, r2, hmul2(p3.y, r3)));
        const bool last = lane == 31;
        if (wq < 2) {
            const uint32_t rc = fb + lane * 8 + wq * 4 + 2048;
            const uint32_t w4 = hmul2(hadd2(hfma2(lds32(rc), r0, hmul2(lds32(rc + 3072), r1)), hfma2(lds32(rc + 6144), r2, hmul2(lds32(rc + 9216), r3))), 0x18001800u);
            const uint32_t ph = pf + (P_H7 + 16 * wq) + (g & 1) * (2 * P_HS) + cq * 64 + (g >> 1) * 4;
            put16(ph, w4 >> 16); put16(ph + 32, w4);
            const uint32_t pa = pn + (4 + 512 * wq) + lane * 8;
            sts16(pa, w0 >> 16); sts32(pa + 4, w0); sts16(pa + 10, w0);
            sts16(pa + 256, w1 >> 16); sts32(pa + 260, w1); sts16(pa + 266, w1);
            if (last) {
                sts32(sb + SM_SC + k * 4, Em * 0x00800080u);
                put16(wq ? pa + 264 : pn,
                      wq ? w1 : pack_f16(((float)(int)m01.y * f0 + (float)(int)m01.w * f1 + (float)(int)m23.y * f2 + (float)(int)m23.w * f3) * (1.f / 16777216.f)
                                         + __uint_as_float(pD << 16) * __uint_as_float((254u - Em) << 23), 0.f));
            }
        } else if (wq == 2) {
            const uint32_t pa = pn + 258 * 4 + (cq & 1) * 16 + (cq >> 1) * 512 + g * 32;
            if (last) { put16(pf, hmul2(w1, 0x18001800u)); w1 = hadd2(w1, hneg2(__byte_perm(w1, 0, 0x1010))); }
            const uint32_t b0 = __byte_perm(w0, 0, 0x1010), b1 = __byte_perm(w1, 0, 0x1010);
            sts16(pa, w0 >> 16); sts32(pa + 4, w0); sts64(pa + 8, b0, b0); sts16(pa + 18, w0);
            sts16(pa + 256, w1 >> 16); sts32(pa + 260, w1); sts64(pa + 264, b1, b1); sts16(pa + 274, w1);
        } else {
            const uint32_t pa = pf + ((g & 1) ? 3 * P_GS : P_GS) + cq * 32 + (g >> 1) * 4;
            const uint32_t pb = pa + ((g & 1) ? 4 - 3 * P_GS : P_GS);
            w0 = hmul2(w0, 0x18001800u); w1 = hmul2(w1, 0x18001800u);
            put16(pa, w0 >> 16); put16(pb, w0); put16(pa + 16, w1 >> 16); put16(pb + 16, w1);
            if (last) put16(pf + P_H7 + P_HS, w1);
        }
        bar_sync(1 + k, 128);
    }
    STAMP(6);

    asm volatile("barrier.cluster.wait.aligned;" ::: "memory");
    mbar_wait(mb + (MB_X + (k < XSPLIT || k >= nslot)) * 8);
    STAMP(7);
    if (k < nslot) {
        const int role = (wq + k) & 3;
        const uint32_t ub = sb + SM_U + k * US + 128;
        if (role) {
            const int r = (3 - role) * 32 + lane;
            const uint32_t a1 = ub + (r & 3) * (2 * UP) + (r >> 2) * 16, a0 = a1 + ((r & 3) ? -2 * UP : 6 * UP - 16);
            const uint4 q0 = lds128(a0), q1 = lds128(a0 + UP), q2 = lds128(a1), q3 = lds128(a1 + UP);
            const uint32_t U[16] = {q0.x, q0.y, q0.z, q0.w, q1.x, q1.y, q1.z, q1.w, q2.x, q2.y, q2.z, q2.w, q3.x, q3.y, q3.z, q3.w};
            uint32_t V[14], Q[14], R4[12], T[8];
#pragma unroll
            for (int i = 2; i < 14; i++) { V[i] = __byte_perm(U[i], U[i + 1], 0x5432); Q[i] = hadd2(U[i], V[i]); }
#pragma unroll
            for (int i = 2; i < 12; i++) R4[i] = hadd2(Q[i], Q[i + 1]);
            const uint32_t rb = fb + r * 16;
#pragma unroll
            for (int i = 0; i < 8; i++) T[i] = hadd2(V[5 + i], Q[6 + i]);
            sts128(rb + F_E3, T[0], T[1], T[2], T[3]); sts128(rb + F_O3 + 16, T[4], T[5], T[6], T[7]);
#pragma unroll
            for (int i = 0; i < 8; i++) T[i] = hadd2(R4[3 + i], U[5 + i]);
            sts128(rb + F_O5, T[0], T[1], T[2], T[3]); sts128(rb + F_E5, T[4], T[5], T[6], T[7]);
            if (role != 1) {
#pragma unroll
                for (int i = 0; i < 8; i++) T[i] = hadd2(T[i], hadd2(V[2 + i], V[5 + i]));
                sts128(rb + F_E7, T[0], T[1], T[2], T[3]); sts128(rb + F_O7, T[4], T[5], T[6], T[7]);
#pragma unroll
                for (int i = 0; i < 8; i++) T[i] = hadd2(R4[2 + i], hadd2(R4[4 + i], U[6 + i]));
                sts128(rb + F_O9, T[0], T[1], T[2], T[3]); sts128(rb + F_E9 + 16, T[4], T[5], T[6], T[7]);
                sts128(rb + F_E2, Q[6], Q[7], Q[8], Q[9]); sts128(rb + F_O2, Q[10], Q[11], Q[12], Q[13]);
            }
        } else if (lane < 8) {
            uint32_t v[5];
#pragma unroll
            for (int i = 0; i < 5; i++) { const int t = 6 + lane + i; v[i] = lds16(ub + 23 * 16 + (t < 16 ? (6 + (t >> 3)) * UP : 16) + (t & 7) * 2); }
            const uint32_t s = hadd2(hadd2(hadd2(v[0], v[1]), hadd2(v[2], v[3])), v[4]);
            sts16(fb + F_O5 + 96 * 16 + lane * 2, s);
            sts32(fb + (lane < 4 ? F_O3 : F_E9 - 16) + lane * 4, 0);
        }
        bar_sync(1 + k, 128);
        float acc[4][4];
        uint32_t Q[4][4];
        {
            const int h = role & 1, part = role >> 1;
            const uint32_t po = pf + (g - 2 * cq) * 4;
            float fa[7][4];
#pragma unroll
            for (int a = 0; a < 7; a++) fa[a][0] = fa[a][1] = fa[a][2] = fa[a][3] = 0.f;
            uint32_t B[3][4];
            Q[0][2] = zero;
#pragma unroll 1
            for (int s = 2 * part + 1; s >= 2 * part; s--) {
#pragma unroll
                for (int i = 0; i < 3; i++) { Q[i][0] = lds32(po + s * P_GS + i * 64); Q[i][1] = lds32(po + s * P_GS + (i * 64 + 32)); }
                const uint32_t ba = fb + lane * 16 + ((s & 1) * F_E3 + (part == h ? 0 : F_O5 + h * 16));
#pragma unroll
                for (int i = 0; i < 3; i++) ldsm4t(B[i], ba + i * 512);
#pragma unroll
                for (int i = 0; i < 3; i++) { Q[i][3] = CP(Q[i][0]); if (i) Q[i][2] = CP(Q[i - 1][1]); }
#pragma unroll
                for (int dl = 0; dl < 3; dl++)
#pragma unroll
                    for (int ap = 0; ap < 6 - dl; ap++) mma_f16(fa[ap + 1 + dl], Q[dl], B[ap >> 1][2 * (ap & 1)], B[ap >> 1][2 * (ap & 1) + 1]);
            }
#pragma unroll 1
            for (int s = role; s == 1; s++) {
                ldsm2t(B[0][0], B[0][1], fb + ((lane & 15) == 15 ? F_O5 : F_O3));
#pragma unroll
                for (int dl = 0; dl < 3; dl++) mma_f16(fa[dl], Q[dl], B[0][0], B[0][1]);
            }
#pragma unroll 1
            for (int s = part; s <= 2 * part; s++) {
#pragma unroll
                for (int i = 0; i < 4; i++) { Q[i][0] = lds32(po + s * P_HS + (P_H7 + i * 64)); Q[i][1] = lds32(po + s * P_HS + (P_H7 + i * 64 + 32)); }
                const uint32_t ba = fb + lane * 16 + (F_E7 + s * 1024 + h * F_H);
                ldsm4t(B[0], ba); ldsm4t(B[1], ba + 512);
#pragma unroll
                for (int i = 0; i < 4; i++) { Q[i][3] = CP(Q[i][0]); if (i) Q[i][2] = CP(Q[i - 1][1]); }
#pragma unroll
                for (int dl = 0; dl < 4; dl++) {
#pragma unroll
                    for (int ap = 0; ap < 4 - dl; ap++) mma_f16(fa[ap + 3 + dl], Q[dl], B[ap >> 1][2 * (ap & 1)], B[ap >> 1][2 * (ap & 1) + 1]);
                    if (s == 1) break;
                }
            }
            const uint32_t da = fb + role * 2048 + (lane & 3) * 512 + (((lane >> 2) ^ ((lane & 3) * 2)) << 4);
            bar_sync(1 + k, 128);
            stsm4(da, 0u, 0u, pack_f16(fa[0][0], fa[0][1]), pack_f16(fa[0][2], fa[0][3]));
#pragma unroll
            for (int i = 1; i < 4; i++)
                stsm4(da + i * 128, pack_f16(fa[2 * i - 1][0], fa[2 * i - 1][1]), pack_f16(fa[2 * i - 1][2], fa[2 * i - 1][3]),
                      pack_f16(fa[2 * i][0], fa[2 * i][1]), pack_f16(fa[2 * i][2], fa[2 * i][3]));
            Q[0][0] = (g == 2 * cq) ? 0x6000u : ((g == 2 * cq + 1) ? 0x60000000u : 0u);
            Q[0][1] = 0; Q[0][3] = CP(Q[0][0]);
            const uint32_t ra = fb + (lane >> 3) * 2048 + wq * 512 + (((lane & 7) ^ (wq * 2)) << 4);
            bar_sync(1 + k, 128);
#pragma unroll
            for (int i = 0; i < 4; i++) {
                ldsm4(B[0], ra + i * 128);
                acc[i][0] = acc[i][1] = acc[i][2] = acc[i][3] = 0.f;
                mma_f16(acc[i], Q[0], hadd2(B[0][0], B[0][2]), hadd2(B[0][1], B[0][3]));
            }
        }
        bar_arrive(6 + k, 160);
        STAMP(8);
        const uint32_t inv = lds32(sb + SM_SC + k * 4);
        uint32_t yd = mapa(sb, 2 * wq) + (SM_XT + 128 + q * YP + k * YS) + lane * 16;
        PIN(yd);
        {
            uint32_t pp = pn + (16 * (wq - 3) + g - 2 * cq) * 4;
            uint32_t dlo = (((ub + 6 * UP) & 0x3FFFF) >> 4) | ((UP >> 4) << 16);
            uint32_t R[4][4];
            auto loadQ = [&](uint32_t (&X)[4][4], uint32_t prev) {
#pragma unroll
                for (int i = 0; i < 4; i++) { X[i][0] = lds32(pp + i * 64); X[i][1] = lds32(pp + i * 64 + 32); }
                X[0][2] = CP(prev);
#pragma unroll
                for (int i = 0; i < 4; i++) { X[i][3] = CP(X[i][0]); if (i) X[i][2] = CP(X[i - 1][1]); }
                pp += 256;
            };
            auto issue = [&](uint32_t (&X)[4][4]) {
                asm volatile("wgmma.fence.sync.aligned;" ::: "memory");
#pragma unroll
                for (int i = 0; i < 4; i++) wgmma32(acc, X[i], dlo - i * (2 * UP >> 4));
                asm volatile("wgmma.commit_group.sync.aligned;" ::: "memory");
                dlo -= 1;
            };
            loadQ(Q, 0);
#pragma unroll 1
            for (int dl = 0; dl < 4; dl++) {
                issue(Q);
                asm volatile("wgmma.wait_group.sync.aligned 1;" ::: "memory");
                loadQ(R, Q[3][1]);
                issue(R);
                asm volatile("wgmma.wait_group.sync.aligned 1;" ::: "memory");
                loadQ(Q, R[3][1]);
            }
            issue(Q);
            asm volatile("wgmma.wait_group.sync.aligned 0;" ::: "memory");
        }
        const uint32_t pstep = mapa(sb, 1) - mapa(sb, 0), ym = mapa(mb + MB_Y * 8, 2 * wq);
#pragma unroll
        for (int e = 0; e < 2; e++)
            st_async4(yd + e * pstep, bmul2(pack_bf16(acc[0][2 * e], acc[0][2 * e + 1]), inv), bmul2(pack_bf16(acc[1][2 * e], acc[1][2 * e + 1]), inv),
                      bmul2(pack_bf16(acc[2][2 * e], acc[2][2 * e + 1]), inv), bmul2(pack_bf16(acc[3][2 * e], acc[3][2 * e + 1]), inv), ym + e * pstep);
        if (lane == 0) asm volatile("mbarrier.arrive.shared::cta.b64 _, [%0];" :: "r"(mb + MB_Y * 8) : "memory");
    }
    STAMP(9);
    uint32_t ha[5], hb[5];
    if (warp < 16) {
        const uint4 wk = lds128(sb + SM_DW + cq * 16);
        uint32_t sel[5] = {wk.x, wk.y, wk.z, wk.w, lds32(sb + SM_DW + 64 + cq * 4)}, sel2[5];
#pragma unroll
        for (int i = 0; i < 5; i++) {
            if (!(g & 1)) sel[i] = 0x3F803F80u;
            sel2[i] = sel[i]; PIN(sel2[i]);
        }
        const uint32_t y4 = sb + SM_XT + 128 + warp * 32 + (2 * (lane >> 3) + (lane & 1)) * YP + ((lane & 7) >> 1) * YS;
        const uint32_t y1 = sb + SM_XT + 128 + warp * 32 + (lane & 7) * YP + 4 * YS + (lane & 8) * 2;
        uint32_t ao = (256 * q + tn) * 16, hta = sb + SM_HT + tn * 80;
        PIN(ao); PIN(hta);
        mbar_wait(mb + MB_Y * 8);
        STAMP(10);
        float ca[4] = {0.f, 0.f, 0.f, 0.f}, cb[4] = {0.f, 0.f, 0.f, 0.f};
        {
            uint32_t ya[4], yb[4], yc, yd;
            ldsm4t(ya, y4); ldsm4t(yb, y4 + 16); ldsm2t(yc, yd, y1);
#pragma unroll
            for (int i = 0; i < 4; i++) { ha[i] = badd2(xa[i], ya[i]); hb[i] = badd2(xb[i], yb[i]); }
            ha[4] = badd2(xa[4], yc); hb[4] = badd2(xb[4], yd);
        }
        if (nslot != 5) {
            ha[4] = hb[4] = 0;
            if (cq >= 2) ha[0] = ha[1] = ha[2] = ha[3] = hb[0] = hb[1] = hb[2] = hb[3] = 0;
        }
#pragma unroll
        for (int i = 0; i < 5; i++) { mma_bf16_k8(ca, ha[i], sel[i], ha[i]); mma_bf16_k8(cb, hb[i], sel2[i], hb[i]); }
        if (!(g & 1)) { ca[1] = ca[0]; cb[1] = cb[0]; }
        if (cq == (g >> 1)) {
            asm volatile("red.relaxed.gpu.global.add.v4.f32 [%0], {%1,%2,%3,%4};" :: "l"((char*)g_s.acc + ao), "f"(1.0f), "f"(ca[1]), "f"(ca[2]), "f"(ca[3]) : "memory");
            asm volatile("red.relaxed.gpu.global.add.v4.f32 [%0], {%1,%2,%3,%4};" :: "l"((char*)g_s.acc + ao + 128), "f"(1.0f), "f"(cb[1]), "f"(cb[2]), "f"(cb[3]) : "memory");
        }
        sts128(hta + cq * 16, ha[0], ha[1], ha[2], ha[3]); sts32(hta + 64 + cq * 4, ha[4]);
        sts128(hta + cq * 16 + 640, hb[0], hb[1], hb[2], hb[3]); sts32(hta + 704 + cq * 4, hb[4]);
        STAMP(11);
    }
    const int kq = warp / 5, mt = warp - 5 * kq;
    const int mi = lane >> 3, mr = lane & 7;
    const unsigned tk = (unsigned)tid / 72u, ck = tid - tk * 72;
    uint32_t A[9][4];
    auto loadA = [&]() {
        mbar_wait(mb + MB_W1 * 8);
        const uint32_t aa = sb + (mi & 1) * SM_WU + (8 * (mi >> 1) + mr) * 80 + (144 * 80 * kq + mt * 16);
#pragma unroll
        for (int s = 0; s < 9; s++) ldsm4t(A[s], aa + s * 1280);
    };
    const uint32_t par = (epoch & 1) ? 0x40004000u : 0u;
    uint32_t pk0 = mapa(sb, 2 * cq), go = (ck / 5u + ck) * 16, co = ((q * 8 * NCL + c) * 6 + cq) * 16;
    PIN(pk0); PIN(go); PIN(co);
    if (warp < 8) {
        const float wsum = ldsf(sb + SM_SC + 24);
        const uint32_t idx = 2047 - (512 * ((tid >> 1) & 3) + 128 * ((tid >> 3) & 3) + 64 * (tid & 1) + 8 * q + warp);
        uint4 s; int n = 0;
        do { s = ld_rlx128(&g_s.acc[256 * q + tid]); } while (__uint_as_float(s.x) != (float)NCL && ++n < SPIN_LIMIT);
        STAMP(16);
        const uint32_t ox = __shfl_xor_sync(~0u, (lane & 1) ? s.z : s.w, 1);
        const uint32_t ms = ln_stats(__uint_as_float((lane & 1) ? ox : s.z), __uint_as_float(s.y));
        const float rs = rcpf(bf_hi(ms));
        const uint32_t rb = pack_bf16(0.f, fmaf(-bf_lo(ms), wsum, __uint_as_float((lane & 1) ? s.w : ox)) * rs);
        const uint32_t key = (((rb ^ (((int)rb >> 31) | 0x80000000u)) >> 16) << 11) | idx;
        sts32(sb + SM_KEY + tid * 4, key);
        __syncwarp();
        const uint32_t rank = rank4<8, 16>(sb + SM_KEY + warp * 128, key);
        if (rank < 8) sts32(sb + SM_CAND + warp * 32 + rank * 4, key);
        sts64(sb + SM_ST + tid * 8, ms, rsplit(rs));
    } else loadA();
    if (warp < 16) {
        STAMP(17);
        bar_sync(12, 512);
        STAMP(18);
        if (warp < 8) {
            const uint32_t mk = lds32(sb + SM_CAND + (tid >> 2) * 4);
            uint32_t rank = rank4<4, 64>(sb + SM_CAND + cq * 16, mk);
            rank += __shfl_xor_sync(~0u, rank, 1); rank += __shfl_xor_sync(~0u, rank, 2);
            if (rank < 8) {
                const uint32_t pk1 = pk0 + (mapa(sb, 1) - mapa(sb, 0));
                st_async1(pk0 + (SM_RK + q * 32) + rank * 4, mk, pk0 + (SM_MB + MB_KEY * 8));
                st_async1(pk1 + (SM_RK + q * 32) + rank * 4, mk, pk1 + (SM_MB + MB_KEY * 8));
                const uint32_t t = tslot(~mk);
                const uint2 sv = lds64(sb + SM_ST + t * 8);
                const uint4 hv = lds128(sb + SM_HT + t * 80 + cq * 16);
                const uint32_t h4 = lds32(sb + SM_HT + t * 80 + 64 + cq * 4);
                const uint32_t rr = bmul2(sv.y, 0x3C803C80u);
                char* const dp = (char*)g_s.cand + (co + rank * 1440);
                st_rlx128(dp, (norm2(hv.x, sv.x, rr) & 0xBFFFBFFFu) | par, (norm2(hv.y, sv.x, rr) & 0xBFFFBFFFu) | par,
                          (norm2(hv.z, sv.x, rr) & 0xBFFFBFFFu) | par, (norm2(hv.w, sv.x, rr) & 0xBFFFBFFFu) | par);
                asm volatile("st.relaxed.gpu.global.u32 [%0], %1;" :: "l"((char*)g_s.cand + (co + rank * 1440 + 64 - cq * 12)), "r"((norm2(h4, sv.x, rr) & 0xBFFFBFFFu) | par) : "memory");
            }
            __syncwarp();
        }
        {
            const uint2 sa = lds64(sb + SM_ST + tn * 8), sbb = lds64(sb + SM_ST + tn * 8 + 64);
#pragma unroll
            for (int i = 0; i < 5; i++) { ha[i] = badd2(ha[i], norm2(ha[i], sa.x, sa.y)); hb[i] = badd2(hb[i], norm2(hb[i], sbb.x, sbb.y)); }
            const bool hf = (c & 1) && cq == 0;
            const uint32_t o16 = sb + SM_XT + (hf ? 16384 + tn * 16 : tn * 64 + (cq - (c & 1)) * 16), o4 = sb + SM_XT + ((c & 1) ? tn * 64 + 48 : 16384 + tn * 16) + cq * 4;
            sts128(o16, ha[0], ha[1], ha[2], ha[3]); sts32(o4, ha[4]);
            sts128(o16 + (hf ? 128 : 512), hb[0], hb[1], hb[2], hb[3]); sts32(o4 + ((c & 1) ? 512 : 128), hb[4]);
        }
        if (warp >= 8) {
            STAMP(19);
            mbar_wait(mb + MB_KEY * 8);
            STAMP(20);
            const uint32_t mk = lds32(sb + SM_RK - 256 + (tid >> 2) * 4);
            uint32_t rank = rank4<4, 64>(sb + SM_RK + cq * 16, mk);
            rank += __shfl_xor_sync(~0u, rank, 1); rank += __shfl_xor_sync(~0u, rank, 2);
            if (rank < 8) sts64(sb + SM_SEL + rank * 8, mk, ((tid >> 2) - 64) * 1440);
        }
    }
    bar_sync(11, 640);
    STAMP(12);

    const char* gp = (const char*)g_s.cand + (go + lds32(sb + SM_SEL + 4 + (tk & 7) * 8));
    uint4 hv = ld_rlx128(gp);
    if (warp < 8) loadA();
    const bool red = warp < 6;
    const uint32_t ft = red ? (unsigned)tid / 24u : (unsigned)(tid >> 4) & 7u, fj = red ? 24 * q + tid - ft * 24 : d0 / 3 + (lane & 15);
    const uint32_t key = lds32(sb + SM_SEL + ft * 8), k16 = key << 5;
    float sig = bfr(rcpf(1.f + ex2f(__uint_as_float((k16 ^ (~((int)k16 >> 31) | 0x80000000u)) & 0xFFFF0000u) * -1.4426950408889634f)));
    uint32_t ra2 = sb + SM_RED2 + tid * 12 + ft * 16, fo = (ft * 192 + fj) * 16, oo = ((~key & 2047) * D_ + 3 * fj) * 2;
    uint32_t bx = sb + SM_XS + mr * 1168 + mi * 16 + 288 * kq, gd = mapa(sb, kq * (8 / NRED)) + (SM_GU + (q * nslot + mt) * 128) + lane * 4;
    PIN(ra2); PIN(fo); PIN(oo); PIN(bx); PIN(gd);
    asm volatile("" : "+f"(sig));
    {
        if (warp < 18) {
            int n = 0;
            while ((((hv.x ^ par) | (hv.y ^ par) | (hv.z ^ par) | (hv.w ^ par)) & 0x40004000u) && ++n < SPIN_LIMIT) hv = ld_rlx128(gp);
            sts128(sb + SM_XS + tk * 16 + tid * 16, hv.x ^ par, hv.y ^ par, hv.z ^ par, hv.w ^ par);
        }
    }
    bar_sync(14, 672);
    STAMP(13);
    {
        float c0[4] = {0.f, 0.f, 0.f, 0.f}, c1[4] = {0.f, 0.f, 0.f, 0.f}, c2[4] = {0.f, 0.f, 0.f, 0.f};
        uint32_t b[5][4];
#pragma unroll
        for (int s = 0; s < 4; s++) ldsm4(b[s], bx + s * 64);
        asm volatile("ldmatrix.sync.aligned.m8n8.x2.shared.b16 {%0,%1}, [%2];" : "=r"(b[4][0]), "=r"(b[4][1]) : "r"(bx + 256) : "memory");
        mma_bf16(c0, A[0][0], A[0][1], A[0][2], A[0][3], b[0][0], b[0][1]);
        mma_bf16(c1, A[1][0], A[1][1], A[1][2], A[1][3], b[0][2], b[0][3]);
        mma_bf16(c2, A[2][0], A[2][1], A[2][2], A[2][3], b[1][0], b[1][1]);
        mma_bf16(c0, A[3][0], A[3][1], A[3][2], A[3][3], b[1][2], b[1][3]);
        mma_bf16(c1, A[4][0], A[4][1], A[4][2], A[4][3], b[2][0], b[2][1]);
        mma_bf16(c2, A[5][0], A[5][1], A[5][2], A[5][3], b[2][2], b[2][3]);
        mma_bf16(c0, A[6][0], A[6][1], A[6][2], A[6][3], b[3][0], b[3][1]);
        mma_bf16(c1, A[7][0], A[7][1], A[7][2], A[7][3], b[3][2], b[3][3]);
        mma_bf16(c2, A[8][0], A[8][1], A[8][2], A[8][3], b[4][0], b[4][1]);
        sts128f(sb + SM_RED + tid * 16, c0[0] + c1[0] + c2[0], c0[1] + c1[1] + c2[1], c0[2] + c1[2] + c2[2], c0[3] + c1[3] + c2[3]);
    }
    bar_sync(1 + mt, 128);
    STAMP(21);
    if (mt < nslot && kq < NRED) {
        const uint32_t ra = sb + SM_RED + mt * 512 + lane * 16;
        const float4 p0 = lds128f(ra), p1 = lds128f(ra + 2560), p2 = lds128f(ra + 5120), p3 = lds128f(ra + 7680);
        const float g0 = bfr(((p0.x + p1.x) + (p2.x + p3.x)) * 64.f), g1 = bfr(((p0.y + p1.y) + (p2.y + p3.y)) * 64.f);
        const uint32_t sg = pack_bf16(g0 * rcpf(1.f + ex2f(g0 * -1.4426950408889634f)), g1 * rcpf(1.f + ex2f(g1 * -1.4426950408889634f)));
        const uint32_t gu = bmul2(sg, pack_bf16(((p0.z + p1.z) + (p2.z + p3.z)) * 64.f, ((p0.w + p1.w) + (p2.w + p3.w)) * 64.f));
        const uint32_t pstep = mapa(sb, 1) - mapa(sb, 0), gm = mapa(mb + MB_GU * 8, kq * (8 / NRED));
#pragma unroll
        for (int i = 0; i < 8 / NRED; i++) st_async1(gd + i * pstep, gu, gm + i * pstep);
    }
    mbar_wait(mb + MB_W2 * 8);
    {
        const uint32_t aa = sb + (8 * (mi >> 1) + mr) * (2 * W2W) + (mi & 1) * 16 + (SM_FAR + 32 * W2W * kq + mt * 32 + (W2W == 72 ? 0 : (q & 1) * 16));
#pragma unroll
        for (int s = 0; s < 5; s++) ldsm4t(A[s], aa + s * FAR_SZ);
    }
    {
        uint32_t ba = sb + (SM_GU + 256 * kq) + (lane & 15) * 16 + (lane >> 4) * 1024, wa = sb + (SM_RED2 + kq * 2432 + mt * 64) + g * 4 + cq * 608;
        PIN(ba); PIN(wa);
        STAMP(22);
        mbar_wait(mb + MB_GU * 8);
        STAMP(23);
        float c0[4] = {0.f, 0.f, 0.f, 0.f}, c1[4] = {0.f, 0.f, 0.f, 0.f}, c2[4] = {0.f, 0.f, 0.f, 0.f};
        uint32_t b[2][4], b8, b9;
        ldsm4t(b[0], ba); ldsm4t(b[1], ba + 2048); ldsm2t(b8, b9, ba + 4096);
        mma_bf16(c0, A[0][0], A[0][1], A[0][2], A[0][3], b[0][0], b[0][1]);
        mma_bf16(c1, A[1][0], A[1][1], A[1][2], A[1][3], b[0][2], b[0][3]);
        if (nslot == 5) {
            mma_bf16(c2, A[4][0], A[4][1], A[4][2], A[4][3], b8, b9);
            mma_bf16(c0, A[2][0], A[2][1], A[2][2], A[2][3], b[1][0], b[1][1]);
            mma_bf16(c1, A[3][0], A[3][1], A[3][2], A[3][3], b[1][2], b[1][3]);
        }
        stsf(wa, c0[0] + c1[0] + c2[0]); stsf(wa + 304, c0[1] + c1[1] + c2[1]);
        if (mt < 4) { stsf(wa + 32, c0[2] + c1[2] + c2[2]); stsf(wa + 336, c0[3] + c1[3] + c2[3]); }
    }
    if (warp < 10) {
        float v[3], cnt = 3.f;
        if (red) {
            bar_sync(6, 640);
            STAMP(14);
#pragma unroll
            for (int i = 0; i < 3; i++) v[i] = ((ldsf(ra2 + i * 4) + ldsf(ra2 + i * 4 + 2432)) + (ldsf(ra2 + i * 4 + 4864) + ldsf(ra2 + i * 4 + 7296))) * sig;
        } else {
            bar_arrive(6, 640);
            cnt = 0.f;
#pragma unroll
            for (int i = 0; i < 3; i++) {
                const uint32_t cl = 3 * fj + i - d0;
                const bool ok = cl < 8 * nslot && ((~key >> 3) & 7) == q;
                const uint32_t cf = cl - (c & 1) * 8;
                v[i] = ok ? __uint_as_float(lds16(sb + SM_XT + (cf < 32 ? tslot(~key) * 64 + cf * 2 : 16384 + tslot(~key) * 16 + (cl & 7) * 2)) << 16) : 0.f;
                if (ok) cnt += 1.f;
            }
            mbar_wait(mb + MB_OUT * 8);
        }
        if (cnt != 0.f) {
            float x, y, z, w;
            asm volatile("atom.relaxed.gpu.global.add.v4.f32 {%0,%1,%2,%3}, [%4], {%5,%6,%7,%8};" : "=f"(x), "=f"(y), "=f"(z), "=f"(w)
                         : "l"((char*)g_s.fin + fo), "f"(v[0]), "f"(v[1]), "f"(v[2]), "f"(cnt) : "memory");
            if (w + cnt == 3.f * (NCL + 1)) {
                __nv_bfloat16* op = (__nv_bfloat16*)((char*)prm.out + oo);
                op[0] = __float2bfloat16(x + v[0]); op[1] = __float2bfloat16(y + v[1]); op[2] = __float2bfloat16(z + v[2]);
            }
        }
    } else bar_arrive(6, 640);
    STAMP(15);
}

typedef CUresult (*EncodeFn)(CUtensorMap*, CUtensorMapDataType, cuuint32_t, void*, const cuuint64_t*, const cuuint64_t*,
                             const cuuint32_t*, const cuuint32_t*, CUtensorMapInterleave, CUtensorMapSwizzle,
                             CUtensorMapL2promotion, CUtensorMapFloatOOBfill);

void make_map(EncodeFn fn, CUtensorMap* tm, const void* p, int cols, int rows, int bc, int br) {
    cuuint64_t dims[2] = {(cuuint64_t)cols, (cuuint64_t)rows};
    cuuint64_t strides[1] = {(cuuint64_t)cols * 2};
    cuuint32_t box[2] = {(cuuint32_t)bc, (cuuint32_t)br};
    cuuint32_t es[2] = {1, 1};
    fn(tm, CU_TENSOR_MAP_DATA_TYPE_BFLOAT16, 2, const_cast<void*>(p), dims, strides, box, es, CU_TENSOR_MAP_INTERLEAVE_NONE,
       CU_TENSOR_MAP_SWIZZLE_NONE, CU_TENSOR_MAP_L2_PROMOTION_L2_128B, CU_TENSOR_MAP_FLOAT_OOB_FILL_NONE);
}

void make_map3(EncodeFn fn, CUtensorMap* tm, const void* p) {
    cuuint64_t dims[3] = {(cuuint64_t)D_, 64, 32};
    cuuint64_t strides[2] = {(cuuint64_t)D_ * 2, (cuuint64_t)D_ * 128};
    cuuint32_t box[3] = {40, 8, 32};
    cuuint32_t es[3] = {1, 1, 1};
    fn(tm, CU_TENSOR_MAP_DATA_TYPE_BFLOAT16, 3, const_cast<void*>(p), dims, strides, box, es, CU_TENSOR_MAP_INTERLEAVE_NONE,
       CU_TENSOR_MAP_SWIZZLE_NONE, CU_TENSOR_MAP_L2_PROMOTION_NONE, CU_TENSOR_MAP_FLOAT_OOB_FILL_NONE);
}

void make_map5(EncodeFn fn, CUtensorMap* tm, const void* p, int bc) {
    cuuint64_t dims[5] = {(cuuint64_t)D_, 2, 4, 4, 64};
    cuuint64_t strides[4] = {(cuuint64_t)D_ * 128, (cuuint64_t)D_ * 1024, (cuuint64_t)D_ * 256, (cuuint64_t)D_ * 2};
    cuuint32_t box[5] = {(cuuint32_t)bc, 2, 4, 4, 8};
    cuuint32_t es[5] = {1, 1, 1, 1, 1};
    fn(tm, CU_TENSOR_MAP_DATA_TYPE_BFLOAT16, 5, const_cast<void*>(p), dims, strides, box, es, CU_TENSOR_MAP_INTERLEAVE_NONE,
       CU_TENSOR_MAP_SWIZZLE_NONE, CU_TENSOR_MAP_L2_PROMOTION_NONE, CU_TENSOR_MAP_FLOAT_OOB_FILL_NONE);
}

}

extern "C" void kernel_launch(void* const* d_in, const int* in_sizes, int n_in, void* d_out, int out_size) {
    (void)in_sizes; (void)n_in; (void)out_size;
    void* fp = nullptr;
    cudaDriverEntryPointQueryResult qr;
    cudaGetDriverEntryPoint("cuTensorMapEncodeTiled", &fp, cudaEnableDefault, &qr);
    EncodeFn fn = (EncodeFn)fp;
    CUtensorMap tmG, tmU, tmD, tmO, tmX, tmH;
    make_map3(fn, &tmX, d_in[0]);
    make_map(fn, &tmG, d_in[11], F_, D_, 40, 48);
    make_map(fn, &tmU, d_in[12], F_, D_, 40, 48);
    make_map(fn, &tmD, d_in[13], D_, F_, W2W, 64);
    make_map5(fn, &tmO, d_out, 32);
    make_map5(fn, &tmH, d_out, 8);
    Params p;
    p.x = (const unsigned short*)d_in[0];
    for (int i = 0; i < 6; i++) p.prm6[i] = (const unsigned short*)d_in[1 + i];
    p.logdt = (const unsigned short*)d_in[7]; p.dskip = (const unsigned short*)d_in[8];
    p.wr = (const unsigned short*)d_in[10];
    p.out = (__nv_bfloat16*)d_out;
    p.zero = 0;
    cudaGetSymbolAddress((void**)&p.gs, g_s);
    cudaFuncSetAttribute(fused_kernel, cudaFuncAttributeMaxDynamicSharedMemorySize, SM_TOTAL);
    fused_kernel<<<NCTA, NTHR, SM_TOTAL>>>(p, tmG, tmU, tmD, tmO, tmX, tmH);
}
```

```cpp
#include <cuda_runtime.h>
#include <cuda_bf16.h>
#include <cuda_fp16.h>
#include <cuda.h>
#include <stdint.h>

namespace {

constexpr int L_ = 2048, D_ = 576, F_ = 4608;
constexpr int NCL = 15, CS = 8, NCTA = NCL * CS, NTHR = 768;
#define PACE_NS 0
#define AFTERX 0
#define EARLYB 0
#define GAP_NS 0
#define PACE0 200
#define W2W 72
#define ROWE 0
#define SYNC13 2
#define XW 48
#define TILE_NS -1
#define LNPOS 1
#define MMPOS 0
constexpr int XSPLIT = 3, NRED = 2;
constexpr int SPIN_LIMIT = 1 << 22;

constexpr int SM_WG   = 0;
constexpr int SM_WU   = 46080;
constexpr int YP = 3376, YS = 672;
constexpr int UP = 3376, US = 672;
constexpr int SM_XT   = 92160;
constexpr int SM_U    = SM_XT + 8 * YP;
constexpr int SM_FAR  = SM_U + 8 * UP;
constexpr int FAR_SZ  = 12416;
constexpr int F_E5 = 0, F_O5 = 1536, F_E3 = 3088, F_O3 = 4624, F_E7 = 6176, F_E2 = F_E7 + 1024, F_E9 = F_E7 + 2048,
              F_H = 3088, F_O7 = F_E7 + F_H, F_O2 = F_E2 + F_H, F_O9 = F_E9 + F_H;
constexpr int SM_P    = SM_FAR + 5 * FAR_SZ;
constexpr int PN_SZ = 584 * 4, SM_PN = SM_P + 64 * 4;
constexpr int P_GS = 48 * 4, P_H7 = 192 * 4, P_HS = 72 * 4;
constexpr int PF_SZ = (192 + 216) * 4, SM_PF = SM_PN + 5 * PN_SZ + 32;
constexpr int SM_MISC = SM_PF + 5 * PF_SZ;
constexpr int SM_ST   = SM_MISC;
constexpr int SM_RK   = SM_ST + 2048;
constexpr int SM_SEL  = SM_RK + 256;
constexpr int SM_KG   = SM_SEL + 64;
constexpr int SM_SC   = SM_KG + 160;
constexpr int SM_DW   = SM_SC + 32;
constexpr int SM_MB   = SM_DW + 160;
constexpr int SM_TOTAL = SM_MB + 128;
constexpr int SM_ROW  = SM_XT - 20736;
constexpr int SM_XTL  = SM_ROW - 512 * XW;
constexpr int SM_RED2 = SM_WG;
constexpr int SM_HT   = SM_P - 512;
constexpr int SM_KEY  = SM_FAR + 10240 + 128;
constexpr int SM_CAND = SM_KEY + 1024;
constexpr int SM_XS   = SM_U;
constexpr int SM_GU   = SM_XS + 9344;
constexpr int SM_RED  = SM_GU + 5632;
static_assert(F_O9 + 1024 <= FAR_SZ && FAR_SZ % 128 == 0, "far overflow");
static_assert(SM_RED + 10240 <= SM_FAR && SM_HT + 20496 <= SM_MISC, "alias overflow");
static_assert(SM_TOTAL <= 232448, "smem overflow");
static_assert(SM_FAR % 128 == 0 && SM_XT % 128 == 0 && SM_XTL % 128 == 0 && SM_P % 16 == 0 && SM_MISC % 16 == 0 && SM_MB % 8 == 0, "align");

enum { MB_X = 0, MB_W1 = 5, MB_W2 = 6, MB_KEY = 7, MB_GU = 8, MB_Y = 9, MB_OUT = 10, MB_T = 11, MB_R = 12 };

struct __align__(128) Scratch {
    unsigned epoch, zcnt, pad[30];
    uint4  st1[L_ * 2];
    float4 acc[L_];
    uint4  cand[64 * NCL * 6];
    float4 fin[8 * 192 + 24];
};
__device__ Scratch g_s;
#define STAMP(i)

__device__ __forceinline__ uint32_t mapa(uint32_t a, uint32_t r) { uint32_t d; asm("mapa.shared::cluster.u32 %0, %1, %2;" : "=r"(d) : "r"(a), "r"(r)); return d; }
__device__ __forceinline__ void mbar_wait(uint32_t mb) {
    asm volatile("{ .reg .pred p, q; .reg .u32 n; mov.u32 n, 0;\n"
                 "W_%=: mbarrier.try_wait.parity.shared::cta.b64 p, [%0], 0; add.u32 n, n, 1; setp.lt.and.u32 q, n, 65536, !p; @q bra W_%=; }" :: "r"(mb) : "memory");
}
__device__ __forceinline__ void arm(uint32_t mb, uint32_t bytes) { asm volatile("mbarrier.arrive.expect_tx.shared::cta.b64 _, [%0], %1;" :: "r"(mb), "r"(bytes) : "memory"); }
__device__ __forceinline__ void bar_sync(int id, int n) { asm volatile("bar.sync %0, %1;" :: "r"(id), "r"(n) : "memory"); }
__device__ __forceinline__ void bar_arrive(int id, int n) { asm volatile("bar.arrive %0, %1;" :: "r"(id), "r"(n) : "memory"); }
__device__ __forceinline__ uint32_t lds16(uint32_t a) { unsigned short v; asm volatile("ld.shared.u16 %0, [%1];" : "=h"(v) : "r"(a) : "memory"); return v; }
__device__ __forceinline__ uint32_t lds32(uint32_t a) { uint32_t v; asm volatile("ld.shared.u32 %0, [%1];" : "=r"(v) : "r"(a) : "memory"); return v; }
__device__ __forceinline__ uint2 lds64(uint32_t a) { uint2 v; asm volatile("ld.shared.v2.u32 {%0,%1}, [%2];" : "=r"(v.x), "=r"(v.y) : "r"(a) : "memory"); return v; }
__device__ __forceinline__ float ldsf(uint32_t a) { float v; asm volatile("ld.shared.f32 %0, [%1];" : "=f"(v) : "r"(a) : "memory"); return v; }
__device__ __forceinline__ uint4 lds128(uint32_t a) { uint4 v; asm volatile("ld.shared.v4.u32 {%0,%1,%2,%3}, [%4];" : "=r"(v.x), "=r"(v.y), "=r"(v.z), "=r"(v.w) : "r"(a) : "memory"); return v; }
__device__ __forceinline__ float4 lds128f(uint32_t a) { float4 v; asm volatile("ld.shared.v4.f32 {%0,%1,%2,%3}, [%4];" : "=f"(v.x), "=f"(v.y), "=f"(v.z), "=f"(v.w) : "r"(a) : "memory"); return v; }
__device__ __forceinline__ void sts16(uint32_t a, uint32_t v) { asm volatile("{ .reg .b16 l, h; mov.b32 {l, h}, %1; st.shared.b16 [%0], l; }" :: "r"(a), "r"(v) : "memory"); }
__device__ __forceinline__ void sts32(uint32_t a, uint32_t v) { asm volatile("st.shared.u32 [%0], %1;" :: "r"(a), "r"(v) : "memory"); }
__device__ __forceinline__ void sts64(uint32_t a, uint32_t x, uint32_t y) { asm volatile("st.shared.v2.u32 [%0], {%1,%2};" :: "r"(a), "r"(x), "r"(y) : "memory"); }
__device__ __forceinline__ void stsf(uint32_t a, float v) { asm volatile("st.shared.f32 [%0], %1;" :: "r"(a), "f"(v) : "memory"); }
__device__ __forceinline__ void sts128(uint32_t a, uint32_t x, uint32_t y, uint32_t z, uint32_t w) { asm volatile("st.shared.v4.u32 [%0], {%1,%2,%3,%4};" :: "r"(a), "r"(x), "r"(y), "r"(z), "r"(w) : "memory"); }
__device__ __forceinline__ void sts128f(uint32_t a, float x, float y, float z, float w) { asm volatile("st.shared.v4.f32 [%0], {%1,%2,%3,%4};" :: "r"(a), "f"(x), "f"(y), "f"(z), "f"(w) : "memory"); }
__device__ __forceinline__ void ldsm4(uint32_t (&r)[4], uint32_t a) { asm volatile("ldmatrix.sync.aligned.m8n8.x4.shared.b16 {%0,%1,%2,%3}, [%4];" : "=r"(r[0]), "=r"(r[1]), "=r"(r[2]), "=r"(r[3]) : "r"(a) : "memory"); }
__device__ __forceinline__ void ldsm4t(uint32_t (&r)[4], uint32_t a) { asm volatile("ldmatrix.sync.aligned.m8n8.x4.trans.shared.b16 {%0,%1,%2,%3}, [%4];" : "=r"(r[0]), "=r"(r[1]), "=r"(r[2]), "=r"(r[3]) : "r"(a) : "memory"); }
__device__ __forceinline__ void ldsm2t(uint32_t& r0, uint32_t& r1, uint32_t a) { asm volatile("ldmatrix.sync.aligned.m8n8.x2.trans.shared.b16 {%0,%1}, [%2];" : "=r"(r0), "=r"(r1) : "r"(a) : "memory"); }
__device__ __forceinline__ void stsm4t(uint32_t a, uint32_t r0, uint32_t r1, uint32_t r2, uint32_t r3) { asm volatile("stmatrix.sync.aligned.m8n8.x4.trans.shared.b16 [%0], {%1,%2,%3,%4};" :: "r"(a), "r"(r0), "r"(r1), "r"(r2), "r"(r3) : "memory"); }
__device__ __forceinline__ void stsm4(uint32_t a, uint32_t r0, uint32_t r1, uint32_t r2, uint32_t r3) { asm volatile("stmatrix.sync.aligned.m8n8.x4.shared.b16 [%0], {%1,%2,%3,%4};" :: "r"(a), "r"(r0), "r"(r1), "r"(r2), "r"(r3) : "memory"); }
__device__ __forceinline__ void stsm2t(uint32_t a, uint32_t r0, uint32_t r1) { asm volatile("stmatrix.sync.aligned.m8n8.x2.trans.shared.b16 [%0], {%1,%2};" :: "r"(a), "r"(r0), "r"(r1) : "memory"); }
__device__ __forceinline__ uint4 ldg128(const void* p) { uint4 v; asm volatile("ld.global.nc.v4.u32 {%0,%1,%2,%3}, [%4];" : "=r"(v.x), "=r"(v.y), "=r"(v.z), "=r"(v.w) : "l"(p)); return v; }
__device__ __forceinline__ uint32_t ldg16(const void* p) { unsigned short v; asm volatile("ld.global.nc.u16 %0, [%1];" : "=h"(v) : "l"(p)); return v; }
__device__ __forceinline__ uint32_t opaque(uint32_t v) { uint32_t r; asm volatile("mov.b32 %0, %1;" : "=r"(r) : "r"(v)); return r; }
__device__ __forceinline__ void mma_f16(float (&d)[4], const uint32_t (&a)[4], uint32_t b0, uint32_t b1) {
    asm volatile("mma.sync.aligned.m16n8k16.row.col.f32.f16.f16.f32 {%0,%1,%2,%3}, {%4,%5,%6,%7}, {%8,%9}, {%0,%1,%2,%3};"
        : "+f"(d[0]), "+f"(d[1]), "+f"(d[2]), "+f"(d[3]) : "r"(a[0]), "r"(a[1]), "r"(a[2]), "r"(a[3]), "r"(b0), "r"(b1));
}
__device__ __forceinline__ void mma_bf16(float (&d)[4], uint32_t a0, uint32_t a1, uint32_t a2, uint32_t a3, uint32_t b0, uint32_t b1) {
    asm volatile("mma.sync.aligned.m16n8k16.row.col.f32.bf16.bf16.f32 {%0,%1,%2,%3}, {%4,%5,%6,%7}, {%8,%9}, {%0,%1,%2,%3};"
        : "+f"(d[0]), "+f"(d[1]), "+f"(d[2]), "+f"(d[3]) : "r"(a0), "r"(a1), "r"(a2), "r"(a3), "r"(b0), "r"(b1));
}
__device__ __forceinline__ void mma_bf16_k8(float (&d)[4], uint32_t a0, uint32_t a1, uint32_t b0) {
    asm volatile("mma.sync.aligned.m16n8k8.row.col.f32.bf16.bf16.f32 {%0,%1,%2,%3}, {%4,%5}, {%6}, {%0,%1,%2,%3};"
        : "+f"(d[0]), "+f"(d[1]), "+f"(d[2]), "+f"(d[3]) : "r"(a0), "r"(a1), "r"(b0));
}
__device__ __forceinline__ uint32_t pack_f16(float lo, float hi) { uint32_t r; asm("cvt.rn.f16x2.f32 %0, %1, %2;" : "=r"(r) : "f"(hi), "f"(lo)); return r; }
__device__ __forceinline__ uint32_t pack_bf16(float lo, float hi) { uint32_t r; asm("cvt.rn.bf16x2.f32 %0, %1, %2;" : "=r"(r) : "f"(hi), "f"(lo)); return r; }
__device__ __forceinline__ float bf_lo(uint32_t v) { return __uint_as_float(v << 16); }
__device__ __forceinline__ float bf_hi(uint32_t v) { return __uint_as_float(v & 0xFFFF0000u); }
__device__ __forceinline__ float bfr(float x) { return __uint_as_float(pack_bf16(0.f, x)); }
__device__ __forceinline__ uint32_t badd2(uint32_t a, uint32_t b) { uint32_t r; asm("add.rn.bf16x2 %0, %1, %2;" : "=r"(r) : "r"(a), "r"(b)); return r; }
__device__ __forceinline__ uint32_t bmul2(uint32_t a, uint32_t b) { uint32_t r; asm("mul.rn.bf16x2 %0, %1, %2;" : "=r"(r) : "r"(a), "r"(b)); return r; }
__device__ __forceinline__ uint32_t hadd2(uint32_t a, uint32_t b) { uint32_t r; asm("add.rn.f16x2 %0, %1, %2;" : "=r"(r) : "r"(a), "r"(b)); return r; }
__device__ __forceinline__ uint32_t hmul2(uint32_t a, uint32_t b) { uint32_t r; asm("mul.rn.f16x2 %0, %1, %2;" : "=r"(r) : "r"(a), "r"(b)); return r; }
__device__ __forceinline__ uint32_t hfma2(uint32_t a, uint32_t b, uint32_t c) { uint32_t r; asm("fma.rn.f16x2 %0, %1, %2, %3;" : "=r"(r) : "r"(a), "r"(b), "r"(c)); return r; }
__device__ __forceinline__ uint32_t hneg2(uint32_t a) { uint32_t r; asm("neg.f16x2 %0, %1;" : "=r"(r) : "r"(a)); return r; }
__device__ __forceinline__ float rcpf(float x) { float r; asm("rcp.approx.ftz.f32 %0, %1;" : "=f"(r) : "f"(x)); return r; }
__device__ __forceinline__ float sqrta(float x) { float r; asm("sqrt.approx.ftz.f32 %0, %1;" : "=f"(r) : "f"(x)); return r; }
__device__ __forceinline__ float ex2f(float x) { float r; asm("ex2.approx.ftz.f32 %0, %1;" : "=f"(r) : "f"(x)); return r; }
__device__ __forceinline__ void st_async4(uint32_t a, uint32_t x, uint32_t y, uint32_t z, uint32_t w, uint32_t mb) {
    asm volatile("st.async.shared::cluster.mbarrier::complete_tx::bytes.v4.u32 [%0], {%1,%2,%3,%4}, [%5];" :: "r"(a), "r"(x), "r"(y), "r"(z), "r"(w), "r"(mb) : "memory"); }
__device__ __forceinline__ void st_async1(uint32_t a, uint32_t x, uint32_t mb) {
    asm volatile("st.async.shared::cluster.mbarrier::complete_tx::bytes.u32 [%0], %1, [%2];" :: "r"(a), "r"(x), "r"(mb) : "memory"); }
__device__ __forceinline__ unsigned ld_rlx(const void* p) { unsigned v; asm volatile("ld.relaxed.gpu.global.u32 %0, [%1];" : "=r"(v) : "l"(p) : "memory"); return v; }
__device__ __forceinline__ unsigned ld_acq(const void* p) { unsigned v; asm volatile("ld.acquire.gpu.global.u32 %0, [%1];" : "=r"(v) : "l"(p) : "memory"); return v; }
__device__ __forceinline__ uint2 ld_rlx64(const void* p) { unsigned long long v; asm volatile("ld.relaxed.gpu.global.u64 %0, [%1];" : "=l"(v) : "l"(p) : "memory"); return make_uint2((unsigned)v, (unsigned)(v >> 32)); }
__device__ __forceinline__ void st_rlx128(void* p, uint32_t x, uint32_t y, uint32_t z, uint32_t w) {
    asm volatile("st.relaxed.gpu.global.v2.u64 [%0], {%1,%2};" :: "l"(p), "l"((unsigned long long)x | ((unsigned long long)y << 32)), "l"((unsigned long long)z | ((unsigned long long)w << 32)) : "memory"); }
__device__ __forceinline__ uint4 ld_rlx128(const void* p) { unsigned long long a, b; asm volatile("ld.relaxed.gpu.global.v2.u64 {%0,%1}, [%2];" : "=l"(a), "=l"(b) : "l"(p) : "memory"); return make_uint4((unsigned)a, (unsigned)(a >> 32), (unsigned)b, (unsigned)(b >> 32)); }
__device__ __forceinline__ void tma2d(uint32_t dst, const CUtensorMap* tm, int x, int y, uint32_t mb) {
    asm volatile("cp.async.bulk.tensor.2d.shared::cluster.global.mbarrier::complete_tx::bytes [%0], [%1, {%3, %4}], [%2];"
                 :: "r"(dst), "l"(tm), "r"(mb), "r"(x), "r"(y) : "memory");
}
__device__ __forceinline__ void cmul(float& xr, float& xi, float ar, float ai, float br, float bi) {
    const float r = fmaf(ar, br, -ai * bi), i = fmaf(ar, bi, ai * br); xr = r; xi = i;
}
__device__ __forceinline__ void csq(float& xr, float& xi, float ar, float ai) {
    const float r = fmaf(ar, ar, -ai * ai), i = (ar + ar) * ai; xr = r; xi = i;
}
__device__ __forceinline__ void cexp_s(float& zr, float& zi, float e2, float turns) {
    const float mag = ex2f(e2), r = (turns - rintf(turns)) * 6.283185307179586f;
    zr = mag * __cosf(r); zi = mag * __sinf(r);
}
__device__ __forceinline__ uint32_t ln_stats(float s1, float s2) {
    const float m = s1 * (1.f / D_);
    const float var = fmaxf(fmaf(s2, 1.f / D_, -m * m), 0.f);
    return pack_bf16(m, sqrta(bfr(bfr(var) + 1e-5f)));
}
__device__ __forceinline__ uint32_t rsplit(float rs) { const float h = bfr(rs); return pack_bf16(h, rs - h); }
__device__ __forceinline__ uint32_t norm2(uint32_t v, uint32_t mx, uint32_t hl) {
    uint32_t r;
    asm("{ .reg .b16 m, h, l, x; .reg .b32 m2, h2, l2, d, t; mov.b32 {m, x}, %2; mov.b32 {h, l}, %3; mov.b32 m2, {m, m}; mov.b32 h2, {h, h}; mov.b32 l2, {l, l};\n"
        "sub.rn.bf16x2 d, %1, m2; mul.rn.bf16x2 t, d, l2; fma.rn.bf16x2 %0, d, h2, t; }" : "=r"(r) : "r"(v), "r"(mx), "r"(hl));
    return r;
}
template <int N, int S>
__device__ __forceinline__ uint32_t rank4(uint32_t a, uint32_t key) {
    uint32_t r0 = 0, r1 = 0, r2 = 0, r3 = 0;
#pragma unroll
    for (int i = 0; i < N; i++) {
        const uint4 o = lds128(a + i * S);
        r0 += (key - o.x) >> 31; r1 += (key - o.y) >> 31; r2 += (key - o.z) >> 31; r3 += (key - o.w) >> 31;
    }
    return (r0 + r1) + (r2 + r3);
}
typedef uint32_t H2C;
__device__ __forceinline__ H2C splat(float r, float i) { return pack_f16(r, i); }
__device__ __forceinline__ void hcmul(uint32_t& xr, uint32_t& xi, uint32_t R, uint32_t I, H2C m) {
    asm("{ .reg .b16 a, b; .reg .b32 a2, b2, t; mov.b32 {a, b}, %4; mov.b32 a2, {a, a}; mov.b32 b2, {b, b};\n"
        "mul.rn.f16x2 t, %3, b2; neg.f16x2 t, t; fma.rn.f16x2 %0, %2, a2, t; mul.rn.f16x2 t, %3, a2; fma.rn.f16x2 %1, %2, b2, t; }"
        : "=&r"(xr), "=r"(xi) : "r"(R), "r"(I), "r"(m));
}
__device__ __forceinline__ void expand4(uint32_t are, uint32_t aim, uint32_t R0, uint32_t R1, uint32_t I0, uint32_t I1, H2C m4) {
    uint32_t R2, I2, R3, I3;
    hcmul(R2, I2, R0, I0, m4); hcmul(R3, I3, R1, I1, m4);
    sts128(are, R0, R1, R2, R3);
    sts128(aim, I0, I1, I2, I3);
}
__device__ __forceinline__ void expand8(uint32_t are, uint32_t aim, float sr, float si, float m1r, float m1i, float m2r, float m2i, H2C m4) {
    float r1, i1, r2, i2, r3, i3;
    cmul(r1, i1, sr, si, m1r, m1i); cmul(r2, i2, sr, si, m2r, m2i); cmul(r3, i3, r1, i1, m2r, m2i);
    expand4(are, aim, pack_f16(sr, r1), pack_f16(r2, r3), pack_f16(si, i1), pack_f16(i2, i3), m4);
}
__device__ __forceinline__ void put16(uint32_t a, uint32_t v) { sts16(a, v); sts16(a + 6, v); }

struct Params {
    const unsigned short *x, *prm6[6], *logdt, *dskip, *wr;
    __nv_bfloat16* out;
    Scratch* gs;
    unsigned zero;
};
__device__ __forceinline__ uint32_t tslot(uint32_t t) { return (t & 7) * 32 + ((t >> 4) & 24) + ((t >> 8) & 6) + ((t >> 6) & 1); }
#define CP(x) ((x) | zero)
#define PIN(x) asm volatile("or.b32 %0, %0, %1;" : "+r"(x) : "r"(zero))
__device__ __forceinline__ void wgmma32(float (&d)[4][4], const uint32_t (&a)[4], uint32_t dlo) {
    asm volatile("{ .reg .b64 ds; mov.b64 ds, {%20, %21};\n"
                 "wgmma.mma_async.sync.aligned.m64n32k16.f32.f16.f16 {%0,%1,%2,%3,%4,%5,%6,%7,%8,%9,%10,%11,%12,%13,%14,%15}, {%16,%17,%18,%19}, ds, 1, 1, 1, 0; }"
        : "+f"(d[0][0]), "+f"(d[0][1]), "+f"(d[0][2]), "+f"(d[0][3]), "+f"(d[1][0]), "+f"(d[1][1]), "+f"(d[1][2]), "+f"(d[1][3]),
          "+f"(d[2][0]), "+f"(d[2][1]), "+f"(d[2][2]), "+f"(d[2][3]), "+f"(d[3][0]), "+f"(d[3][1]), "+f"(d[3][2]), "+f"(d[3][3])
        : "r"(a[0]), "r"(a[1]), "r"(a[2]), "r"(a[3]), "r"(dlo), "n"(128 >> 4));
}

__global__ void __cluster_dims__(CS, 1, 1) __launch_bounds__(NTHR, 1)
fused_kernel(const __grid_constant__ Params prm, const __grid_constant__ CUtensorMap tmG, const __grid_constant__ CUtensorMap tmU,
             const __grid_constant__ CUtensorMap tmD, const __grid_constant__ CUtensorMap tmO, const __grid_constant__ CUtensorMap tmX, const __grid_constant__ CUtensorMap tmH)
{
    extern __shared__ __align__(1024) unsigned char smem[];
    const int tid = threadIdx.x, lane = tid & 31, warp = __shfl_sync(~0u, tid >> 5, 0);
    const int c = blockIdx.x >> 3, q = blockIdx.x & 7;
    const int nslot = (c < NCL - 1) ? 5 : 2;
    const int d0 = 40 * c;
    const uint32_t sb = opaque((uint32_t)__cvta_generic_to_shared(smem));
    const uint32_t mb = sb + SM_MB;
    Scratch& g_s = *prm.gs;
    const unsigned& zero = prm.zero;
    STAMP(0);

    if (warp >= 20) {
        unsigned epoch = 0;
        if (warp == 20) {
            if (lane == 0) {
#pragma unroll
                for (int i = 0; i < 13; i++)
                    asm volatile("mbarrier.init.shared::cta.b64 [%0], %1;" :: "r"(mb + i * 8), "r"((i == MB_R || i < 2) ? 2 : i == MB_Y ? 1 + 4 * nslot : 1) : "memory");
                asm volatile("fence.mbarrier_init.release.cluster;" ::: "memory");
                arm(mb + MB_W1 * 8, 92160); arm(mb + MB_W2 * 8, nslot * (128 * W2W)); arm(mb + MB_KEY * 8, 256); arm(mb + MB_GU * 8, nslot * 1024); arm(mb + MB_T * 8, 512 * XW);
                const int bytes = max(min(18, L_ - 18 * (int)blockIdx.x), 1) * (D_ * 2);
                arm(mb + MB_R * 8, bytes);
                if (ROWE) asm volatile("cp.async.bulk.shared::cluster.global.mbarrier::complete_tx::bytes [%0], [%1], %2, [%3];"
                             :: "r"(sb + SM_ROW), "l"(prm.x + min(18 * (int)blockIdx.x, L_ - 1) * D_), "r"(max(min(18, L_ - 18 * (int)blockIdx.x), 1) * (D_ * 2)), "r"(mb + MB_R * 8) : "memory");
            }
            __syncwarp();
        } else if (warp == 22) {
            epoch = ld_rlx(&g_s.epoch);
            if (lane < 18 ? 18 * c + lane < 256 : lane < 31) (lane < 18 ? &g_s.acc[256 * q + 18 * c] : &g_s.fin[13 * (int)blockIdx.x - 18])[lane] = make_float4(0.f, 0.f, 0.f, 0.f);
        } else if (warp == 23 && lane == 0) asm volatile("prefetch.tensormap [%0];" :: "l"(&tmX) : "memory");
        asm volatile("barrier.cluster.arrive.relaxed.aligned;" ::: "memory");
        bar_sync(12, NTHR);
        if (warp == 22) {
            if (lane == 0) { sts32(sb + SM_SC + 28, epoch); asm volatile("mbarrier.arrive.shared::cta.b64 _, [%0];" :: "r"(mb + MB_R * 8) : "memory"); }
            epoch++;
            asm volatile("fence.acq_rel.gpu;" ::: "memory");
            __syncwarp();
            if (lane == 0) asm volatile("red.relaxed.gpu.global.add.u32 [%0], 1;" :: "l"(&g_s.zcnt) : "memory");
            STAMP(1);
            uint4 wv = make_uint4(0, 0, 0, 0), wv2 = ldg128((const uint4*)prm.wr + lane), wv3 = ldg128((const uint4*)prm.wr + 32 + lane);
            if (lane < 8) wv = ldg128((const uint4*)prm.wr + 64 + lane);
            if (lane < 5) {
                uint4 v = make_uint4(0, 0, 0, 0);
                if (lane < nslot) v = ldg128((const uint4*)(prm.wr + d0) + lane);
                sts128(sb + SM_DW + lane * 16, v.x, v.y, v.z, v.w);
            }
            __syncwarp();
            if (lane < 2) asm volatile("mbarrier.arrive.shared::cta.b64 _, [%0];" :: "r"(mb + (MB_X + lane) * 8) : "memory");
            mbar_wait(mb + (MB_X + 1) * 8);
            const uint32_t old = (epoch & 1) ? 0u : 0x40004000u;
#pragma unroll
            for (int t = 0; t < 2; t++)
                if ((lane & 7) < 6) g_s.cand[((q * 8 + 4 * t + (lane >> 3)) * NCL + c) * 6 + (lane & 7)] = make_uint4(old, old, old, old);
            float a[4] = {0.f, 0.f, 0.f, 0.f};
            const uint32_t one = 0x3F803F80u;
            mma_bf16(a, one, one, one, one, wv.x, wv.y);  mma_bf16(a, one, one, one, one, wv.z, wv.w);
            mma_bf16(a, one, one, one, one, wv2.x, wv2.y); mma_bf16(a, one, one, one, one, wv2.z, wv2.w);
            mma_bf16(a, one, one, one, one, wv3.x, wv3.y); mma_bf16(a, one, one, one, one, wv3.z, wv3.w);
            float s = a[0] + a[1];
            s += __shfl_xor_sync(~0u, s, 1); s += __shfl_xor_sync(~0u, s, 2);
            stsf(sb + SM_SC + 24, s);
            __syncwarp();
            if (lane == 0) {
                int n = 0;
                while ((int)(ld_acq(&g_s.zcnt) - epoch * NCTA) < 0 && ++n < SPIN_LIMIT) __nanosleep(200);
                arm(mb + MB_Y * 8, 8 * 512 * nslot);
                if (blockIdx.x == 0) g_s.epoch = epoch;
            }
            STAMP(2);
            return;
        }
        if (warp == 21) {
            if (lane == 0) { asm volatile("prefetch.tensormap [%0];" :: "l"(&tmG) : "memory"); asm volatile("prefetch.tensormap [%0];" :: "l"(&tmU) : "memory"); asm volatile("prefetch.tensormap [%0];" :: "l"(&tmD) : "memory"); }
            __syncwarp();
            if (EARLYB) { bar_arrive(13, 736); mbar_wait(mb + MB_T * 8); if (GAP_NS) __nanosleep(GAP_NS); } else bar_sync(13, 736);
#pragma unroll 1
            for (int i = 0; i < 24; i++) {
                if (AFTERX && i == EARLYB) bar_sync(0, 96);
                if (i == SM_XTL / 3840) { bar_sync(15, 544); asm volatile("fence.proxy.async.shared::cta;" ::: "memory"); }
                if (lane == 0) tma2d(sb + SM_WG + i * 3840, i < 12 ? &tmG : &tmU, 320 * c + 8 * nslot * q, 48 * (i < 12 ? i : i - 12), mb + MB_W1 * 8);
                if (PACE_NS >= 0) __nanosleep(i < EARLYB ? PACE0 : PACE_NS);
            }
            STAMP(1);
            return;
        }
        if (warp == 20) {
            if (!ROWE && lane == 0) {
                asm volatile("cp.async.bulk.shared::cluster.global.mbarrier::complete_tx::bytes [%0], [%1], %2, [%3];"
                             :: "r"(sb + SM_ROW), "l"(prm.x + min(18 * (int)blockIdx.x, L_ - 1) * D_), "r"(max(min(18, L_ - 18 * (int)blockIdx.x), 1) * (D_ * 2)), "r"(mb + MB_R * 8) : "memory");
            }
            __syncwarp();
            if (TILE_NS < 0) mbar_wait(mb + MB_R * 8); else if (TILE_NS) __nanosleep(TILE_NS);
            if (lane == 0) {
                asm volatile("cp.async.bulk.tensor.3d.shared::cluster.global.mbarrier::complete_tx::bytes [%0], [%1, {%3, %4, %5}], [%2];"
                             :: "r"(sb + SM_XTL), "l"(&tmX), "r"(mb + MB_T * 8), "r"(XW == 40 ? d0 : d0 & ~15), "r"(8 * q), "r"(0) : "memory");
            }
            STAMP(6);
        }
        asm volatile("barrier.cluster.wait.aligned;" ::: "memory");
        bar_sync(13, 736);
        asm volatile("fence.proxy.async.shared::cta;" ::: "memory");
        {
            const int gr = lane >> 2, pe = (((lane & 3) ^ (gr * 3)) * 2 + (warp & 1)) & 7;
            const int s0 = gr ? 0 : XSPLIT, ns = gr ? min(XSPLIT, nslot) : nslot - XSPLIT;
            if (gr < 2 && ns > 0) {
                const int bytes = ns * YS - 160;
                if (pe == q) arm(mb + (MB_X + gr) * 8, 7 * bytes);
                else {
                    const uint32_t rb_ = mapa(sb, pe);
                    asm volatile("cp.async.bulk.shared::cluster.shared::cta.mbarrier::complete_tx::bytes [%0], [%1], %2, [%3];"
                                 :: "r"(rb_ + SM_U + 128 + q * UP + s0 * US), "r"(sb + SM_XT + 128 + pe * YP + s0 * YS), "r"(bytes), "r"(rb_ + SM_MB + (MB_X + gr) * 8) : "memory");
                }
            }
        }
        __syncwarp();
        if (AFTERX) bar_arrive(0, 96);
        STAMP(1);
        if (warp == 20 && lane == 0) { asm volatile("prefetch.tensormap [%0];" :: "l"(&tmO) : "memory"); asm volatile("prefetch.tensormap [%0];" :: "l"(&tmH) : "memory"); }
        if (warp == 23) {
#pragma unroll 1
            for (int kk = nslot - 1; kk >= 0; kk--) {
                __syncwarp();
                bar_sync(6 + kk, 160);
                if (lane == 0) { asm volatile("fence.proxy.async.shared::cta;" ::: "memory"); tma2d(sb + SM_FAR + kk * FAR_SZ, &tmD, W2W == 72 ? 72 * q : (72 * q) & ~15, 320 * c + 64 * kk, mb + MB_W2 * 8); }
            }
            return;
        }
        __syncwarp();
        bar_sync(14, 672);
        if (lane == 0) {
            asm volatile("fence.proxy.async.shared::cta;" ::: "memory");
            asm volatile("cp.async.bulk.tensor.5d.global.shared::cta.bulk_group [%0, {%2, %4, %4, %4, %3}], [%1];" :: "l"(&tmH), "r"(sb + SM_XT + 16384), "r"(d0 + ((c & 1) ? 0 : 32)), "r"(8 * q), "r"(0) : "memory");
            asm volatile("cp.async.bulk.tensor.5d.global.shared::cta.bulk_group [%0, {%2, %4, %4, %4, %3}], [%1];" :: "l"(&tmO), "r"(sb + SM_XT), "r"(d0 + (c & 1) * 8), "r"(8 * q), "r"(0) : "memory");
            asm volatile("cp.async.bulk.commit_group;" ::: "memory");
            asm volatile("cp.async.bulk.wait_group 0;" ::: "memory");
            asm volatile("fence.proxy.async.global;" ::: "memory");
            asm volatile("mbarrier.arrive.shared::cta.b64 _, [%0];" :: "r"(mb + MB_OUT * 8) : "memory");
        }
        STAMP(2);
        return;
    }

    const int g = lane >> 2, cq = lane & 3;
    const int k = warp >> 2, wq = warp & 3;
    const int trow = 18 * blockIdx.x + warp;
    const bool rowact = warp < 18 && trow < L_;
    const int dch = min(d0 + 8 * k + q, D_ - 1);
    uint32_t pv[6];
#pragma unroll
    for (int i = 0; i < 6; i++) pv[i] = ldg16(prm.prm6[i] + (uint32_t)(dch * 128 + wq * 32 + lane));
    const uint32_t pLdt = ldg16(prm.logdt + dch), pD = ldg16(prm.dskip + dch);
    const int tn = 16 * (warp & 15) + g;
    uint32_t xa[5], xb[5];
    asm volatile("barrier.cluster.arrive.relaxed.aligned;" ::: "memory");
    uint4* const st1p = &g_s.st1[(((trow >> 3) & 7) * 256 + ((trow >> 6) & 31) * 8 + (trow & 7)) * 2 + (lane >> 2)];
    const bool pub = rowact && (lane & 0x1B) == 0;
    if (pub) st_rlx128(st1p, 0, 0, 0, 0);
    {
        const uint32_t za = sb + SM_P + tid * 16;
        sts128(za, 0, 0, 0, 0);
        if (tid < (SM_MISC - SM_P) / 16 - 640) sts128(za + 10240, 0, 0, 0, 0);
        sts128(sb + SM_XT + ((tid >> 3) & 15) * YP + k * YS + (lane & 7) * 16, 0, 0, 0, 0);
    }
    bar_sync(12, NTHR);
    const uint32_t dep = lds32(sb + SM_P);
#define PV(x) __uint_as_float(__byte_perm(dep, x, 0x5410))
    STAMP(1);
    const uint32_t fb = sb + SM_FAR + k * FAR_SZ;
    const uint32_t pn = sb + SM_PN + k * PN_SZ, pf = sb + SM_PF + k * PF_SZ;
    unsigned epoch;
    {
        const uint32_t kb = fb + wq * 3072;
        const uint32_t kl = kb + lane * 16;
        uint32_t Af[4][4];
        float sr, si, z1r, z1i, z2r, z2i, z4r, z4i, hr, hi_;
        {
            const float dt = bfr(ex2f(PV(pLdt) * 1.4426950408889634f));
            const float e2 = dt * PV(pv[0]) * 1.4426950408889634f, an = dt * PV(pv[1]);
            cmul(sr, si, PV(pv[4]), PV(pv[5]), dt * PV(pv[2]), dt * PV(pv[3]));
            const unsigned E = min(max(__reduce_max_sync(~0u, __float_as_uint(fmaxf(fmaxf(fabsf(sr), fabsf(si)), fabsf(PV(pD)) * (1.f / 8192.f)))) >> 23, 1u), 253u);
            const float sc = __uint_as_float((254u - E) << 23);
            sr *= sc; si *= -sc;
            sts64(sb + SM_KG + warp * 8, E, __reduce_add_sync(~0u, __float2int_rn(sr * 16777216.f)));
            float ar, ai, br, bi, cr, ci, dr, di;
            { const float m = ex2f(e2 * 8.f); ar = m * __cosf(an * 8.f); ai = m * __sinf(an * 8.f); }
            csq(br, bi, ar, ai); csq(cr, ci, br, bi); csq(dr, di, cr, ci);
            const H2C m4 = splat(cr, ci);
            {
                float r3, i3;
                cmul(r3, i3, ar, ai, br, bi);
                expand4(kl, kl + 1024, pack_f16(1.f, ar), pack_f16(br, r3), pack_f16(0.f, ai), pack_f16(bi, i3), m4);
            }
            expand8(kl + 512, kl + 1536, dr, di, ar, ai, br, bi, m4);
            { const float m = ex2f(e2); z1r = m * __cosf(an); z1i = -m * __sinf(an); }
            cexp_s(hr, hi_, e2 * 128.f, an * (-128.f * 0.15915494309189535f));
            csq(z2r, z2i, z1r, z1i); csq(z4r, z4i, z2r, z2i);
        }
        __syncwarp();
#pragma unroll
        for (int ks = 0; ks < 4; ks++) ldsm4t(Af[ks], kb + (lane >> 3) * 512 + (lane & 7) * 16 + ks * 128);
        STAMP(2);
        const uint32_t la = kb + ((lane >> 3) & 1) * 512 + (lane >> 4) * 128 + (lane & 7) * 16;
        uint32_t kp[5][2], b0[4], b1[4], b2[4], b3[4];
        auto mm2 = [&](int t) {
            float a0[4] = {0.f, 0.f, 0.f, 0.f}, a1[4] = {0.f, 0.f, 0.f, 0.f};
            mma_f16(a0, Af[0], b0[0], b0[1]); mma_f16(a1, Af[0], b2[0], b2[1]); mma_f16(a0, Af[1], b0[2], b0[3]); mma_f16(a1, Af[1], b2[2], b2[3]);
            mma_f16(a0, Af[2], b1[0], b1[1]); mma_f16(a1, Af[2], b3[0], b3[1]); mma_f16(a0, Af[3], b1[2], b1[3]); mma_f16(a1, Af[3], b3[2], b3[3]);
            kp[t][0] = pack_f16(a0[1], a0[0]); kp[t][1] = pack_f16(a0[3], a0[2]); kp[t + 1][0] = pack_f16(a1[1], a1[0]); kp[t + 1][1] = pack_f16(a1[3], a1[2]);
        };
        auto ln1 = [&]() {
        mbar_wait(mb + MB_R * 8);
        epoch = lds32(sb + SM_SC + 28) + 1;
        {
            const uint32_t ra = sb + SM_ROW + warp * (D_ * 2);
            const uint4 r0 = lds128(ra + lane * 16), r1 = lds128(ra + 512 + lane * 16);
            const uint32_t rx[9] = {r0.x, r0.y, r0.z, r0.w, r1.x, r1.y, r1.z, r1.w, lds32(ra + 1024 + lane * 4)};
            float a0 = bf_lo(rx[0]), a1 = bf_hi(rx[0]), c0 = a0 * a0, c1 = a1 * a1;
#pragma unroll
            for (int i = 1; i < 9; i++) { const float l = bf_lo(rx[i]), h = bf_hi(rx[i]); a0 += l; a1 += h; c0 = fmaf(l, l, c0); c1 = fmaf(h, h, c1); }
            a0 += a1; c0 += c1;
            float s1 = ((lane & 1) ? c0 : a0) + __shfl_xor_sync(~0u, (lane & 1) ? a0 : c0, 1);
#pragma unroll
            for (int o = 2; o < 32; o <<= 1) s1 += __shfl_xor_sync(~0u, s1, o);
            const float s2 = __shfl_xor_sync(~0u, s1, 1);
            const uint32_t ms = ln_stats(s1, s2);
            const uint32_t p0 = __byte_perm(ms, epoch | 0x8000u, 0x5410), p1 = rsplit(rcpf(bf_hi(ms)));
            if (pub) st_rlx128(st1p, p0, p1, p0, p1);
        }
        mbar_wait(mb + MB_R * 8);
        STAMP(1);
        };
        const uint4* sp = &g_s.st1[(256 * q + tn) * 2];
        uint2 sa, sc;
        auto poll = [&]() { sa = ld_rlx64(sp); sc = ld_rlx64(sp + 16); };
        auto norm = [&]() {
        STAMP(3);
        if (warp < 16) {
            uint32_t va[5], vc[5];
            poll();
            mbar_wait(mb + MB_T * 8);
            {
                const uint32_t xt = sb + SM_XTL + (XW == 40 ? 0 : (c & 1) * 16) + tn * (2 * XW);
                uint4 a4 = lds128(xt + cq * 16), b4 = lds128(xt + cq * 16 + 16 * XW);
                va[0] = a4.x; va[1] = a4.y; va[2] = a4.z; va[3] = a4.w; va[4] = lds32(xt + 64 + cq * 4);
                vc[0] = b4.x; vc[1] = b4.y; vc[2] = b4.z; vc[3] = b4.w; vc[4] = lds32(xt + (64 + 16 * XW) + cq * 4);
            }
            const int d4 = 2 * (lane >> 3) + (lane & 1), d1_ = lane & 7;
            uint32_t a4 = sb + warp * 32 + d4 * YP + (d4 == q ? SM_U + 128 : SM_XT + 128) + ((lane & 7) >> 1) * YS;
            uint32_t a1 = sb + warp * 32 + d1_ * YP + (d1_ == q ? SM_U + 128 : SM_XT + 128) + 4 * YS + (lane & 8) * 2;
            PIN(a4); PIN(a1);
            const uint32_t tag = __byte_perm(epoch | 0x8000u, 0, 0x1010) | ((va[0] & va[4] & vc[0] & vc[4]) & zero);
            int n = 0;
            while (__byte_perm(sa.x, sc.x, 0x7632) != tag && ++n < SPIN_LIMIT) poll();
            STAMP(4);
#pragma unroll
            for (int i = 0; i < 5; i++) {
                va[i] = norm2(va[i], sa.x, sa.y); va[i] = pack_f16(bf_lo(va[i]), bf_hi(va[i]));
                vc[i] = norm2(vc[i], sc.x, sc.y); vc[i] = pack_f16(bf_lo(vc[i]), bf_hi(vc[i]));
            }
            stsm4t(a4, va[0], va[1], va[2], va[3]); stsm4t(a4 + 16, vc[0], vc[1], vc[2], vc[3]); stsm2t(a1, va[4], vc[4]);
        }
        if (SYNC13 == 0 || (SYNC13 == 1 && warp < 16) || (SYNC13 == 3 && warp >= 16)) bar_arrive(13, 736);
        if (warp < 16) {
            const uint32_t xh = sb + SM_XTL + (XW == 40 ? 0 : (c & 1) * 16) + (64 * (g >> 1) + 32 * (warp & 1) + 8 * (g & 1) + (warp >> 1)) * (2 * XW);
            const uint4 a4 = lds128(xh + cq * 16), b4 = lds128(xh + cq * 16 + 32 * XW);
            xa[0] = a4.x; xa[1] = a4.y; xa[2] = a4.z; xa[3] = a4.w; xa[4] = lds32(xh + 64 + cq * 4);
            xb[0] = b4.x; xb[1] = b4.y; xb[2] = b4.z; xb[3] = b4.w; xb[4] = lds32(xh + (64 + 32 * XW) + cq * 4);
            bar_arrive(15, 544);
        }
        STAMP(5);
        if (SYNC13 == 2 || (SYNC13 == 1 && warp >= 16) || (SYNC13 == 3 && warp < 16)) bar_sync(13, 736);
        if (SYNC13) Af[0][0] |= lds32(sb + SM_P);
        };
        if (LNPOS == 0) ln1();
        cmul(sr, si, sr, si, z1r, z1i);
        {
            const H2C h4 = splat(z4r, z4i);
            expand8(kl, kl + 512, sr, si, z1r, z1i, z2r, z2i, h4);
            cmul(sr, si, sr, si, hr, hi_);
            expand8(kl + 1024, kl + 1536, sr, si, z1r, z1i, z2r, z2i, h4);
        }
        __syncwarp();
        ldsm4t(b0, la); ldsm4t(b1, la + 256); ldsm4t(b2, la + 1024); ldsm4t(b3, la + 1280);
        cmul(z1r, z1i, z1r, z1i, hr, hi_);
        cmul(sr, si, sr, si, z1r, z1i);
        if (LNPOS == 1) ln1();
        expand8(kl, kl + 512, sr, si, z2r, z2i, z4r, z4i, splat(hr, hi_));
        if (LNPOS == 2) ln1();
        csq(z1r, z1i, z1r, z1i);
        cmul(sr, si, sr, si, z1r, z1i);
        csq(z2r, z2i, hr, hi_);
        expand8(kl + 1024, kl + 1536, sr, si, z4r, z4i, hr, hi_, splat(z2r, z2i));
        if (LNPOS == 3) ln1();
        csq(z1r, z1i, z1r, z1i);
        cmul(sr, si, sr, si, z1r, z1i);
        csq(z4r, z4i, z2r, z2i);
        expand8(kl + 2048, kl + 2560, sr, si, hr, hi_, z2r, z2i, splat(z4r, z4i));
        if (LNPOS == 4) ln1();
        if (MMPOS == 0) norm();
        mm2(0);
        __syncwarp();
        ldsm4t(b0, la); ldsm4t(b1, la + 256); ldsm4t(b2, la + 1024); ldsm4t(b3, la + 1280);
        if (MMPOS == 1) norm();
        mm2(2);
        if (MMPOS == 2) norm();
        ldsm4t(b0, la + 2048); ldsm4t(b1, la + 2304);
#pragma unroll
        for (int t = 0; t < 4; t++) sts64(kb + lane * 8 + 1024 + t * 256, kp[t][0], kp[t][1]);
        {
            float a0[4] = {0.f, 0.f, 0.f, 0.f}, a1[4] = {0.f, 0.f, 0.f, 0.f};
            mma_f16(a0, Af[0], b0[0], b0[1]); mma_f16(a1, Af[1], b0[2], b0[3]); mma_f16(a0, Af[2], b1[0], b1[1]); mma_f16(a1, Af[3], b1[2], b1[3]);
            sts64(kb + lane * 8 + 2048, pack_f16(a0[1] + a1[1], a0[0] + a1[0]), pack_f16(a0[3] + a1[3], a0[2] + a1[2]));
        }
        bar_sync(1 + k, 128);
        const uint4 m01 = lds128(sb + SM_KG + k * 32), m23 = lds128(sb + SM_KG + k * 32 + 16);
        const unsigned Em = max(max(m01.x, m01.z), max(m23.x, m23.z));
        const float f0 = __uint_as_float(max((int)(127 + m01.x - Em), 0) << 23), f1 = __uint_as_float(max((int)(127 + m01.z - Em), 0) << 23),
                    f2 = __uint_as_float(max((int)(127 + m23.x - Em), 0) << 23), f3 = __uint_as_float(max((int)(127 + m23.z - Em), 0) << 23);
        const uint32_t r0 = pack_f16(f0, f0), r1 = pack_f16(f1, f1), r2 = pack_f16(f2, f2), r3 = pack_f16(f3, f3);
        const uint32_t ra = fb + lane * 8 + wq * 256 + 1024;
        const uint2 p0 = lds64(ra), p1 = lds64(ra + 3072), p2 = lds64(ra + 6144), p3 = lds64(ra + 9216);
        uint32_t w0 = hadd2(hfma2(p0.x, r0, hmul2(p1.x, r1)), hfma2(p2.x, r2, hmul2(p3.x, r3)));
        uint32_t w1 = hadd2(hfma2(p0.y, r0, hmul2(p1.y, r1)), hfma2(p2.y, r2, hmul2(p3.y, r3)));
        const bool last = lane == 31;
        if (wq < 2) {
            const uint32_t rc = fb + lane * 8 + wq * 4 + 2048;
            const uint32_t w4 = hmul2(hadd2(hfma2(lds32(rc), r0, hmul2(lds32(rc + 3072), r1)), hfma2(lds32(rc + 6144), r2, hmul2(lds32(rc + 9216), r3))), 0x18001800u);
            const uint32_t ph = pf + (P_H7 + 16 * wq) + (g & 1) * (2 * P_HS) + cq * 64 + (g >> 1) * 4;
            put16(ph, w4 >> 16); put16(ph + 32, w4);
            const uint32_t pa = pn + (4 + 512 * wq) + lane * 8;
            sts16(pa, w0 >> 16); sts32(pa + 4, w0); sts16(pa + 10, w0);
            sts16(pa + 256, w1 >> 16); sts32(pa + 260, w1); sts16(pa + 266, w1);
            if (last) {
                sts32(sb + SM_SC + k * 4, Em * 0x00800080u);
                put16(wq ? pa + 264 : pn,
                      wq ? w1 : pack_f16(((float)(int)m01.y * f0 + (float)(int)m01.w * f1 + (float)(int)m23.y * f2 + (float)(int)m23.w * f3) * (1.f / 16777216.f)
                                         + __uint_as_float(pD << 16) * __uint_as_float((254u - Em) << 23), 0.f));
            }
        } else if (wq == 2) {
            const uint32_t pa = pn + 258 * 4 + (cq & 1) * 16 + (cq >> 1) * 512 + g * 32;
            if (last) { put16(pf, hmul2(w1, 0x18001800u)); w1 = hadd2(w1, hneg2(__byte_perm(w1, 0, 0x1010))); }
            const uint32_t b0 = __byte_perm(w0, 0, 0x1010), b1 = __byte_perm(w1, 0, 0x1010);
            sts16(pa, w0 >> 16); sts32(pa + 4, w0); sts64(pa + 8, b0, b0); sts16(pa + 18, w0);
            sts16(pa + 256, w1 >> 16); sts32(pa + 260, w1); sts64(pa + 264, b1, b1); sts16(pa + 274, w1);
        } else {
            const uint32_t pa = pf + ((g & 1) ? 3 * P_GS : P_GS) + cq * 32 + (g >> 1) * 4;
            const uint32_t pb = pa + ((g & 1) ? 4 - 3 * P_GS : P_GS);
            w0 = hmul2(w0, 0x18001800u); w1 = hmul2(w1, 0x18001800u);
            put16(pa, w0 >> 16); put16(pb, w0); put16(pa + 16, w1 >> 16); put16(pb + 16, w1);
            if (last) put16(pf + P_H7 + P_HS, w1);
        }
        bar_sync(1 + k, 128);
    }
    STAMP(6);

    asm volatile("barrier.cluster.wait.aligned;" ::: "memory");
    mbar_wait(mb + (MB_X + (k < XSPLIT || k >= nslot)) * 8);
    STAMP(7);
    if (k < nslot) {
        const int role = (wq + k) & 3;
        const uint32_t ub = sb + SM_U + k * US + 128;
        if (role) {
            const int r = (3 - role) * 32 + lane;
            const uint32_t a1 = ub + (r & 3) * (2 * UP) + (r >> 2) * 16, a0 = a1 + ((r & 3) ? -2 * UP : 6 * UP - 16);
            const uint4 q0 = lds128(a0), q1 = lds128(a0 + UP), q2 = lds128(a1), q3 = lds128(a1 + UP);
            const uint32_t U[16] = {q0.x, q0.y, q0.z, q0.w, q1.x, q1.y, q1.z, q1.w, q2.x, q2.y, q2.z, q2.w, q3.x, q3.y, q3.z, q3.w};
            uint32_t V[14], Q[14], R4[12], T[8];
#pragma unroll
            for (int i = 2; i < 14; i++) { V[i] = __byte_perm(U[i], U[i + 1], 0x5432); Q[i] = hadd2(U[i], V[i]); }
#pragma unroll
            for (int i = 2; i < 12; i++) R4[i] = hadd2(Q[i], Q[i + 1]);
            const uint32_t rb = fb + r * 16;
#pragma unroll
            for (int i = 0; i < 8; i++) T[i] = hadd2(V[5 + i], Q[6 + i]);
            sts128(rb + F_E3, T[0], T[1], T[2], T[3]); sts128(rb + F_O3 + 16, T[4], T[5], T[6], T[7]);
#pragma unroll
            for (int i = 0; i < 8; i++) T[i] = hadd2(R4[3 + i], U[5 + i]);
            sts128(rb + F_O5, T[0], T[1], T[2], T[3]); sts128(rb + F_E5, T[4], T[5], T[6], T[7]);
            if (role != 1) {
#pragma unroll
                for (int i = 0; i < 8; i++) T[i] = hadd2(T[i], hadd2(V[2 + i], V[5 + i]));
                sts128(rb + F_E7, T[0], T[1], T[2], T[3]); sts128(rb + F_O7, T[4], T[5], T[6], T[7]);
#pragma unroll
                for (int i = 0; i < 8; i++) T[i] = hadd2(R4[2 + i], hadd2(R4[4 + i], U[6 + i]));
                sts128(rb + F_O9, T[0], T[1], T[2], T[3]); sts128(rb + F_E9 + 16, T[4], T[5], T[6], T[7]);
                sts128(rb + F_E2, Q[6], Q[7], Q[8], Q[9]); sts128(rb + F_O2, Q[10], Q[11], Q[12], Q[13]);
            }
        } else if (lane < 8) {
            uint32_t v[5];
#pragma unroll
            for (int i = 0; i < 5; i++) { const int t = 6 + lane + i; v[i] = lds16(ub + 23 * 16 + (t < 16 ? (6 + (t >> 3)) * UP : 16) + (t & 7) * 2); }
            const uint32_t s = hadd2(hadd2(hadd2(v[0], v[1]), hadd2(v[2], v[3])), v[4]);
            sts16(fb + F_O5 + 96 * 16 + lane * 2, s);
            sts32(fb + (lane < 4 ? F_O3 : F_E9 - 16) + lane * 4, 0);
        }
        bar_sync(1 + k, 128);
        float acc[4][4];
        uint32_t Q[4][4];
        {
            const int h = role & 1, part = role >> 1;
            const uint32_t po = pf + (g - 2 * cq) * 4;
            float fa[7][4];
#pragma unroll
            for (int a = 0; a < 7; a++) fa[a][0] = fa[a][1] = fa[a][2] = fa[a][3] = 0.f;
            uint32_t B[3][4];
            Q[0][2] = zero;
#pragma unroll 1
            for (int s = 2 * part + 1; s >= 2 * part; s--) {
#pragma unroll
                for (int i = 0; i < 3; i++) { Q[i][0] = lds32(po + s * P_GS + i * 64); Q[i][1] = lds32(po + s * P_GS + (i * 64 + 32)); }
                const uint32_t ba = fb + lane * 16 + ((s & 1) * F_E3 + (part == h ? 0 : F_O5 + h * 16));
#pragma unroll
                for (int i = 0; i < 3; i++) ldsm4t(B[i], ba + i * 512);
#pragma unroll
                for (int i = 0; i < 3; i++) { Q[i][3] = CP(Q[i][0]); if (i) Q[i][2] = CP(Q[i - 1][1]); }
#pragma unroll
                for (int dl = 0; dl < 3; dl++)
#pragma unroll
                    for (int ap = 0; ap < 6 - dl; ap++) mma_f16(fa[ap + 1 + dl], Q[dl], B[ap >> 1][2 * (ap & 1)], B[ap >> 1][2 * (ap & 1) + 1]);
            }
#pragma unroll 1
            for (int s = role; s == 1; s++) {
                ldsm2t(B[0][0], B[0][1], fb + ((lane & 15) == 15 ? F_O5 : F_O3));
#pragma unroll
                for (int dl = 0; dl < 3; dl++) mma_f16(fa[dl], Q[dl], B[0][0], B[0][1]);
            }
#pragma unroll 1
            for (int s = part; s <= 2 * part; s++) {
#pragma unroll
                for (int i = 0; i < 4; i++) { Q[i][0] = lds32(po + s * P_HS + (P_H7 + i * 64)); Q[i][1] = lds32(po + s * P_HS + (P_H7 + i * 64 + 32)); }
                const uint32_t ba = fb + lane * 16 + (F_E7 + s * 1024 + h * F_H);
                ldsm4t(B[0], ba); ldsm4t(B[1], ba + 512);
#pragma unroll
                for (int i = 0; i < 4; i++) { Q[i][3] = CP(Q[i][0]); if (i) Q[i][2] = CP(Q[i - 1][1]); }
#pragma unroll
                for (int dl = 0; dl < 4; dl++) {
#pragma unroll
                    for (int ap = 0; ap < 4 - dl; ap++) mma_f16(fa[ap + 3 + dl], Q[dl], B[ap >> 1][2 * (ap & 1)], B[ap >> 1][2 * (ap & 1) + 1]);
                    if (s == 1) break;
                }
            }
            const uint32_t da = fb + role * 2048 + (lane & 3) * 512 + (((lane >> 2) ^ ((lane & 3) * 2)) << 4);
            bar_sync(1 + k, 128);
            stsm4(da, 0u, 0u, pack_f16(fa[0][0], fa[0][1]), pack_f16(fa[0][2], fa[0][3]));
#pragma unroll
            for (int i = 1; i < 4; i++)
                stsm4(da + i * 128, pack_f16(fa[2 * i - 1][0], fa[2 * i - 1][1]), pack_f16(fa[2 * i - 1][2], fa[2 * i - 1][3]),
                      pack_f16(fa[2 * i][0], fa[2 * i][1]), pack_f16(fa[2 * i][2], fa[2 * i][3]));
            Q[0][0] = (g == 2 * cq) ? 0x6000u : ((g == 2 * cq + 1) ? 0x60000000u : 0u);
            Q[0][1] = 0; Q[0][3] = CP(Q[0][0]);
            const uint32_t ra = fb + (lane >> 3) * 2048 + wq * 512 + (((lane & 7) ^ (wq * 2)) << 4);
            bar_sync(1 + k, 128);
#pragma unroll
            for (int i = 0; i < 4; i++) {
                ldsm4(B[0], ra + i * 128);
                acc[i][0] = acc[i][1] = acc[i][2] = acc[i][3] = 0.f;
                mma_f16(acc[i], Q[0], hadd2(B[0][0], B[0][2]), hadd2(B[0][1], B[0][3]));
            }
        }
        bar_arrive(6 + k, 160);
        STAMP(8);
        const uint32_t inv = lds32(sb + SM_SC + k * 4);
        uint32_t yd = mapa(sb, 2 * wq) + (SM_XT + 128 + q * YP + k * YS) + lane * 16;
        PIN(yd);
        {
            uint32_t pp = pn + (16 * (wq - 3) + g - 2 * cq) * 4;
            uint32_t dlo = (((ub + 6 * UP) & 0x3FFFF) >> 4) | ((UP >> 4) << 16);
            uint32_t R[4][4];
            auto loadQ = [&](uint32_t (&X)[4][4], uint32_t prev) {
#pragma unroll
                for (int i = 0; i < 4; i++) { X[i][0] = lds32(pp + i * 64); X[i][1] = lds32(pp + i * 64 + 32); }
                X[0][2] = CP(prev);
#pragma unroll
                for (int i = 0; i < 4; i++) { X[i][3] = CP(X[i][0]); if (i) X[i][2] = CP(X[i - 1][1]); }
                pp += 256;
            };
            auto issue = [&](uint32_t (&X)[4][4]) {
                asm volatile("wgmma.fence.sync.aligned;" ::: "memory");
#pragma unroll
                for (int i = 0; i < 4; i++) wgmma32(acc, X[i], dlo - i * (2 * UP >> 4));
                asm volatile("wgmma.commit_group.sync.aligned;" ::: "memory");
                dlo -= 1;
            };
            loadQ(Q, 0);
#pragma unroll 1
            for (int dl = 0; dl < 4; dl++) {
                issue(Q);
                asm volatile("wgmma.wait_group.sync.aligned 1;" ::: "memory");
                loadQ(R, Q[3][1]);
                issue(R);
                asm volatile("wgmma.wait_group.sync.aligned 1;" ::: "memory");
                loadQ(Q, R[3][1]);
            }
            issue(Q);
            asm volatile("wgmma.wait_group.sync.aligned 0;" ::: "memory");
        }
        const uint32_t pstep = mapa(sb, 1) - mapa(sb, 0), ym = mapa(mb + MB_Y * 8, 2 * wq);
#pragma unroll
        for (int e = 0; e < 2; e++)
            st_async4(yd + e * pstep, bmul2(pack_bf16(acc[0][2 * e], acc[0][2 * e + 1]), inv), bmul2(pack_bf16(acc[1][2 * e], acc[1][2 * e + 1]), inv),
                      bmul2(pack_bf16(acc[2][2 * e], acc[2][2 * e + 1]), inv), bmul2(pack_bf16(acc[3][2 * e], acc[3][2 * e + 1]), inv), ym + e * pstep);
        if (lane == 0) asm volatile("mbarrier.arrive.shared::cta.b64 _, [%0];" :: "r"(mb + MB_Y * 8) : "memory");
    }
    STAMP(9);
    uint32_t ha[5], hb[5];
    if (warp < 16) {
        const uint4 wk = lds128(sb + SM_DW + cq * 16);
        uint32_t sel[5] = {wk.x, wk.y, wk.z, wk.w, lds32(sb + SM_DW + 64 + cq * 4)}, sel2[5];
#pragma unroll
        for (int i = 0; i < 5; i++) {
            if (!(g & 1)) sel[i] = 0x3F803F80u;
            sel2[i] = sel[i]; PIN(sel2[i]);
        }
        const uint32_t y4 = sb + SM_XT + 128 + warp * 32 + (2 * (lane >> 3) + (lane & 1)) * YP + ((lane & 7) >> 1) * YS;
        const uint32_t y1 = sb + SM_XT + 128 + warp * 32 + (lane & 7) * YP + 4 * YS + (lane & 8) * 2;
        uint32_t ao = (256 * q + tn) * 16, hta = sb + SM_HT + tn * 80;
        PIN(ao); PIN(hta);
        mbar_wait(mb + MB_Y * 8);
        STAMP(10);
        float ca[4] = {0.f, 0.f, 0.f, 0.f}, cb[4] = {0.f, 0.f, 0.f, 0.f};
        {
            uint32_t ya[4], yb[4], yc, yd;
            ldsm4t(ya, y4); ldsm4t(yb, y4 + 16); ldsm2t(yc, yd, y1);
#pragma unroll
            for (int i = 0; i < 4; i++) { ha[i] = badd2(xa[i], ya[i]); hb[i] = badd2(xb[i], yb[i]); }
            ha[4] = badd2(xa[4], yc); hb[4] = badd2(xb[4], yd);
        }
        if (nslot != 5) {
            ha[4] = hb[4] = 0;
            if (cq >= 2) ha[0] = ha[1] = ha[2] = ha[3] = hb[0] = hb[1] = hb[2] = hb[3] = 0;
        }
#pragma unroll
        for (int i = 0; i < 5; i++) { mma_bf16_k8(ca, ha[i], sel[i], ha[i]); mma_bf16_k8(cb, hb[i], sel2[i], hb[i]); }
        if (!(g & 1)) { ca[1] = ca[0]; cb[1] = cb[0]; }
        if (cq == (g >> 1)) {
            asm volatile("red.relaxed.gpu.global.add.v4.f32 [%0], {%1,%2,%3,%4};" :: "l"((char*)g_s.acc + ao), "f"(1.0f), "f"(ca[1]), "f"(ca[2]), "f"(ca[3]) : "memory");
            asm volatile("red.relaxed.gpu.global.add.v4.f32 [%0], {%1,%2,%3,%4};" :: "l"((char*)g_s.acc + ao + 128), "f"(1.0f), "f"(cb[1]), "f"(cb[2]), "f"(cb[3]) : "memory");
        }
        sts128(hta + cq * 16, ha[0], ha[1], ha[2], ha[3]); sts32(hta + 64 + cq * 4, ha[4]);
        sts128(hta + cq * 16 + 640, hb[0], hb[1], hb[2], hb[3]); sts32(hta + 704 + cq * 4, hb[4]);
        STAMP(11);
    }
    const int kq = warp / 5, mt = warp - 5 * kq;
    const int mi = lane >> 3, mr = lane & 7;
    const unsigned tk = (unsigned)tid / 72u, ck = tid - tk * 72;
    uint32_t A[9][4];
    auto loadA = [&]() {
        mbar_wait(mb + MB_W1 * 8);
        const uint32_t aa = sb + (mi & 1) * SM_WU + (8 * (mi >> 1) + mr) * 80 + (144 * 80 * kq + mt * 16);
#pragma unroll
        for (int s = 0; s < 9; s++) ldsm4t(A[s], aa + s * 1280);
    };
    const uint32_t par = (epoch & 1) ? 0x40004000u : 0u;
    uint32_t pk0 = mapa(sb, 2 * cq), go = (ck / 5u + ck) * 16, co = ((q * 8 * NCL + c) * 6 + cq) * 16;
    PIN(pk0); PIN(go); PIN(co);
    if (warp < 8) {
        const float wsum = ldsf(sb + SM_SC + 24);
        const uint32_t idx = 2047 - (512 * ((tid >> 1) & 3) + 128 * ((tid >> 3) & 3) + 64 * (tid & 1) + 8 * q + warp);
        uint4 s; int n = 0;
        do { s = ld_rlx128(&g_s.acc[256 * q + tid]); } while (__uint_as_float(s.x) != (float)NCL && ++n < SPIN_LIMIT);
        STAMP(16);
        const uint32_t ox = __shfl_xor_sync(~0u, (lane & 1) ? s.z : s.w, 1);
        const uint32_t ms = ln_stats(__uint_as_float((lane & 1) ? ox : s.z), __uint_as_float(s.y));
        const float rs = rcpf(bf_hi(ms));
        const uint32_t rb = pack_bf16(0.f, fmaf(-bf_lo(ms), wsum, __uint_as_float((lane & 1) ? s.w : ox)) * rs);
        const uint32_t key = (((rb ^ (((int)rb >> 31) | 0x80000000u)) >> 16) << 11) | idx;
        sts32(sb + SM_KEY + tid * 4, key);
        __syncwarp();
        const uint32_t rank = rank4<8, 16>(sb + SM_KEY + warp * 128, key);
        if (rank < 8) sts32(sb + SM_CAND + warp * 32 + rank * 4, key);
        sts64(sb + SM_ST + tid * 8, ms, rsplit(rs));
    } else loadA();
    if (warp < 16) {
        STAMP(17);
        bar_sync(12, 512);
        STAMP(18);
        if (warp < 8) {
            const uint32_t mk = lds32(sb + SM_CAND + (tid >> 2) * 4);
            uint32_t rank = rank4<4, 64>(sb + SM_CAND + cq * 16, mk);
            rank += __shfl_xor_sync(~0u, rank, 1); rank += __shfl_xor_sync(~0u, rank, 2);
            if (rank < 8) {
                const uint32_t pk1 = pk0 + (mapa(sb, 1) - mapa(sb, 0));
                st_async1(pk0 + (SM_RK + q * 32) + rank * 4, mk, pk0 + (SM_MB + MB_KEY * 8));
                st_async1(pk1 + (SM_RK + q * 32) + rank * 4, mk, pk1 + (SM_MB + MB_KEY * 8));
                const uint32_t t = tslot(~mk);
                const uint2 sv = lds64(sb + SM_ST + t * 8);
                const uint4 hv = lds128(sb + SM_HT + t * 80 + cq * 16);
                const uint32_t h4 = lds32(sb + SM_HT + t * 80 + 64 + cq * 4);
                const uint32_t rr = bmul2(sv.y, 0x3C803C80u);
                char* const dp = (char*)g_s.cand + (co + rank * 1440);
                st_rlx128(dp, (norm2(hv.x, sv.x, rr) & 0xBFFFBFFFu) | par, (norm2(hv.y, sv.x, rr) & 0xBFFFBFFFu) | par,
                          (norm2(hv.z, sv.x, rr) & 0xBFFFBFFFu) | par, (norm2(hv.w, sv.x, rr) & 0xBFFFBFFFu) | par);
                asm volatile("st.relaxed.gpu.global.u32 [%0], %1;" :: "l"((char*)g_s.cand + (co + rank * 1440 + 64 - cq * 12)), "r"((norm2(h4, sv.x, rr) & 0xBFFFBFFFu) | par) : "memory");
            }
            __syncwarp();
        }
        {
            const uint2 sa = lds64(sb + SM_ST + tn * 8), sbb = lds64(sb + SM_ST + tn * 8 + 64);
#pragma unroll
            for (int i = 0; i < 5; i++) { ha[i] = badd2(ha[i], norm2(ha[i], sa.x, sa.y)); hb[i] = badd2(hb[i], norm2(hb[i], sbb.x, sbb.y)); }
            const bool hf = (c & 1) && cq == 0;
            const uint32_t o16 = sb + SM_XT + (hf ? 16384 + tn * 16 : tn * 64 + (cq - (c & 1)) * 16), o4 = sb + SM_XT + ((c & 1) ? tn * 64 + 48 : 16384 + tn * 16) + cq * 4;
            sts128(o16, ha[0], ha[1], ha[2], ha[3]); sts32(o4, ha[4]);
            sts128(o16 + (hf ? 128 : 512), hb[0], hb[1], hb[2], hb[3]); sts32(o4 + ((c & 1) ? 512 : 128), hb[4]);
        }
        if (warp >= 8) {
            STAMP(19);
            mbar_wait(mb + MB_KEY * 8);
            STAMP(20);
            const uint32_t mk = lds32(sb + SM_RK - 256 + (tid >> 2) * 4);
            uint32_t rank = rank4<4, 64>(sb + SM_RK + cq * 16, mk);
            rank += __shfl_xor_sync(~0u, rank, 1); rank += __shfl_xor_sync(~0u, rank, 2);
            if (rank < 8) sts64(sb + SM_SEL + rank * 8, mk, ((tid >> 2) - 64) * 1440);
        }
    }
    bar_sync(11, 640);
    STAMP(12);

    const char* gp = (const char*)g_s.cand + (go + lds32(sb + SM_SEL + 4 + (tk & 7) * 8));
    uint4 hv = ld_rlx128(gp);
    if (warp < 8) loadA();
    const bool red = warp < 6;
    const uint32_t ft = red ? (unsigned)tid / 24u : (unsigned)(tid >> 4) & 7u, fj = red ? 24 * q + tid - ft * 24 : d0 / 3 + (lane & 15);
    const uint32_t key = lds32(sb + SM_SEL + ft * 8), k16 = key << 5;
    float sig = bfr(rcpf(1.f + ex2f(__uint_as_float((k16 ^ (~((int)k16 >> 31) | 0x80000000u)) & 0xFFFF0000u) * -1.4426950408889634f)));
    uint32_t ra2 = sb + SM_RED2 + tid * 12 + ft * 16, fo = (ft * 192 + fj) * 16, oo = ((~key & 2047) * D_ + 3 * fj) * 2;
    uint32_t bx = sb + SM_XS + mr * 1168 + mi * 16 + 288 * kq, gd = mapa(sb, kq * (8 / NRED)) + (SM_GU + (q * nslot + mt) * 128) + lane * 4;
    PIN(ra2); PIN(fo); PIN(oo); PIN(bx); PIN(gd);
    asm volatile("" : "+f"(sig));
    {
        if (warp < 18) {
            int n = 0;
            while ((((hv.x ^ par) | (hv.y ^ par) | (hv.z ^ par) | (hv.w ^ par)) & 0x40004000u) && ++n < SPIN_LIMIT) hv = ld_rlx128(gp);
            sts128(sb + SM_XS + tk * 16 + tid * 16, hv.x ^ par, hv.y ^ par, hv.z ^ par, hv.w ^ par);
        }
    }
    bar_sync(14, 672);
    STAMP(13);
    {
        float c0[4] = {0.f, 0.f, 0.f, 0.f}, c1[4] = {0.f, 0.f, 0.f, 0.f}, c2[4] = {0.f, 0.f, 0.f, 0.f};
        uint32_t b[5][4];
#pragma unroll
        for (int s = 0; s < 4; s++) ldsm4(b[s], bx + s * 64);
        asm volatile("ldmatrix.sync.aligned.m8n8.x2.shared.b16 {%0,%1}, [%2];" : "=r"(b[4][0]), "=r"(b[4][1]) : "r"(bx + 256) : "memory");
        mma_bf16(c0, A[0][0], A[0][1], A[0][2], A[0][3], b[0][0], b[0][1]);
        mma_bf16(c1, A[1][0], A[1][1], A[1][2], A[1][3], b[0][2], b[0][3]);
        mma_bf16(c2, A[2][0], A[2][1], A[2][2], A[2][3], b[1][0], b[1][1]);
        mma_bf16(c0, A[3][0], A[3][1], A[3][2], A[3][3], b[1][2], b[1][3]);
        mma_bf16(c1, A[4][0], A[4][1], A[4][2], A[4][3], b[2][0], b[2][1]);
        mma_bf16(c2, A[5][0], A[5][1], A[5][2], A[5][3], b[2][2], b[2][3]);
        mma_bf16(c0, A[6][0], A[6][1], A[6][2], A[6][3], b[3][0], b[3][1]);
        mma_bf16(c1, A[7][0], A[7][1], A[7][2], A[7][3], b[3][2], b[3][3]);
        mma_bf16(c2, A[8][0], A[8][1], A[8][2], A[8][3], b[4][0], b[4][1]);
        sts128f(sb + SM_RED + tid * 16, c0[0] + c1[0] + c2[0], c0[1] + c1[1] + c2[1], c0[2] + c1[2] + c2[2], c0[3] + c1[3] + c2[3]);
    }
    bar_sync(1 + mt, 128);
    STAMP(21);
    if (mt < nslot && kq < NRED) {
        const uint32_t ra = sb + SM_RED + mt * 512 + lane * 16;
        const float4 p0 = lds128f(ra), p1 = lds128f(ra + 2560), p2 = lds128f(ra + 5120), p3 = lds128f(ra + 7680);
        const float g0 = bfr(((p0.x + p1.x) + (p2.x + p3.x)) * 64.f), g1 = bfr(((p0.y + p1.y) + (p2.y + p3.y)) * 64.f);
        const uint32_t sg = pack_bf16(g0 * rcpf(1.f + ex2f(g0 * -1.4426950408889634f)), g1 * rcpf(1.f + ex2f(g1 * -1.4426950408889634f)));
        const uint32_t gu = bmul2(sg, pack_bf16(((p0.z + p1.z) + (p2.z + p3.z)) * 64.f, ((p0.w + p1.w) + (p2.w + p3.w)) * 64.f));
        const uint32_t pstep = mapa(sb, 1) - mapa(sb, 0), gm = mapa(mb + MB_GU * 8, kq * (8 / NRED));
#pragma unroll
        for (int i = 0; i < 8 / NRED; i++) st_async1(gd + i * pstep, gu, gm + i * pstep);
    }
    mbar_wait(mb + MB_W2 * 8);
    {
        const uint32_t aa = sb + (8 * (mi >> 1) + mr) * (2 * W2W) + (mi & 1) * 16 + (SM_FAR + 32 * W2W * kq + mt * 32 + (W2W == 72 ? 0 : (q & 1) * 16));
#pragma unroll
        for (int s = 0; s < 5; s++) ldsm4t(A[s], aa + s * FAR_SZ);
    }
    {
        uint32_t ba = sb + (SM_GU + 256 * kq) + (lane & 15) * 16 + (lane >> 4) * 1024, wa = sb + (SM_RED2 + kq * 2432 + mt * 64) + g * 4 + cq * 608;
        PIN(ba); PIN(wa);
        STAMP(22);
        mbar_wait(mb + MB_GU * 8);
        STAMP(23);
        float c0[4] = {0.f, 0.f, 0.f, 0.f}, c1[4] = {0.f, 0.f, 0.f, 0.f}, c2[4] = {0.f, 0.f, 0.f, 0.f};
        uint32_t b[2][4], b8, b9;
        ldsm4t(b[0], ba); ldsm4t(b[1], ba + 2048); ldsm2t(b8, b9, ba + 4096);
        mma_bf16(c0, A[0][0], A[0][1], A[0][2], A[0][3], b[0][0], b[0][1]);
        mma_bf16(c1, A[1][0], A[1][1], A[1][2], A[1][3], b[0][2], b[0][3]);
        if (nslot == 5) {
            mma_bf16(c2, A[4][0], A[4][1], A[4][2], A[4][3], b8, b9);
            mma_bf16(c0, A[2][0], A[2][1], A[2][2], A[2][3], b[1][0], b[1][1]);
            mma_bf16(c1, A[3][0], A[3][1], A[3][2], A[3][3], b[1][2], b[1][3]);
        }
        stsf(wa, c0[0] + c1[0] + c2[0]); stsf(wa + 304, c0[1] + c1[1] + c2[1]);
        if (mt < 4) { stsf(wa + 32, c0[2] + c1[2] + c2[2]); stsf(wa + 336, c0[3] + c1[3] + c2[3]); }
    }
    if (warp < 10) {
        float v[3], cnt = 3.f;
        if (red) {
            bar_sync(6, 640);
            STAMP(14);
#pragma unroll
            for (int i = 0; i < 3; i++) v[i] = ((ldsf(ra2 + i * 4) + ldsf(ra2 + i * 4 + 2432)) + (ldsf(ra2 + i * 4 + 4864) + ldsf(ra2 + i * 4 + 7296))) * sig;
        } else {
            bar_arrive(6, 640);
            cnt = 0.f;
#pragma unroll
            for (int i = 0; i < 3; i++) {
                const uint32_t cl = 3 * fj + i - d0;
                const bool ok = cl < 8 * nslot && ((~key >> 3) & 7) == q;
                const uint32_t cf = cl - (c & 1) * 8;
                v[i] = ok ? __uint_as_float(lds16(sb + SM_XT + (cf < 32 ? tslot(~key) * 64 + cf * 2 : 16384 + tslot(~key) * 16 + (cl & 7) * 2)) << 16) : 0.f;
                if (ok) cnt += 1.f;
            }
            mbar_wait(mb + MB_OUT * 8);
        }
        if (cnt != 0.f) {
            float x, y, z, w;
            asm volatile("atom.relaxed.gpu.global.add.v4.f32 {%0,%1,%2,%3}, [%4], {%5,%6,%7,%8};" : "=f"(x), "=f"(y), "=f"(z), "=f"(w)
                         : "l"((char*)g_s.fin + fo), "f"(v[0]), "f"(v[1]), "f"(v[2]), "f"(cnt) : "memory");
            if (w + cnt == 3.f * (NCL + 1)) {
                __nv_bfloat16* op = (__nv_bfloat16*)((char*)prm.out + oo);
                op[0] = __float2bfloat16(x + v[0]); op[1] = __float2bfloat16(y + v[1]); op[2] = __float2bfloat16(z + v[2]);
            }
        }
    } else bar_arrive(6, 640);
    STAMP(15);
}

typedef CUresult (*EncodeFn)(CUtensorMap*, CUtensorMapDataType, cuuint32_t, void*, const cuuint64_t*, const cuuint64_t*,
                             const cuuint32_t*, const cuuint32_t*, CUtensorMapInterleave, CUtensorMapSwizzle,
                             CUtensorMapL2promotion, CUtensorMapFloatOOBfill);

void make_map(EncodeFn fn, CUtensorMap* tm, const void* p, int cols, int rows, int bc, int br) {
    cuuint64_t dims[2] = {(cuuint64_t)cols, (cuuint64_t)rows};
    cuuint64_t strides[1] = {(cuuint64_t)cols * 2};
    cuuint32_t box[2] = {(cuuint32_t)bc, (cuuint32_t)br};
    cuuint32_t es[2] = {1, 1};
    fn(tm, CU_TENSOR_MAP_DATA_TYPE_BFLOAT16, 2, const_cast<void*>(p), dims, strides, box, es, CU_TENSOR_MAP_INTERLEAVE_NONE,
       CU_TENSOR_MAP_SWIZZLE_NONE, CU_TENSOR_MAP_L2_PROMOTION_L2_128B, CU_TENSOR_MAP_FLOAT_OOB_FILL_NONE);
}

void make_map3(EncodeFn fn, CUtensorMap* tm, const void* p) {
    cuuint64_t dims[3] = {(cuuint64_t)D_, 64, 32};
    cuuint64_t strides[2] = {(cuuint64_t)D_ * 2, (cuuint64_t)D_ * 128};
    cuuint32_t box[3] = {XW, 8, 32};
    cuuint32_t es[3] = {1, 1, 1};
    fn(tm, CU_TENSOR_MAP_DATA_TYPE_BFLOAT16, 3, const_cast<void*>(p), dims, strides, box, es, CU_TENSOR_MAP_INTERLEAVE_NONE,
       CU_TENSOR_MAP_SWIZZLE_NONE, CU_TENSOR_MAP_L2_PROMOTION_NONE, CU_TENSOR_MAP_FLOAT_OOB_FILL_NONE);
}

void make_map5(EncodeFn fn, CUtensorMap* tm, const void* p, int bc) {
    cuuint64_t dims[5] = {(cuuint64_t)D_, 2, 4, 4, 64};
    cuuint64_t strides[4] = {(cuuint64_t)D_ * 128, (cuuint64_t)D_ * 1024, (cuuint64_t)D_ * 256, (cuuint64_t)D_ * 2};
    cuuint32_t box[5] = {(cuuint32_t)bc, 2, 4, 4, 8};
    cuuint32_t es[5] = {1, 1, 1, 1, 1};
    fn(tm, CU_TENSOR_MAP_DATA_TYPE_BFLOAT16, 5, const_cast<void*>(p), dims, strides, box, es, CU_TENSOR_MAP_INTERLEAVE_NONE,
       CU_TENSOR_MAP_SWIZZLE_NONE, CU_TENSOR_MAP_L2_PROMOTION_NONE, CU_TENSOR_MAP_FLOAT_OOB_FILL_NONE);
}

}

extern "C" void kernel_launch(void* const* d_in, const int* in_sizes, int n_in, void* d_out, int out_size) {
    (void)in_sizes; (void)n_in; (void)out_size;
    void* fp = nullptr;
    cudaDriverEntryPointQueryResult qr;
    cudaGetDriverEntryPoint("cuTensorMapEncodeTiled", &fp, cudaEnableDefault, &qr);
    EncodeFn fn = (EncodeFn)fp;
    CUtensorMap tmG, tmU, tmD, tmO, tmX, tmH;
    make_map3(fn, &tmX, d_in[0]);
    make_map(fn, &tmG, d_in[11], F_, D_, 40, 48);
    make_map(fn, &tmU, d_in[12], F_, D_, 40, 48);
    make_map(fn, &tmD, d_in[13], D_, F_, W2W, 64);
    make_map5(fn, &tmO, d_out, 32);
    make_map5(fn, &tmH, d_out, 8);
    Params p;
    p.x = (const unsigned short*)d_in[0];
    for (int i = 0; i < 6; i++) p.prm6[i] = (const unsigned short*)d_in[1 + i];
    p.logdt = (const unsigned short*)d_in[7]; p.dskip = (const unsigned short*)d_in[8];
    p.wr = (const unsigned short*)d_in[10];
    p.out = (__nv_bfloat16*)d_out;
    p.zero = 0;
    cudaGetSymbolAddress((void**)&p.gs, g_s);
    cudaFuncSetAttribute(fused_kernel, cudaFuncAttributeMaxDynamicSharedMemorySize, SM_TOTAL);
    fused_kernel<<<NCTA, NTHR, SM_TOTAL>>>(p, tmG, tmU, tmD, tmO, tmX, tmH);
}
```

```cpp
#include <cuda_runtime.h>
#include <cuda_bf16.h>
#include <cuda_fp16.h>
#include <cuda.h>
#include <stdint.h>

namespace {

constexpr int L_ = 2048, D_ = 576, F_ = 4608;
constexpr int NCL = 15, CS = 8, NCTA = NCL * CS, NTHR = 768;
#define PACE_NS 0
#define AFTERX 0
#define EARLYB 0
#define GAP_NS 0
#define PACE0 200
#define W2W 72
#define ROWE 0
#define SYNC13 2
#define XW 48
#define TILE_NS -1
#define XROT 0
#define LNPOS 1
#define MMPOS 0
#define XSPLIT 3
constexpr int NRED = 2;
constexpr int SPIN_LIMIT = 1 << 22;

constexpr int SM_WG   = 0;
constexpr int SM_WU   = 46080;
constexpr int YP = 3392, YS = 656;
constexpr int UP = 3280, US = 656;
constexpr int SM_XT   = 92160;
constexpr int SM_U    = SM_XT + 8 * YP;
constexpr int SM_FAR  = SM_U + 8 * UP;
constexpr int FAR_SZ  = 12416;
constexpr int F_E5 = 0, F_O5 = 1536, F_E3 = 3088, F_O3 = 4624, F_E7 = 6176, F_E2 = F_E7 + 1024, F_E9 = F_E7 + 2048,
              F_H = 3088, F_O7 = F_E7 + F_H, F_O2 = F_E2 + F_H, F_O9 = F_E9 + F_H;
constexpr int SM_P    = SM_FAR + 5 * FAR_SZ;
constexpr int PN_SZ = 584 * 4, SM_PN = SM_P + 64 * 4;
constexpr int P_GS = 48 * 4, P_H7 = 192 * 4, P_HS = 72 * 4;
constexpr int PF_SZ = (192 + 216) * 4, SM_PF = SM_PN + 5 * PN_SZ + 32;
constexpr int SM_MISC = SM_PF + 5 * PF_SZ;
constexpr int SM_ST   = SM_MISC;
constexpr int SM_RK   = SM_ST + 2048;
constexpr int SM_SEL  = SM_RK + 256;
constexpr int SM_KG   = SM_SEL + 64;
constexpr int SM_SC   = SM_KG + 160;
constexpr int SM_DW   = SM_SC + 32;
constexpr int SM_MB   = SM_DW + 160;
constexpr int SM_TOTAL = SM_MB + 128;
constexpr int SM_ROW  = SM_XT - 20736;
constexpr int SM_XTL  = SM_ROW - 512 * XW;
constexpr int SM_RED2 = SM_WG;
constexpr int SM_HT   = SM_P - 512;
constexpr int SM_KEY  = SM_FAR + 10240 + 128;
constexpr int SM_CAND = SM_KEY + 1024;
constexpr int SM_XS   = SM_U;
constexpr int SM_GU   = SM_XS + 9344;
constexpr int SM_RED  = SM_GU + 5632;
static_assert(F_O9 + 1024 <= FAR_SZ && FAR_SZ % 128 == 0, "far overflow");
static_assert(SM_RED + 10240 <= SM_FAR && SM_HT + 20496 <= SM_MISC, "alias overflow");
static_assert(SM_TOTAL <= 232448, "smem overflow");
static_assert(SM_FAR % 128 == 0 && SM_XT % 128 == 0 && SM_XTL % 128 == 0 && SM_P % 16 == 0 && SM_MISC % 16 == 0 && SM_MB % 8 == 0, "align");

enum { MB_X = 0, MB_W1 = 5, MB_W2 = 6, MB_KEY = 7, MB_GU = 8, MB_Y = 9, MB_OUT = 10, MB_T = 11, MB_R = 12 };

struct __align__(128) Scratch {
    unsigned epoch, zcnt, pad[30];
    uint4  st1[L_ * 2];
    float4 acc[L_];
    uint4  cand[64 * NCL * 6];
    float4 fin[8 * 192 + 24];
};
__device__ Scratch g_s;
#define STAMP(i)

__device__ __forceinline__ uint32_t mapa(uint32_t a, uint32_t r) { uint32_t d; asm("mapa.shared::cluster.u32 %0, %1, %2;" : "=r"(d) : "r"(a), "r"(r)); return d; }
__device__ __forceinline__ void mbar_wait(uint32_t mb) {
    asm volatile("{ .reg .pred p, q; .reg .u32 n; mov.u32 n, 0;\n"
                 "W_%=: mbarrier.try_wait.parity.shared::cta.b64 p, [%0], 0; add.u32 n, n, 1; setp.lt.and.u32 q, n, 65536, !p; @q bra W_%=; }" :: "r"(mb) : "memory");
}
__device__ __forceinline__ void arm(uint32_t mb, uint32_t bytes) { asm volatile("mbarrier.arrive.expect_tx.shared::cta.b64 _, [%0], %1;" :: "r"(mb), "r"(bytes) : "memory"); }
__device__ __forceinline__ void bar_sync(int id, int n) { asm volatile("bar.sync %0, %1;" :: "r"(id), "r"(n) : "memory"); }
__device__ __forceinline__ void bar_arrive(int id, int n) { asm volatile("bar.arrive %0, %1;" :: "r"(id), "r"(n) : "memory"); }
__device__ __forceinline__ uint32_t lds16(uint32_t a) { unsigned short v; asm volatile("ld.shared.u16 %0, [%1];" : "=h"(v) : "r"(a) : "memory"); return v; }
__device__ __forceinline__ uint32_t lds32(uint32_t a) { uint32_t v; asm volatile("ld.shared.u32 %0, [%1];" : "=r"(v) : "r"(a) : "memory"); return v; }
__device__ __forceinline__ uint2 lds64(uint32_t a) { uint2 v; asm volatile("ld.shared.v2.u32 {%0,%1}, [%2];" : "=r"(v.x), "=r"(v.y) : "r"(a) : "memory"); return v; }
__device__ __forceinline__ float ldsf(uint32_t a) { float v; asm volatile("ld.shared.f32 %0, [%1];" : "=f"(v) : "r"(a) : "memory"); return v; }
__device__ __forceinline__ uint4 lds128(uint32_t a) { uint4 v; asm volatile("ld.shared.v4.u32 {%0,%1,%2,%3}, [%4];" : "=r"(v.x), "=r"(v.y), "=r"(v.z), "=r"(v.w) : "r"(a) : "memory"); return v; }
__device__ __forceinline__ float4 lds128f(uint32_t a) { float4 v; asm volatile("ld.shared.v4.f32 {%0,%1,%2,%3}, [%4];" : "=f"(v.x), "=f"(v.y), "=f"(v.z), "=f"(v.w) : "r"(a) : "memory"); return v; }
__device__ __forceinline__ void sts16(uint32_t a, uint32_t v) { asm volatile("{ .reg .b16 l, h; mov.b32 {l, h}, %1; st.shared.b16 [%0], l; }" :: "r"(a), "r"(v) : "memory"); }
__device__ __forceinline__ void sts32(uint32_t a, uint32_t v) { asm volatile("st.shared.u32 [%0], %1;" :: "r"(a), "r"(v) : "memory"); }
__device__ __forceinline__ void sts64(uint32_t a, uint32_t x, uint32_t y) { asm volatile("st.shared.v2.u32 [%0], {%1,%2};" :: "r"(a), "r"(x), "r"(y) : "memory"); }
__device__ __forceinline__ void stsf(uint32_t a, float v) { asm volatile("st.shared.f32 [%0], %1;" :: "r"(a), "f"(v) : "memory"); }
__device__ __forceinline__ void sts128(uint32_t a, uint32_t x, uint32_t y, uint32_t z, uint32_t w) { asm volatile("st.shared.v4.u32 [%0], {%1,%2,%3,%4};" :: "r"(a), "r"(x), "r"(y), "r"(z), "r"(w) : "memory"); }
__device__ __forceinline__ void sts128f(uint32_t a, float x, float y, float z, float w) { asm volatile("st.shared.v4.f32 [%0], {%1,%2,%3,%4};" :: "r"(a), "f"(x), "f"(y), "f"(z), "f"(w) : "memory"); }
__device__ __forceinline__ void ldsm4(uint32_t (&r)[4], uint32_t a) { asm volatile("ldmatrix.sync.aligned.m8n8.x4.shared.b16 {%0,%1,%2,%3}, [%4];" : "=r"(r[0]), "=r"(r[1]), "=r"(r[2]), "=r"(r[3]) : "r"(a) : "memory"); }
__device__ __forceinline__ void ldsm4t(uint32_t (&r)[4], uint32_t a) { asm volatile("ldmatrix.sync.aligned.m8n8.x4.trans.shared.b16 {%0,%1,%2,%3}, [%4];" : "=r"(r[0]), "=r"(r[1]), "=r"(r[2]), "=r"(r[3]) : "r"(a) : "memory"); }
__device__ __forceinline__ void ldsm2t(uint32_t& r0, uint32_t& r1, uint32_t a) { asm volatile("ldmatrix.sync.aligned.m8n8.x2.trans.shared.b16 {%0,%1}, [%2];" : "=r"(r0), "=r"(r1) : "r"(a) : "memory"); }
__device__ __forceinline__ void stsm4t(uint32_t a, uint32_t r0, uint32_t r1, uint32_t r2, uint32_t r3) { asm volatile("stmatrix.sync.aligned.m8n8.x4.trans.shared.b16 [%0], {%1,%2,%3,%4};" :: "r"(a), "r"(r0), "r"(r1), "r"(r2), "r"(r3) : "memory"); }
__device__ __forceinline__ void stsm4(uint32_t a, uint32_t r0, uint32_t r1, uint32_t r2, uint32_t r3) { asm volatile("stmatrix.sync.aligned.m8n8.x4.shared.b16 [%0], {%1,%2,%3,%4};" :: "r"(a), "r"(r0), "r"(r1), "r"(r2), "r"(r3) : "memory"); }
__device__ __forceinline__ void stsm2t(uint32_t a, uint32_t r0, uint32_t r1) { asm volatile("stmatrix.sync.aligned.m8n8.x2.trans.shared.b16 [%0], {%1,%2};" :: "r"(a), "r"(r0), "r"(r1) : "memory"); }
__device__ __forceinline__ uint4 ldg128(const void* p) { uint4 v; asm volatile("ld.global.nc.v4.u32 {%0,%1,%2,%3}, [%4];" : "=r"(v.x), "=r"(v.y), "=r"(v.z), "=r"(v.w) : "l"(p)); return v; }
__device__ __forceinline__ uint32_t ldg16(const void* p) { unsigned short v; asm volatile("ld.global.nc.u16 %0, [%1];" : "=h"(v) : "l"(p)); return v; }
__device__ __forceinline__ uint32_t opaque(uint32_t v) { uint32_t r; asm volatile("mov.b32 %0, %1;" : "=r"(r) : "r"(v)); return r; }
__device__ __forceinline__ void mma_f16(float (&d)[4], const uint32_t (&a)[4], uint32_t b0, uint32_t b1) {
    asm volatile("mma.sync.aligned.m16n8k16.row.col.f32.f16.f16.f32 {%0,%1,%2,%3}, {%4,%5,%6,%7}, {%8,%9}, {%0,%1,%2,%3};"
        : "+f"(d[0]), "+f"(d[1]), "+f"(d[2]), "+f"(d[3]) : "r"(a[0]), "r"(a[1]), "r"(a[2]), "r"(a[3]), "r"(b0), "r"(b1));
}
__device__ __forceinline__ void mma_bf16(float (&d)[4], uint32_t a0, uint32_t a1, uint32_t a2, uint32_t a3, uint32_t b0, uint32_t b1) {
    asm volatile("mma.sync.aligned.m16n8k16.row.col.f32.bf16.bf16.f32 {%0,%1,%2,%3}, {%4,%5,%6,%7}, {%8,%9}, {%0,%1,%2,%3};"
        : "+f"(d[0]), "+f"(d[1]), "+f"(d[2]), "+f"(d[3]) : "r"(a0), "r"(a1), "r"(a2), "r"(a3), "r"(b0), "r"(b1));
}
__device__ __forceinline__ void mma_bf16_k8(float (&d)[4], uint32_t a0, uint32_t a1, uint32_t b0) {
    asm volatile("mma.sync.aligned.m16n8k8.row.col.f32.bf16.bf16.f32 {%0,%1,%2,%3}, {%4,%5}, {%6}, {%0,%1,%2,%3};"
        : "+f"(d[0]), "+f"(d[1]), "+f"(d[2]), "+f"(d[3]) : "r"(a0), "r"(a1), "r"(b0));
}
__device__ __forceinline__ uint32_t pack_f16(float lo, float hi) { uint32_t r; asm("cvt.rn.f16x2.f32 %0, %1, %2;" : "=r"(r) : "f"(hi), "f"(lo)); return r; }
__device__ __forceinline__ uint32_t pack_bf16(float lo, float hi) { uint32_t r; asm("cvt.rn.bf16x2.f32 %0, %1, %2;" : "=r"(r) : "f"(hi), "f"(lo)); return r; }
__device__ __forceinline__ float bf_lo(uint32_t v) { return __uint_as_float(v << 16); }
__device__ __forceinline__ float bf_hi(uint32_t v) { return __uint_as_float(v & 0xFFFF0000u); }
__device__ __forceinline__ float bfr(float x) { return __uint_as_float(pack_bf16(0.f, x)); }
__device__ __forceinline__ uint32_t badd2(uint32_t a, uint32_t b) { uint32_t r; asm("add.rn.bf16x2 %0, %1, %2;" : "=r"(r) : "r"(a), "r"(b)); return r; }
__device__ __forceinline__ uint32_t bmul2(uint32_t a, uint32_t b) { uint32_t r; asm("mul.rn.bf16x2 %0, %1, %2;" : "=r"(r) : "r"(a), "r"(b)); return r; }
__device__ __forceinline__ uint32_t hadd2(uint32_t a, uint32_t b) { uint32_t r; asm("add.rn.f16x2 %0, %1, %2;" : "=r"(r) : "r"(a), "r"(b)); return r; }
__device__ __forceinline__ uint32_t hmul2(uint32_t a, uint32_t b) { uint32_t r; asm("mul.rn.f16x2 %0, %1, %2;" : "=r"(r) : "r"(a), "r"(b)); return r; }
__device__ __forceinline__ uint32_t hfma2(uint32_t a, uint32_t b, uint32_t c) { uint32_t r; asm("fma.rn.f16x2 %0, %1, %2, %3;" : "=r"(r) : "r"(a), "r"(b), "r"(c)); return r; }
__device__ __forceinline__ uint32_t hneg2(uint32_t a) { uint32_t r; asm("neg.f16x2 %0, %1;" : "=r"(r) : "r"(a)); return r; }
__device__ __forceinline__ float rcpf(float x) { float r; asm("rcp.approx.ftz.f32 %0, %1;" : "=f"(r) : "f"(x)); return r; }
__device__ __forceinline__ float sqrta(float x) { float r; asm("sqrt.approx.ftz.f32 %0, %1;" : "=f"(r) : "f"(x)); return r; }
__device__ __forceinline__ float ex2f(float x) { float r; asm("ex2.approx.ftz.f32 %0, %1;" : "=f"(r) : "f"(x)); return r; }
__device__ __forceinline__ void st_async4(uint32_t a, uint32_t x, uint32_t y, uint32_t z, uint32_t w, uint32_t mb) {
    asm volatile("st.async.shared::cluster.mbarrier::complete_tx::bytes.v4.u32 [%0], {%1,%2,%3,%4}, [%5];" :: "r"(a), "r"(x), "r"(y), "r"(z), "r"(w), "r"(mb) : "memory"); }
__device__ __forceinline__ void st_async1(uint32_t a, uint32_t x, uint32_t mb) {
    asm volatile("st.async.shared::cluster.mbarrier::complete_tx::bytes.u32 [%0], %1, [%2];" :: "r"(a), "r"(x), "r"(mb) : "memory"); }
__device__ __forceinline__ unsigned ld_rlx(const void* p) { unsigned v; asm volatile("ld.relaxed.gpu.global.u32 %0, [%1];" : "=r"(v) : "l"(p) : "memory"); return v; }
__device__ __forceinline__ unsigned ld_acq(const void* p) { unsigned v; asm volatile("ld.acquire.gpu.global.u32 %0, [%1];" : "=r"(v) : "l"(p) : "memory"); return v; }
__device__ __forceinline__ uint2 ld_rlx64(const void* p) { unsigned long long v; asm volatile("ld.relaxed.gpu.global.u64 %0, [%1];" : "=l"(v) : "l"(p) : "memory"); return make_uint2((unsigned)v, (unsigned)(v >> 32)); }
__device__ __forceinline__ void st_rlx128(void* p, uint32_t x, uint32_t y, uint32_t z, uint32_t w) {
    asm volatile("st.relaxed.gpu.global.v2.u64 [%0], {%1,%2};" :: "l"(p), "l"((unsigned long long)x | ((unsigned long long)y << 32)), "l"((unsigned long long)z | ((unsigned long long)w << 32)) : "memory"); }
__device__ __forceinline__ uint4 ld_rlx128(const void* p) { unsigned long long a, b; asm volatile("ld.relaxed.gpu.global.v2.u64 {%0,%1}, [%2];" : "=l"(a), "=l"(b) : "l"(p) : "memory"); return make_uint4((unsigned)a, (unsigned)(a >> 32), (unsigned)b, (unsigned)(b >> 32)); }
__device__ __forceinline__ void tma2d(uint32_t dst, const CUtensorMap* tm, int x, int y, uint32_t mb) {
    asm volatile("cp.async.bulk.tensor.2d.shared::cluster.global.mbarrier::complete_tx::bytes [%0], [%1, {%3, %4}], [%2];"
                 :: "r"(dst), "l"(tm), "r"(mb), "r"(x), "r"(y) : "memory");
}
__device__ __forceinline__ void cmul(float& xr, float& xi, float ar, float ai, float br, float bi) {
    const float r = fmaf(ar, br, -ai * bi), i = fmaf(ar, bi, ai * br); xr = r; xi = i;
}
__device__ __forceinline__ void csq(float& xr, float& xi, float ar, float ai) {
    const float r = fmaf(ar, ar, -ai * ai), i = (ar + ar) * ai; xr = r; xi = i;
}
__device__ __forceinline__ void cexp_s(float& zr, float& zi, float e2, float turns) {
    const float mag = ex2f(e2), r = (turns - rintf(turns)) * 6.283185307179586f;
    zr = mag * __cosf(r); zi = mag * __sinf(r);
}
__device__ __forceinline__ uint32_t ln_stats(float s1, float s2) {
    const float m = s1 * (1.f / D_);
    const float var = fmaxf(fmaf(s2, 1.f / D_, -m * m), 0.f);
    return pack_bf16(m, sqrta(bfr(bfr(var) + 1e-5f)));
}
__device__ __forceinline__ uint32_t rsplit(float rs) { const float h = bfr(rs); return pack_bf16(h, rs - h); }
__device__ __forceinline__ uint32_t norm2(uint32_t v, uint32_t mx, uint32_t hl) {
    uint32_t r;
    asm("{ .reg .b16 m, h, l, x; .reg .b32 m2, h2, l2, d, t; mov.b32 {m, x}, %2; mov.b32 {h, l}, %3; mov.b32 m2, {m, m}; mov.b32 h2, {h, h}; mov.b32 l2, {l, l};\n"
        "sub.rn.bf16x2 d, %1, m2; mul.rn.bf16x2 t, d, l2; fma.rn.bf16x2 %0, d, h2, t; }" : "=r"(r) : "r"(v), "r"(mx), "r"(hl));
    return r;
}
template <int N, int S>
__device__ __forceinline__ uint32_t rank4(uint32_t a, uint32_t key) {
    uint32_t r0 = 0, r1 = 0, r2 = 0, r3 = 0;
#pragma unroll
    for (int i = 0; i < N; i++) {
        const uint4 o = lds128(a + i * S);
        r0 += (key - o.x) >> 31; r1 += (key - o.y) >> 31; r2 += (key - o.z) >> 31; r3 += (key - o.w) >> 31;
    }
    return (r0 + r1) + (r2 + r3);
}
typedef uint32_t H2C;
__device__ __forceinline__ H2C splat(float r, float i) { return pack_f16(r, i); }
__device__ __forceinline__ void hcmul(uint32_t& xr, uint32_t& xi, uint32_t R, uint32_t I, H2C m) {
    asm("{ .reg .b16 a, b; .reg .b32 a2, b2, t; mov.b32 {a, b}, %4; mov.b32 a2, {a, a}; mov.b32 b2, {b, b};\n"
        "mul.rn.f16x2 t, %3, b2; neg.f16x2 t, t; fma.rn.f16x2 %0, %2, a2, t; mul.rn.f16x2 t, %3, a2; fma.rn.f16x2 %1, %2, b2, t; }"
        : "=&r"(xr), "=r"(xi) : "r"(R), "r"(I), "r"(m));
}
__device__ __forceinline__ void expand4(uint32_t are, uint32_t aim, uint32_t R0, uint32_t R1, uint32_t I0, uint32_t I1, H2C m4) {
    uint32_t R2, I2, R3, I3;
    hcmul(R2, I2, R0, I0, m4); hcmul(R3, I3, R1, I1, m4);
    sts128(are, R0, R1, R2, R3);
    sts128(aim, I0, I1, I2, I3);
}
__device__ __forceinline__ void expand8(uint32_t are, uint32_t aim, float sr, float si, float m1r, float m1i, float m2r, float m2i, H2C m4) {
    float r1, i1, r2, i2, r3, i3;
    cmul(r1, i1, sr, si, m1r, m1i); cmul(r2, i2, sr, si, m2r, m2i); cmul(r3, i3, r1, i1, m2r, m2i);
    expand4(are, aim, pack_f16(sr, r1), pack_f16(r2, r3), pack_f16(si, i1), pack_f16(i2, i3), m4);
}
__device__ __forceinline__ void put16(uint32_t a, uint32_t v) { sts16(a, v); sts16(a + 6, v); }

struct Params {
    const unsigned short *x, *prm6[6], *logdt, *dskip, *wr;
    __nv_bfloat16* out;
    Scratch* gs;
    unsigned zero;
};
__device__ __forceinline__ uint32_t tslot(uint32_t t) { return (t & 7) * 32 + ((t >> 4) & 24) + ((t >> 8) & 6) + ((t >> 6) & 1); }
#define CP(x) ((x) | zero)
#define PIN(x) asm volatile("or.b32 %0, %0, %1;" : "+r"(x) : "r"(zero))
__device__ __forceinline__ void wgmma32(float (&d)[4][4], const uint32_t (&a)[4], uint32_t dlo) {
    asm volatile("{ .reg .b64 ds; mov.b64 ds, {%20, %21};\n"
                 "wgmma.mma_async.sync.aligned.m64n32k16.f32.f16.f16 {%0,%1,%2,%3,%4,%5,%6,%7,%8,%9,%10,%11,%12,%13,%14,%15}, {%16,%17,%18,%19}, ds, 1, 1, 1, 0; }"
        : "+f"(d[0][0]), "+f"(d[0][1]), "+f"(d[0][2]), "+f"(d[0][3]), "+f"(d[1][0]), "+f"(d[1][1]), "+f"(d[1][2]), "+f"(d[1][3]),
          "+f"(d[2][0]), "+f"(d[2][1]), "+f"(d[2][2]), "+f"(d[2][3]), "+f"(d[3][0]), "+f"(d[3][1]), "+f"(d[3][2]), "+f"(d[3][3])
        : "r"(a[0]), "r"(a[1]), "r"(a[2]), "r"(a[3]), "r"(dlo), "n"(128 >> 4));
}

__global__ void __cluster_dims__(CS, 1, 1) __launch_bounds__(NTHR, 1)
fused_kernel(const __grid_constant__ Params prm, const __grid_constant__ CUtensorMap tmG, const __grid_constant__ CUtensorMap tmU,
             const __grid_constant__ CUtensorMap tmD, const __grid_constant__ CUtensorMap tmO, const __grid_constant__ CUtensorMap tmX, const __grid_constant__ CUtensorMap tmH)
{
    extern __shared__ __align__(1024) unsigned char smem[];
    const int tid = threadIdx.x, lane = tid & 31, warp = __shfl_sync(~0u, tid >> 5, 0);
    const int c = blockIdx.x >> 3, q = blockIdx.x & 7;
    const int nslot = (c < NCL - 1) ? 5 : 2;
    const int d0 = 40 * c;
    const uint32_t sb = opaque((uint32_t)__cvta_generic_to_shared(smem));
    const uint32_t mb = sb + SM_MB;
    Scratch& g_s = *prm.gs;
    const unsigned& zero = prm.zero;
    STAMP(0);

    if (warp >= 20) {
        unsigned epoch = 0;
        if (warp == 20) {
            if (lane == 0) {
#pragma unroll
                for (int i = 0; i < 13; i++)
                    asm volatile("mbarrier.init.shared::cta.b64 [%0], %1;" :: "r"(mb + i * 8), "r"((i == MB_R || i < 2) ? 2 : i == MB_Y ? 1 + 4 * nslot : 1) : "memory");
                asm volatile("fence.mbarrier_init.release.cluster;" ::: "memory");
                arm(mb + MB_W1 * 8, 92160); arm(mb + MB_W2 * 8, nslot * (128 * W2W)); arm(mb + MB_KEY * 8, 256); arm(mb + MB_GU * 8, nslot * 1024); arm(mb + MB_T * 8, 512 * XW);
                const int bytes = max(min(18, L_ - 18 * (int)blockIdx.x), 1) * (D_ * 2);
                arm(mb + MB_R * 8, bytes);
                if (ROWE) asm volatile("cp.async.bulk.shared::cluster.global.mbarrier::complete_tx::bytes [%0], [%1], %2, [%3];"
                             :: "r"(sb + SM_ROW), "l"(prm.x + min(18 * (int)blockIdx.x, L_ - 1) * D_), "r"(max(min(18, L_ - 18 * (int)blockIdx.x), 1) * (D_ * 2)), "r"(mb + MB_R * 8) : "memory");
            }
            __syncwarp();
        } else if (warp == 22) {
            epoch = ld_rlx(&g_s.epoch);
            if (lane < 18 ? 18 * c + lane < 256 : lane < 31) (lane < 18 ? &g_s.acc[256 * q + 18 * c] : &g_s.fin[13 * (int)blockIdx.x - 18])[lane] = make_float4(0.f, 0.f, 0.f, 0.f);
        } else if (warp == 23 && lane == 0) asm volatile("prefetch.tensormap [%0];" :: "l"(&tmX) : "memory");
        asm volatile("barrier.cluster.arrive.relaxed.aligned;" ::: "memory");
        bar_sync(12, NTHR);
        if (warp == 22) {
            if (lane == 0) { sts32(sb + SM_SC + 28, epoch); asm volatile("mbarrier.arrive.shared::cta.b64 _, [%0];" :: "r"(mb + MB_R * 8) : "memory"); }
            epoch++;
            asm volatile("fence.acq_rel.gpu;" ::: "memory");
            __syncwarp();
            if (lane == 0) asm volatile("red.relaxed.gpu.global.add.u32 [%0], 1;" :: "l"(&g_s.zcnt) : "memory");
            STAMP(1);
            uint4 wv = make_uint4(0, 0, 0, 0), wv2 = ldg128((const uint4*)prm.wr + lane), wv3 = ldg128((const uint4*)prm.wr + 32 + lane);
            if (lane < 8) wv = ldg128((const uint4*)prm.wr + 64 + lane);
            if (lane < 5) {
                uint4 v = make_uint4(0, 0, 0, 0);
                if (lane < nslot) v = ldg128((const uint4*)(prm.wr + d0) + lane);
                sts128(sb + SM_DW + lane * 16, v.x, v.y, v.z, v.w);
            }
            __syncwarp();
            if (lane < 2) asm volatile("mbarrier.arrive.shared::cta.b64 _, [%0];" :: "r"(mb + (MB_X + lane) * 8) : "memory");
            mbar_wait(mb + (MB_X + 1) * 8);
            const uint32_t old = (epoch & 1) ? 0u : 0x40004000u;
#pragma unroll
            for (int t = 0; t < 2; t++)
                if ((lane & 7) < 6) g_s.cand[((q * 8 + 4 * t + (lane >> 3)) * NCL + c) * 6 + (lane & 7)] = make_uint4(old, old, old, old);
            float a[4] = {0.f, 0.f, 0.f, 0.f};
            const uint32_t one = 0x3F803F80u;
            mma_bf16(a, one, one, one, one, wv.x, wv.y);  mma_bf16(a, one, one, one, one, wv.z, wv.w);
            mma_bf16(a, one, one, one, one, wv2.x, wv2.y); mma_bf16(a, one, one, one, one, wv2.z, wv2.w);
            mma_bf16(a, one, one, one, one, wv3.x, wv3.y); mma_bf16(a, one, one, one, one, wv3.z, wv3.w);
            float s = a[0] + a[1];
            s += __shfl_xor_sync(~0u, s, 1); s += __shfl_xor_sync(~0u, s, 2);
            stsf(sb + SM_SC + 24, s);
            __syncwarp();
            if (lane == 0) {
                int n = 0;
                while ((int)(ld_acq(&g_s.zcnt) - epoch * NCTA) < 0 && ++n < SPIN_LIMIT) __nanosleep(200);
                arm(mb + MB_Y * 8, 8 * 512 * nslot);
                if (blockIdx.x == 0) g_s.epoch = epoch;
            }
            STAMP(2);
            return;
        }
        if (warp == 21) {
            if (lane == 0) { asm volatile("prefetch.tensormap [%0];" :: "l"(&tmG) : "memory"); asm volatile("prefetch.tensormap [%0];" :: "l"(&tmU) : "memory"); asm volatile("prefetch.tensormap [%0];" :: "l"(&tmD) : "memory"); }
            __syncwarp();
            if (EARLYB) { bar_arrive(13, 736); mbar_wait(mb + MB_T * 8); if (GAP_NS) __nanosleep(GAP_NS); } else bar_sync(13, 736);
#pragma unroll 1
            for (int i = 0; i < 24; i++) {
                if (AFTERX && i == EARLYB) bar_sync(0, 96);
                if (i == SM_XTL / 3840) { bar_sync(15, 544); asm volatile("fence.proxy.async.shared::cta;" ::: "memory"); }
                if (lane == 0) tma2d(sb + SM_WG + i * 3840, i < 12 ? &tmG : &tmU, 320 * c + 8 * nslot * q, 48 * (i < 12 ? i : i - 12), mb + MB_W1 * 8);
                if (PACE_NS >= 0) __nanosleep(i < EARLYB ? PACE0 : PACE_NS);
            }
            STAMP(1);
            return;
        }
        if (warp == 20) {
            if (!ROWE && lane == 0) {
                asm volatile("cp.async.bulk.shared::cluster.global.mbarrier::complete_tx::bytes [%0], [%1], %2, [%3];"
                             :: "r"(sb + SM_ROW), "l"(prm.x + min(18 * (int)blockIdx.x, L_ - 1) * D_), "r"(max(min(18, L_ - 18 * (int)blockIdx.x), 1) * (D_ * 2)), "r"(mb + MB_R * 8) : "memory");
            }
            __syncwarp();
            if (TILE_NS < 0) mbar_wait(mb + MB_R * 8); else if (TILE_NS) __nanosleep(TILE_NS);
            if (lane == 0) {
                asm volatile("cp.async.bulk.tensor.3d.shared::cluster.global.mbarrier::complete_tx::bytes [%0], [%1, {%3, %4, %5}], [%2];"
                             :: "r"(sb + SM_XTL), "l"(&tmX), "r"(mb + MB_T * 8), "r"(XW == 40 ? d0 : d0 & ~15), "r"(8 * q), "r"(0) : "memory");
            }
            STAMP(6);
        }
        asm volatile("barrier.cluster.wait.aligned;" ::: "memory");
        bar_sync(13, 736);
        asm volatile("fence.proxy.async.shared::cta;" ::: "memory");
        {
            const int gr = lane >> 2, pe = XROT ? ((lane & 3) * 2 + (warp & 1) + q + 1) & 7 : (((lane & 3) ^ (gr * 3)) * 2 + (warp & 1)) & 7;
            const int s0 = gr ? 0 : XSPLIT, ns = gr ? min(XSPLIT, nslot) : nslot - XSPLIT;
            if (gr < 2 && ns > 0) {
                const int bytes = ns * YS - 144;
                if (pe == q) arm(mb + (MB_X + gr) * 8, 7 * bytes);
                else {
                    const uint32_t rb_ = mapa(sb, pe);
                    asm volatile("cp.async.bulk.shared::cluster.shared::cta.mbarrier::complete_tx::bytes [%0], [%1], %2, [%3];"
                                 :: "r"(rb_ + SM_U + 128 + q * UP + s0 * US), "r"(sb + SM_XT + 128 + (q & 3) * 16 + pe * YP + s0 * YS), "r"(bytes), "r"(rb_ + SM_MB + (MB_X + gr) * 8) : "memory");
                }
            }
        }
        __syncwarp();
        if (AFTERX) bar_arrive(0, 96);
        STAMP(1);
        if (warp == 20 && lane == 0) { asm volatile("prefetch.tensormap [%0];" :: "l"(&tmO) : "memory"); asm volatile("prefetch.tensormap [%0];" :: "l"(&tmH) : "memory"); }
        if (warp == 23) {
#pragma unroll 1
            for (int kk = nslot - 1; kk >= 0; kk--) {
                __syncwarp();
                bar_sync(6 + kk, 160);
                if (lane == 0) { asm volatile("fence.proxy.async.shared::cta;" ::: "memory"); tma2d(sb + SM_FAR + kk * FAR_SZ, &tmD, W2W == 72 ? 72 * q : (72 * q) & ~15, 320 * c + 64 * kk, mb + MB_W2 * 8); }
            }
            return;
        }
        __syncwarp();
        bar_sync(14, 672);
        if (lane == 0) {
            asm volatile("fence.proxy.async.shared::cta;" ::: "memory");
            asm volatile("cp.async.bulk.tensor.5d.global.shared::cta.bulk_group [%0, {%2, %4, %4, %4, %3}], [%1];" :: "l"(&tmH), "r"(sb + SM_XT + 16384), "r"(d0 + ((c & 1) ? 0 : 32)), "r"(8 * q), "r"(0) : "memory");
            asm volatile("cp.async.bulk.tensor.5d.global.shared::cta.bulk_group [%0, {%2, %4, %4, %4, %3}], [%1];" :: "l"(&tmO), "r"(sb + SM_XT), "r"(d0 + (c & 1) * 8), "r"(8 * q), "r"(0) : "memory");
            asm volatile("cp.async.bulk.commit_group;" ::: "memory");
            asm volatile("cp.async.bulk.wait_group 0;" ::: "memory");
            asm volatile("fence.proxy.async.global;" ::: "memory");
            asm volatile("mbarrier.arrive.shared::cta.b64 _, [%0];" :: "r"(mb + MB_OUT * 8) : "memory");
        }
        STAMP(2);
        return;
    }

    const int g = lane >> 2, cq = lane & 3;
    const int k = warp >> 2, wq = warp & 3;
    const int trow = 18 * blockIdx.x + warp;
    const bool rowact = warp < 18 && trow < L_;
    const int dch = min(d0 + 8 * k + q, D_ - 1);
    uint32_t pv[6];
#pragma unroll
    for (int i = 0; i < 6; i++) pv[i] = ldg16(prm.prm6[i] + (uint32_t)(dch * 128 + wq * 32 + lane));
    const uint32_t pLdt = ldg16(prm.logdt + dch), pD = ldg16(prm.dskip + dch);
    const int tn = 16 * (warp & 15) + g;
    uint32_t xa[5], xb[5];
    asm volatile("barrier.cluster.arrive.relaxed.aligned;" ::: "memory");
    uint4* const st1p = &g_s.st1[(((trow >> 3) & 7) * 256 + ((trow >> 6) & 31) * 8 + (trow & 7)) * 2 + (lane >> 2)];
    const bool pub = rowact && (lane & 0x1B) == 0;
    if (pub) st_rlx128(st1p, 0, 0, 0, 0);
    {
        const uint32_t za = sb + SM_P + tid * 16;
        sts128(za, 0, 0, 0, 0);
        if (tid < (SM_MISC - SM_P) / 16 - 640) sts128(za + 10240, 0, 0, 0, 0);
        sts128(sb + ((wq & 2) ? SM_U : SM_XT + (q & 3) * 16) + ((tid >> 3) & 7) * ((wq & 2) ? UP : YP) + k * YS + (lane & 7) * 16, 0, 0, 0, 0);
    }
    bar_sync(12, NTHR);
    const uint32_t dep = lds32(sb + SM_P);
#define PV(x) __uint_as_float(__byte_perm(dep, x, 0x5410))
    STAMP(1);
    const uint32_t fb = sb + SM_FAR + k * FAR_SZ;
    const uint32_t pn = sb + SM_PN + k * PN_SZ, pf = sb + SM_PF + k * PF_SZ;
    unsigned epoch;
    {
        const uint32_t kb = fb + wq * 3072;
        const uint32_t kl = kb + lane * 16;
        uint32_t Af[4][4];
        float sr, si, z1r, z1i, z2r, z2i, z4r, z4i, hr, hi_;
        {
            const float dt = bfr(ex2f(PV(pLdt) * 1.4426950408889634f));
            const float e2 = dt * PV(pv[0]) * 1.4426950408889634f, an = dt * PV(pv[1]);
            cmul(sr, si, PV(pv[4]), PV(pv[5]), dt * PV(pv[2]), dt * PV(pv[3]));
            const unsigned E = min(max(__reduce_max_sync(~0u, __float_as_uint(fmaxf(fmaxf(fabsf(sr), fabsf(si)), fabsf(PV(pD)) * (1.f / 8192.f)))) >> 23, 1u), 253u);
            const float sc = __uint_as_float((254u - E) << 23);
            sr *= sc; si *= -sc;
            sts64(sb + SM_KG + warp * 8, E, __reduce_add_sync(~0u, __float2int_rn(sr * 16777216.f)));
            float ar, ai, br, bi, cr, ci, dr, di;
            { const float m = ex2f(e2 * 8.f); ar = m * __cosf(an * 8.f); ai = m * __sinf(an * 8.f); }
            csq(br, bi, ar, ai); csq(cr, ci, br, bi); csq(dr, di, cr, ci);
            const H2C m4 = splat(cr, ci);
            {
                float r3, i3;
                cmul(r3, i3, ar, ai, br, bi);
                expand4(kl, kl + 1024, pack_f16(1.f, ar), pack_f16(br, r3), pack_f16(0.f, ai), pack_f16(bi, i3), m4);
            }
            expand8(kl + 512, kl + 1536, dr, di, ar, ai, br, bi, m4);
            { const float m = ex2f(e2); z1r = m * __cosf(an); z1i = -m * __sinf(an); }
            cexp_s(hr, hi_, e2 * 128.f, an * (-128.f * 0.15915494309189535f));
            csq(z2r, z2i, z1r, z1i); csq(z4r, z4i, z2r, z2i);
        }
        __syncwarp();
#pragma unroll
        for (int ks = 0; ks < 4; ks++) ldsm4t(Af[ks], kb + (lane >> 3) * 512 + (lane & 7) * 16 + ks * 128);
        STAMP(2);
        const uint32_t la = kb + ((lane >> 3) & 1) * 512 + (lane >> 4) * 128 + (lane & 7) * 16;
        uint32_t kp[5][2], b0[4], b1[4], b2[4], b3[4];
        auto mm2 = [&](int t) {
            float a0[4] = {0.f, 0.f, 0.f, 0.f}, a1[4] = {0.f, 0.f, 0.f, 0.f};
            mma_f16(a0, Af[0], b0[0], b0[1]); mma_f16(a1, Af[0], b2[0], b2[1]); mma_f16(a0, Af[1], b0[2], b0[3]); mma_f16(a1, Af[1], b2[2], b2[3]);
            mma_f16(a0, Af[2], b1[0], b1[1]); mma_f16(a1, Af[2], b3[0], b3[1]); mma_f16(a0, Af[3], b1[2], b1[3]); mma_f16(a1, Af[3], b3[2], b3[3]);
            kp[t][0] = pack_f16(a0[1], a0[0]); kp[t][1] = pack_f16(a0[3], a0[2]); kp[t + 1][0] = pack_f16(a1[1], a1[0]); kp[t + 1][1] = pack_f16(a1[3], a1[2]);
        };
        auto ln1 = [&]() {
        mbar_wait(mb + MB_R * 8);
        epoch = lds32(sb + SM_SC + 28) + 1;
        {
            const uint32_t ra = sb + SM_ROW + warp * (D_ * 2);
            const uint4 r0 = lds128(ra + lane * 16), r1 = lds128(ra + 512 + lane * 16);
            const uint32_t rx[9] = {r0.x, r0.y, r0.z, r0.w, r1.x, r1.y, r1.z, r1.w, lds32(ra + 1024 + lane * 4)};
            float a0 = bf_lo(rx[0]), a1 = bf_hi(rx[0]), c0 = a0 * a0, c1 = a1 * a1;
#pragma unroll
            for (int i = 1; i < 9; i++) { const float l = bf_lo(rx[i]), h = bf_hi(rx[i]); a0 += l; a1 += h; c0 = fmaf(l, l, c0); c1 = fmaf(h, h, c1); }
            a0 += a1; c0 += c1;
            float s1 = ((lane & 1) ? c0 : a0) + __shfl_xor_sync(~0u, (lane & 1) ? a0 : c0, 1);
#pragma unroll
            for (int o = 2; o < 32; o <<= 1) s1 += __shfl_xor_sync(~0u, s1, o);
            const float s2 = __shfl_xor_sync(~0u, s1, 1);
            const uint32_t ms = ln_stats(s1, s2);
            const uint32_t p0 = __byte_perm(ms, epoch | 0x8000u, 0x5410), p1 = rsplit(rcpf(bf_hi(ms)));
            if (pub) st_rlx128(st1p, p0, p1, p0, p1);
        }
        mbar_wait(mb + MB_R * 8);
        STAMP(1);
        };
        const uint4* sp = &g_s.st1[(256 * q + tn) * 2];
        uint2 sa, sc;
        auto poll = [&]() { sa = ld_rlx64(sp); sc = ld_rlx64(sp + 16); };
        auto norm = [&]() {
        STAMP(3);
        if (warp < 16) {
            uint32_t va[5], vc[5];
            poll();
            mbar_wait(mb + MB_T * 8);
            {
                const uint32_t xt = sb + SM_XTL + (XW == 40 ? 0 : (c & 1) * 16) + tn * (2 * XW);
                uint4 a4 = lds128(xt + cq * 16), b4 = lds128(xt + cq * 16 + 16 * XW);
                va[0] = a4.x; va[1] = a4.y; va[2] = a4.z; va[3] = a4.w; va[4] = lds32(xt + 64 + cq * 4);
                vc[0] = b4.x; vc[1] = b4.y; vc[2] = b4.z; vc[3] = b4.w; vc[4] = lds32(xt + (64 + 16 * XW) + cq * 4);
            }
            const int d4 = 2 * (lane >> 3) + (lane & 1), d1_ = lane & 7;
            const uint32_t own = SM_U + 128 + q * (UP - YP), oth = SM_XT + 128 + (q & 3) * 16;
            uint32_t a4 = sb + warp * 32 + d4 * YP + (d4 == q ? own : oth) + ((lane & 7) >> 1) * YS;
            uint32_t a1 = sb + warp * 32 + d1_ * YP + (d1_ == q ? own : oth) + 4 * YS + (lane & 8) * 2;
            PIN(a4); PIN(a1);
            const uint32_t tag = __byte_perm(epoch | 0x8000u, 0, 0x1010) | ((va[0] & va[4] & vc[0] & vc[4]) & zero);
            int n = 0;
            while (__byte_perm(sa.x, sc.x, 0x7632) != tag && ++n < SPIN_LIMIT) poll();
            STAMP(4);
#pragma unroll
            for (int i = 0; i < 5; i++) {
                va[i] = norm2(va[i], sa.x, sa.y); va[i] = pack_f16(bf_lo(va[i]), bf_hi(va[i]));
                vc[i] = norm2(vc[i], sc.x, sc.y); vc[i] = pack_f16(bf_lo(vc[i]), bf_hi(vc[i]));
            }
            stsm4t(a4, va[0], va[1], va[2], va[3]); stsm4t(a4 + 16, vc[0], vc[1], vc[2], vc[3]); stsm2t(a1, va[4], vc[4]);
        }
        if (SYNC13 == 0 || (SYNC13 == 1 && warp < 16) || (SYNC13 == 3 && warp >= 16)) bar_arrive(13, 736);
        if (warp < 16) {
            const uint32_t xh = sb + SM_XTL + (XW == 40 ? 0 : (c & 1) * 16) + (64 * (g >> 1) + 32 * (warp & 1) + 8 * (g & 1) + (warp >> 1)) * (2 * XW);
            const uint4 a4 = lds128(xh + cq * 16), b4 = lds128(xh + cq * 16 + 32 * XW);
            xa[0] = a4.x; xa[1] = a4.y; xa[2] = a4.z; xa[3] = a4.w; xa[4] = lds32(xh + 64 + cq * 4);
            xb[0] = b4.x; xb[1] = b4.y; xb[2] = b4.z; xb[3] = b4.w; xb[4] = lds32(xh + (64 + 32 * XW) + cq * 4);
            bar_arrive(15, 544);
        }
        STAMP(5);
        if (SYNC13 == 2 || (SYNC13 == 1 && warp >= 16) || (SYNC13 == 3 && warp < 16)) bar_sync(13, 736);
        if (SYNC13) Af[0][0] |= lds32(sb + SM_P);
        };
        if (LNPOS == 0) ln1();
        cmul(sr, si, sr, si, z1r, z1i);
        {
            const H2C h4 = splat(z4r, z4i);
            expand8(kl, kl + 512, sr, si, z1r, z1i, z2r, z2i, h4);
            cmul(sr, si, sr, si, hr, hi_);
            expand8(kl + 1024, kl + 1536, sr, si, z1r, z1i, z2r, z2i, h4);
        }
        __syncwarp();
        ldsm4t(b0, la); ldsm4t(b1, la + 256); ldsm4t(b2, la + 1024); ldsm4t(b3, la + 1280);
        cmul(z1r, z1i, z1r, z1i, hr, hi_);
        cmul(sr, si, sr, si, z1r, z1i);
        if (LNPOS == 1) ln1();
        expand8(kl, kl + 512, sr, si, z2r, z2i, z4r, z4i, splat(hr, hi_));
        if (LNPOS == 2) ln1();
        csq(z1r, z1i, z1r, z1i);
        cmul(sr, si, sr, si, z1r, z1i);
        csq(z2r, z2i, hr, hi_);
        expand8(kl + 1024, kl + 1536, sr, si, z4r, z4i, hr, hi_, splat(z2r, z2i));
        if (LNPOS == 3) ln1();
        csq(z1r, z1i, z1r, z1i);
        cmul(sr, si, sr, si, z1r, z1i);
        csq(z4r, z4i, z2r, z2i);
        expand8(kl + 2048, kl + 2560, sr, si, hr, hi_, z2r, z2i, splat(z4r, z4i));
        if (LNPOS == 4) ln1();
        if (MMPOS == 0) norm();
        mm2(0);
        __syncwarp();
        ldsm4t(b0, la); ldsm4t(b1, la + 256); ldsm4t(b2, la + 1024); ldsm4t(b3, la + 1280);
        if (MMPOS == 1) norm();
        mm2(2);
        if (MMPOS == 2) norm();
        ldsm4t(b0, la + 2048); ldsm4t(b1, la + 2304);
#pragma unroll
        for (int t = 0; t < 4; t++) sts64(kb + lane * 8 + 1024 + t * 256, kp[t][0], kp[t][1]);
        {
            float a0[4] = {0.f, 0.f, 0.f, 0.f}, a1[4] = {0.f, 0.f, 0.f, 0.f};
            mma_f16(a0, Af[0], b0[0], b0[1]); mma_f16(a1, Af[1], b0[2], b0[3]); mma_f16(a0, Af[2], b1[0], b1[1]); mma_f16(a1, Af[3], b1[2], b1[3]);
            sts64(kb + lane * 8 + 2048, pack_f16(a0[1] + a1[1], a0[0] + a1[0]), pack_f16(a0[3] + a1[3], a0[2] + a1[2]));
        }
        bar_sync(1 + k, 128);
        const uint4 m01 = lds128(sb + SM_KG + k * 32), m23 = lds128(sb + SM_KG + k * 32 + 16);
        const unsigned Em = max(max(m01.x, m01.z), max(m23.x, m23.z));
        const float f0 = __uint_as_float(max((int)(127 + m01.x - Em), 0) << 23), f1 = __uint_as_float(max((int)(127 + m01.z - Em), 0) << 23),
                    f2 = __uint_as_float(max((int)(127 + m23.x - Em), 0) << 23), f3 = __uint_as_float(max((int)(127 + m23.z - Em), 0) << 23);
        const uint32_t r0 = pack_f16(f0, f0), r1 = pack_f16(f1, f1), r2 = pack_f16(f2, f2), r3 = pack_f16(f3, f3);
        const uint32_t ra = fb + lane * 8 + wq * 256 + 1024;
        const uint2 p0 = lds64(ra), p1 = lds64(ra + 3072), p2 = lds64(ra + 6144), p3 = lds64(ra + 9216);
        uint32_t w0 = hadd2(hfma2(p0.x, r0, hmul2(p1.x, r1)), hfma2(p2.x, r2, hmul2(p3.x, r3)));
        uint32_t w1 = hadd2(hfma2(p0.y, r0, hmul2(p1.y, r1)), hfma2(p2.y, r2, hmul2(p3.y, r3)));
        const bool last = lane == 31;
        if (wq < 2) {
            const uint32_t rc = fb + lane * 8 + wq * 4 + 2048;
            const uint32_t w4 = hmul2(hadd2(hfma2(lds32(rc), r0, hmul2(lds32(rc + 3072), r1)), hfma2(lds32(rc + 6144), r2, hmul2(lds32(rc + 9216), r3))), 0x18001800u);
            const uint32_t ph = pf + (P_H7 + 16 * wq) + (g & 1) * (2 * P_HS) + cq * 64 + (g >> 1) * 4;
            put16(ph, w4 >> 16); put16(ph + 32, w4);
            const uint32_t pa = pn + (4 + 512 * wq) + lane * 8;
            sts16(pa, w0 >> 16); sts32(pa + 4, w0); sts16(pa + 10, w0);
            sts16(pa + 256, w1 >> 16); sts32(pa + 260, w1); sts16(pa + 266, w1);
            if (last) {
                sts32(sb + SM_SC + k * 4, Em * 0x00800080u);
                put16(wq ? pa + 264 : pn,
                      wq ? w1 : pack_f16(((float)(int)m01.y * f0 + (float)(int)m01.w * f1 + (float)(int)m23.y * f2 + (float)(int)m23.w * f3) * (1.f / 16777216.f)
                                         + __uint_as_float(pD << 16) * __uint_as_float((254u - Em) << 23), 0.f));
            }
        } else if (wq == 2) {
            const uint32_t pa = pn + 258 * 4 + (cq & 1) * 16 + (cq >> 1) * 512 + g * 32;
            if (last) { put16(pf, hmul2(w1, 0x18001800u)); w1 = hadd2(w1, hneg2(__byte_perm(w1, 0, 0x1010))); }
            const uint32_t b0 = __byte_perm(w0, 0, 0x1010), b1 = __byte_perm(w1, 0, 0x1010);
            sts16(pa, w0 >> 16); sts32(pa + 4, w0); sts64(pa + 8, b0, b0); sts16(pa + 18, w0);
            sts16(pa + 256, w1 >> 16); sts32(pa + 260, w1); sts64(pa + 264, b1, b1); sts16(pa + 274, w1);
        } else {
            const uint32_t pa = pf + ((g & 1) ? 3 * P_GS : P_GS) + cq * 32 + (g >> 1) * 4;
            const uint32_t pb = pa + ((g & 1) ? 4 - 3 * P_GS : P_GS);
            w0 = hmul2(w0, 0x18001800u); w1 = hmul2(w1, 0x18001800u);
            put16(pa, w0 >> 16); put16(pb, w0); put16(pa + 16, w1 >> 16); put16(pb + 16, w1);
            if (last) put16(pf + P_H7 + P_HS, w1);
        }
        bar_sync(1 + k, 128);
    }
    STAMP(6);

    asm volatile("barrier.cluster.wait.aligned;" ::: "memory");
    mbar_wait(mb + (MB_X + (k < XSPLIT || k >= nslot)) * 8);
    STAMP(7);
    if (k < nslot) {
        const int role = (wq + k) & 3;
        const uint32_t ub = sb + SM_U + k * US + 128;
        if (role) {
            const int r = (3 - role) * 32 + lane;
            const uint32_t a1 = ub + (r & 3) * (2 * UP) + (r >> 2) * 16, a0 = a1 + ((r & 3) ? -2 * UP : 6 * UP - 16);
            const uint4 q0 = lds128(a0), q1 = lds128(a0 + UP), q2 = lds128(a1), q3 = lds128(a1 + UP);
            const uint32_t U[16] = {q0.x, q0.y, q0.z, q0.w, q1.x, q1.y, q1.z, q1.w, q2.x, q2.y, q2.z, q2.w, q3.x, q3.y, q3.z, q3.w};
            uint32_t V[14], Q[14], R4[12], T[8];
#pragma unroll
            for (int i = 2; i < 14; i++) { V[i] = __byte_perm(U[i], U[i + 1], 0x5432); Q[i] = hadd2(U[i], V[i]); }
#pragma unroll
            for (int i = 2; i < 12; i++) R4[i] = hadd2(Q[i], Q[i + 1]);
            const uint32_t rb = fb + r * 16;
#pragma unroll
            for (int i = 0; i < 8; i++) T[i] = hadd2(V[5 + i], Q[6 + i]);
            sts128(rb + F_E3, T[0], T[1], T[2], T[3]); sts128(rb + F_O3 + 16, T[4], T[5], T[6], T[7]);
#pragma unroll
            for (int i = 0; i < 8; i++) T[i] = hadd2(R4[3 + i], U[5 + i]);
            sts128(rb + F_O5, T[0], T[1], T[2], T[3]); sts128(rb + F_E5, T[4], T[5], T[6], T[7]);
            if (role != 1) {
#pragma unroll
                for (int i = 0; i < 8; i++) T[i] = hadd2(T[i], hadd2(V[2 + i], V[5 + i]));
                sts128(rb + F_E7, T[0], T[1], T[2], T[3]); sts128(rb + F_O7, T[4], T[5], T[6], T[7]);
#pragma unroll
                for (int i = 0; i < 8; i++) T[i] = hadd2(R4[2 + i], hadd2(R4[4 + i], U[6 + i]));
                sts128(rb + F_O9, T[0], T[1], T[2], T[3]); sts128(rb + F_E9 + 16, T[4], T[5], T[6], T[7]);
                sts128(rb + F_E2, Q[6], Q[7], Q[8], Q[9]); sts128(rb + F_O2, Q[10], Q[11], Q[12], Q[13]);
            }
        } else if (lane < 8) {
            uint32_t v[5];
#pragma unroll
            for (int i = 0; i < 5; i++) { const int t = 6 + lane + i; v[i] = lds16(ub + 23 * 16 + (t < 16 ? (6 + (t >> 3)) * UP : 16) + (t & 7) * 2); }
            const uint32_t s = hadd2(hadd2(hadd2(v[0], v[1]), hadd2(v[2], v[3])), v[4]);
            sts16(fb + F_O5 + 96 * 16 + lane * 2, s);
            sts32(fb + (lane < 4 ? F_O3 : F_E9 - 16) + lane * 4, 0);
        }
        bar_sync(1 + k, 128);
        float acc[4][4];
        uint32_t Q[4][4];
        {
            const int h = role & 1, part = role >> 1;
            const uint32_t po = pf + (g - 2 * cq) * 4;
            float fa[7][4];
#pragma unroll
            for (int a = 0; a < 7; a++) fa[a][0] = fa[a][1] = fa[a][2] = fa[a][3] = 0.f;
            uint32_t B[3][4];
            Q[0][2] = zero;
#pragma unroll 1
            for (int s = 2 * part + 1; s >= 2 * part; s--) {
#pragma unroll
                for (int i = 0; i < 3; i++) { Q[i][0] = lds32(po + s * P_GS + i * 64); Q[i][1] = lds32(po + s * P_GS + (i * 64 + 32)); }
                const uint32_t ba = fb + lane * 16 + ((s & 1) * F_E3 + (part == h ? 0 : F_O5 + h * 16));
#pragma unroll
                for (int i = 0; i < 3; i++) ldsm4t(B[i], ba + i * 512);
#pragma unroll
                for (int i = 0; i < 3; i++) { Q[i][3] = CP(Q[i][0]); if (i) Q[i][2] = CP(Q[i - 1][1]); }
#pragma unroll
                for (int dl = 0; dl < 3; dl++)
#pragma unroll
                    for (int ap = 0; ap < 6 - dl; ap++) mma_f16(fa[ap + 1 + dl], Q[dl], B[ap >> 1][2 * (ap & 1)], B[ap >> 1][2 * (ap & 1) + 1]);
            }
#pragma unroll 1
            for (int s = role; s == 1; s++) {
                ldsm2t(B[0][0], B[0][1], fb + ((lane & 15) == 15 ? F_O5 : F_O3));
#pragma unroll
                for (int dl = 0; dl < 3; dl++) mma_f16(fa[dl], Q[dl], B[0][0], B[0][1]);
            }
#pragma unroll 1
            for (int s = part; s <= 2 * part; s++) {
#pragma unroll
                for (int i = 0; i < 4; i++) { Q[i][0] = lds32(po + s * P_HS + (P_H7 + i * 64)); Q[i][1] = lds32(po + s * P_HS + (P_H7 + i * 64 + 32)); }
                const uint32_t ba = fb + lane * 16 + (F_E7 + s * 1024 + h * F_H);
                ldsm4t(B[0], ba); ldsm4t(B[1], ba + 512);
#pragma unroll
                for (int i = 0; i < 4; i++) { Q[i][3] = CP(Q[i][0]); if (i) Q[i][2] = CP(Q[i - 1][1]); }
#pragma unroll
                for (int dl = 0; dl < 4; dl++) {
#pragma unroll
                    for (int ap = 0; ap < 4 - dl; ap++) mma_f16(fa[ap + 3 + dl], Q[dl], B[ap >> 1][2 * (ap & 1)], B[ap >> 1][2 * (ap & 1) + 1]);
                    if (s == 1) break;
                }
            }
            const uint32_t da = fb + role * 2048 + (lane & 3) * 512 + (((lane >> 2) ^ ((lane & 3) * 2)) << 4);
            bar_sync(1 + k, 128);
            stsm4(da, 0u, 0u, pack_f16(fa[0][0], fa[0][1]), pack_f16(fa[0][2], fa[0][3]));
#pragma unroll
            for (int i = 1; i < 4; i++)
                stsm4(da + i * 128, pack_f16(fa[2 * i - 1][0], fa[2 * i - 1][1]), pack_f16(fa[2 * i - 1][2], fa[2 * i - 1][3]),
                      pack_f16(fa[2 * i][0], fa[2 * i][1]), pack_f16(fa[2 * i][2], fa[2 * i][3]));
            Q[0][0] = (g == 2 * cq) ? 0x6000u : ((g == 2 * cq + 1) ? 0x60000000u : 0u);
            Q[0][1] = 0; Q[0][3] = CP(Q[0][0]);
            const uint32_t ra = fb + (lane >> 3) * 2048 + wq * 512 + (((lane & 7) ^ (wq * 2)) << 4);
            bar_sync(1 + k, 128);
#pragma unroll
            for (int i = 0; i < 4; i++) {
                ldsm4(B[0], ra + i * 128);
                acc[i][0] = acc[i][1] = acc[i][2] = acc[i][3] = 0.f;
                mma_f16(acc[i], Q[0], hadd2(B[0][0], B[0][2]), hadd2(B[0][1], B[0][3]));
            }
        }
        bar_arrive(6 + k, 160);
        STAMP(8);
        const uint32_t inv = lds32(sb + SM_SC + k * 4);
        uint32_t yd = mapa(sb, 2 * wq) + (SM_XT + 128 + q * YP + k * YS + (k >> 2) * (q >> 1) * 16) + lane * 16;
        PIN(yd);
        {
            uint32_t pp = pn + (16 * (wq - 3) + g - 2 * cq) * 4;
            uint32_t dlo = (((ub + 6 * UP) & 0x3FFFF) >> 4) | ((UP >> 4) << 16);
            uint32_t R[4][4];
            auto loadQ = [&](uint32_t (&X)[4][4], uint32_t prev) {
#pragma unroll
                for (int i = 0; i < 4; i++) { X[i][0] = lds32(pp + i * 64); X[i][1] = lds32(pp + i * 64 + 32); }
                X[0][2] = CP(prev);
#pragma unroll
                for (int i = 0; i < 4; i++) { X[i][3] = CP(X[i][0]); if (i) X[i][2] = CP(X[i - 1][1]); }
                pp += 256;
            };
            auto issue = [&](uint32_t (&X)[4][4]) {
                asm volatile("wgmma.fence.sync.aligned;" ::: "memory");
#pragma unroll
                for (int i = 0; i < 4; i++) wgmma32(acc, X[i], dlo - i * (2 * UP >> 4));
                asm volatile("wgmma.commit_group.sync.aligned;" ::: "memory");
                dlo -= 1;
            };
            loadQ(Q, 0);
#pragma unroll 1
            for (int dl = 0; dl < 4; dl++) {
                issue(Q);
                asm volatile("wgmma.wait_group.sync.aligned 1;" ::: "memory");
                loadQ(R, Q[3][1]);
                issue(R);
                asm volatile("wgmma.wait_group.sync.aligned 1;" ::: "memory");
                loadQ(Q, R[3][1]);
            }
            issue(Q);
            asm volatile("wgmma.wait_group.sync.aligned 0;" ::: "memory");
        }
        const uint32_t pstep = mapa(sb, 1) - mapa(sb, 0), ym = mapa(mb + MB_Y * 8, 2 * wq);
#pragma unroll
        for (int e = 0; e < 2; e++)
            st_async4(yd + e * pstep, bmul2(pack_bf16(acc[0][2 * e], acc[0][2 * e + 1]), inv), bmul2(pack_bf16(acc[1][2 * e], acc[1][2 * e + 1]), inv),
                      bmul2(pack_bf16(acc[2][2 * e], acc[2][2 * e + 1]), inv), bmul2(pack_bf16(acc[3][2 * e], acc[3][2 * e + 1]), inv), ym + e * pstep);
        if (lane == 0) asm volatile("mbarrier.arrive.shared::cta.b64 _, [%0];" :: "r"(mb + MB_Y * 8) : "memory");
    }
    STAMP(9);
    uint32_t ha[5], hb[5];
    if (warp < 16) {
        const uint4 wk = lds128(sb + SM_DW + cq * 16);
        uint32_t sel[5] = {wk.x, wk.y, wk.z, wk.w, lds32(sb + SM_DW + 64 + cq * 4)}, sel2[5];
#pragma unroll
        for (int i = 0; i < 5; i++) {
            if (!(g & 1)) sel[i] = 0x3F803F80u;
            sel2[i] = sel[i]; PIN(sel2[i]);
        }
        const uint32_t y4 = sb + SM_XT + 128 + warp * 32 + (2 * (lane >> 3) + (lane & 1)) * YP + ((lane & 7) >> 1) * YS;
        const uint32_t y1 = sb + SM_XT + 128 + warp * 32 + (lane & 7) * YP + 4 * YS + (lane & 8) * 2 + (lane & 6) * 8;
        uint32_t ao = (256 * q + tn) * 16, hta = sb + SM_HT + tn * 80;
        PIN(ao); PIN(hta);
        mbar_wait(mb + MB_Y * 8);
        STAMP(10);
        float ca[4] = {0.f, 0.f, 0.f, 0.f}, cb[4] = {0.f, 0.f, 0.f, 0.f};
        {
            uint32_t ya[4], yb[4], yc, yd;
            ldsm4t(ya, y4); ldsm4t(yb, y4 + 16); ldsm2t(yc, yd, y1);
#pragma unroll
            for (int i = 0; i < 4; i++) { ha[i] = badd2(xa[i], ya[i]); hb[i] = badd2(xb[i], yb[i]); }
            ha[4] = badd2(xa[4], yc); hb[4] = badd2(xb[4], yd);
        }
        if (nslot != 5) {
            ha[4] = hb[4] = 0;
            if (cq >= 2) ha[0] = ha[1] = ha[2] = ha[3] = hb[0] = hb[1] = hb[2] = hb[3] = 0;
        }
#pragma unroll
        for (int i = 0; i < 5; i++) { mma_bf16_k8(ca, ha[i], sel[i], ha[i]); mma_bf16_k8(cb, hb[i], sel2[i], hb[i]); }
        if (!(g & 1)) { ca[1] = ca[0]; cb[1] = cb[0]; }
        if (cq == (g >> 1)) {
            asm volatile("red.relaxed.gpu.global.add.v4.f32 [%0], {%1,%2,%3,%4};" :: "l"((char*)g_s.acc + ao), "f"(1.0f), "f"(ca[1]), "f"(ca[2]), "f"(ca[3]) : "memory");
            asm volatile("red.relaxed.gpu.global.add.v4.f32 [%0], {%1,%2,%3,%4};" :: "l"((char*)g_s.acc + ao + 128), "f"(1.0f), "f"(cb[1]), "f"(cb[2]), "f"(cb[3]) : "memory");
        }
        sts128(hta + cq * 16, ha[0], ha[1], ha[2], ha[3]); sts32(hta + 64 + cq * 4, ha[4]);
        sts128(hta + cq * 16 + 640, hb[0], hb[1], hb[2], hb[3]); sts32(hta + 704 + cq * 4, hb[4]);
        STAMP(11);
    }
    const int kq = warp / 5, mt = warp - 5 * kq;
    const int mi = lane >> 3, mr = lane & 7;
    const unsigned tk = (unsigned)tid / 72u, ck = tid - tk * 72;
    uint32_t A[9][4];
    auto loadA = [&]() {
        mbar_wait(mb + MB_W1 * 8);
        const uint32_t aa = sb + (mi & 1) * SM_WU + (8 * (mi >> 1) + mr) * 80 + (144 * 80 * kq + mt * 16);
#pragma unroll
        for (int s = 0; s < 9; s++) ldsm4t(A[s], aa + s * 1280);
    };
    const uint32_t par = (epoch & 1) ? 0x40004000u : 0u;
    uint32_t pk0 = mapa(sb, 2 * cq), go = (ck / 5u + ck) * 16, co = ((q * 8 * NCL + c) * 6 + cq) * 16;
    PIN(pk0); PIN(go); PIN(co);
    if (warp < 8) {
        const float wsum = ldsf(sb + SM_SC + 24);
        const uint32_t idx = 2047 - (512 * ((tid >> 1) & 3) + 128 * ((tid >> 3) & 3) + 64 * (tid & 1) + 8 * q + warp);
        uint4 s; int n = 0;
        do { s = ld_rlx128(&g_s.acc[256 * q + tid]); } while (__uint_as_float(s.x) != (float)NCL && ++n < SPIN_LIMIT);
        STAMP(16);
        const uint32_t ox = __shfl_xor_sync(~0u, (lane & 1) ? s.z : s.w, 1);
        const uint32_t ms = ln_stats(__uint_as_float((lane & 1) ? ox : s.z), __uint_as_float(s.y));
        const float rs = rcpf(bf_hi(ms));
        const uint32_t rb = pack_bf16(0.f, fmaf(-bf_lo(ms), wsum, __uint_as_float((lane & 1) ? s.w : ox)) * rs);
        const uint32_t key = (((rb ^ (((int)rb >> 31) | 0x80000000u)) >> 16) << 11) | idx;
        sts32(sb + SM_KEY + tid * 4, key);
        __syncwarp();
        const uint32_t rank = rank4<8, 16>(sb + SM_KEY + warp * 128, key);
        if (rank < 8) sts32(sb + SM_CAND + warp * 32 + rank * 4, key);
        sts64(sb + SM_ST + tid * 8, ms, rsplit(rs));
    } else loadA();
    if (warp < 16) {
        STAMP(17);
        bar_sync(12, 512);
        STAMP(18);
        if (warp < 8) {
            const uint32_t mk = lds32(sb + SM_CAND + (tid >> 2) * 4);
            uint32_t rank = rank4<4, 64>(sb + SM_CAND + cq * 16, mk);
            rank += __shfl_xor_sync(~0u, rank, 1); rank += __shfl_xor_sync(~0u, rank, 2);
            if (rank < 8) {
                const uint32_t pk1 = pk0 + (mapa(sb, 1) - mapa(sb, 0));
                st_async1(pk0 + (SM_RK + q * 32) + rank * 4, mk, pk0 + (SM_MB + MB_KEY * 8));
                st_async1(pk1 + (SM_RK + q * 32) + rank * 4, mk, pk1 + (SM_MB + MB_KEY * 8));
                const uint32_t t = tslot(~mk);
                const uint2 sv = lds64(sb + SM_ST + t * 8);
                const uint4 hv = lds128(sb + SM_HT + t * 80 + cq * 16);
                const uint32_t h4 = lds32(sb + SM_HT + t * 80 + 64 + cq * 4);
                const uint32_t rr = bmul2(sv.y, 0x3C803C80u);
                char* const dp = (char*)g_s.cand + (co + rank * 1440);
                st_rlx128(dp, (norm2(hv.x, sv.x, rr) & 0xBFFFBFFFu) | par, (norm2(hv.y, sv.x, rr) & 0xBFFFBFFFu) | par,
                          (norm2(hv.z, sv.x, rr) & 0xBFFFBFFFu) | par, (norm2(hv.w, sv.x, rr) & 0xBFFFBFFFu) | par);
                asm volatile("st.relaxed.gpu.global.u32 [%0], %1;" :: "l"((char*)g_s.cand + (co + rank * 1440 + 64 - cq * 12)), "r"((norm2(h4, sv.x, rr) & 0xBFFFBFFFu) | par) : "memory");
            }
            __syncwarp();
        }
        {
            const uint2 sa = lds64(sb + SM_ST + tn * 8), sbb = lds64(sb + SM_ST + tn * 8 + 64);
#pragma unroll
            for (int i = 0; i < 5; i++) { ha[i] = badd2(ha[i], norm2(ha[i], sa.x, sa.y)); hb[i] = badd2(hb[i], norm2(hb[i], sbb.x, sbb.y)); }
            const bool hf = (c & 1) && cq == 0;
            const uint32_t o16 = sb + SM_XT + (hf ? 16384 + tn * 16 : tn * 64 + (cq - (c & 1)) * 16), o4 = sb + SM_XT + ((c & 1) ? tn * 64 + 48 : 16384 + tn * 16) + cq * 4;
            sts128(o16, ha[0], ha[1], ha[2], ha[3]); sts32(o4, ha[4]);
            sts128(o16 + (hf ? 128 : 512), hb[0], hb[1], hb[2], hb[3]); sts32(o4 + ((c & 1) ? 512 : 128), hb[4]);
        }
        if (warp >= 8) {
            STAMP(19);
            mbar_wait(mb + MB_KEY * 8);
            STAMP(20);
            const uint32_t mk = lds32(sb + SM_RK - 256 + (tid >> 2) * 4);
            uint32_t rank = rank4<4, 64>(sb + SM_RK + cq * 16, mk);
            rank += __shfl_xor_sync(~0u, rank, 1); rank += __shfl_xor_sync(~0u, rank, 2);
            if (rank < 8) sts64(sb + SM_SEL + rank * 8, mk, ((tid >> 2) - 64) * 1440);
        }
    }
    bar_sync(11, 640);
    STAMP(12);

    const char* gp = (const char*)g_s.cand + (go + lds32(sb + SM_SEL + 4 + (tk & 7) * 8));
    uint4 hv = ld_rlx128(gp);
    if (warp < 8) loadA();
    const bool red = warp < 6;
    const uint32_t ft = red ? (unsigned)tid / 24u : (unsigned)(tid >> 4) & 7u, fj = red ? 24 * q + tid - ft * 24 : d0 / 3 + (lane & 15);
    const uint32_t key = lds32(sb + SM_SEL + ft * 8), k16 = key << 5;
    float sig = bfr(rcpf(1.f + ex2f(__uint_as_float((k16 ^ (~((int)k16 >> 31) | 0x80000000u)) & 0xFFFF0000u) * -1.4426950408889634f)));
    uint32_t ra2 = sb + SM_RED2 + tid * 12 + ft * 16, fo = (ft * 192 + fj) * 16, oo = ((~key & 2047) * D_ + 3 * fj) * 2;
    uint32_t bx = sb + SM_XS + mr * 1168 + mi * 16 + 288 * kq, gd = mapa(sb, kq * (8 / NRED)) + (SM_GU + (q * nslot + mt) * 128) + lane * 4;
    PIN(ra2); PIN(fo); PIN(oo); PIN(bx); PIN(gd);
    asm volatile("" : "+f"(sig));
    {
        if (warp < 18) {
            int n = 0;
            while ((((hv.x ^ par) | (hv.y ^ par) | (hv.z ^ par) | (hv.w ^ par)) & 0x40004000u) && ++n < SPIN_LIMIT) hv = ld_rlx128(gp);
            sts128(sb + SM_XS + tk * 16 + tid * 16, hv.x ^ par, hv.y ^ par, hv.z ^ par, hv.w ^ par);
        }
    }
    bar_sync(14, 672);
    STAMP(13);
    {
        float c0[4] = {0.f, 0.f, 0.f, 0.f}, c1[4] = {0.f, 0.f, 0.f, 0.f}, c2[4] = {0.f, 0.f, 0.f, 0.f};
        uint32_t b[5][4];
#pragma unroll
        for (int s = 0; s < 4; s++) ldsm4(b[s], bx + s * 64);
        asm volatile("ldmatrix.sync.aligned.m8n8.x2.shared.b16 {%0,%1}, [%2];" : "=r"(b[4][0]), "=r"(b[4][1]) : "r"(bx + 256) : "memory");
        mma_bf16(c0, A[0][0], A[0][1], A[0][2], A[0][3], b[0][0], b[0][1]);
        mma_bf16(c1, A[1][0], A[1][1], A[1][2], A[1][3], b[0][2], b[0][3]);
        mma_bf16(c2, A[2][0], A[2][1], A[2][2], A[2][3], b[1][0], b[1][1]);
        mma_bf16(c0, A[3][0], A[3][1], A[3][2], A[3][3], b[1][2], b[1][3]);
        mma_bf16(c1, A[4][0], A[4][1], A[4][2], A[4][3], b[2][0], b[2][1]);
        mma_bf16(c2, A[5][0], A[5][1], A[5][2], A[5][3], b[2][2], b[2][3]);
        mma_bf16(c0, A[6][0], A[6][1], A[6][2], A[6][3], b[3][0], b[3][1]);
        mma_bf16(c1, A[7][0], A[7][1], A[7][2], A[7][3], b[3][2], b[3][3]);
        mma_bf16(c2, A[8][0], A[8][1], A[8][2], A[8][3], b[4][0], b[4][1]);
        sts128f(sb + SM_RED + tid * 16, c0[0] + c1[0] + c2[0], c0[1] + c1[1] + c2[1], c0[2] + c1[2] + c2[2], c0[3] + c1[3] + c2[3]);
    }
    bar_sync(1 + mt, 128);
    STAMP(21);
    if (mt < nslot && kq < NRED) {
        const uint32_t ra = sb + SM_RED + mt * 512 + lane * 16;
        const float4 p0 = lds128f(ra), p1 = lds128f(ra + 2560), p2 = lds128f(ra + 5120), p3 = lds128f(ra + 7680);
        const float g0 = bfr(((p0.x + p1.x) + (p2.x + p3.x)) * 64.f), g1 = bfr(((p0.y + p1.y) + (p2.y + p3.y)) * 64.f);
        const uint32_t sg = pack_bf16(g0 * rcpf(1.f + ex2f(g0 * -1.4426950408889634f)), g1 * rcpf(1.f + ex2f(g1 * -1.4426950408889634f)));
        const uint32_t gu = bmul2(sg, pack_bf16(((p0.z + p1.z) + (p2.z + p3.z)) * 64.f, ((p0.w + p1.w) + (p2.w + p3.w)) * 64.f));
        const uint32_t pstep = mapa(sb, 1) - mapa(sb, 0), gm = mapa(mb + MB_GU * 8, kq * (8 / NRED));
#pragma unroll
        for (int i = 0; i < 8 / NRED; i++) st_async1(gd + i * pstep, gu, gm + i * pstep);
    }
    mbar_wait(mb + MB_W2 * 8);
    {
        const uint32_t aa = sb + (8 * (mi >> 1) + mr) * (2 * W2W) + (mi & 1) * 16 + (SM_FAR + 32 * W2W * kq + mt * 32 + (W2W == 72 ? 0 : (q & 1) * 16));
#pragma unroll
        for (int s = 0; s < 5; s++) ldsm4t(A[s], aa + s * FAR_SZ);
    }
    {
        uint32_t ba = sb + (SM_GU + 256 * kq) + (lane & 15) * 16 + (lane >> 4) * 1024, wa = sb + (SM_RED2 + kq * 2432 + mt * 64) + g * 4 + cq * 608;
        PIN(ba); PIN(wa);
        STAMP(22);
        mbar_wait(mb + MB_GU * 8);
        STAMP(23);
        float c0[4] = {0.f, 0.f, 0.f, 0.f}, c1[4] = {0.f, 0.f, 0.f, 0.f}, c2[4] = {0.f, 0.f, 0.f, 0.f};
        uint32_t b[2][4], b8, b9;
        ldsm4t(b[0], ba); ldsm4t(b[1], ba + 2048); ldsm2t(b8, b9, ba + 4096);
        mma_bf16(c0, A[0][0], A[0][1], A[0][2], A[0][3], b[0][0], b[0][1]);
        mma_bf16(c1, A[1][0], A[1][1], A[1][2], A[1][3], b[0][2], b[0][3]);
        if (nslot == 5) {
            mma_bf16(c2, A[4][0], A[4][1], A[4][2], A[4][3], b8, b9);
            mma_bf16(c0, A[2][0], A[2][1], A[2][2], A[2][3], b[1][0], b[1][1]);
            mma_bf16(c1, A[3][0], A[3][1], A[3][2], A[3][3], b[1][2], b[1][3]);
        }
        stsf(wa, c0[0] + c1[0] + c2[0]); stsf(wa + 304, c0[1] + c1[1] + c2[1]);
        if (mt < 4) { stsf(wa + 32, c0[2] + c1[2] + c2[2]); stsf(wa + 336, c0[3] + c1[3] + c2[3]); }
    }
    if (warp < 10) {
        float v[3], cnt = 3.f;
        if (red) {
            bar_sync(6, 640);
            STAMP(14);
#pragma unroll
            for (int i = 0; i < 3; i++) v[i] = ((ldsf(ra2 + i * 4) + ldsf(ra2 + i * 4 + 2432)) + (ldsf(ra2 + i * 4 + 4864) + ldsf(ra2 + i * 4 + 7296))) * sig;
        } else {
            bar_arrive(6, 640);
            cnt = 0.f;
#pragma unroll
            for (int i = 0; i < 3; i++) {
                const uint32_t cl = 3 * fj + i - d0;
                const bool ok = cl < 8 * nslot && ((~key >> 3) & 7) == q;
                const uint32_t cf = cl - (c & 1) * 8;
                v[i] = ok ? __uint_as_float(lds16(sb + SM_XT + (cf < 32 ? tslot(~key) * 64 + cf * 2 : 16384 + tslot(~key) * 16 + (cl & 7) * 2)) << 16) : 0.f;
                if (ok) cnt += 1.f;
            }
            mbar_wait(mb + MB_OUT * 8);
        }
        if (cnt != 0.f) {
            float x, y, z, w;
            asm volatile("atom.relaxed.gpu.global.add.v4.f32 {%0,%1,%2,%3}, [%4], {%5,%6,%7,%8};" : "=f"(x), "=f"(y), "=f"(z), "=f"(w)
                         : "l"((char*)g_s.fin + fo), "f"(v[0]), "f"(v[1]), "f"(v[2]), "f"(cnt) : "memory");
            if (w + cnt == 3.f * (NCL + 1)) {
                __nv_bfloat16* op = (__nv_bfloat16*)((char*)prm.out + oo);
                op[0] = __float2bfloat16(x + v[0]); op[1] = __float2bfloat16(y + v[1]); op[2] = __float2bfloat16(z + v[2]);
            }
        }
    } else bar_arrive(6, 640);
    STAMP(15);
}

typedef CUresult (*EncodeFn)(CUtensorMap*, CUtensorMapDataType, cuuint32_t, void*, const cuuint64_t*, const cuuint64_t*,
                             const cuuint32_t*, const cuuint32_t*, CUtensorMapInterleave, CUtensorMapSwizzle,
                             CUtensorMapL2promotion, CUtensorMapFloatOOBfill);

void make_map(EncodeFn fn, CUtensorMap* tm, const void* p, int cols, int rows, int bc, int br) {
    cuuint64_t dims[2] = {(cuuint64_t)cols, (cuuint64_t)rows};
    cuuint64_t strides[1] = {(cuuint64_t)cols * 2};
    cuuint32_t box[2] = {(cuuint32_t)bc, (cuuint32_t)br};
    cuuint32_t es[2] = {1, 1};
    fn(tm, CU_TENSOR_MAP_DATA_TYPE_BFLOAT16, 2, const_cast<void*>(p), dims, strides, box, es, CU_TENSOR_MAP_INTERLEAVE_NONE,
       CU_TENSOR_MAP_SWIZZLE_NONE, CU_TENSOR_MAP_L2_PROMOTION_L2_128B, CU_TENSOR_MAP_FLOAT_OOB_FILL_NONE);
}

void make_map3(EncodeFn fn, CUtensorMap* tm, const void* p) {
    cuuint64_t dims[3] = {(cuuint64_t)D_, 64, 32};
    cuuint64_t strides[2] = {(cuuint64_t)D_ * 2, (cuuint64_t)D_ * 128};
    cuuint32_t box[3] = {XW, 8, 32};
    cuuint32_t es[3] = {1, 1, 1};
    fn(tm, CU_TENSOR_MAP_DATA_TYPE_BFLOAT16, 3, const_cast<void*>(p), dims, strides, box, es, CU_TENSOR_MAP_INTERLEAVE_NONE,
       CU_TENSOR_MAP_SWIZZLE_NONE, CU_TENSOR_MAP_L2_PROMOTION_NONE, CU_TENSOR_MAP_FLOAT_OOB_FILL_NONE);
}

void make_map5(EncodeFn fn, CUtensorMap* tm, const void* p, int bc) {
    cuuint64_t dims[5] = {(cuuint64_t)D_, 2, 4, 4, 64};
    cuuint64_t strides[4] = {(cuuint64_t)D_ * 128, (cuuint64_t)D_ * 1024, (cuuint64_t)D_ * 256, (cuuint64_t)D_ * 2};
    cuuint32_t box[5] = {(cuuint32_t)bc, 2, 4, 4, 8};
    cuuint32_t es[5] = {1, 1, 1, 1, 1};
    fn(tm, CU_TENSOR_MAP_DATA_TYPE_BFLOAT16, 5, const_cast<void*>(p), dims, strides, box, es, CU_TENSOR_MAP_INTERLEAVE_NONE,
       CU_TENSOR_MAP_SWIZZLE_NONE, CU_TENSOR_MAP_L2_PROMOTION_NONE, CU_TENSOR_MAP_FLOAT_OOB_FILL_NONE);
}

}

extern "C" void kernel_launch(void* const* d_in, const int* in_sizes, int n_in, void* d_out, int out_size) {
    (void)in_sizes; (void)n_in; (void)out_size;
    void* fp = nullptr;
    cudaDriverEntryPointQueryResult qr;
    cudaGetDriverEntryPoint("cuTensorMapEncodeTiled", &fp, cudaEnableDefault, &qr);
    EncodeFn fn = (EncodeFn)fp;
    CUtensorMap tmG, tmU, tmD, tmO, tmX, tmH;
    make_map3(fn, &tmX, d_in[0]);
    make_map(fn, &tmG, d_in[11], F_, D_, 40, 48);
    make_map(fn, &tmU, d_in[12], F_, D_, 40, 48);
    make_map(fn, &tmD, d_in[13], D_, F_, W2W, 64);
    make_map5(fn, &tmO, d_out, 32);
    make_map5(fn, &tmH, d_out, 8);
    Params p;
    p.x = (const unsigned short*)d_in[0];
    for (int i = 0; i < 6; i++) p.prm6[i] = (const unsigned short*)d_in[1 + i];
    p.logdt = (const unsigned short*)d_in[7]; p.dskip = (const unsigned short*)d_in[8];
    p.wr = (const unsigned short*)d_in[10];
    p.out = (__nv_bfloat16*)d_out;
    p.zero = 0;
    cudaGetSymbolAddress((void**)&p.gs, g_s);
    cudaFuncSetAttribute(fused_kernel, cudaFuncAttributeMaxDynamicSharedMemorySize, SM_TOTAL);
    fused_kernel<<<NCTA, NTHR, SM_TOTAL>>>(p, tmG, tmU, tmD, tmO, tmX, tmH);
}
```

```cpp
#include <cuda_runtime.h>
#include <cuda_bf16.h>
#include <cuda_fp16.h>
#include <cuda.h>
#include <stdint.h>

namespace {

constexpr int L_ = 2048, D_ = 576, F_ = 4608;
constexpr int NCL = 15, CS = 8, NCTA = NCL * CS, NTHR = 768;
#define W2W 72
#define XW 48
#define TILE_NS -1
#define XROT 0
#define LNPOS 1
#define MMPOS 0
#define XSPLIT 3
constexpr int NRED = 2;
constexpr int SPIN_LIMIT = 1 << 22;

constexpr int SM_WG   = 0;
constexpr int SM_WU   = 46080;
constexpr int YP = 3392, YS = 656;
constexpr int UP = 3280, US = 656;
constexpr int SM_XT   = 92160;
constexpr int SM_U    = SM_XT + 8 * YP;
constexpr int SM_FAR  = SM_U + 8 * UP;
constexpr int FAR_SZ  = 12416;
constexpr int F_E5 = 0, F_O5 = 1536, F_E3 = 3088, F_O3 = 4624, F_E7 = 6176, F_E2 = F_E7 + 1024, F_E9 = F_E7 + 2048,
              F_H = 3088, F_O7 = F_E7 + F_H, F_O2 = F_E2 + F_H, F_O9 = F_E9 + F_H;
constexpr int SM_P    = SM_FAR + 5 * FAR_SZ;
constexpr int PN_SZ = 584 * 4, SM_PN = SM_P + 64 * 4;
constexpr int P_GS = 48 * 4, P_H7 = 192 * 4, P_HS = 72 * 4;
constexpr int PF_SZ = (192 + 216) * 4, SM_PF = SM_PN + 5 * PN_SZ + 32;
constexpr int SM_MISC = SM_PF + 5 * PF_SZ;
constexpr int SM_ST   = SM_MISC;
constexpr int SM_RK   = SM_ST + 2048;
constexpr int SM_SEL  = SM_RK + 256;
constexpr int SM_KG   = SM_SEL + 64;
constexpr int SM_SC   = SM_KG + 160;
constexpr int SM_DW   = SM_SC + 32;
constexpr int SM_MB   = SM_DW + 160;
constexpr int SM_TOTAL = SM_MB + 128;
constexpr int SM_ROW  = SM_XT - 20736;
constexpr int SM_XTL  = SM_ROW - 512 * XW;
constexpr int SM_RED2 = SM_WG;
constexpr int SM_HT   = SM_P - 512;
constexpr int SM_KEY  = SM_FAR + 10240 + 128;
constexpr int SM_CAND = SM_KEY + 1024;
constexpr int SM_XS   = SM_U;
constexpr int SM_GU   = SM_XS + 9344;
constexpr int SM_RED  = SM_GU + 5632;
static_assert(F_O9 + 1024 <= FAR_SZ && FAR_SZ % 128 == 0, "far overflow");
static_assert(SM_RED + 10240 <= SM_FAR && SM_HT + 20496 <= SM_MISC, "alias overflow");
static_assert(SM_TOTAL <= 232448, "smem overflow");
static_assert(SM_FAR % 128 == 0 && SM_XT % 128 == 0 && SM_XTL % 128 == 0 && SM_P % 16 == 0 && SM_MISC % 16 == 0 && SM_MB % 8 == 0, "align");

enum { MB_X = 0, MB_W1 = 5, MB_W2 = 6, MB_KEY = 7, MB_GU = 8, MB_Y = 9, MB_OUT = 10, MB_T = 11, MB_R = 12 };

struct __align__(128) Scratch {
    unsigned epoch, zcnt, pad[30];
    uint4  st1[L_ * 2];
    float4 acc[L_];
    uint4  cand[64 * NCL * 6];
    float4 fin[8 * 192 + 24];
};
__device__ Scratch g_s;
#define STAMP(i)

__device__ __forceinline__ uint32_t mapa(uint32_t a, uint32_t r) { uint32_t d; asm("mapa.shared::cluster.u32 %0, %1, %2;" : "=r"(d) : "r"(a), "r"(r)); return d; }
__device__ __forceinline__ void mbar_wait(uint32_t mb) {
    asm volatile("{ .reg .pred p, q; .reg .u32 n; mov.u32 n, 0;\n"
                 "W_%=: mbarrier.try_wait.parity.shared::cta.b64 p, [%0], 0; add.u32 n, n, 1; setp.lt.and.u32 q, n, 65536, !p; @q bra W_%=; }" :: "r"(mb) : "memory");
}
__device__ __forceinline__ void arm(uint32_t mb, uint32_t bytes) { asm volatile("mbarrier.arrive.expect_tx.shared::cta.b64 _, [%0], %1;" :: "r"(mb), "r"(bytes) : "memory"); }
__device__ __forceinline__ void bar_sync(int id, int n) { asm volatile("bar.sync %0, %1;" :: "r"(id), "r"(n) : "memory"); }
__device__ __forceinline__ void bar_arrive(int id, int n) { asm volatile("bar.arrive %0, %1;" :: "r"(id), "r"(n) : "memory"); }
__device__ __forceinline__ uint32_t lds16(uint32_t a) { unsigned short v; asm volatile("ld.shared.u16 %0, [%1];" : "=h"(v) : "r"(a) : "memory"); return v; }
__device__ __forceinline__ uint32_t lds32(uint32_t a) { uint32_t v; asm volatile("ld.shared.u32 %0, [%1];" : "=r"(v) : "r"(a) : "memory"); return v; }
__device__ __forceinline__ uint2 lds64(uint32_t a) { uint2 v; asm volatile("ld.shared.v2.u32 {%0,%1}, [%2];" : "=r"(v.x), "=r"(v.y) : "r"(a) : "memory"); return v; }
__device__ __forceinline__ float ldsf(uint32_t a) { float v; asm volatile("ld.shared.f32 %0, [%1];" : "=f"(v) : "r"(a) : "memory"); return v; }
__device__ __forceinline__ uint4 lds128(uint32_t a) { uint4 v; asm volatile("ld.shared.v4.u32 {%0,%1,%2,%3}, [%4];" : "=r"(v.x), "=r"(v.y), "=r"(v.z), "=r"(v.w) : "r"(a) : "memory"); return v; }
__device__ __forceinline__ float4 lds128f(uint32_t a) { float4 v; asm volatile("ld.shared.v4.f32 {%0,%1,%2,%3}, [%4];" : "=f"(v.x), "=f"(v.y), "=f"(v.z), "=f"(v.w) : "r"(a) : "memory"); return v; }
__device__ __forceinline__ void sts16(uint32_t a, uint32_t v) { asm volatile("{ .reg .b16 l, h; mov.b32 {l, h}, %1; st.shared.b16 [%0], l; }" :: "r"(a), "r"(v) : "memory"); }
__device__ __forceinline__ void sts32(uint32_t a, uint32_t v) { asm volatile("st.shared.u32 [%0], %1;" :: "r"(a), "r"(v) : "memory"); }
__device__ __forceinline__ void sts64(uint32_t a, uint32_t x, uint32_t y) { asm volatile("st.shared.v2.u32 [%0], {%1,%2};" :: "r"(a), "r"(x), "r"(y) : "memory"); }
__device__ __forceinline__ void stsf(uint32_t a, float v) { asm volatile("st.shared.f32 [%0], %1;" :: "r"(a), "f"(v) : "memory"); }
__device__ __forceinline__ void sts128(uint32_t a, uint32_t x, uint32_t y, uint32_t z, uint32_t w) { asm volatile("st.shared.v4.u32 [%0], {%1,%2,%3,%4};" :: "r"(a), "r"(x), "r"(y), "r"(z), "r"(w) : "memory"); }
__device__ __forceinline__ void sts128f(uint32_t a, float x, float y, float z, float w) { asm volatile("st.shared.v4.f32 [%0], {%1,%2,%3,%4};" :: "r"(a), "f"(x), "f"(y), "f"(z), "f"(w) : "memory"); }
__device__ __forceinline__ void ldsm4(uint32_t (&r)[4], uint32_t a) { asm volatile("ldmatrix.sync.aligned.m8n8.x4.shared.b16 {%0,%1,%2,%3}, [%4];" : "=r"(r[0]), "=r"(r[1]), "=r"(r[2]), "=r"(r[3]) : "r"(a) : "memory"); }
__device__ __forceinline__ void ldsm4t(uint32_t (&r)[4], uint32_t a) { asm volatile("ldmatrix.sync.aligned.m8n8.x4.trans.shared.b16 {%0,%1,%2,%3}, [%4];" : "=r"(r[0]), "=r"(r[1]), "=r"(r[2]), "=r"(r[3]) : "r"(a) : "memory"); }
__device__ __forceinline__ void ldsm2t(uint32_t& r0, uint32_t& r1, uint32_t a) { asm volatile("ldmatrix.sync.aligned.m8n8.x2.trans.shared.b16 {%0,%1}, [%2];" : "=r"(r0), "=r"(r1) : "r"(a) : "memory"); }
__device__ __forceinline__ void stsm4t(uint32_t a, uint32_t r0, uint32_t r1, uint32_t r2, uint32_t r3) { asm volatile("stmatrix.sync.aligned.m8n8.x4.trans.shared.b16 [%0], {%1,%2,%3,%4};" :: "r"(a), "r"(r0), "r"(r1), "r"(r2), "r"(r3) : "memory"); }
__device__ __forceinline__ void stsm4(uint32_t a, uint32_t r0, uint32_t r1, uint32_t r2, uint32_t r3) { asm volatile("stmatrix.sync.aligned.m8n8.x4.shared.b16 [%0], {%1,%2,%3,%4};" :: "r"(a), "r"(r0), "r"(r1), "r"(r2), "r"(r3) : "memory"); }
__device__ __forceinline__ void stsm2t(uint32_t a, uint32_t r0, uint32_t r1) { asm volatile("stmatrix.sync.aligned.m8n8.x2.trans.shared.b16 [%0], {%1,%2};" :: "r"(a), "r"(r0), "r"(r1) : "memory"); }
__device__ __forceinline__ uint4 ldg128(const void* p) { uint4 v; asm volatile("ld.global.nc.v4.u32 {%0,%1,%2,%3}, [%4];" : "=r"(v.x), "=r"(v.y), "=r"(v.z), "=r"(v.w) : "l"(p)); return v; }
__device__ __forceinline__ uint32_t ldg16(const void* p) { unsigned short v; asm volatile("ld.global.nc.u16 %0, [%1];" : "=h"(v) : "l"(p)); return v; }
__device__ __forceinline__ uint32_t opaque(uint32_t v) { uint32_t r; asm volatile("mov.b32 %0, %1;" : "=r"(r) : "r"(v)); return r; }
__device__ __forceinline__ void mma_f16(float (&d)[4], const uint32_t (&a)[4], uint32_t b0, uint32_t b1) {
    asm volatile("mma.sync.aligned.m16n8k16.row.col.f32.f16.f16.f32 {%0,%1,%2,%3}, {%4,%5,%6,%7}, {%8,%9}, {%0,%1,%2,%3};"
        : "+f"(d[0]), "+f"(d[1]), "+f"(d[2]), "+f"(d[3]) : "r"(a[0]), "r"(a[1]), "r"(a[2]), "r"(a[3]), "r"(b0), "r"(b1));
}
__device__ __forceinline__ void mma_bf16(float (&d)[4], uint32_t a0, uint32_t a1, uint32_t a2, uint32_t a3, uint32_t b0, uint32_t b1) {
    asm volatile("mma.sync.aligned.m16n8k16.row.col.f32.bf16.bf16.f32 {%0,%1,%2,%3}, {%4,%5,%6,%7}, {%8,%9}, {%0,%1,%2,%3};"
        : "+f"(d[0]), "+f"(d[1]), "+f"(d[2]), "+f"(d[3]) : "r"(a0), "r"(a1), "r"(a2), "r"(a3), "r"(b0), "r"(b1));
}
__device__ __forceinline__ void mma_bf16_k8(float (&d)[4], uint32_t a0, uint32_t a1, uint32_t b0) {
    asm volatile("mma.sync.aligned.m16n8k8.row.col.f32.bf16.bf16.f32 {%0,%1,%2,%3}, {%4,%5}, {%6}, {%0,%1,%2,%3};"
        : "+f"(d[0]), "+f"(d[1]), "+f"(d[2]), "+f"(d[3]) : "r"(a0), "r"(a1), "r"(b0));
}
__device__ __forceinline__ uint32_t pack_f16(float lo, float hi) { uint32_t r; asm("cvt.rn.f16x2.f32 %0, %1, %2;" : "=r"(r) : "f"(hi), "f"(lo)); return r; }
__device__ __forceinline__ uint32_t pack_bf16(float lo, float hi) { uint32_t r; asm("cvt.rn.bf16x2.f32 %0, %1, %2;" : "=r"(r) : "f"(hi), "f"(lo)); return r; }
__device__ __forceinline__ float bf_lo(uint32_t v) { return __uint_as_float(v << 16); }
__device__ __forceinline__ float bf_hi(uint32_t v) { return __uint_as_float(v & 0xFFFF0000u); }
__device__ __forceinline__ float bfr(float x) { return __uint_as_float(pack_bf16(0.f, x)); }
__device__ __forceinline__ uint32_t badd2(uint32_t a, uint32_t b) { uint32_t r; asm("add.rn.bf16x2 %0, %1, %2;" : "=r"(r) : "r"(a), "r"(b)); return r; }
__device__ __forceinline__ uint32_t bmul2(uint32_t a, uint32_t b) { uint32_t r; asm("mul.rn.bf16x2 %0, %1, %2;" : "=r"(r) : "r"(a), "r"(b)); return r; }
__device__ __forceinline__ uint32_t hadd2(uint32_t a, uint32_t b) { uint32_t r; asm("add.rn.f16x2 %0, %1, %2;" : "=r"(r) : "r"(a), "r"(b)); return r; }
__device__ __forceinline__ uint32_t hmul2(uint32_t a, uint32_t b) { uint32_t r; asm("mul.rn.f16x2 %0, %1, %2;" : "=r"(r) : "r"(a), "r"(b)); return r; }
__device__ __forceinline__ uint32_t hfma2(uint32_t a, uint32_t b, uint32_t c) { uint32_t r; asm("fma.rn.f16x2 %0, %1, %2, %3;" : "=r"(r) : "r"(a), "r"(b), "r"(c)); return r; }
__device__ __forceinline__ uint32_t hneg2(uint32_t a) { uint32_t r; asm("neg.f16x2 %0, %1;" : "=r"(r) : "r"(a)); return r; }
__device__ __forceinline__ float rcpf(float x) { float r; asm("rcp.approx.ftz.f32 %0, %1;" : "=f"(r) : "f"(x)); return r; }
__device__ __forceinline__ float sqrta(float x) { float r; asm("sqrt.approx.ftz.f32 %0, %1;" : "=f"(r) : "f"(x)); return r; }
__device__ __forceinline__ float ex2f(float x) { float r; asm("ex2.approx.ftz.f32 %0, %1;" : "=f"(r) : "f"(x)); return r; }
__device__ __forceinline__ void st_async4(uint32_t a, uint32_t x, uint32_t y, uint32_t z, uint32_t w, uint32_t mb) {
    asm volatile("st.async.shared::cluster.mbarrier::complete_tx::bytes.v4.u32 [%0], {%1,%2,%3,%4}, [%5];" :: "r"(a), "r"(x), "r"(y), "r"(z), "r"(w), "r"(mb) : "memory"); }
__device__ __forceinline__ void st_async1(uint32_t a, uint32_t x, uint32_t mb) {
    asm volatile("st.async.shared::cluster.mbarrier::complete_tx::bytes.u32 [%0], %1, [%2];" :: "r"(a), "r"(x), "r"(mb) : "memory"); }
__device__ __forceinline__ unsigned ld_rlx(const void* p) { unsigned v; asm volatile("ld.relaxed.gpu.global.u32 %0, [%1];" : "=r"(v) : "l"(p) : "memory"); return v; }
__device__ __forceinline__ unsigned ld_acq(const void* p) { unsigned v; asm volatile("ld.acquire.gpu.global.u32 %0, [%1];" : "=r"(v) : "l"(p) : "memory"); return v; }
__device__ __forceinline__ uint2 ld_rlx64(const void* p) { unsigned long long v; asm volatile("ld.relaxed.gpu.global.u64 %0, [%1];" : "=l"(v) : "l"(p) : "memory"); return make_uint2((unsigned)v, (unsigned)(v >> 32)); }
__device__ __forceinline__ void st_rlx128(void* p, uint32_t x, uint32_t y, uint32_t z, uint32_t w) {
    asm volatile("st.relaxed.gpu.global.v2.u64 [%0], {%1,%2};" :: "l"(p), "l"((unsigned long long)x | ((unsigned long long)y << 32)), "l"((unsigned long long)z | ((unsigned long long)w << 32)) : "memory"); }
__device__ __forceinline__ uint4 ld_rlx128(const void* p) { unsigned long long a, b; asm volatile("ld.relaxed.gpu.global.v2.u64 {%0,%1}, [%2];" : "=l"(a), "=l"(b) : "l"(p) : "memory"); return make_uint4((unsigned)a, (unsigned)(a >> 32), (unsigned)b, (unsigned)(b >> 32)); }
__device__ __forceinline__ void tma2d(uint32_t dst, const CUtensorMap* tm, int x, int y, uint32_t mb) {
    asm volatile("cp.async.bulk.tensor.2d.shared::cluster.global.mbarrier::complete_tx::bytes [%0], [%1, {%3, %4}], [%2];"
                 :: "r"(dst), "l"(tm), "r"(mb), "r"(x), "r"(y) : "memory");
}
__device__ __forceinline__ void cmul(float& xr, float& xi, float ar, float ai, float br, float bi) {
    const float r = fmaf(ar, br, -ai * bi), i = fmaf(ar, bi, ai * br); xr = r; xi = i;
}
__device__ __forceinline__ void csq(float& xr, float& xi, float ar, float ai) {
    const float r = fmaf(ar, ar, -ai * ai), i = (ar + ar) * ai; xr = r; xi = i;
}
__device__ __forceinline__ void cexp_s(float& zr, float& zi, float e2, float turns) {
    const float mag = ex2f(e2), r = (turns - rintf(turns)) * 6.283185307179586f;
    zr = mag * __cosf(r); zi = mag * __sinf(r);
}
__device__ __forceinline__ uint32_t ln_stats(float s1, float s2) {
    const float m = s1 * (1.f / D_);
    const float var = fmaxf(fmaf(s2, 1.f / D_, -m * m), 0.f);
    return pack_bf16(m, sqrta(bfr(bfr(var) + 1e-5f)));
}
__device__ __forceinline__ uint32_t rsplit(float rs) { const float h = bfr(rs); return pack_bf16(h, rs - h); }
__device__ __forceinline__ uint32_t norm2(uint32_t v, uint32_t mx, uint32_t hl) {
    uint32_t r;
    asm("{ .reg .b16 m, h, l, x; .reg .b32 m2, h2, l2, d, t; mov.b32 {m, x}, %2; mov.b32 {h, l}, %3; mov.b32 m2, {m, m}; mov.b32 h2, {h, h}; mov.b32 l2, {l, l};\n"
        "sub.rn.bf16x2 d, %1, m2; mul.rn.bf16x2 t, d, l2; fma.rn.bf16x2 %0, d, h2, t; }" : "=r"(r) : "r"(v), "r"(mx), "r"(hl));
    return r;
}
template <int N, int S>
__device__ __forceinline__ uint32_t rank4(uint32_t a, uint32_t key) {
    uint32_t r0 = 0, r1 = 0, r2 = 0, r3 = 0;
#pragma unroll
    for (int i = 0; i < N; i++) {
        const uint4 o = lds128(a + i * S);
        r0 += (key - o.x) >> 31; r1 += (key - o.y) >> 31; r2 += (key - o.z) >> 31; r3 += (key - o.w) >> 31;
    }
    return (r0 + r1) + (r2 + r3);
}
typedef uint32_t H2C;
__device__ __forceinline__ H2C splat(float r, float i) { return pack_f16(r, i); }
__device__ __forceinline__ void hcmul(uint32_t& xr, uint32_t& xi, uint32_t R, uint32_t I, H2C m) {
    asm("{ .reg .b16 a, b; .reg .b32 a2, b2, t; mov.b32 {a, b}, %4; mov.b32 a2, {a, a}; mov.b32 b2, {b, b};\n"
        "mul.rn.f16x2 t, %3, b2; neg.f16x2 t, t; fma.rn.f16x2 %0, %2, a2, t; mul.rn.f16x2 t, %3, a2; fma.rn.f16x2 %1, %2, b2, t; }"
        : "=&r"(xr), "=r"(xi) : "r"(R), "r"(I), "r"(m));
}
__device__ __forceinline__ void expand4(uint32_t are, uint32_t aim, uint32_t R0, uint32_t R1, uint32_t I0, uint32_t I1, H2C m4) {
    uint32_t R2, I2, R3, I3;
    hcmul(R2, I2, R0, I0, m4); hcmul(R3, I3, R1, I1, m4);
    sts128(are, R0, R1, R2, R3);
    sts128(aim, I0, I1, I2, I3);
}
__device__ __forceinline__ void expand8(uint32_t are, uint32_t aim, float sr, float si, float m1r, float m1i, float m2r, float m2i, H2C m4) {
    float r1, i1, r2, i2, r3, i3;
    cmul(r1, i1, sr, si, m1r, m1i); cmul(r2, i2, sr, si, m2r, m2i); cmul(r3, i3, r1, i1, m2r, m2i);
    expand4(are, aim, pack_f16(sr, r1), pack_f16(r2, r3), pack_f16(si, i1), pack_f16(i2, i3), m4);
}
__device__ __forceinline__ void put16(uint32_t a, uint32_t v) { sts16(a, v); sts16(a + 6, v); }

struct Params {
    const unsigned short *x, *prm6[6], *logdt, *dskip, *wr;
    __nv_bfloat16* out;
    Scratch* gs;
    unsigned zero;
};
__device__ __forceinline__ uint32_t tslot(uint32_t t) { return (t & 7) * 32 + ((t >> 4) & 24) + ((t >> 8) & 6) + ((t >> 6) & 1); }
#define CP(x) ((x) | zero)
#define PIN(x) asm volatile("or.b32 %0, %0, %1;" : "+r"(x) : "r"(zero))
__device__ __forceinline__ void wgmma32(float (&d)[4][4], const uint32_t (&a)[4], uint32_t dlo) {
    asm volatile("{ .reg .b64 ds; mov.b64 ds, {%20, %21};\n"
                 "wgmma.mma_async.sync.aligned.m64n32k16.f32.f16.f16 {%0,%1,%2,%3,%4,%5,%6,%7,%8,%9,%10,%11,%12,%13,%14,%15}, {%16,%17,%18,%19}, ds, 1, 1, 1, 0; }"
        : "+f"(d[0][0]), "+f"(d[0][1]), "+f"(d[0][2]), "+f"(d[0][3]), "+f"(d[1][0]), "+f"(d[1][1]), "+f"(d[1][2]), "+f"(d[1][3]),
          "+f"(d[2][0]), "+f"(d[2][1]), "+f"(d[2][2]), "+f"(d[2][3]), "+f"(d[3][0]), "+f"(d[3][1]), "+f"(d[3][2]), "+f"(d[3][3])
        : "r"(a[0]), "r"(a[1]), "r"(a[2]), "r"(a[3]), "r"(dlo), "n"(128 >> 4));
}

__global__ void __cluster_dims__(CS, 1, 1) __launch_bounds__(NTHR, 1)
fused_kernel(const __grid_constant__ Params prm, const __grid_constant__ CUtensorMap tmG, const __grid_constant__ CUtensorMap tmU,
             const __grid_constant__ CUtensorMap tmD, const __grid_constant__ CUtensorMap tmO, const __grid_constant__ CUtensorMap tmX, const __grid_constant__ CUtensorMap tmH)
{
    extern __shared__ __align__(1024) unsigned char smem[];
    const int tid = threadIdx.x, lane = tid & 31, warp = __shfl_sync(~0u, tid >> 5, 0);
    const int c = blockIdx.x >> 3, q = blockIdx.x & 7;
    const int nslot = (c < NCL - 1) ? 5 : 2;
    const int d0 = 40 * c;
    const uint32_t sb = opaque((uint32_t)__cvta_generic_to_shared(smem));
    const uint32_t mb = sb + SM_MB;
    Scratch& g_s = *prm.gs;
    const unsigned& zero = prm.zero;
    STAMP(0);

    if (warp >= 20) {
        unsigned epoch = 0;
        if (warp == 20) {
            if (lane == 0) {
#pragma unroll
                for (int i = 0; i < 13; i++)
                    asm volatile("mbarrier.init.shared::cta.b64 [%0], %1;" :: "r"(mb + i * 8), "r"((i == MB_R || i < 2) ? 2 : i == MB_Y ? 1 + 4 * nslot : 1) : "memory");
                asm volatile("fence.mbarrier_init.release.cluster;" ::: "memory");
                arm(mb + MB_W1 * 8, 92160); arm(mb + MB_W2 * 8, nslot * (128 * W2W)); arm(mb + MB_KEY * 8, 256); arm(mb + MB_GU * 8, nslot * 1024); arm(mb + MB_T * 8, 512 * XW);
                const int bytes = max(min(18, L_ - 18 * (int)blockIdx.x), 1) * (D_ * 2);
                arm(mb + MB_R * 8, bytes);
            }
            __syncwarp();
        } else if (warp == 22) {
            epoch = ld_rlx(&g_s.epoch);
            if (lane < 18 ? 18 * c + lane < 256 : lane < 31) (lane < 18 ? &g_s.acc[256 * q + 18 * c] : &g_s.fin[13 * (int)blockIdx.x - 18])[lane] = make_float4(0.f, 0.f, 0.f, 0.f);
        } else if (warp == 23 && lane == 0) asm volatile("prefetch.tensormap [%0];" :: "l"(&tmX) : "memory");
        asm volatile("barrier.cluster.arrive.relaxed.aligned;" ::: "memory");
        bar_sync(12, NTHR);
        if (warp == 22) {
            if (lane == 0) { sts32(sb + SM_SC + 28, epoch); asm volatile("mbarrier.arrive.shared::cta.b64 _, [%0];" :: "r"(mb + MB_R * 8) : "memory"); }
            epoch++;
            asm volatile("fence.acq_rel.gpu;" ::: "memory");
            __syncwarp();
            if (lane == 0) asm volatile("red.relaxed.gpu.global.add.u32 [%0], 1;" :: "l"(&g_s.zcnt) : "memory");
            STAMP(1);
            uint4 wv = make_uint4(0, 0, 0, 0), wv2 = ldg128((const uint4*)prm.wr + lane), wv3 = ldg128((const uint4*)prm.wr + 32 + lane);
            if (lane < 8) wv = ldg128((const uint4*)prm.wr + 64 + lane);
            if (lane < 5) {
                uint4 v = make_uint4(0, 0, 0, 0);
                if (lane < nslot) v = ldg128((const uint4*)(prm.wr + d0) + lane);
                sts128(sb + SM_DW + lane * 16, v.x, v.y, v.z, v.w);
            }
            __syncwarp();
            if (lane < 2) asm volatile("mbarrier.arrive.shared::cta.b64 _, [%0];" :: "r"(mb + (MB_X + lane) * 8) : "memory");
            mbar_wait(mb + (MB_X + 1) * 8);
            const uint32_t old = (epoch & 1) ? 0u : 0x40004000u;
#pragma unroll
            for (int t = 0; t < 2; t++)
                if ((lane & 7) < 6) g_s.cand[((q * 8 + 4 * t + (lane >> 3)) * NCL + c) * 6 + (lane & 7)] = make_uint4(old, old, old, old);
            float a[4] = {0.f, 0.f, 0.f, 0.f};
            const uint32_t one = 0x3F803F80u;
            mma_bf16(a, one, one, one, one, wv.x, wv.y);  mma_bf16(a, one, one, one, one, wv.z, wv.w);
            mma_bf16(a, one, one, one, one, wv2.x, wv2.y); mma_bf16(a, one, one, one, one, wv2.z, wv2.w);
            mma_bf16(a, one, one, one, one, wv3.x, wv3.y); mma_bf16(a, one, one, one, one, wv3.z, wv3.w);
            float s = a[0] + a[1];
            s += __shfl_xor_sync(~0u, s, 1); s += __shfl_xor_sync(~0u, s, 2);
            stsf(sb + SM_SC + 24, s);
            __syncwarp();
            if (lane == 0) {
                int n = 0;
                while ((int)(ld_acq(&g_s.zcnt) - epoch * NCTA) < 0 && ++n < SPIN_LIMIT) __nanosleep(200);
                arm(mb + MB_Y * 8, 8 * 512 * nslot);
                if (blockIdx.x == 0) g_s.epoch = epoch;
            }
            STAMP(2);
            return;
        }
        if (warp == 21) {
            if (lane == 0) { asm volatile("prefetch.tensormap [%0];" :: "l"(&tmG) : "memory"); asm volatile("prefetch.tensormap [%0];" :: "l"(&tmU) : "memory"); asm volatile("prefetch.tensormap [%0];" :: "l"(&tmD) : "memory"); }
            __syncwarp();
            bar_sync(13, 736);
            asm volatile("fence.proxy.async.shared::cta;" ::: "memory");
#pragma unroll 1
            for (int i = 0; i < 24; i++) {
                if (lane == 0) tma2d(sb + SM_WG + i * 3840, i < 12 ? &tmG : &tmU, 320 * c + 8 * nslot * q, 48 * (i < 12 ? i : i - 12), mb + MB_W1 * 8);
            }
            STAMP(1);
            return;
        }
        if (warp == 20) {
            if (lane == 0) {
                asm volatile("cp.async.bulk.shared::cluster.global.mbarrier::complete_tx::bytes [%0], [%1], %2, [%3];"
                             :: "r"(sb + SM_ROW), "l"(prm.x + min(18 * (int)blockIdx.x, L_ - 1) * D_), "r"(max(min(18, L_ - 18 * (int)blockIdx.x), 1) * (D_ * 2)), "r"(mb + MB_R * 8) : "memory");
            }
            __syncwarp();
            if (TILE_NS < 0) mbar_wait(mb + MB_R * 8); else if (TILE_NS) __nanosleep(TILE_NS);
            if (lane == 0) {
                asm volatile("cp.async.bulk.tensor.3d.shared::cluster.global.mbarrier::complete_tx::bytes [%0], [%1, {%3, %4, %5}], [%2];"
                             :: "r"(sb + SM_XTL), "l"(&tmX), "r"(mb + MB_T * 8), "r"(XW == 40 ? d0 : d0 & ~15), "r"(8 * q), "r"(0) : "memory");
            }
            STAMP(6);
        }
        asm volatile("barrier.cluster.wait.aligned;" ::: "memory");
        bar_sync(13, 736);
        asm volatile("fence.proxy.async.shared::cta;" ::: "memory");
        {
            const int gr = lane >> 2, pe = XROT ? ((lane & 3) * 2 + (warp & 1) + q + 1) & 7 : (((lane & 3) ^ (gr * 3)) * 2 + (warp & 1)) & 7;
            const int s0 = gr ? 0 : XSPLIT, ns = gr ? min(XSPLIT, nslot) : nslot - XSPLIT;
            if (gr < 2 && ns > 0) {
                const int bytes = ns * YS - 144;
                if (pe == q) arm(mb + (MB_X + gr) * 8, 7 * bytes);
                else {
                    const uint32_t rb_ = mapa(sb, pe);
                    asm volatile("cp.async.bulk.shared::cluster.shared::cta.mbarrier::complete_tx::bytes [%0], [%1], %2, [%3];"
                                 :: "r"(rb_ + SM_U + 128 + q * UP + s0 * US), "r"(sb + SM_XT + 128 + (q & 3) * 16 + pe * YP + s0 * YS), "r"(bytes), "r"(rb_ + SM_MB + (MB_X + gr) * 8) : "memory");
                }
            }
        }
        STAMP(1);
        if (warp == 20 && lane == 0) { asm volatile("prefetch.tensormap [%0];" :: "l"(&tmO) : "memory"); asm volatile("prefetch.tensormap [%0];" :: "l"(&tmH) : "memory"); }
        if (warp == 23) {
#pragma unroll 1
            for (int kk = nslot - 1; kk >= 0; kk--) {
                __syncwarp();
                bar_sync(6 + kk, 160);
                if (lane == 0) { asm volatile("fence.proxy.async.shared::cta;" ::: "memory"); tma2d(sb + SM_FAR + kk * FAR_SZ, &tmD, W2W == 72 ? 72 * q : (72 * q) & ~15, 320 * c + 64 * kk, mb + MB_W2 * 8); }
            }
            return;
        }
        __syncwarp();
        bar_sync(14, 672);
        if (lane == 0) {
            asm volatile("fence.proxy.async.shared::cta;" ::: "memory");
            asm volatile("cp.async.bulk.tensor.5d.global.shared::cta.bulk_group [%0, {%2, %4, %4, %4, %3}], [%1];" :: "l"(&tmH), "r"(sb + SM_XT + 16384), "r"(d0 + ((c & 1) ? 0 : 32)), "r"(8 * q), "r"(0) : "memory");
            asm volatile("cp.async.bulk.tensor.5d.global.shared::cta.bulk_group [%0, {%2, %4, %4, %4, %3}], [%1];" :: "l"(&tmO), "r"(sb + SM_XT), "r"(d0 + (c & 1) * 8), "r"(8 * q), "r"(0) : "memory");
            asm volatile("cp.async.bulk.commit_group;" ::: "memory");
            asm volatile("cp.async.bulk.wait_group 0;" ::: "memory");
            asm volatile("fence.proxy.async.global;" ::: "memory");
            asm volatile("mbarrier.arrive.shared::cta.b64 _, [%0];" :: "r"(mb + MB_OUT * 8) : "memory");
        }
        STAMP(2);
        return;
    }

    const int g = lane >> 2, cq = lane & 3;
    const int k = warp >> 2, wq = warp & 3;
    const int trow = 18 * blockIdx.x + warp;
    const bool rowact = warp < 18 && trow < L_;
    const int dch = min(d0 + 8 * k + q, D_ - 1);
    uint32_t pv[6];
#pragma unroll
    for (int i = 0; i < 6; i++) pv[i] = ldg16(prm.prm6[i] + (uint32_t)(dch * 128 + wq * 32 + lane));
    const uint32_t pLdt = ldg16(prm.logdt + dch), pD = ldg16(prm.dskip + dch);
    const int tn = 16 * (warp & 15) + g;
    uint32_t xa[5], xb[5];
    asm volatile("barrier.cluster.arrive.relaxed.aligned;" ::: "memory");
    uint4* const st1p = &g_s.st1[(((trow >> 3) & 7) * 256 + ((trow >> 6) & 31) * 8 + (trow & 7)) * 2 + (lane >> 2)];
    const bool pub = rowact && (lane & 0x1B) == 0;
    if (pub) st_rlx128(st1p, 0, 0, 0, 0);
    {
        const uint32_t za = sb + SM_P + tid * 16;
        sts128(za, 0, 0, 0, 0);
        if (tid < (SM_MISC - SM_P) / 16 - 640) sts128(za + 10240, 0, 0, 0, 0);
        sts128(sb + ((wq & 2) ? SM_U : SM_XT + (q & 3) * 16) + ((tid >> 3) & 7) * ((wq & 2) ? UP : YP) + k * YS + (lane & 7) * 16, 0, 0, 0, 0);
    }
    bar_sync(12, NTHR);
    const uint32_t dep = lds32(sb + SM_P);
#define PV(x) __uint_as_float(__byte_perm(dep, x, 0x5410))
    STAMP(1);
    const uint32_t fb = sb + SM_FAR + k * FAR_SZ;
    const uint32_t pn = sb + SM_PN + k * PN_SZ, pf = sb + SM_PF + k * PF_SZ;
    unsigned epoch;
    {
        const uint32_t kb = fb + wq * 3072;
        const uint32_t kl = kb + lane * 16;
        uint32_t Af[4][4];
        float sr, si, z1r, z1i, z2r, z2i, z4r, z4i, hr, hi_;
        {
            const float dt = bfr(ex2f(PV(pLdt) * 1.4426950408889634f));
            const float e2 = dt * PV(pv[0]) * 1.4426950408889634f, an = dt * PV(pv[1]);
            cmul(sr, si, PV(pv[4]), PV(pv[5]), dt * PV(pv[2]), dt * PV(pv[3]));
            const unsigned E = min(max(__reduce_max_sync(~0u, __float_as_uint(fmaxf(fmaxf(fabsf(sr), fabsf(si)), fabsf(PV(pD)) * (1.f / 8192.f)))) >> 23, 1u), 253u);
            const float sc = __uint_as_float((254u - E) << 23);
            sr *= sc; si *= -sc;
            sts64(sb + SM_KG + warp * 8, E, __reduce_add_sync(~0u, __float2int_rn(sr * 16777216.f)));
            float ar, ai, br, bi, cr, ci, dr, di;
            { const float m = ex2f(e2 * 8.f); ar = m * __cosf(an * 8.f); ai = m * __sinf(an * 8.f); }
            csq(br, bi, ar, ai); csq(cr, ci, br, bi); csq(dr, di, cr, ci);
            const H2C m4 = splat(cr, ci);
            {
                float r3, i3;
                cmul(r3, i3, ar, ai, br, bi);
                expand4(kl, kl + 1024, pack_f16(1.f, ar), pack_f16(br, r3), pack_f16(0.f, ai), pack_f16(bi, i3), m4);
            }
            expand8(kl + 512, kl + 1536, dr, di, ar, ai, br, bi, m4);
            { const float m = ex2f(e2); z1r = m * __cosf(an); z1i = -m * __sinf(an); }
            cexp_s(hr, hi_, e2 * 128.f, an * (-128.f * 0.15915494309189535f));
            csq(z2r, z2i, z1r, z1i); csq(z4r, z4i, z2r, z2i);
        }
        __syncwarp();
#pragma unroll
        for (int ks = 0; ks < 4; ks++) ldsm4t(Af[ks], kb + (lane >> 3) * 512 + (lane & 7) * 16 + ks * 128);
        STAMP(2);
        const uint32_t la = kb + ((lane >> 3) & 1) * 512 + (lane >> 4) * 128 + (lane & 7) * 16;
        uint32_t kp[5][2], b0[4], b1[4], b2[4], b3[4];
        auto mm2 = [&](int t) {
            float a0[4] = {0.f, 0.f, 0.f, 0.f}, a1[4] = {0.f, 0.f, 0.f, 0.f};
            mma_f16(a0, Af[0], b0[0], b0[1]); mma_f16(a1, Af[0], b2[0], b2[1]); mma_f16(a0, Af[1], b0[2], b0[3]); mma_f16(a1, Af[1], b2[2], b2[3]);
            mma_f16(a0, Af[2], b1[0], b1[1]); mma_f16(a1, Af[2], b3[0], b3[1]); mma_f16(a0, Af[3], b1[2], b1[3]); mma_f16(a1, Af[3], b3[2], b3[3]);
            kp[t][0] = pack_f16(a0[1], a0[0]); kp[t][1] = pack_f16(a0[3], a0[2]); kp[t + 1][0] = pack_f16(a1[1], a1[0]); kp[t + 1][1] = pack_f16(a1[3], a1[2]);
        };
        auto ln1 = [&]() {
        mbar_wait(mb + MB_R * 8);
        epoch = lds32(sb + SM_SC + 28) + 1;
        {
            const uint32_t ra = sb + SM_ROW + warp * (D_ * 2);
            const uint4 r0 = lds128(ra + lane * 16), r1 = lds128(ra + 512 + lane * 16);
            const uint32_t rx[9] = {r0.x, r0.y, r0.z, r0.w, r1.x, r1.y, r1.z, r1.w, lds32(ra + 1024 + lane * 4)};
            float a0 = bf_lo(rx[0]), a1 = bf_hi(rx[0]), c0 = a0 * a0, c1 = a1 * a1;
#pragma unroll
            for (int i = 1; i < 9; i++) { const float l = bf_lo(rx[i]), h = bf_hi(rx[i]); a0 += l; a1 += h; c0 = fmaf(l, l, c0); c1 = fmaf(h, h, c1); }
            a0 += a1; c0 += c1;
            float s1 = ((lane & 1) ? c0 : a0) + __shfl_xor_sync(~0u, (lane & 1) ? a0 : c0, 1);
#pragma unroll
            for (int o = 2; o < 32; o <<= 1) s1 += __shfl_xor_sync(~0u, s1, o);
            const float s2 = __shfl_xor_sync(~0u, s1, 1);
            const uint32_t ms = ln_stats(s1, s2);
            const uint32_t p0 = __byte_perm(ms, epoch | 0x8000u, 0x5410), p1 = rsplit(rcpf(bf_hi(ms)));
            if (pub) st_rlx128(st1p, p0, p1, p0, p1);
        }
        mbar_wait(mb + MB_R * 8);
        STAMP(1);
        };
        const uint4* sp = &g_s.st1[(256 * q + tn) * 2];
        uint2 sa, sc;
        auto poll = [&]() { sa = ld_rlx64(sp); sc = ld_rlx64(sp + 16); };
        auto norm = [&]() {
        STAMP(3);
        if (warp < 16) {
            uint32_t va[5], vc[5];
            poll();
            mbar_wait(mb + MB_T * 8);
            {
                const uint32_t xt = sb + SM_XTL + (XW == 40 ? 0 : (c & 1) * 16) + tn * (2 * XW);
                uint4 a4 = lds128(xt + cq * 16), b4 = lds128(xt + cq * 16 + 16 * XW);
                va[0] = a4.x; va[1] = a4.y; va[2] = a4.z; va[3] = a4.w; va[4] = lds32(xt + 64 + cq * 4);
                vc[0] = b4.x; vc[1] = b4.y; vc[2] = b4.z; vc[3] = b4.w; vc[4] = lds32(xt + (64 + 16 * XW) + cq * 4);
            }
            const int d4 = 2 * (lane >> 3) + (lane & 1), d1_ = lane & 7;
            const uint32_t own = SM_U + 128 + q * (UP - YP), oth = SM_XT + 128 + (q & 3) * 16;
            uint32_t a4 = sb + warp * 32 + d4 * YP + (d4 == q ? own : oth) + ((lane & 7) >> 1) * YS;
            uint32_t a1 = sb + warp * 32 + d1_ * YP + (d1_ == q ? own : oth) + 4 * YS + (lane & 8) * 2;
            PIN(a4); PIN(a1);
            uint32_t tag = __byte_perm(epoch | 0x8000u, 0, 0x1010);
            PIN(tag);
            mbar_wait(mb + MB_T * 8);
            int n = 0;
            while (__byte_perm(sa.x, sc.x, 0x7632) != tag && ++n < SPIN_LIMIT) poll();
            STAMP(4);
#pragma unroll
            for (int i = 0; i < 5; i++) {
                va[i] = norm2(va[i], sa.x, sa.y); va[i] = pack_f16(bf_lo(va[i]), bf_hi(va[i]));
                vc[i] = norm2(vc[i], sc.x, sc.y); vc[i] = pack_f16(bf_lo(vc[i]), bf_hi(vc[i]));
            }
            stsm4t(a4, va[0], va[1], va[2], va[3]); stsm4t(a4 + 16, vc[0], vc[1], vc[2], vc[3]); stsm2t(a1, va[4], vc[4]);
            {
            const uint32_t xh = sb + SM_XTL + (XW == 40 ? 0 : (c & 1) * 16) + (64 * (g >> 1) + 32 * (warp & 1) + 8 * (g & 1) + (warp >> 1)) * (2 * XW);
            const uint4 c4 = lds128(xh + cq * 16), d4_ = lds128(xh + cq * 16 + 32 * XW);
            xa[0] = c4.x; xa[1] = c4.y; xa[2] = c4.z; xa[3] = c4.w; xa[4] = lds32(xh + 64 + cq * 4);
            xb[0] = d4_.x; xb[1] = d4_.y; xb[2] = d4_.z; xb[3] = d4_.w; xb[4] = lds32(xh + (64 + 32 * XW) + cq * 4);
            }
        }
        STAMP(5);
        bar_sync(13, 736);
        Af[0][0] |= lds32(sb + SM_P);
        };
        if (LNPOS == 0) ln1();
        cmul(sr, si, sr, si, z1r, z1i);
        {
            const H2C h4 = splat(z4r, z4i);
            expand8(kl, kl + 512, sr, si, z1r, z1i, z2r, z2i, h4);
            cmul(sr, si, sr, si, hr, hi_);
            expand8(kl + 1024, kl + 1536, sr, si, z1r, z1i, z2r, z2i, h4);
        }
        __syncwarp();
        ldsm4t(b0, la); ldsm4t(b1, la + 256); ldsm4t(b2, la + 1024); ldsm4t(b3, la + 1280);
        cmul(z1r, z1i, z1r, z1i, hr, hi_);
        cmul(sr, si, sr, si, z1r, z1i);
        if (LNPOS == 1) ln1();
        expand8(kl, kl + 512, sr, si, z2r, z2i, z4r, z4i, splat(hr, hi_));
        if (LNPOS == 2) ln1();
        csq(z1r, z1i, z1r, z1i);
        cmul(sr, si, sr, si, z1r, z1i);
        csq(z2r, z2i, hr, hi_);
        expand8(kl + 1024, kl + 1536, sr, si, z4r, z4i, hr, hi_, splat(z2r, z2i));
        if (LNPOS == 3) ln1();
        csq(z1r, z1i, z1r, z1i);
        cmul(sr, si, sr, si, z1r, z1i);
        csq(z4r, z4i, z2r, z2i);
        expand8(kl + 2048, kl + 2560, sr, si, hr, hi_, z2r, z2i, splat(z4r, z4i));
        if (LNPOS == 4) ln1();
        if (MMPOS == 0) norm();
        mm2(0);
        __syncwarp();
        ldsm4t(b0, la); ldsm4t(b1, la + 256); ldsm4t(b2, la + 1024); ldsm4t(b3, la + 1280);
        if (MMPOS == 1) norm();
        mm2(2);
        if (MMPOS == 2) norm();
        ldsm4t(b0, la + 2048); ldsm4t(b1, la + 2304);
#pragma unroll
        for (int t = 0; t < 4; t++) sts64(kb + lane * 8 + 1024 + t * 256, kp[t][0], kp[t][1]);
        {
            float a0[4] = {0.f, 0.f, 0.f, 0.f}, a1[4] = {0.f, 0.f, 0.f, 0.f};
            mma_f16(a0, Af[0], b0[0], b0[1]); mma_f16(a1, Af[1], b0[2], b0[3]); mma_f16(a0, Af[2], b1[0], b1[1]); mma_f16(a1, Af[3], b1[2], b1[3]);
            sts64(kb + lane * 8 + 2048, pack_f16(a0[1] + a1[1], a0[0] + a1[0]), pack_f16(a0[3] + a1[3], a0[2] + a1[2]));
        }
        bar_sync(1 + k, 128);
        const uint4 m01 = lds128(sb + SM_KG + k * 32), m23 = lds128(sb + SM_KG + k * 32 + 16);
        const unsigned Em = max(max(m01.x, m01.z), max(m23.x, m23.z));
        const float f0 = __uint_as_float(max((int)(127 + m01.x - Em), 0) << 23), f1 = __uint_as_float(max((int)(127 + m01.z - Em), 0) << 23),
                    f2 = __uint_as_float(max((int)(127 + m23.x - Em), 0) << 23), f3 = __uint_as_float(max((int)(127 + m23.z - Em), 0) << 23);
        const uint32_t r0 = pack_f16(f0, f0), r1 = pack_f16(f1, f1), r2 = pack_f16(f2, f2), r3 = pack_f16(f3, f3);
        const uint32_t ra = fb + lane * 8 + wq * 256 + 1024;
        const uint2 p0 = lds64(ra), p1 = lds64(ra + 3072), p2 = lds64(ra + 6144), p3 = lds64(ra + 9216);
        uint32_t w0 = hadd2(hfma2(p0.x, r0, hmul2(p1.x, r1)), hfma2(p2.x, r2, hmul2(p3.x, r3)));
        uint32_t w1 = hadd2(hfma2(p0.y, r0, hmul2(p1.y, r1)), hfma2(p2.y, r2, hmul2(p3.y, r3)));
        const bool last = lane == 31;
        if (wq < 2) {
            const uint32_t rc = fb + lane * 8 + wq * 4 + 2048;
            const uint32_t w4 = hmul2(hadd2(hfma2(lds32(rc), r0, hmul2(lds32(rc + 3072), r1)), hfma2(lds32(rc + 6144), r2, hmul2(lds32(rc + 9216), r3))), 0x18001800u);
            const uint32_t ph = pf + (P_H7 + 16 * wq) + (g & 1) * (2 * P_HS) + cq * 64 + (g >> 1) * 4;
            put16(ph, w4 >> 16); put16(ph + 32, w4);
            const uint32_t pa = pn + (4 + 512 * wq) + lane * 8;
            sts16(pa, w0 >> 16); sts32(pa + 4, w0); sts16(pa + 10, w0);
            sts16(pa + 256, w1 >> 16); sts32(pa + 260, w1); sts16(pa + 266, w1);
            if (last) {
                sts32(sb + SM_SC + k * 4, Em * 0x00800080u);
                put16(wq ? pa + 264 : pn,
                      wq ? w1 : pack_f16(((float)(int)m01.y * f0 + (float)(int)m01.w * f1 + (float)(int)m23.y * f2 + (float)(int)m23.w * f3) * (1.f / 16777216.f)
                                         + __uint_as_float(pD << 16) * __uint_as_float((254u - Em) << 23), 0.f));
            }
        } else if (wq == 2) {
            const uint32_t pa = pn + 258 * 4 + (cq & 1) * 16 + (cq >> 1) * 512 + g * 32;
            if (last) { put16(pf, hmul2(w1, 0x18001800u)); w1 = hadd2(w1, hneg2(__byte_perm(w1, 0, 0x1010))); }
            const uint32_t b0 = __byte_perm(w0, 0, 0x1010), b1 = __byte_perm(w1, 0, 0x1010);
            sts16(pa, w0 >> 16); sts32(pa + 4, w0); sts64(pa + 8, b0, b0); sts16(pa + 18, w0);
            sts16(pa + 256, w1 >> 16); sts32(pa + 260, w1); sts64(pa + 264, b1, b1); sts16(pa + 274, w1);
        } else {
            const uint32_t pa = pf + ((g & 1) ? 3 * P_GS : P_GS) + cq * 32 + (g >> 1) * 4;
            const uint32_t pb = pa + ((g & 1) ? 4 - 3 * P_GS : P_GS);
            w0 = hmul2(w0, 0x18001800u); w1 = hmul2(w1, 0x18001800u);
            put16(pa, w0 >> 16); put16(pb, w0); put16(pa + 16, w1 >> 16); put16(pb + 16, w1);
            if (last) put16(pf + P_H7 + P_HS, w1);
        }
        bar_sync(1 + k, 128);
    }
    STAMP(6);

    asm volatile("barrier.cluster.wait.aligned;" ::: "memory");
    mbar_wait(mb + (MB_X + (k < XSPLIT || k >= nslot)) * 8);
    STAMP(7);
    if (k < nslot) {
        const int role = (wq + k) & 3;
        const uint32_t ub = sb + SM_U + k * US + 128;
        if (role) {
            const int r = (3 - role) * 32 + lane;
            const uint32_t a1 = ub + (r & 3) * (2 * UP) + (r >> 2) * 16, a0 = a1 + ((r & 3) ? -2 * UP : 6 * UP - 16);
            const uint4 q0 = lds128(a0), q1 = lds128(a0 + UP), q2 = lds128(a1), q3 = lds128(a1 + UP);
            const uint32_t U[16] = {q0.x, q0.y, q0.z, q0.w, q1.x, q1.y, q1.z, q1.w, q2.x, q2.y, q2.z, q2.w, q3.x, q3.y, q3.z, q3.w};
            uint32_t V[14], Q[14], R4[12], T[8];
#pragma unroll
            for (int i = 2; i < 14; i++) { V[i] = __byte_perm(U[i], U[i + 1], 0x5432); Q[i] = hadd2(U[i], V[i]); }
#pragma unroll
            for (int i = 2; i < 12; i++) R4[i] = hadd2(Q[i], Q[i + 1]);
            const uint32_t rb = fb + r * 16;
#pragma unroll
            for (int i = 0; i < 8; i++) T[i] = hadd2(V[5 + i], Q[6 + i]);
            sts128(rb + F_E3, T[0], T[1], T[2], T[3]); sts128(rb + F_O3 + 16, T[4], T[5], T[6], T[7]);
#pragma unroll
            for (int i = 0; i < 8; i++) T[i] = hadd2(R4[3 + i], U[5 + i]);
            sts128(rb + F_O5, T[0], T[1], T[2], T[3]); sts128(rb + F_E5, T[4], T[5], T[6], T[7]);
            if (role != 1) {
#pragma unroll
                for (int i = 0; i < 8; i++) T[i] = hadd2(T[i], hadd2(V[2 + i], V[5 + i]));
                sts128(rb + F_E7, T[0], T[1], T[2], T[3]); sts128(rb + F_O7, T[4], T[5], T[6], T[7]);
#pragma unroll
                for (int i = 0; i < 8; i++) T[i] = hadd2(R4[2 + i], hadd2(R4[4 + i], U[6 + i]));
                sts128(rb + F_O9, T[0], T[1], T[2], T[3]); sts128(rb + F_E9 + 16, T[4], T[5], T[6], T[7]);
                sts128(rb + F_E2, Q[6], Q[7], Q[8], Q[9]); sts128(rb + F_O2, Q[10], Q[11], Q[12], Q[13]);
            }
        } else if (lane < 8) {
            uint32_t v[5];
#pragma unroll
            for (int i = 0; i < 5; i++) { const int t = 6 + lane + i; v[i] = lds16(ub + 23 * 16 + (t < 16 ? (6 + (t >> 3)) * UP : 16) + (t & 7) * 2); }
            const uint32_t s = hadd2(hadd2(hadd2(v[0], v[1]), hadd2(v[2], v[3])), v[4]);
            sts16(fb + F_O5 + 96 * 16 + lane * 2, s);
            sts32(fb + (lane < 4 ? F_O3 : F_E9 - 16) + lane * 4, 0);
        }
        bar_sync(1 + k, 128);
        float acc[4][4];
        uint32_t Q[4][4];
        {
            const int h = role & 1, part = role >> 1;
            const uint32_t po = pf + (g - 2 * cq) * 4;
            float fa[7][4];
#pragma unroll
            for (int a = 0; a < 7; a++) fa[a][0] = fa[a][1] = fa[a][2] = fa[a][3] = 0.f;
            uint32_t B[3][4];
            Q[0][2] = zero;
#pragma unroll 1
            for (int s = 2 * part + 1; s >= 2 * part; s--) {
#pragma unroll
                for (int i = 0; i < 3; i++) { Q[i][0] = lds32(po + s * P_GS + i * 64); Q[i][1] = lds32(po + s * P_GS + (i * 64 + 32)); }
                const uint32_t ba = fb + lane * 16 + ((s & 1) * F_E3 + (part == h ? 0 : F_O5 + h * 16));
#pragma unroll
                for (int i = 0; i < 3; i++) ldsm4t(B[i], ba + i * 512);
#pragma unroll
                for (int i = 0; i < 3; i++) { Q[i][3] = CP(Q[i][0]); if (i) Q[i][2] = CP(Q[i - 1][1]); }
#pragma unroll
                for (int dl = 0; dl < 3; dl++)
#pragma unroll
                    for (int ap = 0; ap < 6 - dl; ap++) mma_f16(fa[ap + 1 + dl], Q[dl], B[ap >> 1][2 * (ap & 1)], B[ap >> 1][2 * (ap & 1) + 1]);
            }
#pragma unroll 1
            for (int s = role; s == 1; s++) {
                ldsm2t(B[0][0], B[0][1], fb + ((lane & 15) == 15 ? F_O5 : F_O3));
#pragma unroll
                for (int dl = 0; dl < 3; dl++) mma_f16(fa[dl], Q[dl], B[0][0], B[0][1]);
            }
#pragma unroll 1
            for (int s = part; s <= 2 * part; s++) {
#pragma unroll
                for (int i = 0; i < 4; i++) { Q[i][0] = lds32(po + s * P_HS + (P_H7 + i * 64)); Q[i][1] = lds32(po + s * P_HS + (P_H7 + i * 64 + 32)); }
                const uint32_t ba = fb + lane * 16 + (F_E7 + s * 1024 + h * F_H);
                ldsm4t(B[0], ba); ldsm4t(B[1], ba + 512);
#pragma unroll
                for (int i = 0; i < 4; i++) { Q[i][3] = CP(Q[i][0]); if (i) Q[i][2] = CP(Q[i - 1][1]); }
#pragma unroll
                for (int dl = 0; dl < 4; dl++) {
#pragma unroll
                    for (int ap = 0; ap < 4 - dl; ap++) mma_f16(fa[ap + 3 + dl], Q[dl], B[ap >> 1][2 * (ap & 1)], B[ap >> 1][2 * (ap & 1) + 1]);
                    if (s == 1) break;
                }
            }
            const uint32_t da = fb + role * 2048 + (lane & 3) * 512 + (((lane >> 2) ^ ((lane & 3) * 2)) << 4);
            bar_sync(1 + k, 128);
            stsm4(da, 0u, 0u, pack_f16(fa[0][0], fa[0][1]), pack_f16(fa[0][2], fa[0][3]));
#pragma unroll
            for (int i = 1; i < 4; i++)
                stsm4(da + i * 128, pack_f16(fa[2 * i - 1][0], fa[2 * i - 1][1]), pack_f16(fa[2 * i - 1][2], fa[2 * i - 1][3]),
                      pack_f16(fa[2 * i][0], fa[2 * i][1]), pack_f16(fa[2 * i][2], fa[2 * i][3]));
            Q[0][0] = (g == 2 * cq) ? 0x6000u : ((g == 2 * cq + 1) ? 0x60000000u : 0u);
            Q[0][1] = 0; Q[0][3] = CP(Q[0][0]);
            const uint32_t ra = fb + (lane >> 3) * 2048 + wq * 512 + (((lane & 7) ^ (wq * 2)) << 4);
            bar_sync(1 + k, 128);
#pragma unroll
            for (int i = 0; i < 4; i++) {
                ldsm4(B[0], ra + i * 128);
                acc[i][0] = acc[i][1] = acc[i][2] = acc[i][3] = 0.f;
                mma_f16(acc[i], Q[0], hadd2(B[0][0], B[0][2]), hadd2(B[0][1], B[0][3]));
            }
        }
        bar_arrive(6 + k, 160);
        STAMP(8);
        const uint32_t inv = lds32(sb + SM_SC + k * 4);
        uint32_t yd = mapa(sb, 2 * wq) + (SM_XT + 128 + q * YP + k * YS + (k >> 2) * (q >> 1) * 16) + lane * 16;
        PIN(yd);
        {
            uint32_t pp = pn + (16 * (wq - 3) + g - 2 * cq) * 4;
            uint32_t dlo = (((ub + 6 * UP) & 0x3FFFF) >> 4) | ((UP >> 4) << 16);
            uint32_t R[4][4];
            auto loadQ = [&](uint32_t (&X)[4][4], uint32_t prev) {
#pragma unroll
                for (int i = 0; i < 4; i++) { X[i][0] = lds32(pp + i * 64); X[i][1] = lds32(pp + i * 64 + 32); }
                X[0][2] = CP(prev);
#pragma unroll
                for (int i = 0; i < 4; i++) { X[i][3] = CP(X[i][0]); if (i) X[i][2] = CP(X[i - 1][1]); }
                pp += 256;
            };
            auto issue = [&](uint32_t (&X)[4][4]) {
                asm volatile("wgmma.fence.sync.aligned;" ::: "memory");
#pragma unroll
                for (int i = 0; i < 4; i++) wgmma32(acc, X[i], dlo - i * (2 * UP >> 4));
                asm volatile("wgmma.commit_group.sync.aligned;" ::: "memory");
                dlo -= 1;
            };
            loadQ(Q, 0);
#pragma unroll 1
            for (int dl = 0; dl < 4; dl++) {
                issue(Q);
                asm volatile("wgmma.wait_group.sync.aligned 1;" ::: "memory");
                loadQ(R, Q[3][1]);
                issue(R);
                asm volatile("wgmma.wait_group.sync.aligned 1;" ::: "memory");
                loadQ(Q, R[3][1]);
            }
            issue(Q);
            asm volatile("wgmma.wait_group.sync.aligned 0;" ::: "memory");
        }
        const uint32_t pstep = mapa(sb, 1) - mapa(sb, 0), ym = mapa(mb + MB_Y * 8, 2 * wq);
#pragma unroll
        for (int e = 0; e < 2; e++)
            st_async4(yd + e * pstep, bmul2(pack_bf16(acc[0][2 * e], acc[0][2 * e + 1]), inv), bmul2(pack_bf16(acc[1][2 * e], acc[1][2 * e + 1]), inv),
                      bmul2(pack_bf16(acc[2][2 * e], acc[2][2 * e + 1]), inv), bmul2(pack_bf16(acc[3][2 * e], acc[3][2 * e + 1]), inv), ym + e * pstep);
        if (lane == 0) asm volatile("mbarrier.arrive.shared::cta.b64 _, [%0];" :: "r"(mb + MB_Y * 8) : "memory");
    }
    STAMP(9);
    uint32_t ha[5], hb[5];
    if (warp < 16) {
        const uint4 wk = lds128(sb + SM_DW + cq * 16);
        uint32_t sel[5] = {wk.x, wk.y, wk.z, wk.w, lds32(sb + SM_DW + 64 + cq * 4)}, sel2[5];
#pragma unroll
        for (int i = 0; i < 5; i++) {
            if (!(g & 1)) sel[i] = 0x3F803F80u;
            sel2[i] = sel[i]; PIN(sel2[i]);
        }
        const uint32_t y4 = sb + SM_XT + 128 + warp * 32 + (2 * (lane >> 3) + (lane & 1)) * YP + ((lane & 7) >> 1) * YS;
        const uint32_t y1 = sb + SM_XT + 128 + warp * 32 + (lane & 7) * YP + 4 * YS + (lane & 8) * 2 + (lane & 6) * 8;
        uint32_t ao = (256 * q + tn) * 16, hta = sb + SM_HT + tn * 80;
        PIN(ao); PIN(hta);
        mbar_wait(mb + MB_Y * 8);
        STAMP(10);
        float ca[4] = {0.f, 0.f, 0.f, 0.f}, cb[4] = {0.f, 0.f, 0.f, 0.f};
        {
            uint32_t ya[4], yb[4], yc, yd;
            ldsm4t(ya, y4); ldsm4t(yb, y4 + 16); ldsm2t(yc, yd, y1);
#pragma unroll
            for (int i = 0; i < 4; i++) { ha[i] = badd2(xa[i], ya[i]); hb[i] = badd2(xb[i], yb[i]); }
            ha[4] = badd2(xa[4], yc); hb[4] = badd2(xb[4], yd);
        }
        if (nslot != 5) {
            ha[4] = hb[4] = 0;
            if (cq >= 2) ha[0] = ha[1] = ha[2] = ha[3] = hb[0] = hb[1] = hb[2] = hb[3] = 0;
        }
#pragma unroll
        for (int i = 0; i < 5; i++) { mma_bf16_k8(ca, ha[i], sel[i], ha[i]); mma_bf16_k8(cb, hb[i], sel2[i], hb[i]); }
        if (!(g & 1)) { ca[1] = ca[0]; cb[1] = cb[0]; }
        if (cq == (g >> 1)) {
            asm volatile("red.relaxed.gpu.global.add.v4.f32 [%0], {%1,%2,%3,%4};" :: "l"((char*)g_s.acc + ao), "f"(1.0f), "f"(ca[1]), "f"(ca[2]), "f"(ca[3]) : "memory");
            asm volatile("red.relaxed.gpu.global.add.v4.f32 [%0], {%1,%2,%3,%4};" :: "l"((char*)g_s.acc + ao + 128), "f"(1.0f), "f"(cb[1]), "f"(cb[2]), "f"(cb[3]) : "memory");
        }
        sts128(hta + cq * 16, ha[0], ha[1], ha[2], ha[3]); sts32(hta + 64 + cq * 4, ha[4]);
        sts128(hta + cq * 16 + 640, hb[0], hb[1], hb[2], hb[3]); sts32(hta + 704 + cq * 4, hb[4]);
        STAMP(11);
    }
    const int kq = warp / 5, mt = warp - 5 * kq;
    const int mi = lane >> 3, mr = lane & 7;
    const unsigned tk = (unsigned)tid / 72u, ck = tid - tk * 72;
    uint32_t A[9][4];
    auto loadA = [&]() {
        mbar_wait(mb + MB_W1 * 8);
        const uint32_t aa = sb + (mi & 1) * SM_WU + (8 * (mi >> 1) + mr) * 80 + (144 * 80 * kq + mt * 16);
#pragma unroll
        for (int s = 0; s < 9; s++) ldsm4t(A[s], aa + s * 1280);
    };
    const uint32_t par = (epoch & 1) ? 0x40004000u : 0u;
    uint32_t pk0 = mapa(sb, 2 * cq), go = (ck / 5u + ck) * 16, co = ((q * 8 * NCL + c) * 6 + cq) * 16;
    PIN(pk0); PIN(go); PIN(co);
    if (warp < 8) {
        const float wsum = ldsf(sb + SM_SC + 24);
        const uint32_t idx = 2047 - (512 * ((tid >> 1) & 3) + 128 * ((tid >> 3) & 3) + 64 * (tid & 1) + 8 * q + warp);
        uint4 s; int n = 0;
        do { s = ld_rlx128(&g_s.acc[256 * q + tid]); } while (__uint_as_float(s.x) != (float)NCL && ++n < SPIN_LIMIT);
        STAMP(16);
        const uint32_t ox = __shfl_xor_sync(~0u, (lane & 1) ? s.z : s.w, 1);
        const uint32_t ms = ln_stats(__uint_as_float((lane & 1) ? ox : s.z), __uint_as_float(s.y));
        const float rs = rcpf(bf_hi(ms));
        const uint32_t rb = pack_bf16(0.f, fmaf(-bf_lo(ms), wsum, __uint_as_float((lane & 1) ? s.w : ox)) * rs);
        const uint32_t key = (((rb ^ (((int)rb >> 31) | 0x80000000u)) >> 16) << 11) | idx;
        sts32(sb + SM_KEY + tid * 4, key);
        __syncwarp();
        const uint32_t rank = rank4<8, 16>(sb + SM_KEY + warp * 128, key);
        if (rank < 8) sts32(sb + SM_CAND + warp * 32 + rank * 4, key);
        sts64(sb + SM_ST + tid * 8, ms, rsplit(rs));
    } else loadA();
    if (warp < 16) {
        STAMP(17);
        bar_sync(12, 512);
        STAMP(18);
        if (warp < 8) {
            const uint32_t mk = lds32(sb + SM_CAND + (tid >> 2) * 4);
            uint32_t rank = rank4<4, 64>(sb + SM_CAND + cq * 16, mk);
            rank += __shfl_xor_sync(~0u, rank, 1); rank += __shfl_xor_sync(~0u, rank, 2);
            if (rank < 8) {
                const uint32_t pk1 = pk0 + (mapa(sb, 1) - mapa(sb, 0));
                st_async1(pk0 + (SM_RK + q * 32) + rank * 4, mk, pk0 + (SM_MB + MB_KEY * 8));
                st_async1(pk1 + (SM_RK + q * 32) + rank * 4, mk, pk1 + (SM_MB + MB_KEY * 8));
                const uint32_t t = tslot(~mk);
                const uint2 sv = lds64(sb + SM_ST + t * 8);
                const uint4 hv = lds128(sb + SM_HT + t * 80 + cq * 16);
                const uint32_t h4 = lds32(sb + SM_HT + t * 80 + 64 + cq * 4);
                const uint32_t rr = bmul2(sv.y, 0x3C803C80u);
                char* const dp = (char*)g_s.cand + (co + rank * 1440);
                st_rlx128(dp, (norm2(hv.x, sv.x, rr) & 0xBFFFBFFFu) | par, (norm2(hv.y, sv.x, rr) & 0xBFFFBFFFu) | par,
                          (norm2(hv.z, sv.x, rr) & 0xBFFFBFFFu) | par, (norm2(hv.w, sv.x, rr) & 0xBFFFBFFFu) | par);
                asm volatile("st.relaxed.gpu.global.u32 [%0], %1;" :: "l"((char*)g_s.cand + (co + rank * 1440 + 64 - cq * 12)), "r"((norm2(h4, sv.x, rr) & 0xBFFFBFFFu) | par) : "memory");
            }
            __syncwarp();
        }
        {
            const uint2 sa = lds64(sb + SM_ST + tn * 8), sbb = lds64(sb + SM_ST + tn * 8 + 64);
#pragma unroll
            for (int i = 0; i < 5; i++) { ha[i] = badd2(ha[i], norm2(ha[i], sa.x, sa.y)); hb[i] = badd2(hb[i], norm2(hb[i], sbb.x, sbb.y)); }
            const bool hf = (c & 1) && cq == 0;
            const uint32_t o16 = sb + SM_XT + (hf ? 16384 + tn * 16 : tn * 64 + (cq - (c & 1)) * 16), o4 = sb + SM_XT + ((c & 1) ? tn * 64 + 48 : 16384 + tn * 16) + cq * 4;
            sts128(o16, ha[0], ha[1], ha[2], ha[3]); sts32(o4, ha[4]);
            sts128(o16 + (hf ? 128 : 512), hb[0], hb[1], hb[2], hb[3]); sts32(o4 + ((c & 1) ? 512 : 128), hb[4]);
        }
        if (warp >= 8) {
            STAMP(19);
            mbar_wait(mb + MB_KEY * 8);
            STAMP(20);
            const uint32_t mk = lds32(sb + SM_RK - 256 + (tid >> 2) * 4);
            uint32_t rank = rank4<4, 64>(sb + SM_RK + cq * 16, mk);
            rank += __shfl_xor_sync(~0u, rank, 1); rank += __shfl_xor_sync(~0u, rank, 2);
            if (rank < 8) sts64(sb + SM_SEL + rank * 8, mk, ((tid >> 2) - 64) * 1440);
        }
    }
    bar_sync(11, 640);
    STAMP(12);

    const char* gp = (const char*)g_s.cand + (go + lds32(sb + SM_SEL + 4 + (tk & 7) * 8));
    uint4 hv = ld_rlx128(gp);
    if (warp < 8) loadA();
    const bool red = warp < 6;
    const uint32_t ft = red ? (unsigned)tid / 24u : (unsigned)(tid >> 4) & 7u, fj = red ? 24 * q + tid - ft * 24 : d0 / 3 + (lane & 15);
    const uint32_t key = lds32(sb + SM_SEL + ft * 8), k16 = key << 5;
    float sig = bfr(rcpf(1.f + ex2f(__uint_as_float((k16 ^ (~((int)k16 >> 31) | 0x80000000u)) & 0xFFFF0000u) * -1.4426950408889634f)));
    uint32_t ra2 = sb + SM_RED2 + tid * 12 + ft * 16, fo = (ft * 192 + fj) * 16, oo = ((~key & 2047) * D_ + 3 * fj) * 2;
    uint32_t bx = sb + SM_XS + mr * 1168 + mi * 16 + 288 * kq, gd = mapa(sb, kq * (8 / NRED)) + (SM_GU + (q * nslot + mt) * 128) + lane * 4;
    PIN(ra2); PIN(fo); PIN(oo); PIN(bx); PIN(gd);
    asm volatile("" : "+f"(sig));
    {
        if (warp < 18) {
            int n = 0;
            while ((((hv.x ^ par) | (hv.y ^ par) | (hv.z ^ par) | (hv.w ^ par)) & 0x40004000u) && ++n < SPIN_LIMIT) hv = ld_rlx128(gp);
            sts128(sb + SM_XS + tk * 16 + tid * 16, hv.x ^ par, hv.y ^ par, hv.z ^ par, hv.w ^ par);
        }
    }
    bar_sync(14, 672);
    STAMP(13);
    {
        float c0[4] = {0.f, 0.f, 0.f, 0.f}, c1[4] = {0.f, 0.f, 0.f, 0.f}, c2[4] = {0.f, 0.f, 0.f, 0.f};
        uint32_t b[5][4];
#pragma unroll
        for (int s = 0; s < 4; s++) ldsm4(b[s], bx + s * 64);
        asm volatile("ldmatrix.sync.aligned.m8n8.x2.shared.b16 {%0,%1}, [%2];" : "=r"(b[4][0]), "=r"(b[4][1]) : "r"(bx + 256) : "memory");
        mma_bf16(c0, A[0][0], A[0][1], A[0][2], A[0][3], b[0][0], b[0][1]);
        mma_bf16(c1, A[1][0], A[1][1], A[1][2], A[1][3], b[0][2], b[0][3]);
        mma_bf16(c2, A[2][0], A[2][1], A[2][2], A[2][3], b[1][0], b[1][1]);
        mma_bf16(c0, A[3][0], A[3][1], A[3][2], A[3][3], b[1][2], b[1][3]);
        mma_bf16(c1, A[4][0], A[4][1], A[4][2], A[4][3], b[2][0], b[2][1]);
        mma_bf16(c2, A[5][0], A[5][1], A[5][2], A[5][3], b[2][2], b[2][3]);
        mma_bf16(c0, A[6][0], A[6][1], A[6][2], A[6][3], b[3][0], b[3][1]);
        mma_bf16(c1, A[7][0], A[7][1], A[7][2], A[7][3], b[3][2], b[3][3]);
        mma_bf16(c2, A[8][0], A[8][1], A[8][2], A[8][3], b[4][0], b[4][1]);
        sts128f(sb + SM_RED + tid * 16, c0[0] + c1[0] + c2[0], c0[1] + c1[1] + c2[1], c0[2] + c1[2] + c2[2], c0[3] + c1[3] + c2[3]);
    }
    bar_sync(1 + mt, 128);
    STAMP(21);
    if (mt < nslot && kq < NRED) {
        const uint32_t ra = sb + SM_RED + mt * 512 + lane * 16;
        const float4 p0 = lds128f(ra), p1 = lds128f(ra + 2560), p2 = lds128f(ra + 5120), p3 = lds128f(ra + 7680);
        const float g0 = bfr(((p0.x + p1.x) + (p2.x + p3.x)) * 64.f), g1 = bfr(((p0.y + p1.y) + (p2.y + p3.y)) * 64.f);
        const uint32_t sg = pack_bf16(g0 * rcpf(1.f + ex2f(g0 * -1.4426950408889634f)), g1 * rcpf(1.f + ex2f(g1 * -1.4426950408889634f)));
        const uint32_t gu = bmul2(sg, pack_bf16(((p0.z + p1.z) + (p2.z + p3.z)) * 64.f, ((p0.w + p1.w) + (p2.w + p3.w)) * 64.f));
        const uint32_t pstep = mapa(sb, 1) - mapa(sb, 0), gm = mapa(mb + MB_GU * 8, kq * (8 / NRED));
#pragma unroll
        for (int i = 0; i < 8 / NRED; i++) st_async1(gd + i * pstep, gu, gm + i * pstep);
    }
    mbar_wait(mb + MB_W2 * 8);
    {
        const uint32_t aa = sb + (8 * (mi >> 1) + mr) * (2 * W2W) + (mi & 1) * 16 + (SM_FAR + 32 * W2W * kq + mt * 32 + (W2W == 72 ? 0 : (q & 1) * 16));
#pragma unroll
        for (int s = 0; s < 5; s++) ldsm4t(A[s], aa + s * FAR_SZ);
    }
    {
        uint32_t ba = sb + (SM_GU + 256 * kq) + (lane & 15) * 16 + (lane >> 4) * 1024, wa = sb + (SM_RED2 + kq * 2432 + mt * 64) + g * 4 + cq * 608;
        PIN(ba); PIN(wa);
        STAMP(22);
        mbar_wait(mb + MB_GU * 8);
        STAMP(23);
        float c0[4] = {0.f, 0.f, 0.f, 0.f}, c1[4] = {0.f, 0.f, 0.f, 0.f}, c2[4] = {0.f, 0.f, 0.f, 0.f};
        uint32_t b[2][4], b8, b9;
        ldsm4t(b[0], ba); ldsm4t(b[1], ba + 2048); ldsm2t(b8, b9, ba + 4096);
        mma_bf16(c0, A[0][0], A[0][1], A[0][2], A[0][3], b[0][0], b[0][1]);
        mma_bf16(c1, A[1][0], A[1][1], A[1][2], A[1][3], b[0][2], b[0][3]);
        if (nslot == 5) {
            mma_bf16(c2, A[4][0], A[4][1], A[4][2], A[4][3], b8, b9);
            mma_bf16(c0, A[2][0], A[2][1], A[2][2], A[2][3], b[1][0], b[1][1]);
            mma_bf16(c1, A[3][0], A[3][1], A[3][2], A[3][3], b[1][2], b[1][3]);
        }
        stsf(wa, c0[0] + c1[0] + c2[0]); stsf(wa + 304, c0[1] + c1[1] + c2[1]);
        if (mt < 4) { stsf(wa + 32, c0[2] + c1[2] + c2[2]); stsf(wa + 336, c0[3] + c1[3] + c2[3]); }
    }
    if (warp < 10) {
        float v[3], cnt = 3.f;
        if (red) {
            bar_sync(6, 640);
            STAMP(14);
#pragma unroll
            for (int i = 0; i < 3; i++) v[i] = ((ldsf(ra2 + i * 4) + ldsf(ra2 + i * 4 + 2432)) + (ldsf(ra2 + i * 4 + 4864) + ldsf(ra2 + i * 4 + 7296))) * sig;
        } else {
            bar_arrive(6, 640);
            cnt = 0.f;
#pragma unroll
            for (int i = 0; i < 3; i++) {
                const uint32_t cl = 3 * fj + i - d0;
                const bool ok = cl < 8 * nslot && ((~key >> 3) & 7) == q;
                const uint32_t cf = cl - (c & 1) * 8;
                v[i] = ok ? __uint_as_float(lds16(sb + SM_XT + (cf < 32 ? tslot(~key) * 64 + cf * 2 : 16384 + tslot(~key) * 16 + (cl & 7) * 2)) << 16) : 0.f;
                if (ok) cnt += 1.f;
            }
            mbar_wait(mb + MB_OUT * 8);
        }
        if (cnt != 0.f) {
            float x, y, z, w;
            asm volatile("atom.relaxed.gpu.global.add.v4.f32 {%0,%1,%2,%3}, [%4], {%5,%6,%7,%8};" : "=f"(x), "=f"(y), "=f"(z), "=f"(w)
                         : "l"((char*)g_s.fin + fo), "f"(v[0]), "f"(v[1]), "f"(v[2]), "f"(cnt) : "memory");
            if (w + cnt == 3.f * (NCL + 1)) {
                __nv_bfloat16* op = (__nv_bfloat16*)((char*)prm.out + oo);
                op[0] = __float2bfloat16(x + v[0]); op[1] = __float2bfloat16(y + v[1]); op[2] = __float2bfloat16(z + v[2]);
            }
        }
    } else bar_arrive(6, 640);
    STAMP(15);
}

typedef CUresult (*EncodeFn)(CUtensorMap*, CUtensorMapDataType, cuuint32_t, void*, const cuuint64_t*, const cuuint64_t*,
                             const cuuint32_t*, const cuuint32_t*, CUtensorMapInterleave, CUtensorMapSwizzle,
                             CUtensorMapL2promotion, CUtensorMapFloatOOBfill);

void make_map(EncodeFn fn, CUtensorMap* tm, const void* p, int cols, int rows, int bc, int br) {
    cuuint64_t dims[2] = {(cuuint64_t)cols, (cuuint64_t)rows};
    cuuint64_t strides[1] = {(cuuint64_t)cols * 2};
    cuuint32_t box[2] = {(cuuint32_t)bc, (cuuint32_t)br};
    cuuint32_t es[2] = {1, 1};
    fn(tm, CU_TENSOR_MAP_DATA_TYPE_BFLOAT16, 2, const_cast<void*>(p), dims, strides, box, es, CU_TENSOR_MAP_INTERLEAVE_NONE,
       CU_TENSOR_MAP_SWIZZLE_NONE, CU_TENSOR_MAP_L2_PROMOTION_L2_128B, CU_TENSOR_MAP_FLOAT_OOB_FILL_NONE);
}

void make_map3(EncodeFn fn, CUtensorMap* tm, const void* p) {
    cuuint64_t dims[3] = {(cuuint64_t)D_, 64, 32};
    cuuint64_t strides[2] = {(cuuint64_t)D_ * 2, (cuuint64_t)D_ * 128};
    cuuint32_t box[3] = {XW, 8, 32};
    cuuint32_t es[3] = {1, 1, 1};
    fn(tm, CU_TENSOR_MAP_DATA_TYPE_BFLOAT16, 3, const_cast<void*>(p), dims, strides, box, es, CU_TENSOR_MAP_INTERLEAVE_NONE,
       CU_TENSOR_MAP_SWIZZLE_NONE, CU_TENSOR_MAP_L2_PROMOTION_NONE, CU_TENSOR_MAP_FLOAT_OOB_FILL_NONE);
}

void make_map5(EncodeFn fn, CUtensorMap* tm, const void* p, int bc) {
    cuuint64_t dims[5] = {(cuuint64_t)D_, 2, 4, 4, 64};
    cuuint64_t strides[4] = {(cuuint64_t)D_ * 128, (cuuint64_t)D_ * 1024, (cuuint64_t)D_ * 256, (cuuint64_t)D_ * 2};
    cuuint32_t box[5] = {(cuuint32_t)bc, 2, 4, 4, 8};
    cuuint32_t es[5] = {1, 1, 1, 1, 1};
    fn(tm, CU_TENSOR_MAP_DATA_TYPE_BFLOAT16, 5, const_cast<void*>(p), dims, strides, box, es, CU_TENSOR_MAP_INTERLEAVE_NONE,
       CU_TENSOR_MAP_SWIZZLE_NONE, CU_TENSOR_MAP_L2_PROMOTION_NONE, CU_TENSOR_MAP_FLOAT_OOB_FILL_NONE);
}

}

extern "C" void kernel_launch(void* const* d_in, const int* in_sizes, int n_in, void* d_out, int out_size) {
    (void)in_sizes; (void)n_in; (void)out_size;
    void* fp = nullptr;
    cudaDriverEntryPointQueryResult qr;
    cudaGetDriverEntryPoint("cuTensorMapEncodeTiled", &fp, cudaEnableDefault, &qr);
    EncodeFn fn = (EncodeFn)fp;
    CUtensorMap tmG, tmU, tmD, tmO, tmX, tmH;
    make_map3(fn, &tmX, d_in[0]);
    make_map(fn, &tmG, d_in[11], F_, D_, 40, 48);
    make_map(fn, &tmU, d_in[12], F_, D_, 40, 48);
    make_map(fn, &tmD, d_in[13], D_, F_, W2W, 64);
    make_map5(fn, &tmO, d_out, 32);
    make_map5(fn, &tmH, d_out, 8);
    Params p;
    p.x = (const unsigned short*)d_in[0];
    for (int i = 0; i < 6; i++) p.prm6[i] = (const unsigned short*)d_in[1 + i];
    p.logdt = (const unsigned short*)d_in[7]; p.dskip = (const unsigned short*)d_in[8];
    p.wr = (const unsigned short*)d_in[10];
    p.out = (__nv_bfloat16*)d_out;
    p.zero = 0;
    cudaGetSymbolAddress((void**)&p.gs, g_s);
    cudaFuncSetAttribute(fused_kernel, cudaFuncAttributeMaxDynamicSharedMemorySize, SM_TOTAL);
    fused_kernel<<<NCTA, NTHR, SM_TOTAL>>>(p, tmG, tmU, tmD, tmO, tmX, tmH);
}
```

```cpp
#include <cuda_runtime.h>
#include <cuda_bf16.h>
#include <cuda_fp16.h>
#include <cuda.h>
#include <stdint.h>

namespace {

constexpr int L_ = 2048, D_ = 576, F_ = 4608;
constexpr int NCL = 15, CS = 8, NCTA = NCL * CS, NTHR = 768;
#define W2W 72
#define XW 48
#define TILE_NS -1
#define XROT 0
#define LNPOS 1
#define MMPOS 0
#define XSPLIT 3
constexpr int NRED = 2;
constexpr int SPIN_LIMIT = 1 << 22;

constexpr int SM_WG   = 0;
constexpr int SM_WU   = 46080;
constexpr int YP = 3392, YS = 656;
constexpr int UP = 3280, US = 656;
constexpr int SM_XT   = 92160;
constexpr int SM_U    = SM_XT + 8 * YP;
constexpr int SM_FAR  = SM_U + 8 * UP;
constexpr int FAR_SZ  = 12416;
constexpr int F_E5 = 0, F_O5 = 1536, F_E3 = 3088, F_O3 = 4624, F_E7 = 6176, F_E2 = F_E7 + 1024, F_E9 = F_E7 + 2048,
              F_H = 3088, F_O7 = F_E7 + F_H, F_O2 = F_E2 + F_H, F_O9 = F_E9 + F_H;
constexpr int SM_P    = SM_FAR + 5 * FAR_SZ;
constexpr int PN_SZ = 584 * 4, SM_PN = SM_P + 64 * 4;
constexpr int P_GS = 48 * 4, P_H7 = 192 * 4, P_HS = 72 * 4;
constexpr int PF_SZ = (192 + 216) * 4, SM_PF = SM_PN + 5 * PN_SZ + 32;
constexpr int SM_MISC = SM_PF + 5 * PF_SZ;
constexpr int SM_ST   = SM_MISC;
constexpr int SM_RK   = SM_ST + 2048;
constexpr int SM_SEL  = SM_RK + 256;
constexpr int SM_KG   = SM_SEL + 64;
constexpr int SM_SC   = SM_KG + 160;
constexpr int SM_DW   = SM_SC + 32;
constexpr int SM_MB   = SM_DW + 160;
constexpr int SM_TOTAL = SM_MB + 128;
constexpr int SM_ROW  = SM_XT - 20736;
constexpr int SM_XTL  = SM_ROW - 576 * XW;
constexpr int SM_RED2 = SM_WG;
constexpr int SM_HT   = SM_P - 512;
constexpr int SM_KEY  = SM_FAR + 10240 + 128;
constexpr int SM_CAND = SM_KEY + 1024;
constexpr int SM_XS   = SM_U;
constexpr int SM_GU   = SM_XS + 9344;
constexpr int SM_RED  = SM_GU + 5632;
static_assert(F_O9 + 1024 <= FAR_SZ && FAR_SZ % 128 == 0, "far overflow");
static_assert(SM_RED + 10240 <= SM_FAR && SM_HT + 20496 <= SM_MISC, "alias overflow");
static_assert(SM_TOTAL <= 232448, "smem overflow");
static_assert(SM_FAR % 128 == 0 && SM_XT % 128 == 0 && SM_XTL % 128 == 0 && SM_P % 16 == 0 && SM_MISC % 16 == 0 && SM_MB % 8 == 0, "align");

enum { MB_X = 0, MB_W1 = 5, MB_W2 = 6, MB_KEY = 7, MB_GU = 8, MB_Y = 9, MB_OUT = 10, MB_T = 11, MB_R = 12 };

struct __align__(128) Scratch {
    unsigned epoch, zcnt, pad[30];
    uint4  st1[L_ * 2];
    float4 acc[L_];
    uint4  cand[64 * NCL * 6];
    float4 fin[8 * 192 + 24];
};
__device__ Scratch g_s;
#define STAMP(i)

__device__ __forceinline__ uint32_t mapa(uint32_t a, uint32_t r) { uint32_t d; asm("mapa.shared::cluster.u32 %0, %1, %2;" : "=r"(d) : "r"(a), "r"(r)); return d; }
__device__ __forceinline__ void mbar_wait(uint32_t mb) {
    asm volatile("{ .reg .pred p, q; .reg .u32 n; mov.u32 n, 0;\n"
                 "W_%=: mbarrier.try_wait.parity.shared::cta.b64 p, [%0], 0; add.u32 n, n, 1; setp.lt.and.u32 q, n, 65536, !p; @q bra W_%=; }" :: "r"(mb) : "memory");
}
__device__ __forceinline__ void arm(uint32_t mb, uint32_t bytes) { asm volatile("mbarrier.arrive.expect_tx.shared::cta.b64 _, [%0], %1;" :: "r"(mb), "r"(bytes) : "memory"); }
__device__ __forceinline__ void bar_sync(int id, int n) { asm volatile("bar.sync %0, %1;" :: "r"(id), "r"(n) : "memory"); }
__device__ __forceinline__ void bar_arrive(int id, int n) { asm volatile("bar.arrive %0, %1;" :: "r"(id), "r"(n) : "memory"); }
__device__ __forceinline__ uint32_t lds16(uint32_t a) { unsigned short v; asm volatile("ld.shared.u16 %0, [%1];" : "=h"(v) : "r"(a) : "memory"); return v; }
__device__ __forceinline__ uint32_t lds32(uint32_t a) { uint32_t v; asm volatile("ld.shared.u32 %0, [%1];" : "=r"(v) : "r"(a) : "memory"); return v; }
__device__ __forceinline__ uint2 lds64(uint32_t a) { uint2 v; asm volatile("ld.shared.v2.u32 {%0,%1}, [%2];" : "=r"(v.x), "=r"(v.y) : "r"(a) : "memory"); return v; }
__device__ __forceinline__ float ldsf(uint32_t a) { float v; asm volatile("ld.shared.f32 %0, [%1];" : "=f"(v) : "r"(a) : "memory"); return v; }
__device__ __forceinline__ uint4 lds128(uint32_t a) { uint4 v; asm volatile("ld.shared.v4.u32 {%0,%1,%2,%3}, [%4];" : "=r"(v.x), "=r"(v.y), "=r"(v.z), "=r"(v.w) : "r"(a) : "memory"); return v; }
__device__ __forceinline__ float4 lds128f(uint32_t a) { float4 v; asm volatile("ld.shared.v4.f32 {%0,%1,%2,%3}, [%4];" : "=f"(v.x), "=f"(v.y), "=f"(v.z), "=f"(v.w) : "r"(a) : "memory"); return v; }
__device__ __forceinline__ void sts16(uint32_t a, uint32_t v) { asm volatile("{ .reg .b16 l, h; mov.b32 {l, h}, %1; st.shared.b16 [%0], l; }" :: "r"(a), "r"(v) : "memory"); }
__device__ __forceinline__ void sts32(uint32_t a, uint32_t v) { asm volatile("st.shared.u32 [%0], %1;" :: "r"(a), "r"(v) : "memory"); }
__device__ __forceinline__ void sts64(uint32_t a, uint32_t x, uint32_t y) { asm volatile("st.shared.v2.u32 [%0], {%1,%2};" :: "r"(a), "r"(x), "r"(y) : "memory"); }
__device__ __forceinline__ void stsf(uint32_t a, float v) { asm volatile("st.shared.f32 [%0], %1;" :: "r"(a), "f"(v) : "memory"); }
__device__ __forceinline__ void sts128(uint32_t a, uint32_t x, uint32_t y, uint32_t z, uint32_t w) { asm volatile("st.shared.v4.u32 [%0], {%1,%2,%3,%4};" :: "r"(a), "r"(x), "r"(y), "r"(z), "r"(w) : "memory"); }
__device__ __forceinline__ void sts128f(uint32_t a, float x, float y, float z, float w) { asm volatile("st.shared.v4.f32 [%0], {%1,%2,%3,%4};" :: "r"(a), "f"(x), "f"(y), "f"(z), "f"(w) : "memory"); }
__device__ __forceinline__ void ldsm4(uint32_t (&r)[4], uint32_t a) { asm volatile("ldmatrix.sync.aligned.m8n8.x4.shared.b16 {%0,%1,%2,%3}, [%4];" : "=r"(r[0]), "=r"(r[1]), "=r"(r[2]), "=r"(r[3]) : "r"(a) : "memory"); }
__device__ __forceinline__ void ldsm4t(uint32_t (&r)[4], uint32_t a) { asm volatile("ldmatrix.sync.aligned.m8n8.x4.trans.shared.b16 {%0,%1,%2,%3}, [%4];" : "=r"(r[0]), "=r"(r[1]), "=r"(r[2]), "=r"(r[3]) : "r"(a) : "memory"); }
__device__ __forceinline__ void ldsm2t(uint32_t& r0, uint32_t& r1, uint32_t a) { asm volatile("ldmatrix.sync.aligned.m8n8.x2.trans.shared.b16 {%0,%1}, [%2];" : "=r"(r0), "=r"(r1) : "r"(a) : "memory"); }
__device__ __forceinline__ void stsm4t(uint32_t a, uint32_t r0, uint32_t r1, uint32_t r2, uint32_t r3) { asm volatile("stmatrix.sync.aligned.m8n8.x4.trans.shared.b16 [%0], {%1,%2,%3,%4};" :: "r"(a), "r"(r0), "r"(r1), "r"(r2), "r"(r3) : "memory"); }
__device__ __forceinline__ void stsm4(uint32_t a, uint32_t r0, uint32_t r1, uint32_t r2, uint32_t r3) { asm volatile("stmatrix.sync.aligned.m8n8.x4.shared.b16 [%0], {%1,%2,%3,%4};" :: "r"(a), "r"(r0), "r"(r1), "r"(r2), "r"(r3) : "memory"); }
__device__ __forceinline__ void stsm2t(uint32_t a, uint32_t r0, uint32_t r1) { asm volatile("stmatrix.sync.aligned.m8n8.x2.trans.shared.b16 [%0], {%1,%2};" :: "r"(a), "r"(r0), "r"(r1) : "memory"); }
__device__ __forceinline__ uint4 ldg128(const void* p) { uint4 v; asm volatile("ld.global.nc.v4.u32 {%0,%1,%2,%3}, [%4];" : "=r"(v.x), "=r"(v.y), "=r"(v.z), "=r"(v.w) : "l"(p)); return v; }
__device__ __forceinline__ uint32_t ldg16(const void* p) { unsigned short v; asm volatile("ld.global.nc.u16 %0, [%1];" : "=h"(v) : "l"(p)); return v; }
__device__ __forceinline__ uint32_t opaque(uint32_t v) { uint32_t r; asm volatile("mov.b32 %0, %1;" : "=r"(r) : "r"(v)); return r; }
__device__ __forceinline__ void mma_f16(float (&d)[4], const uint32_t (&a)[4], uint32_t b0, uint32_t b1) {
    asm volatile("mma.sync.aligned.m16n8k16.row.col.f32.f16.f16.f32 {%0,%1,%2,%3}, {%4,%5,%6,%7}, {%8,%9}, {%0,%1,%2,%3};"
        : "+f"(d[0]), "+f"(d[1]), "+f"(d[2]), "+f"(d[3]) : "r"(a[0]), "r"(a[1]), "r"(a[2]), "r"(a[3]), "r"(b0), "r"(b1));
}
__device__ __forceinline__ void mma_bf16(float (&d)[4], uint32_t a0, uint32_t a1, uint32_t a2, uint32_t a3, uint32_t b0, uint32_t b1) {
    asm volatile("mma.sync.aligned.m16n8k16.row.col.f32.bf16.bf16.f32 {%0,%1,%2,%3}, {%4,%5,%6,%7}, {%8,%9}, {%0,%1,%2,%3};"
        : "+f"(d[0]), "+f"(d[1]), "+f"(d[2]), "+f"(d[3]) : "r"(a0), "r"(a1), "r"(a2), "r"(a3), "r"(b0), "r"(b1));
}
__device__ __forceinline__ void mma_bf16_k8(float (&d)[4], uint32_t a0, uint32_t a1, uint32_t b0) {
    asm volatile("mma.sync.aligned.m16n8k8.row.col.f32.bf16.bf16.f32 {%0,%1,%2,%3}, {%4,%5}, {%6}, {%0,%1,%2,%3};"
        : "+f"(d[0]), "+f"(d[1]), "+f"(d[2]), "+f"(d[3]) : "r"(a0), "r"(a1), "r"(b0));
}
__device__ __forceinline__ uint32_t pack_f16(float lo, float hi) { uint32_t r; asm("cvt.rn.f16x2.f32 %0, %1, %2;" : "=r"(r) : "f"(hi), "f"(lo)); return r; }
__device__ __forceinline__ uint32_t pack_bf16(float lo, float hi) { uint32_t r; asm("cvt.rn.bf16x2.f32 %0, %1, %2;" : "=r"(r) : "f"(hi), "f"(lo)); return r; }
__device__ __forceinline__ float bf_lo(uint32_t v) { return __uint_as_float(v << 16); }
__device__ __forceinline__ float bf_hi(uint32_t v) { return __uint_as_float(v & 0xFFFF0000u); }
__device__ __forceinline__ float bfr(float x) { return __uint_as_float(pack_bf16(0.f, x)); }
__device__ __forceinline__ uint32_t badd2(uint32_t a, uint32_t b) { uint32_t r; asm("add.rn.bf16x2 %0, %1, %2;" : "=r"(r) : "r"(a), "r"(b)); return r; }
__device__ __forceinline__ uint32_t bmul2(uint32_t a, uint32_t b) { uint32_t r; asm("mul.rn.bf16x2 %0, %1, %2;" : "=r"(r) : "r"(a), "r"(b)); return r; }
__device__ __forceinline__ uint32_t hadd2(uint32_t a, uint32_t b) { uint32_t r; asm("add.rn.f16x2 %0, %1, %2;" : "=r"(r) : "r"(a), "r"(b)); return r; }
__device__ __forceinline__ uint32_t hmul2(uint32_t a, uint32_t b) { uint32_t r; asm("mul.rn.f16x2 %0, %1, %2;" : "=r"(r) : "r"(a), "r"(b)); return r; }
__device__ __forceinline__ uint32_t hfma2(uint32_t a, uint32_t b, uint32_t c) { uint32_t r; asm("fma.rn.f16x2 %0, %1, %2, %3;" : "=r"(r) : "r"(a), "r"(b), "r"(c)); return r; }
__device__ __forceinline__ uint32_t hneg2(uint32_t a) { uint32_t r; asm("neg.f16x2 %0, %1;" : "=r"(r) : "r"(a)); return r; }
__device__ __forceinline__ float rcpf(float x) { float r; asm("rcp.approx.ftz.f32 %0, %1;" : "=f"(r) : "f"(x)); return r; }
__device__ __forceinline__ float sqrta(float x) { float r; asm("sqrt.approx.ftz.f32 %0, %1;" : "=f"(r) : "f"(x)); return r; }
__device__ __forceinline__ float ex2f(float x) { float r; asm("ex2.approx.ftz.f32 %0, %1;" : "=f"(r) : "f"(x)); return r; }
__device__ __forceinline__ void st_async4(uint32_t a, uint32_t x, uint32_t y, uint32_t z, uint32_t w, uint32_t mb) {
    asm volatile("st.async.shared::cluster.mbarrier::complete_tx::bytes.v4.u32 [%0], {%1,%2,%3,%4}, [%5];" :: "r"(a), "r"(x), "r"(y), "r"(z), "r"(w), "r"(mb) : "memory"); }
__device__ __forceinline__ void st_async1(uint32_t a, uint32_t x, uint32_t mb) {
    asm volatile("st.async.shared::cluster.mbarrier::complete_tx::bytes.u32 [%0], %1, [%2];" :: "r"(a), "r"(x), "r"(mb) : "memory"); }
__device__ __forceinline__ unsigned ld_rlx(const void* p) { unsigned v; asm volatile("ld.relaxed.gpu.global.u32 %0, [%1];" : "=r"(v) : "l"(p) : "memory"); return v; }
__device__ __forceinline__ unsigned ld_acq(const void* p) { unsigned v; asm volatile("ld.acquire.gpu.global.u32 %0, [%1];" : "=r"(v) : "l"(p) : "memory"); return v; }
__device__ __forceinline__ uint2 ld_rlx64(const void* p) { unsigned long long v; asm volatile("ld.relaxed.gpu.global.u64 %0, [%1];" : "=l"(v) : "l"(p) : "memory"); return make_uint2((unsigned)v, (unsigned)(v >> 32)); }
__device__ __forceinline__ void st_rlx128(void* p, uint32_t x, uint32_t y, uint32_t z, uint32_t w) {
    asm volatile("st.relaxed.gpu.global.v2.u64 [%0], {%1,%2};" :: "l"(p), "l"((unsigned long long)x | ((unsigned long long)y << 32)), "l"((unsigned long long)z | ((unsigned long long)w << 32)) : "memory"); }
__device__ __forceinline__ uint4 ld_rlx128(const void* p) { unsigned long long a, b; asm volatile("ld.relaxed.gpu.global.v2.u64 {%0,%1}, [%2];" : "=l"(a), "=l"(b) : "l"(p) : "memory"); return make_uint4((unsigned)a, (unsigned)(a >> 32), (unsigned)b, (unsigned)(b >> 32)); }
__device__ __forceinline__ void tma2d(uint32_t dst, const CUtensorMap* tm, int x, int y, uint32_t mb) {
    asm volatile("cp.async.bulk.tensor.2d.shared::cluster.global.mbarrier::complete_tx::bytes [%0], [%1, {%3, %4}], [%2];"
                 :: "r"(dst), "l"(tm), "r"(mb), "r"(x), "r"(y) : "memory");
}
__device__ __forceinline__ void cmul(float& xr, float& xi, float ar, float ai, float br, float bi) {
    const float r = fmaf(ar, br, -ai * bi), i = fmaf(ar, bi, ai * br); xr = r; xi = i;
}
__device__ __forceinline__ void csq(float& xr, float& xi, float ar, float ai) {
    const float r = fmaf(ar, ar, -ai * ai), i = (ar + ar) * ai; xr = r; xi = i;
}
__device__ __forceinline__ void cexp_s(float& zr, float& zi, float e2, float turns) {
    const float mag = ex2f(e2), r = (turns - rintf(turns)) * 6.283185307179586f;
    zr = mag * __cosf(r); zi = mag * __sinf(r);
}
__device__ __forceinline__ uint32_t ln_stats(float s1, float s2) {
    const float m = s1 * (1.f / D_);
    const float var = fmaxf(fmaf(s2, 1.f / D_, -m * m), 0.f);
    return pack_bf16(m, sqrta(bfr(bfr(var) + 1e-5f)));
}
__device__ __forceinline__ uint32_t rsplit(float rs) { const float h = bfr(rs); return pack_bf16(h, rs - h); }
__device__ __forceinline__ uint32_t norm2(uint32_t v, uint32_t mx, uint32_t hl) {
    uint32_t r;
    asm("{ .reg .b16 m, h, l, x; .reg .b32 m2, h2, l2, d, t; mov.b32 {m, x}, %2; mov.b32 {h, l}, %3; mov.b32 m2, {m, m}; mov.b32 h2, {h, h}; mov.b32 l2, {l, l};\n"
        "sub.rn.bf16x2 d, %1, m2; mul.rn.bf16x2 t, d, l2; fma.rn.bf16x2 %0, d, h2, t; }" : "=r"(r) : "r"(v), "r"(mx), "r"(hl));
    return r;
}
template <int N, int S>
__device__ __forceinline__ uint32_t rank4(uint32_t a, uint32_t key) {
    uint32_t r0 = 0, r1 = 0, r2 = 0, r3 = 0;
#pragma unroll
    for (int i = 0; i < N; i++) {
        const uint4 o = lds128(a + i * S);
        r0 += (key - o.x) >> 31; r1 += (key - o.y) >> 31; r2 += (key - o.z) >> 31; r3 += (key - o.w) >> 31;
    }
    return (r0 + r1) + (r2 + r3);
}
typedef uint32_t H2C;
__device__ __forceinline__ H2C splat(float r, float i) { return pack_f16(r, i); }
__device__ __forceinline__ void hcmul(uint32_t& xr, uint32_t& xi, uint32_t R, uint32_t I, H2C m) {
    asm("{ .reg .b16 a, b; .reg .b32 a2, b2, t; mov.b32 {a, b}, %4; mov.b32 a2, {a, a}; mov.b32 b2, {b, b};\n"
        "mul.rn.f16x2 t, %3, b2; neg.f16x2 t, t; fma.rn.f16x2 %0, %2, a2, t; mul.rn.f16x2 t, %3, a2; fma.rn.f16x2 %1, %2, b2, t; }"
        : "=&r"(xr), "=r"(xi) : "r"(R), "r"(I), "r"(m));
}
__device__ __forceinline__ void expand4(uint32_t are, uint32_t aim, uint32_t R0, uint32_t R1, uint32_t I0, uint32_t I1, H2C m4) {
    uint32_t R2, I2, R3, I3;
    hcmul(R2, I2, R0, I0, m4); hcmul(R3, I3, R1, I1, m4);
    sts128(are, R0, R1, R2, R3);
    sts128(aim, I0, I1, I2, I3);
}
__device__ __forceinline__ void expand8(uint32_t are, uint32_t aim, float sr, float si, float m1r, float m1i, float m2r, float m2i, H2C m4) {
    float r1, i1, r2, i2, r3, i3;
    cmul(r1, i1, sr, si, m1r, m1i); cmul(r2, i2, sr, si, m2r, m2i); cmul(r3, i3, r1, i1, m2r, m2i);
    expand4(are, aim, pack_f16(sr, r1), pack_f16(r2, r3), pack_f16(si, i1), pack_f16(i2, i3), m4);
}
__device__ __forceinline__ void put16(uint32_t a, uint32_t v) { sts16(a, v); sts16(a + 6, v); }

struct Params {
    const unsigned short *logdt, *dskip, *prm6[6], *x, *wr;
    __nv_bfloat16* out;
    Scratch* gs;
    unsigned zero;
};
__device__ __forceinline__ uint32_t tslot(uint32_t t) { return (t & 7) * 32 + ((t >> 4) & 24) + ((t >> 8) & 6) + ((t >> 6) & 1); }
#define CP(x) ((x) | zero)
#define PIN(x) asm volatile("or.b32 %0, %0, %1;" : "+r"(x) : "r"(zero))
__device__ __forceinline__ void wgmma32(float (&d)[4][4], const uint32_t (&a)[4], uint32_t dlo) {
    asm volatile("{ .reg .b64 ds; mov.b64 ds, {%20, %21};\n"
                 "wgmma.mma_async.sync.aligned.m64n32k16.f32.f16.f16 {%0,%1,%2,%3,%4,%5,%6,%7,%8,%9,%10,%11,%12,%13,%14,%15}, {%16,%17,%18,%19}, ds, 1, 1, 1, 0; }"
        : "+f"(d[0][0]), "+f"(d[0][1]), "+f"(d[0][2]), "+f"(d[0][3]), "+f"(d[1][0]), "+f"(d[1][1]), "+f"(d[1][2]), "+f"(d[1][3]),
          "+f"(d[2][0]), "+f"(d[2][1]), "+f"(d[2][2]), "+f"(d[2][3]), "+f"(d[3][0]), "+f"(d[3][1]), "+f"(d[3][2]), "+f"(d[3][3])
        : "r"(a[0]), "r"(a[1]), "r"(a[2]), "r"(a[3]), "r"(dlo), "n"(128 >> 4));
}

__global__ void __cluster_dims__(CS, 1, 1) __launch_bounds__(NTHR, 1)
fused_kernel(const __grid_constant__ Params prm, const __grid_constant__ CUtensorMap tmG, const __grid_constant__ CUtensorMap tmU,
             const __grid_constant__ CUtensorMap tmD, const __grid_constant__ CUtensorMap tmO, const __grid_constant__ CUtensorMap tmX, const __grid_constant__ CUtensorMap tmH)
{
    extern __shared__ __align__(1024) unsigned char smem[];
    const int tid = threadIdx.x, lane = tid & 31, warp = __shfl_sync(~0u, tid >> 5, 0);
    const int c = blockIdx.x >> 3, q = blockIdx.x & 7;
    const int nslot = (c < NCL - 1) ? 5 : 2;
    const int d0 = 40 * c;
    const uint32_t sb = opaque((uint32_t)__cvta_generic_to_shared(smem));
    const uint32_t mb = sb + SM_MB;
    Scratch& g_s = *prm.gs;
    const unsigned& zero = prm.zero;
    STAMP(0);

    if (warp >= 20) {
        unsigned epoch = 0;
        if (warp == 20) {
            if (lane == 0) {
#pragma unroll
                for (int i = 0; i < 13; i++)
                    asm volatile("mbarrier.init.shared::cta.b64 [%0], %1;" :: "r"(mb + i * 8), "r"((i == MB_R || i < 2) ? 2 : i == MB_Y ? 1 + 4 * nslot : 1) : "memory");
                asm volatile("fence.mbarrier_init.release.cluster;" ::: "memory");
                arm(mb + MB_W1 * 8, 92160); arm(mb + MB_W2 * 8, nslot * (128 * W2W)); arm(mb + MB_KEY * 8, 256); arm(mb + MB_GU * 8, nslot * 1024); arm(mb + MB_T * 8, 576 * XW);
                const int bytes = max(min(18, L_ - 18 * (int)blockIdx.x), 1) * (D_ * 2);
                arm(mb + MB_R * 8, bytes);
            }
            __syncwarp();
        } else if (warp == 22) {
            epoch = ld_rlx(&g_s.epoch);
            if (lane < 18 ? 18 * c + lane < 256 : lane < 31) (lane < 18 ? &g_s.acc[256 * q + 18 * c] : &g_s.fin[13 * (int)blockIdx.x - 18])[lane] = make_float4(0.f, 0.f, 0.f, 0.f);
        } else if (warp == 23 && lane == 0) asm volatile("prefetch.tensormap [%0];" :: "l"(&tmX) : "memory");
        asm volatile("barrier.cluster.arrive.relaxed.aligned;" ::: "memory");
        bar_sync(12, NTHR);
        if (warp == 22) {
            if (lane == 0) { sts32(sb + SM_SC + 28, epoch); asm volatile("mbarrier.arrive.shared::cta.b64 _, [%0];" :: "r"(mb + MB_R * 8) : "memory"); }
            epoch++;
            asm volatile("fence.acq_rel.gpu;" ::: "memory");
            __syncwarp();
            if (lane == 0) asm volatile("red.relaxed.gpu.global.add.u32 [%0], 1;" :: "l"(&g_s.zcnt) : "memory");
            STAMP(1);
            uint4 wv = make_uint4(0, 0, 0, 0), wv2 = ldg128((const uint4*)prm.wr + lane), wv3 = ldg128((const uint4*)prm.wr + 32 + lane);
            if (lane < 8) wv = ldg128((const uint4*)prm.wr + 64 + lane);
            if (lane < 5) {
                uint4 v = make_uint4(0, 0, 0, 0);
                if (lane < nslot) v = ldg128((const uint4*)(prm.wr + d0) + lane);
                sts128(sb + SM_DW + lane * 16, v.x, v.y, v.z, v.w);
            }
            __syncwarp();
            if (lane < 2) asm volatile("mbarrier.arrive.shared::cta.b64 _, [%0];" :: "r"(mb + (MB_X + lane) * 8) : "memory");
            mbar_wait(mb + (MB_X + 1) * 8);
            const uint32_t old = (epoch & 1) ? 0u : 0x40004000u;
#pragma unroll
            for (int t = 0; t < 2; t++)
                if ((lane & 7) < 6) g_s.cand[((q * 8 + 4 * t + (lane >> 3)) * NCL + c) * 6 + (lane & 7)] = make_uint4(old, old, old, old);
            float a[4] = {0.f, 0.f, 0.f, 0.f};
            const uint32_t one = 0x3F803F80u;
            mma_bf16(a, one, one, one, one, wv.x, wv.y);  mma_bf16(a, one, one, one, one, wv.z, wv.w);
            mma_bf16(a, one, one, one, one, wv2.x, wv2.y); mma_bf16(a, one, one, one, one, wv2.z, wv2.w);
            mma_bf16(a, one, one, one, one, wv3.x, wv3.y); mma_bf16(a, one, one, one, one, wv3.z, wv3.w);
            float s = a[0] + a[1];
            s += __shfl_xor_sync(~0u, s, 1); s += __shfl_xor_sync(~0u, s, 2);
            stsf(sb + SM_SC + 24, s);
            __syncwarp();
            if (lane == 0) {
                int n = 0;
                while ((int)(ld_acq(&g_s.zcnt) - epoch * NCTA) < 0 && ++n < SPIN_LIMIT) __nanosleep(200);
                arm(mb + MB_Y * 8, 8 * 512 * nslot);
                if (blockIdx.x == 0) g_s.epoch = epoch;
            }
            STAMP(2);
            return;
        }
        if (warp == 21) {
            if (lane == 0) { asm volatile("prefetch.tensormap [%0];" :: "l"(&tmG) : "memory"); asm volatile("prefetch.tensormap [%0];" :: "l"(&tmU) : "memory"); asm volatile("prefetch.tensormap [%0];" :: "l"(&tmD) : "memory"); }
            __syncwarp();
            bar_sync(13, 736);
            asm volatile("fence.proxy.async.shared::cta;" ::: "memory");
#pragma unroll 1
            for (int i = 0; i < 24; i++) {
                if (lane == 0) tma2d(sb + SM_WG + i * 3840, i < 12 ? &tmG : &tmU, 320 * c + 8 * nslot * q, 48 * (i < 12 ? i : i - 12), mb + MB_W1 * 8);
            }
            STAMP(1);
            return;
        }
        if (warp == 20) {
            if (lane == 0) {
                asm volatile("cp.async.bulk.shared::cluster.global.mbarrier::complete_tx::bytes [%0], [%1], %2, [%3];"
                             :: "r"(sb + SM_ROW), "l"(prm.x + min(18 * (int)blockIdx.x, L_ - 1) * D_), "r"(max(min(18, L_ - 18 * (int)blockIdx.x), 1) * (D_ * 2)), "r"(mb + MB_R * 8) : "memory");
            }
            __syncwarp();
            if (TILE_NS < 0) mbar_wait(mb + MB_R * 8); else if (TILE_NS) __nanosleep(TILE_NS);
            if (lane == 0) {
                asm volatile("cp.async.bulk.tensor.5d.shared::cluster.global.mbarrier::complete_tx::bytes [%0], [%1, {%3, %4, %5, %5, %5}], [%2];"
                             :: "r"(sb + SM_XTL), "l"(&tmX), "r"(mb + MB_T * 8), "r"(XW == 40 ? d0 : d0 & ~15), "r"(8 * q), "r"(0) : "memory");
            }
            STAMP(6);
        }
        asm volatile("barrier.cluster.wait.aligned;" ::: "memory");
        bar_sync(13, 736);
        asm volatile("fence.proxy.async.shared::cta;" ::: "memory");
        {
            const int gr = lane >> 2, pe = XROT ? ((lane & 3) * 2 + (warp & 1) + q + 1) & 7 : (((lane & 3) ^ (gr * 3)) * 2 + (warp & 1)) & 7;
            const int s0 = gr ? 0 : XSPLIT, ns = gr ? min(XSPLIT, nslot) : nslot - XSPLIT;
            if (gr < 2 && ns > 0) {
                const int bytes = ns * YS - 144;
                if (pe == q) arm(mb + (MB_X + gr) * 8, 7 * bytes);
                else {
                    const uint32_t rb_ = mapa(sb, pe);
                    asm volatile("cp.async.bulk.shared::cluster.shared::cta.mbarrier::complete_tx::bytes [%0], [%1], %2, [%3];"
                                 :: "r"(rb_ + SM_U + 128 + q * UP + s0 * US), "r"(sb + SM_XT + 128 + (q & 3) * 16 + pe * YP + s0 * YS), "r"(bytes), "r"(rb_ + SM_MB + (MB_X + gr) * 8) : "memory");
                }
            }
        }
        STAMP(1);
        if (warp == 20 && lane == 0) { asm volatile("prefetch.tensormap [%0];" :: "l"(&tmO) : "memory"); asm volatile("prefetch.tensormap [%0];" :: "l"(&tmH) : "memory"); }
        if (warp == 23) {
#pragma unroll 1
            for (int kk = nslot - 1; kk >= 0; kk--) {
                __syncwarp();
                bar_sync(6 + kk, 160);
                if (lane == 0) { asm volatile("fence.proxy.async.shared::cta;" ::: "memory"); tma2d(sb + SM_FAR + kk * FAR_SZ, &tmD, W2W == 72 ? 72 * q : (72 * q) & ~15, 320 * c + 64 * kk, mb + MB_W2 * 8); }
            }
            return;
        }
        __syncwarp();
        bar_sync(14, 672);
        if (lane == 0) {
            asm volatile("fence.proxy.async.shared::cta;" ::: "memory");
            asm volatile("cp.async.bulk.tensor.5d.global.shared::cta.bulk_group [%0, {%2, %4, %4, %4, %3}], [%1];" :: "l"(&tmH), "r"(sb + SM_XT + 16384), "r"(d0 + ((c & 1) ? 0 : 32)), "r"(8 * q), "r"(0) : "memory");
            asm volatile("cp.async.bulk.tensor.5d.global.shared::cta.bulk_group [%0, {%2, %4, %4, %4, %3}], [%1];" :: "l"(&tmO), "r"(sb + SM_XT), "r"(d0 + (c & 1) * 8), "r"(8 * q), "r"(0) : "memory");
            asm volatile("cp.async.bulk.commit_group;" ::: "memory");
            asm volatile("cp.async.bulk.wait_group 0;" ::: "memory");
            asm volatile("fence.proxy.async.global;" ::: "memory");
            asm volatile("mbarrier.arrive.shared::cta.b64 _, [%0];" :: "r"(mb + MB_OUT * 8) : "memory");
        }
        STAMP(2);
        return;
    }

    const int g = lane >> 2, cq = lane & 3;
    const int k = warp >> 2, wq = warp & 3;
    const int trow = 18 * blockIdx.x + warp;
    const bool rowact = warp < 18 && trow < L_;
    const int dch = min(d0 + 8 * k + q, D_ - 1);
    uint32_t pv[6];
#pragma unroll
    for (int i = 0; i < 6; i++) pv[i] = ldg16(prm.prm6[i] + (uint32_t)(dch * 128 + wq * 32 + lane));
    const uint32_t pLdt = ldg16(prm.logdt + dch), pD = ldg16(prm.dskip + dch);
    const int tn = 16 * (warp & 15) + g;
    uint32_t xa[5], xb[5];
    asm volatile("barrier.cluster.arrive.relaxed.aligned;" ::: "memory");
    uint4* const st1p = &g_s.st1[(((trow >> 3) & 7) * 256 + ((trow >> 6) & 31) * 8 + (trow & 7)) * 2 + (lane >> 2)];
    const bool pub = rowact && (lane & 0x1B) == 0;
    if (pub) st_rlx128(st1p, 0, 0, 0, 0);
    {
        const uint32_t za = sb + SM_P + tid * 16;
        sts128(za, 0, 0, 0, 0);
        if (tid < (SM_MISC - SM_P) / 16 - 640) sts128(za + 10240, 0, 0, 0, 0);
        sts128(sb + ((wq & 2) ? SM_U : SM_XT + (q & 3) * 16) + ((tid >> 3) & 7) * ((wq & 2) ? UP : YP) + k * YS + (lane & 7) * 16, 0, 0, 0, 0);
    }
    bar_sync(12, NTHR);
    const uint32_t dep = lds32(sb + SM_P);
#define PV(x) __uint_as_float(__byte_perm(dep, x, 0x5410))
    STAMP(1);
    const uint32_t fb = sb + SM_FAR + k * FAR_SZ;
    const uint32_t pn = sb + SM_PN + k * PN_SZ, pf = sb + SM_PF + k * PF_SZ;
    unsigned epoch;
    {
        const uint32_t kb = fb + wq * 3072;
        const uint32_t kl = kb + lane * 16;
        uint32_t Af[4][4];
        float sr, si, z1r, z1i, z2r, z2i, z4r, z4i, hr, hi_;
        {
            const float dt = bfr(ex2f(PV(pLdt) * 1.4426950408889634f));
            const float e2 = dt * PV(pv[0]) * 1.4426950408889634f, an = dt * PV(pv[1]);
            cmul(sr, si, PV(pv[4]), PV(pv[5]), dt * PV(pv[2]), dt * PV(pv[3]));
            const unsigned E = min(max(__reduce_max_sync(~0u, __float_as_uint(fmaxf(fmaxf(fabsf(sr), fabsf(si)), fabsf(PV(pD)) * (1.f / 8192.f)))) >> 23, 1u), 253u);
            const float sc = __uint_as_float((254u - E) << 23);
            sr *= sc; si *= -sc;
            sts64(sb + SM_KG + warp * 8, E, __reduce_add_sync(~0u, __float2int_rn(sr * 16777216.f)));
            float ar, ai, br, bi, cr, ci, dr, di;
            { const float m = ex2f(e2 * 8.f); ar = m * __cosf(an * 8.f); ai = m * __sinf(an * 8.f); }
            csq(br, bi, ar, ai); csq(cr, ci, br, bi); csq(dr, di, cr, ci);
            const H2C m4 = splat(cr, ci);
            {
                float r3, i3;
                cmul(r3, i3, ar, ai, br, bi);
                expand4(kl, kl + 1024, pack_f16(1.f, ar), pack_f16(br, r3), pack_f16(0.f, ai), pack_f16(bi, i3), m4);
            }
            expand8(kl + 512, kl + 1536, dr, di, ar, ai, br, bi, m4);
            { const float m = ex2f(e2); z1r = m * __cosf(an); z1i = -m * __sinf(an); }
            cexp_s(hr, hi_, e2 * 128.f, an * (-128.f * 0.15915494309189535f));
            csq(z2r, z2i, z1r, z1i); csq(z4r, z4i, z2r, z2i);
        }
        __syncwarp();
#pragma unroll
        for (int ks = 0; ks < 4; ks++) ldsm4t(Af[ks], kb + (lane >> 3) * 512 + (lane & 7) * 16 + ks * 128);
        STAMP(2);
        const uint32_t la = kb + ((lane >> 3) & 1) * 512 + (lane >> 4) * 128 + (lane & 7) * 16;
        uint32_t kp[5][2], b0[4], b1[4], b2[4], b3[4];
        auto mm2 = [&](int t) {
            float a0[4] = {0.f, 0.f, 0.f, 0.f}, a1[4] = {0.f, 0.f, 0.f, 0.f};
            mma_f16(a0, Af[0], b0[0], b0[1]); mma_f16(a1, Af[0], b2[0], b2[1]); mma_f16(a0, Af[1], b0[2], b0[3]); mma_f16(a1, Af[1], b2[2], b2[3]);
            mma_f16(a0, Af[2], b1[0], b1[1]); mma_f16(a1, Af[2], b3[0], b3[1]); mma_f16(a0, Af[3], b1[2], b1[3]); mma_f16(a1, Af[3], b3[2], b3[3]);
            kp[t][0] = pack_f16(a0[1], a0[0]); kp[t][1] = pack_f16(a0[3], a0[2]); kp[t + 1][0] = pack_f16(a1[1], a1[0]); kp[t + 1][1] = pack_f16(a1[3], a1[2]);
        };
        auto ln1 = [&]() {
        mbar_wait(mb + MB_R * 8);
        epoch = lds32(sb + SM_SC + 28) + 1;
        {
            const uint32_t ra = sb + SM_ROW + warp * (D_ * 2);
            const uint4 r0 = lds128(ra + lane * 16), r1 = lds128(ra + 512 + lane * 16);
            const uint32_t rx[9] = {r0.x, r0.y, r0.z, r0.w, r1.x, r1.y, r1.z, r1.w, lds32(ra + 1024 + lane * 4)};
            float a0 = bf_lo(rx[0]), a1 = bf_hi(rx[0]), c0 = a0 * a0, c1 = a1 * a1;
#pragma unroll
            for (int i = 1; i < 9; i++) { const float l = bf_lo(rx[i]), h = bf_hi(rx[i]); a0 += l; a1 += h; c0 = fmaf(l, l, c0); c1 = fmaf(h, h, c1); }
            a0 += a1; c0 += c1;
            float s1 = ((lane & 1) ? c0 : a0) + __shfl_xor_sync(~0u, (lane & 1) ? a0 : c0, 1);
#pragma unroll
            for (int o = 2; o < 32; o <<= 1) s1 += __shfl_xor_sync(~0u, s1, o);
            const float s2 = __shfl_xor_sync(~0u, s1, 1);
            const uint32_t ms = ln_stats(s1, s2);
            const uint32_t p0 = __byte_perm(ms, epoch | 0x8000u, 0x5410), p1 = rsplit(rcpf(bf_hi(ms)));
            if (pub) st_rlx128(st1p, p0, p1, p0, p1);
        }
        mbar_wait(mb + MB_R * 8);
        STAMP(1);
        };
        const uint4* sp = &g_s.st1[(256 * q + tn) * 2];
        uint2 sa, sc;
        auto poll = [&]() { sa = ld_rlx64(sp); sc = ld_rlx64(sp + 16); };
        auto norm = [&]() {
        STAMP(3);
        if (warp < 16) {
            uint32_t va[5], vc[5];
            poll();
            mbar_wait(mb + MB_T * 8);
            {
                const uint32_t xt = sb + SM_XTL + (XW == 40 ? 0 : (c & 1) * 16) + (72 * wq + 18 * k + g) * (2 * XW);
                uint4 a4 = lds128(xt + cq * 16), b4 = lds128(xt + cq * 16 + 18 * XW);
                va[0] = a4.x; va[1] = a4.y; va[2] = a4.z; va[3] = a4.w; va[4] = lds32(xt + 64 + cq * 4);
                vc[0] = b4.x; vc[1] = b4.y; vc[2] = b4.z; vc[3] = b4.w; vc[4] = lds32(xt + (64 + 18 * XW) + cq * 4);
            }
            const int d4 = 2 * (lane >> 3) + (lane & 1), d1_ = lane & 7;
            const uint32_t own = SM_U + 128 + q * (UP - YP), oth = SM_XT + 128 + (q & 3) * 16;
            uint32_t a4 = sb + warp * 32 + d4 * YP + (d4 == q ? own : oth) + ((lane & 7) >> 1) * YS;
            uint32_t a1 = sb + warp * 32 + d1_ * YP + (d1_ == q ? own : oth) + 4 * YS + (lane & 8) * 2;
            PIN(a4); PIN(a1);
            uint32_t tag = __byte_perm(epoch | 0x8000u, 0, 0x1010);
            PIN(tag);
            mbar_wait(mb + MB_T * 8);
            int n = 0;
            while (__byte_perm(sa.x, sc.x, 0x7632) != tag && ++n < SPIN_LIMIT) poll();
            STAMP(4);
#pragma unroll
            for (int i = 0; i < 5; i++) {
                va[i] = norm2(va[i], sa.x, sa.y); va[i] = pack_f16(bf_lo(va[i]), bf_hi(va[i]));
                vc[i] = norm2(vc[i], sc.x, sc.y); vc[i] = pack_f16(bf_lo(vc[i]), bf_hi(vc[i]));
            }
            stsm4t(a4, va[0], va[1], va[2], va[3]); stsm4t(a4 + 16, vc[0], vc[1], vc[2], vc[3]); stsm2t(a1, va[4], vc[4]);
            {
            const uint32_t xh = sb + SM_XTL + (XW == 40 ? 0 : (c & 1) * 16) + (9 * g + 144 * (warp & 1) + (warp >> 1)) * (2 * XW);
            const uint4 c4 = lds128(xh + cq * 16), d4_ = lds128(xh + cq * 16 + 144 * XW);
            xa[0] = c4.x; xa[1] = c4.y; xa[2] = c4.z; xa[3] = c4.w; xa[4] = lds32(xh + 64 + cq * 4);
            xb[0] = d4_.x; xb[1] = d4_.y; xb[2] = d4_.z; xb[3] = d4_.w; xb[4] = lds32(xh + (64 + 144 * XW) + cq * 4);
            }
        }
        STAMP(5);
        bar_sync(13, 736);
        Af[0][0] |= lds32(sb + SM_P);
        };
        if (LNPOS == 0) ln1();
        cmul(sr, si, sr, si, z1r, z1i);
        {
            const H2C h4 = splat(z4r, z4i);
            expand8(kl, kl + 512, sr, si, z1r, z1i, z2r, z2i, h4);
            cmul(sr, si, sr, si, hr, hi_);
            expand8(kl + 1024, kl + 1536, sr, si, z1r, z1i, z2r, z2i, h4);
        }
        __syncwarp();
        ldsm4t(b0, la); ldsm4t(b1, la + 256); ldsm4t(b2, la + 1024); ldsm4t(b3, la + 1280);
        cmul(z1r, z1i, z1r, z1i, hr, hi_);
        cmul(sr, si, sr, si, z1r, z1i);
        if (LNPOS == 1) ln1();
        expand8(kl, kl + 512, sr, si, z2r, z2i, z4r, z4i, splat(hr, hi_));
        if (LNPOS == 2) ln1();
        csq(z1r, z1i, z1r, z1i);
        cmul(sr, si, sr, si, z1r, z1i);
        csq(z2r, z2i, hr, hi_);
        expand8(kl + 1024, kl + 1536, sr, si, z4r, z4i, hr, hi_, splat(z2r, z2i));
        if (LNPOS == 3) ln1();
        csq(z1r, z1i, z1r, z1i);
        cmul(sr, si, sr, si, z1r, z1i);
        csq(z4r, z4i, z2r, z2i);
        expand8(kl + 2048, kl + 2560, sr, si, hr, hi_, z2r, z2i, splat(z4r, z4i));
        if (LNPOS == 4) ln1();
        if (MMPOS == 0) norm();
        mm2(0);
        __syncwarp();
        ldsm4t(b0, la); ldsm4t(b1, la + 256); ldsm4t(b2, la + 1024); ldsm4t(b3, la + 1280);
        if (MMPOS == 1) norm();
        mm2(2);
        if (MMPOS == 2) norm();
        ldsm4t(b0, la + 2048); ldsm4t(b1, la + 2304);
#pragma unroll
        for (int t = 0; t < 4; t++) sts64(kb + lane * 8 + 1024 + t * 256, kp[t][0], kp[t][1]);
        {
            float a0[4] = {0.f, 0.f, 0.f, 0.f}, a1[4] = {0.f, 0.f, 0.f, 0.f};
            mma_f16(a0, Af[0], b0[0], b0[1]); mma_f16(a1, Af[1], b0[2], b0[3]); mma_f16(a0, Af[2], b1[0], b1[1]); mma_f16(a1, Af[3], b1[2], b1[3]);
            sts64(kb + lane * 8 + 2048, pack_f16(a0[1] + a1[1], a0[0] + a1[0]), pack_f16(a0[3] + a1[3], a0[2] + a1[2]));
        }
        bar_sync(1 + k, 128);
        const uint4 m01 = lds128(sb + SM_KG + k * 32), m23 = lds128(sb + SM_KG + k * 32 + 16);
        const unsigned Em = max(max(m01.x, m01.z), max(m23.x, m23.z));
        const float f0 = __uint_as_float(max((int)(127 + m01.x - Em), 0) << 23), f1 = __uint_as_float(max((int)(127 + m01.z - Em), 0) << 23),
                    f2 = __uint_as_float(max((int)(127 + m23.x - Em), 0) << 23), f3 = __uint_as_float(max((int)(127 + m23.z - Em), 0) << 23);
        const uint32_t r0 = pack_f16(f0, f0), r1 = pack_f16(f1, f1), r2 = pack_f16(f2, f2), r3 = pack_f16(f3, f3);
        const uint32_t ra = fb + lane * 8 + wq * 256 + 1024;
        const uint2 p0 = lds64(ra), p1 = lds64(ra + 3072), p2 = lds64(ra + 6144), p3 = lds64(ra + 9216);
        uint32_t w0 = hadd2(hfma2(p0.x, r0, hmul2(p1.x, r1)), hfma2(p2.x, r2, hmul2(p3.x, r3)));
        uint32_t w1 = hadd2(hfma2(p0.y, r0, hmul2(p1.y, r1)), hfma2(p2.y, r2, hmul2(p3.y, r3)));
        const bool last = lane == 31;
        if (wq < 2) {
            const uint32_t rc = fb + lane * 8 + wq * 4 + 2048;
            const uint32_t w4 = hmul2(hadd2(hfma2(lds32(rc), r0, hmul2(lds32(rc + 3072), r1)), hfma2(lds32(rc + 6144), r2, hmul2(lds32(rc + 9216), r3))), 0x18001800u);
            const uint32_t ph = pf + (P_H7 + 16 * wq) + (g & 1) * (2 * P_HS) + cq * 64 + (g >> 1) * 4;
            put16(ph, w4 >> 16); put16(ph + 32, w4);
            const uint32_t pa = pn + (4 + 512 * wq) + lane * 8;
            sts16(pa, w0 >> 16); sts32(pa + 4, w0); sts16(pa + 10, w0);
            sts16(pa + 256, w1 >> 16); sts32(pa + 260, w1); sts16(pa + 266, w1);
            if (last) {
                sts32(sb + SM_SC + k * 4, Em * 0x00800080u);
                put16(wq ? pa + 264 : pn,
                      wq ? w1 : pack_f16(((float)(int)m01.y * f0 + (float)(int)m01.w * f1 + (float)(int)m23.y * f2 + (float)(int)m23.w * f3) * (1.f / 16777216.f)
                                         + __uint_as_float(pD << 16) * __uint_as_float((254u - Em) << 23), 0.f));
            }
        } else if (wq == 2) {
            const uint32_t pa = pn + 258 * 4 + (cq & 1) * 16 + (cq >> 1) * 512 + g * 32;
            if (last) { put16(pf, hmul2(w1, 0x18001800u)); w1 = hadd2(w1, hneg2(__byte_perm(w1, 0, 0x1010))); }
            const uint32_t b0 = __byte_perm(w0, 0, 0x1010), b1 = __byte_perm(w1, 0, 0x1010);
            sts16(pa, w0 >> 16); sts32(pa + 4, w0); sts64(pa + 8, b0, b0); sts16(pa + 18, w0);
            sts16(pa + 256, w1 >> 16); sts32(pa + 260, w1); sts64(pa + 264, b1, b1); sts16(pa + 274, w1);
        } else {
            const uint32_t pa = pf + ((g & 1) ? 3 * P_GS : P_GS) + cq * 32 + (g >> 1) * 4;
            const uint32_t pb = pa + ((g & 1) ? 4 - 3 * P_GS : P_GS);
            w0 = hmul2(w0, 0x18001800u); w1 = hmul2(w1, 0x18001800u);
            put16(pa, w0 >> 16); put16(pb, w0); put16(pa + 16, w1 >> 16); put16(pb + 16, w1);
            if (last) put16(pf + P_H7 + P_HS, w1);
        }
        bar_sync(1 + k, 128);
    }
    STAMP(6);

    asm volatile("barrier.cluster.wait.aligned;" ::: "memory");
    mbar_wait(mb + (MB_X + (k < XSPLIT || k >= nslot)) * 8);
    STAMP(7);
    if (k < nslot) {
        const int role = (wq + k) & 3;
        const uint32_t ub = sb + SM_U + k * US + 128;
        if (role) {
            const int r = (3 - role) * 32 + lane;
            const uint32_t a1 = ub + (r & 3) * (2 * UP) + (r >> 2) * 16, a0 = a1 + ((r & 3) ? -2 * UP : 6 * UP - 16);
            const uint4 q0 = lds128(a0), q1 = lds128(a0 + UP), q2 = lds128(a1), q3 = lds128(a1 + UP);
            const uint32_t U[16] = {q0.x, q0.y, q0.z, q0.w, q1.x, q1.y, q1.z, q1.w, q2.x, q2.y, q2.z, q2.w, q3.x, q3.y, q3.z, q3.w};
            uint32_t V[14], Q[14], R4[12], T[8];
#pragma unroll
            for (int i = 2; i < 14; i++) { V[i] = __byte_perm(U[i], U[i + 1], 0x5432); Q[i] = hadd2(U[i], V[i]); }
#pragma unroll
            for (int i = 2; i < 12; i++) R4[i] = hadd2(Q[i], Q[i + 1]);
            const uint32_t rb = fb + r * 16;
#pragma unroll
            for (int i = 0; i < 8; i++) T[i] = hadd2(V[5 + i], Q[6 + i]);
            sts128(rb + F_E3, T[0], T[1], T[2], T[3]); sts128(rb + F_O3 + 16, T[4], T[5], T[6], T[7]);
#pragma unroll
            for (int i = 0; i < 8; i++) T[i] = hadd2(R4[3 + i], U[5 + i]);
            sts128(rb + F_O5, T[0], T[1], T[2], T[3]); sts128(rb + F_E5, T[4], T[5], T[6], T[7]);
            if (role != 1) {
#pragma unroll
                for (int i = 0; i < 8; i++) T[i] = hadd2(T[i], hadd2(V[2 + i], V[5 + i]));
                sts128(rb + F_E7, T[0], T[1], T[2], T[3]); sts128(rb + F_O7, T[4], T[5], T[6], T[7]);
#pragma unroll
                for (int i = 0; i < 8; i++) T[i] = hadd2(R4[2 + i], hadd2(R4[4 + i], U[6 + i]));
                sts128(rb + F_O9, T[0], T[1], T[2], T[3]); sts128(rb + F_E9 + 16, T[4], T[5], T[6], T[7]);
                sts128(rb + F_E2, Q[6], Q[7], Q[8], Q[9]); sts128(rb + F_O2, Q[10], Q[11], Q[12], Q[13]);
            }
        } else if (lane < 8) {
            uint32_t v[5];
#pragma unroll
            for (int i = 0; i < 5; i++) { const int t = 6 + lane + i; v[i] = lds16(ub + 23 * 16 + (t < 16 ? (6 + (t >> 3)) * UP : 16) + (t & 7) * 2); }
            const uint32_t s = hadd2(hadd2(hadd2(v[0], v[1]), hadd2(v[2], v[3])), v[4]);
            sts16(fb + F_O5 + 96 * 16 + lane * 2, s);
            sts32(fb + (lane < 4 ? F_O3 : F_E9 - 16) + lane * 4, 0);
        }
        bar_sync(1 + k, 128);
        float acc[4][4];
        uint32_t Q[4][4];
        {
            const int h = role & 1, part = role >> 1;
            const uint32_t po = pf + (g - 2 * cq) * 4;
            float fa[7][4];
#pragma unroll
            for (int a = 0; a < 7; a++) fa[a][0] = fa[a][1] = fa[a][2] = fa[a][3] = 0.f;
            uint32_t B[3][4];
            Q[0][2] = zero;
#pragma unroll 1
            for (int s = 2 * part + 1; s >= 2 * part; s--) {
#pragma unroll
                for (int i = 0; i < 3; i++) { Q[i][0] = lds32(po + s * P_GS + i * 64); Q[i][1] = lds32(po + s * P_GS + (i * 64 + 32)); }
                const uint32_t ba = fb + lane * 16 + ((s & 1) * F_E3 + (part == h ? 0 : F_O5 + h * 16));
#pragma unroll
                for (int i = 0; i < 3; i++) ldsm4t(B[i], ba + i * 512);
#pragma unroll
                for (int i = 0; i < 3; i++) { Q[i][3] = CP(Q[i][0]); if (i) Q[i][2] = CP(Q[i - 1][1]); }
#pragma unroll
                for (int dl = 0; dl < 3; dl++)
#pragma unroll
                    for (int ap = 0; ap < 6 - dl; ap++) mma_f16(fa[ap + 1 + dl], Q[dl], B[ap >> 1][2 * (ap & 1)], B[ap >> 1][2 * (ap & 1) + 1]);
            }
#pragma unroll 1
            for (int s = role; s == 1; s++) {
                ldsm2t(B[0][0], B[0][1], fb + ((lane & 15) == 15 ? F_O5 : F_O3));
#pragma unroll
                for (int dl = 0; dl < 3; dl++) mma_f16(fa[dl], Q[dl], B[0][0], B[0][1]);
            }
#pragma unroll 1
            for (int s = part; s <= 2 * part; s++) {
#pragma unroll
                for (int i = 0; i < 4; i++) { Q[i][0] = lds32(po + s * P_HS + (P_H7 + i * 64)); Q[i][1] = lds32(po + s * P_HS + (P_H7 + i * 64 + 32)); }
                const uint32_t ba = fb + lane * 16 + (F_E7 + s * 1024 + h * F_H);
                ldsm4t(B[0], ba); ldsm4t(B[1], ba + 512);
#pragma unroll
                for (int i = 0; i < 4; i++) { Q[i][3] = CP(Q[i][0]); if (i) Q[i][2] = CP(Q[i - 1][1]); }
#pragma unroll
                for (int dl = 0; dl < 4; dl++) {
#pragma unroll
                    for (int ap = 0; ap < 4 - dl; ap++) mma_f16(fa[ap + 3 + dl], Q[dl], B[ap >> 1][2 * (ap & 1)], B[ap >> 1][2 * (ap & 1) + 1]);
                    if (s == 1) break;
                }
            }
            const uint32_t da = fb + role * 2048 + (lane & 3) * 512 + (((lane >> 2) ^ ((lane & 3) * 2)) << 4);
            bar_sync(1 + k, 128);
            stsm4(da, 0u, 0u, pack_f16(fa[0][0], fa[0][1]), pack_f16(fa[0][2], fa[0][3]));
#pragma unroll
            for (int i = 1; i < 4; i++)
                stsm4(da + i * 128, pack_f16(fa[2 * i - 1][0], fa[2 * i - 1][1]), pack_f16(fa[2 * i - 1][2], fa[2 * i - 1][3]),
                      pack_f16(fa[2 * i][0], fa[2 * i][1]), pack_f16(fa[2 * i][2], fa[2 * i][3]));
            Q[0][0] = (g == 2 * cq) ? 0x6000u : ((g == 2 * cq + 1) ? 0x60000000u : 0u);
            Q[0][1] = 0; Q[0][3] = CP(Q[0][0]);
            const uint32_t ra = fb + (lane >> 3) * 2048 + wq * 512 + (((lane & 7) ^ (wq * 2)) << 4);
            bar_sync(1 + k, 128);
#pragma unroll
            for (int i = 0; i < 4; i++) {
                ldsm4(B[0], ra + i * 128);
                acc[i][0] = acc[i][1] = acc[i][2] = acc[i][3] = 0.f;
                mma_f16(acc[i], Q[0], hadd2(B[0][0], B[0][2]), hadd2(B[0][1], B[0][3]));
            }
        }
        bar_arrive(6 + k, 160);
        STAMP(8);
        const uint32_t inv = lds32(sb + SM_SC + k * 4);
        uint32_t yd = mapa(sb, 2 * wq) + (SM_XT + 128 + q * YP + k * YS + (k >> 2) * (q >> 1) * 16) + lane * 16;
        PIN(yd);
        {
            uint32_t pp = pn + (16 * (wq - 3) + g - 2 * cq) * 4;
            uint32_t dlo = (((ub + 6 * UP) & 0x3FFFF) >> 4) | ((UP >> 4) << 16);
            uint32_t R[4][4];
            auto loadQ = [&](uint32_t (&X)[4][4], uint32_t prev) {
#pragma unroll
                for (int i = 0; i < 4; i++) { X[i][0] = lds32(pp + i * 64); X[i][1] = lds32(pp + i * 64 + 32); }
                X[0][2] = CP(prev);
#pragma unroll
                for (int i = 0; i < 4; i++) { X[i][3] = CP(X[i][0]); if (i) X[i][2] = CP(X[i - 1][1]); }
                pp += 256;
            };
            auto issue = [&](uint32_t (&X)[4][4]) {
                asm volatile("wgmma.fence.sync.aligned;" ::: "memory");
#pragma unroll
                for (int i = 0; i < 4; i++) wgmma32(acc, X[i], dlo - i * (2 * UP >> 4));
                asm volatile("wgmma.commit_group.sync.aligned;" ::: "memory");
                dlo -= 1;
            };
            loadQ(Q, 0);
#pragma unroll 1
            for (int dl = 0; dl < 4; dl++) {
                issue(Q);
                asm volatile("wgmma.wait_group.sync.aligned 1;" ::: "memory");
                loadQ(R, Q[3][1]);
                issue(R);
                asm volatile("wgmma.wait_group.sync.aligned 1;" ::: "memory");
                loadQ(Q, R[3][1]);
            }
            issue(Q);
            asm volatile("wgmma.wait_group.sync.aligned 0;" ::: "memory");
        }
        const uint32_t pstep = mapa(sb, 1) - mapa(sb, 0), ym = mapa(mb + MB_Y * 8, 2 * wq);
#pragma unroll
        for (int e = 0; e < 2; e++)
            st_async4(yd + e * pstep, bmul2(pack_bf16(acc[0][2 * e], acc[0][2 * e + 1]), inv), bmul2(pack_bf16(acc[1][2 * e], acc[1][2 * e + 1]), inv),
                      bmul2(pack_bf16(acc[2][2 * e], acc[2][2 * e + 1]), inv), bmul2(pack_bf16(acc[3][2 * e], acc[3][2 * e + 1]), inv), ym + e * pstep);
        if (lane == 0) asm volatile("mbarrier.arrive.shared::cta.b64 _, [%0];" :: "r"(mb + MB_Y * 8) : "memory");
    }
    STAMP(9);
    uint32_t ha[5], hb[5];
    if (warp < 16) {
        const uint4 wk = lds128(sb + SM_DW + cq * 16);
        uint32_t sel[5] = {wk.x, wk.y, wk.z, wk.w, lds32(sb + SM_DW + 64 + cq * 4)}, sel2[5];
#pragma unroll
        for (int i = 0; i < 5; i++) {
            if (!(g & 1)) sel[i] = 0x3F803F80u;
            sel2[i] = sel[i]; PIN(sel2[i]);
        }
        const uint32_t y4 = sb + SM_XT + 128 + warp * 32 + (2 * (lane >> 3) + (lane & 1)) * YP + ((lane & 7) >> 1) * YS;
        const uint32_t y1 = sb + SM_XT + 128 + warp * 32 + (lane & 7) * YP + 4 * YS + (lane & 8) * 2 + (lane & 6) * 8;
        uint32_t ao = (256 * q + tn) * 16, hta = sb + SM_HT + tn * 80;
        PIN(ao); PIN(hta);
        mbar_wait(mb + MB_Y * 8);
        STAMP(10);
        float ca[4] = {0.f, 0.f, 0.f, 0.f}, cb[4] = {0.f, 0.f, 0.f, 0.f};
        {
            uint32_t ya[4], yb[4], yc, yd;
            ldsm4t(ya, y4); ldsm4t(yb, y4 + 16); ldsm2t(yc, yd, y1);
#pragma unroll
            for (int i = 0; i < 4; i++) { ha[i] = badd2(xa[i], ya[i]); hb[i] = badd2(xb[i], yb[i]); }
            ha[4] = badd2(xa[4], yc); hb[4] = badd2(xb[4], yd);
        }
        if (nslot != 5) {
            ha[4] = hb[4] = 0;
            if (cq >= 2) ha[0] = ha[1] = ha[2] = ha[3] = hb[0] = hb[1] = hb[2] = hb[3] = 0;
        }
#pragma unroll
        for (int i = 0; i < 5; i++) { mma_bf16_k8(ca, ha[i], sel[i], ha[i]); mma_bf16_k8(cb, hb[i], sel2[i], hb[i]); }
        if (!(g & 1)) { ca[1] = ca[0]; cb[1] = cb[0]; }
        if (cq == (g >> 1)) {
            asm volatile("red.relaxed.gpu.global.add.v4.f32 [%0], {%1,%2,%3,%4};" :: "l"((char*)g_s.acc + ao), "f"(1.0f), "f"(ca[1]), "f"(ca[2]), "f"(ca[3]) : "memory");
            asm volatile("red.relaxed.gpu.global.add.v4.f32 [%0], {%1,%2,%3,%4};" :: "l"((char*)g_s.acc + ao + 128), "f"(1.0f), "f"(cb[1]), "f"(cb[2]), "f"(cb[3]) : "memory");
        }
        sts128(hta + cq * 16, ha[0], ha[1], ha[2], ha[3]); sts32(hta + 64 + cq * 4, ha[4]);
        sts128(hta + cq * 16 + 640, hb[0], hb[1], hb[2], hb[3]); sts32(hta + 704 + cq * 4, hb[4]);
        STAMP(11);
    }
    const int kq = warp / 5, mt = warp - 5 * kq;
    const int mi = lane >> 3, mr = lane & 7;
    const unsigned tk = (unsigned)tid / 72u, ck = tid - tk * 72;
    uint32_t A[9][4];
    auto loadA = [&]() {
        mbar_wait(mb + MB_W1 * 8);
        const uint32_t aa = sb + (mi & 1) * SM_WU + (8 * (mi >> 1) + mr) * 80 + (144 * 80 * kq + mt * 16);
#pragma unroll
        for (int s = 0; s < 9; s++) ldsm4t(A[s], aa + s * 1280);
    };
    const uint32_t par = (epoch & 1) ? 0x40004000u : 0u;
    uint32_t pk0 = mapa(sb, 2 * cq), go = (ck / 5u + ck) * 16, co = ((q * 8 * NCL + c) * 6 + cq) * 16;
    PIN(pk0); PIN(go); PIN(co);
    if (warp < 8) {
        const float wsum = ldsf(sb + SM_SC + 24);
        const uint32_t idx = 2047 - (512 * ((tid >> 1) & 3) + 128 * ((tid >> 3) & 3) + 64 * (tid & 1) + 8 * q + warp);
        uint4 s; int n = 0;
        do { s = ld_rlx128(&g_s.acc[256 * q + tid]); } while (__uint_as_float(s.x) != (float)NCL && ++n < SPIN_LIMIT);
        STAMP(16);
        const uint32_t ox = __shfl_xor_sync(~0u, (lane & 1) ? s.z : s.w, 1);
        const uint32_t ms = ln_stats(__uint_as_float((lane & 1) ? ox : s.z), __uint_as_float(s.y));
        const float rs = rcpf(bf_hi(ms));
        const uint32_t rb = pack_bf16(0.f, fmaf(-bf_lo(ms), wsum, __uint_as_float((lane & 1) ? s.w : ox)) * rs);
        const uint32_t key = (((rb ^ (((int)rb >> 31) | 0x80000000u)) >> 16) << 11) | idx;
        sts32(sb + SM_KEY + tid * 4, key);
        __syncwarp();
        const uint32_t rank = rank4<8, 16>(sb + SM_KEY + warp * 128, key);
        if (rank < 8) sts32(sb + SM_CAND + warp * 32 + rank * 4, key);
        sts64(sb + SM_ST + tid * 8, ms, rsplit(rs));
    } else loadA();
    if (warp < 16) {
        STAMP(17);
        bar_sync(12, 512);
        STAMP(18);
        if (warp < 8) {
            const uint32_t mk = lds32(sb + SM_CAND + (tid >> 2) * 4);
            uint32_t rank = rank4<4, 64>(sb + SM_CAND + cq * 16, mk);
            rank += __shfl_xor_sync(~0u, rank, 1); rank += __shfl_xor_sync(~0u, rank, 2);
            if (rank < 8) {
                const uint32_t pk1 = pk0 + (mapa(sb, 1) - mapa(sb, 0));
                st_async1(pk0 + (SM_RK + q * 32) + rank * 4, mk, pk0 + (SM_MB + MB_KEY * 8));
                st_async1(pk1 + (SM_RK + q * 32) + rank * 4, mk, pk1 + (SM_MB + MB_KEY * 8));
                const uint32_t t = tslot(~mk);
                const uint2 sv = lds64(sb + SM_ST + t * 8);
                const uint4 hv = lds128(sb + SM_HT + t * 80 + cq * 16);
                const uint32_t h4 = lds32(sb + SM_HT + t * 80 + 64 + cq * 4);
                const uint32_t rr = bmul2(sv.y, 0x3C803C80u);
                char* const dp = (char*)g_s.cand + (co + rank * 1440);
                st_rlx128(dp, (norm2(hv.x, sv.x, rr) & 0xBFFFBFFFu) | par, (norm2(hv.y, sv.x, rr) & 0xBFFFBFFFu) | par,
                          (norm2(hv.z, sv.x, rr) & 0xBFFFBFFFu) | par, (norm2(hv.w, sv.x, rr) & 0xBFFFBFFFu) | par);
                asm volatile("st.relaxed.gpu.global.u32 [%0], %1;" :: "l"((char*)g_s.cand + (co + rank * 1440 + 64 - cq * 12)), "r"((norm2(h4, sv.x, rr) & 0xBFFFBFFFu) | par) : "memory");
            }
            __syncwarp();
        }
        {
            const uint2 sa = lds64(sb + SM_ST + tn * 8), sbb = lds64(sb + SM_ST + tn * 8 + 64);
#pragma unroll
            for (int i = 0; i < 5; i++) { ha[i] = badd2(ha[i], norm2(ha[i], sa.x, sa.y)); hb[i] = badd2(hb[i], norm2(hb[i], sbb.x, sbb.y)); }
            const bool hf = (c & 1) && cq == 0;
            const uint32_t o16 = sb + SM_XT + (hf ? 16384 + tn * 16 : tn * 64 + (cq - (c & 1)) * 16), o4 = sb + SM_XT + ((c & 1) ? tn * 64 + 48 : 16384 + tn * 16) + cq * 4;
            sts128(o16, ha[0], ha[1], ha[2], ha[3]); sts32(o4, ha[4]);
            sts128(o16 + (hf ? 128 : 512), hb[0], hb[1], hb[2], hb[3]); sts32(o4 + ((c & 1) ? 512 : 128), hb[4]);
        }
        if (warp >= 8) {
            STAMP(19);
            mbar_wait(mb + MB_KEY * 8);
            STAMP(20);
            const uint32_t mk = lds32(sb + SM_RK - 256 + (tid >> 2) * 4);
            uint32_t rank = rank4<4, 64>(sb + SM_RK + cq * 16, mk);
            rank += __shfl_xor_sync(~0u, rank, 1); rank += __shfl_xor_sync(~0u, rank, 2);
            if (rank < 8) sts64(sb + SM_SEL + rank * 8, mk, ((tid >> 2) - 64) * 1440);
        }
    }
    bar_sync(11, 640);
    STAMP(12);

    const char* gp = (const char*)g_s.cand + (go + lds32(sb + SM_SEL + 4 + (tk & 7) * 8));
    uint4 hv = ld_rlx128(gp);
    if (warp < 8) loadA();
    const bool red = warp < 6;
    const uint32_t ft = red ? (unsigned)tid / 24u : (unsigned)(tid >> 4) & 7u, fj = red ? 24 * q + tid - ft * 24 : d0 / 3 + (lane & 15);
    const uint32_t key = lds32(sb + SM_SEL + ft * 8), k16 = key << 5;
    float sig = bfr(rcpf(1.f + ex2f(__uint_as_float((k16 ^ (~((int)k16 >> 31) | 0x80000000u)) & 0xFFFF0000u) * -1.4426950408889634f)));
    uint32_t ra2 = sb + SM_RED2 + tid * 12 + ft * 16, fo = (ft * 192 + fj) * 16, oo = ((~key & 2047) * D_ + 3 * fj) * 2;
    uint32_t bx = sb + SM_XS + mr * 1168 + mi * 16 + 288 * kq, gd = mapa(sb, kq * (8 / NRED)) + (SM_GU + (q * nslot + mt) * 128) + lane * 4;
    PIN(ra2); PIN(fo); PIN(oo); PIN(bx); PIN(gd);
    asm volatile("" : "+f"(sig));
    {
        if (warp < 18) {
            int n = 0;
            while ((((hv.x ^ par) | (hv.y ^ par) | (hv.z ^ par) | (hv.w ^ par)) & 0x40004000u) && ++n < SPIN_LIMIT) hv = ld_rlx128(gp);
            sts128(sb + SM_XS + tk * 16 + tid * 16, hv.x ^ par, hv.y ^ par, hv.z ^ par, hv.w ^ par);
        }
    }
    bar_sync(14, 672);
    STAMP(13);
    {
        float c0[4] = {0.f, 0.f, 0.f, 0.f}, c1[4] = {0.f, 0.f, 0.f, 0.f}, c2[4] = {0.f, 0.f, 0.f, 0.f};
        uint32_t b[5][4];
#pragma unroll
        for (int s = 0; s < 4; s++) ldsm4(b[s], bx + s * 64);
        asm volatile("ldmatrix.sync.aligned.m8n8.x2.shared.b16 {%0,%1}, [%2];" : "=r"(b[4][0]), "=r"(b[4][1]) : "r"(bx + 256) : "memory");
        mma_bf16(c0, A[0][0], A[0][1], A[0][2], A[0][3], b[0][0], b[0][1]);
        mma_bf16(c1, A[1][0], A[1][1], A[1][2], A[1][3], b[0][2], b[0][3]);
        mma_bf16(c2, A[2][0], A[2][1], A[2][2], A[2][3], b[1][0], b[1][1]);
        mma_bf16(c0, A[3][0], A[3][1], A[3][2], A[3][3], b[1][2], b[1][3]);
        mma_bf16(c1, A[4][0], A[4][1], A[4][2], A[4][3], b[2][0], b[2][1]);
        mma_bf16(c2, A[5][0], A[5][1], A[5][2], A[5][3], b[2][2], b[2][3]);
        mma_bf16(c0, A[6][0], A[6][1], A[6][2], A[6][3], b[3][0], b[3][1]);
        mma_bf16(c1, A[7][0], A[7][1], A[7][2], A[7][3], b[3][2], b[3][3]);
        mma_bf16(c2, A[8][0], A[8][1], A[8][2], A[8][3], b[4][0], b[4][1]);
        sts128f(sb + SM_RED + tid * 16, c0[0] + c1[0] + c2[0], c0[1] + c1[1] + c2[1], c0[2] + c1[2] + c2[2], c0[3] + c1[3] + c2[3]);
    }
    bar_sync(1 + mt, 128);
    STAMP(21);
    if (mt < nslot && kq < NRED) {
        const uint32_t ra = sb + SM_RED + mt * 512 + lane * 16;
        const float4 p0 = lds128f(ra), p1 = lds128f(ra + 2560), p2 = lds128f(ra + 5120), p3 = lds128f(ra + 7680);
        const float g0 = bfr(((p0.x + p1.x) + (p2.x + p3.x)) * 64.f), g1 = bfr(((p0.y + p1.y) + (p2.y + p3.y)) * 64.f);
        const uint32_t sg = pack_bf16(g0 * rcpf(1.f + ex2f(g0 * -1.4426950408889634f)), g1 * rcpf(1.f + ex2f(g1 * -1.4426950408889634f)));
        const uint32_t gu = bmul2(sg, pack_bf16(((p0.z + p1.z) + (p2.z + p3.z)) * 64.f, ((p0.w + p1.w) + (p2.w + p3.w)) * 64.f));
        const uint32_t pstep = mapa(sb, 1) - mapa(sb, 0), gm = mapa(mb + MB_GU * 8, kq * (8 / NRED));
#pragma unroll
        for (int i = 0; i < 8 / NRED; i++) st_async1(gd + i * pstep, gu, gm + i * pstep);
    }
    mbar_wait(mb + MB_W2 * 8);
    {
        const uint32_t aa = sb + (8 * (mi >> 1) + mr) * (2 * W2W) + (mi & 1) * 16 + (SM_FAR + 32 * W2W * kq + mt * 32 + (W2W == 72 ? 0 : (q & 1) * 16));
#pragma unroll
        for (int s = 0; s < 5; s++) ldsm4t(A[s], aa + s * FAR_SZ);
    }
    {
        uint32_t ba = sb + (SM_GU + 256 * kq) + (lane & 15) * 16 + (lane >> 4) * 1024, wa = sb + (SM_RED2 + kq * 2432 + mt * 64) + g * 4 + cq * 608;
        PIN(ba); PIN(wa);
        STAMP(22);
        mbar_wait(mb + MB_GU * 8);
        STAMP(23);
        float c0[4] = {0.f, 0.f, 0.f, 0.f}, c1[4] = {0.f, 0.f, 0.f, 0.f}, c2[4] = {0.f, 0.f, 0.f, 0.f};
        uint32_t b[2][4], b8, b9;
        ldsm4t(b[0], ba); ldsm4t(b[1], ba + 2048); ldsm2t(b8, b9, ba + 4096);
        mma_bf16(c0, A[0][0], A[0][1], A[0][2], A[0][3], b[0][0], b[0][1]);
        mma_bf16(c1, A[1][0], A[1][1], A[1][2], A[1][3], b[0][2], b[0][3]);
        if (nslot == 5) {
            mma_bf16(c2, A[4][0], A[4][1], A[4][2], A[4][3], b8, b9);
            mma_bf16(c0, A[2][0], A[2][1], A[2][2], A[2][3], b[1][0], b[1][1]);
            mma_bf16(c1, A[3][0], A[3][1], A[3][2], A[3][3], b[1][2], b[1][3]);
        }
        stsf(wa, c0[0] + c1[0] + c2[0]); stsf(wa + 304, c0[1] + c1[1] + c2[1]);
        if (mt < 4) { stsf(wa + 32, c0[2] + c1[2] + c2[2]); stsf(wa + 336, c0[3] + c1[3] + c2[3]); }
    }
    if (warp < 10) {
        float v[3], cnt = 3.f;
        if (red) {
            bar_sync(6, 640);
            STAMP(14);
#pragma unroll
            for (int i = 0; i < 3; i++) v[i] = ((ldsf(ra2 + i * 4) + ldsf(ra2 + i * 4 + 2432)) + (ldsf(ra2 + i * 4 + 4864) + ldsf(ra2 + i * 4 + 7296))) * sig;
        } else {
            bar_arrive(6, 640);
            cnt = 0.f;
#pragma unroll
            for (int i = 0; i < 3; i++) {
                const uint32_t cl = 3 * fj + i - d0;
                const bool ok = cl < 8 * nslot && ((~key >> 3) & 7) == q;
                const uint32_t cf = cl - (c & 1) * 8;
                v[i] = ok ? __uint_as_float(lds16(sb + SM_XT + (cf < 32 ? tslot(~key) * 64 + cf * 2 : 16384 + tslot(~key) * 16 + (cl & 7) * 2)) << 16) : 0.f;
                if (ok) cnt += 1.f;
            }
            mbar_wait(mb + MB_OUT * 8);
        }
        if (cnt != 0.f) {
            float x, y, z, w;
            asm volatile("atom.relaxed.gpu.global.add.v4.f32 {%0,%1,%2,%3}, [%4], {%5,%6,%7,%8};" : "=f"(x), "=f"(y), "=f"(z), "=f"(w)
                         : "l"((char*)g_s.fin + fo), "f"(v[0]), "f"(v[1]), "f"(v[2]), "f"(cnt) : "memory");
            if (w + cnt == 3.f * (NCL + 1)) {
                __nv_bfloat16* op = (__nv_bfloat16*)((char*)prm.out + oo);
                op[0] = __float2bfloat16(x + v[0]); op[1] = __float2bfloat16(y + v[1]); op[2] = __float2bfloat16(z + v[2]);
            }
        }
    } else bar_arrive(6, 640);
    STAMP(15);
}

typedef CUresult (*EncodeFn)(CUtensorMap*, CUtensorMapDataType, cuuint32_t, void*, const cuuint64_t*, const cuuint64_t*,
                             const cuuint32_t*, const cuuint32_t*, CUtensorMapInterleave, CUtensorMapSwizzle,
                             CUtensorMapL2promotion, CUtensorMapFloatOOBfill);

void make_map(EncodeFn fn, CUtensorMap* tm, const void* p, int cols, int rows, int bc, int br) {
    cuuint64_t dims[2] = {(cuuint64_t)cols, (cuuint64_t)rows};
    cuuint64_t strides[1] = {(cuuint64_t)cols * 2};
    cuuint32_t box[2] = {(cuuint32_t)bc, (cuuint32_t)br};
    cuuint32_t es[2] = {1, 1};
    fn(tm, CU_TENSOR_MAP_DATA_TYPE_BFLOAT16, 2, const_cast<void*>(p), dims, strides, box, es, CU_TENSOR_MAP_INTERLEAVE_NONE,
       CU_TENSOR_MAP_SWIZZLE_NONE, CU_TENSOR_MAP_L2_PROMOTION_L2_128B, CU_TENSOR_MAP_FLOAT_OOB_FILL_NONE);
}

void make_map3(EncodeFn fn, CUtensorMap* tm, const void* p) {
    cuuint64_t dims[5] = {(cuuint64_t)D_, 64, 2, 4, 4};
    cuuint64_t strides[4] = {(cuuint64_t)D_ * 2, (cuuint64_t)D_ * 128, (cuuint64_t)D_ * 1024, (cuuint64_t)D_ * 256};
    cuuint32_t box[5] = {XW, 9, 2, 4, 4};
    cuuint32_t es[5] = {1, 1, 1, 1, 1};
    fn(tm, CU_TENSOR_MAP_DATA_TYPE_BFLOAT16, 5, const_cast<void*>(p), dims, strides, box, es, CU_TENSOR_MAP_INTERLEAVE_NONE,
       CU_TENSOR_MAP_SWIZZLE_NONE, CU_TENSOR_MAP_L2_PROMOTION_NONE, CU_TENSOR_MAP_FLOAT_OOB_FILL_NONE);
}

void make_map5(EncodeFn fn, CUtensorMap* tm, const void* p, int bc) {
    cuuint64_t dims[5] = {(cuuint64_t)D_, 2, 4, 4, 64};
    cuuint64_t strides[4] = {(cuuint64_t)D_ * 128, (cuuint64_t)D_ * 1024, (cuuint64_t)D_ * 256, (cuuint64_t)D_ * 2};
    cuuint32_t box[5] = {(cuuint32_t)bc, 2, 4, 4, 8};
    cuuint32_t es[5] = {1, 1, 1, 1, 1};
    fn(tm, CU_TENSOR_MAP_DATA_TYPE_BFLOAT16, 5, const_cast<void*>(p), dims, strides, box, es, CU_TENSOR_MAP_INTERLEAVE_NONE,
       CU_TENSOR_MAP_SWIZZLE_NONE, CU_TENSOR_MAP_L2_PROMOTION_NONE, CU_TENSOR_MAP_FLOAT_OOB_FILL_NONE);
}

}

extern "C" void kernel_launch(void* const* d_in, const int* in_sizes, int n_in, void* d_out, int out_size) {
    (void)in_sizes; (void)n_in; (void)out_size;
    void* fp = nullptr;
    cudaDriverEntryPointQueryResult qr;
    cudaGetDriverEntryPoint("cuTensorMapEncodeTiled", &fp, cudaEnableDefault, &qr);
    EncodeFn fn = (EncodeFn)fp;
    CUtensorMap tmG, tmU, tmD, tmO, tmX, tmH;
    make_map3(fn, &tmX, d_in[0]);
    make_map(fn, &tmG, d_in[11], F_, D_, 40, 48);
    make_map(fn, &tmU, d_in[12], F_, D_, 40, 48);
    make_map(fn, &tmD, d_in[13], D_, F_, W2W, 64);
    make_map5(fn, &tmO, d_out, 32);
    make_map5(fn, &tmH, d_out, 8);
    Params p;
    p.x = (const unsigned short*)d_in[0];
    for (int i = 0; i < 6; i++) p.prm6[i] = (const unsigned short*)d_in[1 + i];
    p.logdt = (const unsigned short*)d_in[7]; p.dskip = (const unsigned short*)d_in[8];
    p.wr = (const unsigned short*)d_in[10];
    p.out = (__nv_bfloat16*)d_out;
    p.zero = 0;
    cudaGetSymbolAddress((void**)&p.gs, g_s);
    cudaFuncSetAttribute(fused_kernel, cudaFuncAttributeMaxDynamicSharedMemorySize, SM_TOTAL);
    fused_kernel<<<NCTA, NTHR, SM_TOTAL>>>(p, tmG, tmU, tmD, tmO, tmX, tmH);
}
```

```cpp
#include <cuda_runtime.h>
#include <cuda_bf16.h>
#include <cuda_fp16.h>
#include <cuda.h>
#include <stdint.h>

namespace {

constexpr int L_ = 2048, D_ = 576, F_ = 4608;
constexpr int NCL = 15, CS = 8, NCTA = NCL * CS, NTHR = 768;
#define W2W 72
#define XW 48
#define TILE_NS -1
#define XROT 0
#define FORCE_FALLBACK 0
#define LNPOS 1
#define MMPOS 0
#define XSPLIT 3
constexpr int NRED = 2;
constexpr int SPIN_LIMIT = 1 << 22;

constexpr int SM_WG   = 0;
constexpr int SM_WU   = 46080;
constexpr int YP = 3392, YS = 656;
constexpr int UP = 3280, US = 656;
constexpr int SM_XT   = 92160;
constexpr int SM_U    = SM_XT + 8 * YP;
constexpr int SM_FAR  = SM_U + 8 * UP;
constexpr int FAR_SZ  = 12416;
constexpr int F_E5 = 0, F_O5 = 1536, F_E3 = 3088, F_O3 = 4624, F_E7 = 6176, F_E2 = F_E7 + 1024, F_E9 = F_E7 + 2048,
              F_H = 3088, F_O7 = F_E7 + F_H, F_O2 = F_E2 + F_H, F_O9 = F_E9 + F_H;
constexpr int SM_P    = SM_FAR + 5 * FAR_SZ;
constexpr int PN_SZ = 584 * 4, SM_PN = SM_P + 64 * 4;
constexpr int P_GS = 48 * 4, P_H7 = 192 * 4, P_HS = 72 * 4;
constexpr int PF_SZ = (192 + 216) * 4, SM_PF = SM_PN + 5 * PN_SZ + 32;
constexpr int SM_MISC = SM_PF + 5 * PF_SZ;
constexpr int SM_ST   = SM_MISC;
constexpr int SM_RK   = SM_ST + 2048;
constexpr int SM_SEL  = SM_RK + 256;
constexpr int SM_KG   = SM_SEL + 64;
constexpr int SM_SC   = SM_KG + 160;
constexpr int SM_DW   = SM_SC + 32;
constexpr int SM_MB   = SM_DW + 160;
constexpr int SM_TOTAL = SM_MB + 128;
constexpr int SM_ROW  = SM_XT - 20736;
constexpr int SM_XTL  = SM_ROW - 576 * XW;
constexpr int SM_RED2 = SM_WG;
constexpr int SM_HT   = SM_P - 512;
constexpr int SM_KEY  = SM_FAR + 10240 + 128;
constexpr int SM_CAND = SM_KEY + 1024;
constexpr int SM_XS   = SM_U;
constexpr int SM_GU   = SM_XS + 9344;
constexpr int SM_RED  = SM_GU + 5632;
static_assert(F_O9 + 1024 <= FAR_SZ && FAR_SZ % 128 == 0, "far overflow");
static_assert(SM_RED + 10240 <= SM_FAR && SM_HT + 20496 <= SM_MISC, "alias overflow");
static_assert(SM_TOTAL <= 232448, "smem overflow");
static_assert(SM_FAR % 128 == 0 && SM_XT % 128 == 0 && SM_XTL % 128 == 0 && SM_P % 16 == 0 && SM_MISC % 16 == 0 && SM_MB % 8 == 0, "align");

enum { MB_X = 0, MB_W1 = 5, MB_W2 = 6, MB_KEY = 7, MB_GU = 8, MB_Y = 9, MB_OUT = 10, MB_T = 11, MB_R = 12 };

struct __align__(128) Scratch {
    unsigned epoch, zcnt, pad[30];
    uint4  st1[L_ * 2];
    float4 acc[L_];
    uint4  cand[64 * NCL * 6];
    float4 fin[8 * 192 + 24];
};
__device__ Scratch g_s;
#define STAMP(i)

__device__ __forceinline__ uint32_t mapa(uint32_t a, uint32_t r) { uint32_t d; asm("mapa.shared::cluster.u32 %0, %1, %2;" : "=r"(d) : "r"(a), "r"(r)); return d; }
__device__ __forceinline__ void mbar_wait(uint32_t mb) {
    asm volatile("{ .reg .pred p, q; .reg .u32 n; mov.u32 n, 0;\n"
                 "W_%=: mbarrier.try_wait.parity.shared::cta.b64 p, [%0], 0; add.u32 n, n, 1; setp.lt.and.u32 q, n, 65536, !p; @q bra W_%=; }" :: "r"(mb) : "memory");
}
__device__ __forceinline__ void arm(uint32_t mb, uint32_t bytes) { asm volatile("mbarrier.arrive.expect_tx.shared::cta.b64 _, [%0], %1;" :: "r"(mb), "r"(bytes) : "memory"); }
__device__ __forceinline__ void bar_sync(int id, int n) { asm volatile("bar.sync %0, %1;" :: "r"(id), "r"(n) : "memory"); }
__device__ __forceinline__ void bar_arrive(int id, int n) { asm volatile("bar.arrive %0, %1;" :: "r"(id), "r"(n) : "memory"); }
__device__ __forceinline__ uint32_t lds16(uint32_t a) { unsigned short v; asm volatile("ld.shared.u16 %0, [%1];" : "=h"(v) : "r"(a) : "memory"); return v; }
__device__ __forceinline__ uint32_t lds32(uint32_t a) { uint32_t v; asm volatile("ld.shared.u32 %0, [%1];" : "=r"(v) : "r"(a) : "memory"); return v; }
__device__ __forceinline__ uint2 lds64(uint32_t a) { uint2 v; asm volatile("ld.shared.v2.u32 {%0,%1}, [%2];" : "=r"(v.x), "=r"(v.y) : "r"(a) : "memory"); return v; }
__device__ __forceinline__ float ldsf(uint32_t a) { float v; asm volatile("ld.shared.f32 %0, [%1];" : "=f"(v) : "r"(a) : "memory"); return v; }
__device__ __forceinline__ uint4 lds128(uint32_t a) { uint4 v; asm volatile("ld.shared.v4.u32 {%0,%1,%2,%3}, [%4];" : "=r"(v.x), "=r"(v.y), "=r"(v.z), "=r"(v.w) : "r"(a) : "memory"); return v; }
__device__ __forceinline__ float4 lds128f(uint32_t a) { float4 v; asm volatile("ld.shared.v4.f32 {%0,%1,%2,%3}, [%4];" : "=f"(v.x), "=f"(v.y), "=f"(v.z), "=f"(v.w) : "r"(a) : "memory"); return v; }
__device__ __forceinline__ void sts16(uint32_t a, uint32_t v) { asm volatile("{ .reg .b16 l, h; mov.b32 {l, h}, %1; st.shared.b16 [%0], l; }" :: "r"(a), "r"(v) : "memory"); }
__device__ __forceinline__ void sts32(uint32_t a, uint32_t v) { asm volatile("st.shared.u32 [%0], %1;" :: "r"(a), "r"(v) : "memory"); }
__device__ __forceinline__ void sts64(uint32_t a, uint32_t x, uint32_t y) { asm volatile("st.shared.v2.u32 [%0], {%1,%2};" :: "r"(a), "r"(x), "r"(y) : "memory"); }
__device__ __forceinline__ void stsf(uint32_t a, float v) { asm volatile("st.shared.f32 [%0], %1;" :: "r"(a), "f"(v) : "memory"); }
__device__ __forceinline__ void sts128(uint32_t a, uint32_t x, uint32_t y, uint32_t z, uint32_t w) { asm volatile("st.shared.v4.u32 [%0], {%1,%2,%3,%4};" :: "r"(a), "r"(x), "r"(y), "r"(z), "r"(w) : "memory"); }
__device__ __forceinline__ void sts128f(uint32_t a, float x, float y, float z, float w) { asm volatile("st.shared.v4.f32 [%0], {%1,%2,%3,%4};" :: "r"(a), "f"(x), "f"(y), "f"(z), "f"(w) : "memory"); }
__device__ __forceinline__ void ldsm4(uint32_t (&r)[4], uint32_t a) { asm volatile("ldmatrix.sync.aligned.m8n8.x4.shared.b16 {%0,%1,%2,%3}, [%4];" : "=r"(r[0]), "=r"(r[1]), "=r"(r[2]), "=r"(r[3]) : "r"(a) : "memory"); }
__device__ __forceinline__ void ldsm4t(uint32_t (&r)[4], uint32_t a) { asm volatile("ldmatrix.sync.aligned.m8n8.x4.trans.shared.b16 {%0,%1,%2,%3}, [%4];" : "=r"(r[0]), "=r"(r[1]), "=r"(r[2]), "=r"(r[3]) : "r"(a) : "memory"); }
__device__ __forceinline__ void ldsm2t(uint32_t& r0, uint32_t& r1, uint32_t a) { asm volatile("ldmatrix.sync.aligned.m8n8.x2.trans.shared.b16 {%0,%1}, [%2];" : "=r"(r0), "=r"(r1) : "r"(a) : "memory"); }
__device__ __forceinline__ void stsm4t(uint32_t a, uint32_t r0, uint32_t r1, uint32_t r2, uint32_t r3) { asm volatile("stmatrix.sync.aligned.m8n8.x4.trans.shared.b16 [%0], {%1,%2,%3,%4};" :: "r"(a), "r"(r0), "r"(r1), "r"(r2), "r"(r3) : "memory"); }
__device__ __forceinline__ void stsm4(uint32_t a, uint32_t r0, uint32_t r1, uint32_t r2, uint32_t r3) { asm volatile("stmatrix.sync.aligned.m8n8.x4.shared.b16 [%0], {%1,%2,%3,%4};" :: "r"(a), "r"(r0), "r"(r1), "r"(r2), "r"(r3) : "memory"); }
__device__ __forceinline__ void stsm2t(uint32_t a, uint32_t r0, uint32_t r1) { asm volatile("stmatrix.sync.aligned.m8n8.x2.trans.shared.b16 [%0], {%1,%2};" :: "r"(a), "r"(r0), "r"(r1) : "memory"); }
__device__ __forceinline__ uint4 ldg128(const void* p) { uint4 v; asm volatile("ld.global.nc.v4.u32 {%0,%1,%2,%3}, [%4];" : "=r"(v.x), "=r"(v.y), "=r"(v.z), "=r"(v.w) : "l"(p)); return v; }
__device__ __forceinline__ uint32_t ldg16(const void* p) { unsigned short v; asm volatile("ld.global.nc.u16 %0, [%1];" : "=h"(v) : "l"(p)); return v; }
__device__ __forceinline__ uint32_t opaque(uint32_t v) { uint32_t r; asm volatile("mov.b32 %0, %1;" : "=r"(r) : "r"(v)); return r; }
__device__ __forceinline__ void mma_f16(float (&d)[4], const uint32_t (&a)[4], uint32_t b0, uint32_t b1) {
    asm volatile("mma.sync.aligned.m16n8k16.row.col.f32.f16.f16.f32 {%0,%1,%2,%3}, {%4,%5,%6,%7}, {%8,%9}, {%0,%1,%2,%3};"
        : "+f"(d[0]), "+f"(d[1]), "+f"(d[2]), "+f"(d[3]) : "r"(a[0]), "r"(a[1]), "r"(a[2]), "r"(a[3]), "r"(b0), "r"(b1));
}
__device__ __forceinline__ void mma_bf16(float (&d)[4], uint32_t a0, uint32_t a1, uint32_t a2, uint32_t a3, uint32_t b0, uint32_t b1) {
    asm volatile("mma.sync.aligned.m16n8k16.row.col.f32.bf16.bf16.f32 {%0,%1,%2,%3}, {%4,%5,%6,%7}, {%8,%9}, {%0,%1,%2,%3};"
        : "+f"(d[0]), "+f"(d[1]), "+f"(d[2]), "+f"(d[3]) : "r"(a0), "r"(a1), "r"(a2), "r"(a3), "r"(b0), "r"(b1));
}
__device__ __forceinline__ void mma_bf16_k8(float (&d)[4], uint32_t a0, uint32_t a1, uint32_t b0) {
    asm volatile("mma.sync.aligned.m16n8k8.row.col.f32.bf16.bf16.f32 {%0,%1,%2,%3}, {%4,%5}, {%6}, {%0,%1,%2,%3};"
        : "+f"(d[0]), "+f"(d[1]), "+f"(d[2]), "+f"(d[3]) : "r"(a0), "r"(a1), "r"(b0));
}
__device__ __forceinline__ uint32_t pack_f16(float lo, float hi) { uint32_t r; asm("cvt.rn.f16x2.f32 %0, %1, %2;" : "=r"(r) : "f"(hi), "f"(lo)); return r; }
__device__ __forceinline__ uint32_t pack_bf16(float lo, float hi) { uint32_t r; asm("cvt.rn.bf16x2.f32 %0, %1, %2;" : "=r"(r) : "f"(hi), "f"(lo)); return r; }
__device__ __forceinline__ float bf_lo(uint32_t v) { return __uint_as_float(v << 16); }
__device__ __forceinline__ float bf_hi(uint32_t v) { return __uint_as_float(v & 0xFFFF0000u); }
__device__ __forceinline__ float bfr(float x) { return __uint_as_float(pack_bf16(0.f, x)); }
__device__ __forceinline__ uint32_t badd2(uint32_t a, uint32_t b) { uint32_t r; asm("add.rn.bf16x2 %0, %1, %2;" : "=r"(r) : "r"(a), "r"(b)); return r; }
__device__ __forceinline__ uint32_t bmul2(uint32_t a, uint32_t b) { uint32_t r; asm("mul.rn.bf16x2 %0, %1, %2;" : "=r"(r) : "r"(a), "r"(b)); return r; }
__device__ __forceinline__ uint32_t hadd2(uint32_t a, uint32_t b) { uint32_t r; asm("add.rn.f16x2 %0, %1, %2;" : "=r"(r) : "r"(a), "r"(b)); return r; }
__device__ __forceinline__ uint32_t hmul2(uint32_t a, uint32_t b) { uint32_t r; asm("mul.rn.f16x2 %0, %1, %2;" : "=r"(r) : "r"(a), "r"(b)); return r; }
__device__ __forceinline__ uint32_t hfma2(uint32_t a, uint32_t b, uint32_t c) { uint32_t r; asm("fma.rn.f16x2 %0, %1, %2, %3;" : "=r"(r) : "r"(a), "r"(b), "r"(c)); return r; }
__device__ __forceinline__ uint32_t hneg2(uint32_t a) { uint32_t r; asm("neg.f16x2 %0, %1;" : "=r"(r) : "r"(a)); return r; }
__device__ __forceinline__ float rcpf(float x) { float r; asm("rcp.approx.ftz.f32 %0, %1;" : "=f"(r) : "f"(x)); return r; }
__device__ __forceinline__ float sqrta(float x) { float r; asm("sqrt.approx.ftz.f32 %0, %1;" : "=f"(r) : "f"(x)); return r; }
__device__ __forceinline__ float ex2f(float x) { float r; asm("ex2.approx.ftz.f32 %0, %1;" : "=f"(r) : "f"(x)); return r; }
__device__ __forceinline__ void st_async4(uint32_t a, uint32_t x, uint32_t y, uint32_t z, uint32_t w, uint32_t mb) {
    asm volatile("st.async.shared::cluster.mbarrier::complete_tx::bytes.v4.u32 [%0], {%1,%2,%3,%4}, [%5];" :: "r"(a), "r"(x), "r"(y), "r"(z), "r"(w), "r"(mb) : "memory"); }
__device__ __forceinline__ void st_async1(uint32_t a, uint32_t x, uint32_t mb) {
    asm volatile("st.async.shared::cluster.mbarrier::complete_tx::bytes.u32 [%0], %1, [%2];" :: "r"(a), "r"(x), "r"(mb) : "memory"); }
__device__ __forceinline__ unsigned ld_rlx(const void* p) { unsigned v; asm volatile("ld.relaxed.gpu.global.u32 %0, [%1];" : "=r"(v) : "l"(p) : "memory"); return v; }
__device__ __forceinline__ unsigned ld_acq(const void* p) { unsigned v; asm volatile("ld.acquire.gpu.global.u32 %0, [%1];" : "=r"(v) : "l"(p) : "memory"); return v; }
__device__ __forceinline__ uint2 ld_rlx64(const void* p) { unsigned long long v; asm volatile("ld.relaxed.gpu.global.u64 %0, [%1];" : "=l"(v) : "l"(p) : "memory"); return make_uint2((unsigned)v, (unsigned)(v >> 32)); }
__device__ __forceinline__ void st_rlx128(void* p, uint32_t x, uint32_t y, uint32_t z, uint32_t w) {
    asm volatile("st.relaxed.gpu.global.v2.u64 [%0], {%1,%2};" :: "l"(p), "l"((unsigned long long)x | ((unsigned long long)y << 32)), "l"((unsigned long long)z | ((unsigned long long)w << 32)) : "memory"); }
__device__ __forceinline__ uint4 ld_rlx128(const void* p) { unsigned long long a, b; asm volatile("ld.relaxed.gpu.global.v2.u64 {%0,%1}, [%2];" : "=l"(a), "=l"(b) : "l"(p) : "memory"); return make_uint4((unsigned)a, (unsigned)(a >> 32), (unsigned)b, (unsigned)(b >> 32)); }
__device__ __forceinline__ void tma2d(uint32_t dst, const CUtensorMap* tm, int x, int y, uint32_t mb) {
    asm volatile("cp.async.bulk.tensor.2d.shared::cluster.global.mbarrier::complete_tx::bytes [%0], [%1, {%3, %4}], [%2];"
                 :: "r"(dst), "l"(tm), "r"(mb), "r"(x), "r"(y) : "memory");
}
__device__ __forceinline__ void cmul(float& xr, float& xi, float ar, float ai, float br, float bi) {
    const float r = fmaf(ar, br, -ai * bi), i = fmaf(ar, bi, ai * br); xr = r; xi = i;
}
__device__ __forceinline__ void csq(float& xr, float& xi, float ar, float ai) {
    const float r = fmaf(ar, ar, -ai * ai), i = (ar + ar) * ai; xr = r; xi = i;
}
__device__ __forceinline__ void cexp_s(float& zr, float& zi, float e2, float turns) {
    const float mag = ex2f(e2), r = (turns - rintf(turns)) * 6.283185307179586f;
    zr = mag * __cosf(r); zi = mag * __sinf(r);
}
__device__ __forceinline__ uint32_t ln_stats(float s1, float s2) {
    const float m = s1 * (1.f / D_);
    const float var = fmaxf(fmaf(s2, 1.f / D_, -m * m), 0.f);
    return pack_bf16(m, sqrta(bfr(bfr(var) + 1e-5f)));
}
__device__ __forceinline__ uint32_t rsplit(float rs) { const float h = bfr(rs); return pack_bf16(h, rs - h); }
__device__ __forceinline__ uint32_t norm2(uint32_t v, uint32_t mx, uint32_t hl) {
    uint32_t r;
    asm("{ .reg .b16 m, h, l, x; .reg .b32 m2, h2, l2, d, t; mov.b32 {m, x}, %2; mov.b32 {h, l}, %3; mov.b32 m2, {m, m}; mov.b32 h2, {h, h}; mov.b32 l2, {l, l};\n"
        "sub.rn.bf16x2 d, %1, m2; mul.rn.bf16x2 t, d, l2; fma.rn.bf16x2 %0, d, h2, t; }" : "=r"(r) : "r"(v), "r"(mx), "r"(hl));
    return r;
}
template <int N, int S>
__device__ __forceinline__ uint32_t rank4(uint32_t a, uint32_t key) {
    uint32_t r0 = 0, r1 = 0, r2 = 0, r3 = 0;
#pragma unroll
    for (int i = 0; i < N; i++) {
        const uint4 o = lds128(a + i * S);
        r0 += (key - o.x) >> 31; r1 += (key - o.y) >> 31; r2 += (key - o.z) >> 31; r3 += (key - o.w) >> 31;
    }
    return (r0 + r1) + (r2 + r3);
}
typedef uint32_t H2C;
__device__ __forceinline__ H2C splat(float r, float i) { return pack_f16(r, i); }
__device__ __forceinline__ void hcmul(uint32_t& xr, uint32_t& xi, uint32_t R, uint32_t I, H2C m) {
    asm("{ .reg .b16 a, b; .reg .b32 a2, b2, t; mov.b32 {a, b}, %4; mov.b32 a2, {a, a}; mov.b32 b2, {b, b};\n"
        "mul.rn.f16x2 t, %3, b2; neg.f16x2 t, t; fma.rn.f16x2 %0, %2, a2, t; mul.rn.f16x2 t, %3, a2; fma.rn.f16x2 %1, %2, b2, t; }"
        : "=&r"(xr), "=r"(xi) : "r"(R), "r"(I), "r"(m));
}
__device__ __forceinline__ void expand4(uint32_t are, uint32_t aim, uint32_t R0, uint32_t R1, uint32_t I0, uint32_t I1, H2C m4) {
    uint32_t R2, I2, R3, I3;
    hcmul(R2, I2, R0, I0, m4); hcmul(R3, I3, R1, I1, m4);
    sts128(are, R0, R1, R2, R3);
    sts128(aim, I0, I1, I2, I3);
}
__device__ __forceinline__ void expand8(uint32_t are, uint32_t aim, float sr, float si, float m1r, float m1i, float m2r, float m2i, H2C m4) {
    float r1, i1, r2, i2, r3, i3;
    cmul(r1, i1, sr, si, m1r, m1i); cmul(r2, i2, sr, si, m2r, m2i); cmul(r3, i3, r1, i1, m2r, m2i);
    expand4(are, aim, pack_f16(sr, r1), pack_f16(r2, r3), pack_f16(si, i1), pack_f16(i2, i3), m4);
}
__device__ __forceinline__ void put16(uint32_t a, uint32_t v) { sts16(a, v); sts16(a + 6, v); }

struct Params {
    const unsigned short *logdt, *dskip, *prm6[6], *x, *wr;
    __nv_bfloat16* out;
    Scratch* gs;
    unsigned zero;
};
__device__ __forceinline__ uint32_t tslot(uint32_t t) { return (t & 7) * 32 + ((t >> 4) & 24) + ((t >> 8) & 6) + ((t >> 6) & 1); }
#define CP(x) ((x) | zero)
#define PIN(x) asm volatile("or.b32 %0, %0, %1;" : "+r"(x) : "r"(zero))
__device__ __forceinline__ void wgmma32(float (&d)[4][4], const uint32_t (&a)[4], uint32_t dlo) {
    asm volatile("{ .reg .b64 ds; mov.b64 ds, {%20, %21};\n"
                 "wgmma.mma_async.sync.aligned.m64n32k16.f32.f16.f16 {%0,%1,%2,%3,%4,%5,%6,%7,%8,%9,%10,%11,%12,%13,%14,%15}, {%16,%17,%18,%19}, ds, 1, 1, 1, 0; }"
        : "+f"(d[0][0]), "+f"(d[0][1]), "+f"(d[0][2]), "+f"(d[0][3]), "+f"(d[1][0]), "+f"(d[1][1]), "+f"(d[1][2]), "+f"(d[1][3]),
          "+f"(d[2][0]), "+f"(d[2][1]), "+f"(d[2][2]), "+f"(d[2][3]), "+f"(d[3][0]), "+f"(d[3][1]), "+f"(d[3][2]), "+f"(d[3][3])
        : "r"(a[0]), "r"(a[1]), "r"(a[2]), "r"(a[3]), "r"(dlo), "n"(128 >> 4));
}

__global__ void __cluster_dims__(CS, 1, 1) __launch_bounds__(NTHR, 1)
fused_kernel(const __grid_constant__ Params prm, const __grid_constant__ CUtensorMap tmG, const __grid_constant__ CUtensorMap tmU,
             const __grid_constant__ CUtensorMap tmD, const __grid_constant__ CUtensorMap tmO, const __grid_constant__ CUtensorMap tmX, const __grid_constant__ CUtensorMap tmH)
{
    extern __shared__ __align__(1024) unsigned char smem[];
    const int tid = threadIdx.x, lane = tid & 31, warp = __shfl_sync(~0u, tid >> 5, 0);
    const int c = blockIdx.x >> 3, q = blockIdx.x & 7;
    const int nslot = (c < NCL - 1) ? 5 : 2;
    const int d0 = 40 * c;
    const uint32_t sb = opaque((uint32_t)__cvta_generic_to_shared(smem));
    const uint32_t mb = sb + SM_MB;
    Scratch& g_s = *prm.gs;
    const unsigned& zero = prm.zero;
    STAMP(0);

    if (warp >= 20) {
        unsigned epoch = 0;
        if (warp == 20) {
            if (lane == 0) {
#pragma unroll
                for (int i = 0; i < 13; i++)
                    asm volatile("mbarrier.init.shared::cta.b64 [%0], %1;" :: "r"(mb + i * 8), "r"((i == MB_R || i < 2) ? 2 : i == MB_Y ? 1 + 4 * nslot : 1) : "memory");
                asm volatile("fence.mbarrier_init.release.cluster;" ::: "memory");
                arm(mb + MB_W1 * 8, 92160); arm(mb + MB_W2 * 8, nslot * (128 * W2W)); arm(mb + MB_KEY * 8, 256); arm(mb + MB_GU * 8, nslot * 1024); arm(mb + MB_T * 8, 576 * XW);
                const int bytes = max(min(18, L_ - 18 * (int)blockIdx.x), 1) * (D_ * 2);
                arm(mb + MB_R * 8, bytes);
            }
            __syncwarp();
        } else if (warp == 22) {
            epoch = ld_rlx(&g_s.epoch);
            if (lane < 18 ? 18 * c + lane < 256 : lane < 31) (lane < 18 ? &g_s.acc[256 * q + 18 * c] : &g_s.fin[13 * (int)blockIdx.x - 18])[lane] = make_float4(0.f, 0.f, 0.f, 0.f);
        } else if (warp == 23 && lane == 0) asm volatile("prefetch.tensormap [%0];" :: "l"(&tmX) : "memory");
        asm volatile("barrier.cluster.arrive.relaxed.aligned;" ::: "memory");
        bar_sync(12, NTHR);
        if (warp == 22) {
            if (lane == 0) { sts32(sb + SM_SC + 28, epoch); asm volatile("mbarrier.arrive.shared::cta.b64 _, [%0];" :: "r"(mb + MB_R * 8) : "memory"); }
            epoch++;
            asm volatile("fence.acq_rel.gpu;" ::: "memory");
            __syncwarp();
            if (lane == 0) asm volatile("red.relaxed.gpu.global.add.u32 [%0], 1;" :: "l"(&g_s.zcnt) : "memory");
            STAMP(1);
            uint4 wv = make_uint4(0, 0, 0, 0), wv2 = ldg128((const uint4*)prm.wr + lane), wv3 = ldg128((const uint4*)prm.wr + 32 + lane);
            if (lane < 8) wv = ldg128((const uint4*)prm.wr + 64 + lane);
            if (lane < 5) {
                uint4 v = make_uint4(0, 0, 0, 0);
                if (lane < nslot) v = ldg128((const uint4*)(prm.wr + d0) + lane);
                sts128(sb + SM_DW + lane * 16, v.x, v.y, v.z, v.w);
            }
            __syncwarp();
            if (lane < 2) asm volatile("mbarrier.arrive.shared::cta.b64 _, [%0];" :: "r"(mb + (MB_X + lane) * 8) : "memory");
            mbar_wait(mb + (MB_X + 1) * 8);
            const uint32_t old = (epoch & 1) ? 0u : 0x40004000u;
#pragma unroll
            for (int t = 0; t < 2; t++)
                if ((lane & 7) < 6) g_s.cand[((q * 8 + 4 * t + (lane >> 3)) * NCL + c) * 6 + (lane & 7)] = make_uint4(old, old, old, old);
            float a[4] = {0.f, 0.f, 0.f, 0.f};
            const uint32_t one = 0x3F803F80u;
            mma_bf16(a, one, one, one, one, wv.x, wv.y);  mma_bf16(a, one, one, one, one, wv.z, wv.w);
            mma_bf16(a, one, one, one, one, wv2.x, wv2.y); mma_bf16(a, one, one, one, one, wv2.z, wv2.w);
            mma_bf16(a, one, one, one, one, wv3.x, wv3.y); mma_bf16(a, one, one, one, one, wv3.z, wv3.w);
            float s = a[0] + a[1];
            s += __shfl_xor_sync(~0u, s, 1); s += __shfl_xor_sync(~0u, s, 2);
            stsf(sb + SM_SC + 24, s);
            __syncwarp();
            if (lane == 0) {
                int n = 0;
                while ((int)(ld_acq(&g_s.zcnt) - epoch * NCTA) < 0 && ++n < SPIN_LIMIT) __nanosleep(200);
                arm(mb + MB_Y * 8, 8 * 512 * nslot);
                if (blockIdx.x == 0) g_s.epoch = epoch;
            }
            STAMP(2);
            return;
        }
        if (warp == 21) {
            if (lane == 0) { asm volatile("prefetch.tensormap [%0];" :: "l"(&tmG) : "memory"); asm volatile("prefetch.tensormap [%0];" :: "l"(&tmU) : "memory"); asm volatile("prefetch.tensormap [%0];" :: "l"(&tmD) : "memory"); }
            __syncwarp();
            bar_sync(13, 736);
            asm volatile("fence.proxy.async.shared::cta;" ::: "memory");
#pragma unroll 1
            for (int i = 0; i < 24; i++) {
                if (lane == 0) tma2d(sb + SM_WG + i * 3840, i < 12 ? &tmG : &tmU, 320 * c + 8 * nslot * q, 48 * (i < 12 ? i : i - 12), mb + MB_W1 * 8);
            }
            STAMP(1);
            return;
        }
        if (warp == 20) {
            if (lane == 0) {
                asm volatile("cp.async.bulk.shared::cluster.global.mbarrier::complete_tx::bytes [%0], [%1], %2, [%3];"
                             :: "r"(sb + SM_ROW), "l"(prm.x + min(18 * (int)blockIdx.x, L_ - 1) * D_), "r"(max(min(18, L_ - 18 * (int)blockIdx.x), 1) * (D_ * 2)), "r"(mb + MB_R * 8) : "memory");
            }
            __syncwarp();
            if (TILE_NS < 0) mbar_wait(mb + MB_R * 8); else if (TILE_NS) __nanosleep(TILE_NS);
            if (lane == 0) {
                asm volatile("cp.async.bulk.tensor.5d.shared::cluster.global.mbarrier::complete_tx::bytes [%0], [%1, {%3, %4, %5, %5, %5}], [%2];"
                             :: "r"(sb + SM_XTL), "l"(&tmX), "r"(mb + MB_T * 8), "r"(XW == 40 ? d0 : d0 & ~15), "r"(8 * q), "r"(0) : "memory");
            }
            STAMP(6);
        }
        asm volatile("barrier.cluster.wait.aligned;" ::: "memory");
        bar_sync(13, 736);
        asm volatile("fence.proxy.async.shared::cta;" ::: "memory");
        {
            const int gr = lane >> 2, pe = XROT ? ((lane & 3) * 2 + (warp & 1) + q + 1) & 7 : (((lane & 3) ^ (gr * 3)) * 2 + (warp & 1)) & 7;
            const int s0 = gr ? 0 : XSPLIT, ns = gr ? min(XSPLIT, nslot) : nslot - XSPLIT;
            if (gr < 2 && ns > 0) {
                const int bytes = ns * YS - 144;
                if (pe == q) arm(mb + (MB_X + gr) * 8, 7 * bytes);
                else {
                    const uint32_t rb_ = mapa(sb, pe);
                    asm volatile("cp.async.bulk.shared::cluster.shared::cta.mbarrier::complete_tx::bytes [%0], [%1], %2, [%3];"
                                 :: "r"(rb_ + SM_U + 128 + q * UP + s0 * US), "r"(sb + SM_XT + 128 + (q & 3) * 16 + pe * YP + s0 * YS), "r"(bytes), "r"(rb_ + SM_MB + (MB_X + gr) * 8) : "memory");
                }
            }
        }
        STAMP(1);
        if (warp == 20 && lane == 0) { asm volatile("prefetch.tensormap [%0];" :: "l"(&tmO) : "memory"); asm volatile("prefetch.tensormap [%0];" :: "l"(&tmH) : "memory"); }
        if (warp == 23) {
#pragma unroll 1
            for (int kk = nslot - 1; kk >= 0; kk--) {
                __syncwarp();
                bar_sync(6 + kk, 160);
                if (lane == 0) { asm volatile("fence.proxy.async.shared::cta;" ::: "memory"); tma2d(sb + SM_FAR + kk * FAR_SZ, &tmD, W2W == 72 ? 72 * q : (72 * q) & ~15, 320 * c + 64 * kk, mb + MB_W2 * 8); }
            }
            return;
        }
        __syncwarp();
        bar_sync(14, 672);
        if (lane == 0) {
            asm volatile("fence.proxy.async.shared::cta;" ::: "memory");
            asm volatile("cp.async.bulk.tensor.5d.global.shared::cta.bulk_group [%0, {%2, %4, %4, %4, %3}], [%1];" :: "l"(&tmH), "r"(sb + SM_XT + 16384), "r"(d0 + ((c & 1) ? 0 : 32)), "r"(8 * q), "r"(0) : "memory");
            asm volatile("cp.async.bulk.tensor.5d.global.shared::cta.bulk_group [%0, {%2, %4, %4, %4, %3}], [%1];" :: "l"(&tmO), "r"(sb + SM_XT), "r"(d0 + (c & 1) * 8), "r"(8 * q), "r"(0) : "memory");
            asm volatile("cp.async.bulk.commit_group;" ::: "memory");
            asm volatile("cp.async.bulk.wait_group 0;" ::: "memory");
            asm volatile("fence.proxy.async.global;" ::: "memory");
            asm volatile("mbarrier.arrive.shared::cta.b64 _, [%0];" :: "r"(mb + MB_OUT * 8) : "memory");
        }
        STAMP(2);
        return;
    }

    const int g = lane >> 2, cq = lane & 3;
    const int k = warp >> 2, wq = warp & 3;
    const int trow = 18 * blockIdx.x + warp;
    const bool rowact = warp < 18 && trow < L_;
    const int dch = min(d0 + 8 * k + q, D_ - 1);
    uint32_t pv[6];
#pragma unroll
    for (int i = 0; i < 6; i++) pv[i] = ldg16(prm.prm6[i] + (uint32_t)(dch * 128 + wq * 32 + lane));
    const uint32_t pLdt = ldg16(prm.logdt + dch), pD = ldg16(prm.dskip + dch);
    const int tn = 16 * (warp & 15) + g;
    uint32_t xa[5], xb[5];
    asm volatile("barrier.cluster.arrive.relaxed.aligned;" ::: "memory");
    uint4* const st1p = &g_s.st1[(((trow >> 3) & 7) * 256 + ((trow >> 6) & 31) * 8 + (trow & 7)) * 2 + (lane >> 2)];
    const bool pub = rowact && (lane & 0x1B) == 0;
    if (pub) st_rlx128(st1p, 0, 0, 0, 0);
    {
        const uint32_t za = sb + SM_P + tid * 16;
        sts128(za, 0, 0, 0, 0);
        if (tid < (SM_MISC - SM_P) / 16 - 640) sts128(za + 10240, 0, 0, 0, 0);
        sts128(sb + ((wq & 2) ? SM_U : SM_XT + (q & 3) * 16) + ((tid >> 3) & 7) * ((wq & 2) ? UP : YP) + k * YS + (lane & 7) * 16, 0, 0, 0, 0);
    }
    bar_sync(12, NTHR);
    const uint32_t dep = lds32(sb + SM_P);
#define PV(x) __uint_as_float(__byte_perm(dep, x, 0x5410))
    STAMP(1);
    const uint32_t fb = sb + SM_FAR + k * FAR_SZ;
    const uint32_t pn = sb + SM_PN + k * PN_SZ, pf = sb + SM_PF + k * PF_SZ;
    unsigned epoch;
    {
        const uint32_t kb = fb + wq * 3072;
        const uint32_t kl = kb + lane * 16;
        uint32_t Af[4][4];
        float sr, si, z1r, z1i, z2r, z2i, z4r, z4i, hr, hi_;
        {
            const float dt = bfr(ex2f(PV(pLdt) * 1.4426950408889634f));
            const float e2 = dt * PV(pv[0]) * 1.4426950408889634f, an = dt * PV(pv[1]);
            cmul(sr, si, PV(pv[4]), PV(pv[5]), dt * PV(pv[2]), dt * PV(pv[3]));
            const unsigned E = min(max(__reduce_max_sync(~0u, __float_as_uint(fmaxf(fmaxf(fabsf(sr), fabsf(si)), fabsf(PV(pD)) * (1.f / 8192.f)))) >> 23, 1u), 253u);
            const float sc = __uint_as_float((254u - E) << 23);
            sr *= sc; si *= -sc;
            sts64(sb + SM_KG + warp * 8, E, __reduce_add_sync(~0u, __float2int_rn(sr * 16777216.f)));
            float ar, ai, br, bi, cr, ci, dr, di;
            { const float m = ex2f(e2 * 8.f); ar = m * __cosf(an * 8.f); ai = m * __sinf(an * 8.f); }
            csq(br, bi, ar, ai); csq(cr, ci, br, bi); csq(dr, di, cr, ci);
            const H2C m4 = splat(cr, ci);
            {
                float r3, i3;
                cmul(r3, i3, ar, ai, br, bi);
                expand4(kl, kl + 1024, pack_f16(1.f, ar), pack_f16(br, r3), pack_f16(0.f, ai), pack_f16(bi, i3), m4);
            }
            expand8(kl + 512, kl + 1536, dr, di, ar, ai, br, bi, m4);
            { const float m = ex2f(e2); z1r = m * __cosf(an); z1i = -m * __sinf(an); }
            cexp_s(hr, hi_, e2 * 128.f, an * (-128.f * 0.15915494309189535f));
            csq(z2r, z2i, z1r, z1i); csq(z4r, z4i, z2r, z2i);
        }
        __syncwarp();
#pragma unroll
        for (int ks = 0; ks < 4; ks++) ldsm4t(Af[ks], kb + (lane >> 3) * 512 + (lane & 7) * 16 + ks * 128);
        STAMP(2);
        const uint32_t la = kb + ((lane >> 3) & 1) * 512 + (lane >> 4) * 128 + (lane & 7) * 16;
        uint32_t kp[5][2], b0[4], b1[4], b2[4], b3[4];
        auto mm2 = [&](int t) {
            float a0[4] = {0.f, 0.f, 0.f, 0.f}, a1[4] = {0.f, 0.f, 0.f, 0.f};
            mma_f16(a0, Af[0], b0[0], b0[1]); mma_f16(a1, Af[0], b2[0], b2[1]); mma_f16(a0, Af[1], b0[2], b0[3]); mma_f16(a1, Af[1], b2[2], b2[3]);
            mma_f16(a0, Af[2], b1[0], b1[1]); mma_f16(a1, Af[2], b3[0], b3[1]); mma_f16(a0, Af[3], b1[2], b1[3]); mma_f16(a1, Af[3], b3[2], b3[3]);
            kp[t][0] = pack_f16(a0[1], a0[0]); kp[t][1] = pack_f16(a0[3], a0[2]); kp[t + 1][0] = pack_f16(a1[1], a1[0]); kp[t + 1][1] = pack_f16(a1[3], a1[2]);
        };
        auto ln1 = [&]() {
        mbar_wait(mb + MB_R * 8);
        epoch = lds32(sb + SM_SC + 28) + 1;
        {
            const uint32_t ra = sb + SM_ROW + warp * (D_ * 2);
            const uint4 r0 = lds128(ra + lane * 16), r1 = lds128(ra + 512 + lane * 16);
            const uint32_t rx[9] = {r0.x, r0.y, r0.z, r0.w, r1.x, r1.y, r1.z, r1.w, lds32(ra + 1024 + lane * 4)};
            float a0 = bf_lo(rx[0]), a1 = bf_hi(rx[0]), c0 = a0 * a0, c1 = a1 * a1;
#pragma unroll
            for (int i = 1; i < 9; i++) { const float l = bf_lo(rx[i]), h = bf_hi(rx[i]); a0 += l; a1 += h; c0 = fmaf(l, l, c0); c1 = fmaf(h, h, c1); }
            a0 += a1; c0 += c1;
            float s1 = ((lane & 1) ? c0 : a0) + __shfl_xor_sync(~0u, (lane & 1) ? a0 : c0, 1);
#pragma unroll
            for (int o = 2; o < 32; o <<= 1) s1 += __shfl_xor_sync(~0u, s1, o);
            const float s2 = __shfl_xor_sync(~0u, s1, 1);
            const uint32_t ms = ln_stats(s1, s2);
            const uint32_t p0 = __byte_perm(ms, epoch | 0x8000u, 0x5410), p1 = rsplit(rcpf(bf_hi(ms)));
            if (pub) st_rlx128(st1p, p0, p1, p0, p1);
        }
        mbar_wait(mb + MB_R * 8);
        STAMP(1);
        };
        const uint4* sp = &g_s.st1[(256 * q + tn) * 2];
        uint2 sa, sc;
        auto poll = [&]() { sa = ld_rlx64(sp); sc = ld_rlx64(sp + 16); };
        auto norm = [&]() {
        STAMP(3);
        if (warp < 16) {
            uint32_t va[5], vc[5];
            poll();
            mbar_wait(mb + MB_T * 8);
            {
                const uint32_t xt = sb + SM_XTL + (XW == 40 ? 0 : (c & 1) * 16) + (72 * wq + 18 * k + g) * (2 * XW);
                uint4 a4 = lds128(xt + cq * 16), b4 = lds128(xt + cq * 16 + 18 * XW);
                va[0] = a4.x; va[1] = a4.y; va[2] = a4.z; va[3] = a4.w; va[4] = lds32(xt + 64 + cq * 4);
                vc[0] = b4.x; vc[1] = b4.y; vc[2] = b4.z; vc[3] = b4.w; vc[4] = lds32(xt + (64 + 18 * XW) + cq * 4);
            }
            const int d4 = 2 * (lane >> 3) + (lane & 1), d1_ = lane & 7;
            const uint32_t own = SM_U + 128 + q * (UP - YP), oth = SM_XT + 128 + (q & 3) * 16;
            uint32_t a4 = sb + warp * 32 + d4 * YP + (d4 == q ? own : oth) + ((lane & 7) >> 1) * YS;
            uint32_t a1 = sb + warp * 32 + d1_ * YP + (d1_ == q ? own : oth) + 4 * YS + (lane & 8) * 2;
            PIN(a4); PIN(a1);
            uint32_t tag = __byte_perm(epoch | 0x8000u, 0, 0x1010);
            PIN(tag);
            mbar_wait(mb + MB_T * 8);
            int n = 0;
            while (__byte_perm(sa.x, sc.x, 0x7632) != tag && ++n < SPIN_LIMIT) poll();
            STAMP(4);
#pragma unroll
            for (int i = 0; i < 5; i++) {
                va[i] = norm2(va[i], sa.x, sa.y); va[i] = pack_f16(bf_lo(va[i]), bf_hi(va[i]));
                vc[i] = norm2(vc[i], sc.x, sc.y); vc[i] = pack_f16(bf_lo(vc[i]), bf_hi(vc[i]));
            }
            stsm4t(a4, va[0], va[1], va[2], va[3]); stsm4t(a4 + 16, vc[0], vc[1], vc[2], vc[3]); stsm2t(a1, va[4], vc[4]);
            {
            const uint32_t xh = sb + SM_XTL + (XW == 40 ? 0 : (c & 1) * 16) + (9 * g + 144 * (warp & 1) + (warp >> 1)) * (2 * XW);
            const uint4 c4 = lds128(xh + cq * 16), d4_ = lds128(xh + cq * 16 + 144 * XW);
            xa[0] = c4.x; xa[1] = c4.y; xa[2] = c4.z; xa[3] = c4.w; xa[4] = lds32(xh + 64 + cq * 4);
            xb[0] = d4_.x; xb[1] = d4_.y; xb[2] = d4_.z; xb[3] = d4_.w; xb[4] = lds32(xh + (64 + 144 * XW) + cq * 4);
            }
        }
        STAMP(5);
        bar_sync(13, 736);
        Af[0][0] |= lds32(sb + SM_P);
        };
        if (LNPOS == 0) ln1();
        cmul(sr, si, sr, si, z1r, z1i);
        {
            const H2C h4 = splat(z4r, z4i);
            expand8(kl, kl + 512, sr, si, z1r, z1i, z2r, z2i, h4);
            cmul(sr, si, sr, si, hr, hi_);
            expand8(kl + 1024, kl + 1536, sr, si, z1r, z1i, z2r, z2i, h4);
        }
        __syncwarp();
        ldsm4t(b0, la); ldsm4t(b1, la + 256); ldsm4t(b2, la + 1024); ldsm4t(b3, la + 1280);
        cmul(z1r, z1i, z1r, z1i, hr, hi_);
        cmul(sr, si, sr, si, z1r, z1i);
        if (LNPOS == 1) ln1();
        expand8(kl, kl + 512, sr, si, z2r, z2i, z4r, z4i, splat(hr, hi_));
        if (LNPOS == 2) ln1();
        csq(z1r, z1i, z1r, z1i);
        cmul(sr, si, sr, si, z1r, z1i);
        csq(z2r, z2i, hr, hi_);
        expand8(kl + 1024, kl + 1536, sr, si, z4r, z4i, hr, hi_, splat(z2r, z2i));
        if (LNPOS == 3) ln1();
        csq(z1r, z1i, z1r, z1i);
        cmul(sr, si, sr, si, z1r, z1i);
        csq(z4r, z4i, z2r, z2i);
        expand8(kl + 2048, kl + 2560, sr, si, hr, hi_, z2r, z2i, splat(z4r, z4i));
        if (LNPOS == 4) ln1();
        if (MMPOS == 0) norm();
        mm2(0);
        __syncwarp();
        ldsm4t(b0, la); ldsm4t(b1, la + 256); ldsm4t(b2, la + 1024); ldsm4t(b3, la + 1280);
        if (MMPOS == 1) norm();
        mm2(2);
        if (MMPOS == 2) norm();
        ldsm4t(b0, la + 2048); ldsm4t(b1, la + 2304);
#pragma unroll
        for (int t = 0; t < 4; t++) sts64(kb + lane * 8 + 1024 + t * 256, kp[t][0], kp[t][1]);
        {
            float a0[4] = {0.f, 0.f, 0.f, 0.f}, a1[4] = {0.f, 0.f, 0.f, 0.f};
            mma_f16(a0, Af[0], b0[0], b0[1]); mma_f16(a1, Af[1], b0[2], b0[3]); mma_f16(a0, Af[2], b1[0], b1[1]); mma_f16(a1, Af[3], b1[2], b1[3]);
            sts64(kb + lane * 8 + 2048, pack_f16(a0[1] + a1[1], a0[0] + a1[0]), pack_f16(a0[3] + a1[3], a0[2] + a1[2]));
        }
        bar_sync(1 + k, 128);
        const uint4 m01 = lds128(sb + SM_KG + k * 32), m23 = lds128(sb + SM_KG + k * 32 + 16);
        const unsigned Em = max(max(m01.x, m01.z), max(m23.x, m23.z));
        const float f0 = __uint_as_float(max((int)(127 + m01.x - Em), 0) << 23), f1 = __uint_as_float(max((int)(127 + m01.z - Em), 0) << 23),
                    f2 = __uint_as_float(max((int)(127 + m23.x - Em), 0) << 23), f3 = __uint_as_float(max((int)(127 + m23.z - Em), 0) << 23);
        const uint32_t r0 = pack_f16(f0, f0), r1 = pack_f16(f1, f1), r2 = pack_f16(f2, f2), r3 = pack_f16(f3, f3);
        const uint32_t ra = fb + lane * 8 + wq * 256 + 1024;
        const uint2 p0 = lds64(ra), p1 = lds64(ra + 3072), p2 = lds64(ra + 6144), p3 = lds64(ra + 9216);
        uint32_t w0 = hadd2(hfma2(p0.x, r0, hmul2(p1.x, r1)), hfma2(p2.x, r2, hmul2(p3.x, r3)));
        uint32_t w1 = hadd2(hfma2(p0.y, r0, hmul2(p1.y, r1)), hfma2(p2.y, r2, hmul2(p3.y, r3)));
        const bool last = lane == 31;
        if (wq < 2) {
            const uint32_t rc = fb + lane * 8 + wq * 4 + 2048;
            const uint32_t w4 = hmul2(hadd2(hfma2(lds32(rc), r0, hmul2(lds32(rc + 3072), r1)), hfma2(lds32(rc + 6144), r2, hmul2(lds32(rc + 9216), r3))), 0x18001800u);
            const uint32_t ph = pf + (P_H7 + 16 * wq) + (g & 1) * (2 * P_HS) + cq * 64 + (g >> 1) * 4;
            put16(ph, w4 >> 16); put16(ph + 32, w4);
            const uint32_t pa = pn + (4 + 512 * wq) + lane * 8;
            sts16(pa, w0 >> 16); sts32(pa + 4, w0); sts16(pa + 10, w0);
            sts16(pa + 256, w1 >> 16); sts32(pa + 260, w1); sts16(pa + 266, w1);
            if (last) {
                sts32(sb + SM_SC + k * 4, Em * 0x00800080u);
                put16(wq ? pa + 264 : pn,
                      wq ? w1 : pack_f16(((float)(int)m01.y * f0 + (float)(int)m01.w * f1 + (float)(int)m23.y * f2 + (float)(int)m23.w * f3) * (1.f / 16777216.f)
                                         + __uint_as_float(pD << 16) * __uint_as_float((254u - Em) << 23), 0.f));
            }
        } else if (wq == 2) {
            const uint32_t pa = pn + 258 * 4 + (cq & 1) * 16 + (cq >> 1) * 512 + g * 32;
            if (last) { put16(pf, hmul2(w1, 0x18001800u)); w1 = hadd2(w1, hneg2(__byte_perm(w1, 0, 0x1010))); }
            const uint32_t b0 = __byte_perm(w0, 0, 0x1010), b1 = __byte_perm(w1, 0, 0x1010);
            sts16(pa, w0 >> 16); sts32(pa + 4, w0); sts64(pa + 8, b0, b0); sts16(pa + 18, w0);
            sts16(pa + 256, w1 >> 16); sts32(pa + 260, w1); sts64(pa + 264, b1, b1); sts16(pa + 274, w1);
        } else {
            const uint32_t pa = pf + ((g & 1) ? 3 * P_GS : P_GS) + cq * 32 + (g >> 1) * 4;
            const uint32_t pb = pa + ((g & 1) ? 4 - 3 * P_GS : P_GS);
            w0 = hmul2(w0, 0x18001800u); w1 = hmul2(w1, 0x18001800u);
            put16(pa, w0 >> 16); put16(pb, w0); put16(pa + 16, w1 >> 16); put16(pb + 16, w1);
            if (last) put16(pf + P_H7 + P_HS, w1);
        }
        bar_sync(1 + k, 128);
    }
    STAMP(6);

    asm volatile("barrier.cluster.wait.aligned;" ::: "memory");
    mbar_wait(mb + (MB_X + (k < XSPLIT || k >= nslot)) * 8);
    STAMP(7);
    if (k < nslot) {
        const int role = (wq + k) & 3;
        const uint32_t ub = sb + SM_U + k * US + 128;
        if (role) {
            const int r = (3 - role) * 32 + lane;
            const uint32_t a1 = ub + (r & 3) * (2 * UP) + (r >> 2) * 16, a0 = a1 + ((r & 3) ? -2 * UP : 6 * UP - 16);
            const uint4 q0 = lds128(a0), q1 = lds128(a0 + UP), q2 = lds128(a1), q3 = lds128(a1 + UP);
            const uint32_t U[16] = {q0.x, q0.y, q0.z, q0.w, q1.x, q1.y, q1.z, q1.w, q2.x, q2.y, q2.z, q2.w, q3.x, q3.y, q3.z, q3.w};
            uint32_t V[14], Q[14], R4[12], T[8];
#pragma unroll
            for (int i = 2; i < 14; i++) { V[i] = __byte_perm(U[i], U[i + 1], 0x5432); Q[i] = hadd2(U[i], V[i]); }
#pragma unroll
            for (int i = 2; i < 12; i++) R4[i] = hadd2(Q[i], Q[i + 1]);
            const uint32_t rb = fb + r * 16;
#pragma unroll
            for (int i = 0; i < 8; i++) T[i] = hadd2(V[5 + i], Q[6 + i]);
            sts128(rb + F_E3, T[0], T[1], T[2], T[3]); sts128(rb + F_O3 + 16, T[4], T[5], T[6], T[7]);
#pragma unroll
            for (int i = 0; i < 8; i++) T[i] = hadd2(R4[3 + i], U[5 + i]);
            sts128(rb + F_O5, T[0], T[1], T[2], T[3]); sts128(rb + F_E5, T[4], T[5], T[6], T[7]);
            if (role != 1) {
#pragma unroll
                for (int i = 0; i < 8; i++) T[i] = hadd2(T[i], hadd2(V[2 + i], V[5 + i]));
                sts128(rb + F_E7, T[0], T[1], T[2], T[3]); sts128(rb + F_O7, T[4], T[5], T[6], T[7]);
#pragma unroll
                for (int i = 0; i < 8; i++) T[i] = hadd2(R4[2 + i], hadd2(R4[4 + i], U[6 + i]));
                sts128(rb + F_O9, T[0], T[1], T[2], T[3]); sts128(rb + F_E9 + 16, T[4], T[5], T[6], T[7]);
                sts128(rb + F_E2, Q[6], Q[7], Q[8], Q[9]); sts128(rb + F_O2, Q[10], Q[11], Q[12], Q[13]);
            }
        } else if (lane < 8) {
            uint32_t v[5];
#pragma unroll
            for (int i = 0; i < 5; i++) { const int t = 6 + lane + i; v[i] = lds16(ub + 23 * 16 + (t < 16 ? (6 + (t >> 3)) * UP : 16) + (t & 7) * 2); }
            const uint32_t s = hadd2(hadd2(hadd2(v[0], v[1]), hadd2(v[2], v[3])), v[4]);
            sts16(fb + F_O5 + 96 * 16 + lane * 2, s);
            sts32(fb + (lane < 4 ? F_O3 : F_E9 - 16) + lane * 4, 0);
        }
        bar_sync(1 + k, 128);
        float acc[4][4];
        uint32_t Q[4][4];
        {
            const int h = role & 1, part = role >> 1;
            const uint32_t po = pf + (g - 2 * cq) * 4;
            float fa[7][4];
#pragma unroll
            for (int a = 0; a < 7; a++) fa[a][0] = fa[a][1] = fa[a][2] = fa[a][3] = 0.f;
            uint32_t B[3][4];
            Q[0][2] = zero;
#pragma unroll 1
            for (int s = 2 * part + 1; s >= 2 * part; s--) {
#pragma unroll
                for (int i = 0; i < 3; i++) { Q[i][0] = lds32(po + s * P_GS + i * 64); Q[i][1] = lds32(po + s * P_GS + (i * 64 + 32)); }
                const uint32_t ba = fb + lane * 16 + ((s & 1) * F_E3 + (part == h ? 0 : F_O5 + h * 16));
#pragma unroll
                for (int i = 0; i < 3; i++) ldsm4t(B[i], ba + i * 512);
#pragma unroll
                for (int i = 0; i < 3; i++) { Q[i][3] = CP(Q[i][0]); if (i) Q[i][2] = CP(Q[i - 1][1]); }
#pragma unroll
                for (int dl = 0; dl < 3; dl++)
#pragma unroll
                    for (int ap = 0; ap < 6 - dl; ap++) mma_f16(fa[ap + 1 + dl], Q[dl], B[ap >> 1][2 * (ap & 1)], B[ap >> 1][2 * (ap & 1) + 1]);
            }
#pragma unroll 1
            for (int s = role; s == 1; s++) {
                ldsm2t(B[0][0], B[0][1], fb + ((lane & 15) == 15 ? F_O5 : F_O3));
#pragma unroll
                for (int dl = 0; dl < 3; dl++) mma_f16(fa[dl], Q[dl], B[0][0], B[0][1]);
            }
#pragma unroll 1
            for (int s = part; s <= 2 * part; s++) {
#pragma unroll
                for (int i = 0; i < 4; i++) { Q[i][0] = lds32(po + s * P_HS + (P_H7 + i * 64)); Q[i][1] = lds32(po + s * P_HS + (P_H7 + i * 64 + 32)); }
                const uint32_t ba = fb + lane * 16 + (F_E7 + s * 1024 + h * F_H);
                ldsm4t(B[0], ba); ldsm4t(B[1], ba + 512);
#pragma unroll
                for (int i = 0; i < 4; i++) { Q[i][3] = CP(Q[i][0]); if (i) Q[i][2] = CP(Q[i - 1][1]); }
#pragma unroll
                for (int dl = 0; dl < 4; dl++) {
#pragma unroll
                    for (int ap = 0; ap < 4 - dl; ap++) mma_f16(fa[ap + 3 + dl], Q[dl], B[ap >> 1][2 * (ap & 1)], B[ap >> 1][2 * (ap & 1) + 1]);
                    if (s == 1) break;
                }
            }
            const uint32_t da = fb + role * 2048 + (lane & 3) * 512 + (((lane >> 2) ^ ((lane & 3) * 2)) << 4);
            bar_sync(1 + k, 128);
            stsm4(da, 0u, 0u, pack_f16(fa[0][0], fa[0][1]), pack_f16(fa[0][2], fa[0][3]));
#pragma unroll
            for (int i = 1; i < 4; i++)
                stsm4(da + i * 128, pack_f16(fa[2 * i - 1][0], fa[2 * i - 1][1]), pack_f16(fa[2 * i - 1][2], fa[2 * i - 1][3]),
                      pack_f16(fa[2 * i][0], fa[2 * i][1]), pack_f16(fa[2 * i][2], fa[2 * i][3]));
            Q[0][0] = (g == 2 * cq) ? 0x6000u : ((g == 2 * cq + 1) ? 0x60000000u : 0u);
            Q[0][1] = 0; Q[0][3] = CP(Q[0][0]);
            const uint32_t ra = fb + (lane >> 3) * 2048 + wq * 512 + (((lane & 7) ^ (wq * 2)) << 4);
            bar_sync(1 + k, 128);
#pragma unroll
            for (int i = 0; i < 4; i++) {
                ldsm4(B[0], ra + i * 128);
                acc[i][0] = acc[i][1] = acc[i][2] = acc[i][3] = 0.f;
                mma_f16(acc[i], Q[0], hadd2(B[0][0], B[0][2]), hadd2(B[0][1], B[0][3]));
            }
        }
        bar_arrive(6 + k, 160);
        STAMP(8);
        const uint32_t inv = lds32(sb + SM_SC + k * 4);
        uint32_t yd = mapa(sb, 2 * wq) + (SM_XT + 128 + q * YP + k * YS + (k >> 2) * (q >> 1) * 16) + lane * 16;
        PIN(yd);
        {
            uint32_t pp = pn + (16 * (wq - 3) + g - 2 * cq) * 4;
            uint32_t dlo = (((ub + 6 * UP) & 0x3FFFF) >> 4) | ((UP >> 4) << 16);
            uint32_t R[4][4];
            auto loadQ = [&](uint32_t (&X)[4][4], uint32_t prev) {
#pragma unroll
                for (int i = 0; i < 4; i++) { X[i][0] = lds32(pp + i * 64); X[i][1] = lds32(pp + i * 64 + 32); }
                X[0][2] = CP(prev);
#pragma unroll
                for (int i = 0; i < 4; i++) { X[i][3] = CP(X[i][0]); if (i) X[i][2] = CP(X[i - 1][1]); }
                pp += 256;
            };
            auto issue = [&](uint32_t (&X)[4][4]) {
                asm volatile("wgmma.fence.sync.aligned;" ::: "memory");
#pragma unroll
                for (int i = 0; i < 4; i++) wgmma32(acc, X[i], dlo - i * (2 * UP >> 4));
                asm volatile("wgmma.commit_group.sync.aligned;" ::: "memory");
                dlo -= 1;
            };
            loadQ(Q, 0);
#pragma unroll 1
            for (int dl = 0; dl < 4; dl++) {
                issue(Q);
                asm volatile("wgmma.wait_group.sync.aligned 1;" ::: "memory");
                loadQ(R, Q[3][1]);
                issue(R);
                asm volatile("wgmma.wait_group.sync.aligned 1;" ::: "memory");
                loadQ(Q, R[3][1]);
            }
            issue(Q);
            asm volatile("wgmma.wait_group.sync.aligned 0;" ::: "memory");
        }
        const uint32_t pstep = mapa(sb, 1) - mapa(sb, 0), ym = mapa(mb + MB_Y * 8, 2 * wq);
#pragma unroll
        for (int e = 0; e < 2; e++)
            st_async4(yd + e * pstep, bmul2(pack_bf16(acc[0][2 * e], acc[0][2 * e + 1]), inv), bmul2(pack_bf16(acc[1][2 * e], acc[1][2 * e + 1]), inv),
                      bmul2(pack_bf16(acc[2][2 * e], acc[2][2 * e + 1]), inv), bmul2(pack_bf16(acc[3][2 * e], acc[3][2 * e + 1]), inv), ym + e * pstep);
        if (lane == 0) asm volatile("mbarrier.arrive.shared::cta.b64 _, [%0];" :: "r"(mb + MB_Y * 8) : "memory");
    }
    STAMP(9);
    uint32_t ha[5], hb[5];
    if (warp < 16) {
        const uint4 wk = lds128(sb + SM_DW + cq * 16);
        uint32_t sel[5] = {wk.x, wk.y, wk.z, wk.w, lds32(sb + SM_DW + 64 + cq * 4)}, sel2[5];
#pragma unroll
        for (int i = 0; i < 5; i++) {
            if (!(g & 1)) sel[i] = 0x3F803F80u;
            sel2[i] = sel[i]; PIN(sel2[i]);
        }
        const uint32_t y4 = sb + SM_XT + 128 + warp * 32 + (2 * (lane >> 3) + (lane & 1)) * YP + ((lane & 7) >> 1) * YS;
        const uint32_t y1 = sb + SM_XT + 128 + warp * 32 + (lane & 7) * YP + 4 * YS + (lane & 8) * 2 + (lane & 6) * 8;
        uint32_t ao = (256 * q + tn) * 16, hta = sb + SM_HT + tn * 80;
        PIN(ao); PIN(hta);
        mbar_wait(mb + MB_Y * 8);
        STAMP(10);
        float ca[4] = {0.f, 0.f, 0.f, 0.f}, cb[4] = {0.f, 0.f, 0.f, 0.f};
        {
            uint32_t ya[4], yb[4], yc, yd;
            ldsm4t(ya, y4); ldsm4t(yb, y4 + 16); ldsm2t(yc, yd, y1);
#pragma unroll
            for (int i = 0; i < 4; i++) { ha[i] = badd2(xa[i], ya[i]); hb[i] = badd2(xb[i], yb[i]); }
            ha[4] = badd2(xa[4], yc); hb[4] = badd2(xb[4], yd);
        }
        if (nslot != 5) {
            ha[4] = hb[4] = 0;
            if (cq >= 2) ha[0] = ha[1] = ha[2] = ha[3] = hb[0] = hb[1] = hb[2] = hb[3] = 0;
        }
#pragma unroll
        for (int i = 0; i < 5; i++) { mma_bf16_k8(ca, ha[i], sel[i], ha[i]); mma_bf16_k8(cb, hb[i], sel2[i], hb[i]); }
        if (!(g & 1)) { ca[1] = ca[0]; cb[1] = cb[0]; }
        if (cq == (g >> 1)) {
            asm volatile("red.relaxed.gpu.global.add.v4.f32 [%0], {%1,%2,%3,%4};" :: "l"((char*)g_s.acc + ao), "f"(1.0f), "f"(ca[1]), "f"(ca[2]), "f"(ca[3]) : "memory");
            asm volatile("red.relaxed.gpu.global.add.v4.f32 [%0], {%1,%2,%3,%4};" :: "l"((char*)g_s.acc + ao + 128), "f"(1.0f), "f"(cb[1]), "f"(cb[2]), "f"(cb[3]) : "memory");
        }
        sts128(hta + cq * 16, ha[0], ha[1], ha[2], ha[3]); sts32(hta + 64 + cq * 4, ha[4]);
        sts128(hta + cq * 16 + 640, hb[0], hb[1], hb[2], hb[3]); sts32(hta + 704 + cq * 4, hb[4]);
        STAMP(11);
    }
    const int kq = warp / 5, mt = warp - 5 * kq;
    const int mi = lane >> 3, mr = lane & 7;
    const unsigned tk = (unsigned)tid / 72u, ck = tid - tk * 72;
    uint32_t A[9][4];
    auto loadA = [&]() {
        mbar_wait(mb + MB_W1 * 8);
        const uint32_t aa = sb + (mi & 1) * SM_WU + (8 * (mi >> 1) + mr) * 80 + (144 * 80 * kq + mt * 16);
#pragma unroll
        for (int s = 0; s < 9; s++) ldsm4t(A[s], aa + s * 1280);
    };
    const uint32_t par = (epoch & 1) ? 0x40004000u : 0u;
    uint32_t pk0 = mapa(sb, 2 * cq), go = (ck / 5u + ck) * 16, co = ((q * 8 * NCL + c) * 6 + cq) * 16;
    PIN(pk0); PIN(go); PIN(co);
    if (warp < 8) {
        const float wsum = ldsf(sb + SM_SC + 24);
        const uint32_t idx = 2047 - (512 * ((tid >> 1) & 3) + 128 * ((tid >> 3) & 3) + 64 * (tid & 1) + 8 * q + warp);
        uint4 s; int n = 0;
        do { s = ld_rlx128(&g_s.acc[256 * q + tid]); } while (__uint_as_float(s.x) != (float)NCL && ++n < SPIN_LIMIT);
        STAMP(16);
        const uint32_t ox = __shfl_xor_sync(~0u, (lane & 1) ? s.z : s.w, 1);
        const uint32_t ms = ln_stats(__uint_as_float((lane & 1) ? ox : s.z), __uint_as_float(s.y));
        const float rs = rcpf(bf_hi(ms));
        const uint32_t rb = pack_bf16(0.f, fmaf(-bf_lo(ms), wsum, __uint_as_float((lane & 1) ? s.w : ox)) * rs);
        const uint32_t key = (((rb ^ (((int)rb >> 31) | 0x80000000u)) >> 16) << 11) | idx;
        sts32(sb + SM_KEY + tid * 4, key);
        __syncwarp();
        const uint32_t rank = rank4<8, 16>(sb + SM_KEY + warp * 128, key);
        if (rank < 8) sts32(sb + SM_CAND + warp * 32 + rank * 4, key);
        sts64(sb + SM_ST + tid * 8, ms, rsplit(rs));
    } else loadA();
    if (warp < 16) {
        STAMP(17);
        bar_sync(12, 512);
        STAMP(18);
        if (warp < 8) {
            const uint32_t mk = lds32(sb + SM_CAND + (tid >> 2) * 4);
            uint32_t rank = rank4<4, 64>(sb + SM_CAND + cq * 16, mk);
            rank += __shfl_xor_sync(~0u, rank, 1); rank += __shfl_xor_sync(~0u, rank, 2);
            if (rank < 8) {
                const uint32_t pk1 = pk0 + (mapa(sb, 1) - mapa(sb, 0));
                st_async1(pk0 + (SM_RK + q * 32) + rank * 4, mk, pk0 + (SM_MB + MB_KEY * 8));
                st_async1(pk1 + (SM_RK + q * 32) + rank * 4, mk, pk1 + (SM_MB + MB_KEY * 8));
                const uint32_t t = tslot(~mk);
                const uint2 sv = lds64(sb + SM_ST + t * 8);
                const uint4 hv = lds128(sb + SM_HT + t * 80 + cq * 16);
                const uint32_t h4 = lds32(sb + SM_HT + t * 80 + 64 + cq * 4);
                const uint32_t rr = bmul2(sv.y, 0x3C803C80u);
                char* const dp = (char*)g_s.cand + (co + rank * 1440);
                st_rlx128(dp, (norm2(hv.x, sv.x, rr) & 0xBFFFBFFFu) | par, (norm2(hv.y, sv.x, rr) & 0xBFFFBFFFu) | par,
                          (norm2(hv.z, sv.x, rr) & 0xBFFFBFFFu) | par, (norm2(hv.w, sv.x, rr) & 0xBFFFBFFFu) | par);
                asm volatile("st.relaxed.gpu.global.u32 [%0], %1;" :: "l"((char*)g_s.cand + (co + rank * 1440 + 64 - cq * 12)), "r"((norm2(h4, sv.x, rr) & 0xBFFFBFFFu) | par) : "memory");
            }
            __syncwarp();
        }
        {
            const uint2 sa = lds64(sb + SM_ST + tn * 8), sbb = lds64(sb + SM_ST + tn * 8 + 64);
#pragma unroll
            for (int i = 0; i < 5; i++) { ha[i] = badd2(ha[i], norm2(ha[i], sa.x, sa.y)); hb[i] = badd2(hb[i], norm2(hb[i], sbb.x, sbb.y)); }
            const bool hf = (c & 1) && cq == 0;
            const uint32_t o16 = sb + SM_XT + (hf ? 16384 + tn * 16 : tn * 64 + (cq - (c & 1)) * 16), o4 = sb + SM_XT + ((c & 1) ? tn * 64 + 48 : 16384 + tn * 16) + cq * 4;
            sts128(o16, ha[0], ha[1], ha[2], ha[3]); sts32(o4, ha[4]);
            sts128(o16 + (hf ? 128 : 512), hb[0], hb[1], hb[2], hb[3]); sts32(o4 + ((c & 1) ? 512 : 128), hb[4]);
        }
        if (warp >= 8) {
            STAMP(19);
            mbar_wait(mb + MB_KEY * 8);
            STAMP(20);
            const uint32_t mk = lds32(sb + SM_RK - 256 + (tid >> 2) * 4);
            uint32_t rank = rank4<4, 64>(sb + SM_RK + cq * 16, mk);
            rank += __shfl_xor_sync(~0u, rank, 1); rank += __shfl_xor_sync(~0u, rank, 2);
            if (rank < 8) sts64(sb + SM_SEL + rank * 8, mk, ((tid >> 2) - 64) * 1440);
        }
    }
    bar_sync(11, 640);
    STAMP(12);

    const char* gp = (const char*)g_s.cand + (go + lds32(sb + SM_SEL + 4 + (tk & 7) * 8));
    uint4 hv = ld_rlx128(gp);
    if (warp < 8) loadA();
    const bool red = warp < 6;
    const uint32_t ft = red ? (unsigned)tid / 24u : (unsigned)(tid >> 4) & 7u, fj = red ? 24 * q + tid - ft * 24 : d0 / 3 + (lane & 15);
    const uint32_t key = lds32(sb + SM_SEL + ft * 8), k16 = key << 5;
    float sig = bfr(rcpf(1.f + ex2f(__uint_as_float((k16 ^ (~((int)k16 >> 31) | 0x80000000u)) & 0xFFFF0000u) * -1.4426950408889634f)));
    uint32_t ra2 = sb + SM_RED2 + tid * 12 + ft * 16, fo = (ft * 192 + fj) * 16, oo = ((~key & 2047) * D_ + 3 * fj) * 2;
    uint32_t bx = sb + SM_XS + mr * 1168 + mi * 16 + 288 * kq, gd = mapa(sb, kq * (8 / NRED)) + (SM_GU + (q * nslot + mt) * 128) + lane * 4;
    PIN(ra2); PIN(fo); PIN(oo); PIN(bx); PIN(gd);
    asm volatile("" : "+f"(sig));
    {
        if (warp < 18) {
            int n = 0;
            while ((((hv.x ^ par) | (hv.y ^ par) | (hv.z ^ par) | (hv.w ^ par)) & 0x40004000u) && ++n < SPIN_LIMIT) hv = ld_rlx128(gp);
            sts128(sb + SM_XS + tk * 16 + tid * 16, hv.x ^ par, hv.y ^ par, hv.z ^ par, hv.w ^ par);
        }
    }
    bar_sync(14, 672);
    STAMP(13);
    {
        float c0[4] = {0.f, 0.f, 0.f, 0.f}, c1[4] = {0.f, 0.f, 0.f, 0.f}, c2[4] = {0.f, 0.f, 0.f, 0.f};
        uint32_t b[5][4];
#pragma unroll
        for (int s = 0; s < 4; s++) ldsm4(b[s], bx + s * 64);
        asm volatile("ldmatrix.sync.aligned.m8n8.x2.shared.b16 {%0,%1}, [%2];" : "=r"(b[4][0]), "=r"(b[4][1]) : "r"(bx + 256) : "memory");
        mma_bf16(c0, A[0][0], A[0][1], A[0][2], A[0][3], b[0][0], b[0][1]);
        mma_bf16(c1, A[1][0], A[1][1], A[1][2], A[1][3], b[0][2], b[0][3]);
        mma_bf16(c2, A[2][0], A[2][1], A[2][2], A[2][3], b[1][0], b[1][1]);
        mma_bf16(c0, A[3][0], A[3][1], A[3][2], A[3][3], b[1][2], b[1][3]);
        mma_bf16(c1, A[4][0], A[4][1], A[4][2], A[4][3], b[2][0], b[2][1]);
        mma_bf16(c2, A[5][0], A[5][1], A[5][2], A[5][3], b[2][2], b[2][3]);
        mma_bf16(c0, A[6][0], A[6][1], A[6][2], A[6][3], b[3][0], b[3][1]);
        mma_bf16(c1, A[7][0], A[7][1], A[7][2], A[7][3], b[3][2], b[3][3]);
        mma_bf16(c2, A[8][0], A[8][1], A[8][2], A[8][3], b[4][0], b[4][1]);
        sts128f(sb + SM_RED + tid * 16, c0[0] + c1[0] + c2[0], c0[1] + c1[1] + c2[1], c0[2] + c1[2] + c2[2], c0[3] + c1[3] + c2[3]);
    }
    bar_sync(1 + mt, 128);
    STAMP(21);
    if (mt < nslot && kq < NRED) {
        const uint32_t ra = sb + SM_RED + mt * 512 + lane * 16;
        const float4 p0 = lds128f(ra), p1 = lds128f(ra + 2560), p2 = lds128f(ra + 5120), p3 = lds128f(ra + 7680);
        const float g0 = bfr(((p0.x + p1.x) + (p2.x + p3.x)) * 64.f), g1 = bfr(((p0.y + p1.y) + (p2.y + p3.y)) * 64.f);
        const uint32_t sg = pack_bf16(g0 * rcpf(1.f + ex2f(g0 * -1.4426950408889634f)), g1 * rcpf(1.f + ex2f(g1 * -1.4426950408889634f)));
        const uint32_t gu = bmul2(sg, pack_bf16(((p0.z + p1.z) + (p2.z + p3.z)) * 64.f, ((p0.w + p1.w) + (p2.w + p3.w)) * 64.f));
        const uint32_t pstep = mapa(sb, 1) - mapa(sb, 0), gm = mapa(mb + MB_GU * 8, kq * (8 / NRED));
#pragma unroll
        for (int i = 0; i < 8 / NRED; i++) st_async1(gd + i * pstep, gu, gm + i * pstep);
    }
    mbar_wait(mb + MB_W2 * 8);
    {
        const uint32_t aa = sb + (8 * (mi >> 1) + mr) * (2 * W2W) + (mi & 1) * 16 + (SM_FAR + 32 * W2W * kq + mt * 32 + (W2W == 72 ? 0 : (q & 1) * 16));
#pragma unroll
        for (int s = 0; s < 5; s++) ldsm4t(A[s], aa + s * FAR_SZ);
    }
    {
        uint32_t ba = sb + (SM_GU + 256 * kq) + (lane & 15) * 16 + (lane >> 4) * 1024, wa = sb + (SM_RED2 + kq * 2432 + mt * 64) + g * 4 + cq * 608;
        PIN(ba); PIN(wa);
        STAMP(22);
        mbar_wait(mb + MB_GU * 8);
        STAMP(23);
        float c0[4] = {0.f, 0.f, 0.f, 0.f}, c1[4] = {0.f, 0.f, 0.f, 0.f}, c2[4] = {0.f, 0.f, 0.f, 0.f};
        uint32_t b[2][4], b8, b9;
        ldsm4t(b[0], ba); ldsm4t(b[1], ba + 2048); ldsm2t(b8, b9, ba + 4096);
        mma_bf16(c0, A[0][0], A[0][1], A[0][2], A[0][3], b[0][0], b[0][1]);
        mma_bf16(c1, A[1][0], A[1][1], A[1][2], A[1][3], b[0][2], b[0][3]);
        if (nslot == 5) {
            mma_bf16(c2, A[4][0], A[4][1], A[4][2], A[4][3], b8, b9);
            mma_bf16(c0, A[2][0], A[2][1], A[2][2], A[2][3], b[1][0], b[1][1]);
            mma_bf16(c1, A[3][0], A[3][1], A[3][2], A[3][3], b[1][2], b[1][3]);
        }
        stsf(wa, c0[0] + c1[0] + c2[0]); stsf(wa + 304, c0[1] + c1[1] + c2[1]);
        if (mt < 4) { stsf(wa + 32, c0[2] + c1[2] + c2[2]); stsf(wa + 336, c0[3] + c1[3] + c2[3]); }
    }
    if (warp < 10) {
        float v[3], cnt = 3.f;
        if (red) {
            bar_sync(6, 640);
            STAMP(14);
#pragma unroll
            for (int i = 0; i < 3; i++) v[i] = ((ldsf(ra2 + i * 4) + ldsf(ra2 + i * 4 + 2432)) + (ldsf(ra2 + i * 4 + 4864) + ldsf(ra2 + i * 4 + 7296))) * sig;
        } else {
            bar_arrive(6, 640);
            cnt = 0.f;
#pragma unroll
            for (int i = 0; i < 3; i++) {
                const uint32_t cl = 3 * fj + i - d0;
                const bool ok = cl < 8 * nslot && ((~key >> 3) & 7) == q;
                const uint32_t cf = cl - (c & 1) * 8;
                v[i] = ok ? __uint_as_float(lds16(sb + SM_XT + (cf < 32 ? tslot(~key) * 64 + cf * 2 : 16384 + tslot(~key) * 16 + (cl & 7) * 2)) << 16) : 0.f;
                if (ok) cnt += 1.f;
            }
            mbar_wait(mb + MB_OUT * 8);
        }
        if (cnt != 0.f) {
            float x, y, z, w;
            asm volatile("atom.relaxed.gpu.global.add.v4.f32 {%0,%1,%2,%3}, [%4], {%5,%6,%7,%8};" : "=f"(x), "=f"(y), "=f"(z), "=f"(w)
                         : "l"((char*)g_s.fin + fo), "f"(v[0]), "f"(v[1]), "f"(v[2]), "f"(cnt) : "memory");
            if (w + cnt == 3.f * (NCL + 1)) {
                __nv_bfloat16* op = (__nv_bfloat16*)((char*)prm.out + oo);
                op[0] = __float2bfloat16(x + v[0]); op[1] = __float2bfloat16(y + v[1]); op[2] = __float2bfloat16(z + v[2]);
            }
        }
    } else bar_arrive(6, 640);
    STAMP(15);
}

typedef __nv_bfloat16 bf16;
__device__ bf16 f_n[L_ * D_], f_h[L_ * D_];
__device__ float f_k[D_ * L_], f_r[L_], f_gu[8 * F_];
__device__ int f_idx[8];
__device__ __forceinline__ float b2f(bf16 v) { return __bfloat162float(v); }
__global__ void fb_ln(const bf16* in, const bf16* wr, bf16* out) {
    const int t = blockIdx.x * 8 + (threadIdx.x >> 5), lane = threadIdx.x & 31;
    const bf16* r = (in ? in : f_h) + t * D_;
    float s1 = 0.f, s2 = 0.f, s3 = 0.f;
    for (int i = lane; i < D_; i += 32) s1 += b2f(r[i]);
    for (int o = 16; o; o >>= 1) s1 += __shfl_xor_sync(~0u, s1, o);
    for (int i = lane; i < D_; i += 32) { const float d = b2f(r[i]) - s1 / D_; s2 += d * d; }
    for (int o = 16; o; o >>= 1) s2 += __shfl_xor_sync(~0u, s2, o);
    const float m = bfr(s1 / D_), sd = bfr(sqrtf(bfr(bfr(s2 / D_) + 1e-5f)));
    for (int i = lane; i < D_; i += 32) {
        const float v = bfr(bfr(b2f(r[i]) - m) / sd);
        f_n[t * D_ + i] = __float2bfloat16(v);
        if (!in) { s3 += v * b2f(wr[i]); out[t * D_ + i] = __float2bfloat16(b2f(r[i]) + v); }
    }
    for (int o = 16; o; o >>= 1) s3 += __shfl_xor_sync(~0u, s3, o);
    f_r[t] = bfr(s3);
}
__global__ void fb_taps(Params p) {
    const int d = blockIdx.x >> 3, l = (blockIdx.x & 7) * 256 + threadIdx.x;
    const float dt = bfr(expf(bf_lo(p.logdt[d]))), lf = bfr((float)l);
    float k = 0.f;
    for (int n = d * 128; n < d * 128 + 128; n++) {
        float wr, wi, sn, cs;
        cmul(wr, wi, bf_lo(p.prm6[4][n]), bf_lo(p.prm6[5][n]), dt * bf_lo(p.prm6[2][n]), dt * bf_lo(p.prm6[3][n]));
        sincosf(dt * bf_lo(p.prm6[1][n]) * lf, &sn, &cs);
        k += expf(dt * bf_lo(p.prm6[0][n]) * lf) * (wr * cs - wi * sn);
    }
    f_k[l * D_ + d] = k;
}
__global__ void fb_conv(Params p) {
    const int t = blockIdx.x, d = threadIdx.x;
    float y = 0.f;
    for (int l = 0; l <= t; l++) y += f_k[l * D_ + d] * b2f(f_n[(t - l) * D_ + d]);
    f_h[t * D_ + d] = __float2bfloat16(bf_lo(p.x[t * D_ + d]) + bfr(bfr(y) + bfr(b2f(f_n[t * D_ + d]) * bf_lo(p.dskip[d]))));
}
__global__ void fb_top() {
    const int t = blockIdx.x * 256 + threadIdx.x;
    int rank = 0;
    for (int j = 0; j < L_; j++) rank += f_r[j] > f_r[t] || (f_r[j] == f_r[t] && j < t);
    if (rank < 8) f_idx[rank] = t;
}
__global__ void fb_ffn1(const bf16* wg, const bf16* wu) {
    const int f = blockIdx.x * 256 + threadIdx.x, j = blockIdx.y;
    float g = 0.f, u = 0.f;
    for (int i = 0; i < D_; i++) { const float v = b2f(f_n[f_idx[j] * D_ + i]); g += v * b2f(wg[i * F_ + f]); u += v * b2f(wu[i * F_ + f]); }
    g = bfr(g);
    f_gu[j * F_ + f] = bfr(bfr(g / (1.f + expf(-g))) * bfr(u));
}
__global__ void fb_ffn2(const bf16* wd, bf16* out) {
    const int d = threadIdx.x, j = blockIdx.x, t = f_idx[j];
    float y = 0.f;
    for (int f = 0; f < F_; f++) y += f_gu[j * F_ + f] * b2f(wd[f * D_ + d]);
    out[t * D_ + d] = __float2bfloat16(b2f(f_h[t * D_ + d]) + bfr(b2f(f_n[t * D_ + d]) + bfr(bfr(y) * bfr(1.f / (1.f + expf(-f_r[t]))))));
}

typedef CUresult (*EncodeFn)(CUtensorMap*, CUtensorMapDataType, cuuint32_t, void*, const cuuint64_t*, const cuuint64_t*,
                             const cuuint32_t*, const cuuint32_t*, CUtensorMapInterleave, CUtensorMapSwizzle,
                             CUtensorMapL2promotion, CUtensorMapFloatOOBfill);

void make_map(EncodeFn fn, CUtensorMap* tm, const void* p, int cols, int rows, int bc, int br) {
    cuuint64_t dims[2] = {(cuuint64_t)cols, (cuuint64_t)rows};
    cuuint64_t strides[1] = {(cuuint64_t)cols * 2};
    cuuint32_t box[2] = {(cuuint32_t)bc, (cuuint32_t)br};
    cuuint32_t es[2] = {1, 1};
    fn(tm, CU_TENSOR_MAP_DATA_TYPE_BFLOAT16, 2, const_cast<void*>(p), dims, strides, box, es, CU_TENSOR_MAP_INTERLEAVE_NONE,
       CU_TENSOR_MAP_SWIZZLE_NONE, CU_TENSOR_MAP_L2_PROMOTION_L2_128B, CU_TENSOR_MAP_FLOAT_OOB_FILL_NONE);
}

void make_map3(EncodeFn fn, CUtensorMap* tm, const void* p) {
    cuuint64_t dims[5] = {(cuuint64_t)D_, 64, 2, 4, 4};
    cuuint64_t strides[4] = {(cuuint64_t)D_ * 2, (cuuint64_t)D_ * 128, (cuuint64_t)D_ * 1024, (cuuint64_t)D_ * 256};
    cuuint32_t box[5] = {XW, 9, 2, 4, 4};
    cuuint32_t es[5] = {1, 1, 1, 1, 1};
    fn(tm, CU_TENSOR_MAP_DATA_TYPE_BFLOAT16, 5, const_cast<void*>(p), dims, strides, box, es, CU_TENSOR_MAP_INTERLEAVE_NONE,
       CU_TENSOR_MAP_SWIZZLE_NONE, CU_TENSOR_MAP_L2_PROMOTION_NONE, CU_TENSOR_MAP_FLOAT_OOB_FILL_NONE);
}

void make_map5(EncodeFn fn, CUtensorMap* tm, const void* p, int bc) {
    cuuint64_t dims[5] = {(cuuint64_t)D_, 2, 4, 4, 64};
    cuuint64_t strides[4] = {(cuuint64_t)D_ * 128, (cuuint64_t)D_ * 1024, (cuuint64_t)D_ * 256, (cuuint64_t)D_ * 2};
    cuuint32_t box[5] = {(cuuint32_t)bc, 2, 4, 4, 8};
    cuuint32_t es[5] = {1, 1, 1, 1, 1};
    fn(tm, CU_TENSOR_MAP_DATA_TYPE_BFLOAT16, 5, const_cast<void*>(p), dims, strides, box, es, CU_TENSOR_MAP_INTERLEAVE_NONE,
       CU_TENSOR_MAP_SWIZZLE_NONE, CU_TENSOR_MAP_L2_PROMOTION_NONE, CU_TENSOR_MAP_FLOAT_OOB_FILL_NONE);
}

}

extern "C" void kernel_launch(void* const* d_in, const int* in_sizes, int n_in, void* d_out, int out_size) {
    (void)in_sizes; (void)n_in; (void)out_size;
    void* fp = nullptr;
    cudaDriverEntryPointQueryResult qr;
    cudaGetDriverEntryPoint("cuTensorMapEncodeTiled", &fp, cudaEnableDefault, &qr);
    EncodeFn fn = (EncodeFn)fp;
    CUtensorMap tmG, tmU, tmD, tmO, tmX, tmH;
    make_map3(fn, &tmX, d_in[0]);
    make_map(fn, &tmG, d_in[11], F_, D_, 40, 48);
    make_map(fn, &tmU, d_in[12], F_, D_, 40, 48);
    make_map(fn, &tmD, d_in[13], D_, F_, W2W, 64);
    make_map5(fn, &tmO, d_out, 32);
    make_map5(fn, &tmH, d_out, 8);
    Params p;
    p.x = (const unsigned short*)d_in[0];
    for (int i = 0; i < 6; i++) p.prm6[i] = (const unsigned short*)d_in[1 + i];
    p.logdt = (const unsigned short*)d_in[7]; p.dskip = (const unsigned short*)d_in[8];
    p.wr = (const unsigned short*)d_in[10];
    p.out = (__nv_bfloat16*)d_out;
    p.zero = 0;
    cudaGetSymbolAddress((void**)&p.gs, g_s);
    cudaFuncSetAttribute(fused_kernel, cudaFuncAttributeMaxDynamicSharedMemorySize, SM_TOTAL);
    static int nclusters = -1;
    if (nclusters < 0) {
        cudaLaunchConfig_t cfg = {};
        cudaLaunchAttribute at;
        at.id = cudaLaunchAttributeClusterDimension; at.val.clusterDim.x = CS; at.val.clusterDim.y = 1; at.val.clusterDim.z = 1;
        cfg.gridDim = dim3(NCTA); cfg.blockDim = dim3(NTHR); cfg.dynamicSmemBytes = SM_TOTAL; cfg.attrs = &at; cfg.numAttrs = 1;
        if (cudaOccupancyMaxActiveClusters(&nclusters, fused_kernel, &cfg) != cudaSuccess) { (void)cudaGetLastError(); nclusters = NCL; }
    }
    if (nclusters >= NCL && !FORCE_FALLBACK) {
        fused_kernel<<<NCTA, NTHR, SM_TOTAL>>>(p, tmG, tmU, tmD, tmO, tmX, tmH);
        return;
    }
    fb_ln<<<L_ / 8, 256>>>((const bf16*)d_in[0], nullptr, nullptr);
    fb_taps<<<D_ * 8, 256>>>(p);
    fb_conv<<<L_, D_>>>(p);
    fb_ln<<<L_ / 8, 256>>>(nullptr, (const bf16*)d_in[10], p.out);
    fb_top<<<L_ / 256, 256>>>();
    fb_ffn1<<<dim3(F_ / 256, 8), 256>>>((const bf16*)d_in[11], (const bf16*)d_in[12]);
    fb_ffn2<<<8, D_>>>((const bf16*)d_in[13], p.out);
}
```

```cpp
#include <cuda_runtime.h>
#include <cuda_bf16.h>
#include <cuda_fp16.h>
#include <cuda.h>
#include <stdint.h>

namespace {

constexpr int L_ = 2048, D_ = 576, F_ = 4608;
constexpr int NCL = 15, CS = 8, NCTA = NCL * CS, NTHR = 768;
#define W2W 72
#define XW 48
#define TILE_NS -1
#define XROT 0
#define FORCE_FALLBACK 0
#define ROTK 1
#define LNPOS 1
#define MMPOS 0
#define XSPLIT 3
constexpr int NRED = 2;
constexpr int SPIN_LIMIT = 1 << 22;

constexpr int SM_WG   = 0;
constexpr int SM_WU   = 46080;
constexpr int YP = 3392, YS = 656;
constexpr int UP = 3280, US = 656;
constexpr int SM_XT   = 92160;
constexpr int SM_U    = SM_XT + 8 * YP;
constexpr int SM_FAR  = SM_U + 8 * UP;
constexpr int FAR_SZ  = 12416;
constexpr int F_E5 = 0, F_O5 = 1536, F_E3 = 3088, F_O3 = 4624, F_E7 = 6176, F_E2 = F_E7 + 1024, F_E9 = F_E7 + 2048,
              F_H = 3088, F_O7 = F_E7 + F_H, F_O2 = F_E2 + F_H, F_O9 = F_E9 + F_H;
constexpr int SM_P    = SM_FAR + 5 * FAR_SZ;
constexpr int PN_SZ = 584 * 4, SM_PN = SM_P + 64 * 4;
constexpr int P_GS = 48 * 4, P_H7 = 192 * 4, P_HS = 72 * 4;
constexpr int PF_SZ = (192 + 216) * 4, SM_PF = SM_PN + 5 * PN_SZ + 32;
constexpr int SM_MISC = SM_PF + 5 * PF_SZ;
constexpr int SM_ST   = SM_MISC;
constexpr int SM_RK   = SM_ST + 2048;
constexpr int SM_SEL  = SM_RK + 256;
constexpr int SM_KG   = SM_SEL + 64;
constexpr int SM_SC   = SM_KG + 160;
constexpr int SM_DW   = SM_SC + 32;
constexpr int SM_MB   = SM_DW + 160;
constexpr int SM_TOTAL = SM_MB + 128;
constexpr int SM_ROW  = SM_XT - 20736;
constexpr int SM_XTL  = SM_ROW - 576 * XW;
constexpr int SM_RED2 = SM_WG;
constexpr int SM_HT   = SM_P - 512;
constexpr int SM_KEY  = SM_FAR + 10240 + 128;
constexpr int SM_CAND = SM_KEY + 1024;
constexpr int SM_XS   = SM_U;
constexpr int SM_GU   = SM_XS + 9344;
constexpr int SM_RED  = SM_GU + 5632;
static_assert(F_O9 + 1024 <= FAR_SZ && FAR_SZ % 128 == 0, "far overflow");
static_assert(SM_RED + 10240 <= SM_FAR && SM_HT + 20496 <= SM_MISC, "alias overflow");
static_assert(SM_TOTAL <= 232448, "smem overflow");
static_assert(SM_FAR % 128 == 0 && SM_XT % 128 == 0 && SM_XTL % 128 == 0 && SM_P % 16 == 0 && SM_MISC % 16 == 0 && SM_MB % 8 == 0, "align");

enum { MB_X = 0, MB_W1 = 5, MB_W2 = 6, MB_KEY = 7, MB_GU = 8, MB_Y = 9, MB_OUT = 10, MB_T = 11, MB_R = 12 };

struct __align__(128) Scratch {
    unsigned epoch, zcnt, pad[30];
    uint4  st1[L_ * 2];
    float4 acc[L_];
    uint4  cand[64 * NCL * 6];
    float4 fin[8 * 192 + 24];
};
__device__ Scratch g_s;
#define STAMP(i)

__device__ __forceinline__ uint32_t mapa(uint32_t a, uint32_t r) { uint32_t d; asm("mapa.shared::cluster.u32 %0, %1, %2;" : "=r"(d) : "r"(a), "r"(r)); return d; }
__device__ __forceinline__ void mbar_wait(uint32_t mb) {
    asm volatile("{ .reg .pred p, q; .reg .u32 n; mov.u32 n, 0;\n"
                 "W_%=: mbarrier.try_wait.parity.shared::cta.b64 p, [%0], 0; add.u32 n, n, 1; setp.lt.and.u32 q, n, 65536, !p; @q bra W_%=; }" :: "r"(mb) : "memory");
}
__device__ __forceinline__ void arm(uint32_t mb, uint32_t bytes) { asm volatile("mbarrier.arrive.expect_tx.shared::cta.b64 _, [%0], %1;" :: "r"(mb), "r"(bytes) : "memory"); }
__device__ __forceinline__ void bar_sync(int id, int n) { asm volatile("bar.sync %0, %1;" :: "r"(id), "r"(n) : "memory"); }
__device__ __forceinline__ void bar_arrive(int id, int n) { asm volatile("bar.arrive %0, %1;" :: "r"(id), "r"(n) : "memory"); }
__device__ __forceinline__ uint32_t lds16(uint32_t a) { unsigned short v; asm volatile("ld.shared.u16 %0, [%1];" : "=h"(v) : "r"(a) : "memory"); return v; }
__device__ __forceinline__ uint32_t lds32(uint32_t a) { uint32_t v; asm volatile("ld.shared.u32 %0, [%1];" : "=r"(v) : "r"(a) : "memory"); return v; }
__device__ __forceinline__ uint2 lds64(uint32_t a) { uint2 v; asm volatile("ld.shared.v2.u32 {%0,%1}, [%2];" : "=r"(v.x), "=r"(v.y) : "r"(a) : "memory"); return v; }
__device__ __forceinline__ float ldsf(uint32_t a) { float v; asm volatile("ld.shared.f32 %0, [%1];" : "=f"(v) : "r"(a) : "memory"); return v; }
__device__ __forceinline__ uint4 lds128(uint32_t a) { uint4 v; asm volatile("ld.shared.v4.u32 {%0,%1,%2,%3}, [%4];" : "=r"(v.x), "=r"(v.y), "=r"(v.z), "=r"(v.w) : "r"(a) : "memory"); return v; }
__device__ __forceinline__ float4 lds128f(uint32_t a) { float4 v; asm volatile("ld.shared.v4.f32 {%0,%1,%2,%3}, [%4];" : "=f"(v.x), "=f"(v.y), "=f"(v.z), "=f"(v.w) : "r"(a) : "memory"); return v; }
__device__ __forceinline__ void sts16(uint32_t a, uint32_t v) { asm volatile("{ .reg .b16 l, h; mov.b32 {l, h}, %1; st.shared.b16 [%0], l; }" :: "r"(a), "r"(v) : "memory"); }
__device__ __forceinline__ void sts32(uint32_t a, uint32_t v) { asm volatile("st.shared.u32 [%0], %1;" :: "r"(a), "r"(v) : "memory"); }
__device__ __forceinline__ void sts64(uint32_t a, uint32_t x, uint32_t y) { asm volatile("st.shared.v2.u32 [%0], {%1,%2};" :: "r"(a), "r"(x), "r"(y) : "memory"); }
__device__ __forceinline__ void stsf(uint32_t a, float v) { asm volatile("st.shared.f32 [%0], %1;" :: "r"(a), "f"(v) : "memory"); }
__device__ __forceinline__ void sts128(uint32_t a, uint32_t x, uint32_t y, uint32_t z, uint32_t w) { asm volatile("st.shared.v4.u32 [%0], {%1,%2,%3,%4};" :: "r"(a), "r"(x), "r"(y), "r"(z), "r"(w) : "memory"); }
__device__ __forceinline__ void sts128f(uint32_t a, float x, float y, float z, float w) { asm volatile("st.shared.v4.f32 [%0], {%1,%2,%3,%4};" :: "r"(a), "f"(x), "f"(y), "f"(z), "f"(w) : "memory"); }
__device__ __forceinline__ void ldsm4(uint32_t (&r)[4], uint32_t a) { asm volatile("ldmatrix.sync.aligned.m8n8.x4.shared.b16 {%0,%1,%2,%3}, [%4];" : "=r"(r[0]), "=r"(r[1]), "=r"(r[2]), "=r"(r[3]) : "r"(a) : "memory"); }
__device__ __forceinline__ void ldsm4t(uint32_t (&r)[4], uint32_t a) { asm volatile("ldmatrix.sync.aligned.m8n8.x4.trans.shared.b16 {%0,%1,%2,%3}, [%4];" : "=r"(r[0]), "=r"(r[1]), "=r"(r[2]), "=r"(r[3]) : "r"(a) : "memory"); }
__device__ __forceinline__ void ldsm2t(uint32_t& r0, uint32_t& r1, uint32_t a) { asm volatile("ldmatrix.sync.aligned.m8n8.x2.trans.shared.b16 {%0,%1}, [%2];" : "=r"(r0), "=r"(r1) : "r"(a) : "memory"); }
__device__ __forceinline__ void stsm4t(uint32_t a, uint32_t r0, uint32_t r1, uint32_t r2, uint32_t r3) { asm volatile("stmatrix.sync.aligned.m8n8.x4.trans.shared.b16 [%0], {%1,%2,%3,%4};" :: "r"(a), "r"(r0), "r"(r1), "r"(r2), "r"(r3) : "memory"); }
__device__ __forceinline__ void stsm4(uint32_t a, uint32_t r0, uint32_t r1, uint32_t r2, uint32_t r3) { asm volatile("stmatrix.sync.aligned.m8n8.x4.shared.b16 [%0], {%1,%2,%3,%4};" :: "r"(a), "r"(r0), "r"(r1), "r"(r2), "r"(r3) : "memory"); }
__device__ __forceinline__ void stsm2t(uint32_t a, uint32_t r0, uint32_t r1) { asm volatile("stmatrix.sync.aligned.m8n8.x2.trans.shared.b16 [%0], {%1,%2};" :: "r"(a), "r"(r0), "r"(r1) : "memory"); }
__device__ __forceinline__ uint4 ldg128(const void* p) { uint4 v; asm volatile("ld.global.nc.v4.u32 {%0,%1,%2,%3}, [%4];" : "=r"(v.x), "=r"(v.y), "=r"(v.z), "=r"(v.w) : "l"(p)); return v; }
__device__ __forceinline__ uint32_t ldg16(const void* p) { unsigned short v; asm volatile("ld.global.nc.u16 %0, [%1];" : "=h"(v) : "l"(p)); return v; }
__device__ __forceinline__ uint32_t opaque(uint32_t v) { uint32_t r; asm volatile("mov.b32 %0, %1;" : "=r"(r) : "r"(v)); return r; }
__device__ __forceinline__ void mma_f16(float (&d)[4], const uint32_t (&a)[4], uint32_t b0, uint32_t b1) {
    asm volatile("mma.sync.aligned.m16n8k16.row.col.f32.f16.f16.f32 {%0,%1,%2,%3}, {%4,%5,%6,%7}, {%8,%9}, {%0,%1,%2,%3};"
        : "+f"(d[0]), "+f"(d[1]), "+f"(d[2]), "+f"(d[3]) : "r"(a[0]), "r"(a[1]), "r"(a[2]), "r"(a[3]), "r"(b0), "r"(b1));
}
__device__ __forceinline__ void mma_bf16(float (&d)[4], uint32_t a0, uint32_t a1, uint32_t a2, uint32_t a3, uint32_t b0, uint32_t b1) {
    asm volatile("mma.sync.aligned.m16n8k16.row.col.f32.bf16.bf16.f32 {%0,%1,%2,%3}, {%4,%5,%6,%7}, {%8,%9}, {%0,%1,%2,%3};"
        : "+f"(d[0]), "+f"(d[1]), "+f"(d[2]), "+f"(d[3]) : "r"(a0), "r"(a1), "r"(a2), "r"(a3), "r"(b0), "r"(b1));
}
__device__ __forceinline__ void mma_bf16_k8(float (&d)[4], uint32_t a0, uint32_t a1, uint32_t b0) {
    asm volatile("mma.sync.aligned.m16n8k8.row.col.f32.bf16.bf16.f32 {%0,%1,%2,%3}, {%4,%5}, {%6}, {%0,%1,%2,%3};"
        : "+f"(d[0]), "+f"(d[1]), "+f"(d[2]), "+f"(d[3]) : "r"(a0), "r"(a1), "r"(b0));
}
__device__ __forceinline__ uint32_t pack_f16(float lo, float hi) { uint32_t r; asm("cvt.rn.f16x2.f32 %0, %1, %2;" : "=r"(r) : "f"(hi), "f"(lo)); return r; }
__device__ __forceinline__ uint32_t pack_bf16(float lo, float hi) { uint32_t r; asm("cvt.rn.bf16x2.f32 %0, %1, %2;" : "=r"(r) : "f"(hi), "f"(lo)); return r; }
__device__ __forceinline__ float bf_lo(uint32_t v) { return __uint_as_float(v << 16); }
__device__ __forceinline__ float bf_hi(uint32_t v) { return __uint_as_float(v & 0xFFFF0000u); }
__device__ __forceinline__ float bfr(float x) { return __uint_as_float(pack_bf16(0.f, x)); }
__device__ __forceinline__ uint32_t badd2(uint32_t a, uint32_t b) { uint32_t r; asm("add.rn.bf16x2 %0, %1, %2;" : "=r"(r) : "r"(a), "r"(b)); return r; }
__device__ __forceinline__ uint32_t bmul2(uint32_t a, uint32_t b) { uint32_t r; asm("mul.rn.bf16x2 %0, %1, %2;" : "=r"(r) : "r"(a), "r"(b)); return r; }
__device__ __forceinline__ uint32_t hadd2(uint32_t a, uint32_t b) { uint32_t r; asm("add.rn.f16x2 %0, %1, %2;" : "=r"(r) : "r"(a), "r"(b)); return r; }
__device__ __forceinline__ uint32_t hmul2(uint32_t a, uint32_t b) { uint32_t r; asm("mul.rn.f16x2 %0, %1, %2;" : "=r"(r) : "r"(a), "r"(b)); return r; }
__device__ __forceinline__ uint32_t hfma2(uint32_t a, uint32_t b, uint32_t c) { uint32_t r; asm("fma.rn.f16x2 %0, %1, %2, %3;" : "=r"(r) : "r"(a), "r"(b), "r"(c)); return r; }
__device__ __forceinline__ uint32_t hneg2(uint32_t a) { uint32_t r; asm("neg.f16x2 %0, %1;" : "=r"(r) : "r"(a)); return r; }
__device__ __forceinline__ float rcpf(float x) { float r; asm("rcp.approx.ftz.f32 %0, %1;" : "=f"(r) : "f"(x)); return r; }
__device__ __forceinline__ float sqrta(float x) { float r; asm("sqrt.approx.ftz.f32 %0, %1;" : "=f"(r) : "f"(x)); return r; }
__device__ __forceinline__ float ex2f(float x) { float r; asm("ex2.approx.ftz.f32 %0, %1;" : "=f"(r) : "f"(x)); return r; }
__device__ __forceinline__ void st_async4(uint32_t a, uint32_t x, uint32_t y, uint32_t z, uint32_t w, uint32_t mb) {
    asm volatile("st.async.shared::cluster.mbarrier::complete_tx::bytes.v4.u32 [%0], {%1,%2,%3,%4}, [%5];" :: "r"(a), "r"(x), "r"(y), "r"(z), "r"(w), "r"(mb) : "memory"); }
__device__ __forceinline__ void st_async1(uint32_t a, uint32_t x, uint32_t mb) {
    asm volatile("st.async.shared::cluster.mbarrier::complete_tx::bytes.u32 [%0], %1, [%2];" :: "r"(a), "r"(x), "r"(mb) : "memory"); }
__device__ __forceinline__ unsigned ld_rlx(const void* p) { unsigned v; asm volatile("ld.relaxed.gpu.global.u32 %0, [%1];" : "=r"(v) : "l"(p) : "memory"); return v; }
__device__ __forceinline__ unsigned ld_acq(const void* p) { unsigned v; asm volatile("ld.acquire.gpu.global.u32 %0, [%1];" : "=r"(v) : "l"(p) : "memory"); return v; }
__device__ __forceinline__ uint2 ld_rlx64(const void* p) { unsigned long long v; asm volatile("ld.relaxed.gpu.global.u64 %0, [%1];" : "=l"(v) : "l"(p) : "memory"); return make_uint2((unsigned)v, (unsigned)(v >> 32)); }
__device__ __forceinline__ void st_rlx128(void* p, uint32_t x, uint32_t y, uint32_t z, uint32_t w) {
    asm volatile("st.relaxed.gpu.global.v2.u64 [%0], {%1,%2};" :: "l"(p), "l"((unsigned long long)x | ((unsigned long long)y << 32)), "l"((unsigned long long)z | ((unsigned long long)w << 32)) : "memory"); }
__device__ __forceinline__ uint4 ld_rlx128(const void* p) { unsigned long long a, b; asm volatile("ld.relaxed.gpu.global.v2.u64 {%0,%1}, [%2];" : "=l"(a), "=l"(b) : "l"(p) : "memory"); return make_uint4((unsigned)a, (unsigned)(a >> 32), (unsigned)b, (unsigned)(b >> 32)); }
__device__ __forceinline__ void tma2d(uint32_t dst, const CUtensorMap* tm, int x, int y, uint32_t mb) {
    asm volatile("cp.async.bulk.tensor.2d.shared::cluster.global.mbarrier::complete_tx::bytes [%0], [%1, {%3, %4}], [%2];"
                 :: "r"(dst), "l"(tm), "r"(mb), "r"(x), "r"(y) : "memory");
}
__device__ __forceinline__ void cmul(float& xr, float& xi, float ar, float ai, float br, float bi) {
    const float r = fmaf(ar, br, -ai * bi), i = fmaf(ar, bi, ai * br); xr = r; xi = i;
}
__device__ __forceinline__ void csq(float& xr, float& xi, float ar, float ai) {
    const float r = fmaf(ar, ar, -ai * ai), i = (ar + ar) * ai; xr = r; xi = i;
}
__device__ __forceinline__ void cexp_s(float& zr, float& zi, float e2, float turns) {
    const float mag = ex2f(e2), r = (turns - rintf(turns)) * 6.283185307179586f;
    zr = mag * __cosf(r); zi = mag * __sinf(r);
}
__device__ __forceinline__ uint32_t ln_stats(float s1, float s2) {
    const float m = s1 * (1.f / D_);
    const float var = fmaxf(fmaf(s2, 1.f / D_, -m * m), 0.f);
    return pack_bf16(m, sqrta(bfr(bfr(var) + 1e-5f)));
}
__device__ __forceinline__ uint32_t rsplit(float rs) { const float h = bfr(rs); return pack_bf16(h, rs - h); }
__device__ __forceinline__ uint32_t norm2(uint32_t v, uint32_t mx, uint32_t hl) {
    uint32_t r;
    asm("{ .reg .b16 m, h, l, x; .reg .b32 m2, h2, l2, d, t; mov.b32 {m, x}, %2; mov.b32 {h, l}, %3; mov.b32 m2, {m, m}; mov.b32 h2, {h, h}; mov.b32 l2, {l, l};\n"
        "sub.rn.bf16x2 d, %1, m2; mul.rn.bf16x2 t, d, l2; fma.rn.bf16x2 %0, d, h2, t; }" : "=r"(r) : "r"(v), "r"(mx), "r"(hl));
    return r;
}
template <int N, int S>
__device__ __forceinline__ uint32_t rank4(uint32_t a, uint32_t key) {
    uint32_t r0 = 0, r1 = 0, r2 = 0, r3 = 0;
#pragma unroll
    for (int i = 0; i < N; i++) {
        const uint4 o = lds128(a + i * S);
        r0 += (key - o.x) >> 31; r1 += (key - o.y) >> 31; r2 += (key - o.z) >> 31; r3 += (key - o.w) >> 31;
    }
    return (r0 + r1) + (r2 + r3);
}
typedef uint32_t H2C;
__device__ __forceinline__ H2C splat(float r, float i) { return pack_f16(r, i); }
__device__ __forceinline__ void hcmul(uint32_t& xr, uint32_t& xi, uint32_t R, uint32_t I, H2C m) {
    asm("{ .reg .b16 a, b; .reg .b32 a2, b2, t; mov.b32 {a, b}, %4; mov.b32 a2, {a, a}; mov.b32 b2, {b, b};\n"
        "mul.rn.f16x2 t, %3, b2; neg.f16x2 t, t; fma.rn.f16x2 %0, %2, a2, t; mul.rn.f16x2 t, %3, a2; fma.rn.f16x2 %1, %2, b2, t; }"
        : "=&r"(xr), "=r"(xi) : "r"(R), "r"(I), "r"(m));
}
__device__ __forceinline__ void expand4(uint32_t are, uint32_t aim, uint32_t R0, uint32_t R1, uint32_t I0, uint32_t I1, H2C m4) {
    uint32_t R2, I2, R3, I3;
    hcmul(R2, I2, R0, I0, m4); hcmul(R3, I3, R1, I1, m4);
    sts128(are, R0, R1, R2, R3);
    sts128(aim, I0, I1, I2, I3);
}
__device__ __forceinline__ void expand8(uint32_t are, uint32_t aim, float sr, float si, float m1r, float m1i, float m2r, float m2i, H2C m4) {
    float r1, i1, r2, i2, r3, i3;
    cmul(r1, i1, sr, si, m1r, m1i); cmul(r2, i2, sr, si, m2r, m2i); cmul(r3, i3, r1, i1, m2r, m2i);
    expand4(are, aim, pack_f16(sr, r1), pack_f16(r2, r3), pack_f16(si, i1), pack_f16(i2, i3), m4);
}
__device__ __forceinline__ void put16(uint32_t a, uint32_t v) { sts16(a, v); sts16(a + 6, v); }

struct Params {
    const unsigned short *logdt, *dskip, *prm6[6], *x, *wr;
    __nv_bfloat16* out;
    Scratch* gs;
    unsigned zero;
};
__device__ __forceinline__ uint32_t tslot(uint32_t t) { return (t & 7) * 32 + ((t >> 4) & 24) + ((t >> 8) & 6) + ((t >> 6) & 1); }
#define CP(x) ((x) | zero)
#define PIN(x) asm volatile("or.b32 %0, %0, %1;" : "+r"(x) : "r"(zero))
__device__ __forceinline__ void wgmma32(float (&d)[4][4], const uint32_t (&a)[4], uint32_t dlo) {
    asm volatile("{ .reg .b64 ds; mov.b64 ds, {%20, %21};\n"
                 "wgmma.mma_async.sync.aligned.m64n32k16.f32.f16.f16 {%0,%1,%2,%3,%4,%5,%6,%7,%8,%9,%10,%11,%12,%13,%14,%15}, {%16,%17,%18,%19}, ds, 1, 1, 1, 0; }"
        : "+f"(d[0][0]), "+f"(d[0][1]), "+f"(d[0][2]), "+f"(d[0][3]), "+f"(d[1][0]), "+f"(d[1][1]), "+f"(d[1][2]), "+f"(d[1][3]),
          "+f"(d[2][0]), "+f"(d[2][1]), "+f"(d[2][2]), "+f"(d[2][3]), "+f"(d[3][0]), "+f"(d[3][1]), "+f"(d[3][2]), "+f"(d[3][3])
        : "r"(a[0]), "r"(a[1]), "r"(a[2]), "r"(a[3]), "r"(dlo), "n"(128 >> 4));
}

__global__ void __cluster_dims__(CS, 1, 1) __launch_bounds__(NTHR, 1)
fused_kernel(const __grid_constant__ Params prm, const __grid_constant__ CUtensorMap tmG, const __grid_constant__ CUtensorMap tmU,
             const __grid_constant__ CUtensorMap tmD, const __grid_constant__ CUtensorMap tmO, const __grid_constant__ CUtensorMap tmX, const __grid_constant__ CUtensorMap tmH)
{
    extern __shared__ __align__(1024) unsigned char smem[];
    const int tid = threadIdx.x, lane = tid & 31, warp = __shfl_sync(~0u, tid >> 5, 0);
    const int c = blockIdx.x >> 3, q = blockIdx.x & 7;
    const int nslot = (c < NCL - 1) ? 5 : 2;
    const int d0 = 40 * c;
    const uint32_t sb = opaque((uint32_t)__cvta_generic_to_shared(smem));
    const uint32_t mb = sb + SM_MB;
    Scratch& g_s = *prm.gs;
    const unsigned& zero = prm.zero;
    STAMP(0);

    if (warp >= 20) {
        unsigned epoch = 0;
        if (warp == 20) {
            if (lane == 0) {
#pragma unroll
                for (int i = 0; i < 13; i++)
                    asm volatile("mbarrier.init.shared::cta.b64 [%0], %1;" :: "r"(mb + i * 8), "r"((i == MB_R || i < 2) ? 2 : i == MB_Y ? 1 + 4 * nslot : 1) : "memory");
                asm volatile("fence.mbarrier_init.release.cluster;" ::: "memory");
                arm(mb + MB_W1 * 8, 92160); arm(mb + MB_W2 * 8, nslot * (128 * W2W)); arm(mb + MB_KEY * 8, 256); arm(mb + MB_GU * 8, nslot * 1024); arm(mb + MB_T * 8, 576 * XW);
                const int bytes = max(min(18, L_ - 18 * (int)blockIdx.x), 1) * (D_ * 2);
                arm(mb + MB_R * 8, bytes);
            }
            __syncwarp();
        } else if (warp == 22) {
            epoch = ld_rlx(&g_s.epoch);
            if (lane < 18 ? 18 * c + lane < 256 : lane < 31) (lane < 18 ? &g_s.acc[256 * q + 18 * c] : &g_s.fin[13 * (int)blockIdx.x - 18])[lane] = make_float4(0.f, 0.f, 0.f, 0.f);
        } else if (warp == 23 && lane == 0) asm volatile("prefetch.tensormap [%0];" :: "l"(&tmX) : "memory");
        asm volatile("barrier.cluster.arrive.relaxed.aligned;" ::: "memory");
        bar_sync(12, NTHR);
        if (warp == 22) {
            if (lane == 0) { sts32(sb + SM_SC + 28, epoch); asm volatile("mbarrier.arrive.shared::cta.b64 _, [%0];" :: "r"(mb + MB_R * 8) : "memory"); }
            epoch++;
            asm volatile("fence.acq_rel.gpu;" ::: "memory");
            __syncwarp();
            if (lane == 0) asm volatile("red.relaxed.gpu.global.add.u32 [%0], 1;" :: "l"(&g_s.zcnt) : "memory");
            STAMP(1);
            uint4 wv = make_uint4(0, 0, 0, 0), wv2 = ldg128((const uint4*)prm.wr + lane), wv3 = ldg128((const uint4*)prm.wr + 32 + lane);
            if (lane < 8) wv = ldg128((const uint4*)prm.wr + 64 + lane);
            if (lane < 5) {
                uint4 v = make_uint4(0, 0, 0, 0);
                if (lane < nslot) v = ldg128((const uint4*)(prm.wr + d0) + lane);
                sts128(sb + SM_DW + lane * 16, v.x, v.y, v.z, v.w);
            }
            __syncwarp();
            if (lane < 2) asm volatile("mbarrier.arrive.shared::cta.b64 _, [%0];" :: "r"(mb + (MB_X + lane) * 8) : "memory");
            mbar_wait(mb + (MB_X + 1) * 8);
            const uint32_t old = (epoch & 1) ? 0u : 0x40004000u;
#pragma unroll
            for (int t = 0; t < 2; t++)
                if ((lane & 7) < 6) g_s.cand[((q * 8 + 4 * t + (lane >> 3)) * NCL + c) * 6 + (lane & 7)] = make_uint4(old, old, old, old);
            float a[4] = {0.f, 0.f, 0.f, 0.f};
            const uint32_t one = 0x3F803F80u;
            mma_bf16(a, one, one, one, one, wv.x, wv.y);  mma_bf16(a, one, one, one, one, wv.z, wv.w);
            mma_bf16(a, one, one, one, one, wv2.x, wv2.y); mma_bf16(a, one, one, one, one, wv2.z, wv2.w);
            mma_bf16(a, one, one, one, one, wv3.x, wv3.y); mma_bf16(a, one, one, one, one, wv3.z, wv3.w);
            float s = a[0] + a[1];
            s += __shfl_xor_sync(~0u, s, 1); s += __shfl_xor_sync(~0u, s, 2);
            stsf(sb + SM_SC + 24, s);
            __syncwarp();
            if (lane == 0) {
                int n = 0;
                while ((int)(ld_acq(&g_s.zcnt) - epoch * NCTA) < 0 && ++n < SPIN_LIMIT) __nanosleep(200);
                arm(mb + MB_Y * 8, 8 * 512 * nslot);
                if (blockIdx.x == 0) g_s.epoch = epoch;
            }
            STAMP(2);
            return;
        }
        if (warp == 21) {
            if (lane == 0) { asm volatile("prefetch.tensormap [%0];" :: "l"(&tmG) : "memory"); asm volatile("prefetch.tensormap [%0];" :: "l"(&tmU) : "memory"); asm volatile("prefetch.tensormap [%0];" :: "l"(&tmD) : "memory"); }
            __syncwarp();
            bar_sync(13, 736);
            asm volatile("fence.proxy.async.shared::cta;" ::: "memory");
#pragma unroll 1
            for (int i = 0; i < 24; i++) {
                if (lane == 0) tma2d(sb + SM_WG + i * 3840, i < 12 ? &tmG : &tmU, 320 * c + 8 * nslot * q, 48 * (i < 12 ? i : i - 12), mb + MB_W1 * 8);
            }
            STAMP(1);
            return;
        }
        if (warp == 20) {
            if (lane == 0) {
                asm volatile("cp.async.bulk.shared::cluster.global.mbarrier::complete_tx::bytes [%0], [%1], %2, [%3];"
                             :: "r"(sb + SM_ROW), "l"(prm.x + min(18 * (int)blockIdx.x, L_ - 1) * D_), "r"(max(min(18, L_ - 18 * (int)blockIdx.x), 1) * (D_ * 2)), "r"(mb + MB_R * 8) : "memory");
            }
            __syncwarp();
            if (TILE_NS < 0) mbar_wait(mb + MB_R * 8); else if (TILE_NS) __nanosleep(TILE_NS);
            if (lane == 0) {
                asm volatile("cp.async.bulk.tensor.5d.shared::cluster.global.mbarrier::complete_tx::bytes [%0], [%1, {%3, %4, %5, %5, %5}], [%2];"
                             :: "r"(sb + SM_XTL), "l"(&tmX), "r"(mb + MB_T * 8), "r"(XW == 40 ? d0 : d0 & ~15), "r"(8 * q), "r"(0) : "memory");
            }
            STAMP(6);
        }
        asm volatile("barrier.cluster.wait.aligned;" ::: "memory");
        bar_sync(13, 736);
        asm volatile("fence.proxy.async.shared::cta;" ::: "memory");
        {
            const int gr = lane >> 2, pe = XROT ? ((lane & 3) * 2 + (warp & 1) + q + 1) & 7 : (((lane & 3) ^ (gr * 3)) * 2 + (warp & 1)) & 7;
            const int s0 = gr ? 0 : XSPLIT, ns = gr ? min(XSPLIT, nslot) : nslot - XSPLIT;
            if (gr < 2 && ns > 0) {
                const int bytes = ns * YS - 144;
                if (pe == q) arm(mb + (MB_X + gr) * 8, 7 * bytes);
                else {
                    const uint32_t rb_ = mapa(sb, pe);
                    asm volatile("cp.async.bulk.shared::cluster.shared::cta.mbarrier::complete_tx::bytes [%0], [%1], %2, [%3];"
                                 :: "r"(rb_ + SM_U + 128 + q * UP + s0 * US), "r"(sb + SM_XT + 128 + (q & 3) * 16 + pe * YP + s0 * YS), "r"(bytes), "r"(rb_ + SM_MB + (MB_X + gr) * 8) : "memory");
                }
            }
        }
        STAMP(1);
        if (warp == 20 && lane == 0) { asm volatile("prefetch.tensormap [%0];" :: "l"(&tmO) : "memory"); asm volatile("prefetch.tensormap [%0];" :: "l"(&tmH) : "memory"); }
        if (warp == 23) {
#pragma unroll 1
            for (int kk = nslot - 1; kk >= 0; kk--) {
                __syncwarp();
                bar_sync(6 + kk, 160);
                if (lane == 0) { asm volatile("fence.proxy.async.shared::cta;" ::: "memory"); tma2d(sb + SM_FAR + kk * FAR_SZ, &tmD, W2W == 72 ? 72 * q : (72 * q) & ~15, 320 * c + 64 * kk, mb + MB_W2 * 8); }
            }
            return;
        }
        __syncwarp();
        bar_sync(14, 672);
        if (lane == 0) {
            asm volatile("fence.proxy.async.shared::cta;" ::: "memory");
            asm volatile("cp.async.bulk.tensor.5d.global.shared::cta.bulk_group [%0, {%2, %4, %4, %4, %3}], [%1];" :: "l"(&tmH), "r"(sb + SM_XT + 16384), "r"(d0 + ((c & 1) ? 0 : 32)), "r"(8 * q), "r"(0) : "memory");
            asm volatile("cp.async.bulk.tensor.5d.global.shared::cta.bulk_group [%0, {%2, %4, %4, %4, %3}], [%1];" :: "l"(&tmO), "r"(sb + SM_XT), "r"(d0 + (c & 1) * 8), "r"(8 * q), "r"(0) : "memory");
            asm volatile("cp.async.bulk.commit_group;" ::: "memory");
            asm volatile("cp.async.bulk.wait_group 0;" ::: "memory");
            asm volatile("fence.proxy.async.global;" ::: "memory");
            asm volatile("mbarrier.arrive.shared::cta.b64 _, [%0];" :: "r"(mb + MB_OUT * 8) : "memory");
        }
        STAMP(2);
        return;
    }

    const int g = lane >> 2, cq = lane & 3;
    const int k = warp >> 2, wq = warp & 3;
    const int trow = 18 * blockIdx.x + warp;
    const bool rowact = warp < 18 && trow < L_;
    const int dch = min(d0 + 8 * k + q, D_ - 1);
    uint32_t pv[6];
#pragma unroll
    for (int i = 0; i < 6; i++) pv[i] = ldg16(prm.prm6[i] + (uint32_t)(dch * 128 + wq * 32 + lane));
    const uint32_t pLdt = ldg16(prm.logdt + dch), pD = ldg16(prm.dskip + dch);
    const int tn = 16 * (warp & 15) + g;
    uint32_t xa[5], xb[5];
    asm volatile("barrier.cluster.arrive.relaxed.aligned;" ::: "memory");
    uint4* const st1p = &g_s.st1[(((trow >> 3) & 7) * 256 + ((trow >> 6) & 31) * 8 + (trow & 7)) * 2 + (lane >> 2)];
    const bool pub = rowact && (lane & 0x1B) == 0;
    if (pub) st_rlx128(st1p, 0, 0, 0, 0);
    {
        const uint32_t za = sb + SM_P + tid * 16;
        sts128(za, 0, 0, 0, 0);
        if (tid < (SM_MISC - SM_P) / 16 - 640) sts128(za + 10240, 0, 0, 0, 0);
        sts128(sb + ((wq & 2) ? SM_U : SM_XT + (q & 3) * 16) + ((tid >> 3) & 7) * ((wq & 2) ? UP : YP) + k * YS + (lane & 7) * 16, 0, 0, 0, 0);
    }
    bar_sync(12, NTHR);
    const uint32_t dep = lds32(sb + SM_P);
#define PV(x) __uint_as_float(__byte_perm(dep, x, 0x5410))
    STAMP(1);
    const uint32_t fb = sb + SM_FAR + k * FAR_SZ;
    const uint32_t pn = sb + SM_PN + k * PN_SZ, pf = sb + SM_PF + k * PF_SZ;
    unsigned epoch;
    {
        const uint32_t kb = fb + wq * 3072;
        const uint32_t kl = kb + lane * 16;
        uint32_t Af[4][4];
        float sr, si, z1r, z1i, z2r, z2i, z4r, z4i, hr, hi_;
        {
            const float dt = bfr(ex2f(PV(pLdt) * 1.4426950408889634f));
            const float e2 = dt * PV(pv[0]) * 1.4426950408889634f, an = dt * PV(pv[1]);
            cmul(sr, si, PV(pv[4]), PV(pv[5]), dt * PV(pv[2]), dt * PV(pv[3]));
            const unsigned E = min(max(__reduce_max_sync(~0u, __float_as_uint(fmaxf(fmaxf(fabsf(sr), fabsf(si)), fabsf(PV(pD)) * (1.f / 8192.f)))) >> 23, 1u), 253u);
            const float sc = __uint_as_float((254u - E) << 23);
            sr *= sc; si *= -sc;
            sts64(sb + SM_KG + warp * 8, E, __reduce_add_sync(~0u, __float2int_rn(sr * 16777216.f)));
            float ar, ai, br, bi, cr, ci, dr, di;
            { const float m = ex2f(e2 * 8.f); ar = m * __cosf(an * 8.f); ai = m * __sinf(an * 8.f); }
            csq(br, bi, ar, ai); csq(cr, ci, br, bi); csq(dr, di, cr, ci);
            const H2C m4 = splat(cr, ci);
            {
                float r3, i3;
                cmul(r3, i3, ar, ai, br, bi);
                expand4(kl, kl + 1024, pack_f16(1.f, ar), pack_f16(br, r3), pack_f16(0.f, ai), pack_f16(bi, i3), m4);
            }
            expand8(kl + 512, kl + 1536, dr, di, ar, ai, br, bi, m4);
            { const float m = ex2f(e2); z1r = m * __cosf(an); z1i = -m * __sinf(an); }
            cexp_s(hr, hi_, e2 * 128.f, an * (-128.f * 0.15915494309189535f));
            csq(z2r, z2i, z1r, z1i); csq(z4r, z4i, z2r, z2i);
        }
        __syncwarp();
#pragma unroll
        for (int ks = 0; ks < 4; ks++) ldsm4t(Af[ks], kb + (lane >> 3) * 512 + (lane & 7) * 16 + ks * 128);
        STAMP(2);
        const uint32_t la = kb + ((lane >> 3) & 1) * 512 + (lane >> 4) * 128 + (lane & 7) * 16;
        uint32_t kp[5][2], b0[4], b1[4], b2[4], b3[4];
        auto mm2 = [&](int t) {
            float a0[4] = {0.f, 0.f, 0.f, 0.f}, a1[4] = {0.f, 0.f, 0.f, 0.f};
            mma_f16(a0, Af[0], b0[0], b0[1]); mma_f16(a1, Af[0], b2[0], b2[1]); mma_f16(a0, Af[1], b0[2], b0[3]); mma_f16(a1, Af[1], b2[2], b2[3]);
            mma_f16(a0, Af[2], b1[0], b1[1]); mma_f16(a1, Af[2], b3[0], b3[1]); mma_f16(a0, Af[3], b1[2], b1[3]); mma_f16(a1, Af[3], b3[2], b3[3]);
            kp[t][0] = pack_f16(a0[1], a0[0]); kp[t][1] = pack_f16(a0[3], a0[2]); kp[t + 1][0] = pack_f16(a1[1], a1[0]); kp[t + 1][1] = pack_f16(a1[3], a1[2]);
        };
        auto ln1 = [&]() {
        mbar_wait(mb + MB_R * 8);
        epoch = lds32(sb + SM_SC + 28) + 1;
        {
            const uint32_t ra = sb + SM_ROW + warp * (D_ * 2);
            const uint4 r0 = lds128(ra + lane * 16), r1 = lds128(ra + 512 + lane * 16);
            const uint32_t rx[9] = {r0.x, r0.y, r0.z, r0.w, r1.x, r1.y, r1.z, r1.w, lds32(ra + 1024 + lane * 4)};
            float a0 = bf_lo(rx[0]), a1 = bf_hi(rx[0]), c0 = a0 * a0, c1 = a1 * a1;
#pragma unroll
            for (int i = 1; i < 9; i++) { const float l = bf_lo(rx[i]), h = bf_hi(rx[i]); a0 += l; a1 += h; c0 = fmaf(l, l, c0); c1 = fmaf(h, h, c1); }
            a0 += a1; c0 += c1;
            float s1 = ((lane & 1) ? c0 : a0) + __shfl_xor_sync(~0u, (lane & 1) ? a0 : c0, 1);
#pragma unroll
            for (int o = 2; o < 32; o <<= 1) s1 += __shfl_xor_sync(~0u, s1, o);
            const float s2 = __shfl_xor_sync(~0u, s1, 1);
            const uint32_t ms = ln_stats(s1, s2);
            const uint32_t p0 = __byte_perm(ms, epoch | 0x8000u, 0x5410), p1 = rsplit(rcpf(bf_hi(ms)));
            if (pub) st_rlx128(st1p, p0, p1, p0, p1);
        }
        mbar_wait(mb + MB_R * 8);
        STAMP(1);
        };
        const uint4* sp = &g_s.st1[(256 * q + tn) * 2];
        uint2 sa, sc;
        auto poll = [&]() { sa = ld_rlx64(sp); sc = ld_rlx64(sp + 16); };
        auto norm = [&]() {
        STAMP(3);
        if (warp < 16) {
            uint32_t va[5], vc[5];
            poll();
            mbar_wait(mb + MB_T * 8);
            {
                const uint32_t xt = sb + SM_XTL + (XW == 40 ? 0 : (c & 1) * 16) + (72 * wq + 18 * k + g) * (2 * XW);
                uint4 a4 = lds128(xt + cq * 16), b4 = lds128(xt + cq * 16 + 18 * XW);
                va[0] = a4.x; va[1] = a4.y; va[2] = a4.z; va[3] = a4.w; va[4] = lds32(xt + 64 + cq * 4);
                vc[0] = b4.x; vc[1] = b4.y; vc[2] = b4.z; vc[3] = b4.w; vc[4] = lds32(xt + (64 + 18 * XW) + cq * 4);
            }
            const int d4 = 2 * (lane >> 3) + (lane & 1), d1_ = lane & 7;
            const uint32_t own = SM_U + 128 + q * (UP - YP), oth = SM_XT + 128 + (q & 3) * 16;
            uint32_t a4 = sb + warp * 32 + d4 * YP + (d4 == q ? own : oth) + ((lane & 7) >> 1) * YS;
            uint32_t a1 = sb + warp * 32 + d1_ * YP + (d1_ == q ? own : oth) + 4 * YS + (lane & 8) * 2;
            PIN(a4); PIN(a1);
            uint32_t tag = __byte_perm(epoch | 0x8000u, 0, 0x1010);
            PIN(tag);
            mbar_wait(mb + MB_T * 8);
            int n = 0;
            while (__byte_perm(sa.x, sc.x, 0x7632) != tag && ++n < SPIN_LIMIT) poll();
            STAMP(4);
#pragma unroll
            for (int i = 0; i < 5; i++) {
                va[i] = norm2(va[i], sa.x, sa.y); va[i] = pack_f16(bf_lo(va[i]), bf_hi(va[i]));
                vc[i] = norm2(vc[i], sc.x, sc.y); vc[i] = pack_f16(bf_lo(vc[i]), bf_hi(vc[i]));
            }
            stsm4t(a4, va[0], va[1], va[2], va[3]); stsm4t(a4 + 16, vc[0], vc[1], vc[2], vc[3]); stsm2t(a1, va[4], vc[4]);
            {
            const uint32_t xh = sb + SM_XTL + (XW == 40 ? 0 : (c & 1) * 16) + (9 * g + 144 * (warp & 1) + (warp >> 1)) * (2 * XW);
            const uint4 c4 = lds128(xh + cq * 16), d4_ = lds128(xh + cq * 16 + 144 * XW);
            xa[0] = c4.x; xa[1] = c4.y; xa[2] = c4.z; xa[3] = c4.w; xa[4] = lds32(xh + 64 + cq * 4);
            xb[0] = d4_.x; xb[1] = d4_.y; xb[2] = d4_.z; xb[3] = d4_.w; xb[4] = lds32(xh + (64 + 144 * XW) + cq * 4);
            }
        }
        STAMP(5);
        bar_sync(13, 736);
        Af[0][0] |= lds32(sb + SM_P);
        };
        if (LNPOS == 0) ln1();
        cmul(sr, si, sr, si, z1r, z1i);
        {
            const H2C h4 = splat(z4r, z4i);
            expand8(kl, kl + 512, sr, si, z1r, z1i, z2r, z2i, h4);
            cmul(sr, si, sr, si, hr, hi_);
            expand8(kl + 1024, kl + 1536, sr, si, z1r, z1i, z2r, z2i, h4);
        }
        __syncwarp();
        ldsm4t(b0, la); ldsm4t(b1, la + 256); ldsm4t(b2, la + 1024); ldsm4t(b3, la + 1280);
        cmul(z1r, z1i, z1r, z1i, hr, hi_);
        cmul(sr, si, sr, si, z1r, z1i);
        if (LNPOS == 1) ln1();
        expand8(kl, kl + 512, sr, si, z2r, z2i, z4r, z4i, splat(hr, hi_));
        if (LNPOS == 2) ln1();
        csq(z1r, z1i, z1r, z1i);
        cmul(sr, si, sr, si, z1r, z1i);
        csq(z2r, z2i, hr, hi_);
        expand8(kl + 1024, kl + 1536, sr, si, z4r, z4i, hr, hi_, splat(z2r, z2i));
        if (LNPOS == 3) ln1();
        csq(z1r, z1i, z1r, z1i);
        cmul(sr, si, sr, si, z1r, z1i);
        csq(z4r, z4i, z2r, z2i);
        expand8(kl + 2048, kl + 2560, sr, si, hr, hi_, z2r, z2i, splat(z4r, z4i));
        if (LNPOS == 4) ln1();
        if (MMPOS == 0) norm();
        mm2(0);
        __syncwarp();
        ldsm4t(b0, la); ldsm4t(b1, la + 256); ldsm4t(b2, la + 1024); ldsm4t(b3, la + 1280);
        if (MMPOS == 1) norm();
        mm2(2);
        if (MMPOS == 2) norm();
        ldsm4t(b0, la + 2048); ldsm4t(b1, la + 2304);
#pragma unroll
        for (int t = 0; t < 4; t++) sts64(kb + lane * 8 + 1024 + t * 256, kp[t][0], kp[t][1]);
        {
            float a0[4] = {0.f, 0.f, 0.f, 0.f}, a1[4] = {0.f, 0.f, 0.f, 0.f};
            mma_f16(a0, Af[0], b0[0], b0[1]); mma_f16(a1, Af[1], b0[2], b0[3]); mma_f16(a0, Af[2], b1[0], b1[1]); mma_f16(a1, Af[3], b1[2], b1[3]);
            sts64(kb + lane * 8 + 2048, pack_f16(a0[1] + a1[1], a0[0] + a1[0]), pack_f16(a0[3] + a1[3], a0[2] + a1[2]));
        }
        bar_sync(1 + k, 128);
        const uint4 m01 = lds128(sb + SM_KG + k * 32), m23 = lds128(sb + SM_KG + k * 32 + 16);
        const unsigned Em = max(max(m01.x, m01.z), max(m23.x, m23.z));
        const float f0 = __uint_as_float(max((int)(127 + m01.x - Em), 0) << 23), f1 = __uint_as_float(max((int)(127 + m01.z - Em), 0) << 23),
                    f2 = __uint_as_float(max((int)(127 + m23.x - Em), 0) << 23), f3 = __uint_as_float(max((int)(127 + m23.z - Em), 0) << 23);
        const uint32_t r0 = pack_f16(f0, f0), r1 = pack_f16(f1, f1), r2 = pack_f16(f2, f2), r3 = pack_f16(f3, f3);
        const int tq = (wq + ROTK * k) & 3;
        const uint32_t ra = fb + lane * 8 + tq * 256 + 1024;
        const uint2 p0 = lds64(ra), p1 = lds64(ra + 3072), p2 = lds64(ra + 6144), p3 = lds64(ra + 9216);
        uint32_t w0 = hadd2(hfma2(p0.x, r0, hmul2(p1.x, r1)), hfma2(p2.x, r2, hmul2(p3.x, r3)));
        uint32_t w1 = hadd2(hfma2(p0.y, r0, hmul2(p1.y, r1)), hfma2(p2.y, r2, hmul2(p3.y, r3)));
        const bool last = lane == 31;
        if (tq < 2) {
            const uint32_t rc = fb + lane * 8 + tq * 4 + 2048;
            const uint32_t w4 = hmul2(hadd2(hfma2(lds32(rc), r0, hmul2(lds32(rc + 3072), r1)), hfma2(lds32(rc + 6144), r2, hmul2(lds32(rc + 9216), r3))), 0x18001800u);
            const uint32_t ph = pf + (P_H7 + 16 * tq) + (g & 1) * (2 * P_HS) + cq * 64 + (g >> 1) * 4;
            put16(ph, w4 >> 16); put16(ph + 32, w4);
            const uint32_t pa = pn + (4 + 512 * tq) + lane * 8;
            sts16(pa, w0 >> 16); sts32(pa + 4, w0); sts16(pa + 10, w0);
            sts16(pa + 256, w1 >> 16); sts32(pa + 260, w1); sts16(pa + 266, w1);
            if (last) {
                sts32(sb + SM_SC + k * 4, Em * 0x00800080u);
                put16(tq ? pa + 264 : pn,
                      tq ? w1 : pack_f16(((float)(int)m01.y * f0 + (float)(int)m01.w * f1 + (float)(int)m23.y * f2 + (float)(int)m23.w * f3) * (1.f / 16777216.f)
                                         + __uint_as_float(pD << 16) * __uint_as_float((254u - Em) << 23), 0.f));
            }
        } else if (tq == 2) {
            const uint32_t pa = pn + 258 * 4 + (cq & 1) * 16 + (cq >> 1) * 512 + g * 32;
            if (last) { put16(pf, hmul2(w1, 0x18001800u)); w1 = hadd2(w1, hneg2(__byte_perm(w1, 0, 0x1010))); }
            const uint32_t b0 = __byte_perm(w0, 0, 0x1010), b1 = __byte_perm(w1, 0, 0x1010);
            sts16(pa, w0 >> 16); sts32(pa + 4, w0); sts64(pa + 8, b0, b0); sts16(pa + 18, w0);
            sts16(pa + 256, w1 >> 16); sts32(pa + 260, w1); sts64(pa + 264, b1, b1); sts16(pa + 274, w1);
        } else {
            const uint32_t pa = pf + ((g & 1) ? 3 * P_GS : P_GS) + cq * 32 + (g >> 1) * 4;
            const uint32_t pb = pa + ((g & 1) ? 4 - 3 * P_GS : P_GS);
            w0 = hmul2(w0, 0x18001800u); w1 = hmul2(w1, 0x18001800u);
            put16(pa, w0 >> 16); put16(pb, w0); put16(pa + 16, w1 >> 16); put16(pb + 16, w1);
            if (last) put16(pf + P_H7 + P_HS, w1);
        }
        bar_sync(1 + k, 128);
    }
    STAMP(6);

    asm volatile("barrier.cluster.wait.aligned;" ::: "memory");
    mbar_wait(mb + (MB_X + (k < XSPLIT || k >= nslot)) * 8);
    STAMP(7);
    if (k < nslot) {
        const int role = (wq + k) & 3;
        const uint32_t ub = sb + SM_U + k * US + 128;
        if (role) {
            const int r = (3 - role) * 32 + lane;
            const uint32_t a1 = ub + (r & 3) * (2 * UP) + (r >> 2) * 16, a0 = a1 + ((r & 3) ? -2 * UP : 6 * UP - 16);
            const uint4 q0 = lds128(a0), q1 = lds128(a0 + UP), q2 = lds128(a1), q3 = lds128(a1 + UP);
            const uint32_t U[16] = {q0.x, q0.y, q0.z, q0.w, q1.x, q1.y, q1.z, q1.w, q2.x, q2.y, q2.z, q2.w, q3.x, q3.y, q3.z, q3.w};
            uint32_t V[14], Q[14], R4[12], T[8];
#pragma unroll
            for (int i = 2; i < 14; i++) { V[i] = __byte_perm(U[i], U[i + 1], 0x5432); Q[i] = hadd2(U[i], V[i]); }
#pragma unroll
            for (int i = 2; i < 12; i++) R4[i] = hadd2(Q[i], Q[i + 1]);
            const uint32_t rb = fb + r * 16;
#pragma unroll
            for (int i = 0; i < 8; i++) T[i] = hadd2(V[5 + i], Q[6 + i]);
            sts128(rb + F_E3, T[0], T[1], T[2], T[3]); sts128(rb + F_O3 + 16, T[4], T[5], T[6], T[7]);
#pragma unroll
            for (int i = 0; i < 8; i++) T[i] = hadd2(R4[3 + i], U[5 + i]);
            sts128(rb + F_O5, T[0], T[1], T[2], T[3]); sts128(rb + F_E5, T[4], T[5], T[6], T[7]);
            if (role != 1) {
#pragma unroll
                for (int i = 0; i < 8; i++) T[i] = hadd2(T[i], hadd2(V[2 + i], V[5 + i]));
                sts128(rb + F_E7, T[0], T[1], T[2], T[3]); sts128(rb + F_O7, T[4], T[5], T[6], T[7]);
#pragma unroll
                for (int i = 0; i < 8; i++) T[i] = hadd2(R4[2 + i], hadd2(R4[4 + i], U[6 + i]));
                sts128(rb + F_O9, T[0], T[1], T[2], T[3]); sts128(rb + F_E9 + 16, T[4], T[5], T[6], T[7]);
                sts128(rb + F_E2, Q[6], Q[7], Q[8], Q[9]); sts128(rb + F_O2, Q[10], Q[11], Q[12], Q[13]);
            }
        } else if (lane < 8) {
            uint32_t v[5];
#pragma unroll
            for (int i = 0; i < 5; i++) { const int t = 6 + lane + i; v[i] = lds16(ub + 23 * 16 + (t < 16 ? (6 + (t >> 3)) * UP : 16) + (t & 7) * 2); }
            const uint32_t s = hadd2(hadd2(hadd2(v[0], v[1]), hadd2(v[2], v[3])), v[4]);
            sts16(fb + F_O5 + 96 * 16 + lane * 2, s);
            sts32(fb + (lane < 4 ? F_O3 : F_E9 - 16) + lane * 4, 0);
        }
        bar_sync(1 + k, 128);
        float acc[4][4];
        uint32_t Q[4][4];
        {
            const int h = role & 1, part = role >> 1;
            const uint32_t po = pf + (g - 2 * cq) * 4;
            float fa[7][4];
#pragma unroll
            for (int a = 0; a < 7; a++) fa[a][0] = fa[a][1] = fa[a][2] = fa[a][3] = 0.f;
            uint32_t B[3][4];
            Q[0][2] = zero;
#pragma unroll 1
            for (int s = 2 * part + 1; s >= 2 * part; s--) {
#pragma unroll
                for (int i = 0; i < 3; i++) { Q[i][0] = lds32(po + s * P_GS + i * 64); Q[i][1] = lds32(po + s * P_GS + (i * 64 + 32)); }
                const uint32_t ba = fb + lane * 16 + ((s & 1) * F_E3 + (part == h ? 0 : F_O5 + h * 16));
#pragma unroll
                for (int i = 0; i < 3; i++) ldsm4t(B[i], ba + i * 512);
#pragma unroll
                for (int i = 0; i < 3; i++) { Q[i][3] = CP(Q[i][0]); if (i) Q[i][2] = CP(Q[i - 1][1]); }
#pragma unroll
                for (int dl = 0; dl < 3; dl++)
#pragma unroll
                    for (int ap = 0; ap < 6 - dl; ap++) mma_f16(fa[ap + 1 + dl], Q[dl], B[ap >> 1][2 * (ap & 1)], B[ap >> 1][2 * (ap & 1) + 1]);
            }
#pragma unroll 1
            for (int s = role; s == 1; s++) {
                ldsm2t(B[0][0], B[0][1], fb + ((lane & 15) == 15 ? F_O5 : F_O3));
#pragma unroll
                for (int dl = 0; dl < 3; dl++) mma_f16(fa[dl], Q[dl], B[0][0], B[0][1]);
            }
#pragma unroll 1
            for (int s = part; s <= 2 * part; s++) {
#pragma unroll
                for (int i = 0; i < 4; i++) { Q[i][0] = lds32(po + s * P_HS + (P_H7 + i * 64)); Q[i][1] = lds32(po + s * P_HS + (P_H7 + i * 64 + 32)); }
                const uint32_t ba = fb + lane * 16 + (F_E7 + s * 1024 + h * F_H);
                ldsm4t(B[0], ba); ldsm4t(B[1], ba + 512);
#pragma unroll
                for (int i = 0; i < 4; i++) { Q[i][3] = CP(Q[i][0]); if (i) Q[i][2] = CP(Q[i - 1][1]); }
#pragma unroll
                for (int dl = 0; dl < 4; dl++) {
#pragma unroll
                    for (int ap = 0; ap < 4 - dl; ap++) mma_f16(fa[ap + 3 + dl], Q[dl], B[ap >> 1][2 * (ap & 1)], B[ap >> 1][2 * (ap & 1) + 1]);
                    if (s == 1) break;
                }
            }
            const uint32_t da = fb + role * 2048 + (lane & 3) * 512 + (((lane >> 2) ^ ((lane & 3) * 2)) << 4);
            bar_sync(1 + k, 128);
            stsm4(da, 0u, 0u, pack_f16(fa[0][0], fa[0][1]), pack_f16(fa[0][2], fa[0][3]));
#pragma unroll
            for (int i = 1; i < 4; i++)
                stsm4(da + i * 128, pack_f16(fa[2 * i - 1][0], fa[2 * i - 1][1]), pack_f16(fa[2 * i - 1][2], fa[2 * i - 1][3]),
                      pack_f16(fa[2 * i][0], fa[2 * i][1]), pack_f16(fa[2 * i][2], fa[2 * i][3]));
            Q[0][0] = (g == 2 * cq) ? 0x6000u : ((g == 2 * cq + 1) ? 0x60000000u : 0u);
            Q[0][1] = 0; Q[0][3] = CP(Q[0][0]);
            const uint32_t ra = fb + (lane >> 3) * 2048 + wq * 512 + (((lane & 7) ^ (wq * 2)) << 4);
            bar_sync(1 + k, 128);
#pragma unroll
            for (int i = 0; i < 4; i++) {
                ldsm4(B[0], ra + i * 128);
                acc[i][0] = acc[i][1] = acc[i][2] = acc[i][3] = 0.f;
                mma_f16(acc[i], Q[0], hadd2(B[0][0], B[0][2]), hadd2(B[0][1], B[0][3]));
            }
        }
        bar_arrive(6 + k, 160);
        STAMP(8);
        const uint32_t inv = lds32(sb + SM_SC + k * 4);
        uint32_t yd = mapa(sb, 2 * wq) + (SM_XT + 128 + q * YP + k * YS + (k >> 2) * (q >> 1) * 16) + lane * 16;
        PIN(yd);
        {
            uint32_t pp = pn + (16 * (wq - 3) + g - 2 * cq) * 4;
            uint32_t dlo = (((ub + 6 * UP) & 0x3FFFF) >> 4) | ((UP >> 4) << 16);
            uint32_t R[4][4];
            auto loadQ = [&](uint32_t (&X)[4][4], uint32_t prev) {
#pragma unroll
                for (int i = 0; i < 4; i++) { X[i][0] = lds32(pp + i * 64); X[i][1] = lds32(pp + i * 64 + 32); }
                X[0][2] = CP(prev);
#pragma unroll
                for (int i = 0; i < 4; i++) { X[i][3] = CP(X[i][0]); if (i) X[i][2] = CP(X[i - 1][1]); }
                pp += 256;
            };
            auto issue = [&](uint32_t (&X)[4][4]) {
                asm volatile("wgmma.fence.sync.aligned;" ::: "memory");
#pragma unroll
                for (int i = 0; i < 4; i++) wgmma32(acc, X[i], dlo - i * (2 * UP >> 4));
                asm volatile("wgmma.commit_group.sync.aligned;" ::: "memory");
                dlo -= 1;
            };
            loadQ(Q, 0);
#pragma unroll 1
            for (int dl = 0; dl < 4; dl++) {
                issue(Q);
                asm volatile("wgmma.wait_group.sync.aligned 1;" ::: "memory");
                loadQ(R, Q[3][1]);
                issue(R);
                asm volatile("wgmma.wait_group.sync.aligned 1;" ::: "memory");
                loadQ(Q, R[3][1]);
            }
            issue(Q);
            asm volatile("wgmma.wait_group.sync.aligned 0;" ::: "memory");
        }
        const uint32_t pstep = mapa(sb, 1) - mapa(sb, 0), ym = mapa(mb + MB_Y * 8, 2 * wq);
#pragma unroll
        for (int e = 0; e < 2; e++)
            st_async4(yd + e * pstep, bmul2(pack_bf16(acc[0][2 * e], acc[0][2 * e + 1]), inv), bmul2(pack_bf16(acc[1][2 * e], acc[1][2 * e + 1]), inv),
                      bmul2(pack_bf16(acc[2][2 * e], acc[2][2 * e + 1]), inv), bmul2(pack_bf16(acc[3][2 * e], acc[3][2 * e + 1]), inv), ym + e * pstep);
        if (lane == 0) asm volatile("mbarrier.arrive.shared::cta.b64 _, [%0];" :: "r"(mb + MB_Y * 8) : "memory");
    }
    STAMP(9);
    uint32_t ha[5], hb[5];
    if (warp < 16) {
        const uint4 wk = lds128(sb + SM_DW + cq * 16);
        uint32_t sel[5] = {wk.x, wk.y, wk.z, wk.w, lds32(sb + SM_DW + 64 + cq * 4)}, sel2[5];
#pragma unroll
        for (int i = 0; i < 5; i++) {
            if (!(g & 1)) sel[i] = 0x3F803F80u;
            sel2[i] = sel[i]; PIN(sel2[i]);
        }
        const uint32_t y4 = sb + SM_XT + 128 + warp * 32 + (2 * (lane >> 3) + (lane & 1)) * YP + ((lane & 7) >> 1) * YS;
        const uint32_t y1 = sb + SM_XT + 128 + warp * 32 + (lane & 7) * YP + 4 * YS + (lane & 8) * 2 + (lane & 6) * 8;
        uint32_t ao = (256 * q + tn) * 16, hta = sb + SM_HT + tn * 80;
        PIN(ao); PIN(hta);
        mbar_wait(mb + MB_Y * 8);
        STAMP(10);
        float ca[4] = {0.f, 0.f, 0.f, 0.f}, cb[4] = {0.f, 0.f, 0.f, 0.f};
        {
            uint32_t ya[4], yb[4], yc, yd;
            ldsm4t(ya, y4); ldsm4t(yb, y4 + 16); ldsm2t(yc, yd, y1);
#pragma unroll
            for (int i = 0; i < 4; i++) { ha[i] = badd2(xa[i], ya[i]); hb[i] = badd2(xb[i], yb[i]); }
            ha[4] = badd2(xa[4], yc); hb[4] = badd2(xb[4], yd);
        }
        if (nslot != 5) {
            ha[4] = hb[4] = 0;
            if (cq >= 2) ha[0] = ha[1] = ha[2] = ha[3] = hb[0] = hb[1] = hb[2] = hb[3] = 0;
        }
#pragma unroll
        for (int i = 0; i < 5; i++) { mma_bf16_k8(ca, ha[i], sel[i], ha[i]); mma_bf16_k8(cb, hb[i], sel2[i], hb[i]); }
        if (!(g & 1)) { ca[1] = ca[0]; cb[1] = cb[0]; }
        if (cq == (g >> 1)) {
            asm volatile("red.relaxed.gpu.global.add.v4.f32 [%0], {%1,%2,%3,%4};" :: "l"((char*)g_s.acc + ao), "f"(1.0f), "f"(ca[1]), "f"(ca[2]), "f"(ca[3]) : "memory");
            asm volatile("red.relaxed.gpu.global.add.v4.f32 [%0], {%1,%2,%3,%4};" :: "l"((char*)g_s.acc + ao + 128), "f"(1.0f), "f"(cb[1]), "f"(cb[2]), "f"(cb[3]) : "memory");
        }
        sts128(hta + cq * 16, ha[0], ha[1], ha[2], ha[3]); sts32(hta + 64 + cq * 4, ha[4]);
        sts128(hta + cq * 16 + 640, hb[0], hb[1], hb[2], hb[3]); sts32(hta + 704 + cq * 4, hb[4]);
        STAMP(11);
    }
    const int kq = warp / 5, mt = warp - 5 * kq;
    const int mi = lane >> 3, mr = lane & 7;
    const unsigned tk = (unsigned)tid / 72u, ck = tid - tk * 72;
    uint32_t A[9][4];
    auto loadA = [&]() {
        mbar_wait(mb + MB_W1 * 8);
        const uint32_t aa = sb + (mi & 1) * SM_WU + (8 * (mi >> 1) + mr) * 80 + (144 * 80 * kq + mt * 16);
#pragma unroll
        for (int s = 0; s < 9; s++) ldsm4t(A[s], aa + s * 1280);
    };
    const uint32_t par = (epoch & 1) ? 0x40004000u : 0u;
    uint32_t pk0 = mapa(sb, 2 * cq), go = (ck / 5u + ck) * 16, co = ((q * 8 * NCL + c) * 6 + cq) * 16;
    PIN(pk0); PIN(go); PIN(co);
    if (warp < 8) {
        const float wsum = ldsf(sb + SM_SC + 24);
        const uint32_t idx = 2047 - (512 * ((tid >> 1) & 3) + 128 * ((tid >> 3) & 3) + 64 * (tid & 1) + 8 * q + warp);
        uint4 s; int n = 0;
        do { s = ld_rlx128(&g_s.acc[256 * q + tid]); } while (__uint_as_float(s.x) != (float)NCL && ++n < SPIN_LIMIT);
        STAMP(16);
        const uint32_t ox = __shfl_xor_sync(~0u, (lane & 1) ? s.z : s.w, 1);
        const uint32_t ms = ln_stats(__uint_as_float((lane & 1) ? ox : s.z), __uint_as_float(s.y));
        const float rs = rcpf(bf_hi(ms));
        const uint32_t rb = pack_bf16(0.f, fmaf(-bf_lo(ms), wsum, __uint_as_float((lane & 1) ? s.w : ox)) * rs);
        const uint32_t key = (((rb ^ (((int)rb >> 31) | 0x80000000u)) >> 16) << 11) | idx;
        sts32(sb + SM_KEY + tid * 4, key);
        __syncwarp();
        const uint32_t rank = rank4<8, 16>(sb + SM_KEY + warp * 128, key);
        if (rank < 8) sts32(sb + SM_CAND + warp * 32 + rank * 4, key);
        sts64(sb + SM_ST + tid * 8, ms, rsplit(rs));
    } else loadA();
    if (warp < 16) {
        STAMP(17);
        bar_sync(12, 512);
        STAMP(18);
        if (warp < 8) {
            const uint32_t mk = lds32(sb + SM_CAND + (tid >> 2) * 4);
            uint32_t rank = rank4<4, 64>(sb + SM_CAND + cq * 16, mk);
            rank += __shfl_xor_sync(~0u, rank, 1); rank += __shfl_xor_sync(~0u, rank, 2);
            if (rank < 8) {
                const uint32_t pk1 = pk0 + (mapa(sb, 1) - mapa(sb, 0));
                st_async1(pk0 + (SM_RK + q * 32) + rank * 4, mk, pk0 + (SM_MB + MB_KEY * 8));
                st_async1(pk1 + (SM_RK + q * 32) + rank * 4, mk, pk1 + (SM_MB + MB_KEY * 8));
                const uint32_t t = tslot(~mk);
                const uint2 sv = lds64(sb + SM_ST + t * 8);
                const uint4 hv = lds128(sb + SM_HT + t * 80 + cq * 16);
                const uint32_t h4 = lds32(sb + SM_HT + t * 80 + 64 + cq * 4);
                const uint32_t rr = bmul2(sv.y, 0x3C803C80u);
                char* const dp = (char*)g_s.cand + (co + rank * 1440);
                st_rlx128(dp, (norm2(hv.x, sv.x, rr) & 0xBFFFBFFFu) | par, (norm2(hv.y, sv.x, rr) & 0xBFFFBFFFu) | par,
                          (norm2(hv.z, sv.x, rr) & 0xBFFFBFFFu) | par, (norm2(hv.w, sv.x, rr) & 0xBFFFBFFFu) | par);
                asm volatile("st.relaxed.gpu.global.u32 [%0], %1;" :: "l"((char*)g_s.cand + (co + rank * 1440 + 64 - cq * 12)), "r"((norm2(h4, sv.x, rr) & 0xBFFFBFFFu) | par) : "memory");
            }
            __syncwarp();
        }
        {
            const uint2 sa = lds64(sb + SM_ST + tn * 8), sbb = lds64(sb + SM_ST + tn * 8 + 64);
#pragma unroll
            for (int i = 0; i < 5; i++) { ha[i] = badd2(ha[i], norm2(ha[i], sa.x, sa.y)); hb[i] = badd2(hb[i], norm2(hb[i], sbb.x, sbb.y)); }
            const bool hf = (c & 1) && cq == 0;
            const uint32_t o16 = sb + SM_XT + (hf ? 16384 + tn * 16 : tn * 64 + (cq - (c & 1)) * 16), o4 = sb + SM_XT + ((c & 1) ? tn * 64 + 48 : 16384 + tn * 16) + cq * 4;
            sts128(o16, ha[0], ha[1], ha[2], ha[3]); sts32(o4, ha[4]);
            sts128(o16 + (hf ? 128 : 512), hb[0], hb[1], hb[2], hb[3]); sts32(o4 + ((c & 1) ? 512 : 128), hb[4]);
        }
        if (warp >= 8) {
            STAMP(19);
            mbar_wait(mb + MB_KEY * 8);
            STAMP(20);
            const uint32_t mk = lds32(sb + SM_RK - 256 + (tid >> 2) * 4);
            uint32_t rank = rank4<4, 64>(sb + SM_RK + cq * 16, mk);
            rank += __shfl_xor_sync(~0u, rank, 1); rank += __shfl_xor_sync(~0u, rank, 2);
            if (rank < 8) sts64(sb + SM_SEL + rank * 8, mk, ((tid >> 2) - 64) * 1440);
        }
    }
    bar_sync(11, 640);
    STAMP(12);

    const char* gp = (const char*)g_s.cand + (go + lds32(sb + SM_SEL + 4 + (tk & 7) * 8));
    uint4 hv = ld_rlx128(gp);
    if (warp < 8) loadA();
    const bool red = warp < 6;
    const uint32_t ft = red ? (unsigned)tid / 24u : (unsigned)(tid >> 4) & 7u, fj = red ? 24 * q + tid - ft * 24 : d0 / 3 + (lane & 15);
    const uint32_t key = lds32(sb + SM_SEL + ft * 8), k16 = key << 5;
    float sig = bfr(rcpf(1.f + ex2f(__uint_as_float((k16 ^ (~((int)k16 >> 31) | 0x80000000u)) & 0xFFFF0000u) * -1.4426950408889634f)));
    uint32_t ra2 = sb + SM_RED2 + tid * 12 + ft * 16, fo = (ft * 192 + fj) * 16, oo = ((~key & 2047) * D_ + 3 * fj) * 2;
    uint32_t bx = sb + SM_XS + mr * 1168 + mi * 16 + 288 * kq, gd = mapa(sb, kq * (8 / NRED)) + (SM_GU + (q * nslot + mt) * 128) + lane * 4;
    PIN(ra2); PIN(fo); PIN(oo); PIN(bx); PIN(gd);
    asm volatile("" : "+f"(sig));
    {
        if (warp < 18) {
            int n = 0;
            while ((((hv.x ^ par) | (hv.y ^ par) | (hv.z ^ par) | (hv.w ^ par)) & 0x40004000u) && ++n < SPIN_LIMIT) hv = ld_rlx128(gp);
            sts128(sb + SM_XS + tk * 16 + tid * 16, hv.x ^ par, hv.y ^ par, hv.z ^ par, hv.w ^ par);
        }
    }
    bar_sync(14, 672);
    STAMP(13);
    {
        float c0[4] = {0.f, 0.f, 0.f, 0.f}, c1[4] = {0.f, 0.f, 0.f, 0.f}, c2[4] = {0.f, 0.f, 0.f, 0.f};
        uint32_t b[5][4];
#pragma unroll
        for (int s = 0; s < 4; s++) ldsm4(b[s], bx + s * 64);
        asm volatile("ldmatrix.sync.aligned.m8n8.x2.shared.b16 {%0,%1}, [%2];" : "=r"(b[4][0]), "=r"(b[4][1]) : "r"(bx + 256) : "memory");
        mma_bf16(c0, A[0][0], A[0][1], A[0][2], A[0][3], b[0][0], b[0][1]);
        mma_bf16(c1, A[1][0], A[1][1], A[1][2], A[1][3], b[0][2], b[0][3]);
        mma_bf16(c2, A[2][0], A[2][1], A[2][2], A[2][3], b[1][0], b[1][1]);
        mma_bf16(c0, A[3][0], A[3][1], A[3][2], A[3][3], b[1][2], b[1][3]);
        mma_bf16(c1, A[4][0], A[4][1], A[4][2], A[4][3], b[2][0], b[2][1]);
        mma_bf16(c2, A[5][0], A[5][1], A[5][2], A[5][3], b[2][2], b[2][3]);
        mma_bf16(c0, A[6][0], A[6][1], A[6][2], A[6][3], b[3][0], b[3][1]);
        mma_bf16(c1, A[7][0], A[7][1], A[7][2], A[7][3], b[3][2], b[3][3]);
        mma_bf16(c2, A[8][0], A[8][1], A[8][2], A[8][3], b[4][0], b[4][1]);
        sts128f(sb + SM_RED + tid * 16, c0[0] + c1[0] + c2[0], c0[1] + c1[1] + c2[1], c0[2] + c1[2] + c2[2], c0[3] + c1[3] + c2[3]);
    }
    bar_sync(1 + mt, 128);
    STAMP(21);
    if (mt < nslot && kq < NRED) {
        const uint32_t ra = sb + SM_RED + mt * 512 + lane * 16;
        const float4 p0 = lds128f(ra), p1 = lds128f(ra + 2560), p2 = lds128f(ra + 5120), p3 = lds128f(ra + 7680);
        const float g0 = bfr(((p0.x + p1.x) + (p2.x + p3.x)) * 64.f), g1 = bfr(((p0.y + p1.y) + (p2.y + p3.y)) * 64.f);
        const uint32_t sg = pack_bf16(g0 * rcpf(1.f + ex2f(g0 * -1.4426950408889634f)), g1 * rcpf(1.f + ex2f(g1 * -1.4426950408889634f)));
        const uint32_t gu = bmul2(sg, pack_bf16(((p0.z + p1.z) + (p2.z + p3.z)) * 64.f, ((p0.w + p1.w) + (p2.w + p3.w)) * 64.f));
        const uint32_t pstep = mapa(sb, 1) - mapa(sb, 0), gm = mapa(mb + MB_GU * 8, kq * (8 / NRED));
#pragma unroll
        for (int i = 0; i < 8 / NRED; i++) st_async1(gd + i * pstep, gu, gm + i * pstep);
    }
    mbar_wait(mb + MB_W2 * 8);
    {
        const uint32_t aa = sb + (8 * (mi >> 1) + mr) * (2 * W2W) + (mi & 1) * 16 + (SM_FAR + 32 * W2W * kq + mt * 32 + (W2W == 72 ? 0 : (q & 1) * 16));
#pragma unroll
        for (int s = 0; s < 5; s++) ldsm4t(A[s], aa + s * FAR_SZ);
    }
    {
        uint32_t ba = sb + (SM_GU + 256 * kq) + (lane & 15) * 16 + (lane >> 4) * 1024, wa = sb + (SM_RED2 + kq * 2432 + mt * 64) + g * 4 + cq * 608;
        PIN(ba); PIN(wa);
        STAMP(22);
        mbar_wait(mb + MB_GU * 8);
        STAMP(23);
        float c0[4] = {0.f, 0.f, 0.f, 0.f}, c1[4] = {0.f, 0.f, 0.f, 0.f}, c2[4] = {0.f, 0.f, 0.f, 0.f};
        uint32_t b[2][4], b8, b9;
        ldsm4t(b[0], ba); ldsm4t(b[1], ba + 2048); ldsm2t(b8, b9, ba + 4096);
        mma_bf16(c0, A[0][0], A[0][1], A[0][2], A[0][3], b[0][0], b[0][1]);
        mma_bf16(c1, A[1][0], A[1][1], A[1][2], A[1][3], b[0][2], b[0][3]);
        if (nslot == 5) {
            mma_bf16(c2, A[4][0], A[4][1], A[4][2], A[4][3], b8, b9);
            mma_bf16(c0, A[2][0], A[2][1], A[2][2], A[2][3], b[1][0], b[1][1]);
            mma_bf16(c1, A[3][0], A[3][1], A[3][2], A[3][3], b[1][2], b[1][3]);
        }
        stsf(wa, c0[0] + c1[0] + c2[0]); stsf(wa + 304, c0[1] + c1[1] + c2[1]);
        if (mt < 4) { stsf(wa + 32, c0[2] + c1[2] + c2[2]); stsf(wa + 336, c0[3] + c1[3] + c2[3]); }
    }
    if (warp < 10) {
        float v[3], cnt = 3.f;
        if (red) {
            bar_sync(6, 640);
            STAMP(14);
#pragma unroll
            for (int i = 0; i < 3; i++) v[i] = ((ldsf(ra2 + i * 4) + ldsf(ra2 + i * 4 + 2432)) + (ldsf(ra2 + i * 4 + 4864) + ldsf(ra2 + i * 4 + 7296))) * sig;
        } else {
            bar_arrive(6, 640);
            cnt = 0.f;
#pragma unroll
            for (int i = 0; i < 3; i++) {
                const uint32_t cl = 3 * fj + i - d0;
                const bool ok = cl < 8 * nslot && ((~key >> 3) & 7) == q;
                const uint32_t cf = cl - (c & 1) * 8;
                v[i] = ok ? __uint_as_float(lds16(sb + SM_XT + (cf < 32 ? tslot(~key) * 64 + cf * 2 : 16384 + tslot(~key) * 16 + (cl & 7) * 2)) << 16) : 0.f;
                if (ok) cnt += 1.f;
            }
            mbar_wait(mb + MB_OUT * 8);
        }
        if (cnt != 0.f) {
            float x, y, z, w;
            asm volatile("atom.relaxed.gpu.global.add.v4.f32 {%0,%1,%2,%3}, [%4], {%5,%6,%7,%8};" : "=f"(x), "=f"(y), "=f"(z), "=f"(w)
                         : "l"((char*)g_s.fin + fo), "f"(v[0]), "f"(v[1]), "f"(v[2]), "f"(cnt) : "memory");
            if (w + cnt == 3.f * (NCL + 1)) {
                __nv_bfloat16* op = (__nv_bfloat16*)((char*)prm.out + oo);
                op[0] = __float2bfloat16(x + v[0]); op[1] = __float2bfloat16(y + v[1]); op[2] = __float2bfloat16(z + v[2]);
            }
        }
    } else bar_arrive(6, 640);
    STAMP(15);
}

typedef __nv_bfloat16 bf16;
__device__ bf16 f_n[L_ * D_], f_h[L_ * D_];
__device__ float f_k[D_ * L_], f_r[L_], f_gu[8 * F_];
__device__ int f_idx[8];
__device__ __forceinline__ float b2f(bf16 v) { return __bfloat162float(v); }
__global__ void fb_ln(const bf16* in, const bf16* wr, bf16* out) {
    const int t = blockIdx.x * 8 + (threadIdx.x >> 5), lane = threadIdx.x & 31;
    const bf16* r = (in ? in : f_h) + t * D_;
    float s1 = 0.f, s2 = 0.f, s3 = 0.f;
    for (int i = lane; i < D_; i += 32) s1 += b2f(r[i]);
    for (int o = 16; o; o >>= 1) s1 += __shfl_xor_sync(~0u, s1, o);
    for (int i = lane; i < D_; i += 32) { const float d = b2f(r[i]) - s1 / D_; s2 += d * d; }
    for (int o = 16; o; o >>= 1) s2 += __shfl_xor_sync(~0u, s2, o);
    const float m = bfr(s1 / D_), sd = bfr(sqrtf(bfr(bfr(s2 / D_) + 1e-5f)));
    for (int i = lane; i < D_; i += 32) {
        const float v = bfr(bfr(b2f(r[i]) - m) / sd);
        f_n[t * D_ + i] = __float2bfloat16(v);
        if (!in) { s3 += v * b2f(wr[i]); out[t * D_ + i] = __float2bfloat16(b2f(r[i]) + v); }
    }
    for (int o = 16; o; o >>= 1) s3 += __shfl_xor_sync(~0u, s3, o);
    f_r[t] = bfr(s3);
}
__global__ void fb_taps(Params p) {
    const int d = blockIdx.x >> 3, l = (blockIdx.x & 7) * 256 + threadIdx.x;
    const float dt = bfr(expf(bf_lo(p.logdt[d]))), lf = bfr((float)l);
    float k = 0.f;
    for (int n = d * 128; n < d * 128 + 128; n++) {
        float wr, wi, sn, cs;
        cmul(wr, wi, bf_lo(p.prm6[4][n]), bf_lo(p.prm6[5][n]), dt * bf_lo(p.prm6[2][n]), dt * bf_lo(p.prm6[3][n]));
        sincosf(dt * bf_lo(p.prm6[1][n]) * lf, &sn, &cs);
        k += expf(dt * bf_lo(p.prm6[0][n]) * lf) * (wr * cs - wi * sn);
    }
    f_k[l * D_ + d] = k;
}
__global__ void fb_conv(Params p) {
    const int t = blockIdx.x, d = threadIdx.x;
    float y = 0.f;
    for (int l = 0; l <= t; l++) y += f_k[l * D_ + d] * b2f(f_n[(t - l) * D_ + d]);
    f_h[t * D_ + d] = __float2bfloat16(bf_lo(p.x[t * D_ + d]) + bfr(bfr(y) + bfr(b2f(f_n[t * D_ + d]) * bf_lo(p.dskip[d]))));
}
__global__ void fb_top() {
    const int t = blockIdx.x * 256 + threadIdx.x;
    int rank = 0;
    for (int j = 0; j < L_; j++) rank += f_r[j] > f_r[t] || (f_r[j] == f_r[t] && j < t);
    if (rank < 8) f_idx[rank] = t;
}
__global__ void fb_ffn1(const bf16* wg, const bf16* wu) {
    const int f = blockIdx.x * 256 + threadIdx.x, j = blockIdx.y;
    float g = 0.f, u = 0.f;
    for (int i = 0; i < D_; i++) { const float v = b2f(f_n[f_idx[j] * D_ + i]); g += v * b2f(wg[i * F_ + f]); u += v * b2f(wu[i * F_ + f]); }
    g = bfr(g);
    f_gu[j * F_ + f] = bfr(bfr(g / (1.f + expf(-g))) * bfr(u));
}
__global__ void fb_ffn2(const bf16* wd, bf16* out) {
    const int d = threadIdx.x, j = blockIdx.x, t = f_idx[j];
    float y = 0.f;
    for (int f = 0; f < F_; f++) y += f_gu[j * F_ + f] * b2f(wd[f * D_ + d]);
    out[t * D_ + d] = __float2bfloat16(b2f(f_h[t * D_ + d]) + bfr(b2f(f_n[t * D_ + d]) + bfr(bfr(y) * bfr(1.f / (1.f + expf(-f_r[t]))))));
}

typedef CUresult (*EncodeFn)(CUtensorMap*, CUtensorMapDataType, cuuint32_t, void*, const cuuint64_t*, const cuuint64_t*,
                             const cuuint32_t*, const cuuint32_t*, CUtensorMapInterleave, CUtensorMapSwizzle,
                             CUtensorMapL2promotion, CUtensorMapFloatOOBfill);

void make_map(EncodeFn fn, CUtensorMap* tm, const void* p, int cols, int rows, int bc, int br) {
    cuuint64_t dims[2] = {(cuuint64_t)cols, (cuuint64_t)rows};
    cuuint64_t strides[1] = {(cuuint64_t)cols * 2};
    cuuint32_t box[2] = {(cuuint32_t)bc, (cuuint32_t)br};
    cuuint32_t es[2] = {1, 1};
    fn(tm, CU_TENSOR_MAP_DATA_TYPE_BFLOAT16, 2, const_cast<void*>(p), dims, strides, box, es, CU_TENSOR_MAP_INTERLEAVE_NONE,
       CU_TENSOR_MAP_SWIZZLE_NONE, CU_TENSOR_MAP_L2_PROMOTION_L2_128B, CU_TENSOR_MAP_FLOAT_OOB_FILL_NONE);
}

void make_map3(EncodeFn fn, CUtensorMap* tm, const void* p) {
    cuuint64_t dims[5] = {(cuuint64_t)D_, 64, 2, 4, 4};
    cuuint64_t strides[4] = {(cuuint64_t)D_ * 2, (cuuint64_t)D_ * 128, (cuuint64_t)D_ * 1024, (cuuint64_t)D_ * 256};
    cuuint32_t box[5] = {XW, 9, 2, 4, 4};
    cuuint32_t es[5] = {1, 1, 1, 1, 1};
    fn(tm, CU_TENSOR_MAP_DATA_TYPE_BFLOAT16, 5, const_cast<void*>(p), dims, strides, box, es, CU_TENSOR_MAP_INTERLEAVE_NONE,
       CU_TENSOR_MAP_SWIZZLE_NONE, CU_TENSOR_MAP_L2_PROMOTION_NONE, CU_TENSOR_MAP_FLOAT_OOB_FILL_NONE);
}

void make_map5(EncodeFn fn, CUtensorMap* tm, const void* p, int bc) {
    cuuint64_t dims[5] = {(cuuint64_t)D_, 2, 4, 4, 64};
    cuuint64_t strides[4] = {(cuuint64_t)D_ * 128, (cuuint64_t)D_ * 1024, (cuuint64_t)D_ * 256, (cuuint64_t)D_ * 2};
    cuuint32_t box[5] = {(cuuint32_t)bc, 2, 4, 4, 8};
    cuuint32_t es[5] = {1, 1, 1, 1, 1};
    fn(tm, CU_TENSOR_MAP_DATA_TYPE_BFLOAT16, 5, const_cast<void*>(p), dims, strides, box, es, CU_TENSOR_MAP_INTERLEAVE_NONE,
       CU_TENSOR_MAP_SWIZZLE_NONE, CU_TENSOR_MAP_L2_PROMOTION_NONE, CU_TENSOR_MAP_FLOAT_OOB_FILL_NONE);
}

}

extern "C" void kernel_launch(void* const* d_in, const int* in_sizes, int n_in, void* d_out, int out_size) {
    (void)in_sizes; (void)n_in; (void)out_size;
    void* fp = nullptr;
    cudaDriverEntryPointQueryResult qr;
    cudaGetDriverEntryPoint("cuTensorMapEncodeTiled", &fp, cudaEnableDefault, &qr);
    EncodeFn fn = (EncodeFn)fp;
    CUtensorMap tmG, tmU, tmD, tmO, tmX, tmH;
    make_map3(fn, &tmX, d_in[0]);
    make_map(fn, &tmG, d_in[11], F_, D_, 40, 48);
    make_map(fn, &tmU, d_in[12], F_, D_, 40, 48);
    make_map(fn, &tmD, d_in[13], D_, F_, W2W, 64);
    make_map5(fn, &tmO, d_out, 32);
    make_map5(fn, &tmH, d_out, 8);
    Params p;
    p.x = (const unsigned short*)d_in[0];
    for (int i = 0; i < 6; i++) p.prm6[i] = (const unsigned short*)d_in[1 + i];
    p.logdt = (const unsigned short*)d_in[7]; p.dskip = (const unsigned short*)d_in[8];
    p.wr = (const unsigned short*)d_in[10];
    p.out = (__nv_bfloat16*)d_out;
    p.zero = 0;
    cudaGetSymbolAddress((void**)&p.gs, g_s);
    cudaFuncSetAttribute(fused_kernel, cudaFuncAttributeMaxDynamicSharedMemorySize, SM_TOTAL);
    static int nclusters = -1;
    if (nclusters < 0) {
        cudaLaunchConfig_t cfg = {};
        cudaLaunchAttribute at;
        at.id = cudaLaunchAttributeClusterDimension; at.val.clusterDim.x = CS; at.val.clusterDim.y = 1; at.val.clusterDim.z = 1;
        cfg.gridDim = dim3(NCTA); cfg.blockDim = dim3(NTHR); cfg.dynamicSmemBytes = SM_TOTAL; cfg.attrs = &at; cfg.numAttrs = 1;
        if (cudaOccupancyMaxActiveClusters(&nclusters, fused_kernel, &cfg) != cudaSuccess) { (void)cudaGetLastError(); nclusters = NCL; }
    }
    if (nclusters >= NCL && !FORCE_FALLBACK) {
        fused_kernel<<<NCTA, NTHR, SM_TOTAL>>>(p, tmG, tmU, tmD, tmO, tmX, tmH);
        return;
    }
    fb_ln<<<L_ / 8, 256>>>((const bf16*)d_in[0], nullptr, nullptr);
    fb_taps<<<D_ * 8, 256>>>(p);
    fb_conv<<<L_, D_>>>(p);
    fb_ln<<<L_ / 8, 256>>>(nullptr, (const bf16*)d_in[10], p.out);
    fb_top<<<L_ / 256, 256>>>();
    fb_ffn1<<<dim3(F_ / 256, 8), 256>>>((const bf16*)d_in[11], (const bf16*)d_in[12]);
    fb_ffn2<<<8, D_>>>((const bf16*)d_in[13], p.out);
}
```

```cpp
#include <cuda_runtime.h>
#include <cuda_bf16.h>
#include <cuda_fp16.h>
#include <cuda.h>
#include <stdint.h>

namespace {

constexpr int L_ = 2048, D_ = 576, F_ = 4608;
constexpr int NCL = 15, CS = 8, NCTA = NCL * CS, NTHR = 768;
#define W2W 72
#define XW 48
#define TILE_NS -1
#define XROT 1
#define FORCE_FALLBACK 0
#define ROTK 1
#define LNPOS 1
#define MMPOS 0
#define XSPLIT 3
constexpr int NRED = 2;
constexpr int SPIN_LIMIT = 1 << 22;

constexpr int SM_WG   = 0;
constexpr int SM_WU   = 46080;
constexpr int YP = 3392, YS = 656;
constexpr int UP = 3280, US = 656;
constexpr int SM_XT   = 92160;
constexpr int SM_U    = SM_XT + 8 * YP;
constexpr int SM_FAR  = SM_U + 8 * UP;
constexpr int FAR_SZ  = 12416;
constexpr int F_E5 = 0, F_O5 = 1536, F_E3 = 3088, F_O3 = 4624, F_E7 = 6176, F_E2 = F_E7 + 1024, F_E9 = F_E7 + 2048,
              F_H = 3088, F_O7 = F_E7 + F_H, F_O2 = F_E2 + F_H, F_O9 = F_E9 + F_H;
constexpr int SM_P    = SM_FAR + 5 * FAR_SZ;
constexpr int PN_SZ = 584 * 4, SM_PN = SM_P + 64 * 4;
constexpr int P_GS = 48 * 4, P_H7 = 192 * 4, P_HS = 72 * 4;
constexpr int PF_SZ = (192 + 216) * 4, SM_PF = SM_PN + 5 * PN_SZ + 32;
constexpr int SM_MISC = SM_PF + 5 * PF_SZ;
constexpr int SM_ST   = SM_MISC;
constexpr int SM_RK   = SM_ST + 2048;
constexpr int SM_SEL  = SM_RK + 256;
constexpr int SM_KG   = SM_SEL + 64;
constexpr int SM_SC   = SM_KG + 160;
constexpr int SM_DW   = SM_SC + 32;
constexpr int SM_MB   = SM_DW + 160;
constexpr int SM_TOTAL = SM_MB + 128;
constexpr int SM_ROW  = SM_XT - 20736;
constexpr int SM_XTL  = SM_ROW - 576 * XW;
constexpr int SM_RED2 = SM_WG;
constexpr int SM_HT   = SM_P - 512;
constexpr int SM_KEY  = SM_FAR + 10240 + 128;
constexpr int SM_CAND = SM_KEY + 1024;
constexpr int SM_XS   = SM_U;
constexpr int SM_GU   = SM_XS + 9344;
constexpr int SM_RED  = SM_GU + 5632;
static_assert(F_O9 + 1024 <= FAR_SZ && FAR_SZ % 128 == 0, "far overflow");
static_assert(SM_RED + 10240 <= SM_FAR && SM_HT + 20496 <= SM_MISC, "alias overflow");
static_assert(SM_TOTAL <= 232448, "smem overflow");
static_assert(SM_FAR % 128 == 0 && SM_XT % 128 == 0 && SM_XTL % 128 == 0 && SM_P % 16 == 0 && SM_MISC % 16 == 0 && SM_MB % 8 == 0, "align");

enum { MB_X = 0, MB_W1 = 5, MB_W2 = 6, MB_KEY = 7, MB_GU = 8, MB_Y = 9, MB_OUT = 10, MB_T = 11, MB_R = 12 };

struct __align__(128) Scratch {
    unsigned epoch, zcnt, pad[30];
    uint4  st1[L_ * 2];
    float4 acc[L_];
    uint4  cand[64 * NCL * 6];
    float4 fin[8 * 192 + 24];
};
__device__ Scratch g_s;
#define STAMP(i)

__device__ __forceinline__ uint32_t mapa(uint32_t a, uint32_t r) { uint32_t d; asm("mapa.shared::cluster.u32 %0, %1, %2;" : "=r"(d) : "r"(a), "r"(r)); return d; }
__device__ __forceinline__ void mbar_wait(uint32_t mb) {
    asm volatile("{ .reg .pred p, q; .reg .u32 n; mov.u32 n, 0;\n"
                 "W_%=: mbarrier.try_wait.parity.shared::cta.b64 p, [%0], 0; add.u32 n, n, 1; setp.lt.and.u32 q, n, 65536, !p; @q bra W_%=; }" :: "r"(mb) : "memory");
}
__device__ __forceinline__ void arm(uint32_t mb, uint32_t bytes) { asm volatile("mbarrier.arrive.expect_tx.shared::cta.b64 _, [%0], %1;" :: "r"(mb), "r"(bytes) : "memory"); }
__device__ __forceinline__ void bar_sync(int id, int n) { asm volatile("bar.sync %0, %1;" :: "r"(id), "r"(n) : "memory"); }
__device__ __forceinline__ void bar_arrive(int id, int n) { asm volatile("bar.arrive %0, %1;" :: "r"(id), "r"(n) : "memory"); }
__device__ __forceinline__ uint32_t lds16(uint32_t a) { unsigned short v; asm volatile("ld.shared.u16 %0, [%1];" : "=h"(v) : "r"(a) : "memory"); return v; }
__device__ __forceinline__ uint32_t lds32(uint32_t a) { uint32_t v; asm volatile("ld.shared.u32 %0, [%1];" : "=r"(v) : "r"(a) : "memory"); return v; }
__device__ __forceinline__ uint2 lds64(uint32_t a) { uint2 v; asm volatile("ld.shared.v2.u32 {%0,%1}, [%2];" : "=r"(v.x), "=r"(v.y) : "r"(a) : "memory"); return v; }
__device__ __forceinline__ float ldsf(uint32_t a) { float v; asm volatile("ld.shared.f32 %0, [%1];" : "=f"(v) : "r"(a) : "memory"); return v; }
__device__ __forceinline__ uint4 lds128(uint32_t a) { uint4 v; asm volatile("ld.shared.v4.u32 {%0,%1,%2,%3}, [%4];" : "=r"(v.x), "=r"(v.y), "=r"(v.z), "=r"(v.w) : "r"(a) : "memory"); return v; }
__device__ __forceinline__ float4 lds128f(uint32_t a) { float4 v; asm volatile("ld.shared.v4.f32 {%0,%1,%2,%3}, [%4];" : "=f"(v.x), "=f"(v.y), "=f"(v.z), "=f"(v.w) : "r"(a) : "memory"); return v; }
__device__ __forceinline__ void sts16(uint32_t a, uint32_t v) { asm volatile("{ .reg .b16 l, h; mov.b32 {l, h}, %1; st.shared.b16 [%0], l; }" :: "r"(a), "r"(v) : "memory"); }
__device__ __forceinline__ void sts32(uint32_t a, uint32_t v) { asm volatile("st.shared.u32 [%0], %1;" :: "r"(a), "r"(v) : "memory"); }
__device__ __forceinline__ void sts64(uint32_t a, uint32_t x, uint32_t y) { asm volatile("st.shared.v2.u32 [%0], {%1,%2};" :: "r"(a), "r"(x), "r"(y) : "memory"); }
__device__ __forceinline__ void stsf(uint32_t a, float v) { asm volatile("st.shared.f32 [%0], %1;" :: "r"(a), "f"(v) : "memory"); }
__device__ __forceinline__ void sts128(uint32_t a, uint32_t x, uint32_t y, uint32_t z, uint32_t w) { asm volatile("st.shared.v4.u32 [%0], {%1,%2,%3,%4};" :: "r"(a), "r"(x), "r"(y), "r"(z), "r"(w) : "memory"); }
__device__ __forceinline__ void sts128f(uint32_t a, float x, float y, float z, float w) { asm volatile("st.shared.v4.f32 [%0], {%1,%2,%3,%4};" :: "r"(a), "f"(x), "f"(y), "f"(z), "f"(w) : "memory"); }
__device__ __forceinline__ void ldsm4(uint32_t (&r)[4], uint32_t a) { asm volatile("ldmatrix.sync.aligned.m8n8.x4.shared.b16 {%0,%1,%2,%3}, [%4];" : "=r"(r[0]), "=r"(r[1]), "=r"(r[2]), "=r"(r[3]) : "r"(a) : "memory"); }
__device__ __forceinline__ void ldsm4t(uint32_t (&r)[4], uint32_t a) { asm volatile("ldmatrix.sync.aligned.m8n8.x4.trans.shared.b16 {%0,%1,%2,%3}, [%4];" : "=r"(r[0]), "=r"(r[1]), "=r"(r[2]), "=r"(r[3]) : "r"(a) : "memory"); }
__device__ __forceinline__ void ldsm2t(uint32_t& r0, uint32_t& r1, uint32_t a) { asm volatile("ldmatrix.sync.aligned.m8n8.x2.trans.shared.b16 {%0,%1}, [%2];" : "=r"(r0), "=r"(r1) : "r"(a) : "memory"); }
__device__ __forceinline__ void stsm4t(uint32_t a, uint32_t r0, uint32_t r1, uint32_t r2, uint32_t r3) { asm volatile("stmatrix.sync.aligned.m8n8.x4.trans.shared.b16 [%0], {%1,%2,%3,%4};" :: "r"(a), "r"(r0), "r"(r1), "r"(r2), "r"(r3) : "memory"); }
__device__ __forceinline__ void stsm4(uint32_t a, uint32_t r0, uint32_t r1, uint32_t r2, uint32_t r3) { asm volatile("stmatrix.sync.aligned.m8n8.x4.shared.b16 [%0], {%1,%2,%3,%4};" :: "r"(a), "r"(r0), "r"(r1), "r"(r2), "r"(r3) : "memory"); }
__device__ __forceinline__ void stsm2t(uint32_t a, uint32_t r0, uint32_t r1) { asm volatile("stmatrix.sync.aligned.m8n8.x2.trans.shared.b16 [%0], {%1,%2};" :: "r"(a), "r"(r0), "r"(r1) : "memory"); }
__device__ __forceinline__ uint4 ldg128(const void* p) { uint4 v; asm volatile("ld.global.nc.v4.u32 {%0,%1,%2,%3}, [%4];" : "=r"(v.x), "=r"(v.y), "=r"(v.z), "=r"(v.w) : "l"(p)); return v; }
__device__ __forceinline__ uint32_t ldg16(const void* p) { unsigned short v; asm volatile("ld.global.nc.u16 %0, [%1];" : "=h"(v) : "l"(p)); return v; }
__device__ __forceinline__ uint32_t opaque(uint32_t v) { uint32_t r; asm volatile("mov.b32 %0, %1;" : "=r"(r) : "r"(v)); return r; }
__device__ __forceinline__ void mma_f16(float (&d)[4], const uint32_t (&a)[4], uint32_t b0, uint32_t b1) {
    asm volatile("mma.sync.aligned.m16n8k16.row.col.f32.f16.f16.f32 {%0,%1,%2,%3}, {%4,%5,%6,%7}, {%8,%9}, {%0,%1,%2,%3};"
        : "+f"(d[0]), "+f"(d[1]), "+f"(d[2]), "+f"(d[3]) : "r"(a[0]), "r"(a[1]), "r"(a[2]), "r"(a[3]), "r"(b0), "r"(b1));
}
__device__ __forceinline__ void mma_bf16(float (&d)[4], uint32_t a0, uint32_t a1, uint32_t a2, uint32_t a3, uint32_t b0, uint32_t b1) {
    asm volatile("mma.sync.aligned.m16n8k16.row.col.f32.bf16.bf16.f32 {%0,%1,%2,%3}, {%4,%5,%6,%7}, {%8,%9}, {%0,%1,%2,%3};"
        : "+f"(d[0]), "+f"(d[1]), "+f"(d[2]), "+f"(d[3]) : "r"(a0), "r"(a1), "r"(a2), "r"(a3), "r"(b0), "r"(b1));
}
__device__ __forceinline__ void mma_bf16_k8(float (&d)[4], uint32_t a0, uint32_t a1, uint32_t b0) {
    asm volatile("mma.sync.aligned.m16n8k8.row.col.f32.bf16.bf16.f32 {%0,%1,%2,%3}, {%4,%5}, {%6}, {%0,%1,%2,%3};"
        : "+f"(d[0]), "+f"(d[1]), "+f"(d[2]), "+f"(d[3]) : "r"(a0), "r"(a1), "r"(b0));
}
__device__ __forceinline__ uint32_t pack_f16(float lo, float hi) { uint32_t r; asm("cvt.rn.f16x2.f32 %0, %1, %2;" : "=r"(r) : "f"(hi), "f"(lo)); return r; }
__device__ __forceinline__ uint32_t pack_bf16(float lo, float hi) { uint32_t r; asm("cvt.rn.bf16x2.f32 %0, %1, %2;" : "=r"(r) : "f"(hi), "f"(lo)); return r; }
__device__ __forceinline__ float bf_lo(uint32_t v) { return __uint_as_float(v << 16); }
__device__ __forceinline__ float bf_hi(uint32_t v) { return __uint_as_float(v & 0xFFFF0000u); }
__device__ __forceinline__ float bfr(float x) { return __uint_as_float(pack_bf16(0.f, x)); }
__device__ __forceinline__ uint32_t badd2(uint32_t a, uint32_t b) { uint32_t r; asm("add.rn.bf16x2 %0, %1, %2;" : "=r"(r) : "r"(a), "r"(b)); return r; }
__device__ __forceinline__ uint32_t bmul2(uint32_t a, uint32_t b) { uint32_t r; asm("mul.rn.bf16x2 %0, %1, %2;" : "=r"(r) : "r"(a), "r"(b)); return r; }
__device__ __forceinline__ uint32_t hadd2(uint32_t a, uint32_t b) { uint32_t r; asm("add.rn.f16x2 %0, %1, %2;" : "=r"(r) : "r"(a), "r"(b)); return r; }
__device__ __forceinline__ uint32_t hmul2(uint32_t a, uint32_t b) { uint32_t r; asm("mul.rn.f16x2 %0, %1, %2;" : "=r"(r) : "r"(a), "r"(b)); return r; }
__device__ __forceinline__ uint32_t hfma2(uint32_t a, uint32_t b, uint32_t c) { uint32_t r; asm("fma.rn.f16x2 %0, %1, %2, %3;" : "=r"(r) : "r"(a), "r"(b), "r"(c)); return r; }
__device__ __forceinline__ uint32_t hneg2(uint32_t a) { uint32_t r; asm("neg.f16x2 %0, %1;" : "=r"(r) : "r"(a)); return r; }
__device__ __forceinline__ float rcpf(float x) { float r; asm("rcp.approx.ftz.f32 %0, %1;" : "=f"(r) : "f"(x)); return r; }
__device__ __forceinline__ float sqrta(float x) { float r; asm("sqrt.approx.ftz.f32 %0, %1;" : "=f"(r) : "f"(x)); return r; }
__device__ __forceinline__ float ex2f(float x) { float r; asm("ex2.approx.ftz.f32 %0, %1;" : "=f"(r) : "f"(x)); return r; }
__device__ __forceinline__ void st_async4(uint32_t a, uint32_t x, uint32_t y, uint32_t z, uint32_t w, uint32_t mb) {
    asm volatile("st.async.shared::cluster.mbarrier::complete_tx::bytes.v4.u32 [%0], {%1,%2,%3,%4}, [%5];" :: "r"(a), "r"(x), "r"(y), "r"(z), "r"(w), "r"(mb) : "memory"); }
__device__ __forceinline__ void st_async1(uint32_t a, uint32_t x, uint32_t mb) {
    asm volatile("st.async.shared::cluster.mbarrier::complete_tx::bytes.u32 [%0], %1, [%2];" :: "r"(a), "r"(x), "r"(mb) : "memory"); }
__device__ __forceinline__ unsigned ld_rlx(const void* p) { unsigned v; asm volatile("ld.relaxed.gpu.global.u32 %0, [%1];" : "=r"(v) : "l"(p) : "memory"); return v; }
__device__ __forceinline__ unsigned ld_acq(const void* p) { unsigned v; asm volatile("ld.acquire.gpu.global.u32 %0, [%1];" : "=r"(v) : "l"(p) : "memory"); return v; }
__device__ __forceinline__ uint2 ld_rlx64(const void* p) { unsigned long long v; asm volatile("ld.relaxed.gpu.global.u64 %0, [%1];" : "=l"(v) : "l"(p) : "memory"); return make_uint2((unsigned)v, (unsigned)(v >> 32)); }
__device__ __forceinline__ void st_rlx128(void* p, uint32_t x, uint32_t y, uint32_t z, uint32_t w) {
    asm volatile("st.relaxed.gpu.global.v2.u64 [%0], {%1,%2};" :: "l"(p), "l"((unsigned long long)x | ((unsigned long long)y << 32)), "l"((unsigned long long)z | ((unsigned long long)w << 32)) : "memory"); }
__device__ __forceinline__ uint4 ld_rlx128(const void* p) { unsigned long long a, b; asm volatile("ld.relaxed.gpu.global.v2.u64 {%0,%1}, [%2];" : "=l"(a), "=l"(b) : "l"(p) : "memory"); return make_uint4((unsigned)a, (unsigned)(a >> 32), (unsigned)b, (unsigned)(b >> 32)); }
__device__ __forceinline__ void tma2d(uint32_t dst, const CUtensorMap* tm, int x, int y, uint32_t mb) {
    asm volatile("cp.async.bulk.tensor.2d.shared::cluster.global.mbarrier::complete_tx::bytes [%0], [%1, {%3, %4}], [%2];"
                 :: "r"(dst), "l"(tm), "r"(mb), "r"(x), "r"(y) : "memory");
}
__device__ __forceinline__ void cmul(float& xr, float& xi, float ar, float ai, float br, float bi) {
    const float r = fmaf(ar, br, -ai * bi), i = fmaf(ar, bi, ai * br); xr = r; xi = i;
}
__device__ __forceinline__ void csq(float& xr, float& xi, float ar, float ai) {
    const float r = fmaf(ar, ar, -ai * ai), i = (ar + ar) * ai; xr = r; xi = i;
}
__device__ __forceinline__ void cexp_s(float& zr, float& zi, float e2, float turns) {
    const float mag = ex2f(e2), r = (turns - rintf(turns)) * 6.283185307179586f;
    zr = mag * __cosf(r); zi = mag * __sinf(r);
}
__device__ __forceinline__ uint32_t ln_stats(float s1, float s2) {
    const float m = s1 * (1.f / D_);
    const float var = fmaxf(fmaf(s2, 1.f / D_, -m * m), 0.f);
    return pack_bf16(m, sqrta(bfr(bfr(var) + 1e-5f)));
}
__device__ __forceinline__ uint32_t rsplit(float rs) { const float h = bfr(rs); return pack_bf16(h, rs - h); }
__device__ __forceinline__ uint32_t norm2(uint32_t v, uint32_t mx, uint32_t hl) {
    uint32_t r;
    asm("{ .reg .b16 m, h, l, x; .reg .b32 m2, h2, l2, d, t; mov.b32 {m, x}, %2; mov.b32 {h, l}, %3; mov.b32 m2, {m, m}; mov.b32 h2, {h, h}; mov.b32 l2, {l, l};\n"
        "sub.rn.bf16x2 d, %1, m2; mul.rn.bf16x2 t, d, l2; fma.rn.bf16x2 %0, d, h2, t; }" : "=r"(r) : "r"(v), "r"(mx), "r"(hl));
    return r;
}
template <int N, int S>
__device__ __forceinline__ uint32_t rank4(uint32_t a, uint32_t key) {
    uint32_t r0 = 0, r1 = 0, r2 = 0, r3 = 0;
#pragma unroll
    for (int i = 0; i < N; i++) {
        const uint4 o = lds128(a + i * S);
        r0 += (key - o.x) >> 31; r1 += (key - o.y) >> 31; r2 += (key - o.z) >> 31; r3 += (key - o.w) >> 31;
    }
    return (r0 + r1) + (r2 + r3);
}
typedef uint32_t H2C;
__device__ __forceinline__ H2C splat(float r, float i) { return pack_f16(r, i); }
__device__ __forceinline__ void hcmul(uint32_t& xr, uint32_t& xi, uint32_t R, uint32_t I, H2C m) {
    asm("{ .reg .b16 a, b; .reg .b32 a2, b2, t; mov.b32 {a, b}, %4; mov.b32 a2, {a, a}; mov.b32 b2, {b, b};\n"
        "mul.rn.f16x2 t, %3, b2; neg.f16x2 t, t; fma.rn.f16x2 %0, %2, a2, t; mul.rn.f16x2 t, %3, a2; fma.rn.f16x2 %1, %2, b2, t; }"
        : "=&r"(xr), "=r"(xi) : "r"(R), "r"(I), "r"(m));
}
__device__ __forceinline__ void expand4(uint32_t are, uint32_t aim, uint32_t R0, uint32_t R1, uint32_t I0, uint32_t I1, H2C m4) {
    uint32_t R2, I2, R3, I3;
    hcmul(R2, I2, R0, I0, m4); hcmul(R3, I3, R1, I1, m4);
    sts128(are, R0, R1, R2, R3);
    sts128(aim, I0, I1, I2, I3);
}
__device__ __forceinline__ void expand8(uint32_t are, uint32_t aim, float sr, float si, float m1r, float m1i, float m2r, float m2i, H2C m4) {
    float r1, i1, r2, i2, r3, i3;
    cmul(r1, i1, sr, si, m1r, m1i); cmul(r2, i2, sr, si, m2r, m2i); cmul(r3, i3, r1, i1, m2r, m2i);
    expand4(are, aim, pack_f16(sr, r1), pack_f16(r2, r3), pack_f16(si, i1), pack_f16(i2, i3), m4);
}
__device__ __forceinline__ void put16(uint32_t a, uint32_t v) { sts16(a, v); sts16(a + 6, v); }

struct Params {
    const unsigned short *logdt, *dskip, *prm6[6], *x, *wr;
    __nv_bfloat16* out;
    Scratch* gs;
    unsigned zero;
};
__device__ __forceinline__ uint32_t tslot(uint32_t t) { return (t & 7) * 32 + ((t >> 4) & 24) + ((t >> 8) & 6) + ((t >> 6) & 1); }
#define CP(x) ((x) | zero)
#define PIN(x) asm volatile("or.b32 %0, %0, %1;" : "+r"(x) : "r"(zero))
__device__ __forceinline__ void wgmma32(float (&d)[4][4], const uint32_t (&a)[4], uint32_t dlo) {
    asm volatile("{ .reg .b64 ds; mov.b64 ds, {%20, %21};\n"
                 "wgmma.mma_async.sync.aligned.m64n32k16.f32.f16.f16 {%0,%1,%2,%3,%4,%5,%6,%7,%8,%9,%10,%11,%12,%13,%14,%15}, {%16,%17,%18,%19}, ds, 1, 1, 1, 0; }"
        : "+f"(d[0][0]), "+f"(d[0][1]), "+f"(d[0][2]), "+f"(d[0][3]), "+f"(d[1][0]), "+f"(d[1][1]), "+f"(d[1][2]), "+f"(d[1][3]),
          "+f"(d[2][0]), "+f"(d[2][1]), "+f"(d[2][2]), "+f"(d[2][3]), "+f"(d[3][0]), "+f"(d[3][1]), "+f"(d[3][2]), "+f"(d[3][3])
        : "r"(a[0]), "r"(a[1]), "r"(a[2]), "r"(a[3]), "r"(dlo), "n"(128 >> 4));
}

__global__ void __cluster_dims__(CS, 1, 1) __launch_bounds__(NTHR, 1)
fused_kernel(const __grid_constant__ Params prm, const __grid_constant__ CUtensorMap tmG, const __grid_constant__ CUtensorMap tmU,
             const __grid_constant__ CUtensorMap tmD, const __grid_constant__ CUtensorMap tmO, const __grid_constant__ CUtensorMap tmX, const __grid_constant__ CUtensorMap tmH)
{
    extern __shared__ __align__(1024) unsigned char smem[];
    const int tid = threadIdx.x, lane = tid & 31, warp = __shfl_sync(~0u, tid >> 5, 0);
    const int c = blockIdx.x >> 3, q = blockIdx.x & 7;
    const int nslot = (c < NCL - 1) ? 5 : 2;
    const int d0 = 40 * c;
    const uint32_t sb = opaque((uint32_t)__cvta_generic_to_shared(smem));
    const uint32_t mb = sb + SM_MB;
    Scratch& g_s = *prm.gs;
    const unsigned& zero = prm.zero;
    STAMP(0);

    if (warp >= 20) {
        unsigned epoch = 0;
        if (warp == 20) {
            if (lane == 0) {
#pragma unroll
                for (int i = 0; i < 13; i++)
                    asm volatile("mbarrier.init.shared::cta.b64 [%0], %1;" :: "r"(mb + i * 8), "r"((i == MB_R || i < 5) ? 2 : i == MB_Y ? 1 + 4 * nslot : 1) : "memory");
                asm volatile("fence.mbarrier_init.release.cluster;" ::: "memory");
                arm(mb + MB_W1 * 8, 92160); arm(mb + MB_W2 * 8, nslot * (128 * W2W)); arm(mb + MB_KEY * 8, 256); arm(mb + MB_GU * 8, nslot * 1024); arm(mb + MB_T * 8, 576 * XW);
                const int bytes = max(min(18, L_ - 18 * (int)blockIdx.x), 1) * (D_ * 2);
                arm(mb + MB_R * 8, bytes);
            }
            __syncwarp();
        } else if (warp == 22) {
            epoch = ld_rlx(&g_s.epoch);
            if (lane < 18 ? 18 * c + lane < 256 : lane < 31) (lane < 18 ? &g_s.acc[256 * q + 18 * c] : &g_s.fin[13 * (int)blockIdx.x - 18])[lane] = make_float4(0.f, 0.f, 0.f, 0.f);
        } else if (warp == 23 && lane == 0) asm volatile("prefetch.tensormap [%0];" :: "l"(&tmX) : "memory");
        asm volatile("barrier.cluster.arrive.relaxed.aligned;" ::: "memory");
        bar_sync(12, NTHR);
        if (warp == 22) {
            if (lane == 0) { sts32(sb + SM_SC + 28, epoch); asm volatile("mbarrier.arrive.shared::cta.b64 _, [%0];" :: "r"(mb + MB_R * 8) : "memory"); }
            epoch++;
            asm volatile("fence.acq_rel.gpu;" ::: "memory");
            __syncwarp();
            if (lane == 0) asm volatile("red.relaxed.gpu.global.add.u32 [%0], 1;" :: "l"(&g_s.zcnt) : "memory");
            STAMP(1);
            uint4 wv = make_uint4(0, 0, 0, 0), wv2 = ldg128((const uint4*)prm.wr + lane), wv3 = ldg128((const uint4*)prm.wr + 32 + lane);
            if (lane < 8) wv = ldg128((const uint4*)prm.wr + 64 + lane);
            if (lane < 5) {
                uint4 v = make_uint4(0, 0, 0, 0);
                if (lane < nslot) v = ldg128((const uint4*)(prm.wr + d0) + lane);
                sts128(sb + SM_DW + lane * 16, v.x, v.y, v.z, v.w);
            }
            __syncwarp();
            if (lane < 5) asm volatile("mbarrier.arrive.shared::cta.b64 _, [%0];" :: "r"(mb + (MB_X + lane) * 8) : "memory");
            mbar_wait(mb + (MB_X + 1) * 8);
            const uint32_t old = (epoch & 1) ? 0u : 0x40004000u;
#pragma unroll
            for (int t = 0; t < 2; t++)
                if ((lane & 7) < 6) g_s.cand[((q * 8 + 4 * t + (lane >> 3)) * NCL + c) * 6 + (lane & 7)] = make_uint4(old, old, old, old);
            float a[4] = {0.f, 0.f, 0.f, 0.f};
            const uint32_t one = 0x3F803F80u;
            mma_bf16(a, one, one, one, one, wv.x, wv.y);  mma_bf16(a, one, one, one, one, wv.z, wv.w);
            mma_bf16(a, one, one, one, one, wv2.x, wv2.y); mma_bf16(a, one, one, one, one, wv2.z, wv2.w);
            mma_bf16(a, one, one, one, one, wv3.x, wv3.y); mma_bf16(a, one, one, one, one, wv3.z, wv3.w);
            float s = a[0] + a[1];
            s += __shfl_xor_sync(~0u, s, 1); s += __shfl_xor_sync(~0u, s, 2);
            stsf(sb + SM_SC + 24, s);
            __syncwarp();
            if (lane == 0) {
                int n = 0;
                while ((int)(ld_acq(&g_s.zcnt) - epoch * NCTA) < 0 && ++n < SPIN_LIMIT) __nanosleep(200);
                arm(mb + MB_Y * 8, 8 * 512 * nslot);
                if (blockIdx.x == 0) g_s.epoch = epoch;
            }
            STAMP(2);
            return;
        }
        if (warp == 21) {
            if (lane == 0) { asm volatile("prefetch.tensormap [%0];" :: "l"(&tmG) : "memory"); asm volatile("prefetch.tensormap [%0];" :: "l"(&tmU) : "memory"); asm volatile("prefetch.tensormap [%0];" :: "l"(&tmD) : "memory"); }
            __syncwarp();
            bar_sync(13, 736);
            asm volatile("fence.proxy.async.shared::cta;" ::: "memory");
#pragma unroll 1
            for (int i = 0; i < 24; i++) {
                if (lane == 0) tma2d(sb + SM_WG + i * 3840, i < 12 ? &tmG : &tmU, 320 * c + 8 * nslot * q, 48 * (i < 12 ? i : i - 12), mb + MB_W1 * 8);
            }
            STAMP(1);
            return;
        }
        if (warp == 20) {
            if (lane == 0) {
                asm volatile("cp.async.bulk.shared::cluster.global.mbarrier::complete_tx::bytes [%0], [%1], %2, [%3];"
                             :: "r"(sb + SM_ROW), "l"(prm.x + min(18 * (int)blockIdx.x, L_ - 1) * D_), "r"(max(min(18, L_ - 18 * (int)blockIdx.x), 1) * (D_ * 2)), "r"(mb + MB_R * 8) : "memory");
            }
            __syncwarp();
            if (TILE_NS < 0) mbar_wait(mb + MB_R * 8); else if (TILE_NS) __nanosleep(TILE_NS);
            if (lane == 0) {
                asm volatile("cp.async.bulk.tensor.5d.shared::cluster.global.mbarrier::complete_tx::bytes [%0], [%1, {%3, %4, %5, %5, %5}], [%2];"
                             :: "r"(sb + SM_XTL), "l"(&tmX), "r"(mb + MB_T * 8), "r"(XW == 40 ? d0 : d0 & ~15), "r"(8 * q), "r"(0) : "memory");
            }
            STAMP(6);
        }
        asm volatile("barrier.cluster.wait.aligned;" ::: "memory");
        bar_sync(13, 736);
        asm volatile("fence.proxy.async.shared::cta;" ::: "memory");
        {
            const int sl = nslot - 1 - (lane >> 2), pe = XROT ? ((lane & 3) * 2 + (warp & 1) + q + 1) & 7 : (((lane & 3) ^ ((lane & 4) ? 3 : 0)) * 2 + (warp & 1));
            if (sl >= 0) {
                if (pe == q) arm(mb + (MB_X + sl) * 8, 7 * 512);
                else {
                    const uint32_t rb_ = mapa(sb, pe);
                    asm volatile("cp.async.bulk.shared::cluster.shared::cta.mbarrier::complete_tx::bytes [%0], [%1], 512, [%2];"
                                 :: "r"(rb_ + SM_U + 128 + q * UP + sl * US), "r"(sb + SM_XT + 128 + (q & 3) * 16 + pe * YP + sl * YS), "r"(rb_ + SM_MB + (MB_X + sl) * 8) : "memory");
                }
            }
        }
        STAMP(1);
        if (warp == 20 && lane == 0) { asm volatile("prefetch.tensormap [%0];" :: "l"(&tmO) : "memory"); asm volatile("prefetch.tensormap [%0];" :: "l"(&tmH) : "memory"); }
        if (warp == 23) {
#pragma unroll 1
            for (int kk = nslot - 1; kk >= 0; kk--) {
                __syncwarp();
                bar_sync(6 + kk, 160);
                if (lane == 0) { asm volatile("fence.proxy.async.shared::cta;" ::: "memory"); tma2d(sb + SM_FAR + kk * FAR_SZ, &tmD, W2W == 72 ? 72 * q : (72 * q) & ~15, 320 * c + 64 * kk, mb + MB_W2 * 8); }
            }
            return;
        }
        __syncwarp();
        bar_sync(14, 672);
        if (lane == 0) {
            asm volatile("fence.proxy.async.shared::cta;" ::: "memory");
            asm volatile("cp.async.bulk.tensor.5d.global.shared::cta.bulk_group [%0, {%2, %4, %4, %4, %3}], [%1];" :: "l"(&tmH), "r"(sb + SM_XT + 16384), "r"(d0 + ((c & 1) ? 0 : 32)), "r"(8 * q), "r"(0) : "memory");
            asm volatile("cp.async.bulk.tensor.5d.global.shared::cta.bulk_group [%0, {%2, %4, %4, %4, %3}], [%1];" :: "l"(&tmO), "r"(sb + SM_XT), "r"(d0 + (c & 1) * 8), "r"(8 * q), "r"(0) : "memory");
            asm volatile("cp.async.bulk.commit_group;" ::: "memory");
            asm volatile("cp.async.bulk.wait_group 0;" ::: "memory");
            asm volatile("fence.proxy.async.global;" ::: "memory");
            asm volatile("mbarrier.arrive.shared::cta.b64 _, [%0];" :: "r"(mb + MB_OUT * 8) : "memory");
        }
        STAMP(2);
        return;
    }

    const int g = lane >> 2, cq = lane & 3;
    const int k = warp >> 2, wq = warp & 3;
    const int trow = 18 * blockIdx.x + warp;
    const bool rowact = warp < 18 && trow < L_;
    const int dch = min(d0 + 8 * k + q, D_ - 1);
    uint32_t pv[6];
#pragma unroll
    for (int i = 0; i < 6; i++) pv[i] = ldg16(prm.prm6[i] + (uint32_t)(dch * 128 + wq * 32 + lane));
    const uint32_t pLdt = ldg16(prm.logdt + dch), pD = ldg16(prm.dskip + dch);
    const int tn = 16 * (warp & 15) + g;
    uint32_t xa[5], xb[5];
    asm volatile("barrier.cluster.arrive.relaxed.aligned;" ::: "memory");
    uint4* const st1p = &g_s.st1[(((trow >> 3) & 7) * 256 + ((trow >> 6) & 31) * 8 + (trow & 7)) * 2 + (lane >> 2)];
    const bool pub = rowact && (lane & 0x1B) == 0;
    if (pub) st_rlx128(st1p, 0, 0, 0, 0);
    {
        const uint32_t za = sb + SM_P + tid * 16;
        sts128(za, 0, 0, 0, 0);
        if (tid < (SM_MISC - SM_P) / 16 - 640) sts128(za + 10240, 0, 0, 0, 0);
        sts128(sb + ((wq & 2) ? SM_U : SM_XT + (q & 3) * 16) + ((tid >> 3) & 7) * ((wq & 2) ? UP : YP) + k * YS + (lane & 7) * 16, 0, 0, 0, 0);
    }
    bar_sync(12, NTHR);
    const uint32_t dep = lds32(sb + SM_P);
#define PV(x) __uint_as_float(__byte_perm(dep, x, 0x5410))
    STAMP(1);
    const uint32_t fb = sb + SM_FAR + k * FAR_SZ;
    const uint32_t pn = sb + SM_PN + k * PN_SZ, pf = sb + SM_PF + k * PF_SZ;
    unsigned epoch;
    {
        const uint32_t kb = fb + wq * 3072;
        const uint32_t kl = kb + lane * 16;
        uint32_t Af[4][4];
        float sr, si, z1r, z1i, z2r, z2i, z4r, z4i, hr, hi_;
        {
            const float dt = bfr(ex2f(PV(pLdt) * 1.4426950408889634f));
            const float e2 = dt * PV(pv[0]) * 1.4426950408889634f, an = dt * PV(pv[1]);
            cmul(sr, si, PV(pv[4]), PV(pv[5]), dt * PV(pv[2]), dt * PV(pv[3]));
            const unsigned E = min(max(__reduce_max_sync(~0u, __float_as_uint(fmaxf(fmaxf(fabsf(sr), fabsf(si)), fabsf(PV(pD)) * (1.f / 8192.f)))) >> 23, 1u), 253u);
            const float sc = __uint_as_float((254u - E) << 23);
            sr *= sc; si *= -sc;
            sts64(sb + SM_KG + warp * 8, E, __reduce_add_sync(~0u, __float2int_rn(sr * 16777216.f)));
            float ar, ai, br, bi, cr, ci, dr, di;
            { const float m = ex2f(e2 * 8.f); ar = m * __cosf(an * 8.f); ai = m * __sinf(an * 8.f); }
            csq(br, bi, ar, ai); csq(cr, ci, br, bi); csq(dr, di, cr, ci);
            const H2C m4 = splat(cr, ci);
            {
                float r3, i3;
                cmul(r3, i3, ar, ai, br, bi);
                expand4(kl, kl + 1024, pack_f16(1.f, ar), pack_f16(br, r3), pack_f16(0.f, ai), pack_f16(bi, i3), m4);
            }
            expand8(kl + 512, kl + 1536, dr, di, ar, ai, br, bi, m4);
            { const float m = ex2f(e2); z1r = m * __cosf(an); z1i = -m * __sinf(an); }
            cexp_s(hr, hi_, e2 * 128.f, an * (-128.f * 0.15915494309189535f));
            csq(z2r, z2i, z1r, z1i); csq(z4r, z4i, z2r, z2i);
        }
        __syncwarp();
#pragma unroll
        for (int ks = 0; ks < 4; ks++) ldsm4t(Af[ks], kb + (lane >> 3) * 512 + (lane & 7) * 16 + ks * 128);
        STAMP(2);
        const uint32_t la = kb + ((lane >> 3) & 1) * 512 + (lane >> 4) * 128 + (lane & 7) * 16;
        uint32_t kp[5][2], b0[4], b1[4], b2[4], b3[4];
        auto mm2 = [&](int t) {
            float a0[4] = {0.f, 0.f, 0.f, 0.f}, a1[4] = {0.f, 0.f, 0.f, 0.f};
            mma_f16(a0, Af[0], b0[0], b0[1]); mma_f16(a1, Af[0], b2[0], b2[1]); mma_f16(a0, Af[1], b0[2], b0[3]); mma_f16(a1, Af[1], b2[2], b2[3]);
            mma_f16(a0, Af[2], b1[0], b1[1]); mma_f16(a1, Af[2], b3[0], b3[1]); mma_f16(a0, Af[3], b1[2], b1[3]); mma_f16(a1, Af[3], b3[2], b3[3]);
            kp[t][0] = pack_f16(a0[1], a0[0]); kp[t][1] = pack_f16(a0[3], a0[2]); kp[t + 1][0] = pack_f16(a1[1], a1[0]); kp[t + 1][1] = pack_f16(a1[3], a1[2]);
        };
        auto ln1 = [&]() {
        mbar_wait(mb + MB_R * 8);
        epoch = lds32(sb + SM_SC + 28) + 1;
        {
            const uint32_t ra = sb + SM_ROW + warp * (D_ * 2);
            const uint4 r0 = lds128(ra + lane * 16), r1 = lds128(ra + 512 + lane * 16);
            const uint32_t rx[9] = {r0.x, r0.y, r0.z, r0.w, r1.x, r1.y, r1.z, r1.w, lds32(ra + 1024 + lane * 4)};
            float a0 = bf_lo(rx[0]), a1 = bf_hi(rx[0]), c0 = a0 * a0, c1 = a1 * a1;
#pragma unroll
            for (int i = 1; i < 9; i++) { const float l = bf_lo(rx[i]), h = bf_hi(rx[i]); a0 += l; a1 += h; c0 = fmaf(l, l, c0); c1 = fmaf(h, h, c1); }
            a0 += a1; c0 += c1;
            float s1 = ((lane & 1) ? c0 : a0) + __shfl_xor_sync(~0u, (lane & 1) ? a0 : c0, 1);
#pragma unroll
            for (int o = 2; o < 32; o <<= 1) s1 += __shfl_xor_sync(~0u, s1, o);
            const float s2 = __shfl_xor_sync(~0u, s1, 1);
            const uint32_t ms = ln_stats(s1, s2);
            const uint32_t p0 = __byte_perm(ms, epoch | 0x8000u, 0x5410), p1 = rsplit(rcpf(bf_hi(ms)));
            if (pub) st_rlx128(st1p, p0, p1, p0, p1);
        }
        mbar_wait(mb + MB_R * 8);
        STAMP(1);
        };
        const uint4* sp = &g_s.st1[(256 * q + tn) * 2];
        uint2 sa, sc;
        auto poll = [&]() { sa = ld_rlx64(sp); sc = ld_rlx64(sp + 16); };
        auto norm = [&]() {
        STAMP(3);
        if (warp < 16) {
            uint32_t va[5], vc[5];
            poll();
            mbar_wait(mb + MB_T * 8);
            {
                const uint32_t xt = sb + SM_XTL + (XW == 40 ? 0 : (c & 1) * 16) + (72 * wq + 18 * k + g) * (2 * XW);
                uint4 a4 = lds128(xt + cq * 16), b4 = lds128(xt + cq * 16 + 18 * XW);
                va[0] = a4.x; va[1] = a4.y; va[2] = a4.z; va[3] = a4.w; va[4] = lds32(xt + 64 + cq * 4);
                vc[0] = b4.x; vc[1] = b4.y; vc[2] = b4.z; vc[3] = b4.w; vc[4] = lds32(xt + (64 + 18 * XW) + cq * 4);
            }
            const int d4 = 2 * (lane >> 3) + (lane & 1), d1_ = lane & 7;
            const uint32_t own = SM_U + 128 + q * (UP - YP), oth = SM_XT + 128 + (q & 3) * 16;
            uint32_t a4 = sb + warp * 32 + d4 * YP + (d4 == q ? own : oth) + ((lane & 7) >> 1) * YS;
            uint32_t a1 = sb + warp * 32 + d1_ * YP + (d1_ == q ? own : oth) + 4 * YS + (lane & 8) * 2;
            PIN(a4); PIN(a1);
            uint32_t tag = __byte_perm(epoch | 0x8000u, 0, 0x1010);
            PIN(tag);
            mbar_wait(mb + MB_T * 8);
            int n = 0;
            while (__byte_perm(sa.x, sc.x, 0x7632) != tag && ++n < SPIN_LIMIT) poll();
            STAMP(4);
#pragma unroll
            for (int i = 0; i < 5; i++) {
                va[i] = norm2(va[i], sa.x, sa.y); va[i] = pack_f16(bf_lo(va[i]), bf_hi(va[i]));
                vc[i] = norm2(vc[i], sc.x, sc.y); vc[i] = pack_f16(bf_lo(vc[i]), bf_hi(vc[i]));
            }
            stsm4t(a4, va[0], va[1], va[2], va[3]); stsm4t(a4 + 16, vc[0], vc[1], vc[2], vc[3]); stsm2t(a1, va[4], vc[4]);
            {
            const uint32_t xh = sb + SM_XTL + (XW == 40 ? 0 : (c & 1) * 16) + (9 * g + 144 * (warp & 1) + (warp >> 1)) * (2 * XW);
            const uint4 c4 = lds128(xh + cq * 16), d4_ = lds128(xh + cq * 16 + 144 * XW);
            xa[0] = c4.x; xa[1] = c4.y; xa[2] = c4.z; xa[3] = c4.w; xa[4] = lds32(xh + 64 + cq * 4);
            xb[0] = d4_.x; xb[1] = d4_.y; xb[2] = d4_.z; xb[3] = d4_.w; xb[4] = lds32(xh + (64 + 144 * XW) + cq * 4);
            }
        }
        STAMP(5);
        bar_sync(13, 736);
        Af[0][0] |= lds32(sb + SM_P);
        };
        if (LNPOS == 0) ln1();
        cmul(sr, si, sr, si, z1r, z1i);
        {
            const H2C h4 = splat(z4r, z4i);
            expand8(kl, kl + 512, sr, si, z1r, z1i, z2r, z2i, h4);
            cmul(sr, si, sr, si, hr, hi_);
            expand8(kl + 1024, kl + 1536, sr, si, z1r, z1i, z2r, z2i, h4);
        }
        __syncwarp();
        ldsm4t(b0, la); ldsm4t(b1, la + 256); ldsm4t(b2, la + 1024); ldsm4t(b3, la + 1280);
        cmul(z1r, z1i, z1r, z1i, hr, hi_);
        cmul(sr, si, sr, si, z1r, z1i);
        if (LNPOS == 1) ln1();
        expand8(kl, kl + 512, sr, si, z2r, z2i, z4r, z4i, splat(hr, hi_));
        if (LNPOS == 2) ln1();
        csq(z1r, z1i, z1r, z1i);
        cmul(sr, si, sr, si, z1r, z1i);
        csq(z2r, z2i, hr, hi_);
        expand8(kl + 1024, kl + 1536, sr, si, z4r, z4i, hr, hi_, splat(z2r, z2i));
        if (LNPOS == 3) ln1();
        csq(z1r, z1i, z1r, z1i);
        cmul(sr, si, sr, si, z1r, z1i);
        csq(z4r, z4i, z2r, z2i);
        expand8(kl + 2048, kl + 2560, sr, si, hr, hi_, z2r, z2i, splat(z4r, z4i));
        if (LNPOS == 4) ln1();
        if (MMPOS == 0) norm();
        mm2(0);
        __syncwarp();
        ldsm4t(b0, la); ldsm4t(b1, la + 256); ldsm4t(b2, la + 1024); ldsm4t(b3, la + 1280);
        if (MMPOS == 1) norm();
        mm2(2);
        if (MMPOS == 2) norm();
        ldsm4t(b0, la + 2048); ldsm4t(b1, la + 2304);
#pragma unroll
        for (int t = 0; t < 4; t++) sts64(kb + lane * 8 + 1024 + t * 256, kp[t][0], kp[t][1]);
        {
            float a0[4] = {0.f, 0.f, 0.f, 0.f}, a1[4] = {0.f, 0.f, 0.f, 0.f};
            mma_f16(a0, Af[0], b0[0], b0[1]); mma_f16(a1, Af[1], b0[2], b0[3]); mma_f16(a0, Af[2], b1[0], b1[1]); mma_f16(a1, Af[3], b1[2], b1[3]);
            sts64(kb + lane * 8 + 2048, pack_f16(a0[1] + a1[1], a0[0] + a1[0]), pack_f16(a0[3] + a1[3], a0[2] + a1[2]));
        }
        bar_sync(1 + k, 128);
        const uint4 m01 = lds128(sb + SM_KG + k * 32), m23 = lds128(sb + SM_KG + k * 32 + 16);
        const unsigned Em = max(max(m01.x, m01.z), max(m23.x, m23.z));
        const float f0 = __uint_as_float(max((int)(127 + m01.x - Em), 0) << 23), f1 = __uint_as_float(max((int)(127 + m01.z - Em), 0) << 23),
                    f2 = __uint_as_float(max((int)(127 + m23.x - Em), 0) << 23), f3 = __uint_as_float(max((int)(127 + m23.z - Em), 0) << 23);
        const uint32_t r0 = pack_f16(f0, f0), r1 = pack_f16(f1, f1), r2 = pack_f16(f2, f2), r3 = pack_f16(f3, f3);
        const int tq = (wq + ROTK * k) & 3;
        const uint32_t ra = fb + lane * 8 + tq * 256 + 1024;
        const uint2 p0 = lds64(ra), p1 = lds64(ra + 3072), p2 = lds64(ra + 6144), p3 = lds64(ra + 9216);
        uint32_t w0 = hadd2(hfma2(p0.x, r0, hmul2(p1.x, r1)), hfma2(p2.x, r2, hmul2(p3.x, r3)));
        uint32_t w1 = hadd2(hfma2(p0.y, r0, hmul2(p1.y, r1)), hfma2(p2.y, r2, hmul2(p3.y, r3)));
        const bool last = lane == 31;
        if (tq < 2) {
            const uint32_t rc = fb + lane * 8 + tq * 4 + 2048;
            const uint32_t w4 = hmul2(hadd2(hfma2(lds32(rc), r0, hmul2(lds32(rc + 3072), r1)), hfma2(lds32(rc + 6144), r2, hmul2(lds32(rc + 9216), r3))), 0x18001800u);
            const uint32_t ph = pf + (P_H7 + 16 * tq) + (g & 1) * (2 * P_HS) + cq * 64 + (g >> 1) * 4;
            put16(ph, w4 >> 16); put16(ph + 32, w4);
            const uint32_t pa = pn + (4 + 512 * tq) + lane * 8;
            sts16(pa, w0 >> 16); sts32(pa + 4, w0); sts16(pa + 10, w0);
            sts16(pa + 256, w1 >> 16); sts32(pa + 260, w1); sts16(pa + 266, w1);
            if (last) {
                sts32(sb + SM_SC + k * 4, Em * 0x00800080u);
                put16(tq ? pa + 264 : pn,
                      tq ? w1 : pack_f16(((float)(int)m01.y * f0 + (float)(int)m01.w * f1 + (float)(int)m23.y * f2 + (float)(int)m23.w * f3) * (1.f / 16777216.f)
                                         + __uint_as_float(pD << 16) * __uint_as_float((254u - Em) << 23), 0.f));
            }
        } else if (tq == 2) {
            const uint32_t pa = pn + 258 * 4 + (cq & 1) * 16 + (cq >> 1) * 512 + g * 32;
            if (last) { put16(pf, hmul2(w1, 0x18001800u)); w1 = hadd2(w1, hneg2(__byte_perm(w1, 0, 0x1010))); }
            const uint32_t b0 = __byte_perm(w0, 0, 0x1010), b1 = __byte_perm(w1, 0, 0x1010);
            sts16(pa, w0 >> 16); sts32(pa + 4, w0); sts64(pa + 8, b0, b0); sts16(pa + 18, w0);
            sts16(pa + 256, w1 >> 16); sts32(pa + 260, w1); sts64(pa + 264, b1, b1); sts16(pa + 274, w1);
        } else {
            const uint32_t pa = pf + ((g & 1) ? 3 * P_GS : P_GS) + cq * 32 + (g >> 1) * 4;
            const uint32_t pb = pa + ((g & 1) ? 4 - 3 * P_GS : P_GS);
            w0 = hmul2(w0, 0x18001800u); w1 = hmul2(w1, 0x18001800u);
            put16(pa, w0 >> 16); put16(pb, w0); put16(pa + 16, w1 >> 16); put16(pb + 16, w1);
            if (last) put16(pf + P_H7 + P_HS, w1);
        }
        bar_sync(1 + k, 128);
    }
    STAMP(6);

    asm volatile("barrier.cluster.wait.aligned;" ::: "memory");
    mbar_wait(mb + (MB_X + (k < nslot ? k : 0)) * 8);
    STAMP(7);
    if (k < nslot) {
        const int role = (wq + k) & 3;
        const uint32_t ub = sb + SM_U + k * US + 128;
        if (role) {
            const int r = (3 - role) * 32 + lane;
            const uint32_t a1 = ub + (r & 3) * (2 * UP) + (r >> 2) * 16, a0 = a1 + ((r & 3) ? -2 * UP : 6 * UP - 16);
            const uint4 q0 = lds128(a0), q1 = lds128(a0 + UP), q2 = lds128(a1), q3 = lds128(a1 + UP);
            const uint32_t U[16] = {q0.x, q0.y, q0.z, q0.w, q1.x, q1.y, q1.z, q1.w, q2.x, q2.y, q2.z, q2.w, q3.x, q3.y, q3.z, q3.w};
            uint32_t V[14], Q[14], R4[12], T[8];
#pragma unroll
            for (int i = 2; i < 14; i++) { V[i] = __byte_perm(U[i], U[i + 1], 0x5432); Q[i] = hadd2(U[i], V[i]); }
#pragma unroll
            for (int i = 2; i < 12; i++) R4[i] = hadd2(Q[i], Q[i + 1]);
            const uint32_t rb = fb + r * 16;
#pragma unroll
            for (int i = 0; i < 8; i++) T[i] = hadd2(V[5 + i], Q[6 + i]);
            sts128(rb + F_E3, T[0], T[1], T[2], T[3]); sts128(rb + F_O3 + 16, T[4], T[5], T[6], T[7]);
#pragma unroll
            for (int i = 0; i < 8; i++) T[i] = hadd2(R4[3 + i], U[5 + i]);
            sts128(rb + F_O5, T[0], T[1], T[2], T[3]); sts128(rb + F_E5, T[4], T[5], T[6], T[7]);
            if (role != 1) {
#pragma unroll
                for (int i = 0; i < 8; i++) T[i] = hadd2(T[i], hadd2(V[2 + i], V[5 + i]));
                sts128(rb + F_E7, T[0], T[1], T[2], T[3]); sts128(rb + F_O7, T[4], T[5], T[6], T[7]);
#pragma unroll
                for (int i = 0; i < 8; i++) T[i] = hadd2(R4[2 + i], hadd2(R4[4 + i], U[6 + i]));
                sts128(rb + F_O9, T[0], T[1], T[2], T[3]); sts128(rb + F_E9 + 16, T[4], T[5], T[6], T[7]);
                sts128(rb + F_E2, Q[6], Q[7], Q[8], Q[9]); sts128(rb + F_O2, Q[10], Q[11], Q[12], Q[13]);
            }
        } else if (lane < 8) {
            uint32_t v[5];
#pragma unroll
            for (int i = 0; i < 5; i++) { const int t = 6 + lane + i; v[i] = lds16(ub + 23 * 16 + (t < 16 ? (6 + (t >> 3)) * UP : 16) + (t & 7) * 2); }
            const uint32_t s = hadd2(hadd2(hadd2(v[0], v[1]), hadd2(v[2], v[3])), v[4]);
            sts16(fb + F_O5 + 96 * 16 + lane * 2, s);
            sts32(fb + (lane < 4 ? F_O3 : F_E9 - 16) + lane * 4, 0);
        }
        bar_sync(1 + k, 128);
        float acc[4][4];
        uint32_t Q[4][4];
        {
            const int h = role & 1, part = role >> 1;
            const uint32_t po = pf + (g - 2 * cq) * 4;
            float fa[7][4];
#pragma unroll
            for (int a = 0; a < 7; a++) fa[a][0] = fa[a][1] = fa[a][2] = fa[a][3] = 0.f;
            uint32_t B[3][4];
            Q[0][2] = zero;
#pragma unroll 1
            for (int s = 2 * part + 1; s >= 2 * part; s--) {
#pragma unroll
                for (int i = 0; i < 3; i++) { Q[i][0] = lds32(po + s * P_GS + i * 64); Q[i][1] = lds32(po + s * P_GS + (i * 64 + 32)); }
                const uint32_t ba = fb + lane * 16 + ((s & 1) * F_E3 + (part == h ? 0 : F_O5 + h * 16));
#pragma unroll
                for (int i = 0; i < 3; i++) ldsm4t(B[i], ba + i * 512);
#pragma unroll
                for (int i = 0; i < 3; i++) { Q[i][3] = CP(Q[i][0]); if (i) Q[i][2] = CP(Q[i - 1][1]); }
#pragma unroll
                for (int dl = 0; dl < 3; dl++)
#pragma unroll
                    for (int ap = 0; ap < 6 - dl; ap++) mma_f16(fa[ap + 1 + dl], Q[dl], B[ap >> 1][2 * (ap & 1)], B[ap >> 1][2 * (ap & 1) + 1]);
            }
#pragma unroll 1
            for (int s = role; s == 1; s++) {
                ldsm2t(B[0][0], B[0][1], fb + ((lane & 15) == 15 ? F_O5 : F_O3));
#pragma unroll
                for (int dl = 0; dl < 3; dl++) mma_f16(fa[dl], Q[dl], B[0][0], B[0][1]);
            }
#pragma unroll 1
            for (int s = part; s <= 2 * part; s++) {
#pragma unroll
                for (int i = 0; i < 4; i++) { Q[i][0] = lds32(po + s * P_HS + (P_H7 + i * 64)); Q[i][1] = lds32(po + s * P_HS + (P_H7 + i * 64 + 32)); }
                const uint32_t ba = fb + lane * 16 + (F_E7 + s * 1024 + h * F_H);
                ldsm4t(B[0], ba); ldsm4t(B[1], ba + 512);
#pragma unroll
                for (int i = 0; i < 4; i++) { Q[i][3] = CP(Q[i][0]); if (i) Q[i][2] = CP(Q[i - 1][1]); }
#pragma unroll
                for (int dl = 0; dl < 4; dl++) {
#pragma unroll
                    for (int ap = 0; ap < 4 - dl; ap++) mma_f16(fa[ap + 3 + dl], Q[dl], B[ap >> 1][2 * (ap & 1)], B[ap >> 1][2 * (ap & 1) + 1]);
                    if (s == 1) break;
                }
            }
            const uint32_t da = fb + role * 2048 + (lane & 3) * 512 + (((lane >> 2) ^ ((lane & 3) * 2)) << 4);
            bar_sync(1 + k, 128);
            stsm4(da, 0u, 0u, pack_f16(fa[0][0], fa[0][1]), pack_f16(fa[0][2], fa[0][3]));
#pragma unroll
            for (int i = 1; i < 4; i++)
                stsm4(da + i * 128, pack_f16(fa[2 * i - 1][0], fa[2 * i - 1][1]), pack_f16(fa[2 * i - 1][2], fa[2 * i - 1][3]),
                      pack_f16(fa[2 * i][0], fa[2 * i][1]), pack_f16(fa[2 * i][2], fa[2 * i][3]));
            Q[0][0] = (g == 2 * cq) ? 0x6000u : ((g == 2 * cq + 1) ? 0x60000000u : 0u);
            Q[0][1] = 0; Q[0][3] = CP(Q[0][0]);
            const uint32_t ra = fb + (lane >> 3) * 2048 + wq * 512 + (((lane & 7) ^ (wq * 2)) << 4);
            bar_sync(1 + k, 128);
#pragma unroll
            for (int i = 0; i < 4; i++) {
                ldsm4(B[0], ra + i * 128);
                acc[i][0] = acc[i][1] = acc[i][2] = acc[i][3] = 0.f;
                mma_f16(acc[i], Q[0], hadd2(B[0][0], B[0][2]), hadd2(B[0][1], B[0][3]));
            }
        }
        bar_arrive(6 + k, 160);
        STAMP(8);
        const uint32_t inv = lds32(sb + SM_SC + k * 4);
        uint32_t yd = mapa(sb, 2 * wq) + (SM_XT + 128 + q * YP + k * YS + (k >> 2) * (q >> 1) * 16) + lane * 16;
        PIN(yd);
        {
            uint32_t pp = pn + (16 * (wq - 3) + g - 2 * cq) * 4;
            uint32_t dlo = (((ub + 6 * UP) & 0x3FFFF) >> 4) | ((UP >> 4) << 16);
            uint32_t R[4][4];
            auto loadQ = [&](uint32_t (&X)[4][4], uint32_t prev) {
#pragma unroll
                for (int i = 0; i < 4; i++) { X[i][0] = lds32(pp + i * 64); X[i][1] = lds32(pp + i * 64 + 32); }
                X[0][2] = CP(prev);
#pragma unroll
                for (int i = 0; i < 4; i++) { X[i][3] = CP(X[i][0]); if (i) X[i][2] = CP(X[i - 1][1]); }
                pp += 256;
            };
            auto issue = [&](uint32_t (&X)[4][4]) {
                asm volatile("wgmma.fence.sync.aligned;" ::: "memory");
#pragma unroll
                for (int i = 0; i < 4; i++) wgmma32(acc, X[i], dlo - i * (2 * UP >> 4));
                asm volatile("wgmma.commit_group.sync.aligned;" ::: "memory");
                dlo -= 1;
            };
            loadQ(Q, 0);
#pragma unroll 1
            for (int dl = 0; dl < 4; dl++) {
                issue(Q);
                asm volatile("wgmma.wait_group.sync.aligned 1;" ::: "memory");
                loadQ(R, Q[3][1]);
                issue(R);
                asm volatile("wgmma.wait_group.sync.aligned 1;" ::: "memory");
                loadQ(Q, R[3][1]);
            }
            issue(Q);
            asm volatile("wgmma.wait_group.sync.aligned 0;" ::: "memory");
        }
        const uint32_t pstep = mapa(sb, 1) - mapa(sb, 0), ym = mapa(mb + MB_Y * 8, 2 * wq);
#pragma unroll
        for (int e = 0; e < 2; e++)
            st_async4(yd + e * pstep, bmul2(pack_bf16(acc[0][2 * e], acc[0][2 * e + 1]), inv), bmul2(pack_bf16(acc[1][2 * e], acc[1][2 * e + 1]), inv),
                      bmul2(pack_bf16(acc[2][2 * e], acc[2][2 * e + 1]), inv), bmul2(pack_bf16(acc[3][2 * e], acc[3][2 * e + 1]), inv), ym + e * pstep);
        if (lane == 0) asm volatile("mbarrier.arrive.shared::cta.b64 _, [%0];" :: "r"(mb + MB_Y * 8) : "memory");
    }
    STAMP(9);
    uint32_t ha[5], hb[5];
    if (warp < 16) {
        const uint4 wk = lds128(sb + SM_DW + cq * 16);
        uint32_t sel[5] = {wk.x, wk.y, wk.z, wk.w, lds32(sb + SM_DW + 64 + cq * 4)}, sel2[5];
#pragma unroll
        for (int i = 0; i < 5; i++) {
            if (!(g & 1)) sel[i] = 0x3F803F80u;
            sel2[i] = sel[i]; PIN(sel2[i]);
        }
        const uint32_t y4 = sb + SM_XT + 128 + warp * 32 + (2 * (lane >> 3) + (lane & 1)) * YP + ((lane & 7) >> 1) * YS;
        const uint32_t y1 = sb + SM_XT + 128 + warp * 32 + (lane & 7) * YP + 4 * YS + (lane & 8) * 2 + (lane & 6) * 8;
        uint32_t ao = (256 * q + tn) * 16, hta = sb + SM_HT + tn * 80;
        PIN(ao); PIN(hta);
        mbar_wait(mb + MB_Y * 8);
        STAMP(10);
        float ca[4] = {0.f, 0.f, 0.f, 0.f}, cb[4] = {0.f, 0.f, 0.f, 0.f};
        {
            uint32_t ya[4], yb[4], yc, yd;
            ldsm4t(ya, y4); ldsm4t(yb, y4 + 16); ldsm2t(yc, yd, y1);
#pragma unroll
            for (int i = 0; i < 4; i++) { ha[i] = badd2(xa[i], ya[i]); hb[i] = badd2(xb[i], yb[i]); }
            ha[4] = badd2(xa[4], yc); hb[4] = badd2(xb[4], yd);
        }
        if (nslot != 5) {
            ha[4] = hb[4] = 0;
            if (cq >= 2) ha[0] = ha[1] = ha[2] = ha[3] = hb[0] = hb[1] = hb[2] = hb[3] = 0;
        }
#pragma unroll
        for (int i = 0; i < 5; i++) { mma_bf16_k8(ca, ha[i], sel[i], ha[i]); mma_bf16_k8(cb, hb[i], sel2[i], hb[i]); }
        if (!(g & 1)) { ca[1] = ca[0]; cb[1] = cb[0]; }
        if (cq == (g >> 1)) {
            asm volatile("red.relaxed.gpu.global.add.v4.f32 [%0], {%1,%2,%3,%4};" :: "l"((char*)g_s.acc + ao), "f"(1.0f), "f"(ca[1]), "f"(ca[2]), "f"(ca[3]) : "memory");
            asm volatile("red.relaxed.gpu.global.add.v4.f32 [%0], {%1,%2,%3,%4};" :: "l"((char*)g_s.acc + ao + 128), "f"(1.0f), "f"(cb[1]), "f"(cb[2]), "f"(cb[3]) : "memory");
        }
        sts128(hta + cq * 16, ha[0], ha[1], ha[2], ha[3]); sts32(hta + 64 + cq * 4, ha[4]);
        sts128(hta + cq * 16 + 640, hb[0], hb[1], hb[2], hb[3]); sts32(hta + 704 + cq * 4, hb[4]);
        STAMP(11);
    }
    const int kq = warp / 5, mt = warp - 5 * kq;
    const int mi = lane >> 3, mr = lane & 7;
    const unsigned tk = (unsigned)tid / 72u, ck = tid - tk * 72;
    uint32_t A[9][4];
    auto loadA = [&]() {
        mbar_wait(mb + MB_W1 * 8);
        const uint32_t aa = sb + (mi & 1) * SM_WU + (8 * (mi >> 1) + mr) * 80 + (144 * 80 * kq + mt * 16);
#pragma unroll
        for (int s = 0; s < 9; s++) ldsm4t(A[s], aa + s * 1280);
    };
    const uint32_t par = (epoch & 1) ? 0x40004000u : 0u;
    uint32_t pk0 = mapa(sb, 2 * cq), go = (ck / 5u + ck) * 16, co = ((q * 8 * NCL + c) * 6 + cq) * 16;
    PIN(pk0); PIN(go); PIN(co);
    if (warp < 8) {
        const float wsum = ldsf(sb + SM_SC + 24);
        const uint32_t idx = 2047 - (512 * ((tid >> 1) & 3) + 128 * ((tid >> 3) & 3) + 64 * (tid & 1) + 8 * q + warp);
        uint4 s; int n = 0;
        do { s = ld_rlx128(&g_s.acc[256 * q + tid]); } while (__uint_as_float(s.x) != (float)NCL && ++n < SPIN_LIMIT);
        STAMP(16);
        const uint32_t ox = __shfl_xor_sync(~0u, (lane & 1) ? s.z : s.w, 1);
        const uint32_t ms = ln_stats(__uint_as_float((lane & 1) ? ox : s.z), __uint_as_float(s.y));
        const float rs = rcpf(bf_hi(ms));
        const uint32_t rb = pack_bf16(0.f, fmaf(-bf_lo(ms), wsum, __uint_as_float((lane & 1) ? s.w : ox)) * rs);
        const uint32_t key = (((rb ^ (((int)rb >> 31) | 0x80000000u)) >> 16) << 11) | idx;
        sts32(sb + SM_KEY + tid * 4, key);
        __syncwarp();
        const uint32_t rank = rank4<8, 16>(sb + SM_KEY + warp * 128, key);
        if (rank < 8) sts32(sb + SM_CAND + warp * 32 + rank * 4, key);
        sts64(sb + SM_ST + tid * 8, ms, rsplit(rs));
    } else loadA();
    if (warp < 16) {
        STAMP(17);
        bar_sync(12, 512);
        STAMP(18);
        if (warp < 8) {
            const uint32_t mk = lds32(sb + SM_CAND + (tid >> 2) * 4);
            uint32_t rank = rank4<4, 64>(sb + SM_CAND + cq * 16, mk);
            rank += __shfl_xor_sync(~0u, rank, 1); rank += __shfl_xor_sync(~0u, rank, 2);
            if (rank < 8) {
                const uint32_t pk1 = pk0 + (mapa(sb, 1) - mapa(sb, 0));
                st_async1(pk0 + (SM_RK + q * 32) + rank * 4, mk, pk0 + (SM_MB + MB_KEY * 8));
                st_async1(pk1 + (SM_RK + q * 32) + rank * 4, mk, pk1 + (SM_MB + MB_KEY * 8));
                const uint32_t t = tslot(~mk);
                const uint2 sv = lds64(sb + SM_ST + t * 8);
                const uint4 hv = lds128(sb + SM_HT + t * 80 + cq * 16);
                const uint32_t h4 = lds32(sb + SM_HT + t * 80 + 64 + cq * 4);
                const uint32_t rr = bmul2(sv.y, 0x3C803C80u);
                char* const dp = (char*)g_s.cand + (co + rank * 1440);
                st_rlx128(dp, (norm2(hv.x, sv.x, rr) & 0xBFFFBFFFu) | par, (norm2(hv.y, sv.x, rr) & 0xBFFFBFFFu) | par,
                          (norm2(hv.z, sv.x, rr) & 0xBFFFBFFFu) | par, (norm2(hv.w, sv.x, rr) & 0xBFFFBFFFu) | par);
                asm volatile("st.relaxed.gpu.global.u32 [%0], %1;" :: "l"((char*)g_s.cand + (co + rank * 1440 + 64 - cq * 12)), "r"((norm2(h4, sv.x, rr) & 0xBFFFBFFFu) | par) : "memory");
            }
            __syncwarp();
        }
        {
            const uint2 sa = lds64(sb + SM_ST + tn * 8), sbb = lds64(sb + SM_ST + tn * 8 + 64);
#pragma unroll
            for (int i = 0; i < 5; i++) { ha[i] = badd2(ha[i], norm2(ha[i], sa.x, sa.y)); hb[i] = badd2(hb[i], norm2(hb[i], sbb.x, sbb.y)); }
            const bool hf = (c & 1) && cq == 0;
            const uint32_t o16 = sb + SM_XT + (hf ? 16384 + tn * 16 : tn * 64 + (cq - (c & 1)) * 16), o4 = sb + SM_XT + ((c & 1) ? tn * 64 + 48 : 16384 + tn * 16) + cq * 4;
            sts128(o16, ha[0], ha[1], ha[2], ha[3]); sts32(o4, ha[4]);
            sts128(o16 + (hf ? 128 : 512), hb[0], hb[1], hb[2], hb[3]); sts32(o4 + ((c & 1) ? 512 : 128), hb[4]);
        }
        if (warp >= 8) {
            STAMP(19);
            mbar_wait(mb + MB_KEY * 8);
            STAMP(20);
            const uint32_t mk = lds32(sb + SM_RK - 256 + (tid >> 2) * 4);
            uint32_t rank = rank4<4, 64>(sb + SM_RK + cq * 16, mk);
            rank += __shfl_xor_sync(~0u, rank, 1); rank += __shfl_xor_sync(~0u, rank, 2);
            if (rank < 8) sts64(sb + SM_SEL + rank * 8, mk, ((tid >> 2) - 64) * 1440);
        }
    }
    bar_sync(11, 640);
    STAMP(12);

    const char* gp = (const char*)g_s.cand + (go + lds32(sb + SM_SEL + 4 + (tk & 7) * 8));
    uint4 hv = ld_rlx128(gp);
    if (warp < 8) loadA();
    const bool red = warp < 6;
    const uint32_t ft = red ? (unsigned)tid / 24u : (unsigned)(tid >> 4) & 7u, fj = red ? 24 * q + tid - ft * 24 : d0 / 3 + (lane & 15);
    const uint32_t key = lds32(sb + SM_SEL + ft * 8), k16 = key << 5;
    float sig = bfr(rcpf(1.f + ex2f(__uint_as_float((k16 ^ (~((int)k16 >> 31) | 0x80000000u)) & 0xFFFF0000u) * -1.4426950408889634f)));
    uint32_t ra2 = sb + SM_RED2 + tid * 12 + ft * 16, fo = (ft * 192 + fj) * 16, oo = ((~key & 2047) * D_ + 3 * fj) * 2;
    uint32_t bx = sb + SM_XS + mr * 1168 + mi * 16 + 288 * kq, gd = mapa(sb, kq * (8 / NRED)) + (SM_GU + (q * nslot + mt) * 128) + lane * 4;
    PIN(ra2); PIN(fo); PIN(oo); PIN(bx); PIN(gd);
    asm volatile("" : "+f"(sig));
    {
        if (warp < 18) {
            int n = 0;
            while ((((hv.x ^ par) | (hv.y ^ par) | (hv.z ^ par) | (hv.w ^ par)) & 0x40004000u) && ++n < SPIN_LIMIT) hv = ld_rlx128(gp);
            sts128(sb + SM_XS + tk * 16 + tid * 16, hv.x ^ par, hv.y ^ par, hv.z ^ par, hv.w ^ par);
        }
    }
    bar_sync(14, 672);
    STAMP(13);
    {
        float c0[4] = {0.f, 0.f, 0.f, 0.f}, c1[4] = {0.f, 0.f, 0.f, 0.f}, c2[4] = {0.f, 0.f, 0.f, 0.f};
        uint32_t b[5][4];
#pragma unroll
        for (int s = 0; s < 4; s++) ldsm4(b[s], bx + s * 64);
        asm volatile("ldmatrix.sync.aligned.m8n8.x2.shared.b16 {%0,%1}, [%2];" : "=r"(b[4][0]), "=r"(b[4][1]) : "r"(bx + 256) : "memory");
        mma_bf16(c0, A[0][0], A[0][1], A[0][2], A[0][3], b[0][0], b[0][1]);
        mma_bf16(c1, A[1][0], A[1][1], A[1][2], A[1][3], b[0][2], b[0][3]);
        mma_bf16(c2, A[2][0], A[2][1], A[2][2], A[2][3], b[1][0], b[1][1]);
        mma_bf16(c0, A[3][0], A[3][1], A[3][2], A[3][3], b[1][2], b[1][3]);
        mma_bf16(c1, A[4][0], A[4][1], A[4][2], A[4][3], b[2][0], b[2][1]);
        mma_bf16(c2, A[5][0], A[5][1], A[5][2], A[5][3], b[2][2], b[2][3]);
        mma_bf16(c0, A[6][0], A[6][1], A[6][2], A[6][3], b[3][0], b[3][1]);
        mma_bf16(c1, A[7][0], A[7][1], A[7][2], A[7][3], b[3][2], b[3][3]);
        mma_bf16(c2, A[8][0], A[8][1], A[8][2], A[8][3], b[4][0], b[4][1]);
        sts128f(sb + SM_RED + tid * 16, c0[0] + c1[0] + c2[0], c0[1] + c1[1] + c2[1], c0[2] + c1[2] + c2[2], c0[3] + c1[3] + c2[3]);
    }
    bar_sync(1 + mt, 128);
    STAMP(21);
    if (mt < nslot && kq < NRED) {
        const uint32_t ra = sb + SM_RED + mt * 512 + lane * 16;
        const float4 p0 = lds128f(ra), p1 = lds128f(ra + 2560), p2 = lds128f(ra + 5120), p3 = lds128f(ra + 7680);
        const float g0 = bfr(((p0.x + p1.x) + (p2.x + p3.x)) * 64.f), g1 = bfr(((p0.y + p1.y) + (p2.y + p3.y)) * 64.f);
        const uint32_t sg = pack_bf16(g0 * rcpf(1.f + ex2f(g0 * -1.4426950408889634f)), g1 * rcpf(1.f + ex2f(g1 * -1.4426950408889634f)));
        const uint32_t gu = bmul2(sg, pack_bf16(((p0.z + p1.z) + (p2.z + p3.z)) * 64.f, ((p0.w + p1.w) + (p2.w + p3.w)) * 64.f));
        const uint32_t pstep = mapa(sb, 1) - mapa(sb, 0), gm = mapa(mb + MB_GU * 8, kq * (8 / NRED));
#pragma unroll
        for (int i = 0; i < 8 / NRED; i++) st_async1(gd + i * pstep, gu, gm + i * pstep);
    }
    mbar_wait(mb + MB_W2 * 8);
    {
        const uint32_t aa = sb + (8 * (mi >> 1) + mr) * (2 * W2W) + (mi & 1) * 16 + (SM_FAR + 32 * W2W * kq + mt * 32 + (W2W == 72 ? 0 : (q & 1) * 16));
#pragma unroll
        for (int s = 0; s < 5; s++) ldsm4t(A[s], aa + s * FAR_SZ);
    }
    {
        uint32_t ba = sb + (SM_GU + 256 * kq) + (lane & 15) * 16 + (lane >> 4) * 1024, wa = sb + (SM_RED2 + kq * 2432 + mt * 64) + g * 4 + cq * 608;
        PIN(ba); PIN(wa);
        STAMP(22);
        mbar_wait(mb + MB_GU * 8);
        STAMP(23);
        float c0[4] = {0.f, 0.f, 0.f, 0.f}, c1[4] = {0.f, 0.f, 0.f, 0.f}, c2[4] = {0.f, 0.f, 0.f, 0.f};
        uint32_t b[2][4], b8, b9;
        ldsm4t(b[0], ba); ldsm4t(b[1], ba + 2048); ldsm2t(b8, b9, ba + 4096);
        mma_bf16(c0, A[0][0], A[0][1], A[0][2], A[0][3], b[0][0], b[0][1]);
        mma_bf16(c1, A[1][0], A[1][1], A[1][2], A[1][3], b[0][2], b[0][3]);
        if (nslot == 5) {
            mma_bf16(c2, A[4][0], A[4][1], A[4][2], A[4][3], b8, b9);
            mma_bf16(c0, A[2][0], A[2][1], A[2][2], A[2][3], b[1][0], b[1][1]);
            mma_bf16(c1, A[3][0], A[3][1], A[3][2], A[3][3], b[1][2], b[1][3]);
        }
        stsf(wa, c0[0] + c1[0] + c2[0]); stsf(wa + 304, c0[1] + c1[1] + c2[1]);
        if (mt < 4) { stsf(wa + 32, c0[2] + c1[2] + c2[2]); stsf(wa + 336, c0[3] + c1[3] + c2[3]); }
    }
    if (warp < 10) {
        float v[3], cnt = 3.f;
        if (red) {
            bar_sync(6, 640);
            STAMP(14);
#pragma unroll
            for (int i = 0; i < 3; i++) v[i] = ((ldsf(ra2 + i * 4) + ldsf(ra2 + i * 4 + 2432)) + (ldsf(ra2 + i * 4 + 4864) + ldsf(ra2 + i * 4 + 7296))) * sig;
        } else {
            bar_arrive(6, 640);
            cnt = 0.f;
#pragma unroll
            for (int i = 0; i < 3; i++) {
                const uint32_t cl = 3 * fj + i - d0;
                const bool ok = cl < 8 * nslot && ((~key >> 3) & 7) == q;
                const uint32_t cf = cl - (c & 1) * 8;
                v[i] = ok ? __uint_as_float(lds16(sb + SM_XT + (cf < 32 ? tslot(~key) * 64 + cf * 2 : 16384 + tslot(~key) * 16 + (cl & 7) * 2)) << 16) : 0.f;
                if (ok) cnt += 1.f;
            }
            mbar_wait(mb + MB_OUT * 8);
        }
        if (cnt != 0.f) {
            float x, y, z, w;
            asm volatile("atom.relaxed.gpu.global.add.v4.f32 {%0,%1,%2,%3}, [%4], {%5,%6,%7,%8};" : "=f"(x), "=f"(y), "=f"(z), "=f"(w)
                         : "l"((char*)g_s.fin + fo), "f"(v[0]), "f"(v[1]), "f"(v[2]), "f"(cnt) : "memory");
            if (w + cnt == 3.f * (NCL + 1)) {
                __nv_bfloat16* op = (__nv_bfloat16*)((char*)prm.out + oo);
                op[0] = __float2bfloat16(x + v[0]); op[1] = __float2bfloat16(y + v[1]); op[2] = __float2bfloat16(z + v[2]);
            }
        }
    } else bar_arrive(6, 640);
    STAMP(15);
}

typedef __nv_bfloat16 bf16;
__device__ bf16 f_n[L_ * D_], f_h[L_ * D_];
__device__ float f_k[D_ * L_], f_r[L_], f_gu[8 * F_];
__device__ int f_idx[8];
__device__ __forceinline__ float b2f(bf16 v) { return __bfloat162float(v); }
__global__ void fb_ln(const bf16* in, const bf16* wr, bf16* out) {
    const int t = blockIdx.x * 8 + (threadIdx.x >> 5), lane = threadIdx.x & 31;
    const bf16* r = (in ? in : f_h) + t * D_;
    float s1 = 0.f, s2 = 0.f, s3 = 0.f;
    for (int i = lane; i < D_; i += 32) s1 += b2f(r[i]);
    for (int o = 16; o; o >>= 1) s1 += __shfl_xor_sync(~0u, s1, o);
    for (int i = lane; i < D_; i += 32) { const float d = b2f(r[i]) - s1 / D_; s2 += d * d; }
    for (int o = 16; o; o >>= 1) s2 += __shfl_xor_sync(~0u, s2, o);
    const float m = bfr(s1 / D_), sd = bfr(sqrtf(bfr(bfr(s2 / D_) + 1e-5f)));
    for (int i = lane; i < D_; i += 32) {
        const float v = bfr(bfr(b2f(r[i]) - m) / sd);
        f_n[t * D_ + i] = __float2bfloat16(v);
        if (!in) { s3 += v * b2f(wr[i]); out[t * D_ + i] = __float2bfloat16(b2f(r[i]) + v); }
    }
    for (int o = 16; o; o >>= 1) s3 += __shfl_xor_sync(~0u, s3, o);
    f_r[t] = bfr(s3);
}
__global__ void fb_taps(Params p) {
    const int d = blockIdx.x >> 3, l = (blockIdx.x & 7) * 256 + threadIdx.x;
    const float dt = bfr(expf(bf_lo(p.logdt[d]))), lf = bfr((float)l);
    float k = 0.f;
    for (int n = d * 128; n < d * 128 + 128; n++) {
        float wr, wi, sn, cs;
        cmul(wr, wi, bf_lo(p.prm6[4][n]), bf_lo(p.prm6[5][n]), dt * bf_lo(p.prm6[2][n]), dt * bf_lo(p.prm6[3][n]));
        sincosf(dt * bf_lo(p.prm6[1][n]) * lf, &sn, &cs);
        k += expf(dt * bf_lo(p.prm6[0][n]) * lf) * (wr * cs - wi * sn);
    }
    f_k[l * D_ + d] = k;
}
__global__ void fb_conv(Params p) {
    const int t = blockIdx.x, d = threadIdx.x;
    float y = 0.f;
    for (int l = 0; l <= t; l++) y += f_k[l * D_ + d] * b2f(f_n[(t - l) * D_ + d]);
    f_h[t * D_ + d] = __float2bfloat16(bf_lo(p.x[t * D_ + d]) + bfr(bfr(y) + bfr(b2f(f_n[t * D_ + d]) * bf_lo(p.dskip[d]))));
}
__global__ void fb_top() {
    const int t = blockIdx.x * 256 + threadIdx.x;
    int rank = 0;
    for (int j = 0; j < L_; j++) rank += f_r[j] > f_r[t] || (f_r[j] == f_r[t] && j < t);
    if (rank < 8) f_idx[rank] = t;
}
__global__ void fb_ffn1(const bf16* wg, const bf16* wu) {
    const int f = blockIdx.x * 256 + threadIdx.x, j = blockIdx.y;
    float g = 0.f, u = 0.f;
    for (int i = 0; i < D_; i++) { const float v = b2f(f_n[f_idx[j] * D_ + i]); g += v * b2f(wg[i * F_ + f]); u += v * b2f(wu[i * F_ + f]); }
    g = bfr(g);
    f_gu[j * F_ + f] = bfr(bfr(g / (1.f + expf(-g))) * bfr(u));
}
__global__ void fb_ffn2(const bf16* wd, bf16* out) {
    const int d = threadIdx.x, j = blockIdx.x, t = f_idx[j];
    float y = 0.f;
    for (int f = 0; f < F_; f++) y += f_gu[j * F_ + f] * b2f(wd[f * D_ + d]);
    out[t * D_ + d] = __float2bfloat16(b2f(f_h[t * D_ + d]) + bfr(b2f(f_n[t * D_ + d]) + bfr(bfr(y) * bfr(1.f / (1.f + expf(-f_r[t]))))));
}

typedef CUresult (*EncodeFn)(CUtensorMap*, CUtensorMapDataType, cuuint32_t, void*, const cuuint64_t*, const cuuint64_t*,
                             const cuuint32_t*, const cuuint32_t*, CUtensorMapInterleave, CUtensorMapSwizzle,
                             CUtensorMapL2promotion, CUtensorMapFloatOOBfill);

void make_map(EncodeFn fn, CUtensorMap* tm, const void* p, int cols, int rows, int bc, int br) {
    cuuint64_t dims[2] = {(cuuint64_t)cols, (cuuint64_t)rows};
    cuuint64_t strides[1] = {(cuuint64_t)cols * 2};
    cuuint32_t box[2] = {(cuuint32_t)bc, (cuuint32_t)br};
    cuuint32_t es[2] = {1, 1};
    fn(tm, CU_TENSOR_MAP_DATA_TYPE_BFLOAT16, 2, const_cast<void*>(p), dims, strides, box, es, CU_TENSOR_MAP_INTERLEAVE_NONE,
       CU_TENSOR_MAP_SWIZZLE_NONE, CU_TENSOR_MAP_L2_PROMOTION_L2_128B, CU_TENSOR_MAP_FLOAT_OOB_FILL_NONE);
}

void make_map3(EncodeFn fn, CUtensorMap* tm, const void* p) {
    cuuint64_t dims[5] = {(cuuint64_t)D_, 64, 2, 4, 4};
    cuuint64_t strides[4] = {(cuuint64_t)D_ * 2, (cuuint64_t)D_ * 128, (cuuint64_t)D_ * 1024, (cuuint64_t)D_ * 256};
    cuuint32_t box[5] = {XW, 9, 2, 4, 4};
    cuuint32_t es[5] = {1, 1, 1, 1, 1};
    fn(tm, CU_TENSOR_MAP_DATA_TYPE_BFLOAT16, 5, const_cast<void*>(p), dims, strides, box, es, CU_TENSOR_MAP_INTERLEAVE_NONE,
       CU_TENSOR_MAP_SWIZZLE_NONE, CU_TENSOR_MAP_L2_PROMOTION_NONE, CU_TENSOR_MAP_FLOAT_OOB_FILL_NONE);
}

void make_map5(EncodeFn fn, CUtensorMap* tm, const void* p, int bc) {
    cuuint64_t dims[5] = {(cuuint64_t)D_, 2, 4, 4, 64};
    cuuint64_t strides[4] = {(cuuint64_t)D_ * 128, (cuuint64_t)D_ * 1024, (cuuint64_t)D_ * 256, (cuuint64_t)D_ * 2};
    cuuint32_t box[5] = {(cuuint32_t)bc, 2, 4, 4, 8};
    cuuint32_t es[5] = {1, 1, 1, 1, 1};
    fn(tm, CU_TENSOR_MAP_DATA_TYPE_BFLOAT16, 5, const_cast<void*>(p), dims, strides, box, es, CU_TENSOR_MAP_INTERLEAVE_NONE,
       CU_TENSOR_MAP_SWIZZLE_NONE, CU_TENSOR_MAP_L2_PROMOTION_NONE, CU_TENSOR_MAP_FLOAT_OOB_FILL_NONE);
}

}

extern "C" void kernel_launch(void* const* d_in, const int* in_sizes, int n_in, void* d_out, int out_size) {
    (void)in_sizes; (void)n_in; (void)out_size;
    void* fp = nullptr;
    cudaDriverEntryPointQueryResult qr;
    cudaGetDriverEntryPoint("cuTensorMapEncodeTiled", &fp, cudaEnableDefault, &qr);
    EncodeFn fn = (EncodeFn)fp;
    CUtensorMap tmG, tmU, tmD, tmO, tmX, tmH;
    make_map3(fn, &tmX, d_in[0]);
    make_map(fn, &tmG, d_in[11], F_, D_, 40, 48);
    make_map(fn, &tmU, d_in[12], F_, D_, 40, 48);
    make_map(fn, &tmD, d_in[13], D_, F_, W2W, 64);
    make_map5(fn, &tmO, d_out, 32);
    make_map5(fn, &tmH, d_out, 8);
    Params p;
    p.x = (const unsigned short*)d_in[0];
    for (int i = 0; i < 6; i++) p.prm6[i] = (const unsigned short*)d_in[1 + i];
    p.logdt = (const unsigned short*)d_in[7]; p.dskip = (const unsigned short*)d_in[8];
    p.wr = (const unsigned short*)d_in[10];
    p.out = (__nv_bfloat16*)d_out;
    p.zero = 0;
    cudaGetSymbolAddress((void**)&p.gs, g_s);
    cudaFuncSetAttribute(fused_kernel, cudaFuncAttributeMaxDynamicSharedMemorySize, SM_TOTAL);
    static int nclusters = -1;
    if (nclusters < 0) {
        cudaLaunchConfig_t cfg = {};
        cudaLaunchAttribute at;
        at.id = cudaLaunchAttributeClusterDimension; at.val.clusterDim.x = CS; at.val.clusterDim.y = 1; at.val.clusterDim.z = 1;
        cfg.gridDim = dim3(NCTA); cfg.blockDim = dim3(NTHR); cfg.dynamicSmemBytes = SM_TOTAL; cfg.attrs = &at; cfg.numAttrs = 1;
        if (cudaOccupancyMaxActiveClusters(&nclusters, fused_kernel, &cfg) != cudaSuccess) { (void)cudaGetLastError(); nclusters = NCL; }
    }
    if (nclusters >= NCL && !FORCE_FALLBACK) {
        fused_kernel<<<NCTA, NTHR, SM_TOTAL>>>(p, tmG, tmU, tmD, tmO, tmX, tmH);
        return;
    }
    fb_ln<<<L_ / 8, 256>>>((const bf16*)d_in[0], nullptr, nullptr);
    fb_taps<<<D_ * 8, 256>>>(p);
    fb_conv<<<L_, D_>>>(p);
    fb_ln<<<L_ / 8, 256>>>(nullptr, (const bf16*)d_in[10], p.out);
    fb_top<<<L_ / 256, 256>>>();
    fb_ffn1<<<dim3(F_ / 256, 8), 256>>>((const bf16*)d_in[11], (const bf16*)d_in[12]);
    fb_ffn2<<<8, D_>>>((const bf16*)d_in[13], p.out);
}
```

```cpp
#include <cuda_runtime.h>
#include <cuda_bf16.h>
#include <cuda_fp16.h>
#include <cuda.h>
#include <stdint.h>

namespace {

constexpr int L_ = 2048, D_ = 576, F_ = 4608;
constexpr int NCL = 15, CS = 8, NCTA = NCL * CS, NTHR = 768;
#define W2W 72
#define XW 48
#define TILE_NS -1
#define XROT 1
#define FORCE_FALLBACK 0
#define ROTK 1
#define LNPOS 1
#define MMPOS 0
#define XSPLIT 3
constexpr int NRED = 2;
constexpr int SPIN_LIMIT = 1 << 22;

constexpr int SM_WG   = 0;
constexpr int SM_WU   = 46080;
constexpr int YP = 3392, YS = 656;
constexpr int UP = 3280, US = 656;
constexpr int SM_XT   = 92160;
constexpr int SM_U    = SM_XT + 8 * YP;
constexpr int SM_FAR  = SM_U + 8 * UP;
constexpr int FAR_SZ  = 12416;
constexpr int F_E5 = 0, F_O5 = 1536, F_E3 = 3088, F_O3 = 4624, F_E7 = 6176, F_E2 = F_E7 + 1024, F_E9 = F_E7 + 2048,
              F_H = 3088, F_O7 = F_E7 + F_H, F_O2 = F_E2 + F_H, F_O9 = F_E9 + F_H;
constexpr int SM_P    = SM_FAR + 5 * FAR_SZ;
constexpr int PN_SZ = 584 * 4, SM_PN = SM_P + 64 * 4;
constexpr int P_GS = 48 * 4, P_H7 = 192 * 4, P_HS = 72 * 4;
constexpr int PF_SZ = (192 + 216) * 4, SM_PF = SM_PN + 5 * PN_SZ + 32;
constexpr int SM_MISC = SM_PF + 5 * PF_SZ;
constexpr int SM_ST   = SM_MISC;
constexpr int SM_RK   = SM_ST + 2048;
constexpr int SM_SEL  = SM_RK + 256;
constexpr int SM_KG   = SM_SEL + 64;
constexpr int SM_SC   = SM_KG + 160;
constexpr int SM_DW   = SM_SC + 32;
constexpr int SM_MB   = SM_DW + 160;
constexpr int SM_TOTAL = SM_MB + 128;
constexpr int SM_ROW  = SM_XT - 20736;
constexpr int SM_XTL  = SM_ROW - 576 * XW;
constexpr int SM_RED2 = SM_WG;
constexpr int SM_HT   = SM_P - 512;
constexpr int SM_KEY  = SM_FAR + 10240 + 128;
constexpr int SM_CAND = SM_KEY + 1024;
constexpr int SM_XS   = SM_U;
constexpr int SM_GU   = SM_XS + 9344;
constexpr int SM_RED  = SM_GU + 5632;
static_assert(F_O9 + 1024 <= FAR_SZ && FAR_SZ % 128 == 0, "far overflow");
static_assert(SM_RED + 10240 <= SM_FAR && SM_HT + 20496 <= SM_MISC, "alias overflow");
static_assert(SM_TOTAL <= 232448, "smem overflow");
static_assert(SM_FAR % 128 == 0 && SM_XT % 128 == 0 && SM_XTL % 128 == 0 && SM_P % 16 == 0 && SM_MISC % 16 == 0 && SM_MB % 8 == 0, "align");

enum { MB_X = 0, MB_W1 = 5, MB_W2 = 6, MB_KEY = 7, MB_GU = 8, MB_Y = 9, MB_OUT = 10, MB_T = 11, MB_R = 12 };

struct __align__(128) Scratch {
    unsigned epoch, zcnt, pad[30];
    uint4  st1[L_ * 2];
    float4 acc[L_];
    uint4  cand[64 * NCL * 6];
    float4 fin[8 * 192 + 24];
};
__device__ Scratch g_s;
#define STAMP(i)

__device__ __forceinline__ uint32_t mapa(uint32_t a, uint32_t r) { uint32_t d; asm("mapa.shared::cluster.u32 %0, %1, %2;" : "=r"(d) : "r"(a), "r"(r)); return d; }
__device__ __forceinline__ void mbar_wait(uint32_t mb) {
    asm volatile("{ .reg .pred p, q; .reg .u32 n; mov.u32 n, 0;\n"
                 "W_%=: mbarrier.try_wait.parity.shared::cta.b64 p, [%0], 0; add.u32 n, n, 1; setp.lt.and.u32 q, n, 65536, !p; @q bra W_%=; }" :: "r"(mb) : "memory");
}
__device__ __forceinline__ void arm(uint32_t mb, uint32_t bytes) { asm volatile("mbarrier.arrive.expect_tx.shared::cta.b64 _, [%0], %1;" :: "r"(mb), "r"(bytes) : "memory"); }
__device__ __forceinline__ void bar_sync(int id, int n) { asm volatile("bar.sync %0, %1;" :: "r"(id), "r"(n) : "memory"); }
__device__ __forceinline__ void bar_arrive(int id, int n) { asm volatile("bar.arrive %0, %1;" :: "r"(id), "r"(n) : "memory"); }
__device__ __forceinline__ uint32_t lds16(uint32_t a) { unsigned short v; asm volatile("ld.shared.u16 %0, [%1];" : "=h"(v) : "r"(a) : "memory"); return v; }
__device__ __forceinline__ uint32_t lds32(uint32_t a) { uint32_t v; asm volatile("ld.shared.u32 %0, [%1];" : "=r"(v) : "r"(a) : "memory"); return v; }
__device__ __forceinline__ uint2 lds64(uint32_t a) { uint2 v; asm volatile("ld.shared.v2.u32 {%0,%1}, [%2];" : "=r"(v.x), "=r"(v.y) : "r"(a) : "memory"); return v; }
__device__ __forceinline__ float ldsf(uint32_t a) { float v; asm volatile("ld.shared.f32 %0, [%1];" : "=f"(v) : "r"(a) : "memory"); return v; }
__device__ __forceinline__ uint4 lds128(uint32_t a) { uint4 v; asm volatile("ld.shared.v4.u32 {%0,%1,%2,%3}, [%4];" : "=r"(v.x), "=r"(v.y), "=r"(v.z), "=r"(v.w) : "r"(a) : "memory"); return v; }
__device__ __forceinline__ float4 lds128f(uint32_t a) { float4 v; asm volatile("ld.shared.v4.f32 {%0,%1,%2,%3}, [%4];" : "=f"(v.x), "=f"(v.y), "=f"(v.z), "=f"(v.w) : "r"(a) : "memory"); return v; }
__device__ __forceinline__ void sts16(uint32_t a, uint32_t v) { asm volatile("{ .reg .b16 l, h; mov.b32 {l, h}, %1; st.shared.b16 [%0], l; }" :: "r"(a), "r"(v) : "memory"); }
__device__ __forceinline__ void sts32(uint32_t a, uint32_t v) { asm volatile("st.shared.u32 [%0], %1;" :: "r"(a), "r"(v) : "memory"); }
__device__ __forceinline__ void sts64(uint32_t a, uint32_t x, uint32_t y) { asm volatile("st.shared.v2.u32 [%0], {%1,%2};" :: "r"(a), "r"(x), "r"(y) : "memory"); }
__device__ __forceinline__ void stsf(uint32_t a, float v) { asm volatile("st.shared.f32 [%0], %1;" :: "r"(a), "f"(v) : "memory"); }
__device__ __forceinline__ void sts128(uint32_t a, uint32_t x, uint32_t y, uint32_t z, uint32_t w) { asm volatile("st.shared.v4.u32 [%0], {%1,%2,%3,%4};" :: "r"(a), "r"(x), "r"(y), "r"(z), "r"(w) : "memory"); }
__device__ __forceinline__ void sts128f(uint32_t a, float x, float y, float z, float w) { asm volatile("st.shared.v4.f32 [%0], {%1,%2,%3,%4};" :: "r"(a), "f"(x), "f"(y), "f"(z), "f"(w) : "memory"); }
__device__ __forceinline__ void ldsm4(uint32_t (&r)[4], uint32_t a) { asm volatile("ldmatrix.sync.aligned.m8n8.x4.shared.b16 {%0,%1,%2,%3}, [%4];" : "=r"(r[0]), "=r"(r[1]), "=r"(r[2]), "=r"(r[3]) : "r"(a) : "memory"); }
__device__ __forceinline__ void ldsm4t(uint32_t (&r)[4], uint32_t a) { asm volatile("ldmatrix.sync.aligned.m8n8.x4.trans.shared.b16 {%0,%1,%2,%3}, [%4];" : "=r"(r[0]), "=r"(r[1]), "=r"(r[2]), "=r"(r[3]) : "r"(a) : "memory"); }
__device__ __forceinline__ void ldsm2t(uint32_t& r0, uint32_t& r1, uint32_t a) { asm volatile("ldmatrix.sync.aligned.m8n8.x2.trans.shared.b16 {%0,%1}, [%2];" : "=r"(r0), "=r"(r1) : "r"(a) : "memory"); }
__device__ __forceinline__ void stsm4t(uint32_t a, uint32_t r0, uint32_t r1, uint32_t r2, uint32_t r3) { asm volatile("stmatrix.sync.aligned.m8n8.x4.trans.shared.b16 [%0], {%1,%2,%3,%4};" :: "r"(a), "r"(r0), "r"(r1), "r"(r2), "r"(r3) : "memory"); }
__device__ __forceinline__ void stsm4(uint32_t a, uint32_t r0, uint32_t r1, uint32_t r2, uint32_t r3) { asm volatile("stmatrix.sync.aligned.m8n8.x4.shared.b16 [%0], {%1,%2,%3,%4};" :: "r"(a), "r"(r0), "r"(r1), "r"(r2), "r"(r3) : "memory"); }
__device__ __forceinline__ void stsm2t(uint32_t a, uint32_t r0, uint32_t r1) { asm volatile("stmatrix.sync.aligned.m8n8.x2.trans.shared.b16 [%0], {%1,%2};" :: "r"(a), "r"(r0), "r"(r1) : "memory"); }
__device__ __forceinline__ uint4 ldg128(const void* p) { uint4 v; asm volatile("ld.global.nc.v4.u32 {%0,%1,%2,%3}, [%4];" : "=r"(v.x), "=r"(v.y), "=r"(v.z), "=r"(v.w) : "l"(p)); return v; }
__device__ __forceinline__ uint32_t ldg16(const void* p) { unsigned short v; asm volatile("ld.global.nc.u16 %0, [%1];" : "=h"(v) : "l"(p)); return v; }
__device__ __forceinline__ uint32_t opaque(uint32_t v) { uint32_t r; asm volatile("mov.b32 %0, %1;" : "=r"(r) : "r"(v)); return r; }
__device__ __forceinline__ void mma_f16(float (&d)[4], const uint32_t (&a)[4], uint32_t b0, uint32_t b1) {
    asm volatile("mma.sync.aligned.m16n8k16.row.col.f32.f16.f16.f32 {%0,%1,%2,%3}, {%4,%5,%6,%7}, {%8,%9}, {%0,%1,%2,%3};"
        : "+f"(d[0]), "+f"(d[1]), "+f"(d[2]), "+f"(d[3]) : "r"(a[0]), "r"(a[1]), "r"(a[2]), "r"(a[3]), "r"(b0), "r"(b1));
}
__device__ __forceinline__ void mma_bf16(float (&d)[4], uint32_t a0, uint32_t a1, uint32_t a2, uint32_t a3, uint32_t b0, uint32_t b1) {
    asm volatile("mma.sync.aligned.m16n8k16.row.col.f32.bf16.bf16.f32 {%0,%1,%2,%3}, {%4,%5,%6,%7}, {%8,%9}, {%0,%1,%2,%3};"
        : "+f"(d[0]), "+f"(d[1]), "+f"(d[2]), "+f"(d[3]) : "r"(a0), "r"(a1), "r"(a2), "r"(a3), "r"(b0), "r"(b1));
}
__device__ __forceinline__ void mma_bf16_k8(float (&d)[4], uint32_t a0, uint32_t a1, uint32_t b0) {
    asm volatile("mma.sync.aligned.m16n8k8.row.col.f32.bf16.bf16.f32 {%0,%1,%2,%3}, {%4,%5}, {%6}, {%0,%1,%2,%3};"
        : "+f"(d[0]), "+f"(d[1]), "+f"(d[2]), "+f"(d[3]) : "r"(a0), "r"(a1), "r"(b0));
}
__device__ __forceinline__ uint32_t pack_f16(float lo, float hi) { uint32_t r; asm("cvt.rn.f16x2.f32 %0, %1, %2;" : "=r"(r) : "f"(hi), "f"(lo)); return r; }
__device__ __forceinline__ uint32_t pack_bf16(float lo, float hi) { uint32_t r; asm("cvt.rn.bf16x2.f32 %0, %1, %2;" : "=r"(r) : "f"(hi), "f"(lo)); return r; }
__device__ __forceinline__ float bf_lo(uint32_t v) { return __uint_as_float(v << 16); }
__device__ __forceinline__ float bf_hi(uint32_t v) { return __uint_as_float(v & 0xFFFF0000u); }
__device__ __forceinline__ float bfr(float x) { return __uint_as_float(pack_bf16(0.f, x)); }
__device__ __forceinline__ uint32_t badd2(uint32_t a, uint32_t b) { uint32_t r; asm("add.rn.bf16x2 %0, %1, %2;" : "=r"(r) : "r"(a), "r"(b)); return r; }
__device__ __forceinline__ uint32_t bmul2(uint32_t a, uint32_t b) { uint32_t r; asm("mul.rn.bf16x2 %0, %1, %2;" : "=r"(r) : "r"(a), "r"(b)); return r; }
__device__ __forceinline__ uint32_t hadd2(uint32_t a, uint32_t b) { uint32_t r; asm("add.rn.f16x2 %0, %1, %2;" : "=r"(r) : "r"(a), "r"(b)); return r; }
__device__ __forceinline__ uint32_t hmul2(uint32_t a, uint32_t b) { uint32_t r; asm("mul.rn.f16x2 %0, %1, %2;" : "=r"(r) : "r"(a), "r"(b)); return r; }
__device__ __forceinline__ uint32_t hfma2(uint32_t a, uint32_t b, uint32_t c) { uint32_t r; asm("fma.rn.f16x2 %0, %1, %2, %3;" : "=r"(r) : "r"(a), "r"(b), "r"(c)); return r; }
__device__ __forceinline__ uint32_t hneg2(uint32_t a) { uint32_t r; asm("neg.f16x2 %0, %1;" : "=r"(r) : "r"(a)); return r; }
__device__ __forceinline__ float rcpf(float x) { float r; asm("rcp.approx.ftz.f32 %0, %1;" : "=f"(r) : "f"(x)); return r; }
__device__ __forceinline__ float sqrta(float x) { float r; asm("sqrt.approx.ftz.f32 %0, %1;" : "=f"(r) : "f"(x)); return r; }
__device__ __forceinline__ float ex2f(float x) { float r; asm("ex2.approx.ftz.f32 %0, %1;" : "=f"(r) : "f"(x)); return r; }
__device__ __forceinline__ void st_async4(uint32_t a, uint32_t x, uint32_t y, uint32_t z, uint32_t w, uint32_t mb) {
    asm volatile("st.async.shared::cluster.mbarrier::complete_tx::bytes.v4.u32 [%0], {%1,%2,%3,%4}, [%5];" :: "r"(a), "r"(x), "r"(y), "r"(z), "r"(w), "r"(mb) : "memory"); }
__device__ __forceinline__ void st_async1(uint32_t a, uint32_t x, uint32_t mb) {
    asm volatile("st.async.shared::cluster.mbarrier::complete_tx::bytes.u32 [%0], %1, [%2];" :: "r"(a), "r"(x), "r"(mb) : "memory"); }
__device__ __forceinline__ unsigned ld_rlx(const void* p) { unsigned v; asm volatile("ld.relaxed.gpu.global.u32 %0, [%1];" : "=r"(v) : "l"(p) : "memory"); return v; }
__device__ __forceinline__ unsigned ld_acq(const void* p) { unsigned v; asm volatile("ld.acquire.gpu.global.u32 %0, [%1];" : "=r"(v) : "l"(p) : "memory"); return v; }
__device__ __forceinline__ uint2 ld_rlx64(const void* p) { unsigned long long v; asm volatile("ld.relaxed.gpu.global.u64 %0, [%1];" : "=l"(v) : "l"(p) : "memory"); return make_uint2((unsigned)v, (unsigned)(v >> 32)); }
__device__ __forceinline__ void st_rlx128(void* p, uint32_t x, uint32_t y, uint32_t z, uint32_t w) {
    asm volatile("st.relaxed.gpu.global.v2.u64 [%0], {%1,%2};" :: "l"(p), "l"((unsigned long long)x | ((unsigned long long)y << 32)), "l"((unsigned long long)z | ((unsigned long long)w << 32)) : "memory"); }
__device__ __forceinline__ uint4 ld_rlx128(const void* p) { unsigned long long a, b; asm volatile("ld.relaxed.gpu.global.v2.u64 {%0,%1}, [%2];" : "=l"(a), "=l"(b) : "l"(p) : "memory"); return make_uint4((unsigned)a, (unsigned)(a >> 32), (unsigned)b, (unsigned)(b >> 32)); }
__device__ __forceinline__ void tma2d(uint32_t dst, const CUtensorMap* tm, int x, int y, uint32_t mb) {
    asm volatile("cp.async.bulk.tensor.2d.shared::cluster.global.mbarrier::complete_tx::bytes [%0], [%1, {%3, %4}], [%2];"
                 :: "r"(dst), "l"(tm), "r"(mb), "r"(x), "r"(y) : "memory");
}
__device__ __forceinline__ void cmul(float& xr, float& xi, float ar, float ai, float br, float bi) {
    const float r = fmaf(ar, br, -ai * bi), i = fmaf(ar, bi, ai * br); xr = r; xi = i;
}
__device__ __forceinline__ void csq(float& xr, float& xi, float ar, float ai) {
    const float r = fmaf(ar, ar, -ai * ai), i = (ar + ar) * ai; xr = r; xi = i;
}
__device__ __forceinline__ void cexp_s(float& zr, float& zi, float e2, float turns) {
    const float mag = ex2f(e2), r = (turns - rintf(turns)) * 6.283185307179586f;
    zr = mag * __cosf(r); zi = mag * __sinf(r);
}
__device__ __forceinline__ uint32_t ln_stats(float s1, float s2) {
    const float m = s1 * (1.f / D_);
    const float var = fmaxf(fmaf(s2, 1.f / D_, -m * m), 0.f);
    return pack_bf16(m, sqrta(bfr(bfr(var) + 1e-5f)));
}
__device__ __forceinline__ uint32_t rsplit(float rs) { const float h = bfr(rs); return pack_bf16(h, rs - h); }
__device__ __forceinline__ uint32_t norm2(uint32_t v, uint32_t mx, uint32_t hl) {
    uint32_t r;
    asm("{ .reg .b16 m, h, l, x; .reg .b32 m2, h2, l2, d, t; mov.b32 {m, x}, %2; mov.b32 {h, l}, %3; mov.b32 m2, {m, m}; mov.b32 h2, {h, h}; mov.b32 l2, {l, l};\n"
        "sub.rn.bf16x2 d, %1, m2; mul.rn.bf16x2 t, d, l2; fma.rn.bf16x2 %0, d, h2, t; }" : "=r"(r) : "r"(v), "r"(mx), "r"(hl));
    return r;
}
template <int N, int S>
__device__ __forceinline__ uint32_t rank4(uint32_t a, uint32_t key) {
    uint32_t r0 = 0, r1 = 0, r2 = 0, r3 = 0;
#pragma unroll
    for (int i = 0; i < N; i++) {
        const uint4 o = lds128(a + i * S);
        r0 += (key - o.x) >> 31; r1 += (key - o.y) >> 31; r2 += (key - o.z) >> 31; r3 += (key - o.w) >> 31;
    }
    return (r0 + r1) + (r2 + r3);
}
typedef uint32_t H2C;
__device__ __forceinline__ H2C splat(float r, float i) { return pack_f16(r, i); }
__device__ __forceinline__ void hcmul(uint32_t& xr, uint32_t& xi, uint32_t R, uint32_t I, H2C m) {
    asm("{ .reg .b16 a, b; .reg .b32 a2, b2, t; mov.b32 {a, b}, %4; mov.b32 a2, {a, a}; mov.b32 b2, {b, b};\n"
        "mul.rn.f16x2 t, %3, b2; neg.f16x2 t, t; fma.rn.f16x2 %0, %2, a2, t; mul.rn.f16x2 t, %3, a2; fma.rn.f16x2 %1, %2, b2, t; }"
        : "=&r"(xr), "=r"(xi) : "r"(R), "r"(I), "r"(m));
}
__device__ __forceinline__ void expand4(uint32_t are, uint32_t aim, uint32_t R0, uint32_t R1, uint32_t I0, uint32_t I1, H2C m4) {
    uint32_t R2, I2, R3, I3;
    hcmul(R2, I2, R0, I0, m4); hcmul(R3, I3, R1, I1, m4);
    sts128(are, R0, R1, R2, R3);
    sts128(aim, I0, I1, I2, I3);
}
__device__ __forceinline__ void expand8(uint32_t are, uint32_t aim, float sr, float si, float m1r, float m1i, float m2r, float m2i, H2C m4) {
    float r1, i1, r2, i2, r3, i3;
    cmul(r1, i1, sr, si, m1r, m1i); cmul(r2, i2, sr, si, m2r, m2i); cmul(r3, i3, r1, i1, m2r, m2i);
    expand4(are, aim, pack_f16(sr, r1), pack_f16(r2, r3), pack_f16(si, i1), pack_f16(i2, i3), m4);
}
__device__ __forceinline__ void put16(uint32_t a, uint32_t v) { sts16(a, v); sts16(a + 6, v); }

struct Params {
    const unsigned short *logdt, *dskip, *prm6[6], *x, *wr;
    __nv_bfloat16* out;
    Scratch* gs;
    unsigned zero;
};
__device__ __forceinline__ uint32_t tslot(uint32_t t) { return (t & 7) * 32 + ((t >> 4) & 24) + ((t >> 8) & 6) + ((t >> 6) & 1); }
#define CP(x) ((x) | zero)
#define PIN(x) asm volatile("or.b32 %0, %0, %1;" : "+r"(x) : "r"(zero))
__device__ __forceinline__ void wgmma32(float (&d)[4][4], const uint32_t (&a)[4], uint32_t dlo) {
    asm volatile("{ .reg .b64 ds; mov.b64 ds, {%20, %21};\n"
                 "wgmma.mma_async.sync.aligned.m64n32k16.f32.f16.f16 {%0,%1,%2,%3,%4,%5,%6,%7,%8,%9,%10,%11,%12,%13,%14,%15}, {%16,%17,%18,%19}, ds, 1, 1, 1, 0; }"
        : "+f"(d[0][0]), "+f"(d[0][1]), "+f"(d[0][2]), "+f"(d[0][3]), "+f"(d[1][0]), "+f"(d[1][1]), "+f"(d[1][2]), "+f"(d[1][3]),
          "+f"(d[2][0]), "+f"(d[2][1]), "+f"(d[2][2]), "+f"(d[2][3]), "+f"(d[3][0]), "+f"(d[3][1]), "+f"(d[3][2]), "+f"(d[3][3])
        : "r"(a[0]), "r"(a[1]), "r"(a[2]), "r"(a[3]), "r"(dlo), "n"(128 >> 4));
}

__global__ void __cluster_dims__(CS, 1, 1) __launch_bounds__(NTHR, 1)
fused_kernel(const __grid_constant__ Params prm, const __grid_constant__ CUtensorMap tmG, const __grid_constant__ CUtensorMap tmU,
             const __grid_constant__ CUtensorMap tmD, const __grid_constant__ CUtensorMap tmO, const __grid_constant__ CUtensorMap tmX, const __grid_constant__ CUtensorMap tmH)
{
    extern __shared__ __align__(1024) unsigned char smem[];
    const int tid = threadIdx.x, lane = tid & 31, warp = __shfl_sync(~0u, tid >> 5, 0);
    const int c = blockIdx.x >> 3, q = blockIdx.x & 7;
    const int nslot = (c < NCL - 1) ? 5 : 2;
    const int d0 = 40 * c;
    const uint32_t sb = opaque((uint32_t)__cvta_generic_to_shared(smem));
    const uint32_t mb = sb + SM_MB;
    Scratch& g_s = *prm.gs;
    const unsigned& zero = prm.zero;
    STAMP(0);

    if (warp >= 20) {
        unsigned epoch = 0;
        if (warp == 20) {
            if (lane == 0) {
#pragma unroll
                for (int i = 0; i < 13; i++)
                    asm volatile("mbarrier.init.shared::cta.b64 [%0], %1;" :: "r"(mb + i * 8), "r"((i == MB_R || i < 5) ? 2 : i == MB_Y ? 1 + 4 * nslot : 1) : "memory");
                asm volatile("fence.mbarrier_init.release.cluster;" ::: "memory");
                arm(mb + MB_W1 * 8, 92160); arm(mb + MB_W2 * 8, nslot * (128 * W2W)); arm(mb + MB_KEY * 8, 256); arm(mb + MB_GU * 8, nslot * 1024); arm(mb + MB_T * 8, 576 * XW);
                const int bytes = max(min(18, L_ - 18 * (int)blockIdx.x), 1) * (D_ * 2);
                arm(mb + MB_R * 8, bytes);
            }
            __syncwarp();
        } else if (warp == 22) {
            epoch = ld_rlx(&g_s.epoch);
            if (lane < 18 ? 18 * c + lane < 256 : lane < 31) (lane < 18 ? &g_s.acc[256 * q + 18 * c] : &g_s.fin[13 * (int)blockIdx.x - 18])[lane] = make_float4(0.f, 0.f, 0.f, 0.f);
        } else if (warp == 23 && lane == 0) asm volatile("prefetch.tensormap [%0];" :: "l"(&tmX) : "memory");
        asm volatile("barrier.cluster.arrive.relaxed.aligned;" ::: "memory");
        bar_sync(12, NTHR);
        uint4 wv = make_uint4(0, 0, 0, 0), wv2, wv3;
        if (warp == 22) {
            if (lane == 0) { sts32(sb + SM_SC + 28, epoch); asm volatile("mbarrier.arrive.shared::cta.b64 _, [%0];" :: "r"(mb + MB_R * 8) : "memory"); }
            epoch++;
            asm volatile("fence.acq_rel.gpu;" ::: "memory");
            __syncwarp();
            if (lane == 0) asm volatile("red.relaxed.gpu.global.add.u32 [%0], 1;" :: "l"(&g_s.zcnt) : "memory");
            STAMP(1);
            wv2 = ldg128((const uint4*)prm.wr + lane); wv3 = ldg128((const uint4*)prm.wr + 32 + lane);
            if (lane < 8) wv = ldg128((const uint4*)prm.wr + 64 + lane);
            if (lane < 5) {
                uint4 v = make_uint4(0, 0, 0, 0);
                if (lane < nslot) v = ldg128((const uint4*)(prm.wr + d0) + lane);
                sts128(sb + SM_DW + lane * 16, v.x, v.y, v.z, v.w);
            }
            __syncwarp();
            if (lane < 5) asm volatile("mbarrier.arrive.shared::cta.b64 _, [%0];" :: "r"(mb + (MB_X + lane) * 8) : "memory");
        }
        if (warp == 21) {
            if (lane == 0) { asm volatile("prefetch.tensormap [%0];" :: "l"(&tmG) : "memory"); asm volatile("prefetch.tensormap [%0];" :: "l"(&tmU) : "memory"); asm volatile("prefetch.tensormap [%0];" :: "l"(&tmD) : "memory"); }
            __syncwarp();
            bar_sync(13, 768);
            asm volatile("fence.proxy.async.shared::cta;" ::: "memory");
#pragma unroll 1
            for (int i = 0; i < 24; i++) {
                if (lane == 0) tma2d(sb + SM_WG + i * 3840, i < 12 ? &tmG : &tmU, 320 * c + 8 * nslot * q, 48 * (i < 12 ? i : i - 12), mb + MB_W1 * 8);
            }
            STAMP(1);
            return;
        }
        if (warp == 20) {
            if (lane == 0) {
                asm volatile("cp.async.bulk.shared::cluster.global.mbarrier::complete_tx::bytes [%0], [%1], %2, [%3];"
                             :: "r"(sb + SM_ROW), "l"(prm.x + min(18 * (int)blockIdx.x, L_ - 1) * D_), "r"(max(min(18, L_ - 18 * (int)blockIdx.x), 1) * (D_ * 2)), "r"(mb + MB_R * 8) : "memory");
            }
            __syncwarp();
            if (TILE_NS < 0) mbar_wait(mb + MB_R * 8); else if (TILE_NS) __nanosleep(TILE_NS);
            if (lane == 0) {
                asm volatile("cp.async.bulk.tensor.5d.shared::cluster.global.mbarrier::complete_tx::bytes [%0], [%1, {%3, %4, %5, %5, %5}], [%2];"
                             :: "r"(sb + SM_XTL), "l"(&tmX), "r"(mb + MB_T * 8), "r"(XW == 40 ? d0 : d0 & ~15), "r"(8 * q), "r"(0) : "memory");
            }
            STAMP(6);
        }
        asm volatile("barrier.cluster.wait.aligned;" ::: "memory");
        bar_sync(13, 768);
        asm volatile("fence.proxy.async.shared::cta;" ::: "memory");
        {
            const int idx = lane * 3 + max(warp - 21, 0), sl = nslot - 1 - (idx >> 3), pe = (idx + q + 1) & 7;
            if (sl >= 0) {
                if (pe == q) arm(mb + (MB_X + sl) * 8, 7 * 512);
                else {
                    const uint32_t rb_ = mapa(sb, pe);
                    asm volatile("cp.async.bulk.shared::cluster.shared::cta.mbarrier::complete_tx::bytes [%0], [%1], 512, [%2];"
                                 :: "r"(rb_ + SM_U + 128 + q * UP + sl * US), "r"(sb + SM_XT + 128 + (q & 3) * 16 + pe * YP + sl * YS), "r"(rb_ + SM_MB + (MB_X + sl) * 8) : "memory");
                }
            }
        }
        STAMP(1);
        if (warp == 20 && lane == 0) { asm volatile("prefetch.tensormap [%0];" :: "l"(&tmO) : "memory"); asm volatile("prefetch.tensormap [%0];" :: "l"(&tmH) : "memory"); }
        if (warp == 22) {
            __syncwarp();
            mbar_wait(mb + (MB_X + 1) * 8);
            const uint32_t old = (epoch & 1) ? 0u : 0x40004000u;
#pragma unroll
            for (int t = 0; t < 2; t++)
                if ((lane & 7) < 6) g_s.cand[((q * 8 + 4 * t + (lane >> 3)) * NCL + c) * 6 + (lane & 7)] = make_uint4(old, old, old, old);
            float a[4] = {0.f, 0.f, 0.f, 0.f};
            const uint32_t one = 0x3F803F80u;
            mma_bf16(a, one, one, one, one, wv.x, wv.y);  mma_bf16(a, one, one, one, one, wv.z, wv.w);
            mma_bf16(a, one, one, one, one, wv2.x, wv2.y); mma_bf16(a, one, one, one, one, wv2.z, wv2.w);
            mma_bf16(a, one, one, one, one, wv3.x, wv3.y); mma_bf16(a, one, one, one, one, wv3.z, wv3.w);
            float s = a[0] + a[1];
            s += __shfl_xor_sync(~0u, s, 1); s += __shfl_xor_sync(~0u, s, 2);
            stsf(sb + SM_SC + 24, s);
            __syncwarp();
            if (lane == 0) {
                int n = 0;
                while ((int)(ld_acq(&g_s.zcnt) - epoch * NCTA) < 0 && ++n < SPIN_LIMIT) __nanosleep(200);
                arm(mb + MB_Y * 8, 8 * 512 * nslot);
                if (blockIdx.x == 0) g_s.epoch = epoch;
            }
            STAMP(2);
            return;
        }
        if (warp == 23) {
#pragma unroll 1
            for (int kk = nslot - 1; kk >= 0; kk--) {
                __syncwarp();
                bar_sync(6 + kk, 160);
                if (lane == 0) { asm volatile("fence.proxy.async.shared::cta;" ::: "memory"); tma2d(sb + SM_FAR + kk * FAR_SZ, &tmD, W2W == 72 ? 72 * q : (72 * q) & ~15, 320 * c + 64 * kk, mb + MB_W2 * 8); }
            }
            return;
        }
        __syncwarp();
        bar_sync(14, 672);
        if (lane == 0) {
            asm volatile("fence.proxy.async.shared::cta;" ::: "memory");
            asm volatile("cp.async.bulk.tensor.5d.global.shared::cta.bulk_group [%0, {%2, %4, %4, %4, %3}], [%1];" :: "l"(&tmH), "r"(sb + SM_XT + 16384), "r"(d0 + ((c & 1) ? 0 : 32)), "r"(8 * q), "r"(0) : "memory");
            asm volatile("cp.async.bulk.tensor.5d.global.shared::cta.bulk_group [%0, {%2, %4, %4, %4, %3}], [%1];" :: "l"(&tmO), "r"(sb + SM_XT), "r"(d0 + (c & 1) * 8), "r"(8 * q), "r"(0) : "memory");
            asm volatile("cp.async.bulk.commit_group;" ::: "memory");
            asm volatile("cp.async.bulk.wait_group 0;" ::: "memory");
            asm volatile("fence.proxy.async.global;" ::: "memory");
            asm volatile("mbarrier.arrive.shared::cta.b64 _, [%0];" :: "r"(mb + MB_OUT * 8) : "memory");
        }
        STAMP(2);
        return;
    }

    const int g = lane >> 2, cq = lane & 3;
    const int k = warp >> 2, wq = warp & 3;
    const int trow = 18 * blockIdx.x + warp;
    const bool rowact = warp < 18 && trow < L_;
    const int dch = min(d0 + 8 * k + q, D_ - 1);
    uint32_t pv[6];
#pragma unroll
    for (int i = 0; i < 6; i++) pv[i] = ldg16(prm.prm6[i] + (uint32_t)(dch * 128 + wq * 32 + lane));
    const uint32_t pLdt = ldg16(prm.logdt + dch), pD = ldg16(prm.dskip + dch);
    const int tn = 16 * (warp & 15) + g;
    uint32_t xa[5], xb[5];
    asm volatile("barrier.cluster.arrive.relaxed.aligned;" ::: "memory");
    uint4* const st1p = &g_s.st1[(((trow >> 3) & 7) * 256 + ((trow >> 6) & 31) * 8 + (trow & 7)) * 2 + (lane >> 2)];
    const bool pub = rowact && (lane & 0x1B) == 0;
    if (pub) st_rlx128(st1p, 0, 0, 0, 0);
    {
        const uint32_t za = sb + SM_P + tid * 16;
        sts128(za, 0, 0, 0, 0);
        if (tid < (SM_MISC - SM_P) / 16 - 640) sts128(za + 10240, 0, 0, 0, 0);
        sts128(sb + ((wq & 2) ? SM_U : SM_XT + (q & 3) * 16) + ((tid >> 3) & 7) * ((wq & 2) ? UP : YP) + k * YS + (lane & 7) * 16, 0, 0, 0, 0);
    }
    bar_sync(12, NTHR);
    const uint32_t dep = lds32(sb + SM_P);
#define PV(x) __uint_as_float(__byte_perm(dep, x, 0x5410))
    STAMP(1);
    const uint32_t fb = sb + SM_FAR + k * FAR_SZ;
    const uint32_t pn = sb + SM_PN + k * PN_SZ, pf = sb + SM_PF + k * PF_SZ;
    unsigned epoch;
    {
        const uint32_t kb = fb + wq * 3072;
        const uint32_t kl = kb + lane * 16;
        uint32_t Af[4][4];
        float sr, si, z1r, z1i, z2r, z2i, z4r, z4i, hr, hi_;
        {
            const float dt = bfr(ex2f(PV(pLdt) * 1.4426950408889634f));
            const float e2 = dt * PV(pv[0]) * 1.4426950408889634f, an = dt * PV(pv[1]);
            cmul(sr, si, PV(pv[4]), PV(pv[5]), dt * PV(pv[2]), dt * PV(pv[3]));
            const unsigned E = min(max(__reduce_max_sync(~0u, __float_as_uint(fmaxf(fmaxf(fabsf(sr), fabsf(si)), fabsf(PV(pD)) * (1.f / 8192.f)))) >> 23, 1u), 253u);
            const float sc = __uint_as_float((254u - E) << 23);
            sr *= sc; si *= -sc;
            sts64(sb + SM_KG + warp * 8, E, __reduce_add_sync(~0u, __float2int_rn(sr * 16777216.f)));
            float ar, ai, br, bi, cr, ci, dr, di;
            { const float m = ex2f(e2 * 8.f); ar = m * __cosf(an * 8.f); ai = m * __sinf(an * 8.f); }
            csq(br, bi, ar, ai); csq(cr, ci, br, bi); csq(dr, di, cr, ci);
            const H2C m4 = splat(cr, ci);
            {
                float r3, i3;
                cmul(r3, i3, ar, ai, br, bi);
                expand4(kl, kl + 1024, pack_f16(1.f, ar), pack_f16(br, r3), pack_f16(0.f, ai), pack_f16(bi, i3), m4);
            }
            expand8(kl + 512, kl + 1536, dr, di, ar, ai, br, bi, m4);
            { const float m = ex2f(e2); z1r = m * __cosf(an); z1i = -m * __sinf(an); }
            cexp_s(hr, hi_, e2 * 128.f, an * (-128.f * 0.15915494309189535f));
            csq(z2r, z2i, z1r, z1i); csq(z4r, z4i, z2r, z2i);
        }
        __syncwarp();
#pragma unroll
        for (int ks = 0; ks < 4; ks++) ldsm4t(Af[ks], kb + (lane >> 3) * 512 + (lane & 7) * 16 + ks * 128);
        STAMP(2);
        const uint32_t la = kb + ((lane >> 3) & 1) * 512 + (lane >> 4) * 128 + (lane & 7) * 16;
        uint32_t kp[5][2], b0[4], b1[4], b2[4], b3[4];
        auto mm2 = [&](int t) {
            float a0[4] = {0.f, 0.f, 0.f, 0.f}, a1[4] = {0.f, 0.f, 0.f, 0.f};
            mma_f16(a0, Af[0], b0[0], b0[1]); mma_f16(a1, Af[0], b2[0], b2[1]); mma_f16(a0, Af[1], b0[2], b0[3]); mma_f16(a1, Af[1], b2[2], b2[3]);
            mma_f16(a0, Af[2], b1[0], b1[1]); mma_f16(a1, Af[2], b3[0], b3[1]); mma_f16(a0, Af[3], b1[2], b1[3]); mma_f16(a1, Af[3], b3[2], b3[3]);
            kp[t][0] = pack_f16(a0[1], a0[0]); kp[t][1] = pack_f16(a0[3], a0[2]); kp[t + 1][0] = pack_f16(a1[1], a1[0]); kp[t + 1][1] = pack_f16(a1[3], a1[2]);
        };
        auto ln1 = [&]() {
        mbar_wait(mb + MB_R * 8);
        epoch = lds32(sb + SM_SC + 28) + 1;
        {
            const uint32_t ra = sb + SM_ROW + warp * (D_ * 2);
            const uint4 r0 = lds128(ra + lane * 16), r1 = lds128(ra + 512 + lane * 16);
            const uint32_t rx[9] = {r0.x, r0.y, r0.z, r0.w, r1.x, r1.y, r1.z, r1.w, lds32(ra + 1024 + lane * 4)};
            float a0 = bf_lo(rx[0]), a1 = bf_hi(rx[0]), c0 = a0 * a0, c1 = a1 * a1;
#pragma unroll
            for (int i = 1; i < 9; i++) { const float l = bf_lo(rx[i]), h = bf_hi(rx[i]); a0 += l; a1 += h; c0 = fmaf(l, l, c0); c1 = fmaf(h, h, c1); }
            a0 += a1; c0 += c1;
            float s1 = ((lane & 1) ? c0 : a0) + __shfl_xor_sync(~0u, (lane & 1) ? a0 : c0, 1);
#pragma unroll
            for (int o = 2; o < 32; o <<= 1) s1 += __shfl_xor_sync(~0u, s1, o);
            const float s2 = __shfl_xor_sync(~0u, s1, 1);
            const uint32_t ms = ln_stats(s1, s2);
            const uint32_t p0 = __byte_perm(ms, epoch | 0x8000u, 0x5410), p1 = rsplit(rcpf(bf_hi(ms)));
            if (pub) st_rlx128(st1p, p0, p1, p0, p1);
        }
        mbar_wait(mb + MB_R * 8);
        STAMP(1);
        };
        const uint4* sp = &g_s.st1[(256 * q + tn) * 2];
        uint2 sa, sc;
        auto poll = [&]() { sa = ld_rlx64(sp); sc = ld_rlx64(sp + 16); };
        auto norm = [&]() {
        STAMP(3);
        if (warp < 16) {
            uint32_t va[5], vc[5];
            poll();
            mbar_wait(mb + MB_T * 8);
            {
                const uint32_t xt = sb + SM_XTL + (XW == 40 ? 0 : (c & 1) * 16) + (72 * wq + 18 * k + g) * (2 * XW);
                uint4 a4 = lds128(xt + cq * 16), b4 = lds128(xt + cq * 16 + 18 * XW);
                va[0] = a4.x; va[1] = a4.y; va[2] = a4.z; va[3] = a4.w; va[4] = lds32(xt + 64 + cq * 4);
                vc[0] = b4.x; vc[1] = b4.y; vc[2] = b4.z; vc[3] = b4.w; vc[4] = lds32(xt + (64 + 18 * XW) + cq * 4);
            }
            const int d4 = 2 * (lane >> 3) + (lane & 1), d1_ = lane & 7;
            const uint32_t own = SM_U + 128 + q * (UP - YP), oth = SM_XT + 128 + (q & 3) * 16;
            uint32_t a4 = sb + warp * 32 + d4 * YP + (d4 == q ? own : oth) + ((lane & 7) >> 1) * YS;
            uint32_t a1 = sb + warp * 32 + d1_ * YP + (d1_ == q ? own : oth) + 4 * YS + (lane & 8) * 2;
            PIN(a4); PIN(a1);
            uint32_t tag = __byte_perm(epoch | 0x8000u, 0, 0x1010);
            PIN(tag);
            mbar_wait(mb + MB_T * 8);
            int n = 0;
            while (__byte_perm(sa.x, sc.x, 0x7632) != tag && ++n < SPIN_LIMIT) poll();
            STAMP(4);
#pragma unroll
            for (int i = 0; i < 5; i++) {
                va[i] = norm2(va[i], sa.x, sa.y); va[i] = pack_f16(bf_lo(va[i]), bf_hi(va[i]));
                vc[i] = norm2(vc[i], sc.x, sc.y); vc[i] = pack_f16(bf_lo(vc[i]), bf_hi(vc[i]));
            }
            stsm4t(a4, va[0], va[1], va[2], va[3]); stsm4t(a4 + 16, vc[0], vc[1], vc[2], vc[3]); stsm2t(a1, va[4], vc[4]);
            {
            const uint32_t xh = sb + SM_XTL + (XW == 40 ? 0 : (c & 1) * 16) + (9 * g + 144 * (warp & 1) + (warp >> 1)) * (2 * XW);
            const uint4 c4 = lds128(xh + cq * 16), d4_ = lds128(xh + cq * 16 + 144 * XW);
            xa[0] = c4.x; xa[1] = c4.y; xa[2] = c4.z; xa[3] = c4.w; xa[4] = lds32(xh + 64 + cq * 4);
            xb[0] = d4_.x; xb[1] = d4_.y; xb[2] = d4_.z; xb[3] = d4_.w; xb[4] = lds32(xh + (64 + 144 * XW) + cq * 4);
            }
        }
        STAMP(5);
        bar_sync(13, 768);
        Af[0][0] |= lds32(sb + SM_P);
        };
        if (LNPOS == 0) ln1();
        cmul(sr, si, sr, si, z1r, z1i);
        {
            const H2C h4 = splat(z4r, z4i);
            expand8(kl, kl + 512, sr, si, z1r, z1i, z2r, z2i, h4);
            cmul(sr, si, sr, si, hr, hi_);
            expand8(kl + 1024, kl + 1536, sr, si, z1r, z1i, z2r, z2i, h4);
        }
        __syncwarp();
        ldsm4t(b0, la); ldsm4t(b1, la + 256); ldsm4t(b2, la + 1024); ldsm4t(b3, la + 1280);
        cmul(z1r, z1i, z1r, z1i, hr, hi_);
        cmul(sr, si, sr, si, z1r, z1i);
        if (LNPOS == 1) ln1();
        expand8(kl, kl + 512, sr, si, z2r, z2i, z4r, z4i, splat(hr, hi_));
        if (LNPOS == 2) ln1();
        csq(z1r, z1i, z1r, z1i);
        cmul(sr, si, sr, si, z1r, z1i);
        csq(z2r, z2i, hr, hi_);
        expand8(kl + 1024, kl + 1536, sr, si, z4r, z4i, hr, hi_, splat(z2r, z2i));
        if (LNPOS == 3) ln1();
        csq(z1r, z1i, z1r, z1i);
        cmul(sr, si, sr, si, z1r, z1i);
        csq(z4r, z4i, z2r, z2i);
        expand8(kl + 2048, kl + 2560, sr, si, hr, hi_, z2r, z2i, splat(z4r, z4i));
        if (LNPOS == 4) ln1();
        if (MMPOS == 0) norm();
        mm2(0);
        __syncwarp();
        ldsm4t(b0, la); ldsm4t(b1, la + 256); ldsm4t(b2, la + 1024); ldsm4t(b3, la + 1280);
        if (MMPOS == 1) norm();
        mm2(2);
        if (MMPOS == 2) norm();
        ldsm4t(b0, la + 2048); ldsm4t(b1, la + 2304);
#pragma unroll
        for (int t = 0; t < 4; t++) sts64(kb + lane * 8 + 1024 + t * 256, kp[t][0], kp[t][1]);
        {
            float a0[4] = {0.f, 0.f, 0.f, 0.f}, a1[4] = {0.f, 0.f, 0.f, 0.f};
            mma_f16(a0, Af[0], b0[0], b0[1]); mma_f16(a1, Af[1], b0[2], b0[3]); mma_f16(a0, Af[2], b1[0], b1[1]); mma_f16(a1, Af[3], b1[2], b1[3]);
            sts64(kb + lane * 8 + 2048, pack_f16(a0[1] + a1[1], a0[0] + a1[0]), pack_f16(a0[3] + a1[3], a0[2] + a1[2]));
        }
        bar_sync(1 + k, 128);
        const uint4 m01 = lds128(sb + SM_KG + k * 32), m23 = lds128(sb + SM_KG + k * 32 + 16);
        const unsigned Em = max(max(m01.x, m01.z), max(m23.x, m23.z));
        const float f0 = __uint_as_float(max((int)(127 + m01.x - Em), 0) << 23), f1 = __uint_as_float(max((int)(127 + m01.z - Em), 0) << 23),
                    f2 = __uint_as_float(max((int)(127 + m23.x - Em), 0) << 23), f3 = __uint_as_float(max((int)(127 + m23.z - Em), 0) << 23);
        const uint32_t r0 = pack_f16(f0, f0), r1 = pack_f16(f1, f1), r2 = pack_f16(f2, f2), r3 = pack_f16(f3, f3);
        const int tq = (wq + ROTK * k) & 3;
        const uint32_t ra = fb + lane * 8 + tq * 256 + 1024;
        const uint2 p0 = lds64(ra), p1 = lds64(ra + 3072), p2 = lds64(ra + 6144), p3 = lds64(ra + 9216);
        uint32_t w0 = hadd2(hfma2(p0.x, r0, hmul2(p1.x, r1)), hfma2(p2.x, r2, hmul2(p3.x, r3)));
        uint32_t w1 = hadd2(hfma2(p0.y, r0, hmul2(p1.y, r1)), hfma2(p2.y, r2, hmul2(p3.y, r3)));
        const bool last = lane == 31;
        if (tq < 2) {
            const uint32_t rc = fb + lane * 8 + tq * 4 + 2048;
            const uint32_t w4 = hmul2(hadd2(hfma2(lds32(rc), r0, hmul2(lds32(rc + 3072), r1)), hfma2(lds32(rc + 6144), r2, hmul2(lds32(rc + 9216), r3))), 0x18001800u);
            const uint32_t ph = pf + (P_H7 + 16 * tq) + (g & 1) * (2 * P_HS) + cq * 64 + (g >> 1) * 4;
            put16(ph, w4 >> 16); put16(ph + 32, w4);
            const uint32_t pa = pn + (4 + 512 * tq) + lane * 8;
            sts16(pa, w0 >> 16); sts32(pa + 4, w0); sts16(pa + 10, w0);
            sts16(pa + 256, w1 >> 16); sts32(pa + 260, w1); sts16(pa + 266, w1);
            if (last) {
                sts32(sb + SM_SC + k * 4, Em * 0x00800080u);
                put16(tq ? pa + 264 : pn,
                      tq ? w1 : pack_f16(((float)(int)m01.y * f0 + (float)(int)m01.w * f1 + (float)(int)m23.y * f2 + (float)(int)m23.w * f3) * (1.f / 16777216.f)
                                         + __uint_as_float(pD << 16) * __uint_as_float((254u - Em) << 23), 0.f));
            }
        } else if (tq == 2) {
            const uint32_t pa = pn + 258 * 4 + (cq & 1) * 16 + (cq >> 1) * 512 + g * 32;
            if (last) { put16(pf, hmul2(w1, 0x18001800u)); w1 = hadd2(w1, hneg2(__byte_perm(w1, 0, 0x1010))); }
            const uint32_t b0 = __byte_perm(w0, 0, 0x1010), b1 = __byte_perm(w1, 0, 0x1010);
            sts16(pa, w0 >> 16); sts32(pa + 4, w0); sts64(pa + 8, b0, b0); sts16(pa + 18, w0);
            sts16(pa + 256, w1 >> 16); sts32(pa + 260, w1); sts64(pa + 264, b1, b1); sts16(pa + 274, w1);
        } else {
            const uint32_t pa = pf + ((g & 1) ? 3 * P_GS : P_GS) + cq * 32 + (g >> 1) * 4;
            const uint32_t pb = pa + ((g & 1) ? 4 - 3 * P_GS : P_GS);
            w0 = hmul2(w0, 0x18001800u); w1 = hmul2(w1, 0x18001800u);
            put16(pa, w0 >> 16); put16(pb, w0); put16(pa + 16, w1 >> 16); put16(pb + 16, w1);
            if (last) put16(pf + P_H7 + P_HS, w1);
        }
        bar_sync(1 + k, 128);
    }
    STAMP(6);

    asm volatile("barrier.cluster.wait.aligned;" ::: "memory");
    mbar_wait(mb + (MB_X + (k < nslot ? k : 0)) * 8);
    STAMP(7);
    if (k < nslot) {
        const int role = (wq + k) & 3;
        const uint32_t ub = sb + SM_U + k * US + 128;
        if (role) {
            const int r = (3 - role) * 32 + lane;
            const uint32_t a1 = ub + (r & 3) * (2 * UP) + (r >> 2) * 16, a0 = a1 + ((r & 3) ? -2 * UP : 6 * UP - 16);
            const uint4 q0 = lds128(a0), q1 = lds128(a0 + UP), q2 = lds128(a1), q3 = lds128(a1 + UP);
            const uint32_t U[16] = {q0.x, q0.y, q0.z, q0.w, q1.x, q1.y, q1.z, q1.w, q2.x, q2.y, q2.z, q2.w, q3.x, q3.y, q3.z, q3.w};
            uint32_t V[14], Q[14], R4[12], T[8];
#pragma unroll
            for (int i = 2; i < 14; i++) { V[i] = __byte_perm(U[i], U[i + 1], 0x5432); Q[i] = hadd2(U[i], V[i]); }
#pragma unroll
            for (int i = 2; i < 12; i++) R4[i] = hadd2(Q[i], Q[i + 1]);
            const uint32_t rb = fb + r * 16;
#pragma unroll
            for (int i = 0; i < 8; i++) T[i] = hadd2(V[5 + i], Q[6 + i]);
            sts128(rb + F_E3, T[0], T[1], T[2], T[3]); sts128(rb + F_O3 + 16, T[4], T[5], T[6], T[7]);
#pragma unroll
            for (int i = 0; i < 8; i++) T[i] = hadd2(R4[3 + i], U[5 + i]);
            sts128(rb + F_O5, T[0], T[1], T[2], T[3]); sts128(rb + F_E5, T[4], T[5], T[6], T[7]);
            if (role != 1) {
#pragma unroll
                for (int i = 0; i < 8; i++) T[i] = hadd2(T[i], hadd2(V[2 + i], V[5 + i]));
                sts128(rb + F_E7, T[0], T[1], T[2], T[3]); sts128(rb + F_O7, T[4], T[5], T[6], T[7]);
#pragma unroll
                for (int i = 0; i < 8; i++) T[i] = hadd2(R4[2 + i], hadd2(R4[4 + i], U[6 + i]));
                sts128(rb + F_O9, T[0], T[1], T[2], T[3]); sts128(rb + F_E9 + 16, T[4], T[5], T[6], T[7]);
                sts128(rb + F_E2, Q[6], Q[7], Q[8], Q[9]); sts128(rb + F_O2, Q[10], Q[11], Q[12], Q[13]);
            }
        } else if (lane < 8) {
            uint32_t v[5];
#pragma unroll
            for (int i = 0; i < 5; i++) { const int t = 6 + lane + i; v[i] = lds16(ub + 23 * 16 + (t < 16 ? (6 + (t >> 3)) * UP : 16) + (t & 7) * 2); }
            const uint32_t s = hadd2(hadd2(hadd2(v[0], v[1]), hadd2(v[2], v[3])), v[4]);
            sts16(fb + F_O5 + 96 * 16 + lane * 2, s);
            sts32(fb + (lane < 4 ? F_O3 : F_E9 - 16) + lane * 4, 0);
        }
        bar_sync(1 + k, 128);
        float acc[4][4];
        uint32_t Q[4][4];
        {
            const int h = role & 1, part = role >> 1;
            const uint32_t po = pf + (g - 2 * cq) * 4;
            float fa[7][4];
#pragma unroll
            for (int a = 0; a < 7; a++) fa[a][0] = fa[a][1] = fa[a][2] = fa[a][3] = 0.f;
            uint32_t B[3][4];
            Q[0][2] = zero;
#pragma unroll 1
            for (int s = 2 * part + 1; s >= 2 * part; s--) {
#pragma unroll
                for (int i = 0; i < 3; i++) { Q[i][0] = lds32(po + s * P_GS + i * 64); Q[i][1] = lds32(po + s * P_GS + (i * 64 + 32)); }
                const uint32_t ba = fb + lane * 16 + ((s & 1) * F_E3 + (part == h ? 0 : F_O5 + h * 16));
#pragma unroll
                for (int i = 0; i < 3; i++) ldsm4t(B[i], ba + i * 512);
#pragma unroll
                for (int i = 0; i < 3; i++) { Q[i][3] = CP(Q[i][0]); if (i) Q[i][2] = CP(Q[i - 1][1]); }
#pragma unroll
                for (int dl = 0; dl < 3; dl++)
#pragma unroll
                    for (int ap = 0; ap < 6 - dl; ap++) mma_f16(fa[ap + 1 + dl], Q[dl], B[ap >> 1][2 * (ap & 1)], B[ap >> 1][2 * (ap & 1) + 1]);
            }
#pragma unroll 1
            for (int s = role; s == 1; s++) {
                ldsm2t(B[0][0], B[0][1], fb + ((lane & 15) == 15 ? F_O5 : F_O3));
#pragma unroll
                for (int dl = 0; dl < 3; dl++) mma_f16(fa[dl], Q[dl], B[0][0], B[0][1]);
            }
#pragma unroll 1
            for (int s = part; s <= 2 * part; s++) {
#pragma unroll
                for (int i = 0; i < 4; i++) { Q[i][0] = lds32(po + s * P_HS + (P_H7 + i * 64)); Q[i][1] = lds32(po + s * P_HS + (P_H7 + i * 64 + 32)); }
                const uint32_t ba = fb + lane * 16 + (F_E7 + s * 1024 + h * F_H);
                ldsm4t(B[0], ba); ldsm4t(B[1], ba + 512);
#pragma unroll
                for (int i = 0; i < 4; i++) { Q[i][3] = CP(Q[i][0]); if (i) Q[i][2] = CP(Q[i - 1][1]); }
#pragma unroll
                for (int dl = 0; dl < 4; dl++) {
#pragma unroll
                    for (int ap = 0; ap < 4 - dl; ap++) mma_f16(fa[ap + 3 + dl], Q[dl], B[ap >> 1][2 * (ap & 1)], B[ap >> 1][2 * (ap & 1) + 1]);
                    if (s == 1) break;
                }
            }
            const uint32_t da = fb + role * 2048 + (lane & 3) * 512 + (((lane >> 2) ^ ((lane & 3) * 2)) << 4);
            bar_sync(1 + k, 128);
            stsm4(da, 0u, 0u, pack_f16(fa[0][0], fa[0][1]), pack_f16(fa[0][2], fa[0][3]));
#pragma unroll
            for (int i = 1; i < 4; i++)
                stsm4(da + i * 128, pack_f16(fa[2 * i - 1][0], fa[2 * i - 1][1]), pack_f16(fa[2 * i - 1][2], fa[2 * i - 1][3]),
                      pack_f16(fa[2 * i][0], fa[2 * i][1]), pack_f16(fa[2 * i][2], fa[2 * i][3]));
            Q[0][0] = (g == 2 * cq) ? 0x6000u : ((g == 2 * cq + 1) ? 0x60000000u : 0u);
            Q[0][1] = 0; Q[0][3] = CP(Q[0][0]);
            const uint32_t ra = fb + (lane >> 3) * 2048 + wq * 512 + (((lane & 7) ^ (wq * 2)) << 4);
            bar_sync(1 + k, 128);
#pragma unroll
            for (int i = 0; i < 4; i++) {
                ldsm4(B[0], ra + i * 128);
                acc[i][0] = acc[i][1] = acc[i][2] = acc[i][3] = 0.f;
                mma_f16(acc[i], Q[0], hadd2(B[0][0], B[0][2]), hadd2(B[0][1], B[0][3]));
            }
        }
        bar_arrive(6 + k, 160);
        STAMP(8);
        const uint32_t inv = lds32(sb + SM_SC + k * 4);
        uint32_t yd = mapa(sb, 2 * wq) + (SM_XT + 128 + q * YP + k * YS + (k >> 2) * (q >> 1) * 16) + lane * 16;
        PIN(yd);
        {
            uint32_t pp = pn + (16 * (wq - 3) + g - 2 * cq) * 4;
            uint32_t dlo = (((ub + 6 * UP) & 0x3FFFF) >> 4) | ((UP >> 4) << 16);
            uint32_t R[4][4];
            auto loadQ = [&](uint32_t (&X)[4][4], uint32_t prev) {
#pragma unroll
                for (int i = 0; i < 4; i++) { X[i][0] = lds32(pp + i * 64); X[i][1] = lds32(pp + i * 64 + 32); }
                X[0][2] = CP(prev);
#pragma unroll
                for (int i = 0; i < 4; i++) { X[i][3] = CP(X[i][0]); if (i) X[i][2] = CP(X[i - 1][1]); }
                pp += 256;
            };
            auto issue = [&](uint32_t (&X)[4][4]) {
                asm volatile("wgmma.fence.sync.aligned;" ::: "memory");
#pragma unroll
                for (int i = 0; i < 4; i++) wgmma32(acc, X[i], dlo - i * (2 * UP >> 4));
                asm volatile("wgmma.commit_group.sync.aligned;" ::: "memory");
                dlo -= 1;
            };
            loadQ(Q, 0);
#pragma unroll 1
            for (int dl = 0; dl < 4; dl++) {
                issue(Q);
                asm volatile("wgmma.wait_group.sync.aligned 1;" ::: "memory");
                loadQ(R, Q[3][1]);
                issue(R);
                asm volatile("wgmma.wait_group.sync.aligned 1;" ::: "memory");
                loadQ(Q, R[3][1]);
            }
            issue(Q);
            asm volatile("wgmma.wait_group.sync.aligned 0;" ::: "memory");
        }
        const uint32_t pstep = mapa(sb, 1) - mapa(sb, 0), ym = mapa(mb + MB_Y * 8, 2 * wq);
#pragma unroll
        for (int e = 0; e < 2; e++)
            st_async4(yd + e * pstep, bmul2(pack_bf16(acc[0][2 * e], acc[0][2 * e + 1]), inv), bmul2(pack_bf16(acc[1][2 * e], acc[1][2 * e + 1]), inv),
                      bmul2(pack_bf16(acc[2][2 * e], acc[2][2 * e + 1]), inv), bmul2(pack_bf16(acc[3][2 * e], acc[3][2 * e + 1]), inv), ym + e * pstep);
        if (lane == 0) asm volatile("mbarrier.arrive.shared::cta.b64 _, [%0];" :: "r"(mb + MB_Y * 8) : "memory");
    }
    STAMP(9);
    uint32_t ha[5], hb[5];
    if (warp < 16) {
        const uint4 wk = lds128(sb + SM_DW + cq * 16);
        uint32_t sel[5] = {wk.x, wk.y, wk.z, wk.w, lds32(sb + SM_DW + 64 + cq * 4)}, sel2[5];
#pragma unroll
        for (int i = 0; i < 5; i++) {
            if (!(g & 1)) sel[i] = 0x3F803F80u;
            sel2[i] = sel[i]; PIN(sel2[i]);
        }
        const uint32_t y4 = sb + SM_XT + 128 + warp * 32 + (2 * (lane >> 3) + (lane & 1)) * YP + ((lane & 7) >> 1) * YS;
        const uint32_t y1 = sb + SM_XT + 128 + warp * 32 + (lane & 7) * YP + 4 * YS + (lane & 8) * 2 + (lane & 6) * 8;
        uint32_t ao = (256 * q + tn) * 16, hta = sb + SM_HT + tn * 80;
        PIN(ao); PIN(hta);
        mbar_wait(mb + MB_Y * 8);
        STAMP(10);
        float ca[4] = {0.f, 0.f, 0.f, 0.f}, cb[4] = {0.f, 0.f, 0.f, 0.f};
        {
            uint32_t ya[4], yb[4], yc, yd;
            ldsm4t(ya, y4); ldsm4t(yb, y4 + 16); ldsm2t(yc, yd, y1);
#pragma unroll
            for (int i = 0; i < 4; i++) { ha[i] = badd2(xa[i], ya[i]); hb[i] = badd2(xb[i], yb[i]); }
            ha[4] = badd2(xa[4], yc); hb[4] = badd2(xb[4], yd);
        }
        if (nslot != 5) {
            ha[4] = hb[4] = 0;
            if (cq >= 2) ha[0] = ha[1] = ha[2] = ha[3] = hb[0] = hb[1] = hb[2] = hb[3] = 0;
        }
#pragma unroll
        for (int i = 0; i < 5; i++) { mma_bf16_k8(ca, ha[i], sel[i], ha[i]); mma_bf16_k8(cb, hb[i], sel2[i], hb[i]); }
        if (!(g & 1)) { ca[1] = ca[0]; cb[1] = cb[0]; }
        if (cq == (g >> 1)) {
            asm volatile("red.relaxed.gpu.global.add.v4.f32 [%0], {%1,%2,%3,%4};" :: "l"((char*)g_s.acc + ao), "f"(1.0f), "f"(ca[1]), "f"(ca[2]), "f"(ca[3]) : "memory");
            asm volatile("red.relaxed.gpu.global.add.v4.f32 [%0], {%1,%2,%3,%4};" :: "l"((char*)g_s.acc + ao + 128), "f"(1.0f), "f"(cb[1]), "f"(cb[2]), "f"(cb[3]) : "memory");
        }
        sts128(hta + cq * 16, ha[0], ha[1], ha[2], ha[3]); sts32(hta + 64 + cq * 4, ha[4]);
        sts128(hta + cq * 16 + 640, hb[0], hb[1], hb[2], hb[3]); sts32(hta + 704 + cq * 4, hb[4]);
        STAMP(11);
    }
    const int kq = warp / 5, mt = warp - 5 * kq;
    const int mi = lane >> 3, mr = lane & 7;
    const unsigned tk = (unsigned)tid / 72u, ck = tid - tk * 72;
    uint32_t A[9][4];
    auto loadA = [&]() {
        mbar_wait(mb + MB_W1 * 8);
        const uint32_t aa = sb + (mi & 1) * SM_WU + (8 * (mi >> 1) + mr) * 80 + (144 * 80 * kq + mt * 16);
#pragma unroll
        for (int s = 0; s < 9; s++) ldsm4t(A[s], aa + s * 1280);
    };
    const uint32_t par = (epoch & 1) ? 0x40004000u : 0u;
    uint32_t pk0 = mapa(sb, 2 * cq), go = (ck / 5u + ck) * 16, co = ((q * 8 * NCL + c) * 6 + cq) * 16;
    PIN(pk0); PIN(go); PIN(co);
    if (warp < 8) {
        const float wsum = ldsf(sb + SM_SC + 24);
        const uint32_t idx = 2047 - (512 * ((tid >> 1) & 3) + 128 * ((tid >> 3) & 3) + 64 * (tid & 1) + 8 * q + warp);
        uint4 s; int n = 0;
        do { s = ld_rlx128(&g_s.acc[256 * q + tid]); } while (__uint_as_float(s.x) != (float)NCL && ++n < SPIN_LIMIT);
        STAMP(16);
        const uint32_t ox = __shfl_xor_sync(~0u, (lane & 1) ? s.z : s.w, 1);
        const uint32_t ms = ln_stats(__uint_as_float((lane & 1) ? ox : s.z), __uint_as_float(s.y));
        const float rs = rcpf(bf_hi(ms));
        const uint32_t rb = pack_bf16(0.f, fmaf(-bf_lo(ms), wsum, __uint_as_float((lane & 1) ? s.w : ox)) * rs);
        const uint32_t key = (((rb ^ (((int)rb >> 31) | 0x80000000u)) >> 16) << 11) | idx;
        sts32(sb + SM_KEY + tid * 4, key);
        __syncwarp();
        const uint32_t rank = rank4<8, 16>(sb + SM_KEY + warp * 128, key);
        if (rank < 8) sts32(sb + SM_CAND + warp * 32 + rank * 4, key);
        sts64(sb + SM_ST + tid * 8, ms, rsplit(rs));
    } else loadA();
    if (warp < 16) {
        STAMP(17);
        bar_sync(12, 512);
        STAMP(18);
        if (warp < 8) {
            const uint32_t mk = lds32(sb + SM_CAND + (tid >> 2) * 4);
            uint32_t rank = rank4<4, 64>(sb + SM_CAND + cq * 16, mk);
            rank += __shfl_xor_sync(~0u, rank, 1); rank += __shfl_xor_sync(~0u, rank, 2);
            if (rank < 8) {
                const uint32_t pk1 = pk0 + (mapa(sb, 1) - mapa(sb, 0));
                st_async1(pk0 + (SM_RK + q * 32) + rank * 4, mk, pk0 + (SM_MB + MB_KEY * 8));
                st_async1(pk1 + (SM_RK + q * 32) + rank * 4, mk, pk1 + (SM_MB + MB_KEY * 8));
                const uint32_t t = tslot(~mk);
                const uint2 sv = lds64(sb + SM_ST + t * 8);
                const uint4 hv = lds128(sb + SM_HT + t * 80 + cq * 16);
                const uint32_t h4 = lds32(sb + SM_HT + t * 80 + 64 + cq * 4);
                const uint32_t rr = bmul2(sv.y, 0x3C803C80u);
                char* const dp = (char*)g_s.cand + (co + rank * 1440);
                st_rlx128(dp, (norm2(hv.x, sv.x, rr) & 0xBFFFBFFFu) | par, (norm2(hv.y, sv.x, rr) & 0xBFFFBFFFu) | par,
                          (norm2(hv.z, sv.x, rr) & 0xBFFFBFFFu) | par, (norm2(hv.w, sv.x, rr) & 0xBFFFBFFFu) | par);
                asm volatile("st.relaxed.gpu.global.u32 [%0], %1;" :: "l"((char*)g_s.cand + (co + rank * 1440 + 64 - cq * 12)), "r"((norm2(h4, sv.x, rr) & 0xBFFFBFFFu) | par) : "memory");
            }
            __syncwarp();
        }
        {
            const uint2 sa = lds64(sb + SM_ST + tn * 8), sbb = lds64(sb + SM_ST + tn * 8 + 64);
#pragma unroll
            for (int i = 0; i < 5; i++) { ha[i] = badd2(ha[i], norm2(ha[i], sa.x, sa.y)); hb[i] = badd2(hb[i], norm2(hb[i], sbb.x, sbb.y)); }
            const bool hf = (c & 1) && cq == 0;
            const uint32_t o16 = sb + SM_XT + (hf ? 16384 + tn * 16 : tn * 64 + (cq - (c & 1)) * 16), o4 = sb + SM_XT + ((c & 1) ? tn * 64 + 48 : 16384 + tn * 16) + cq * 4;
            sts128(o16, ha[0], ha[1], ha[2], ha[3]); sts32(o4, ha[4]);
            sts128(o16 + (hf ? 128 : 512), hb[0], hb[1], hb[2], hb[3]); sts32(o4 + ((c & 1) ? 512 : 128), hb[4]);
        }
        if (warp >= 8) {
            STAMP(19);
            mbar_wait(mb + MB_KEY * 8);
            STAMP(20);
            const uint32_t mk = lds32(sb + SM_RK - 256 + (tid >> 2) * 4);
            uint32_t rank = rank4<4, 64>(sb + SM_RK + cq * 16, mk);
            rank += __shfl_xor_sync(~0u, rank, 1); rank += __shfl_xor_sync(~0u, rank, 2);
            if (rank < 8) sts64(sb + SM_SEL + rank * 8, mk, ((tid >> 2) - 64) * 1440);
        }
    }
    bar_sync(11, 640);
    STAMP(12);

    const char* gp = (const char*)g_s.cand + (go + lds32(sb + SM_SEL + 4 + (tk & 7) * 8));
    uint4 hv = ld_rlx128(gp);
    if (warp < 8) loadA();
    const bool red = warp < 6;
    const uint32_t ft = red ? (unsigned)tid / 24u : (unsigned)(tid >> 4) & 7u, fj = red ? 24 * q + tid - ft * 24 : d0 / 3 + (lane & 15);
    const uint32_t key = lds32(sb + SM_SEL + ft * 8), k16 = key << 5;
    float sig = bfr(rcpf(1.f + ex2f(__uint_as_float((k16 ^ (~((int)k16 >> 31) | 0x80000000u)) & 0xFFFF0000u) * -1.4426950408889634f)));
    uint32_t ra2 = sb + SM_RED2 + tid * 12 + ft * 16, fo = (ft * 192 + fj) * 16, oo = ((~key & 2047) * D_ + 3 * fj) * 2;
    uint32_t bx = sb + SM_XS + mr * 1168 + mi * 16 + 288 * kq, gd = mapa(sb, kq * (8 / NRED)) + (SM_GU + (q * nslot + mt) * 128) + lane * 4;
    PIN(ra2); PIN(fo); PIN(oo); PIN(bx); PIN(gd);
    asm volatile("" : "+f"(sig));
    {
        if (warp < 18) {
            int n = 0;
            while ((((hv.x ^ par) | (hv.y ^ par) | (hv.z ^ par) | (hv.w ^ par)) & 0x40004000u) && ++n < SPIN_LIMIT) hv = ld_rlx128(gp);
            sts128(sb + SM_XS + tk * 16 + tid * 16, hv.x ^ par, hv.y ^ par, hv.z ^ par, hv.w ^ par);
        }
    }
    bar_sync(14, 672);
    STAMP(13);
    {
        float c0[4] = {0.f, 0.f, 0.f, 0.f}, c1[4] = {0.f, 0.f, 0.f, 0.f}, c2[4] = {0.f, 0.f, 0.f, 0.f};
        uint32_t b[5][4];
#pragma unroll
        for (int s = 0; s < 4; s++) ldsm4(b[s], bx + s * 64);
        asm volatile("ldmatrix.sync.aligned.m8n8.x2.shared.b16 {%0,%1}, [%2];" : "=r"(b[4][0]), "=r"(b[4][1]) : "r"(bx + 256) : "memory");
        mma_bf16(c0, A[0][0], A[0][1], A[0][2], A[0][3], b[0][0], b[0][1]);
        mma_bf16(c1, A[1][0], A[1][1], A[1][2], A[1][3], b[0][2], b[0][3]);
        mma_bf16(c2, A[2][0], A[2][1], A[2][2], A[2][3], b[1][0], b[1][1]);
        mma_bf16(c0, A[3][0], A[3][1], A[3][2], A[3][3], b[1][2], b[1][3]);
        mma_bf16(c1, A[4][0], A[4][1], A[4][2], A[4][3], b[2][0], b[2][1]);
        mma_bf16(c2, A[5][0], A[5][1], A[5][2], A[5][3], b[2][2], b[2][3]);
        mma_bf16(c0, A[6][0], A[6][1], A[6][2], A[6][3], b[3][0], b[3][1]);
        mma_bf16(c1, A[7][0], A[7][1], A[7][2], A[7][3], b[3][2], b[3][3]);
        mma_bf16(c2, A[8][0], A[8][1], A[8][2], A[8][3], b[4][0], b[4][1]);
        sts128f(sb + SM_RED + tid * 16, c0[0] + c1[0] + c2[0], c0[1] + c1[1] + c2[1], c0[2] + c1[2] + c2[2], c0[3] + c1[3] + c2[3]);
    }
    bar_sync(1 + mt, 128);
    STAMP(21);
    if (mt < nslot && kq < NRED) {
        const uint32_t ra = sb + SM_RED + mt * 512 + lane * 16;
        const float4 p0 = lds128f(ra), p1 = lds128f(ra + 2560), p2 = lds128f(ra + 5120), p3 = lds128f(ra + 7680);
        const float g0 = bfr(((p0.x + p1.x) + (p2.x + p3.x)) * 64.f), g1 = bfr(((p0.y + p1.y) + (p2.y + p3.y)) * 64.f);
        const uint32_t sg = pack_bf16(g0 * rcpf(1.f + ex2f(g0 * -1.4426950408889634f)), g1 * rcpf(1.f + ex2f(g1 * -1.4426950408889634f)));
        const uint32_t gu = bmul2(sg, pack_bf16(((p0.z + p1.z) + (p2.z + p3.z)) * 64.f, ((p0.w + p1.w) + (p2.w + p3.w)) * 64.f));
        const uint32_t pstep = mapa(sb, 1) - mapa(sb, 0), gm = mapa(mb + MB_GU * 8, kq * (8 / NRED));
#pragma unroll
        for (int i = 0; i < 8 / NRED; i++) st_async1(gd + i * pstep, gu, gm + i * pstep);
    }
    mbar_wait(mb + MB_W2 * 8);
    {
        const uint32_t aa = sb + (8 * (mi >> 1) + mr) * (2 * W2W) + (mi & 1) * 16 + (SM_FAR + 32 * W2W * kq + mt * 32 + (W2W == 72 ? 0 : (q & 1) * 16));
#pragma unroll
        for (int s = 0; s < 5; s++) ldsm4t(A[s], aa + s * FAR_SZ);
    }
    {
        uint32_t ba = sb + (SM_GU + 256 * kq) + (lane & 15) * 16 + (lane >> 4) * 1024, wa = sb + (SM_RED2 + kq * 2432 + mt * 64) + g * 4 + cq * 608;
        PIN(ba); PIN(wa);
        STAMP(22);
        mbar_wait(mb + MB_GU * 8);
        STAMP(23);
        float c0[4] = {0.f, 0.f, 0.f, 0.f}, c1[4] = {0.f, 0.f, 0.f, 0.f}, c2[4] = {0.f, 0.f, 0.f, 0.f};
        uint32_t b[2][4], b8, b9;
        ldsm4t(b[0], ba); ldsm4t(b[1], ba + 2048); ldsm2t(b8, b9, ba + 4096);
        mma_bf16(c0, A[0][0], A[0][1], A[0][2], A[0][3], b[0][0], b[0][1]);
        mma_bf16(c1, A[1][0], A[1][1], A[1][2], A[1][3], b[0][2], b[0][3]);
        if (nslot == 5) {
            mma_bf16(c2, A[4][0], A[4][1], A[4][2], A[4][3], b8, b9);
            mma_bf16(c0, A[2][0], A[2][1], A[2][2], A[2][3], b[1][0], b[1][1]);
            mma_bf16(c1, A[3][0], A[3][1], A[3][2], A[3][3], b[1][2], b[1][3]);
        }
        stsf(wa, c0[0] + c1[0] + c2[0]); stsf(wa + 304, c0[1] + c1[1] + c2[1]);
        if (mt < 4) { stsf(wa + 32, c0[2] + c1[2] + c2[2]); stsf(wa + 336, c0[3] + c1[3] + c2[3]); }
    }
    if (warp < 10) {
        float v[3], cnt = 3.f;
        if (red) {
            bar_sync(6, 640);
            STAMP(14);
#pragma unroll
            for (int i = 0; i < 3; i++) v[i] = ((ldsf(ra2 + i * 4) + ldsf(ra2 + i * 4 + 2432)) + (ldsf(ra2 + i * 4 + 4864) + ldsf(ra2 + i * 4 + 7296))) * sig;
        } else {
            bar_arrive(6, 640);
            cnt = 0.f;
#pragma unroll
            for (int i = 0; i < 3; i++) {
                const uint32_t cl = 3 * fj + i - d0;
                const bool ok = cl < 8 * nslot && ((~key >> 3) & 7) == q;
                const uint32_t cf = cl - (c & 1) * 8;
                v[i] = ok ? __uint_as_float(lds16(sb + SM_XT + (cf < 32 ? tslot(~key) * 64 + cf * 2 : 16384 + tslot(~key) * 16 + (cl & 7) * 2)) << 16) : 0.f;
                if (ok) cnt += 1.f;
            }
            mbar_wait(mb + MB_OUT * 8);
        }
        if (cnt != 0.f) {
            float x, y, z, w;
            asm volatile("atom.relaxed.gpu.global.add.v4.f32 {%0,%1,%2,%3}, [%4], {%5,%6,%7,%8};" : "=f"(x), "=f"(y), "=f"(z), "=f"(w)
                         : "l"((char*)g_s.fin + fo), "f"(v[0]), "f"(v[1]), "f"(v[2]), "f"(cnt) : "memory");
            if (w + cnt == 3.f * (NCL + 1)) {
                __nv_bfloat16* op = (__nv_bfloat16*)((char*)prm.out + oo);
                op[0] = __float2bfloat16(x + v[0]); op[1] = __float2bfloat16(y + v[1]); op[2] = __float2bfloat16(z + v[2]);
            }
        }
    } else bar_arrive(6, 640);
    STAMP(15);
}

typedef __nv_bfloat16 bf16;
__device__ bf16 f_n[L_ * D_], f_h[L_ * D_];
__device__ float f_k[D_ * L_], f_r[L_], f_gu[8 * F_];
__device__ int f_idx[8];
__device__ __forceinline__ float b2f(bf16 v) { return __bfloat162float(v); }
__global__ void fb_ln(const bf16* in, const bf16* wr, bf16* out) {
    const int t = blockIdx.x * 8 + (threadIdx.x >> 5), lane = threadIdx.x & 31;
    const bf16* r = (in ? in : f_h) + t * D_;
    float s1 = 0.f, s2 = 0.f, s3 = 0.f;
    for (int i = lane; i < D_; i += 32) s1 += b2f(r[i]);
    for (int o = 16; o; o >>= 1) s1 += __shfl_xor_sync(~0u, s1, o);
    for (int i = lane; i < D_; i += 32) { const float d = b2f(r[i]) - s1 / D_; s2 += d * d; }
    for (int o = 16; o; o >>= 1) s2 += __shfl_xor_sync(~0u, s2, o);
    const float m = bfr(s1 / D_), sd = bfr(sqrtf(bfr(bfr(s2 / D_) + 1e-5f)));
    for (int i = lane; i < D_; i += 32) {
        const float v = bfr(bfr(b2f(r[i]) - m) / sd);
        f_n[t * D_ + i] = __float2bfloat16(v);
        if (!in) { s3 += v * b2f(wr[i]); out[t * D_ + i] = __float2bfloat16(b2f(r[i]) + v); }
    }
    for (int o = 16; o; o >>= 1) s3 += __shfl_xor_sync(~0u, s3, o);
    f_r[t] = bfr(s3);
}
__global__ void fb_taps(Params p) {
    const int d = blockIdx.x >> 3, l = (blockIdx.x & 7) * 256 + threadIdx.x;
    const float dt = bfr(expf(bf_lo(p.logdt[d]))), lf = bfr((float)l);
    float k = 0.f;
    for (int n = d * 128; n < d * 128 + 128; n++) {
        float wr, wi, sn, cs;
        cmul(wr, wi, bf_lo(p.prm6[4][n]), bf_lo(p.prm6[5][n]), dt * bf_lo(p.prm6[2][n]), dt * bf_lo(p.prm6[3][n]));
        sincosf(dt * bf_lo(p.prm6[1][n]) * lf, &sn, &cs);
        k += expf(dt * bf_lo(p.prm6[0][n]) * lf) * (wr * cs - wi * sn);
    }
    f_k[l * D_ + d] = k;
}
__global__ void fb_conv(Params p) {
    const int t = blockIdx.x, d = threadIdx.x;
    float y = 0.f;
    for (int l = 0; l <= t; l++) y += f_k[l * D_ + d] * b2f(f_n[(t - l) * D_ + d]);
    f_h[t * D_ + d] = __float2bfloat16(bf_lo(p.x[t * D_ + d]) + bfr(bfr(y) + bfr(b2f(f_n[t * D_ + d]) * bf_lo(p.dskip[d]))));
}
__global__ void fb_top() {
    const int t = blockIdx.x * 256 + threadIdx.x;
    int rank = 0;
    for (int j = 0; j < L_; j++) rank += f_r[j] > f_r[t] || (f_r[j] == f_r[t] && j < t);
    if (rank < 8) f_idx[rank] = t;
}
__global__ void fb_ffn1(const bf16* wg, const bf16* wu) {
    const int f = blockIdx.x * 256 + threadIdx.x, j = blockIdx.y;
    float g = 0.f, u = 0.f;
    for (int i = 0; i < D_; i++) { const float v = b2f(f_n[f_idx[j] * D_ + i]); g += v * b2f(wg[i * F_ + f]); u += v * b2f(wu[i * F_ + f]); }
    g = bfr(g);
    f_gu[j * F_ + f] = bfr(bfr(g / (1.f + expf(-g))) * bfr(u));
}
__global__ void fb_ffn2(const bf16* wd, bf16* out) {
    const int d = threadIdx.x, j = blockIdx.x, t = f_idx[j];
    float y = 0.f;
    for (int f = 0; f < F_; f++) y += f_gu[j * F_ + f] * b2f(wd[f * D_ + d]);
    out[t * D_ + d] = __float2bfloat16(b2f(f_h[t * D_ + d]) + bfr(b2f(f_n[t * D_ + d]) + bfr(bfr(y) * bfr(1.f / (1.f + expf(-f_r[t]))))));
}

typedef CUresult (*EncodeFn)(CUtensorMap*, CUtensorMapDataType, cuuint32_t, void*, const cuuint64_t*, const cuuint64_t*,
                             const cuuint32_t*, const cuuint32_t*, CUtensorMapInterleave, CUtensorMapSwizzle,
                             CUtensorMapL2promotion, CUtensorMapFloatOOBfill);

void make_map(EncodeFn fn, CUtensorMap* tm, const void* p, int cols, int rows, int bc, int br) {
    cuuint64_t dims[2] = {(cuuint64_t)cols, (cuuint64_t)rows};
    cuuint64_t strides[1] = {(cuuint64_t)cols * 2};
    cuuint32_t box[2] = {(cuuint32_t)bc, (cuuint32_t)br};
    cuuint32_t es[2] = {1, 1};
    fn(tm, CU_TENSOR_MAP_DATA_TYPE_BFLOAT16, 2, const_cast<void*>(p), dims, strides, box, es, CU_TENSOR_MAP_INTERLEAVE_NONE,
       CU_TENSOR_MAP_SWIZZLE_NONE, CU_TENSOR_MAP_L2_PROMOTION_L2_128B, CU_TENSOR_MAP_FLOAT_OOB_FILL_NONE);
}

void make_map3(EncodeFn fn, CUtensorMap* tm, const void* p) {
    cuuint64_t dims[5] = {(cuuint64_t)D_, 64, 2, 4, 4};
    cuuint64_t strides[4] = {(cuuint64_t)D_ * 2, (cuuint64_t)D_ * 128, (cuuint64_t)D_ * 1024, (cuuint64_t)D_ * 256};
    cuuint32_t box[5] = {XW, 9, 2, 4, 4};
    cuuint32_t es[5] = {1, 1, 1, 1, 1};
    fn(tm, CU_TENSOR_MAP_DATA_TYPE_BFLOAT16, 5, const_cast<void*>(p), dims, strides, box, es, CU_TENSOR_MAP_INTERLEAVE_NONE,
       CU_TENSOR_MAP_SWIZZLE_NONE, CU_TENSOR_MAP_L2_PROMOTION_NONE, CU_TENSOR_MAP_FLOAT_OOB_FILL_NONE);
}

void make_map5(EncodeFn fn, CUtensorMap* tm, const void* p, int bc) {
    cuuint64_t dims[5] = {(cuuint64_t)D_, 2, 4, 4, 64};
    cuuint64_t strides[4] = {(cuuint64_t)D_ * 128, (cuuint64_t)D_ * 1024, (cuuint64_t)D_ * 256, (cuuint64_t)D_ * 2};
    cuuint32_t box[5] = {(cuuint32_t)bc, 2, 4, 4, 8};
    cuuint32_t es[5] = {1, 1, 1, 1, 1};
    fn(tm, CU_TENSOR_MAP_DATA_TYPE_BFLOAT16, 5, const_cast<void*>(p), dims, strides, box, es, CU_TENSOR_MAP_INTERLEAVE_NONE,
       CU_TENSOR_MAP_SWIZZLE_NONE, CU_TENSOR_MAP_L2_PROMOTION_NONE, CU_TENSOR_MAP_FLOAT_OOB_FILL_NONE);
}

}

extern "C" void kernel_launch(void* const* d_in, const int* in_sizes, int n_in, void* d_out, int out_size) {
    (void)in_sizes; (void)n_in; (void)out_size;
    void* fp = nullptr;
    cudaDriverEntryPointQueryResult qr;
    cudaGetDriverEntryPoint("cuTensorMapEncodeTiled", &fp, cudaEnableDefault, &qr);
    EncodeFn fn = (EncodeFn)fp;
    CUtensorMap tmG, tmU, tmD, tmO, tmX, tmH;
    make_map3(fn, &tmX, d_in[0]);
    make_map(fn, &tmG, d_in[11], F_, D_, 40, 48);
    make_map(fn, &tmU, d_in[12], F_, D_, 40, 48);
    make_map(fn, &tmD, d_in[13], D_, F_, W2W, 64);
    make_map5(fn, &tmO, d_out, 32);
    make_map5(fn, &tmH, d_out, 8);
    Params p;
    p.x = (const unsigned short*)d_in[0];
    for (int i = 0; i < 6; i++) p.prm6[i] = (const unsigned short*)d_in[1 + i];
    p.logdt = (const unsigned short*)d_in[7]; p.dskip = (const unsigned short*)d_in[8];
    p.wr = (const unsigned short*)d_in[10];
    p.out = (__nv_bfloat16*)d_out;
    p.zero = 0;
    cudaGetSymbolAddress((void**)&p.gs, g_s);
    cudaFuncSetAttribute(fused_kernel, cudaFuncAttributeMaxDynamicSharedMemorySize, SM_TOTAL);
    static int nclusters = -1;
    if (nclusters < 0) {
        cudaLaunchConfig_t cfg = {};
        cudaLaunchAttribute at;
        at.id = cudaLaunchAttributeClusterDimension; at.val.clusterDim.x = CS; at.val.clusterDim.y = 1; at.val.clusterDim.z = 1;
        cfg.gridDim = dim3(NCTA); cfg.blockDim = dim3(NTHR); cfg.dynamicSmemBytes = SM_TOTAL; cfg.attrs = &at; cfg.numAttrs = 1;
        if (cudaOccupancyMaxActiveClusters(&nclusters, fused_kernel, &cfg) != cudaSuccess) { (void)cudaGetLastError(); nclusters = NCL; }
    }
    if (nclusters >= NCL && !FORCE_FALLBACK) {
        fused_kernel<<<NCTA, NTHR, SM_TOTAL>>>(p, tmG, tmU, tmD, tmO, tmX, tmH);
        return;
    }
    fb_ln<<<L_ / 8, 256>>>((const bf16*)d_in[0], nullptr, nullptr);
    fb_taps<<<D_ * 8, 256>>>(p);
    fb_conv<<<L_, D_>>>(p);
    fb_ln<<<L_ / 8, 256>>>(nullptr, (const bf16*)d_in[10], p.out);
    fb_top<<<L_ / 256, 256>>>();
    fb_ffn1<<<dim3(F_ / 256, 8), 256>>>((const bf16*)d_in[11], (const bf16*)d_in[12]);
    fb_ffn2<<<8, D_>>>((const bf16*)d_in[13], p.out);
}
```

```cpp
#include <cuda_runtime.h>
#include <cuda_bf16.h>
#include <cuda_fp16.h>
#include <cuda.h>
#include <stdint.h>

namespace {

constexpr int L_ = 2048, D_ = 576, F_ = 4608;
constexpr int NCL = 15, CS = 8, NCTA = NCL * CS, NTHR = 768;
#define FORCE_FALLBACK 0
constexpr int XW = 48, NRED = 2;
constexpr int SPIN_LIMIT = 1 << 22;

constexpr int SM_WG   = 0;
constexpr int SM_WU   = 46080;
constexpr int YP = 3392, YS = 656;
constexpr int UP = 3280, US = 656;
constexpr int SM_XT   = 92160;
constexpr int SM_U    = SM_XT + 8 * YP;
constexpr int SM_FAR  = SM_U + 8 * UP;
constexpr int FAR_SZ  = 12416;
constexpr int F_E5 = 0, F_O5 = 1536, F_E3 = 3088, F_O3 = 4624, F_E7 = 6176, F_E2 = F_E7 + 1024, F_E9 = F_E7 + 2048,
              F_H = 3088, F_O7 = F_E7 + F_H, F_O2 = F_E2 + F_H, F_O9 = F_E9 + F_H;
constexpr int SM_P    = SM_FAR + 5 * FAR_SZ;
constexpr int PN_SZ = 584 * 4, SM_PN = SM_P + 64 * 4;
constexpr int P_GS = 48 * 4, P_H7 = 192 * 4, P_HS = 72 * 4;
constexpr int PF_SZ = (192 + 216) * 4, SM_PF = SM_PN + 5 * PN_SZ + 32;
constexpr int SM_MISC = SM_PF + 5 * PF_SZ;
constexpr int SM_ST   = SM_MISC;
constexpr int SM_RK   = SM_ST + 2048;
constexpr int SM_SEL  = SM_RK + 256;
constexpr int SM_KG   = SM_SEL + 64;
constexpr int SM_SC   = SM_KG + 160;
constexpr int SM_DW   = SM_SC + 32;
constexpr int SM_MB   = SM_DW + 160;
constexpr int SM_TOTAL = SM_MB + 128;
constexpr int SM_ROW  = SM_XT - 20736;
constexpr int SM_XTL  = SM_ROW - 576 * XW;
constexpr int SM_RED2 = SM_WG;
constexpr int SM_HT   = SM_P - 512;
constexpr int SM_KEY  = SM_FAR + 10240 + 128;
constexpr int SM_CAND = SM_KEY + 1024;
constexpr int SM_XS   = SM_U;
constexpr int SM_GU   = SM_XS + 9344;
constexpr int SM_RED  = SM_GU + 5632;
static_assert(F_O9 + 1024 <= FAR_SZ && FAR_SZ % 128 == 0, "far overflow");
static_assert(SM_RED + 10240 <= SM_FAR && SM_HT + 20496 <= SM_MISC, "alias overflow");
static_assert(SM_TOTAL <= 232448, "smem overflow");
static_assert(SM_FAR % 128 == 0 && SM_XT % 128 == 0 && SM_XTL % 128 == 0 && SM_P % 16 == 0 && SM_MISC % 16 == 0 && SM_MB % 8 == 0, "align");

enum { MB_X = 0, MB_W1 = 5, MB_W2 = 6, MB_KEY = 7, MB_GU = 8, MB_Y = 9, MB_OUT = 10, MB_T = 11, MB_R = 12 };

struct __align__(128) Scratch {
    unsigned epoch, zcnt, pad[30];
    uint4  st1[L_ * 2];
    float4 acc[L_];
    uint4  cand[64 * NCL * 6];
    float4 fin[8 * 192 + 24];
};
__device__ Scratch g_s;
#define STAMP(i)

__device__ __forceinline__ uint32_t mapa(uint32_t a, uint32_t r) { uint32_t d; asm("mapa.shared::cluster.u32 %0, %1, %2;" : "=r"(d) : "r"(a), "r"(r)); return d; }
__device__ __forceinline__ void mbar_wait(uint32_t mb) {
    asm volatile("{ .reg .pred p, q; .reg .u32 n; mov.u32 n, 0;\n"
                 "W_%=: mbarrier.try_wait.parity.shared::cta.b64 p, [%0], 0; add.u32 n, n, 1; setp.lt.and.u32 q, n, 65536, !p; @q bra W_%=; }" :: "r"(mb) : "memory");
}
__device__ __forceinline__ void arm(uint32_t mb, uint32_t bytes) { asm volatile("mbarrier.arrive.expect_tx.shared::cta.b64 _, [%0], %1;" :: "r"(mb), "r"(bytes) : "memory"); }
__device__ __forceinline__ void bar_sync(int id, int n) { asm volatile("bar.sync %0, %1;" :: "r"(id), "r"(n) : "memory"); }
__device__ __forceinline__ void bar_arrive(int id, int n) { asm volatile("bar.arrive %0, %1;" :: "r"(id), "r"(n) : "memory"); }
__device__ __forceinline__ uint32_t lds16(uint32_t a) { unsigned short v; asm volatile("ld.shared.u16 %0, [%1];" : "=h"(v) : "r"(a) : "memory"); return v; }
__device__ __forceinline__ uint32_t lds32(uint32_t a) { uint32_t v; asm volatile("ld.shared.u32 %0, [%1];" : "=r"(v) : "r"(a) : "memory"); return v; }
__device__ __forceinline__ uint2 lds64(uint32_t a) { uint2 v; asm volatile("ld.shared.v2.u32 {%0,%1}, [%2];" : "=r"(v.x), "=r"(v.y) : "r"(a) : "memory"); return v; }
__device__ __forceinline__ float ldsf(uint32_t a) { float v; asm volatile("ld.shared.f32 %0, [%1];" : "=f"(v) : "r"(a) : "memory"); return v; }
__device__ __forceinline__ uint4 lds128(uint32_t a) { uint4 v; asm volatile("ld.shared.v4.u32 {%0,%1,%2,%3}, [%4];" : "=r"(v.x), "=r"(v.y), "=r"(v.z), "=r"(v.w) : "r"(a) : "memory"); return v; }
__device__ __forceinline__ float4 lds128f(uint32_t a) { float4 v; asm volatile("ld.shared.v4.f32 {%0,%1,%2,%3}, [%4];" : "=f"(v.x), "=f"(v.y), "=f"(v.z), "=f"(v.w) : "r"(a) : "memory"); return v; }
__device__ __forceinline__ void sts16(uint32_t a, uint32_t v) { asm volatile("{ .reg .b16 l, h; mov.b32 {l, h}, %1; st.shared.b16 [%0], l; }" :: "r"(a), "r"(v) : "memory"); }
__device__ __forceinline__ void sts32(uint32_t a, uint32_t v) { asm volatile("st.shared.u32 [%0], %1;" :: "r"(a), "r"(v) : "memory"); }
__device__ __forceinline__ void sts64(uint32_t a, uint32_t x, uint32_t y) { asm volatile("st.shared.v2.u32 [%0], {%1,%2};" :: "r"(a), "r"(x), "r"(y) : "memory"); }
__device__ __forceinline__ void stsf(uint32_t a, float v) { asm volatile("st.shared.f32 [%0], %1;" :: "r"(a), "f"(v) : "memory"); }
__device__ __forceinline__ void sts128(uint32_t a, uint32_t x, uint32_t y, uint32_t z, uint32_t w) { asm volatile("st.shared.v4.u32 [%0], {%1,%2,%3,%4};" :: "r"(a), "r"(x), "r"(y), "r"(z), "r"(w) : "memory"); }
__device__ __forceinline__ void sts128f(uint32_t a, float x, float y, float z, float w) { asm volatile("st.shared.v4.f32 [%0], {%1,%2,%3,%4};" :: "r"(a), "f"(x), "f"(y), "f"(z), "f"(w) : "memory"); }
__device__ __forceinline__ void ldsm4(uint32_t (&r)[4], uint32_t a) { asm volatile("ldmatrix.sync.aligned.m8n8.x4.shared.b16 {%0,%1,%2,%3}, [%4];" : "=r"(r[0]), "=r"(r[1]), "=r"(r[2]), "=r"(r[3]) : "r"(a) : "memory"); }
__device__ __forceinline__ void ldsm4t(uint32_t (&r)[4], uint32_t a) { asm volatile("ldmatrix.sync.aligned.m8n8.x4.trans.shared.b16 {%0,%1,%2,%3}, [%4];" : "=r"(r[0]), "=r"(r[1]), "=r"(r[2]), "=r"(r[3]) : "r"(a) : "memory"); }
__device__ __forceinline__ void ldsm2t(uint32_t& r0, uint32_t& r1, uint32_t a) { asm volatile("ldmatrix.sync.aligned.m8n8.x2.trans.shared.b16 {%0,%1}, [%2];" : "=r"(r0), "=r"(r1) : "r"(a) : "memory"); }
__device__ __forceinline__ void stsm4t(uint32_t a, uint32_t r0, uint32_t r1, uint32_t r2, uint32_t r3) { asm volatile("stmatrix.sync.aligned.m8n8.x4.trans.shared.b16 [%0], {%1,%2,%3,%4};" :: "r"(a), "r"(r0), "r"(r1), "r"(r2), "r"(r3) : "memory"); }
__device__ __forceinline__ void stsm4(uint32_t a, uint32_t r0, uint32_t r1, uint32_t r2, uint32_t r3) { asm volatile("stmatrix.sync.aligned.m8n8.x4.shared.b16 [%0], {%1,%2,%3,%4};" :: "r"(a), "r"(r0), "r"(r1), "r"(r2), "r"(r3) : "memory"); }
__device__ __forceinline__ void stsm2t(uint32_t a, uint32_t r0, uint32_t r1) { asm volatile("stmatrix.sync.aligned.m8n8.x2.trans.shared.b16 [%0], {%1,%2};" :: "r"(a), "r"(r0), "r"(r1) : "memory"); }
__device__ __forceinline__ uint4 ldg128(const void* p) { uint4 v; asm volatile("ld.global.nc.v4.u32 {%0,%1,%2,%3}, [%4];" : "=r"(v.x), "=r"(v.y), "=r"(v.z), "=r"(v.w) : "l"(p)); return v; }
__device__ __forceinline__ uint32_t ldg16(const void* p) { unsigned short v; asm volatile("ld.global.nc.u16 %0, [%1];" : "=h"(v) : "l"(p)); return v; }
__device__ __forceinline__ uint32_t opaque(uint32_t v) { uint32_t r; asm volatile("mov.b32 %0, %1;" : "=r"(r) : "r"(v)); return r; }
__device__ __forceinline__ void mma_f16(float (&d)[4], const uint32_t (&a)[4], uint32_t b0, uint32_t b1) {
    asm volatile("mma.sync.aligned.m16n8k16.row.col.f32.f16.f16.f32 {%0,%1,%2,%3}, {%4,%5,%6,%7}, {%8,%9}, {%0,%1,%2,%3};"
        : "+f"(d[0]), "+f"(d[1]), "+f"(d[2]), "+f"(d[3]) : "r"(a[0]), "r"(a[1]), "r"(a[2]), "r"(a[3]), "r"(b0), "r"(b1));
}
__device__ __forceinline__ void mma_bf16(float (&d)[4], uint32_t a0, uint32_t a1, uint32_t a2, uint32_t a3, uint32_t b0, uint32_t b1) {
    asm volatile("mma.sync.aligned.m16n8k16.row.col.f32.bf16.bf16.f32 {%0,%1,%2,%3}, {%4,%5,%6,%7}, {%8,%9}, {%0,%1,%2,%3};"
        : "+f"(d[0]), "+f"(d[1]), "+f"(d[2]), "+f"(d[3]) : "r"(a0), "r"(a1), "r"(a2), "r"(a3), "r"(b0), "r"(b1));
}
__device__ __forceinline__ void mma_bf16_k8(float (&d)[4], uint32_t a0, uint32_t a1, uint32_t b0) {
    asm volatile("mma.sync.aligned.m16n8k8.row.col.f32.bf16.bf16.f32 {%0,%1,%2,%3}, {%4,%5}, {%6}, {%0,%1,%2,%3};"
        : "+f"(d[0]), "+f"(d[1]), "+f"(d[2]), "+f"(d[3]) : "r"(a0), "r"(a1), "r"(b0));
}
__device__ __forceinline__ uint32_t pack_f16(float lo, float hi) { uint32_t r; asm("cvt.rn.f16x2.f32 %0, %1, %2;" : "=r"(r) : "f"(hi), "f"(lo)); return r; }
__device__ __forceinline__ uint32_t pack_bf16(float lo, float hi) { uint32_t r; asm("cvt.rn.bf16x2.f32 %0, %1, %2;" : "=r"(r) : "f"(hi), "f"(lo)); return r; }
__device__ __forceinline__ float bf_lo(uint32_t v) { return __uint_as_float(v << 16); }
__device__ __forceinline__ float bf_hi(uint32_t v) { return __uint_as_float(v & 0xFFFF0000u); }
__device__ __forceinline__ float bfr(float x) { return __uint_as_float(pack_bf16(0.f, x)); }
__device__ __forceinline__ uint32_t badd2(uint32_t a, uint32_t b) { uint32_t r; asm("add.rn.bf16x2 %0, %1, %2;" : "=r"(r) : "r"(a), "r"(b)); return r; }
__device__ __forceinline__ uint32_t bmul2(uint32_t a, uint32_t b) { uint32_t r; asm("mul.rn.bf16x2 %0, %1, %2;" : "=r"(r) : "r"(a), "r"(b)); return r; }
__device__ __forceinline__ uint32_t hadd2(uint32_t a, uint32_t b) { uint32_t r; asm("add.rn.f16x2 %0, %1, %2;" : "=r"(r) : "r"(a), "r"(b)); return r; }
__device__ __forceinline__ uint32_t hmul2(uint32_t a, uint32_t b) { uint32_t r; asm("mul.rn.f16x2 %0, %1, %2;" : "=r"(r) : "r"(a), "r"(b)); return r; }
__device__ __forceinline__ uint32_t hfma2(uint32_t a, uint32_t b, uint32_t c) { uint32_t r; asm("fma.rn.f16x2 %0, %1, %2, %3;" : "=r"(r) : "r"(a), "r"(b), "r"(c)); return r; }
__device__ __forceinline__ uint32_t hneg2(uint32_t a) { uint32_t r; asm("neg.f16x2 %0, %1;" : "=r"(r) : "r"(a)); return r; }
__device__ __forceinline__ float rcpf(float x) { float r; asm("rcp.approx.ftz.f32 %0, %1;" : "=f"(r) : "f"(x)); return r; }
__device__ __forceinline__ float sqrta(float x) { float r; asm("sqrt.approx.ftz.f32 %0, %1;" : "=f"(r) : "f"(x)); return r; }
__device__ __forceinline__ float ex2f(float x) { float r; asm("ex2.approx.ftz.f32 %0, %1;" : "=f"(r) : "f"(x)); return r; }
__device__ __forceinline__ void st_async4(uint32_t a, uint32_t x, uint32_t y, uint32_t z, uint32_t w, uint32_t mb) {
    asm volatile("st.async.shared::cluster.mbarrier::complete_tx::bytes.v4.u32 [%0], {%1,%2,%3,%4}, [%5];" :: "r"(a), "r"(x), "r"(y), "r"(z), "r"(w), "r"(mb) : "memory"); }
__device__ __forceinline__ void st_async1(uint32_t a, uint32_t x, uint32_t mb) {
    asm volatile("st.async.shared::cluster.mbarrier::complete_tx::bytes.u32 [%0], %1, [%2];" :: "r"(a), "r"(x), "r"(mb) : "memory"); }
__device__ __forceinline__ unsigned ld_rlx(const void* p) { unsigned v; asm volatile("ld.relaxed.gpu.global.u32 %0, [%1];" : "=r"(v) : "l"(p) : "memory"); return v; }
__device__ __forceinline__ unsigned ld_acq(const void* p) { unsigned v; asm volatile("ld.acquire.gpu.global.u32 %0, [%1];" : "=r"(v) : "l"(p) : "memory"); return v; }
__device__ __forceinline__ uint2 ld_rlx64(const void* p) { unsigned long long v; asm volatile("ld.relaxed.gpu.global.u64 %0, [%1];" : "=l"(v) : "l"(p) : "memory"); return make_uint2((unsigned)v, (unsigned)(v >> 32)); }
__device__ __forceinline__ void st_rlx128(void* p, uint32_t x, uint32_t y, uint32_t z, uint32_t w) {
    asm volatile("st.relaxed.gpu.global.v2.u64 [%0], {%1,%2};" :: "l"(p), "l"((unsigned long long)x | ((unsigned long long)y << 32)), "l"((unsigned long long)z | ((unsigned long long)w << 32)) : "memory"); }
__device__ __forceinline__ uint4 ld_rlx128(const void* p) { unsigned long long a, b; asm volatile("ld.relaxed.gpu.global.v2.u64 {%0,%1}, [%2];" : "=l"(a), "=l"(b) : "l"(p) : "memory"); return make_uint4((unsigned)a, (unsigned)(a >> 32), (unsigned)b, (unsigned)(b >> 32)); }
__device__ __forceinline__ void tma2d(uint32_t dst, const CUtensorMap* tm, int x, int y, uint32_t mb) {
    asm volatile("cp.async.bulk.tensor.2d.shared::cluster.global.mbarrier::complete_tx::bytes [%0], [%1, {%3, %4}], [%2];"
                 :: "r"(dst), "l"(tm), "r"(mb), "r"(x), "r"(y) : "memory");
}
__device__ __forceinline__ void cmul(float& xr, float& xi, float ar, float ai, float br, float bi) {
    const float r = fmaf(ar, br, -ai * bi), i = fmaf(ar, bi, ai * br); xr = r; xi = i;
}
__device__ __forceinline__ void csq(float& xr, float& xi, float ar, float ai) {
    const float r = fmaf(ar, ar, -ai * ai), i = (ar + ar) * ai; xr = r; xi = i;
}
__device__ __forceinline__ void cexp_s(float& zr, float& zi, float e2, float turns) {
    const float mag = ex2f(e2), r = (turns - rintf(turns)) * 6.283185307179586f;
    zr = mag * __cosf(r); zi = mag * __sinf(r);
}
__device__ __forceinline__ uint32_t ln_stats(float s1, float s2) {
    const float m = s1 * (1.f / D_);
    const float var = fmaxf(fmaf(s2, 1.f / D_, -m * m), 0.f);
    return pack_bf16(m, sqrta(bfr(bfr(var) + 1e-5f)));
}
__device__ __forceinline__ uint32_t rsplit(float rs) { const float h = bfr(rs); return pack_bf16(h, rs - h); }
__device__ __forceinline__ uint32_t norm2(uint32_t v, uint32_t mx, uint32_t hl) {
    uint32_t r;
    asm("{ .reg .b16 m, h, l, x; .reg .b32 m2, h2, l2, d, t; mov.b32 {m, x}, %2; mov.b32 {h, l}, %3; mov.b32 m2, {m, m}; mov.b32 h2, {h, h}; mov.b32 l2, {l, l};\n"
        "sub.rn.bf16x2 d, %1, m2; mul.rn.bf16x2 t, d, l2; fma.rn.bf16x2 %0, d, h2, t; }" : "=r"(r) : "r"(v), "r"(mx), "r"(hl));
    return r;
}
template <int N, int S>
__device__ __forceinline__ uint32_t rank4(uint32_t a, uint32_t key) {
    uint32_t r0 = 0, r1 = 0, r2 = 0, r3 = 0;
#pragma unroll
    for (int i = 0; i < N; i++) {
        const uint4 o = lds128(a + i * S);
        r0 += (key - o.x) >> 31; r1 += (key - o.y) >> 31; r2 += (key - o.z) >> 31; r3 += (key - o.w) >> 31;
    }
    return (r0 + r1) + (r2 + r3);
}
typedef uint32_t H2C;
__device__ __forceinline__ H2C splat(float r, float i) { return pack_f16(r, i); }
__device__ __forceinline__ void hcmul(uint32_t& xr, uint32_t& xi, uint32_t R, uint32_t I, H2C m) {
    asm("{ .reg .b16 a, b; .reg .b32 a2, b2, t; mov.b32 {a, b}, %4; mov.b32 a2, {a, a}; mov.b32 b2, {b, b};\n"
        "mul.rn.f16x2 t, %3, b2; neg.f16x2 t, t; fma.rn.f16x2 %0, %2, a2, t; mul.rn.f16x2 t, %3, a2; fma.rn.f16x2 %1, %2, b2, t; }"
        : "=&r"(xr), "=r"(xi) : "r"(R), "r"(I), "r"(m));
}
__device__ __forceinline__ void expand4(uint32_t are, uint32_t aim, uint32_t R0, uint32_t R1, uint32_t I0, uint32_t I1, H2C m4) {
    uint32_t R2, I2, R3, I3;
    hcmul(R2, I2, R0, I0, m4); hcmul(R3, I3, R1, I1, m4);
    sts128(are, R0, R1, R2, R3);
    sts128(aim, I0, I1, I2, I3);
}
__device__ __forceinline__ void expand8(uint32_t are, uint32_t aim, float sr, float si, float m1r, float m1i, float m2r, float m2i, H2C m4) {
    float r1, i1, r2, i2, r3, i3;
    cmul(r1, i1, sr, si, m1r, m1i); cmul(r2, i2, sr, si, m2r, m2i); cmul(r3, i3, r1, i1, m2r, m2i);
    expand4(are, aim, pack_f16(sr, r1), pack_f16(r2, r3), pack_f16(si, i1), pack_f16(i2, i3), m4);
}
__device__ __forceinline__ void put16(uint32_t a, uint32_t v) { sts16(a, v); sts16(a + 6, v); }

struct Params {
    const unsigned short *logdt, *dskip, *prm6[6], *x, *wr;
    __nv_bfloat16* out;
    Scratch* gs;
    unsigned zero;
};
__device__ __forceinline__ uint32_t tslot(uint32_t t) { return (t & 7) * 32 + ((t >> 4) & 24) + ((t >> 8) & 6) + ((t >> 6) & 1); }
#define CP(x) ((x) | zero)
#define PIN(x) asm volatile("or.b32 %0, %0, %1;" : "+r"(x) : "r"(zero))
__device__ __forceinline__ void wgmma32(float (&d)[4][4], const uint32_t (&a)[4], uint32_t dlo) {
    asm volatile("{ .reg .b64 ds; mov.b64 ds, {%20, %21};\n"
                 "wgmma.mma_async.sync.aligned.m64n32k16.f32.f16.f16 {%0,%1,%2,%3,%4,%5,%6,%7,%8,%9,%10,%11,%12,%13,%14,%15}, {%16,%17,%18,%19}, ds, 1, 1, 1, 0; }"
        : "+f"(d[0][0]), "+f"(d[0][1]), "+f"(d[0][2]), "+f"(d[0][3]), "+f"(d[1][0]), "+f"(d[1][1]), "+f"(d[1][2]), "+f"(d[1][3]),
          "+f"(d[2][0]), "+f"(d[2][1]), "+f"(d[2][2]), "+f"(d[2][3]), "+f"(d[3][0]), "+f"(d[3][1]), "+f"(d[3][2]), "+f"(d[3][3])
        : "r"(a[0]), "r"(a[1]), "r"(a[2]), "r"(a[3]), "r"(dlo), "n"(128 >> 4));
}

__global__ void __cluster_dims__(CS, 1, 1) __launch_bounds__(NTHR, 1)
fused_kernel(const __grid_constant__ Params prm, const __grid_constant__ CUtensorMap tmG, const __grid_constant__ CUtensorMap tmU,
             const __grid_constant__ CUtensorMap tmD, const __grid_constant__ CUtensorMap tmO, const __grid_constant__ CUtensorMap tmX, const __grid_constant__ CUtensorMap tmH)
{
    extern __shared__ __align__(1024) unsigned char smem[];
    const int tid = threadIdx.x, lane = tid & 31, warp = __shfl_sync(~0u, tid >> 5, 0);
    const int c = blockIdx.x >> 3, q = blockIdx.x & 7;
    const int nslot = (c < NCL - 1) ? 5 : 2;
    const int d0 = 40 * c;
    const uint32_t sb = opaque((uint32_t)__cvta_generic_to_shared(smem));
    const uint32_t mb = sb + SM_MB;
    Scratch& g_s = *prm.gs;
    const unsigned& zero = prm.zero;
    STAMP(0);

    if (warp >= 20) {
        unsigned epoch = 0;
        if (warp == 20) {
            if (lane == 0) {
#pragma unroll
                for (int i = 0; i < 13; i++)
                    asm volatile("mbarrier.init.shared::cta.b64 [%0], %1;" :: "r"(mb + i * 8), "r"((i == MB_R || i < 5) ? 2 : i == MB_Y ? 1 + 4 * nslot : 1) : "memory");
                asm volatile("fence.mbarrier_init.release.cluster;" ::: "memory");
                arm(mb + MB_W1 * 8, 92160); arm(mb + MB_W2 * 8, nslot * 9216); arm(mb + MB_KEY * 8, 256); arm(mb + MB_GU * 8, nslot * 1024); arm(mb + MB_T * 8, 576 * XW);
                const int bytes = max(min(18, L_ - 18 * (int)blockIdx.x), 1) * (D_ * 2);
                arm(mb + MB_R * 8, bytes);
            }
            __syncwarp();
        } else if (warp == 22) {
            epoch = ld_rlx(&g_s.epoch);
            if (lane < 18 ? 18 * c + lane < 256 : lane < 31) (lane < 18 ? &g_s.acc[256 * q + 18 * c] : &g_s.fin[13 * (int)blockIdx.x - 18])[lane] = make_float4(0.f, 0.f, 0.f, 0.f);
        } else if (warp == 23 && lane == 0) asm volatile("prefetch.tensormap [%0];" :: "l"(&tmX) : "memory");
        asm volatile("barrier.cluster.arrive.relaxed.aligned;" ::: "memory");
        bar_sync(12, NTHR);
        uint4 wv = make_uint4(0, 0, 0, 0), wv2, wv3;
        if (warp == 22) {
            if (lane == 0) { sts32(sb + SM_SC + 28, epoch); asm volatile("mbarrier.arrive.shared::cta.b64 _, [%0];" :: "r"(mb + MB_R * 8) : "memory"); }
            epoch++;
            asm volatile("fence.acq_rel.gpu;" ::: "memory");
            __syncwarp();
            if (lane == 0) asm volatile("red.relaxed.gpu.global.add.u32 [%0], 1;" :: "l"(&g_s.zcnt) : "memory");
            STAMP(1);
            wv2 = ldg128((const uint4*)prm.wr + lane); wv3 = ldg128((const uint4*)prm.wr + 32 + lane);
            if (lane < 8) wv = ldg128((const uint4*)prm.wr + 64 + lane);
            if (lane < 5) {
                uint4 v = make_uint4(0, 0, 0, 0);
                if (lane < nslot) v = ldg128((const uint4*)(prm.wr + d0) + lane);
                sts128(sb + SM_DW + lane * 16, v.x, v.y, v.z, v.w);
            }
            __syncwarp();
            if (lane < 5) asm volatile("mbarrier.arrive.shared::cta.b64 _, [%0];" :: "r"(mb + (MB_X + lane) * 8) : "memory");
        }
        if (warp == 21) {
            if (lane == 0) { asm volatile("prefetch.tensormap [%0];" :: "l"(&tmG) : "memory"); asm volatile("prefetch.tensormap [%0];" :: "l"(&tmU) : "memory"); asm volatile("prefetch.tensormap [%0];" :: "l"(&tmD) : "memory"); }
            __syncwarp();
            bar_sync(13, 768);
            asm volatile("fence.proxy.async.shared::cta;" ::: "memory");
#pragma unroll 1
            for (int i = 0; i < 24; i++) {
                if (lane == 0) tma2d(sb + SM_WG + i * 3840, i < 12 ? &tmG : &tmU, 320 * c + 8 * nslot * q, 48 * (i < 12 ? i : i - 12), mb + MB_W1 * 8);
            }
            STAMP(1);
            return;
        }
        if (warp == 20) {
            if (lane == 0) {
                asm volatile("cp.async.bulk.shared::cluster.global.mbarrier::complete_tx::bytes [%0], [%1], %2, [%3];"
                             :: "r"(sb + SM_ROW), "l"(prm.x + min(18 * (int)blockIdx.x, L_ - 1) * D_), "r"(max(min(18, L_ - 18 * (int)blockIdx.x), 1) * (D_ * 2)), "r"(mb + MB_R * 8) : "memory");
            }
            __syncwarp();
            mbar_wait(mb + MB_R * 8);
            if (lane == 0) {
                asm volatile("cp.async.bulk.tensor.5d.shared::cluster.global.mbarrier::complete_tx::bytes [%0], [%1, {%3, %4, %5, %5, %5}], [%2];"
                             :: "r"(sb + SM_XTL), "l"(&tmX), "r"(mb + MB_T * 8), "r"(d0 & ~15), "r"(8 * q), "r"(0) : "memory");
            }
            STAMP(6);
        }
        asm volatile("barrier.cluster.wait.aligned;" ::: "memory");
        bar_sync(13, 768);
        asm volatile("fence.proxy.async.shared::cta;" ::: "memory");
        {
            const int idx = lane * 3 + max(warp - 21, 0), sl = nslot - 1 - (idx >> 3), pe = (idx + q + 1) & 7;
            if (sl >= 0) {
                if (pe == q) arm(mb + (MB_X + sl) * 8, 7 * 512);
                else {
                    const uint32_t rb_ = mapa(sb, pe);
                    asm volatile("cp.async.bulk.shared::cluster.shared::cta.mbarrier::complete_tx::bytes [%0], [%1], 512, [%2];"
                                 :: "r"(rb_ + SM_U + 128 + q * UP + sl * US), "r"(sb + SM_XT + 128 + (q & 3) * 16 + pe * YP + sl * YS), "r"(rb_ + SM_MB + (MB_X + sl) * 8) : "memory");
                }
            }
        }
        STAMP(1);
        if (warp == 20 && lane == 0) { asm volatile("prefetch.tensormap [%0];" :: "l"(&tmO) : "memory"); asm volatile("prefetch.tensormap [%0];" :: "l"(&tmH) : "memory"); }
        if (warp == 22) {
            __syncwarp();
            mbar_wait(mb + (MB_X + 1) * 8);
            const uint32_t old = (epoch & 1) ? 0u : 0x40004000u;
#pragma unroll
            for (int t = 0; t < 2; t++)
                if ((lane & 7) < 6) g_s.cand[((q * 8 + 4 * t + (lane >> 3)) * NCL + c) * 6 + (lane & 7)] = make_uint4(old, old, old, old);
            float a[4] = {0.f, 0.f, 0.f, 0.f};
            const uint32_t one = 0x3F803F80u;
            mma_bf16(a, one, one, one, one, wv.x, wv.y);  mma_bf16(a, one, one, one, one, wv.z, wv.w);
            mma_bf16(a, one, one, one, one, wv2.x, wv2.y); mma_bf16(a, one, one, one, one, wv2.z, wv2.w);
            mma_bf16(a, one, one, one, one, wv3.x, wv3.y); mma_bf16(a, one, one, one, one, wv3.z, wv3.w);
            float s = a[0] + a[1];
            s += __shfl_xor_sync(~0u, s, 1); s += __shfl_xor_sync(~0u, s, 2);
            stsf(sb + SM_SC + 24, s);
            __syncwarp();
            if (lane == 0) {
                int n = 0;
                while ((int)(ld_acq(&g_s.zcnt) - epoch * NCTA) < 0 && ++n < SPIN_LIMIT) __nanosleep(200);
                arm(mb + MB_Y * 8, 8 * 512 * nslot);
                if (blockIdx.x == 0) g_s.epoch = epoch;
            }
            STAMP(2);
            return;
        }
        if (warp == 23) {
#pragma unroll 1
            for (int kk = nslot - 1; kk >= 0; kk--) {
                __syncwarp();
                bar_sync(6 + kk, 160);
                if (lane == 0) { asm volatile("fence.proxy.async.shared::cta;" ::: "memory"); tma2d(sb + SM_FAR + kk * FAR_SZ, &tmD, 72 * q, 320 * c + 64 * kk, mb + MB_W2 * 8); }
            }
            return;
        }
        __syncwarp();
        bar_sync(14, 672);
        if (lane == 0) {
            asm volatile("fence.proxy.async.shared::cta;" ::: "memory");
            asm volatile("cp.async.bulk.tensor.5d.global.shared::cta.bulk_group [%0, {%2, %4, %4, %4, %3}], [%1];" :: "l"(&tmH), "r"(sb + SM_XT + 16384), "r"(d0 + ((c & 1) ? 0 : 32)), "r"(8 * q), "r"(0) : "memory");
            asm volatile("cp.async.bulk.tensor.5d.global.shared::cta.bulk_group [%0, {%2, %4, %4, %4, %3}], [%1];" :: "l"(&tmO), "r"(sb + SM_XT), "r"(d0 + (c & 1) * 8), "r"(8 * q), "r"(0) : "memory");
            asm volatile("cp.async.bulk.commit_group;" ::: "memory");
            asm volatile("cp.async.bulk.wait_group 0;" ::: "memory");
            asm volatile("fence.proxy.async.global;" ::: "memory");
            asm volatile("mbarrier.arrive.shared::cta.b64 _, [%0];" :: "r"(mb + MB_OUT * 8) : "memory");
        }
        STAMP(2);
        return;
    }

    const int g = lane >> 2, cq = lane & 3;
    const int k = warp >> 2, wq = warp & 3;
    const int trow = 18 * blockIdx.x + warp;
    const bool rowact = warp < 18 && trow < L_;
    const int dch = min(d0 + 8 * k + q, D_ - 1);
    uint32_t pv[6];
#pragma unroll
    for (int i = 0; i < 6; i++) pv[i] = ldg16(prm.prm6[i] + (uint32_t)(dch * 128 + wq * 32 + lane));
    const uint32_t pLdt = ldg16(prm.logdt + dch), pD = ldg16(prm.dskip + dch);
    const int tn = 16 * (warp & 15) + g;
    uint32_t xa[5], xb[5];
    asm volatile("barrier.cluster.arrive.relaxed.aligned;" ::: "memory");
    uint4* const st1p = &g_s.st1[(((trow >> 3) & 7) * 256 + ((trow >> 6) & 31) * 8 + (trow & 7)) * 2 + (lane >> 2)];
    const bool pub = rowact && (lane & 0x1B) == 0;
    if (pub) st_rlx128(st1p, 0, 0, 0, 0);
    {
        const uint32_t za = sb + SM_P + tid * 16;
        sts128(za, 0, 0, 0, 0);
        if (tid < (SM_MISC - SM_P) / 16 - 640) sts128(za + 10240, 0, 0, 0, 0);
        sts128(sb + ((wq & 2) ? SM_U : SM_XT + (q & 3) * 16) + ((tid >> 3) & 7) * ((wq & 2) ? UP : YP) + k * YS + (lane & 7) * 16, 0, 0, 0, 0);
    }
    bar_sync(12, NTHR);
    const uint32_t dep = lds32(sb + SM_P);
#define PV(x) __uint_as_float(__byte_perm(dep, x, 0x5410))
    STAMP(1);
    const uint32_t fb = sb + SM_FAR + k * FAR_SZ;
    const uint32_t pn = sb + SM_PN + k * PN_SZ, pf = sb + SM_PF + k * PF_SZ;
    unsigned epoch;
    {
        const uint32_t kb = fb + wq * 3072;
        const uint32_t kl = kb + lane * 16;
        uint32_t Af[4][4];
        float sr, si, z1r, z1i, z2r, z2i, z4r, z4i, hr, hi_;
        {
            const float dt = bfr(ex2f(PV(pLdt) * 1.4426950408889634f));
            const float e2 = dt * PV(pv[0]) * 1.4426950408889634f, an = dt * PV(pv[1]);
            cmul(sr, si, PV(pv[4]), PV(pv[5]), dt * PV(pv[2]), dt * PV(pv[3]));
            const unsigned E = min(max(__reduce_max_sync(~0u, __float_as_uint(fmaxf(fmaxf(fabsf(sr), fabsf(si)), fabsf(PV(pD)) * (1.f / 8192.f)))) >> 23, 1u), 253u);
            const float sc = __uint_as_float((254u - E) << 23);
            sr *= sc; si *= -sc;
            sts64(sb + SM_KG + warp * 8, E, __reduce_add_sync(~0u, __float2int_rn(sr * 16777216.f)));
            float ar, ai, br, bi, cr, ci, dr, di;
            { const float m = ex2f(e2 * 8.f); ar = m * __cosf(an * 8.f); ai = m * __sinf(an * 8.f); }
            csq(br, bi, ar, ai); csq(cr, ci, br, bi); csq(dr, di, cr, ci);
            const H2C m4 = splat(cr, ci);
            {
                float r3, i3;
                cmul(r3, i3, ar, ai, br, bi);
                expand4(kl, kl + 1024, pack_f16(1.f, ar), pack_f16(br, r3), pack_f16(0.f, ai), pack_f16(bi, i3), m4);
            }
            expand8(kl + 512, kl + 1536, dr, di, ar, ai, br, bi, m4);
            { const float m = ex2f(e2); z1r = m * __cosf(an); z1i = -m * __sinf(an); }
            cexp_s(hr, hi_, e2 * 128.f, an * (-128.f * 0.15915494309189535f));
            csq(z2r, z2i, z1r, z1i); csq(z4r, z4i, z2r, z2i);
        }
        __syncwarp();
#pragma unroll
        for (int ks = 0; ks < 4; ks++) ldsm4t(Af[ks], kb + (lane >> 3) * 512 + (lane & 7) * 16 + ks * 128);
        STAMP(2);
        const uint32_t la = kb + ((lane >> 3) & 1) * 512 + (lane >> 4) * 128 + (lane & 7) * 16;
        uint32_t kp[5][2], b0[4], b1[4], b2[4], b3[4];
        auto mm2 = [&](int t) {
            float a0[4] = {0.f, 0.f, 0.f, 0.f}, a1[4] = {0.f, 0.f, 0.f, 0.f};
            mma_f16(a0, Af[0], b0[0], b0[1]); mma_f16(a1, Af[0], b2[0], b2[1]); mma_f16(a0, Af[1], b0[2], b0[3]); mma_f16(a1, Af[1], b2[2], b2[3]);
            mma_f16(a0, Af[2], b1[0], b1[1]); mma_f16(a1, Af[2], b3[0], b3[1]); mma_f16(a0, Af[3], b1[2], b1[3]); mma_f16(a1, Af[3], b3[2], b3[3]);
            kp[t][0] = pack_f16(a0[1], a0[0]); kp[t][1] = pack_f16(a0[3], a0[2]); kp[t + 1][0] = pack_f16(a1[1], a1[0]); kp[t + 1][1] = pack_f16(a1[3], a1[2]);
        };
        auto ln1 = [&]() {
        mbar_wait(mb + MB_R * 8);
        epoch = lds32(sb + SM_SC + 28) + 1;
        {
            const uint32_t ra = sb + SM_ROW + warp * (D_ * 2);
            const uint4 r0 = lds128(ra + lane * 16), r1 = lds128(ra + 512 + lane * 16);
            const uint32_t rx[9] = {r0.x, r0.y, r0.z, r0.w, r1.x, r1.y, r1.z, r1.w, lds32(ra + 1024 + lane * 4)};
            float a0 = bf_lo(rx[0]), a1 = bf_hi(rx[0]), c0 = a0 * a0, c1 = a1 * a1;
#pragma unroll
            for (int i = 1; i < 9; i++) { const float l = bf_lo(rx[i]), h = bf_hi(rx[i]); a0 += l; a1 += h; c0 = fmaf(l, l, c0); c1 = fmaf(h, h, c1); }
            a0 += a1; c0 += c1;
            float s1 = ((lane & 1) ? c0 : a0) + __shfl_xor_sync(~0u, (lane & 1) ? a0 : c0, 1);
#pragma unroll
            for (int o = 2; o < 32; o <<= 1) s1 += __shfl_xor_sync(~0u, s1, o);
            const float s2 = __shfl_xor_sync(~0u, s1, 1);
            const uint32_t ms = ln_stats(s1, s2);
            const uint32_t p0 = __byte_perm(ms, epoch | 0x8000u, 0x5410), p1 = rsplit(rcpf(bf_hi(ms)));
            if (pub) st_rlx128(st1p, p0, p1, p0, p1);
        }
        mbar_wait(mb + MB_R * 8);
        STAMP(1);
        };
        const uint4* sp = &g_s.st1[(256 * q + tn) * 2];
        uint2 sa, sc;
        auto poll = [&]() { sa = ld_rlx64(sp); sc = ld_rlx64(sp + 16); };
        auto norm = [&]() {
        STAMP(3);
        if (warp < 16) {
            uint32_t va[5], vc[5];
            poll();
            mbar_wait(mb + MB_T * 8);
            {
                const uint32_t xt = sb + SM_XTL + (c & 1) * 16 + (72 * wq + 18 * k + g) * (2 * XW);
                uint4 a4 = lds128(xt + cq * 16), b4 = lds128(xt + cq * 16 + 18 * XW);
                va[0] = a4.x; va[1] = a4.y; va[2] = a4.z; va[3] = a4.w; va[4] = lds32(xt + 64 + cq * 4);
                vc[0] = b4.x; vc[1] = b4.y; vc[2] = b4.z; vc[3] = b4.w; vc[4] = lds32(xt + (64 + 18 * XW) + cq * 4);
            }
            const int d4 = 2 * (lane >> 3) + (lane & 1), d1_ = lane & 7;
            const uint32_t own = SM_U + 128 + q * (UP - YP), oth = SM_XT + 128 + (q & 3) * 16;
            uint32_t a4 = sb + warp * 32 + d4 * YP + (d4 == q ? own : oth) + ((lane & 7) >> 1) * YS;
            uint32_t a1 = sb + warp * 32 + d1_ * YP + (d1_ == q ? own : oth) + 4 * YS + (lane & 8) * 2;
            PIN(a4); PIN(a1);
            uint32_t tag = __byte_perm(epoch | 0x8000u, 0, 0x1010);
            PIN(tag);
            mbar_wait(mb + MB_T * 8);
            int n = 0;
            while (__byte_perm(sa.x, sc.x, 0x7632) != tag && ++n < SPIN_LIMIT) poll();
            STAMP(4);
#pragma unroll
            for (int i = 0; i < 5; i++) {
                va[i] = norm2(va[i], sa.x, sa.y); va[i] = pack_f16(bf_lo(va[i]), bf_hi(va[i]));
                vc[i] = norm2(vc[i], sc.x, sc.y); vc[i] = pack_f16(bf_lo(vc[i]), bf_hi(vc[i]));
            }
            stsm4t(a4, va[0], va[1], va[2], va[3]); stsm4t(a4 + 16, vc[0], vc[1], vc[2], vc[3]); stsm2t(a1, va[4], vc[4]);
            {
            const uint32_t xh = sb + SM_XTL + (c & 1) * 16 + (9 * g + 144 * (warp & 1) + (warp >> 1)) * (2 * XW);
            const uint4 c4 = lds128(xh + cq * 16), d4_ = lds128(xh + cq * 16 + 144 * XW);
            xa[0] = c4.x; xa[1] = c4.y; xa[2] = c4.z; xa[3] = c4.w; xa[4] = lds32(xh + 64 + cq * 4);
            xb[0] = d4_.x; xb[1] = d4_.y; xb[2] = d4_.z; xb[3] = d4_.w; xb[4] = lds32(xh + (64 + 144 * XW) + cq * 4);
            }
        }
        STAMP(5);
        bar_sync(13, 768);
        Af[0][0] |= lds32(sb + SM_P);
        };
        cmul(sr, si, sr, si, z1r, z1i);
        {
            const H2C h4 = splat(z4r, z4i);
            expand8(kl, kl + 512, sr, si, z1r, z1i, z2r, z2i, h4);
            cmul(sr, si, sr, si, hr, hi_);
            expand8(kl + 1024, kl + 1536, sr, si, z1r, z1i, z2r, z2i, h4);
        }
        __syncwarp();
        ldsm4t(b0, la); ldsm4t(b1, la + 256); ldsm4t(b2, la + 1024); ldsm4t(b3, la + 1280);
        cmul(z1r, z1i, z1r, z1i, hr, hi_);
        cmul(sr, si, sr, si, z1r, z1i);
        ln1();
        expand8(kl, kl + 512, sr, si, z2r, z2i, z4r, z4i, splat(hr, hi_));
        csq(z1r, z1i, z1r, z1i);
        cmul(sr, si, sr, si, z1r, z1i);
        csq(z2r, z2i, hr, hi_);
        expand8(kl + 1024, kl + 1536, sr, si, z4r, z4i, hr, hi_, splat(z2r, z2i));
        csq(z1r, z1i, z1r, z1i);
        cmul(sr, si, sr, si, z1r, z1i);
        csq(z4r, z4i, z2r, z2i);
        expand8(kl + 2048, kl + 2560, sr, si, hr, hi_, z2r, z2i, splat(z4r, z4i));
        norm();
        mm2(0);
        __syncwarp();
        ldsm4t(b0, la); ldsm4t(b1, la + 256); ldsm4t(b2, la + 1024); ldsm4t(b3, la + 1280);
        mm2(2);
        ldsm4t(b0, la + 2048); ldsm4t(b1, la + 2304);
#pragma unroll
        for (int t = 0; t < 4; t++) sts64(kb + lane * 8 + 1024 + t * 256, kp[t][0], kp[t][1]);
        {
            float a0[4] = {0.f, 0.f, 0.f, 0.f}, a1[4] = {0.f, 0.f, 0.f, 0.f};
            mma_f16(a0, Af[0], b0[0], b0[1]); mma_f16(a1, Af[1], b0[2], b0[3]); mma_f16(a0, Af[2], b1[0], b1[1]); mma_f16(a1, Af[3], b1[2], b1[3]);
            sts64(kb + lane * 8 + 2048, pack_f16(a0[1] + a1[1], a0[0] + a1[0]), pack_f16(a0[3] + a1[3], a0[2] + a1[2]));
        }
        bar_sync(1 + k, 128);
        const uint4 m01 = lds128(sb + SM_KG + k * 32), m23 = lds128(sb + SM_KG + k * 32 + 16);
        const unsigned Em = max(max(m01.x, m01.z), max(m23.x, m23.z));
        const float f0 = __uint_as_float(max((int)(127 + m01.x - Em), 0) << 23), f1 = __uint_as_float(max((int)(127 + m01.z - Em), 0) << 23),
                    f2 = __uint_as_float(max((int)(127 + m23.x - Em), 0) << 23), f3 = __uint_as_float(max((int)(127 + m23.z - Em), 0) << 23);
        const uint32_t r0 = pack_f16(f0, f0), r1 = pack_f16(f1, f1), r2 = pack_f16(f2, f2), r3 = pack_f16(f3, f3);
        const int tq = (wq + k) & 3;
        const uint32_t ra = fb + lane * 8 + tq * 256 + 1024;
        const uint2 p0 = lds64(ra), p1 = lds64(ra + 3072), p2 = lds64(ra + 6144), p3 = lds64(ra + 9216);
        uint32_t w0 = hadd2(hfma2(p0.x, r0, hmul2(p1.x, r1)), hfma2(p2.x, r2, hmul2(p3.x, r3)));
        uint32_t w1 = hadd2(hfma2(p0.y, r0, hmul2(p1.y, r1)), hfma2(p2.y, r2, hmul2(p3.y, r3)));
        const bool last = lane == 31;
        if (tq < 2) {
            const uint32_t rc = fb + lane * 8 + tq * 4 + 2048;
            const uint32_t w4 = hmul2(hadd2(hfma2(lds32(rc), r0, hmul2(lds32(rc + 3072), r1)), hfma2(lds32(rc + 6144), r2, hmul2(lds32(rc + 9216), r3))), 0x18001800u);
            const uint32_t ph = pf + (P_H7 + 16 * tq) + (g & 1) * (2 * P_HS) + cq * 64 + (g >> 1) * 4;
            put16(ph, w4 >> 16); put16(ph + 32, w4);
            const uint32_t pa = pn + (4 + 512 * tq) + lane * 8;
            sts16(pa, w0 >> 16); sts32(pa + 4, w0); sts16(pa + 10, w0);
            sts16(pa + 256, w1 >> 16); sts32(pa + 260, w1); sts16(pa + 266, w1);
            if (last) {
                sts32(sb + SM_SC + k * 4, Em * 0x00800080u);
                put16(tq ? pa + 264 : pn,
                      tq ? w1 : pack_f16(((float)(int)m01.y * f0 + (float)(int)m01.w * f1 + (float)(int)m23.y * f2 + (float)(int)m23.w * f3) * (1.f / 16777216.f)
                                         + __uint_as_float(pD << 16) * __uint_as_float((254u - Em) << 23), 0.f));
            }
        } else if (tq == 2) {
            const uint32_t pa = pn + 258 * 4 + (cq & 1) * 16 + (cq >> 1) * 512 + g * 32;
            if (last) { put16(pf, hmul2(w1, 0x18001800u)); w1 = hadd2(w1, hneg2(__byte_perm(w1, 0, 0x1010))); }
            const uint32_t b0 = __byte_perm(w0, 0, 0x1010), b1 = __byte_perm(w1, 0, 0x1010);
            sts16(pa, w0 >> 16); sts32(pa + 4, w0); sts64(pa + 8, b0, b0); sts16(pa + 18, w0);
            sts16(pa + 256, w1 >> 16); sts32(pa + 260, w1); sts64(pa + 264, b1, b1); sts16(pa + 274, w1);
        } else {
            const uint32_t pa = pf + ((g & 1) ? 3 * P_GS : P_GS) + cq * 32 + (g >> 1) * 4;
            const uint32_t pb = pa + ((g & 1) ? 4 - 3 * P_GS : P_GS);
            w0 = hmul2(w0, 0x18001800u); w1 = hmul2(w1, 0x18001800u);
            put16(pa, w0 >> 16); put16(pb, w0); put16(pa + 16, w1 >> 16); put16(pb + 16, w1);
            if (last) put16(pf + P_H7 + P_HS, w1);
        }
        bar_sync(1 + k, 128);
    }
    STAMP(6);

    asm volatile("barrier.cluster.wait.aligned;" ::: "memory");
    mbar_wait(mb + (MB_X + (k < nslot ? k : 0)) * 8);
    STAMP(7);
    if (k < nslot) {
        const int role = (wq + k) & 3;
        const uint32_t ub = sb + SM_U + k * US + 128;
        if (role) {
            const int r = (3 - role) * 32 + lane;
            const uint32_t a1 = ub + (r & 3) * (2 * UP) + (r >> 2) * 16, a0 = a1 + ((r & 3) ? -2 * UP : 6 * UP - 16);
            const uint4 q0 = lds128(a0), q1 = lds128(a0 + UP), q2 = lds128(a1), q3 = lds128(a1 + UP);
            const uint32_t U[16] = {q0.x, q0.y, q0.z, q0.w, q1.x, q1.y, q1.z, q1.w, q2.x, q2.y, q2.z, q2.w, q3.x, q3.y, q3.z, q3.w};
            uint32_t V[14], Q[14], R4[12], T[8];
#pragma unroll
            for (int i = 2; i < 14; i++) { V[i] = __byte_perm(U[i], U[i + 1], 0x5432); Q[i] = hadd2(U[i], V[i]); }
#pragma unroll
            for (int i = 2; i < 12; i++) R4[i] = hadd2(Q[i], Q[i + 1]);
            const uint32_t rb = fb + r * 16;
#pragma unroll
            for (int i = 0; i < 8; i++) T[i] = hadd2(V[5 + i], Q[6 + i]);
            sts128(rb + F_E3, T[0], T[1], T[2], T[3]); sts128(rb + F_O3 + 16, T[4], T[5], T[6], T[7]);
#pragma unroll
            for (int i = 0; i < 8; i++) T[i] = hadd2(R4[3 + i], U[5 + i]);
            sts128(rb + F_O5, T[0], T[1], T[2], T[3]); sts128(rb + F_E5, T[4], T[5], T[6], T[7]);
            if (role != 1) {
#pragma unroll
                for (int i = 0; i < 8; i++) T[i] = hadd2(T[i], hadd2(V[2 + i], V[5 + i]));
                sts128(rb + F_E7, T[0], T[1], T[2], T[3]); sts128(rb + F_O7, T[4], T[5], T[6], T[7]);
#pragma unroll
                for (int i = 0; i < 8; i++) T[i] = hadd2(R4[2 + i], hadd2(R4[4 + i], U[6 + i]));
                sts128(rb + F_O9, T[0], T[1], T[2], T[3]); sts128(rb + F_E9 + 16, T[4], T[5], T[6], T[7]);
                sts128(rb + F_E2, Q[6], Q[7], Q[8], Q[9]); sts128(rb + F_O2, Q[10], Q[11], Q[12], Q[13]);
            }
        } else if (lane < 8) {
            uint32_t v[5];
#pragma unroll
            for (int i = 0; i < 5; i++) { const int t = 6 + lane + i; v[i] = lds16(ub + 23 * 16 + (t < 16 ? (6 + (t >> 3)) * UP : 16) + (t & 7) * 2); }
            const uint32_t s = hadd2(hadd2(hadd2(v[0], v[1]), hadd2(v[2], v[3])), v[4]);
            sts16(fb + F_O5 + 96 * 16 + lane * 2, s);
            sts32(fb + (lane < 4 ? F_O3 : F_E9 - 16) + lane * 4, 0);
        }
        bar_sync(1 + k, 128);
        float acc[4][4];
        uint32_t Q[4][4];
        {
            const int h = role & 1, part = role >> 1;
            const uint32_t po = pf + (g - 2 * cq) * 4;
            float fa[7][4];
#pragma unroll
            for (int a = 0; a < 7; a++) fa[a][0] = fa[a][1] = fa[a][2] = fa[a][3] = 0.f;
            uint32_t B[3][4];
            Q[0][2] = zero;
#pragma unroll 1
            for (int s = 2 * part + 1; s >= 2 * part; s--) {
#pragma unroll
                for (int i = 0; i < 3; i++) { Q[i][0] = lds32(po + s * P_GS + i * 64); Q[i][1] = lds32(po + s * P_GS + (i * 64 + 32)); }
                const uint32_t ba = fb + lane * 16 + ((s & 1) * F_E3 + (part == h ? 0 : F_O5 + h * 16));
#pragma unroll
                for (int i = 0; i < 3; i++) ldsm4t(B[i], ba + i * 512);
#pragma unroll
                for (int i = 0; i < 3; i++) { Q[i][3] = CP(Q[i][0]); if (i) Q[i][2] = CP(Q[i - 1][1]); }
#pragma unroll
                for (int dl = 0; dl < 3; dl++)
#pragma unroll
                    for (int ap = 0; ap < 6 - dl; ap++) mma_f16(fa[ap + 1 + dl], Q[dl], B[ap >> 1][2 * (ap & 1)], B[ap >> 1][2 * (ap & 1) + 1]);
            }
#pragma unroll 1
            for (int s = role; s == 1; s++) {
                ldsm2t(B[0][0], B[0][1], fb + ((lane & 15) == 15 ? F_O5 : F_O3));
#pragma unroll
                for (int dl = 0; dl < 3; dl++) mma_f16(fa[dl], Q[dl], B[0][0], B[0][1]);
            }
#pragma unroll 1
            for (int s = part; s <= 2 * part; s++) {
#pragma unroll
                for (int i = 0; i < 4; i++) { Q[i][0] = lds32(po + s * P_HS + (P_H7 + i * 64)); Q[i][1] = lds32(po + s * P_HS + (P_H7 + i * 64 + 32)); }
                const uint32_t ba = fb + lane * 16 + (F_E7 + s * 1024 + h * F_H);
                ldsm4t(B[0], ba); ldsm4t(B[1], ba + 512);
#pragma unroll
                for (int i = 0; i < 4; i++) { Q[i][3] = CP(Q[i][0]); if (i) Q[i][2] = CP(Q[i - 1][1]); }
#pragma unroll
                for (int dl = 0; dl < 4; dl++) {
#pragma unroll
                    for (int ap = 0; ap < 4 - dl; ap++) mma_f16(fa[ap + 3 + dl], Q[dl], B[ap >> 1][2 * (ap & 1)], B[ap >> 1][2 * (ap & 1) + 1]);
                    if (s == 1) break;
                }
            }
            const uint32_t da = fb + role * 2048 + (lane & 3) * 512 + (((lane >> 2) ^ ((lane & 3) * 2)) << 4);
            bar_sync(1 + k, 128);
            stsm4(da, 0u, 0u, pack_f16(fa[0][0], fa[0][1]), pack_f16(fa[0][2], fa[0][3]));
#pragma unroll
            for (int i = 1; i < 4; i++)
                stsm4(da + i * 128, pack_f16(fa[2 * i - 1][0], fa[2 * i - 1][1]), pack_f16(fa[2 * i - 1][2], fa[2 * i - 1][3]),
                      pack_f16(fa[2 * i][0], fa[2 * i][1]), pack_f16(fa[2 * i][2], fa[2 * i][3]));
            Q[0][0] = (g == 2 * cq) ? 0x6000u : ((g == 2 * cq + 1) ? 0x60000000u : 0u);
            Q[0][1] = 0; Q[0][3] = CP(Q[0][0]);
            const uint32_t ra = fb + (lane >> 3) * 2048 + wq * 512 + (((lane & 7) ^ (wq * 2)) << 4);
            bar_sync(1 + k, 128);
#pragma unroll
            for (int i = 0; i < 4; i++) {
                ldsm4(B[0], ra + i * 128);
                acc[i][0] = acc[i][1] = acc[i][2] = acc[i][3] = 0.f;
                mma_f16(acc[i], Q[0], hadd2(B[0][0], B[0][2]), hadd2(B[0][1], B[0][3]));
            }
        }
        bar_arrive(6 + k, 160);
        STAMP(8);
        const uint32_t inv = lds32(sb + SM_SC + k * 4);
        uint32_t yd = mapa(sb, 2 * wq) + (SM_XT + 128 + q * YP + k * YS + (k >> 2) * (q >> 1) * 16) + lane * 16;
        PIN(yd);
        {
            uint32_t pp = pn + (16 * (wq - 3) + g - 2 * cq) * 4;
            uint32_t dlo = (((ub + 6 * UP) & 0x3FFFF) >> 4) | ((UP >> 4) << 16);
            uint32_t R[4][4];
            auto loadQ = [&](uint32_t (&X)[4][4], uint32_t prev) {
#pragma unroll
                for (int i = 0; i < 4; i++) { X[i][0] = lds32(pp + i * 64); X[i][1] = lds32(pp + i * 64 + 32); }
                X[0][2] = CP(prev);
#pragma unroll
                for (int i = 0; i < 4; i++) { X[i][3] = CP(X[i][0]); if (i) X[i][2] = CP(X[i - 1][1]); }
                pp += 256;
            };
            auto issue = [&](uint32_t (&X)[4][4]) {
                asm volatile("wgmma.fence.sync.aligned;" ::: "memory");
#pragma unroll
                for (int i = 0; i < 4; i++) wgmma32(acc, X[i], dlo - i * (2 * UP >> 4));
                asm volatile("wgmma.commit_group.sync.aligned;" ::: "memory");
                dlo -= 1;
            };
            loadQ(Q, 0);
#pragma unroll 1
            for (int dl = 0; dl < 4; dl++) {
                issue(Q);
                asm volatile("wgmma.wait_group.sync.aligned 1;" ::: "memory");
                loadQ(R, Q[3][1]);
                issue(R);
                asm volatile("wgmma.wait_group.sync.aligned 1;" ::: "memory");
                loadQ(Q, R[3][1]);
            }
            issue(Q);
            asm volatile("wgmma.wait_group.sync.aligned 0;" ::: "memory");
        }
        const uint32_t pstep = mapa(sb, 1) - mapa(sb, 0), ym = mapa(mb + MB_Y * 8, 2 * wq);
#pragma unroll
        for (int e = 0; e < 2; e++)
            st_async4(yd + e * pstep, bmul2(pack_bf16(acc[0][2 * e], acc[0][2 * e + 1]), inv), bmul2(pack_bf16(acc[1][2 * e], acc[1][2 * e + 1]), inv),
                      bmul2(pack_bf16(acc[2][2 * e], acc[2][2 * e + 1]), inv), bmul2(pack_bf16(acc[3][2 * e], acc[3][2 * e + 1]), inv), ym + e * pstep);
        if (lane == 0) asm volatile("mbarrier.arrive.shared::cta.b64 _, [%0];" :: "r"(mb + MB_Y * 8) : "memory");
    }
    STAMP(9);
    uint32_t ha[5], hb[5];
    if (warp < 16) {
        const uint4 wk = lds128(sb + SM_DW + cq * 16);
        uint32_t sel[5] = {wk.x, wk.y, wk.z, wk.w, lds32(sb + SM_DW + 64 + cq * 4)}, sel2[5];
#pragma unroll
        for (int i = 0; i < 5; i++) {
            if (!(g & 1)) sel[i] = 0x3F803F80u;
            sel2[i] = sel[i]; PIN(sel2[i]);
        }
        const uint32_t y4 = sb + SM_XT + 128 + warp * 32 + (2 * (lane >> 3) + (lane & 1)) * YP + ((lane & 7) >> 1) * YS;
        const uint32_t y1 = sb + SM_XT + 128 + warp * 32 + (lane & 7) * YP + 4 * YS + (lane & 8) * 2 + (lane & 6) * 8;
        uint32_t ao = (256 * q + tn) * 16, hta = sb + SM_HT + tn * 80;
        PIN(ao); PIN(hta);
        mbar_wait(mb + MB_Y * 8);
        STAMP(10);
        float ca[4] = {0.f, 0.f, 0.f, 0.f}, cb[4] = {0.f, 0.f, 0.f, 0.f};
        {
            uint32_t ya[4], yb[4], yc, yd;
            ldsm4t(ya, y4); ldsm4t(yb, y4 + 16); ldsm2t(yc, yd, y1);
#pragma unroll
            for (int i = 0; i < 4; i++) { ha[i] = badd2(xa[i], ya[i]); hb[i] = badd2(xb[i], yb[i]); }
            ha[4] = badd2(xa[4], yc); hb[4] = badd2(xb[4], yd);
        }
        if (nslot != 5) {
            ha[4] = hb[4] = 0;
            if (cq >= 2) ha[0] = ha[1] = ha[2] = ha[3] = hb[0] = hb[1] = hb[2] = hb[3] = 0;
        }
#pragma unroll
        for (int i = 0; i < 5; i++) { mma_bf16_k8(ca, ha[i], sel[i], ha[i]); mma_bf16_k8(cb, hb[i], sel2[i], hb[i]); }
        if (!(g & 1)) { ca[1] = ca[0]; cb[1] = cb[0]; }
        if (cq == (g >> 1)) {
            asm volatile("red.relaxed.gpu.global.add.v4.f32 [%0], {%1,%2,%3,%4};" :: "l"((char*)g_s.acc + ao), "f"(1.0f), "f"(ca[1]), "f"(ca[2]), "f"(ca[3]) : "memory");
            asm volatile("red.relaxed.gpu.global.add.v4.f32 [%0], {%1,%2,%3,%4};" :: "l"((char*)g_s.acc + ao + 128), "f"(1.0f), "f"(cb[1]), "f"(cb[2]), "f"(cb[3]) : "memory");
        }
        sts128(hta + cq * 16, ha[0], ha[1], ha[2], ha[3]); sts32(hta + 64 + cq * 4, ha[4]);
        sts128(hta + cq * 16 + 640, hb[0], hb[1], hb[2], hb[3]); sts32(hta + 704 + cq * 4, hb[4]);
        STAMP(11);
    }
    const int kq = warp / 5, mt = warp - 5 * kq;
    const int mi = lane >> 3, mr = lane & 7;
    const unsigned tk = (unsigned)tid / 72u, ck = tid - tk * 72;
    uint32_t A[9][4];
    auto loadA = [&]() {
        mbar_wait(mb + MB_W1 * 8);
        const uint32_t aa = sb + (mi & 1) * SM_WU + (8 * (mi >> 1) + mr) * 80 + (144 * 80 * kq + mt * 16);
#pragma unroll
        for (int s = 0; s < 9; s++) ldsm4t(A[s], aa + s * 1280);
    };
    const uint32_t par = (epoch & 1) ? 0x40004000u : 0u;
    uint32_t pk0 = mapa(sb, 2 * cq), go = (ck / 5u + ck) * 16, co = ((q * 8 * NCL + c) * 6 + cq) * 16;
    PIN(pk0); PIN(go); PIN(co);
    if (warp < 8) {
        const float wsum = ldsf(sb + SM_SC + 24);
        const uint32_t idx = 2047 - (512 * ((tid >> 1) & 3) + 128 * ((tid >> 3) & 3) + 64 * (tid & 1) + 8 * q + warp);
        uint4 s; int n = 0;
        do { s = ld_rlx128(&g_s.acc[256 * q + tid]); } while (__uint_as_float(s.x) != (float)NCL && ++n < SPIN_LIMIT);
        STAMP(16);
        const uint32_t ox = __shfl_xor_sync(~0u, (lane & 1) ? s.z : s.w, 1);
        const uint32_t ms = ln_stats(__uint_as_float((lane & 1) ? ox : s.z), __uint_as_float(s.y));
        const float rs = rcpf(bf_hi(ms));
        const uint32_t rb = pack_bf16(0.f, fmaf(-bf_lo(ms), wsum, __uint_as_float((lane & 1) ? s.w : ox)) * rs);
        const uint32_t key = (((rb ^ (((int)rb >> 31) | 0x80000000u)) >> 16) << 11) | idx;
        sts32(sb + SM_KEY + tid * 4, key);
        __syncwarp();
        const uint32_t rank = rank4<8, 16>(sb + SM_KEY + warp * 128, key);
        if (rank < 8) sts32(sb + SM_CAND + warp * 32 + rank * 4, key);
        sts64(sb + SM_ST + tid * 8, ms, rsplit(rs));
    } else loadA();
    if (warp < 16) {
        STAMP(17);
        bar_sync(12, 512);
        STAMP(18);
        if (warp < 8) {
            const uint32_t mk = lds32(sb + SM_CAND + (tid >> 2) * 4);
            uint32_t rank = rank4<4, 64>(sb + SM_CAND + cq * 16, mk);
            rank += __shfl_xor_sync(~0u, rank, 1); rank += __shfl_xor_sync(~0u, rank, 2);
            if (rank < 8) {
                const uint32_t pk1 = pk0 + (mapa(sb, 1) - mapa(sb, 0));
                st_async1(pk0 + (SM_RK + q * 32) + rank * 4, mk, pk0 + (SM_MB + MB_KEY * 8));
                st_async1(pk1 + (SM_RK + q * 32) + rank * 4, mk, pk1 + (SM_MB + MB_KEY * 8));
                const uint32_t t = tslot(~mk);
                const uint2 sv = lds64(sb + SM_ST + t * 8);
                const uint4 hv = lds128(sb + SM_HT + t * 80 + cq * 16);
                const uint32_t h4 = lds32(sb + SM_HT + t * 80 + 64 + cq * 4);
                const uint32_t rr = bmul2(sv.y, 0x3C803C80u);
                char* const dp = (char*)g_s.cand + (co + rank * 1440);
                st_rlx128(dp, (norm2(hv.x, sv.x, rr) & 0xBFFFBFFFu) | par, (norm2(hv.y, sv.x, rr) & 0xBFFFBFFFu) | par,
                          (norm2(hv.z, sv.x, rr) & 0xBFFFBFFFu) | par, (norm2(hv.w, sv.x, rr) & 0xBFFFBFFFu) | par);
                asm volatile("st.relaxed.gpu.global.u32 [%0], %1;" :: "l"((char*)g_s.cand + (co + rank * 1440 + 64 - cq * 12)), "r"((norm2(h4, sv.x, rr) & 0xBFFFBFFFu) | par) : "memory");
            }
            __syncwarp();
        }
        {
            const uint2 sa = lds64(sb + SM_ST + tn * 8), sbb = lds64(sb + SM_ST + tn * 8 + 64);
#pragma unroll
            for (int i = 0; i < 5; i++) { ha[i] = badd2(ha[i], norm2(ha[i], sa.x, sa.y)); hb[i] = badd2(hb[i], norm2(hb[i], sbb.x, sbb.y)); }
            const bool hf = (c & 1) && cq == 0;
            const uint32_t o16 = sb + SM_XT + (hf ? 16384 + tn * 16 : tn * 64 + (cq - (c & 1)) * 16), o4 = sb + SM_XT + ((c & 1) ? tn * 64 + 48 : 16384 + tn * 16) + cq * 4;
            sts128(o16, ha[0], ha[1], ha[2], ha[3]); sts32(o4, ha[4]);
            sts128(o16 + (hf ? 128 : 512), hb[0], hb[1], hb[2], hb[3]); sts32(o4 + ((c & 1) ? 512 : 128), hb[4]);
        }
        if (warp >= 8) {
            STAMP(19);
            mbar_wait(mb + MB_KEY * 8);
            STAMP(20);
            const uint32_t mk = lds32(sb + SM_RK - 256 + (tid >> 2) * 4);
            uint32_t rank = rank4<4, 64>(sb + SM_RK + cq * 16, mk);
            rank += __shfl_xor_sync(~0u, rank, 1); rank += __shfl_xor_sync(~0u, rank, 2);
            if (rank < 8) sts64(sb + SM_SEL + rank * 8, mk, ((tid >> 2) - 64) * 1440);
        }
    }
    bar_sync(11, 640);
    STAMP(12);

    const char* gp = (const char*)g_s.cand + (go + lds32(sb + SM_SEL + 4 + (tk & 7) * 8));
    uint4 hv = ld_rlx128(gp);
    if (warp < 8) loadA();
    const bool red = warp < 6;
    const uint32_t ft = red ? (unsigned)tid / 24u : (unsigned)(tid >> 4) & 7u, fj = red ? 24 * q + tid - ft * 24 : d0 / 3 + (lane & 15);
    const uint32_t key = lds32(sb + SM_SEL + ft * 8), k16 = key << 5;
    float sig = bfr(rcpf(1.f + ex2f(__uint_as_float((k16 ^ (~((int)k16 >> 31) | 0x80000000u)) & 0xFFFF0000u) * -1.4426950408889634f)));
    uint32_t ra2 = sb + SM_RED2 + tid * 12 + ft * 16, fo = (ft * 192 + fj) * 16, oo = ((~key & 2047) * D_ + 3 * fj) * 2;
    uint32_t bx = sb + SM_XS + mr * 1168 + mi * 16 + 288 * kq, gd = mapa(sb, kq * (8 / NRED)) + (SM_GU + (q * nslot + mt) * 128) + lane * 4;
    PIN(ra2); PIN(fo); PIN(oo); PIN(bx); PIN(gd);
    asm volatile("" : "+f"(sig));
    {
        if (warp < 18) {
            int n = 0;
            while ((((hv.x ^ par) | (hv.y ^ par) | (hv.z ^ par) | (hv.w ^ par)) & 0x40004000u) && ++n < SPIN_LIMIT) hv = ld_rlx128(gp);
            sts128(sb + SM_XS + tk * 16 + tid * 16, hv.x ^ par, hv.y ^ par, hv.z ^ par, hv.w ^ par);
        }
    }
    bar_sync(14, 672);
    STAMP(13);
    {
        float c0[4] = {0.f, 0.f, 0.f, 0.f}, c1[4] = {0.f, 0.f, 0.f, 0.f}, c2[4] = {0.f, 0.f, 0.f, 0.f};
        uint32_t b[5][4];
#pragma unroll
        for (int s = 0; s < 4; s++) ldsm4(b[s], bx + s * 64);
        asm volatile("ldmatrix.sync.aligned.m8n8.x2.shared.b16 {%0,%1}, [%2];" : "=r"(b[4][0]), "=r"(b[4][1]) : "r"(bx + 256) : "memory");
        mma_bf16(c0, A[0][0], A[0][1], A[0][2], A[0][3], b[0][0], b[0][1]);
        mma_bf16(c1, A[1][0], A[1][1], A[1][2], A[1][3], b[0][2], b[0][3]);
        mma_bf16(c2, A[2][0], A[2][1], A[2][2], A[2][3], b[1][0], b[1][1]);
        mma_bf16(c0, A[3][0], A[3][1], A[3][2], A[3][3], b[1][2], b[1][3]);
        mma_bf16(c1, A[4][0], A[4][1], A[4][2], A[4][3], b[2][0], b[2][1]);
        mma_bf16(c2, A[5][0], A[5][1], A[5][2], A[5][3], b[2][2], b[2][3]);
        mma_bf16(c0, A[6][0], A[6][1], A[6][2], A[6][3], b[3][0], b[3][1]);
        mma_bf16(c1, A[7][0], A[7][1], A[7][2], A[7][3], b[3][2], b[3][3]);
        mma_bf16(c2, A[8][0], A[8][1], A[8][2], A[8][3], b[4][0], b[4][1]);
        sts128f(sb + SM_RED + tid * 16, c0[0] + c1[0] + c2[0], c0[1] + c1[1] + c2[1], c0[2] + c1[2] + c2[2], c0[3] + c1[3] + c2[3]);
    }
    bar_sync(1 + mt, 128);
    STAMP(21);
    if (mt < nslot && kq < NRED) {
        const uint32_t ra = sb + SM_RED + mt * 512 + lane * 16;
        const float4 p0 = lds128f(ra), p1 = lds128f(ra + 2560), p2 = lds128f(ra + 5120), p3 = lds128f(ra + 7680);
        const float g0 = bfr(((p0.x + p1.x) + (p2.x + p3.x)) * 64.f), g1 = bfr(((p0.y + p1.y) + (p2.y + p3.y)) * 64.f);
        const uint32_t sg = pack_bf16(g0 * rcpf(1.f + ex2f(g0 * -1.4426950408889634f)), g1 * rcpf(1.f + ex2f(g1 * -1.4426950408889634f)));
        const uint32_t gu = bmul2(sg, pack_bf16(((p0.z + p1.z) + (p2.z + p3.z)) * 64.f, ((p0.w + p1.w) + (p2.w + p3.w)) * 64.f));
        const uint32_t pstep = mapa(sb, 1) - mapa(sb, 0), gm = mapa(mb + MB_GU * 8, kq * (8 / NRED));
#pragma unroll
        for (int i = 0; i < 8 / NRED; i++) st_async1(gd + i * pstep, gu, gm + i * pstep);
    }
    mbar_wait(mb + MB_W2 * 8);
    {
        const uint32_t aa = sb + (8 * (mi >> 1) + mr) * 144 + (mi & 1) * 16 + (SM_FAR + 2304 * kq + mt * 32);
#pragma unroll
        for (int s = 0; s < 5; s++) ldsm4t(A[s], aa + s * FAR_SZ);
    }
    {
        uint32_t ba = sb + (SM_GU + 256 * kq) + (lane & 15) * 16 + (lane >> 4) * 1024, wa = sb + (SM_RED2 + kq * 2432 + mt * 64) + g * 4 + cq * 608;
        PIN(ba); PIN(wa);
        STAMP(22);
        mbar_wait(mb + MB_GU * 8);
        STAMP(23);
        float c0[4] = {0.f, 0.f, 0.f, 0.f}, c1[4] = {0.f, 0.f, 0.f, 0.f}, c2[4] = {0.f, 0.f, 0.f, 0.f};
        uint32_t b[2][4], b8, b9;
        ldsm4t(b[0], ba); ldsm4t(b[1], ba + 2048); ldsm2t(b8, b9, ba + 4096);
        mma_bf16(c0, A[0][0], A[0][1], A[0][2], A[0][3], b[0][0], b[0][1]);
        mma_bf16(c1, A[1][0], A[1][1], A[1][2], A[1][3], b[0][2], b[0][3]);
        if (nslot == 5) {
            mma_bf16(c2, A[4][0], A[4][1], A[4][2], A[4][3], b8, b9);
            mma_bf16(c0, A[2][0], A[2][1], A[2][2], A[2][3], b[1][0], b[1][1]);
            mma_bf16(c1, A[3][0], A[3][1], A[3][2], A[3][3], b[1][2], b[1][3]);
        }
        stsf(wa, c0[0] + c1[0] + c2[0]); stsf(wa + 304, c0[1] + c1[1] + c2[1]);
        if (mt < 4) { stsf(wa + 32, c0[2] + c1[2] + c2[2]); stsf(wa + 336, c0[3] + c1[3] + c2[3]); }
    }
    if (warp < 10) {
        float v[3], cnt = 3.f;
        if (red) {
            bar_sync(6, 640);
            STAMP(14);
#pragma unroll
            for (int i = 0; i < 3; i++) v[i] = ((ldsf(ra2 + i * 4) + ldsf(ra2 + i * 4 + 2432)) + (ldsf(ra2 + i * 4 + 4864) + ldsf(ra2 + i * 4 + 7296))) * sig;
        } else {
            bar_arrive(6, 640);
            cnt = 0.f;
#pragma unroll
            for (int i = 0; i < 3; i++) {
                const uint32_t cl = 3 * fj + i - d0;
                const bool ok = cl < 8 * nslot && ((~key >> 3) & 7) == q;
                const uint32_t cf = cl - (c & 1) * 8;
                v[i] = ok ? __uint_as_float(lds16(sb + SM_XT + (cf < 32 ? tslot(~key) * 64 + cf * 2 : 16384 + tslot(~key) * 16 + (cl & 7) * 2)) << 16) : 0.f;
                if (ok) cnt += 1.f;
            }
            mbar_wait(mb + MB_OUT * 8);
        }
        if (cnt != 0.f) {
            float x, y, z, w;
            asm volatile("atom.relaxed.gpu.global.add.v4.f32 {%0,%1,%2,%3}, [%4], {%5,%6,%7,%8};" : "=f"(x), "=f"(y), "=f"(z), "=f"(w)
                         : "l"((char*)g_s.fin + fo), "f"(v[0]), "f"(v[1]), "f"(v[2]), "f"(cnt) : "memory");
            if (w + cnt == 3.f * (NCL + 1)) {
                __nv_bfloat16* op = (__nv_bfloat16*)((char*)prm.out + oo);
                op[0] = __float2bfloat16(x + v[0]); op[1] = __float2bfloat16(y + v[1]); op[2] = __float2bfloat16(z + v[2]);
            }
        }
    } else bar_arrive(6, 640);
    STAMP(15);
}

typedef __nv_bfloat16 bf16;
__device__ bf16 f_n[L_ * D_], f_h[L_ * D_];
__device__ float f_k[D_ * L_], f_r[L_], f_gu[8 * F_];
__device__ int f_idx[8];
__device__ __forceinline__ float b2f(bf16 v) { return __bfloat162float(v); }
__global__ void fb_ln(const bf16* in, const bf16* wr, bf16* out) {
    const int t = blockIdx.x * 8 + (threadIdx.x >> 5), lane = threadIdx.x & 31;
    const bf16* r = (in ? in : f_h) + t * D_;
    float s1 = 0.f, s2 = 0.f, s3 = 0.f;
    for (int i = lane; i < D_; i += 32) s1 += b2f(r[i]);
    for (int o = 16; o; o >>= 1) s1 += __shfl_xor_sync(~0u, s1, o);
    for (int i = lane; i < D_; i += 32) { const float d = b2f(r[i]) - s1 / D_; s2 += d * d; }
    for (int o = 16; o; o >>= 1) s2 += __shfl_xor_sync(~0u, s2, o);
    const float m = bfr(s1 / D_), sd = bfr(sqrtf(bfr(bfr(s2 / D_) + 1e-5f)));
    for (int i = lane; i < D_; i += 32) {
        const float v = bfr(bfr(b2f(r[i]) - m) / sd);
        f_n[t * D_ + i] = __float2bfloat16(v);
        if (!in) { s3 += v * b2f(wr[i]); out[t * D_ + i] = __float2bfloat16(b2f(r[i]) + v); }
    }
    for (int o = 16; o; o >>= 1) s3 += __shfl_xor_sync(~0u, s3, o);
    f_r[t] = bfr(s3);
}
__global__ void fb_taps(Params p) {
    const int d = blockIdx.x >> 3, l = (blockIdx.x & 7) * 256 + threadIdx.x;
    const float dt = bfr(expf(bf_lo(p.logdt[d]))), lf = bfr((float)l);
    float k = 0.f;
    for (int n = d * 128; n < d * 128 + 128; n++) {
        float wr, wi, sn, cs;
        cmul(wr, wi, bf_lo(p.prm6[4][n]), bf_lo(p.prm6[5][n]), dt * bf_lo(p.prm6[2][n]), dt * bf_lo(p.prm6[3][n]));
        sincosf(dt * bf_lo(p.prm6[1][n]) * lf, &sn, &cs);
        k += expf(dt * bf_lo(p.prm6[0][n]) * lf) * (wr * cs - wi * sn);
    }
    f_k[l * D_ + d] = k;
}
__global__ void fb_conv(Params p) {
    const int t = blockIdx.x, d = threadIdx.x;
    float y = 0.f;
    for (int l = 0; l <= t; l++) y += f_k[l * D_ + d] * b2f(f_n[(t - l) * D_ + d]);
    f_h[t * D_ + d] = __float2bfloat16(bf_lo(p.x[t * D_ + d]) + bfr(bfr(y) + bfr(b2f(f_n[t * D_ + d]) * bf_lo(p.dskip[d]))));
}
__global__ void fb_top() {
    const int t = blockIdx.x * 256 + threadIdx.x;
    int rank = 0;
    for (int j = 0; j < L_; j++) rank += f_r[j] > f_r[t] || (f_r[j] == f_r[t] && j < t);
    if (rank < 8) f_idx[rank] = t;
}
__global__ void fb_ffn1(const bf16* wg, const bf16* wu) {
    const int f = blockIdx.x * 256 + threadIdx.x, j = blockIdx.y;
    float g = 0.f, u = 0.f;
    for (int i = 0; i < D_; i++) { const float v = b2f(f_n[f_idx[j] * D_ + i]); g += v * b2f(wg[i * F_ + f]); u += v * b2f(wu[i * F_ + f]); }
    g = bfr(g);
    f_gu[j * F_ + f] = bfr(bfr(g / (1.f + expf(-g))) * bfr(u));
}
__global__ void fb_ffn2(const bf16* wd, bf16* out) {
    const int d = threadIdx.x, j = blockIdx.x, t = f_idx[j];
    float y = 0.f;
    for (int f = 0; f < F_; f++) y += f_gu[j * F_ + f] * b2f(wd[f * D_ + d]);
    out[t * D_ + d] = __float2bfloat16(b2f(f_h[t * D_ + d]) + bfr(b2f(f_n[t * D_ + d]) + bfr(bfr(y) * bfr(1.f / (1.f + expf(-f_r[t]))))));
}

typedef CUresult (*EncodeFn)(CUtensorMap*, CUtensorMapDataType, cuuint32_t, void*, const cuuint64_t*, const cuuint64_t*,
                             const cuuint32_t*, const cuuint32_t*, CUtensorMapInterleave, CUtensorMapSwizzle,
                             CUtensorMapL2promotion, CUtensorMapFloatOOBfill);

void make_map(EncodeFn fn, CUtensorMap* tm, const void* p, int cols, int rows, int bc, int br) {
    cuuint64_t dims[2] = {(cuuint64_t)cols, (cuuint64_t)rows};
    cuuint64_t strides[1] = {(cuuint64_t)cols * 2};
    cuuint32_t box[2] = {(cuuint32_t)bc, (cuuint32_t)br};
    cuuint32_t es[2] = {1, 1};
    fn(tm, CU_TENSOR_MAP_DATA_TYPE_BFLOAT16, 2, const_cast<void*>(p), dims, strides, box, es, CU_TENSOR_MAP_INTERLEAVE_NONE,
       CU_TENSOR_MAP_SWIZZLE_NONE, CU_TENSOR_MAP_L2_PROMOTION_L2_128B, CU_TENSOR_MAP_FLOAT_OOB_FILL_NONE);
}

void make_map3(EncodeFn fn, CUtensorMap* tm, const void* p) {
    cuuint64_t dims[5] = {(cuuint64_t)D_, 64, 2, 4, 4};
    cuuint64_t strides[4] = {(cuuint64_t)D_ * 2, (cuuint64_t)D_ * 128, (cuuint64_t)D_ * 1024, (cuuint64_t)D_ * 256};
    cuuint32_t box[5] = {XW, 9, 2, 4, 4};
    cuuint32_t es[5] = {1, 1, 1, 1, 1};
    fn(tm, CU_TENSOR_MAP_DATA_TYPE_BFLOAT16, 5, const_cast<void*>(p), dims, strides, box, es, CU_TENSOR_MAP_INTERLEAVE_NONE,
       CU_TENSOR_MAP_SWIZZLE_NONE, CU_TENSOR_MAP_L2_PROMOTION_NONE, CU_TENSOR_MAP_FLOAT_OOB_FILL_NONE);
}

void make_map5(EncodeFn fn, CUtensorMap* tm, const void* p, int bc) {
    cuuint64_t dims[5] = {(cuuint64_t)D_, 2, 4, 4, 64};
    cuuint64_t strides[4] = {(cuuint64_t)D_ * 128, (cuuint64_t)D_ * 1024, (cuuint64_t)D_ * 256, (cuuint64_t)D_ * 2};
    cuuint32_t box[5] = {(cuuint32_t)bc, 2, 4, 4, 8};
    cuuint32_t es[5] = {1, 1, 1, 1, 1};
    fn(tm, CU_TENSOR_MAP_DATA_TYPE_BFLOAT16, 5, const_cast<void*>(p), dims, strides, box, es, CU_TENSOR_MAP_INTERLEAVE_NONE,
       CU_TENSOR_MAP_SWIZZLE_NONE, CU_TENSOR_MAP_L2_PROMOTION_NONE, CU_TENSOR_MAP_FLOAT_OOB_FILL_NONE);
}

}

extern "C" void kernel_launch(void* const* d_in, const int* in_sizes, int n_in, void* d_out, int out_size) {
    (void)in_sizes; (void)n_in; (void)out_size;
    void* fp = nullptr;
    cudaDriverEntryPointQueryResult qr;
    cudaGetDriverEntryPoint("cuTensorMapEncodeTiled", &fp, cudaEnableDefault, &qr);
    EncodeFn fn = (EncodeFn)fp;
    CUtensorMap tmG, tmU, tmD, tmO, tmX, tmH;
    make_map3(fn, &tmX, d_in[0]);
    make_map(fn, &tmG, d_in[11], F_, D_, 40, 48);
    make_map(fn, &tmU, d_in[12], F_, D_, 40, 48);
    make_map(fn, &tmD, d_in[13], D_, F_, 72, 64);
    make_map5(fn, &tmO, d_out, 32);
    make_map5(fn, &tmH, d_out, 8);
    Params p;
    p.x = (const unsigned short*)d_in[0];
    for (int i = 0; i < 6; i++) p.prm6[i] = (const unsigned short*)d_in[1 + i];
    p.logdt = (const unsigned short*)d_in[7]; p.dskip = (const unsigned short*)d_in[8];
    p.wr = (const unsigned short*)d_in[10];
    p.out = (__nv_bfloat16*)d_out;
    p.zero = 0;
    cudaGetSymbolAddress((void**)&p.gs, g_s);
    cudaFuncSetAttribute(fused_kernel, cudaFuncAttributeMaxDynamicSharedMemorySize, SM_TOTAL);
    static int nclusters = -1;
    if (nclusters < 0) {
        cudaLaunchConfig_t cfg = {};
        cudaLaunchAttribute at;
        at.id = cudaLaunchAttributeClusterDimension; at.val.clusterDim.x = CS; at.val.clusterDim.y = 1; at.val.clusterDim.z = 1;
        cfg.gridDim = dim3(NCTA); cfg.blockDim = dim3(NTHR); cfg.dynamicSmemBytes = SM_TOTAL; cfg.attrs = &at; cfg.numAttrs = 1;
        if (cudaOccupancyMaxActiveClusters(&nclusters, fused_kernel, &cfg) != cudaSuccess) { (void)cudaGetLastError(); nclusters = NCL; }
    }
    if (nclusters >= NCL && !FORCE_FALLBACK) {
        fused_kernel<<<NCTA, NTHR, SM_TOTAL>>>(p, tmG, tmU, tmD, tmO, tmX, tmH);
        return;
    }
    fb_ln<<<L_ / 8, 256>>>((const bf16*)d_in[0], nullptr, nullptr);
    fb_taps<<<D_ * 8, 256>>>(p);
    fb_conv<<<L_, D_>>>(p);
    fb_ln<<<L_ / 8, 256>>>(nullptr, (const bf16*)d_in[10], p.out);
    fb_top<<<L_ / 256, 256>>>();
    fb_ffn1<<<dim3(F_ / 256, 8), 256>>>((const bf16*)d_in[11], (const bf16*)d_in[12]);
    fb_ffn2<<<8, D_>>>((const bf16*)d_in[13], p.out);
}
```

```cpp
#include <cuda_runtime.h>
#include <cuda_bf16.h>
#include <cuda_fp16.h>
#include <cuda.h>
#include <stdint.h>

namespace {

constexpr int L_ = 2048, D_ = 576, F_ = 4608;
constexpr int NCL = 15, CS = 8, NCTA = NCL * CS, NTHR = 768;
#define FORCE_FALLBACK 0
constexpr int XW = 48, NRED = 2;
constexpr int SPIN_LIMIT = 1 << 22;

constexpr int SM_WG   = 0;
constexpr int SM_WU   = 46080;
constexpr int YP = 3392, YS = 656;
constexpr int UP = 3280, US = 656;
constexpr int SM_XT   = 92160;
constexpr int SM_U    = SM_XT + 8 * YP;
constexpr int SM_FAR  = SM_U + 8 * UP;
constexpr int FAR_SZ  = 12416;
constexpr int F_E5 = 0, F_O5 = 1536, F_E3 = 3088, F_O3 = 4624, F_E7 = 6176, F_E2 = F_E7 + 1024, F_E9 = F_E7 + 2048,
              F_H = 3088, F_O7 = F_E7 + F_H, F_O2 = F_E2 + F_H, F_O9 = F_E9 + F_H;
constexpr int SM_P    = SM_FAR + 5 * FAR_SZ;
constexpr int PN_SZ = 584 * 4, SM_PN = SM_P + 64 * 4;
constexpr int P_GS = 48 * 4, P_H7 = 192 * 4, P_HS = 72 * 4;
constexpr int PF_SZ = (192 + 216) * 4, SM_PF = SM_PN + 5 * PN_SZ + 32;
constexpr int SM_MISC = SM_PF + 5 * PF_SZ;
constexpr int SM_ST   = SM_MISC;
constexpr int SM_RK   = SM_ST + 2048;
constexpr int SM_SEL  = SM_RK + 256;
constexpr int SM_KG   = SM_SEL + 64;
constexpr int SM_SC   = SM_KG + 160;
constexpr int SM_DW   = SM_SC + 32;
constexpr int SM_MB   = SM_DW + 160;
constexpr int SM_TOTAL = SM_MB + 128;
constexpr int SM_ROW  = SM_XT - 20736;
constexpr int SM_XTL  = SM_ROW - 576 * XW;
constexpr int SM_RED2 = SM_WG;
constexpr int SM_HT   = SM_P - 512;
constexpr int SM_KEY  = SM_FAR + 10240 + 128;
constexpr int SM_CAND = SM_KEY + 1024;
constexpr int SM_XS   = SM_U;
constexpr int SM_GU   = SM_XS + 9344;
constexpr int SM_RED  = SM_GU + 5632;
static_assert(F_O9 + 1024 <= FAR_SZ && FAR_SZ % 128 == 0, "far overflow");
static_assert(SM_RED + 10240 <= SM_FAR && SM_HT + 20496 <= SM_MISC, "alias overflow");
static_assert(SM_TOTAL <= 232448, "smem overflow");
static_assert(SM_FAR % 128 == 0 && SM_XT % 128 == 0 && SM_XTL % 128 == 0 && SM_P % 16 == 0 && SM_MISC % 16 == 0 && SM_MB % 8 == 0, "align");

enum { MB_X = 0, MB_W1 = 5, MB_W2 = 6, MB_KEY = 7, MB_GU = 8, MB_Y = 9, MB_OUT = 10, MB_T = 11, MB_R = 12 };

struct __align__(128) Scratch {
    unsigned epoch, zcnt, pad[30];
    uint4  st1[L_ * 2];
    float4 acc[L_];
    uint4  cand[64 * NCL * 6];
    float4 fin[8 * 192 + 24];
};
__device__ Scratch g_s;
#define STAMP(i)

__device__ __forceinline__ uint32_t mapa(uint32_t a, uint32_t r) { uint32_t d; asm("mapa.shared::cluster.u32 %0, %1, %2;" : "=r"(d) : "r"(a), "r"(r)); return d; }
__device__ __forceinline__ void mbar_wait(uint32_t mb) {
    asm volatile("{ .reg .pred p, q; .reg .u32 n; mov.u32 n, 0;\n"
                 "W_%=: mbarrier.try_wait.parity.shared::cta.b64 p, [%0], 0; add.u32 n, n, 1; setp.lt.and.u32 q, n, 65536, !p; @q bra W_%=; }" :: "r"(mb) : "memory");
}
__device__ __forceinline__ void arm(uint32_t mb, uint32_t bytes) { asm volatile("mbarrier.arrive.expect_tx.shared::cta.b64 _, [%0], %1;" :: "r"(mb), "r"(bytes) : "memory"); }
__device__ __forceinline__ void bar_sync(int id, int n) { asm volatile("bar.sync %0, %1;" :: "r"(id), "r"(n) : "memory"); }
__device__ __forceinline__ void bar_arrive(int id, int n) { asm volatile("bar.arrive %0, %1;" :: "r"(id), "r"(n) : "memory"); }
__device__ __forceinline__ uint32_t lds16(uint32_t a) { unsigned short v; asm volatile("ld.shared.u16 %0, [%1];" : "=h"(v) : "r"(a) : "memory"); return v; }
__device__ __forceinline__ uint32_t lds32(uint32_t a) { uint32_t v; asm volatile("ld.shared.u32 %0, [%1];" : "=r"(v) : "r"(a) : "memory"); return v; }
__device__ __forceinline__ uint2 lds64(uint32_t a) { uint2 v; asm volatile("ld.shared.v2.u32 {%0,%1}, [%2];" : "=r"(v.x), "=r"(v.y) : "r"(a) : "memory"); return v; }
__device__ __forceinline__ float ldsf(uint32_t a) { float v; asm volatile("ld.shared.f32 %0, [%1];" : "=f"(v) : "r"(a) : "memory"); return v; }
__device__ __forceinline__ uint4 lds128(uint32_t a) { uint4 v; asm volatile("ld.shared.v4.u32 {%0,%1,%2,%3}, [%4];" : "=r"(v.x), "=r"(v.y), "=r"(v.z), "=r"(v.w) : "r"(a) : "memory"); return v; }
__device__ __forceinline__ float4 lds128f(uint32_t a) { float4 v; asm volatile("ld.shared.v4.f32 {%0,%1,%2,%3}, [%4];" : "=f"(v.x), "=f"(v.y), "=f"(v.z), "=f"(v.w) : "r"(a) : "memory"); return v; }
__device__ __forceinline__ void sts16(uint32_t a, uint32_t v) { asm volatile("{ .reg .b16 l, h; mov.b32 {l, h}, %1; st.shared.b16 [%0], l; }" :: "r"(a), "r"(v) : "memory"); }
__device__ __forceinline__ void sts32(uint32_t a, uint32_t v) { asm volatile("st.shared.u32 [%0], %1;" :: "r"(a), "r"(v) : "memory"); }
__device__ __forceinline__ void sts64(uint32_t a, uint32_t x, uint32_t y) { asm volatile("st.shared.v2.u32 [%0], {%1,%2};" :: "r"(a), "r"(x), "r"(y) : "memory"); }
__device__ __forceinline__ void stsf(uint32_t a, float v) { asm volatile("st.shared.f32 [%0], %1;" :: "r"(a), "f"(v) : "memory"); }
__device__ __forceinline__ void sts128(uint32_t a, uint32_t x, uint32_t y, uint32_t z, uint32_t w) { asm volatile("st.shared.v4.u32 [%0], {%1,%2,%3,%4};" :: "r"(a), "r"(x), "r"(y), "r"(z), "r"(w) : "memory"); }
__device__ __forceinline__ void sts128f(uint32_t a, float x, float y, float z, float w) { asm volatile("st.shared.v4.f32 [%0], {%1,%2,%3,%4};" :: "r"(a), "f"(x), "f"(y), "f"(z), "f"(w) : "memory"); }
__device__ __forceinline__ void ldsm4(uint32_t (&r)[4], uint32_t a) { asm volatile("ldmatrix.sync.aligned.m8n8.x4.shared.b16 {%0,%1,%2,%3}, [%4];" : "=r"(r[0]), "=r"(r[1]), "=r"(r[2]), "=r"(r[3]) : "r"(a) : "memory"); }
__device__ __forceinline__ void ldsm4t(uint32_t (&r)[4], uint32_t a) { asm volatile("ldmatrix.sync.aligned.m8n8.x4.trans.shared.b16 {%0,%1,%2,%3}, [%4];" : "=r"(r[0]), "=r"(r[1]), "=r"(r[2]), "=r"(r[3]) : "r"(a) : "memory"); }
__device__ __forceinline__ void ldsm2t(uint32_t& r0, uint32_t& r1, uint32_t a) { asm volatile("ldmatrix.sync.aligned.m8n8.x2.trans.shared.b16 {%0,%1}, [%2];" : "=r"(r0), "=r"(r1) : "r"(a) : "memory"); }
__device__ __forceinline__ void stsm4t(uint32_t a, uint32_t r0, uint32_t r1, uint32_t r2, uint32_t r3) { asm volatile("stmatrix.sync.aligned.m8n8.x4.trans.shared.b16 [%0], {%1,%2,%3,%4};" :: "r"(a), "r"(r0), "r"(r1), "r"(r2), "r"(r3) : "memory"); }
__device__ __forceinline__ void stsm4(uint32_t a, uint32_t r0, uint32_t r1, uint32_t r2, uint32_t r3) { asm volatile("stmatrix.sync.aligned.m8n8.x4.shared.b16 [%0], {%1,%2,%3,%4};" :: "r"(a), "r"(r0), "r"(r1), "r"(r2), "r"(r3) : "memory"); }
__device__ __forceinline__ void stsm2t(uint32_t a, uint32_t r0, uint32_t r1) { asm volatile("stmatrix.sync.aligned.m8n8.x2.trans.shared.b16 [%0], {%1,%2};" :: "r"(a), "r"(r0), "r"(r1) : "memory"); }
__device__ __forceinline__ uint4 ldg128(const void* p) { uint4 v; asm volatile("ld.global.nc.v4.u32 {%0,%1,%2,%3}, [%4];" : "=r"(v.x), "=r"(v.y), "=r"(v.z), "=r"(v.w) : "l"(p)); return v; }
__device__ __forceinline__ uint32_t ldg16(const void* p) { unsigned short v; asm volatile("ld.global.nc.u16 %0, [%1];" : "=h"(v) : "l"(p)); return v; }
__device__ __forceinline__ uint32_t opaque(uint32_t v) { uint32_t r; asm volatile("mov.b32 %0, %1;" : "=r"(r) : "r"(v)); return r; }
__device__ __forceinline__ void mma_f16(float (&d)[4], const uint32_t (&a)[4], uint32_t b0, uint32_t b1) {
    asm volatile("mma.sync.aligned.m16n8k16.row.col.f32.f16.f16.f32 {%0,%1,%2,%3}, {%4,%5,%6,%7}, {%8,%9}, {%0,%1,%2,%3};"
        : "+f"(d[0]), "+f"(d[1]), "+f"(d[2]), "+f"(d[3]) : "r"(a[0]), "r"(a[1]), "r"(a[2]), "r"(a[3]), "r"(b0), "r"(b1));
}
__device__ __forceinline__ void mma_f16_z(float (&d)[4], const uint32_t (&a)[4], uint32_t b0, uint32_t b1) {
    asm volatile("mma.sync.aligned.m16n8k16.row.col.f32.f16.f16.f32 {%0,%1,%2,%3}, {%4,%5,%6,%7}, {%8,%9}, {%10,%10,%10,%10};"
        : "=f"(d[0]), "=f"(d[1]), "=f"(d[2]), "=f"(d[3]) : "r"(a[0]), "r"(a[1]), "r"(a[2]), "r"(a[3]), "r"(b0), "r"(b1), "f"(0.f));
}
__device__ __forceinline__ void mma_bf16(float (&d)[4], uint32_t a0, uint32_t a1, uint32_t a2, uint32_t a3, uint32_t b0, uint32_t b1) {
    asm volatile("mma.sync.aligned.m16n8k16.row.col.f32.bf16.bf16.f32 {%0,%1,%2,%3}, {%4,%5,%6,%7}, {%8,%9}, {%0,%1,%2,%3};"
        : "+f"(d[0]), "+f"(d[1]), "+f"(d[2]), "+f"(d[3]) : "r"(a0), "r"(a1), "r"(a2), "r"(a3), "r"(b0), "r"(b1));
}
__device__ __forceinline__ void mma_bf16_k8(float (&d)[4], uint32_t a0, uint32_t a1, uint32_t b0) {
    asm volatile("mma.sync.aligned.m16n8k8.row.col.f32.bf16.bf16.f32 {%0,%1,%2,%3}, {%4,%5}, {%6}, {%0,%1,%2,%3};"
        : "+f"(d[0]), "+f"(d[1]), "+f"(d[2]), "+f"(d[3]) : "r"(a0), "r"(a1), "r"(b0));
}
__device__ __forceinline__ uint32_t pack_f16(float lo, float hi) { uint32_t r; asm("cvt.rn.f16x2.f32 %0, %1, %2;" : "=r"(r) : "f"(hi), "f"(lo)); return r; }
__device__ __forceinline__ uint32_t pack_bf16(float lo, float hi) { uint32_t r; asm("cvt.rn.bf16x2.f32 %0, %1, %2;" : "=r"(r) : "f"(hi), "f"(lo)); return r; }
__device__ __forceinline__ float bf_lo(uint32_t v) { return __uint_as_float(v << 16); }
__device__ __forceinline__ float bf_hi(uint32_t v) { return __uint_as_float(v & 0xFFFF0000u); }
__device__ __forceinline__ float bfr(float x) { return __uint_as_float(pack_bf16(0.f, x)); }
__device__ __forceinline__ uint32_t badd2(uint32_t a, uint32_t b) { uint32_t r; asm("add.rn.bf16x2 %0, %1, %2;" : "=r"(r) : "r"(a), "r"(b)); return r; }
__device__ __forceinline__ uint32_t bmul2(uint32_t a, uint32_t b) { uint32_t r; asm("mul.rn.bf16x2 %0, %1, %2;" : "=r"(r) : "r"(a), "r"(b)); return r; }
__device__ __forceinline__ uint32_t hadd2(uint32_t a, uint32_t b) { uint32_t r; asm("add.rn.f16x2 %0, %1, %2;" : "=r"(r) : "r"(a), "r"(b)); return r; }
__device__ __forceinline__ uint32_t hmul2(uint32_t a, uint32_t b) { uint32_t r; asm("mul.rn.f16x2 %0, %1, %2;" : "=r"(r) : "r"(a), "r"(b)); return r; }
__device__ __forceinline__ uint32_t hfma2(uint32_t a, uint32_t b, uint32_t c) { uint32_t r; asm("fma.rn.f16x2 %0, %1, %2, %3;" : "=r"(r) : "r"(a), "r"(b), "r"(c)); return r; }
__device__ __forceinline__ uint32_t hneg2(uint32_t a) { uint32_t r; asm("neg.f16x2 %0, %1;" : "=r"(r) : "r"(a)); return r; }
__device__ __forceinline__ float rcpf(float x) { float r; asm("rcp.approx.ftz.f32 %0, %1;" : "=f"(r) : "f"(x)); return r; }
__device__ __forceinline__ float sqrta(float x) { float r; asm("sqrt.approx.ftz.f32 %0, %1;" : "=f"(r) : "f"(x)); return r; }
__device__ __forceinline__ float ex2f(float x) { float r; asm("ex2.approx.ftz.f32 %0, %1;" : "=f"(r) : "f"(x)); return r; }
__device__ __forceinline__ void st_async4(uint32_t a, uint32_t x, uint32_t y, uint32_t z, uint32_t w, uint32_t mb) {
    asm volatile("st.async.shared::cluster.mbarrier::complete_tx::bytes.v4.u32 [%0], {%1,%2,%3,%4}, [%5];" :: "r"(a), "r"(x), "r"(y), "r"(z), "r"(w), "r"(mb) : "memory"); }
__device__ __forceinline__ void st_async1(uint32_t a, uint32_t x, uint32_t mb) {
    asm volatile("st.async.shared::cluster.mbarrier::complete_tx::bytes.u32 [%0], %1, [%2];" :: "r"(a), "r"(x), "r"(mb) : "memory"); }
__device__ __forceinline__ unsigned ld_rlx(const void* p) { unsigned v; asm volatile("ld.relaxed.gpu.global.u32 %0, [%1];" : "=r"(v) : "l"(p) : "memory"); return v; }
__device__ __forceinline__ unsigned ld_acq(const void* p) { unsigned v; asm volatile("ld.acquire.gpu.global.u32 %0, [%1];" : "=r"(v) : "l"(p) : "memory"); return v; }
__device__ __forceinline__ uint2 ld_rlx64(const void* p) { unsigned long long v; asm volatile("ld.relaxed.gpu.global.u64 %0, [%1];" : "=l"(v) : "l"(p) : "memory"); return make_uint2((unsigned)v, (unsigned)(v >> 32)); }
__device__ __forceinline__ void st_rlx128(void* p, uint32_t x, uint32_t y, uint32_t z, uint32_t w) {
    asm volatile("st.relaxed.gpu.global.v2.u64 [%0], {%1,%2};" :: "l"(p), "l"((unsigned long long)x | ((unsigned long long)y << 32)), "l"((unsigned long long)z | ((unsigned long long)w << 32)) : "memory"); }
__device__ __forceinline__ uint4 ld_rlx128(const void* p) { unsigned long long a, b; asm volatile("ld.relaxed.gpu.global.v2.u64 {%0,%1}, [%2];" : "=l"(a), "=l"(b) : "l"(p) : "memory"); return make_uint4((unsigned)a, (unsigned)(a >> 32), (unsigned)b, (unsigned)(b >> 32)); }
__device__ __forceinline__ void tma2d(uint32_t dst, const CUtensorMap* tm, int x, int y, uint32_t mb) {
    asm volatile("cp.async.bulk.tensor.2d.shared::cluster.global.mbarrier::complete_tx::bytes [%0], [%1, {%3, %4}], [%2];"
                 :: "r"(dst), "l"(tm), "r"(mb), "r"(x), "r"(y) : "memory");
}
__device__ __forceinline__ void cmul(float& xr, float& xi, float ar, float ai, float br, float bi) {
    const float r = fmaf(ar, br, -ai * bi), i = fmaf(ar, bi, ai * br); xr = r; xi = i;
}
__device__ __forceinline__ void csq(float& xr, float& xi, float ar, float ai) {
    const float r = fmaf(ar, ar, -ai * ai), i = (ar + ar) * ai; xr = r; xi = i;
}
__device__ __forceinline__ void cexp_s(float& zr, float& zi, float e2, float turns) {
    const float mag = ex2f(e2), r = (turns - rintf(turns)) * 6.283185307179586f;
    zr = mag * __cosf(r); zi = mag * __sinf(r);
}
__device__ __forceinline__ uint32_t ln_stats(float s1, float s2) {
    const float m = s1 * (1.f / D_);
    const float var = fmaxf(fmaf(s2, 1.f / D_, -m * m), 0.f);
    return pack_bf16(m, sqrta(bfr(bfr(var) + 1e-5f)));
}
__device__ __forceinline__ uint32_t rsplit(float rs) { const float h = bfr(rs); return pack_bf16(h, rs - h); }
__device__ __forceinline__ uint32_t norm2(uint32_t v, uint32_t mx, uint32_t hl) {
    uint32_t r;
    asm("{ .reg .b16 m, h, l, x; .reg .b32 m2, h2, l2, d, t; mov.b32 {m, x}, %2; mov.b32 {h, l}, %3; mov.b32 m2, {m, m}; mov.b32 h2, {h, h}; mov.b32 l2, {l, l};\n"
        "sub.rn.bf16x2 d, %1, m2; mul.rn.bf16x2 t, d, l2; fma.rn.bf16x2 %0, d, h2, t; }" : "=r"(r) : "r"(v), "r"(mx), "r"(hl));
    return r;
}
template <int N, int S>
__device__ __forceinline__ uint32_t rank4(uint32_t a, uint32_t key) {
    uint32_t r0 = 0, r1 = 0, r2 = 0, r3 = 0;
#pragma unroll
    for (int i = 0; i < N; i++) {
        const uint4 o = lds128(a + i * S);
        r0 += (key - o.x) >> 31; r1 += (key - o.y) >> 31; r2 += (key - o.z) >> 31; r3 += (key - o.w) >> 31;
    }
    return (r0 + r1) + (r2 + r3);
}
typedef uint32_t H2C;
__device__ __forceinline__ H2C splat(float r, float i) { return pack_f16(r, i); }
__device__ __forceinline__ void hcmul(uint32_t& xr, uint32_t& xi, uint32_t R, uint32_t I, H2C m) {
    asm("{ .reg .b16 a, b; .reg .b32 a2, b2, t; mov.b32 {a, b}, %4; mov.b32 a2, {a, a}; mov.b32 b2, {b, b};\n"
        "mul.rn.f16x2 t, %3, b2; neg.f16x2 t, t; fma.rn.f16x2 %0, %2, a2, t; mul.rn.f16x2 t, %3, a2; fma.rn.f16x2 %1, %2, b2, t; }"
        : "=&r"(xr), "=r"(xi) : "r"(R), "r"(I), "r"(m));
}
__device__ __forceinline__ void expand4(uint32_t are, uint32_t aim, uint32_t R0, uint32_t R1, uint32_t I0, uint32_t I1, H2C m4) {
    uint32_t R2, I2, R3, I3;
    hcmul(R2, I2, R0, I0, m4); hcmul(R3, I3, R1, I1, m4);
    sts128(are, R0, R1, R2, R3);
    sts128(aim, I0, I1, I2, I3);
}
__device__ __forceinline__ void expand8(uint32_t are, uint32_t aim, float sr, float si, float m1r, float m1i, float m2r, float m2i, H2C m4) {
    float r1, i1, r2, i2, r3, i3;
    cmul(r1, i1, sr, si, m1r, m1i); cmul(r2, i2, sr, si, m2r, m2i); cmul(r3, i3, r1, i1, m2r, m2i);
    expand4(are, aim, pack_f16(sr, r1), pack_f16(r2, r3), pack_f16(si, i1), pack_f16(i2, i3), m4);
}
__device__ __forceinline__ void put16(uint32_t a, uint32_t v) { sts16(a, v); sts16(a + 6, v); }

struct Params {
    const unsigned short *logdt, *dskip, *prm6[6], *x, *wr;
    __nv_bfloat16* out;
    Scratch* gs;
    unsigned zero;
};
__device__ __forceinline__ uint32_t tslot(uint32_t t) { return (t & 7) * 32 + ((t >> 4) & 24) + ((t >> 8) & 6) + ((t >> 6) & 1); }
#define CP(x) ((x) | zero)
#define PIN(x) asm volatile("or.b32 %0, %0, %1;" : "+r"(x) : "r"(zero))
__device__ __forceinline__ void wgmma32(float (&d)[4][4], const uint32_t (&a)[4], uint32_t dlo) {
    asm volatile("{ .reg .b64 ds; mov.b64 ds, {%20, %21};\n"
                 "wgmma.mma_async.sync.aligned.m64n32k16.f32.f16.f16 {%0,%1,%2,%3,%4,%5,%6,%7,%8,%9,%10,%11,%12,%13,%14,%15}, {%16,%17,%18,%19}, ds, 1, 1, 1, 0; }"
        : "+f"(d[0][0]), "+f"(d[0][1]), "+f"(d[0][2]), "+f"(d[0][3]), "+f"(d[1][0]), "+f"(d[1][1]), "+f"(d[1][2]), "+f"(d[1][3]),
          "+f"(d[2][0]), "+f"(d[2][1]), "+f"(d[2][2]), "+f"(d[2][3]), "+f"(d[3][0]), "+f"(d[3][1]), "+f"(d[3][2]), "+f"(d[3][3])
        : "r"(a[0]), "r"(a[1]), "r"(a[2]), "r"(a[3]), "r"(dlo), "n"(128 >> 4));
}

__global__ void __cluster_dims__(CS, 1, 1) __launch_bounds__(NTHR, 1)
fused_kernel(const __grid_constant__ Params prm, const __grid_constant__ CUtensorMap tmG, const __grid_constant__ CUtensorMap tmU,
             const __grid_constant__ CUtensorMap tmD, const __grid_constant__ CUtensorMap tmO, const __grid_constant__ CUtensorMap tmX, const __grid_constant__ CUtensorMap tmH)
{
    extern __shared__ __align__(1024) unsigned char smem[];
    const int tid = threadIdx.x, lane = tid & 31, warp = __shfl_sync(~0u, tid >> 5, 0);
    const int c = blockIdx.x >> 3, q = blockIdx.x & 7;
    const int nslot = (c < NCL - 1) ? 5 : 2;
    const int d0 = 40 * c;
    const uint32_t sb = opaque((uint32_t)__cvta_generic_to_shared(smem));
    const uint32_t mb = sb + SM_MB;
    Scratch& g_s = *prm.gs;
    const unsigned& zero = prm.zero;
    STAMP(0);

    if (warp >= 20) {
        unsigned epoch = 0;
        if (warp == 20) {
            if (lane == 0) {
#pragma unroll
                for (int i = 0; i < 13; i++)
                    asm volatile("mbarrier.init.shared::cta.b64 [%0], %1;" :: "r"(mb + i * 8), "r"((i == MB_R || i < 5) ? 2 : i == MB_Y ? 1 + 4 * nslot : 1) : "memory");
                asm volatile("fence.mbarrier_init.release.cluster;" ::: "memory");
                arm(mb + MB_W1 * 8, 92160); arm(mb + MB_W2 * 8, nslot * 9216); arm(mb + MB_KEY * 8, 256); arm(mb + MB_GU * 8, nslot * 1024); arm(mb + MB_T * 8, 576 * XW);
                const int bytes = max(min(18, L_ - 18 * (int)blockIdx.x), 1) * (D_ * 2);
                arm(mb + MB_R * 8, bytes);
            }
            __syncwarp();
        } else if (warp == 22) {
            epoch = ld_rlx(&g_s.epoch);
            if (lane < 18 ? 18 * c + lane < 256 : lane < 31) (lane < 18 ? &g_s.acc[256 * q + 18 * c] : &g_s.fin[13 * (int)blockIdx.x - 18])[lane] = make_float4(0.f, 0.f, 0.f, 0.f);
        } else if (warp == 23 && lane == 0) asm volatile("prefetch.tensormap [%0];" :: "l"(&tmX) : "memory");
        asm volatile("barrier.cluster.arrive.relaxed.aligned;" ::: "memory");
        bar_sync(12, NTHR);
        uint4 wv = make_uint4(0, 0, 0, 0), wv2, wv3;
        if (warp == 22) {
            if (lane == 0) { sts32(sb + SM_SC + 28, epoch); asm volatile("mbarrier.arrive.shared::cta.b64 _, [%0];" :: "r"(mb + MB_R * 8) : "memory"); }
            epoch++;
            asm volatile("fence.acq_rel.gpu;" ::: "memory");
            __syncwarp();
            if (lane == 0) asm volatile("red.relaxed.gpu.global.add.u32 [%0], 1;" :: "l"(&g_s.zcnt) : "memory");
            STAMP(1);
            wv2 = ldg128((const uint4*)prm.wr + lane); wv3 = ldg128((const uint4*)prm.wr + 32 + lane);
            if (lane < 8) wv = ldg128((const uint4*)prm.wr + 64 + lane);
            if (lane < 5) {
                uint4 v = make_uint4(0, 0, 0, 0);
                if (lane < nslot) v = ldg128((const uint4*)(prm.wr + d0) + lane);
                sts128(sb + SM_DW + lane * 16, v.x, v.y, v.z, v.w);
            }
            __syncwarp();
            if (lane < 5) asm volatile("mbarrier.arrive.shared::cta.b64 _, [%0];" :: "r"(mb + (MB_X + lane) * 8) : "memory");
        }
        if (warp == 21) {
            if (lane == 0) { asm volatile("prefetch.tensormap [%0];" :: "l"(&tmG) : "memory"); asm volatile("prefetch.tensormap [%0];" :: "l"(&tmU) : "memory"); asm volatile("prefetch.tensormap [%0];" :: "l"(&tmD) : "memory"); }
            __syncwarp();
            bar_sync(13, 768);
            asm volatile("fence.proxy.async.shared::cta;" ::: "memory");
#pragma unroll 1
            for (int i = 0; i < 24; i++) {
                if (lane == 0) tma2d(sb + SM_WG + i * 3840, i < 12 ? &tmG : &tmU, 320 * c + 8 * nslot * q, 48 * (i < 12 ? i : i - 12), mb + MB_W1 * 8);
            }
            STAMP(1);
            return;
        }
        if (warp == 20) {
            if (lane == 0) {
                asm volatile("cp.async.bulk.shared::cluster.global.mbarrier::complete_tx::bytes [%0], [%1], %2, [%3];"
                             :: "r"(sb + SM_ROW), "l"(prm.x + min(18 * (int)blockIdx.x, L_ - 1) * D_), "r"(max(min(18, L_ - 18 * (int)blockIdx.x), 1) * (D_ * 2)), "r"(mb + MB_R * 8) : "memory");
            }
            __syncwarp();
            mbar_wait(mb + MB_R * 8);
            if (lane == 0) {
                asm volatile("cp.async.bulk.tensor.5d.shared::cluster.global.mbarrier::complete_tx::bytes [%0], [%1, {%3, %4, %5, %5, %5}], [%2];"
                             :: "r"(sb + SM_XTL), "l"(&tmX), "r"(mb + MB_T * 8), "r"(d0 & ~15), "r"(8 * q), "r"(0) : "memory");
            }
            STAMP(6);
        }
        asm volatile("barrier.cluster.wait.aligned;" ::: "memory");
        bar_sync(13, 768);
        asm volatile("fence.proxy.async.shared::cta;" ::: "memory");
        {
            const int idx = lane * 3 + max(warp - 21, 0), sl = nslot - 1 - (idx >> 3), pe = (idx + q + 1) & 7;
            if (sl >= 0) {
                if (pe == q) arm(mb + (MB_X + sl) * 8, 7 * 512);
                else {
                    const uint32_t rb_ = mapa(sb, pe);
                    asm volatile("cp.async.bulk.shared::cluster.shared::cta.mbarrier::complete_tx::bytes [%0], [%1], 512, [%2];"
                                 :: "r"(rb_ + SM_U + 128 + q * UP + sl * US), "r"(sb + SM_XT + 128 + (q & 3) * 16 + pe * YP + sl * YS), "r"(rb_ + SM_MB + (MB_X + sl) * 8) : "memory");
                }
            }
        }
        STAMP(1);
        if (warp == 20 && lane == 0) { asm volatile("prefetch.tensormap [%0];" :: "l"(&tmO) : "memory"); asm volatile("prefetch.tensormap [%0];" :: "l"(&tmH) : "memory"); }
        if (warp == 22) {
            __syncwarp();
            mbar_wait(mb + (MB_X + 1) * 8);
            const uint32_t old = (epoch & 1) ? 0u : 0x40004000u;
#pragma unroll
            for (int t = 0; t < 2; t++)
                if ((lane & 7) < 6) g_s.cand[((q * 8 + 4 * t + (lane >> 3)) * NCL + c) * 6 + (lane & 7)] = make_uint4(old, old, old, old);
            float a[4] = {0.f, 0.f, 0.f, 0.f};
            const uint32_t one = 0x3F803F80u;
            mma_bf16(a, one, one, one, one, wv.x, wv.y);  mma_bf16(a, one, one, one, one, wv.z, wv.w);
            mma_bf16(a, one, one, one, one, wv2.x, wv2.y); mma_bf16(a, one, one, one, one, wv2.z, wv2.w);
            mma_bf16(a, one, one, one, one, wv3.x, wv3.y); mma_bf16(a, one, one, one, one, wv3.z, wv3.w);
            float s = a[0] + a[1];
            s += __shfl_xor_sync(~0u, s, 1); s += __shfl_xor_sync(~0u, s, 2);
            stsf(sb + SM_SC + 24, s);
            __syncwarp();
            if (lane == 0) {
                int n = 0;
                while ((int)(ld_acq(&g_s.zcnt) - epoch * NCTA) < 0 && ++n < SPIN_LIMIT) __nanosleep(200);
                arm(mb + MB_Y * 8, 8 * 512 * nslot);
                if (blockIdx.x == 0) g_s.epoch = epoch;
            }
            STAMP(2);
            return;
        }
        if (warp == 23) {
#pragma unroll 1
            for (int kk = nslot - 1; kk >= 0; kk--) {
                __syncwarp();
                bar_sync(6 + kk, 160);
                if (lane == 0) { asm volatile("fence.proxy.async.shared::cta;" ::: "memory"); tma2d(sb + SM_FAR + kk * FAR_SZ, &tmD, 72 * q, 320 * c + 64 * kk, mb + MB_W2 * 8); }
            }
            return;
        }
        __syncwarp();
        bar_sync(14, 672);
        if (lane == 0) {
            asm volatile("fence.proxy.async.shared::cta;" ::: "memory");
            asm volatile("cp.async.bulk.tensor.5d.global.shared::cta.bulk_group [%0, {%2, %4, %4, %4, %3}], [%1];" :: "l"(&tmH), "r"(sb + SM_XT + 16384), "r"(d0 + ((c & 1) ? 0 : 32)), "r"(8 * q), "r"(0) : "memory");
            asm volatile("cp.async.bulk.tensor.5d.global.shared::cta.bulk_group [%0, {%2, %4, %4, %4, %3}], [%1];" :: "l"(&tmO), "r"(sb + SM_XT), "r"(d0 + (c & 1) * 8), "r"(8 * q), "r"(0) : "memory");
            asm volatile("cp.async.bulk.commit_group;" ::: "memory");
            asm volatile("cp.async.bulk.wait_group 0;" ::: "memory");
            asm volatile("fence.proxy.async.global;" ::: "memory");
            asm volatile("mbarrier.arrive.shared::cta.b64 _, [%0];" :: "r"(mb + MB_OUT * 8) : "memory");
        }
        STAMP(2);
        return;
    }

    const int g = lane >> 2, cq = lane & 3;
    const int k = warp >> 2, wq = warp & 3;
    const int trow = 18 * blockIdx.x + warp;
    const bool rowact = warp < 18 && trow < L_;
    const int dch = min(d0 + 8 * k + q, D_ - 1);
    uint32_t pv[6];
#pragma unroll
    for (int i = 0; i < 6; i++) pv[i] = ldg16(prm.prm6[i] + (uint32_t)(dch * 128 + wq * 32 + lane));
    const uint32_t pLdt = ldg16(prm.logdt + dch), pD = ldg16(prm.dskip + dch);
    const int tn = 16 * (warp & 15) + g;
    uint32_t xa[5], xb[5];
    asm volatile("barrier.cluster.arrive.relaxed.aligned;" ::: "memory");
    uint4* const st1p = &g_s.st1[(((trow >> 3) & 7) * 256 + ((trow >> 6) & 31) * 8 + (trow & 7)) * 2 + (lane >> 2)];
    const bool pub = rowact && (lane & 0x1B) == 0;
    if (pub) st_rlx128(st1p, 0, 0, 0, 0);
    {
        const uint32_t za = sb + SM_P + tid * 16;
        sts128(za, 0, 0, 0, 0);
        if (tid < (SM_MISC - SM_P) / 16 - 640) sts128(za + 10240, 0, 0, 0, 0);
        sts128(sb + ((wq & 2) ? SM_U : SM_XT + (q & 3) * 16) + ((tid >> 3) & 7) * ((wq & 2) ? UP : YP) + k * YS + (lane & 7) * 16, 0, 0, 0, 0);
    }
    bar_sync(12, NTHR);
    const uint32_t dep = lds32(sb + SM_P);
#define PV(x) __uint_as_float(__byte_perm(dep, x, 0x5410))
    STAMP(1);
    const uint32_t fb = sb + SM_FAR + k * FAR_SZ;
    const uint32_t pn = sb + SM_PN + k * PN_SZ, pf = sb + SM_PF + k * PF_SZ;
    unsigned epoch;
    {
        const uint32_t kb = fb + wq * 3072;
        const uint32_t kl = kb + lane * 16;
        uint32_t Af[4][4];
        float sr, si, z1r, z1i, z2r, z2i, z4r, z4i, hr, hi_;
        {
            const float dt = bfr(ex2f(PV(pLdt) * 1.4426950408889634f));
            const float e2 = dt * PV(pv[0]) * 1.4426950408889634f, an = dt * PV(pv[1]);
            cmul(sr, si, PV(pv[4]), PV(pv[5]), dt * PV(pv[2]), dt * PV(pv[3]));
            const unsigned E = min(max(__reduce_max_sync(~0u, __float_as_uint(fmaxf(fmaxf(fabsf(sr), fabsf(si)), fabsf(PV(pD)) * (1.f / 8192.f)))) >> 23, 1u), 253u);
            const float sc = __uint_as_float((254u - E) << 23);
            sr *= sc; si *= -sc;
            sts64(sb + SM_KG + warp * 8, E, __reduce_add_sync(~0u, __float2int_rn(sr * 16777216.f)));
            float ar, ai, br, bi, cr, ci, dr, di;
            { const float m = ex2f(e2 * 8.f); ar = m * __cosf(an * 8.f); ai = m * __sinf(an * 8.f); }
            csq(br, bi, ar, ai); csq(cr, ci, br, bi); csq(dr, di, cr, ci);
            const H2C m4 = splat(cr, ci);
            {
                float r3, i3;
                cmul(r3, i3, ar, ai, br, bi);
                expand4(kl, kl + 1024, pack_f16(1.f, ar), pack_f16(br, r3), pack_f16(0.f, ai), pack_f16(bi, i3), m4);
            }
            expand8(kl + 512, kl + 1536, dr, di, ar, ai, br, bi, m4);
            { const float m = ex2f(e2); z1r = m * __cosf(an); z1i = -m * __sinf(an); }
            cexp_s(hr, hi_, e2 * 128.f, an * (-128.f * 0.15915494309189535f));
            csq(z2r, z2i, z1r, z1i); csq(z4r, z4i, z2r, z2i);
        }
        __syncwarp();
#pragma unroll
        for (int ks = 0; ks < 4; ks++) ldsm4t(Af[ks], kb + (lane >> 3) * 512 + (lane & 7) * 16 + ks * 128);
        STAMP(2);
        const uint32_t la = kb + ((lane >> 3) & 1) * 512 + (lane >> 4) * 128 + (lane & 7) * 16;
        uint32_t kp[5][2], b0[4], b1[4], b2[4], b3[4];
        auto mm2 = [&](int t) {
            float a0[4] = {0.f, 0.f, 0.f, 0.f}, a1[4] = {0.f, 0.f, 0.f, 0.f};
            mma_f16(a0, Af[0], b0[0], b0[1]); mma_f16(a1, Af[0], b2[0], b2[1]); mma_f16(a0, Af[1], b0[2], b0[3]); mma_f16(a1, Af[1], b2[2], b2[3]);
            mma_f16(a0, Af[2], b1[0], b1[1]); mma_f16(a1, Af[2], b3[0], b3[1]); mma_f16(a0, Af[3], b1[2], b1[3]); mma_f16(a1, Af[3], b3[2], b3[3]);
            kp[t][0] = pack_f16(a0[1], a0[0]); kp[t][1] = pack_f16(a0[3], a0[2]); kp[t + 1][0] = pack_f16(a1[1], a1[0]); kp[t + 1][1] = pack_f16(a1[3], a1[2]);
        };
        auto ln1 = [&]() {
        mbar_wait(mb + MB_R * 8);
        epoch = lds32(sb + SM_SC + 28) + 1;
        {
            const uint32_t ra = sb + SM_ROW + warp * (D_ * 2);
            const uint4 r0 = lds128(ra + lane * 16), r1 = lds128(ra + 512 + lane * 16);
            const uint32_t rx[9] = {r0.x, r0.y, r0.z, r0.w, r1.x, r1.y, r1.z, r1.w, lds32(ra + 1024 + lane * 4)};
            float a0 = bf_lo(rx[0]), a1 = bf_hi(rx[0]), c0 = a0 * a0, c1 = a1 * a1;
#pragma unroll
            for (int i = 1; i < 9; i++) { const float l = bf_lo(rx[i]), h = bf_hi(rx[i]); a0 += l; a1 += h; c0 = fmaf(l, l, c0); c1 = fmaf(h, h, c1); }
            a0 += a1; c0 += c1;
            float s1 = ((lane & 1) ? c0 : a0) + __shfl_xor_sync(~0u, (lane & 1) ? a0 : c0, 1);
#pragma unroll
            for (int o = 2; o < 32; o <<= 1) s1 += __shfl_xor_sync(~0u, s1, o);
            const float s2 = __shfl_xor_sync(~0u, s1, 1);
            const uint32_t ms = ln_stats(s1, s2);
            const uint32_t p0 = __byte_perm(ms, epoch | 0x8000u, 0x5410), p1 = rsplit(rcpf(bf_hi(ms)));
            if (pub) st_rlx128(st1p, p0, p1, p0, p1);
        }
        mbar_wait(mb + MB_R * 8);
        STAMP(1);
        };
        const uint4* sp = &g_s.st1[(256 * q + tn) * 2];
        uint2 sa, sc;
        auto poll = [&]() { sa = ld_rlx64(sp); sc = ld_rlx64(sp + 16); };
        auto norm = [&]() {
        STAMP(3);
        if (warp < 16) {
            uint32_t va[5], vc[5];
            poll();
            mbar_wait(mb + MB_T * 8);
            {
                const uint32_t xt = sb + SM_XTL + (c & 1) * 16 + (72 * wq + 18 * k + g) * (2 * XW);
                uint4 a4 = lds128(xt + cq * 16), b4 = lds128(xt + cq * 16 + 18 * XW);
                va[0] = a4.x; va[1] = a4.y; va[2] = a4.z; va[3] = a4.w; va[4] = lds32(xt + 64 + cq * 4);
                vc[0] = b4.x; vc[1] = b4.y; vc[2] = b4.z; vc[3] = b4.w; vc[4] = lds32(xt + (64 + 18 * XW) + cq * 4);
            }
            const int d4 = 2 * (lane >> 3) + (lane & 1), d1_ = lane & 7;
            const uint32_t own = SM_U + 128 + q * (UP - YP), oth = SM_XT + 128 + (q & 3) * 16;
            uint32_t a4 = sb + warp * 32 + d4 * YP + (d4 == q ? own : oth) + ((lane & 7) >> 1) * YS;
            uint32_t a1 = sb + warp * 32 + d1_ * YP + (d1_ == q ? own : oth) + 4 * YS + (lane & 8) * 2;
            PIN(a4); PIN(a1);
            uint32_t tag = __byte_perm(epoch | 0x8000u, 0, 0x1010);
            PIN(tag);
            mbar_wait(mb + MB_T * 8);
            int n = 0;
            while (__byte_perm(sa.x, sc.x, 0x7632) != tag && ++n < SPIN_LIMIT) poll();
            STAMP(4);
#pragma unroll
            for (int i = 0; i < 5; i++) {
                va[i] = norm2(va[i], sa.x, sa.y); va[i] = pack_f16(bf_lo(va[i]), bf_hi(va[i]));
                vc[i] = norm2(vc[i], sc.x, sc.y); vc[i] = pack_f16(bf_lo(vc[i]), bf_hi(vc[i]));
            }
            stsm4t(a4, va[0], va[1], va[2], va[3]); stsm4t(a4 + 16, vc[0], vc[1], vc[2], vc[3]); stsm2t(a1, va[4], vc[4]);
            {
            const uint32_t xh = sb + SM_XTL + (c & 1) * 16 + (9 * g + 144 * (warp & 1) + (warp >> 1)) * (2 * XW);
            const uint4 c4 = lds128(xh + cq * 16), d4_ = lds128(xh + cq * 16 + 144 * XW);
            xa[0] = c4.x; xa[1] = c4.y; xa[2] = c4.z; xa[3] = c4.w; xa[4] = lds32(xh + 64 + cq * 4);
            xb[0] = d4_.x; xb[1] = d4_.y; xb[2] = d4_.z; xb[3] = d4_.w; xb[4] = lds32(xh + (64 + 144 * XW) + cq * 4);
            }
        }
        STAMP(5);
        bar_sync(13, 768);
        Af[0][0] |= lds32(sb + SM_P);
        };
        cmul(sr, si, sr, si, z1r, z1i);
        {
            const H2C h4 = splat(z4r, z4i);
            expand8(kl, kl + 512, sr, si, z1r, z1i, z2r, z2i, h4);
            cmul(sr, si, sr, si, hr, hi_);
            expand8(kl + 1024, kl + 1536, sr, si, z1r, z1i, z2r, z2i, h4);
        }
        __syncwarp();
        ldsm4t(b0, la); ldsm4t(b1, la + 256); ldsm4t(b2, la + 1024); ldsm4t(b3, la + 1280);
        cmul(z1r, z1i, z1r, z1i, hr, hi_);
        cmul(sr, si, sr, si, z1r, z1i);
        ln1();
        expand8(kl, kl + 512, sr, si, z2r, z2i, z4r, z4i, splat(hr, hi_));
        csq(z1r, z1i, z1r, z1i);
        cmul(sr, si, sr, si, z1r, z1i);
        csq(z2r, z2i, hr, hi_);
        expand8(kl + 1024, kl + 1536, sr, si, z4r, z4i, hr, hi_, splat(z2r, z2i));
        csq(z1r, z1i, z1r, z1i);
        cmul(sr, si, sr, si, z1r, z1i);
        csq(z4r, z4i, z2r, z2i);
        expand8(kl + 2048, kl + 2560, sr, si, hr, hi_, z2r, z2i, splat(z4r, z4i));
        norm();
        mm2(0);
        __syncwarp();
        ldsm4t(b0, la); ldsm4t(b1, la + 256); ldsm4t(b2, la + 1024); ldsm4t(b3, la + 1280);
        mm2(2);
        ldsm4t(b0, la + 2048); ldsm4t(b1, la + 2304);
#pragma unroll
        for (int t = 0; t < 4; t++) sts64(kb + lane * 8 + 1024 + t * 256, kp[t][0], kp[t][1]);
        {
            float a0[4] = {0.f, 0.f, 0.f, 0.f}, a1[4] = {0.f, 0.f, 0.f, 0.f};
            mma_f16(a0, Af[0], b0[0], b0[1]); mma_f16(a1, Af[1], b0[2], b0[3]); mma_f16(a0, Af[2], b1[0], b1[1]); mma_f16(a1, Af[3], b1[2], b1[3]);
            sts64(kb + lane * 8 + 2048, pack_f16(a0[1] + a1[1], a0[0] + a1[0]), pack_f16(a0[3] + a1[3], a0[2] + a1[2]));
        }
        bar_sync(1 + k, 128);
        const uint4 m01 = lds128(sb + SM_KG + k * 32), m23 = lds128(sb + SM_KG + k * 32 + 16);
        const unsigned Em = max(max(m01.x, m01.z), max(m23.x, m23.z));
        const float f0 = __uint_as_float(max((int)(127 + m01.x - Em), 0) << 23), f1 = __uint_as_float(max((int)(127 + m01.z - Em), 0) << 23),
                    f2 = __uint_as_float(max((int)(127 + m23.x - Em), 0) << 23), f3 = __uint_as_float(max((int)(127 + m23.z - Em), 0) << 23);
        const uint32_t r0 = pack_f16(f0, f0), r1 = pack_f16(f1, f1), r2 = pack_f16(f2, f2), r3 = pack_f16(f3, f3);
        const int tq = (wq + k) & 3;
        const uint32_t ra = fb + lane * 8 + tq * 256 + 1024;
        const uint2 p0 = lds64(ra), p1 = lds64(ra + 3072), p2 = lds64(ra + 6144), p3 = lds64(ra + 9216);
        uint32_t w0 = hadd2(hfma2(p0.x, r0, hmul2(p1.x, r1)), hfma2(p2.x, r2, hmul2(p3.x, r3)));
        uint32_t w1 = hadd2(hfma2(p0.y, r0, hmul2(p1.y, r1)), hfma2(p2.y, r2, hmul2(p3.y, r3)));
        const bool last = lane == 31;
        if (tq < 2) {
            const uint32_t rc = fb + lane * 8 + tq * 4 + 2048;
            const uint32_t w4 = hmul2(hadd2(hfma2(lds32(rc), r0, hmul2(lds32(rc + 3072), r1)), hfma2(lds32(rc + 6144), r2, hmul2(lds32(rc + 9216), r3))), 0x18001800u);
            const uint32_t ph = pf + (P_H7 + 16 * tq) + (g & 1) * (2 * P_HS) + cq * 64 + (g >> 1) * 4;
            put16(ph, w4 >> 16); put16(ph + 32, w4);
            const uint32_t pa = pn + (4 + 512 * tq) + lane * 8;
            sts16(pa, w0 >> 16); sts32(pa + 4, w0); sts16(pa + 10, w0);
            sts16(pa + 256, w1 >> 16); sts32(pa + 260, w1); sts16(pa + 266, w1);
            if (last) {
                sts32(sb + SM_SC + k * 4, Em * 0x00800080u);
                put16(tq ? pa + 264 : pn,
                      tq ? w1 : pack_f16(((float)(int)m01.y * f0 + (float)(int)m01.w * f1 + (float)(int)m23.y * f2 + (float)(int)m23.w * f3) * (1.f / 16777216.f)
                                         + __uint_as_float(pD << 16) * __uint_as_float((254u - Em) << 23), 0.f));
            }
        } else if (tq == 2) {
            const uint32_t pa = pn + 258 * 4 + (cq & 1) * 16 + (cq >> 1) * 512 + g * 32;
            if (last) { put16(pf, hmul2(w1, 0x18001800u)); w1 = hadd2(w1, hneg2(__byte_perm(w1, 0, 0x1010))); }
            const uint32_t b0 = __byte_perm(w0, 0, 0x1010), b1 = __byte_perm(w1, 0, 0x1010);
            sts16(pa, w0 >> 16); sts32(pa + 4, w0); sts64(pa + 8, b0, b0); sts16(pa + 18, w0);
            sts16(pa + 256, w1 >> 16); sts32(pa + 260, w1); sts64(pa + 264, b1, b1); sts16(pa + 274, w1);
        } else {
            const uint32_t pa = pf + ((g & 1) ? 3 * P_GS : P_GS) + cq * 32 + (g >> 1) * 4;
            const uint32_t pb = pa + ((g & 1) ? 4 - 3 * P_GS : P_GS);
            w0 = hmul2(w0, 0x18001800u); w1 = hmul2(w1, 0x18001800u);
            put16(pa, w0 >> 16); put16(pb, w0); put16(pa + 16, w1 >> 16); put16(pb + 16, w1);
            if (last) put16(pf + P_H7 + P_HS, w1);
        }
        bar_sync(1 + k, 128);
    }
    STAMP(6);

    asm volatile("barrier.cluster.wait.aligned;" ::: "memory");
    mbar_wait(mb + (MB_X + (k < nslot ? k : 0)) * 8);
    STAMP(7);
    if (k < nslot) {
        const int role = (wq + k) & 3;
        const uint32_t ub = sb + SM_U + k * US + 128;
        if (role) {
            const int r = (3 - role) * 32 + lane;
            const uint32_t a1 = ub + (r & 3) * (2 * UP) + (r >> 2) * 16, a0 = a1 + ((r & 3) ? -2 * UP : 6 * UP - 16);
            const uint4 q0 = lds128(a0), q1 = lds128(a0 + UP), q2 = lds128(a1), q3 = lds128(a1 + UP);
            const uint32_t U[16] = {q0.x, q0.y, q0.z, q0.w, q1.x, q1.y, q1.z, q1.w, q2.x, q2.y, q2.z, q2.w, q3.x, q3.y, q3.z, q3.w};
            uint32_t V[14], Q[14], R4[12], T[8];
#pragma unroll
            for (int i = 2; i < 14; i++) { V[i] = __byte_perm(U[i], U[i + 1], 0x5432); Q[i] = hadd2(U[i], V[i]); }
#pragma unroll
            for (int i = 2; i < 12; i++) R4[i] = hadd2(Q[i], Q[i + 1]);
            const uint32_t rb = fb + r * 16;
#pragma unroll
            for (int i = 0; i < 8; i++) T[i] = hadd2(V[5 + i], Q[6 + i]);
            sts128(rb + F_E3, T[0], T[1], T[2], T[3]); sts128(rb + F_O3 + 16, T[4], T[5], T[6], T[7]);
#pragma unroll
            for (int i = 0; i < 8; i++) T[i] = hadd2(R4[3 + i], U[5 + i]);
            sts128(rb + F_O5, T[0], T[1], T[2], T[3]); sts128(rb + F_E5, T[4], T[5], T[6], T[7]);
            if (role != 1) {
#pragma unroll
                for (int i = 0; i < 8; i++) T[i] = hadd2(T[i], hadd2(V[2 + i], V[5 + i]));
                sts128(rb + F_E7, T[0], T[1], T[2], T[3]); sts128(rb + F_O7, T[4], T[5], T[6], T[7]);
#pragma unroll
                for (int i = 0; i < 8; i++) T[i] = hadd2(R4[2 + i], hadd2(R4[4 + i], U[6 + i]));
                sts128(rb + F_O9, T[0], T[1], T[2], T[3]); sts128(rb + F_E9 + 16, T[4], T[5], T[6], T[7]);
                sts128(rb + F_E2, Q[6], Q[7], Q[8], Q[9]); sts128(rb + F_O2, Q[10], Q[11], Q[12], Q[13]);
            }
        } else if (lane < 8) {
            uint32_t v[5];
#pragma unroll
            for (int i = 0; i < 5; i++) { const int t = 6 + lane + i; v[i] = lds16(ub + 23 * 16 + (t < 16 ? (6 + (t >> 3)) * UP : 16) + (t & 7) * 2); }
            const uint32_t s = hadd2(hadd2(hadd2(v[0], v[1]), hadd2(v[2], v[3])), v[4]);
            sts16(fb + F_O5 + 96 * 16 + lane * 2, s);
            sts32(fb + (lane < 4 ? F_O3 : F_E9 - 16) + lane * 4, 0);
        }
        bar_sync(1 + k, 128);
        float acc[4][4];
        uint32_t Q[4][4];
        {
            const int h = role & 1, part = role >> 1;
            const uint32_t po = pf + (g - 2 * cq) * 4;
            float fa[7][4];
#pragma unroll
            for (int a = 0; a < 7; a++) fa[a][0] = fa[a][1] = fa[a][2] = fa[a][3] = 0.f;
            uint32_t B[3][4];
            Q[0][2] = tid & zero;
#pragma unroll 1
            for (int s = 2 * part + 1; s >= 2 * part; s--) {
#pragma unroll
                for (int i = 0; i < 3; i++) { Q[i][0] = lds32(po + s * P_GS + i * 64); Q[i][1] = lds32(po + s * P_GS + (i * 64 + 32)); }
                const uint32_t ba = fb + lane * 16 + ((s & 1) * F_E3 + (part == h ? 0 : F_O5 + h * 16));
#pragma unroll
                for (int i = 0; i < 3; i++) ldsm4t(B[i], ba + i * 512);
#pragma unroll
                for (int i = 0; i < 3; i++) { Q[i][3] = CP(Q[i][0]); if (i) Q[i][2] = CP(Q[i - 1][1]); }
#pragma unroll
                for (int dl = 0; dl < 3; dl++)
#pragma unroll
                    for (int ap = 0; ap < 6 - dl; ap++) mma_f16(fa[ap + 1 + dl], Q[dl], B[ap >> 1][2 * (ap & 1)], B[ap >> 1][2 * (ap & 1) + 1]);
            }
#pragma unroll 1
            for (int s = role; s == 1; s++) {
                ldsm2t(B[0][0], B[0][1], fb + ((lane & 15) == 15 ? F_O5 : F_O3));
#pragma unroll
                for (int dl = 0; dl < 3; dl++) mma_f16(fa[dl], Q[dl], B[0][0], B[0][1]);
            }
#pragma unroll 1
            for (int s = part; s <= 2 * part; s++) {
#pragma unroll
                for (int i = 0; i < 4; i++) { Q[i][0] = lds32(po + s * P_HS + (P_H7 + i * 64)); Q[i][1] = lds32(po + s * P_HS + (P_H7 + i * 64 + 32)); }
                const uint32_t ba = fb + lane * 16 + (F_E7 + s * 1024 + h * F_H);
                ldsm4t(B[0], ba); ldsm4t(B[1], ba + 512);
#pragma unroll
                for (int i = 0; i < 4; i++) { Q[i][3] = CP(Q[i][0]); if (i) Q[i][2] = CP(Q[i - 1][1]); }
#pragma unroll
                for (int dl = 0; dl < 4; dl++) {
#pragma unroll
                    for (int ap = 0; ap < 4 - dl; ap++) mma_f16(fa[ap + 3 + dl], Q[dl], B[ap >> 1][2 * (ap & 1)], B[ap >> 1][2 * (ap & 1) + 1]);
                    if (s == 1) break;
                }
            }
            const uint32_t da = fb + role * 2048 + (lane & 3) * 512 + (((lane >> 2) ^ ((lane & 3) * 2)) << 4);
            bar_sync(1 + k, 128);
            stsm4(da, 0u, 0u, pack_f16(fa[0][0], fa[0][1]), pack_f16(fa[0][2], fa[0][3]));
#pragma unroll
            for (int i = 1; i < 4; i++)
                stsm4(da + i * 128, pack_f16(fa[2 * i - 1][0], fa[2 * i - 1][1]), pack_f16(fa[2 * i - 1][2], fa[2 * i - 1][3]),
                      pack_f16(fa[2 * i][0], fa[2 * i][1]), pack_f16(fa[2 * i][2], fa[2 * i][3]));
            Q[0][0] = (g == 2 * cq) ? 0x6000u : ((g == 2 * cq + 1) ? 0x60000000u : 0u);
            Q[0][1] = Q[0][0] & zero; Q[0][2] = lane & zero; Q[0][3] = CP(Q[0][0]);
            const uint32_t ra = fb + (lane >> 3) * 2048 + wq * 512 + (((lane & 7) ^ (wq * 2)) << 4);
            bar_sync(1 + k, 128);
#pragma unroll
            for (int i = 0; i < 4; i++) {
                ldsm4(B[0], ra + i * 128);
                mma_f16_z(acc[i], Q[0], hadd2(B[0][0], B[0][2]), hadd2(B[0][1], B[0][3]));
            }
        }
        bar_arrive(6 + k, 160);
        STAMP(8);
        const uint32_t inv = lds32(sb + SM_SC + k * 4);
        uint32_t yd = mapa(sb, 2 * wq) + (SM_XT + 128 + q * YP + k * YS + (k >> 2) * (q >> 1) * 16) + lane * 16;
        PIN(yd);
        {
            uint32_t pp = pn + (16 * (wq - 3) + g - 2 * cq) * 4;
            uint32_t dlo = (((ub + 6 * UP) & 0x3FFFF) >> 4) | ((UP >> 4) << 16);
            uint32_t R[4][4];
            auto loadQ = [&](uint32_t (&X)[4][4], uint32_t prev) {
#pragma unroll
                for (int i = 0; i < 4; i++) { X[i][0] = lds32(pp + i * 64); X[i][1] = lds32(pp + i * 64 + 32); }
                X[0][2] = CP(prev);
#pragma unroll
                for (int i = 0; i < 4; i++) { X[i][3] = CP(X[i][0]); if (i) X[i][2] = CP(X[i - 1][1]); }
                pp += 256;
            };
            auto issue = [&](uint32_t (&X)[4][4]) {
                asm volatile("wgmma.fence.sync.aligned;" ::: "memory");
#pragma unroll
                for (int i = 0; i < 4; i++) wgmma32(acc, X[i], dlo - i * (2 * UP >> 4));
                asm volatile("wgmma.commit_group.sync.aligned;" ::: "memory");
                dlo -= 1;
            };
            loadQ(Q, 0);
#pragma unroll 1
            for (int dl = 0; dl < 4; dl++) {
                issue(Q);
                asm volatile("wgmma.wait_group.sync.aligned 1;" ::: "memory");
                loadQ(R, Q[3][1]);
                issue(R);
                asm volatile("wgmma.wait_group.sync.aligned 1;" ::: "memory");
                loadQ(Q, R[3][1]);
            }
            issue(Q);
            asm volatile("wgmma.wait_group.sync.aligned 0;" ::: "memory");
        }
        const uint32_t pstep = mapa(sb, 1) - mapa(sb, 0), ym = mapa(mb + MB_Y * 8, 2 * wq);
#pragma unroll
        for (int e = 0; e < 2; e++)
            st_async4(yd + e * pstep, bmul2(pack_bf16(acc[0][2 * e], acc[0][2 * e + 1]), inv), bmul2(pack_bf16(acc[1][2 * e], acc[1][2 * e + 1]), inv),
                      bmul2(pack_bf16(acc[2][2 * e], acc[2][2 * e + 1]), inv), bmul2(pack_bf16(acc[3][2 * e], acc[3][2 * e + 1]), inv), ym + e * pstep);
        if (lane == 0) asm volatile("mbarrier.arrive.shared::cta.b64 _, [%0];" :: "r"(mb + MB_Y * 8) : "memory");
    }
    STAMP(9);
    uint32_t ha[5], hb[5];
    if (warp < 16) {
        const uint4 wk = lds128(sb + SM_DW + cq * 16);
        uint32_t sel[5] = {wk.x, wk.y, wk.z, wk.w, lds32(sb + SM_DW + 64 + cq * 4)}, sel2[5];
#pragma unroll
        for (int i = 0; i < 5; i++) {
            if (!(g & 1)) sel[i] = 0x3F803F80u;
            sel2[i] = sel[i]; PIN(sel2[i]);
        }
        const uint32_t y4 = sb + SM_XT + 128 + warp * 32 + (2 * (lane >> 3) + (lane & 1)) * YP + ((lane & 7) >> 1) * YS;
        const uint32_t y1 = sb + SM_XT + 128 + warp * 32 + (lane & 7) * YP + 4 * YS + (lane & 8) * 2 + (lane & 6) * 8;
        uint32_t ao = (256 * q + tn) * 16, hta = sb + SM_HT + tn * 80;
        PIN(ao); PIN(hta);
        mbar_wait(mb + MB_Y * 8);
        STAMP(10);
        float ca[4] = {0.f, 0.f, 0.f, 0.f}, cb[4] = {0.f, 0.f, 0.f, 0.f};
        {
            uint32_t ya[4], yb[4], yc, yd;
            ldsm4t(ya, y4); ldsm4t(yb, y4 + 16); ldsm2t(yc, yd, y1);
#pragma unroll
            for (int i = 0; i < 4; i++) { ha[i] = badd2(xa[i], ya[i]); hb[i] = badd2(xb[i], yb[i]); }
            ha[4] = badd2(xa[4], yc); hb[4] = badd2(xb[4], yd);
        }
        if (nslot != 5) {
            ha[4] = hb[4] = 0;
            if (cq >= 2) ha[0] = ha[1] = ha[2] = ha[3] = hb[0] = hb[1] = hb[2] = hb[3] = 0;
        }
#pragma unroll
        for (int i = 0; i < 5; i++) { mma_bf16_k8(ca, ha[i], sel[i], ha[i]); mma_bf16_k8(cb, hb[i], sel2[i], hb[i]); }
        if (!(g & 1)) { ca[1] = ca[0]; cb[1] = cb[0]; }
        if (cq == (g >> 1)) {
            asm volatile("red.relaxed.gpu.global.add.v4.f32 [%0], {%1,%2,%3,%4};" :: "l"((char*)g_s.acc + ao), "f"(1.0f), "f"(ca[1]), "f"(ca[2]), "f"(ca[3]) : "memory");
            asm volatile("red.relaxed.gpu.global.add.v4.f32 [%0], {%1,%2,%3,%4};" :: "l"((char*)g_s.acc + ao + 128), "f"(1.0f), "f"(cb[1]), "f"(cb[2]), "f"(cb[3]) : "memory");
        }
        sts128(hta + cq * 16, ha[0], ha[1], ha[2], ha[3]); sts32(hta + 64 + cq * 4, ha[4]);
        sts128(hta + cq * 16 + 640, hb[0], hb[1], hb[2], hb[3]); sts32(hta + 704 + cq * 4, hb[4]);
        STAMP(11);
    }
    const int kq = warp / 5, mt = warp - 5 * kq;
    const int mi = lane >> 3, mr = lane & 7;
    const unsigned tk = (unsigned)tid / 72u, ck = tid - tk * 72;
    uint32_t A[9][4];
    auto loadA = [&]() {
        mbar_wait(mb + MB_W1 * 8);
        const uint32_t aa = sb + (mi & 1) * SM_WU + (8 * (mi >> 1) + mr) * 80 + (144 * 80 * kq + mt * 16);
#pragma unroll
        for (int s = 0; s < 9; s++) ldsm4t(A[s], aa + s * 1280);
    };
    const uint32_t par = (epoch & 1) ? 0x40004000u : 0u;
    uint32_t pk0 = mapa(sb, 2 * cq), go = (ck / 5u + ck) * 16, co = ((q * 8 * NCL + c) * 6 + cq) * 16;
    PIN(pk0); PIN(go); PIN(co);
    if (warp < 8) {
        const float wsum = ldsf(sb + SM_SC + 24);
        const uint32_t idx = 2047 - (512 * ((tid >> 1) & 3) + 128 * ((tid >> 3) & 3) + 64 * (tid & 1) + 8 * q + warp);
        uint4 s; int n = 0;
        do { s = ld_rlx128(&g_s.acc[256 * q + tid]); } while (__uint_as_float(s.x) != (float)NCL && ++n < SPIN_LIMIT);
        STAMP(16);
        const uint32_t ox = __shfl_xor_sync(~0u, (lane & 1) ? s.z : s.w, 1);
        const uint32_t ms = ln_stats(__uint_as_float((lane & 1) ? ox : s.z), __uint_as_float(s.y));
        const float rs = rcpf(bf_hi(ms));
        const uint32_t rb = pack_bf16(0.f, fmaf(-bf_lo(ms), wsum, __uint_as_float((lane & 1) ? s.w : ox)) * rs);
        const uint32_t key = (((rb ^ (((int)rb >> 31) | 0x80000000u)) >> 16) << 11) | idx;
        sts32(sb + SM_KEY + tid * 4, key);
        __syncwarp();
        const uint32_t rank = rank4<8, 16>(sb + SM_KEY + warp * 128, key);
        if (rank < 8) sts32(sb + SM_CAND + warp * 32 + rank * 4, key);
        sts64(sb + SM_ST + tid * 8, ms, rsplit(rs));
    } else loadA();
    if (warp < 16) {
        STAMP(17);
        bar_sync(12, 512);
        STAMP(18);
        if (warp < 8) {
            const uint32_t mk = lds32(sb + SM_CAND + (tid >> 2) * 4);
            uint32_t rank = rank4<4, 64>(sb + SM_CAND + cq * 16, mk);
            rank += __shfl_xor_sync(~0u, rank, 1); rank += __shfl_xor_sync(~0u, rank, 2);
            if (rank < 8) {
                const uint32_t pk1 = pk0 + (mapa(sb, 1) - mapa(sb, 0));
                st_async1(pk0 + (SM_RK + q * 32) + rank * 4, mk, pk0 + (SM_MB + MB_KEY * 8));
                st_async1(pk1 + (SM_RK + q * 32) + rank * 4, mk, pk1 + (SM_MB + MB_KEY * 8));
                const uint32_t t = tslot(~mk);
                const uint2 sv = lds64(sb + SM_ST + t * 8);
                const uint4 hv = lds128(sb + SM_HT + t * 80 + cq * 16);
                const uint32_t h4 = lds32(sb + SM_HT + t * 80 + 64 + cq * 4);
                const uint32_t rr = bmul2(sv.y, 0x3C803C80u);
                char* const dp = (char*)g_s.cand + (co + rank * 1440);
                st_rlx128(dp, (norm2(hv.x, sv.x, rr) & 0xBFFFBFFFu) | par, (norm2(hv.y, sv.x, rr) & 0xBFFFBFFFu) | par,
                          (norm2(hv.z, sv.x, rr) & 0xBFFFBFFFu) | par, (norm2(hv.w, sv.x, rr) & 0xBFFFBFFFu) | par);
                asm volatile("st.relaxed.gpu.global.u32 [%0], %1;" :: "l"((char*)g_s.cand + (co + rank * 1440 + 64 - cq * 12)), "r"((norm2(h4, sv.x, rr) & 0xBFFFBFFFu) | par) : "memory");
            }
            __syncwarp();
        }
        {
            const uint2 sa = lds64(sb + SM_ST + tn * 8), sbb = lds64(sb + SM_ST + tn * 8 + 64);
#pragma unroll
            for (int i = 0; i < 5; i++) { ha[i] = badd2(ha[i], norm2(ha[i], sa.x, sa.y)); hb[i] = badd2(hb[i], norm2(hb[i], sbb.x, sbb.y)); }
            const bool hf = (c & 1) && cq == 0;
            const uint32_t o16 = sb + SM_XT + (hf ? 16384 + tn * 16 : tn * 64 + (cq - (c & 1)) * 16), o4 = sb + SM_XT + ((c & 1) ? tn * 64 + 48 : 16384 + tn * 16) + cq * 4;
            sts128(o16, ha[0], ha[1], ha[2], ha[3]); sts32(o4, ha[4]);
            sts128(o16 + (hf ? 128 : 512), hb[0], hb[1], hb[2], hb[3]); sts32(o4 + ((c & 1) ? 512 : 128), hb[4]);
        }
        if (warp >= 8) {
            STAMP(19);
            mbar_wait(mb + MB_KEY * 8);
            STAMP(20);
            const uint32_t mk = lds32(sb + SM_RK - 256 + (tid >> 2) * 4);
            uint32_t rank = rank4<4, 64>(sb + SM_RK + cq * 16, mk);
            rank += __shfl_xor_sync(~0u, rank, 1); rank += __shfl_xor_sync(~0u, rank, 2);
            if (rank < 8) sts64(sb + SM_SEL + rank * 8, mk, ((tid >> 2) - 64) * 1440);
        }
    }
    bar_sync(11, 640);
    STAMP(12);

    const char* gp = (const char*)g_s.cand + (go + lds32(sb + SM_SEL + 4 + (tk & 7) * 8));
    uint4 hv = ld_rlx128(gp);
    if (warp < 8) loadA();
    const bool red = warp < 6;
    const uint32_t ft = red ? (unsigned)tid / 24u : (unsigned)(tid >> 4) & 7u, fj = red ? 24 * q + tid - ft * 24 : d0 / 3 + (lane & 15);
    const uint32_t key = lds32(sb + SM_SEL + ft * 8), k16 = key << 5;
    float sig = bfr(rcpf(1.f + ex2f(__uint_as_float((k16 ^ (~((int)k16 >> 31) | 0x80000000u)) & 0xFFFF0000u) * -1.4426950408889634f)));
    uint32_t ra2 = sb + SM_RED2 + tid * 12 + ft * 16, fo = (ft * 192 + fj) * 16, oo = ((~key & 2047) * D_ + 3 * fj) * 2;
    uint32_t bx = sb + SM_XS + mr * 1168 + mi * 16 + 288 * kq, gd = mapa(sb, kq * (8 / NRED)) + (SM_GU + (q * nslot + mt) * 128) + lane * 4;
    PIN(ra2); PIN(fo); PIN(oo); PIN(bx); PIN(gd);
    asm volatile("" : "+f"(sig));
    {
        if (warp < 18) {
            int n = 0;
            while ((((hv.x ^ par) | (hv.y ^ par) | (hv.z ^ par) | (hv.w ^ par)) & 0x40004000u) && ++n < SPIN_LIMIT) hv = ld_rlx128(gp);
            sts128(sb + SM_XS + tk * 16 + tid * 16, hv.x ^ par, hv.y ^ par, hv.z ^ par, hv.w ^ par);
        }
    }
    bar_sync(14, 672);
    STAMP(13);
    {
        float c0[4] = {0.f, 0.f, 0.f, 0.f}, c1[4] = {0.f, 0.f, 0.f, 0.f}, c2[4] = {0.f, 0.f, 0.f, 0.f};
        uint32_t b[5][4];
#pragma unroll
        for (int s = 0; s < 4; s++) ldsm4(b[s], bx + s * 64);
        asm volatile("ldmatrix.sync.aligned.m8n8.x2.shared.b16 {%0,%1}, [%2];" : "=r"(b[4][0]), "=r"(b[4][1]) : "r"(bx + 256) : "memory");
        mma_bf16(c0, A[0][0], A[0][1], A[0][2], A[0][3], b[0][0], b[0][1]);
        mma_bf16(c1, A[1][0], A[1][1], A[1][2], A[1][3], b[0][2], b[0][3]);
        mma_bf16(c2, A[2][0], A[2][1], A[2][2], A[2][3], b[1][0], b[1][1]);
        mma_bf16(c0, A[3][0], A[3][1], A[3][2], A[3][3], b[1][2], b[1][3]);
        mma_bf16(c1, A[4][0], A[4][1], A[4][2], A[4][3], b[2][0], b[2][1]);
        mma_bf16(c2, A[5][0], A[5][1], A[5][2], A[5][3], b[2][2], b[2][3]);
        mma_bf16(c0, A[6][0], A[6][1], A[6][2], A[6][3], b[3][0], b[3][1]);
        mma_bf16(c1, A[7][0], A[7][1], A[7][2], A[7][3], b[3][2], b[3][3]);
        mma_bf16(c2, A[8][0], A[8][1], A[8][2], A[8][3], b[4][0], b[4][1]);
        sts128f(sb + SM_RED + tid * 16, c0[0] + c1[0] + c2[0], c0[1] + c1[1] + c2[1], c0[2] + c1[2] + c2[2], c0[3] + c1[3] + c2[3]);
    }
    bar_sync(1 + mt, 128);
    STAMP(21);
    if (mt < nslot && kq < NRED) {
        const uint32_t ra = sb + SM_RED + mt * 512 + lane * 16;
        const float4 p0 = lds128f(ra), p1 = lds128f(ra + 2560), p2 = lds128f(ra + 5120), p3 = lds128f(ra + 7680);
        const float g0 = bfr(((p0.x + p1.x) + (p2.x + p3.x)) * 64.f), g1 = bfr(((p0.y + p1.y) + (p2.y + p3.y)) * 64.f);
        const uint32_t sg = pack_bf16(g0 * rcpf(1.f + ex2f(g0 * -1.4426950408889634f)), g1 * rcpf(1.f + ex2f(g1 * -1.4426950408889634f)));
        const uint32_t gu = bmul2(sg, pack_bf16(((p0.z + p1.z) + (p2.z + p3.z)) * 64.f, ((p0.w + p1.w) + (p2.w + p3.w)) * 64.f));
        const uint32_t pstep = mapa(sb, 1) - mapa(sb, 0), gm = mapa(mb + MB_GU * 8, kq * (8 / NRED));
#pragma unroll
        for (int i = 0; i < 8 / NRED; i++) st_async1(gd + i * pstep, gu, gm + i * pstep);
    }
    mbar_wait(mb + MB_W2 * 8);
    {
        const uint32_t aa = sb + (8 * (mi >> 1) + mr) * 144 + (mi & 1) * 16 + (SM_FAR + 2304 * kq + mt * 32);
#pragma unroll
        for (int s = 0; s < 5; s++) ldsm4t(A[s], aa + s * FAR_SZ);
    }
    {
        uint32_t ba = sb + (SM_GU + 256 * kq) + (lane & 15) * 16 + (lane >> 4) * 1024, wa = sb + (SM_RED2 + kq * 2432 + mt * 64) + g * 4 + cq * 608;
        PIN(ba); PIN(wa);
        STAMP(22);
        mbar_wait(mb + MB_GU * 8);
        STAMP(23);
        float c0[4] = {0.f, 0.f, 0.f, 0.f}, c1[4] = {0.f, 0.f, 0.f, 0.f}, c2[4] = {0.f, 0.f, 0.f, 0.f};
        uint32_t b[2][4], b8, b9;
        ldsm4t(b[0], ba); ldsm4t(b[1], ba + 2048); ldsm2t(b8, b9, ba + 4096);
        mma_bf16(c0, A[0][0], A[0][1], A[0][2], A[0][3], b[0][0], b[0][1]);
        mma_bf16(c1, A[1][0], A[1][1], A[1][2], A[1][3], b[0][2], b[0][3]);
        if (nslot == 5) {
            mma_bf16(c2, A[4][0], A[4][1], A[4][2], A[4][3], b8, b9);
            mma_bf16(c0, A[2][0], A[2][1], A[2][2], A[2][3], b[1][0], b[1][1]);
            mma_bf16(c1, A[3][0], A[3][1], A[3][2], A[3][3], b[1][2], b[1][3]);
        }
        stsf(wa, c0[0] + c1[0] + c2[0]); stsf(wa + 304, c0[1] + c1[1] + c2[1]);
        if (mt < 4) { stsf(wa + 32, c0[2] + c1[2] + c2[2]); stsf(wa + 336, c0[3] + c1[3] + c2[3]); }
    }
    if (warp < 10) {
        float v[3], cnt = 3.f;
        if (red) {
            bar_sync(6, 640);
            STAMP(14);
#pragma unroll
            for (int i = 0; i < 3; i++) v[i] = ((ldsf(ra2 + i * 4) + ldsf(ra2 + i * 4 + 2432)) + (ldsf(ra2 + i * 4 + 4864) + ldsf(ra2 + i * 4 + 7296))) * sig;
        } else {
            bar_arrive(6, 640);
            cnt = 0.f;
#pragma unroll
            for (int i = 0; i < 3; i++) {
                const uint32_t cl = 3 * fj + i - d0;
                const bool ok = cl < 8 * nslot && ((~key >> 3) & 7) == q;
                const uint32_t cf = cl - (c & 1) * 8;
                v[i] = ok ? __uint_as_float(lds16(sb + SM_XT + (cf < 32 ? tslot(~key) * 64 + cf * 2 : 16384 + tslot(~key) * 16 + (cl & 7) * 2)) << 16) : 0.f;
                if (ok) cnt += 1.f;
            }
            mbar_wait(mb + MB_OUT * 8);
        }
        if (cnt != 0.f) {
            float x, y, z, w;
            asm volatile("atom.relaxed.gpu.global.add.v4.f32 {%0,%1,%2,%3}, [%4], {%5,%6,%7,%8};" : "=f"(x), "=f"(y), "=f"(z), "=f"(w)
                         : "l"((char*)g_s.fin + fo), "f"(v[0]), "f"(v[1]), "f"(v[2]), "f"(cnt) : "memory");
            if (w + cnt == 3.f * (NCL + 1)) {
                __nv_bfloat16* op = (__nv_bfloat16*)((char*)prm.out + oo);
                op[0] = __float2bfloat16(x + v[0]); op[1] = __float2bfloat16(y + v[1]); op[2] = __float2bfloat16(z + v[2]);
            }
        }
    } else bar_arrive(6, 640);
    STAMP(15);
}

typedef __nv_bfloat16 bf16;
__device__ bf16 f_n[L_ * D_], f_h[L_ * D_];
__device__ float f_k[D_ * L_], f_r[L_], f_gu[8 * F_];
__device__ int f_idx[8];
__device__ __forceinline__ float b2f(bf16 v) { return __bfloat162float(v); }
__global__ void fb_ln(const bf16* in, const bf16* wr, bf16* out) {
    const int t = blockIdx.x * 8 + (threadIdx.x >> 5), lane = threadIdx.x & 31;
    const bf16* r = (in ? in : f_h) + t * D_;
    float s1 = 0.f, s2 = 0.f, s3 = 0.f;
    for (int i = lane; i < D_; i += 32) s1 += b2f(r[i]);
    for (int o = 16; o; o >>= 1) s1 += __shfl_xor_sync(~0u, s1, o);
    for (int i = lane; i < D_; i += 32) { const float d = b2f(r[i]) - s1 / D_; s2 += d * d; }
    for (int o = 16; o; o >>= 1) s2 += __shfl_xor_sync(~0u, s2, o);
    const float m = bfr(s1 / D_), sd = bfr(sqrtf(bfr(bfr(s2 / D_) + 1e-5f)));
    for (int i = lane; i < D_; i += 32) {
        const float v = bfr(bfr(b2f(r[i]) - m) / sd);
        f_n[t * D_ + i] = __float2bfloat16(v);
        if (!in) { s3 += v * b2f(wr[i]); out[t * D_ + i] = __float2bfloat16(b2f(r[i]) + v); }
    }
    for (int o = 16; o; o >>= 1) s3 += __shfl_xor_sync(~0u, s3, o);
    f_r[t] = bfr(s3);
}
__global__ void fb_taps(Params p) {
    const int d = blockIdx.x >> 3, l = (blockIdx.x & 7) * 256 + threadIdx.x;
    const float dt = bfr(expf(bf_lo(p.logdt[d]))), lf = bfr((float)l);
    float k = 0.f;
    for (int n = d * 128; n < d * 128 + 128; n++) {
        float wr, wi, sn, cs;
        cmul(wr, wi, bf_lo(p.prm6[4][n]), bf_lo(p.prm6[5][n]), dt * bf_lo(p.prm6[2][n]), dt * bf_lo(p.prm6[3][n]));
        sincosf(dt * bf_lo(p.prm6[1][n]) * lf, &sn, &cs);
        k += expf(dt * bf_lo(p.prm6[0][n]) * lf) * (wr * cs - wi * sn);
    }
    f_k[l * D_ + d] = k;
}
__global__ void fb_conv(Params p) {
    const int t = blockIdx.x, d = threadIdx.x;
    float y = 0.f;
    for (int l = 0; l <= t; l++) y += f_k[l * D_ + d] * b2f(f_n[(t - l) * D_ + d]);
    f_h[t * D_ + d] = __float2bfloat16(bf_lo(p.x[t * D_ + d]) + bfr(bfr(y) + bfr(b2f(f_n[t * D_ + d]) * bf_lo(p.dskip[d]))));
}
__global__ void fb_top() {
    const int t = blockIdx.x * 256 + threadIdx.x;
    int rank = 0;
    for (int j = 0; j < L_; j++) rank += f_r[j] > f_r[t] || (f_r[j] == f_r[t] && j < t);
    if (rank < 8) f_idx[rank] = t;
}
__global__ void fb_ffn1(const bf16* wg, const bf16* wu) {
    const int f = blockIdx.x * 256 + threadIdx.x, j = blockIdx.y;
    float g = 0.f, u = 0.f;
    for (int i = 0; i < D_; i++) { const float v = b2f(f_n[f_idx[j] * D_ + i]); g += v * b2f(wg[i * F_ + f]); u += v * b2f(wu[i * F_ + f]); }
    g = bfr(g);
    f_gu[j * F_ + f] = bfr(bfr(g / (1.f + expf(-g))) * bfr(u));
}
__global__ void fb_ffn2(const bf16* wd, bf16* out) {
    const int d = threadIdx.x, j = blockIdx.x, t = f_idx[j];
    float y = 0.f;
    for (int f = 0; f < F_; f++) y += f_gu[j * F_ + f] * b2f(wd[f * D_ + d]);
    out[t * D_ + d] = __float2bfloat16(b2f(f_h[t * D_ + d]) + bfr(b2f(f_n[t * D_ + d]) + bfr(bfr(y) * bfr(1.f / (1.f + expf(-f_r[t]))))));
}

typedef CUresult (*EncodeFn)(CUtensorMap*, CUtensorMapDataType, cuuint32_t, void*, const cuuint64_t*, const cuuint64_t*,
                             const cuuint32_t*, const cuuint32_t*, CUtensorMapInterleave, CUtensorMapSwizzle,
                             CUtensorMapL2promotion, CUtensorMapFloatOOBfill);

void make_map(EncodeFn fn, CUtensorMap* tm, const void* p, int cols, int rows, int bc, int br) {
    cuuint64_t dims[2] = {(cuuint64_t)cols, (cuuint64_t)rows};
    cuuint64_t strides[1] = {(cuuint64_t)cols * 2};
    cuuint32_t box[2] = {(cuuint32_t)bc, (cuuint32_t)br};
    cuuint32_t es[2] = {1, 1};
    fn(tm, CU_TENSOR_MAP_DATA_TYPE_BFLOAT16, 2, const_cast<void*>(p), dims, strides, box, es, CU_TENSOR_MAP_INTERLEAVE_NONE,
       CU_TENSOR_MAP_SWIZZLE_NONE, CU_TENSOR_MAP_L2_PROMOTION_L2_128B, CU_TENSOR_MAP_FLOAT_OOB_FILL_NONE);
}

void make_map3(EncodeFn fn, CUtensorMap* tm, const void* p) {
    cuuint64_t dims[5] = {(cuuint64_t)D_, 64, 2, 4, 4};
    cuuint64_t strides[4] = {(cuuint64_t)D_ * 2, (cuuint64_t)D_ * 128, (cuuint64_t)D_ * 1024, (cuuint64_t)D_ * 256};
    cuuint32_t box[5] = {XW, 9, 2, 4, 4};
    cuuint32_t es[5] = {1, 1, 1, 1, 1};
    fn(tm, CU_TENSOR_MAP_DATA_TYPE_BFLOAT16, 5, const_cast<void*>(p), dims, strides, box, es, CU_TENSOR_MAP_INTERLEAVE_NONE,
       CU_TENSOR_MAP_SWIZZLE_NONE, CU_TENSOR_MAP_L2_PROMOTION_NONE, CU_TENSOR_MAP_FLOAT_OOB_FILL_NONE);
}

void make_map5(EncodeFn fn, CUtensorMap* tm, const void* p, int bc) {
    cuuint64_t dims[5] = {(cuuint64_t)D_, 2, 4, 4, 64};
    cuuint64_t strides[4] = {(cuuint64_t)D_ * 128, (cuuint64_t)D_ * 1024, (cuuint64_t)D_ * 256, (cuuint64_t)D_ * 2};
    cuuint32_t box[5] = {(cuuint32_t)bc, 2, 4, 4, 8};
    cuuint32_t es[5] = {1, 1, 1, 1, 1};
    fn(tm, CU_TENSOR_MAP_DATA_TYPE_BFLOAT16, 5, const_cast<void*>(p), dims, strides, box, es, CU_TENSOR_MAP_INTERLEAVE_NONE,
       CU_TENSOR_MAP_SWIZZLE_NONE, CU_TENSOR_MAP_L2_PROMOTION_NONE, CU_TENSOR_MAP_FLOAT_OOB_FILL_NONE);
}

}

extern "C" void kernel_launch(void* const* d_in, const int* in_sizes, int n_in, void* d_out, int out_size) {
    (void)in_sizes; (void)n_in; (void)out_size;
    void* fp = nullptr;
    cudaDriverEntryPointQueryResult qr;
    cudaGetDriverEntryPoint("cuTensorMapEncodeTiled", &fp, cudaEnableDefault, &qr);
    EncodeFn fn = (EncodeFn)fp;
    CUtensorMap tmG, tmU, tmD, tmO, tmX, tmH;
    make_map3(fn, &tmX, d_in[0]);
    make_map(fn, &tmG, d_in[11], F_, D_, 40, 48);
    make_map(fn, &tmU, d_in[12], F_, D_, 40, 48);
    make_map(fn, &tmD, d_in[13], D_, F_, 72, 64);
    make_map5(fn, &tmO, d_out, 32);
    make_map5(fn, &tmH, d_out, 8);
    Params p;
    p.x = (const unsigned short*)d_in[0];
    for (int i = 0; i < 6; i++) p.prm6[i] = (const unsigned short*)d_in[1 + i];
    p.logdt = (const unsigned short*)d_in[7]; p.dskip = (const unsigned short*)d_in[8];
    p.wr = (const unsigned short*)d_in[10];
    p.out = (__nv_bfloat16*)d_out;
    p.zero = 0;
    cudaGetSymbolAddress((void**)&p.gs, g_s);
    cudaFuncSetAttribute(fused_kernel, cudaFuncAttributeMaxDynamicSharedMemorySize, SM_TOTAL);
    static int nclusters = -1;
    if (nclusters < 0) {
        cudaLaunchConfig_t cfg = {};
        cudaLaunchAttribute at;
        at.id = cudaLaunchAttributeClusterDimension; at.val.clusterDim.x = CS; at.val.clusterDim.y = 1; at.val.clusterDim.z = 1;
        cfg.gridDim = dim3(NCTA); cfg.blockDim = dim3(NTHR); cfg.dynamicSmemBytes = SM_TOTAL; cfg.attrs = &at; cfg.numAttrs = 1;
        if (cudaOccupancyMaxActiveClusters(&nclusters, fused_kernel, &cfg) != cudaSuccess) { (void)cudaGetLastError(); nclusters = NCL; }
    }
    if (nclusters >= NCL && !FORCE_FALLBACK) {
        fused_kernel<<<NCTA, NTHR, SM_TOTAL>>>(p, tmG, tmU, tmD, tmO, tmX, tmH);
        return;
    }
    fb_ln<<<L_ / 8, 256>>>((const bf16*)d_in[0], nullptr, nullptr);
    fb_taps<<<D_ * 8, 256>>>(p);
    fb_conv<<<L_, D_>>>(p);
    fb_ln<<<L_ / 8, 256>>>(nullptr, (const bf16*)d_in[10], p.out);
    fb_top<<<L_ / 256, 256>>>();
    fb_ffn1<<<dim3(F_ / 256, 8), 256>>>((const bf16*)d_in[11], (const bf16*)d_in[12]);
    fb_ffn2<<<8, D_>>>((const bf16*)d_in[13], p.out);
}
```

```cpp
#include <cuda_runtime.h>
#include <cuda_bf16.h>
#include <cuda_fp16.h>
#include <cuda.h>
#include <stdint.h>

namespace {

constexpr int L_ = 2048, D_ = 576, F_ = 4608;
constexpr int NCL = 15, CS = 8, NCTA = NCL * CS, NTHR = 768;
#define PRE4 -1
#define T_SH 0
#define T_PW 1
#define T_W4 1
#define T_L18 0
#define T_EB 0
#define N_D 1
#define N_P 1
#define N_Z 0
#define FORCE_FALLBACK 0
constexpr int XW = 48, NRED = 2;
constexpr int SPIN_LIMIT = 1 << 22;

constexpr int SM_WG   = 0;
constexpr int SM_WU   = 46080;
constexpr int YP = 3392, YS = 656;
constexpr int UP = 3280, US = 656;
constexpr int SM_XT   = 92160;
constexpr int SM_U    = SM_XT + 8 * YP;
constexpr int SM_FAR  = SM_U + 8 * UP;
constexpr int FAR_SZ  = 12416;
constexpr int F_E5 = 0, F_O5 = 1536, F_E3 = 3088, F_O3 = 4624, F_E7 = 6176, F_E2 = F_E7 + 1024, F_E9 = F_E7 + 2048,
              F_H = 3088, F_O7 = F_E7 + F_H, F_O2 = F_E2 + F_H, F_O9 = F_E9 + F_H;
constexpr int SM_P    = SM_FAR + 5 * FAR_SZ;
constexpr int PN_SZ = 584 * 4, SM_PN = SM_P + 64 * 4;
constexpr int P_GS = 48 * 4, P_H7 = 192 * 4, P_HS = 72 * 4;
constexpr int PF_SZ = (192 + 216) * 4, SM_PF = SM_PN + 5 * PN_SZ + 32;
constexpr int SM_MISC = SM_PF + 5 * PF_SZ;
constexpr int SM_ST   = SM_MISC;
constexpr int SM_RK   = SM_ST + 2048;
constexpr int SM_SEL  = SM_RK + 256;
constexpr int SM_KG   = SM_SEL + 64;
constexpr int SM_SC   = SM_KG + 160;
constexpr int SM_DW   = SM_SC + 32;
constexpr int SM_MB   = SM_DW + 160;
constexpr int SM_TOTAL = SM_MB + 128;
constexpr int SM_ROW  = SM_XT - 20736;
constexpr int SM_XTL  = SM_ROW - 576 * XW;
constexpr int SM_RED2 = SM_WG;
constexpr int SM_HT   = SM_P - 512;
constexpr int SM_KEY  = SM_FAR + 10240 + 128;
constexpr int SM_CAND = SM_KEY + 1024;
constexpr int SM_XS   = SM_U;
constexpr int SM_GU   = SM_XS + 9344;
constexpr int SM_RED  = SM_GU + 5632;
static_assert(F_O9 + 1024 <= FAR_SZ && FAR_SZ % 128 == 0, "far overflow");
static_assert(SM_RED + 10240 <= SM_FAR && SM_HT + 20496 <= SM_MISC, "alias overflow");
static_assert(SM_TOTAL <= 232448, "smem overflow");
static_assert(SM_FAR % 128 == 0 && SM_XT % 128 == 0 && SM_XTL % 128 == 0 && SM_P % 16 == 0 && SM_MISC % 16 == 0 && SM_MB % 8 == 0, "align");

enum { MB_X = 0, MB_W1 = 5, MB_W2 = 6, MB_KEY = 7, MB_GU = 8, MB_Y = 9, MB_OUT = 10, MB_T = 11, MB_R = 12 };

struct __align__(128) Scratch {
    unsigned epoch, zcnt, pad[30];
    uint4  st1[L_ * 2];
    float4 acc[L_];
    uint4  cand[64 * NCL * 6];
    float4 fin[8 * 192 + 24];
};
__device__ Scratch g_s;
#define STAMP(i)

__device__ __forceinline__ uint32_t mapa(uint32_t a, uint32_t r) { uint32_t d; asm("mapa.shared::cluster.u32 %0, %1, %2;" : "=r"(d) : "r"(a), "r"(r)); return d; }
__device__ __forceinline__ void mbar_wait(uint32_t mb) {
    asm volatile("{ .reg .pred p, q; .reg .u32 n; mov.u32 n, 0;\n"
                 "W_%=: mbarrier.try_wait.parity.shared::cta.b64 p, [%0], 0; add.u32 n, n, 1; setp.lt.and.u32 q, n, 65536, !p; @q bra W_%=; }" :: "r"(mb) : "memory");
}
__device__ __forceinline__ void arm(uint32_t mb, uint32_t bytes) { asm volatile("mbarrier.arrive.expect_tx.shared::cta.b64 _, [%0], %1;" :: "r"(mb), "r"(bytes) : "memory"); }
__device__ __forceinline__ void bar_sync(int id, int n) { asm volatile("bar.sync %0, %1;" :: "r"(id), "r"(n) : "memory"); }
__device__ __forceinline__ void bar_arrive(int id, int n) { asm volatile("bar.arrive %0, %1;" :: "r"(id), "r"(n) : "memory"); }
__device__ __forceinline__ uint32_t lds16(uint32_t a) { unsigned short v; asm volatile("ld.shared.u16 %0, [%1];" : "=h"(v) : "r"(a) : "memory"); return v; }
__device__ __forceinline__ uint32_t lds32(uint32_t a) { uint32_t v; asm volatile("ld.shared.u32 %0, [%1];" : "=r"(v) : "r"(a) : "memory"); return v; }
__device__ __forceinline__ uint2 lds64(uint32_t a) { uint2 v; asm volatile("ld.shared.v2.u32 {%0,%1}, [%2];" : "=r"(v.x), "=r"(v.y) : "r"(a) : "memory"); return v; }
__device__ __forceinline__ float ldsf(uint32_t a) { float v; asm volatile("ld.shared.f32 %0, [%1];" : "=f"(v) : "r"(a) : "memory"); return v; }
__device__ __forceinline__ uint4 lds128(uint32_t a) { uint4 v; asm volatile("ld.shared.v4.u32 {%0,%1,%2,%3}, [%4];" : "=r"(v.x), "=r"(v.y), "=r"(v.z), "=r"(v.w) : "r"(a) : "memory"); return v; }
__device__ __forceinline__ float4 lds128f(uint32_t a) { float4 v; asm volatile("ld.shared.v4.f32 {%0,%1,%2,%3}, [%4];" : "=f"(v.x), "=f"(v.y), "=f"(v.z), "=f"(v.w) : "r"(a) : "memory"); return v; }
__device__ __forceinline__ void sts16(uint32_t a, uint32_t v) { asm volatile("{ .reg .b16 l, h; mov.b32 {l, h}, %1; st.shared.b16 [%0], l; }" :: "r"(a), "r"(v) : "memory"); }
__device__ __forceinline__ void sts32(uint32_t a, uint32_t v) { asm volatile("st.shared.u32 [%0], %1;" :: "r"(a), "r"(v) : "memory"); }
__device__ __forceinline__ void sts64(uint32_t a, uint32_t x, uint32_t y) { asm volatile("st.shared.v2.u32 [%0], {%1,%2};" :: "r"(a), "r"(x), "r"(y) : "memory"); }
__device__ __forceinline__ void stsf(uint32_t a, float v) { asm volatile("st.shared.f32 [%0], %1;" :: "r"(a), "f"(v) : "memory"); }
__device__ __forceinline__ void sts128(uint32_t a, uint32_t x, uint32_t y, uint32_t z, uint32_t w) { asm volatile("st.shared.v4.u32 [%0], {%1,%2,%3,%4};" :: "r"(a), "r"(x), "r"(y), "r"(z), "r"(w) : "memory"); }
__device__ __forceinline__ void sts128f(uint32_t a, float x, float y, float z, float w) { asm volatile("st.shared.v4.f32 [%0], {%1,%2,%3,%4};" :: "r"(a), "f"(x), "f"(y), "f"(z), "f"(w) : "memory"); }
__device__ __forceinline__ void ldsm4(uint32_t (&r)[4], uint32_t a) { asm volatile("ldmatrix.sync.aligned.m8n8.x4.shared.b16 {%0,%1,%2,%3}, [%4];" : "=r"(r[0]), "=r"(r[1]), "=r"(r[2]), "=r"(r[3]) : "r"(a) : "memory"); }
__device__ __forceinline__ void ldsm4t(uint32_t (&r)[4], uint32_t a) { asm volatile("ldmatrix.sync.aligned.m8n8.x4.trans.shared.b16 {%0,%1,%2,%3}, [%4];" : "=r"(r[0]), "=r"(r[1]), "=r"(r[2]), "=r"(r[3]) : "r"(a) : "memory"); }
__device__ __forceinline__ void ldsm2t(uint32_t& r0, uint32_t& r1, uint32_t a) { asm volatile("ldmatrix.sync.aligned.m8n8.x2.trans.shared.b16 {%0,%1}, [%2];" : "=r"(r0), "=r"(r1) : "r"(a) : "memory"); }
__device__ __forceinline__ void stsm4t(uint32_t a, uint32_t r0, uint32_t r1, uint32_t r2, uint32_t r3) { asm volatile("stmatrix.sync.aligned.m8n8.x4.trans.shared.b16 [%0], {%1,%2,%3,%4};" :: "r"(a), "r"(r0), "r"(r1), "r"(r2), "r"(r3) : "memory"); }
__device__ __forceinline__ void stsm4(uint32_t a, uint32_t r0, uint32_t r1, uint32_t r2, uint32_t r3) { asm volatile("stmatrix.sync.aligned.m8n8.x4.shared.b16 [%0], {%1,%2,%3,%4};" :: "r"(a), "r"(r0), "r"(r1), "r"(r2), "r"(r3) : "memory"); }
__device__ __forceinline__ void stsm2t(uint32_t a, uint32_t r0, uint32_t r1) { asm volatile("stmatrix.sync.aligned.m8n8.x2.trans.shared.b16 [%0], {%1,%2};" :: "r"(a), "r"(r0), "r"(r1) : "memory"); }
__device__ __forceinline__ uint4 ldg128(const void* p) { uint4 v; asm volatile("ld.global.nc.v4.u32 {%0,%1,%2,%3}, [%4];" : "=r"(v.x), "=r"(v.y), "=r"(v.z), "=r"(v.w) : "l"(p)); return v; }
__device__ __forceinline__ uint32_t ldg16(const void* p) { unsigned short v; asm volatile("ld.global.nc.u16 %0, [%1];" : "=h"(v) : "l"(p)); return v; }
__device__ __forceinline__ uint32_t opaque(uint32_t v) { uint32_t r; asm volatile("mov.b32 %0, %1;" : "=r"(r) : "r"(v)); return r; }
__device__ __forceinline__ void mma_f16(float (&d)[4], const uint32_t (&a)[4], uint32_t b0, uint32_t b1) {
    asm volatile("mma.sync.aligned.m16n8k16.row.col.f32.f16.f16.f32 {%0,%1,%2,%3}, {%4,%5,%6,%7}, {%8,%9}, {%0,%1,%2,%3};"
        : "+f"(d[0]), "+f"(d[1]), "+f"(d[2]), "+f"(d[3]) : "r"(a[0]), "r"(a[1]), "r"(a[2]), "r"(a[3]), "r"(b0), "r"(b1));
}
__device__ __forceinline__ void mma_f16_z(float (&d)[4], const uint32_t (&a)[4], uint32_t b0, uint32_t b1) {
    asm volatile("mma.sync.aligned.m16n8k16.row.col.f32.f16.f16.f32 {%0,%1,%2,%3}, {%4,%5,%6,%7}, {%8,%9}, {%10,%10,%10,%10};"
        : "=f"(d[0]), "=f"(d[1]), "=f"(d[2]), "=f"(d[3]) : "r"(a[0]), "r"(a[1]), "r"(a[2]), "r"(a[3]), "r"(b0), "r"(b1), "f"(0.f));
}
__device__ __forceinline__ void mma_bf16(float (&d)[4], uint32_t a0, uint32_t a1, uint32_t a2, uint32_t a3, uint32_t b0, uint32_t b1) {
    asm volatile("mma.sync.aligned.m16n8k16.row.col.f32.bf16.bf16.f32 {%0,%1,%2,%3}, {%4,%5,%6,%7}, {%8,%9}, {%0,%1,%2,%3};"
        : "+f"(d[0]), "+f"(d[1]), "+f"(d[2]), "+f"(d[3]) : "r"(a0), "r"(a1), "r"(a2), "r"(a3), "r"(b0), "r"(b1));
}
__device__ __forceinline__ void mma_bf16_k8(float (&d)[4], uint32_t a0, uint32_t a1, uint32_t b0) {
    asm volatile("mma.sync.aligned.m16n8k8.row.col.f32.bf16.bf16.f32 {%0,%1,%2,%3}, {%4,%5}, {%6}, {%0,%1,%2,%3};"
        : "+f"(d[0]), "+f"(d[1]), "+f"(d[2]), "+f"(d[3]) : "r"(a0), "r"(a1), "r"(b0));
}
__device__ __forceinline__ uint32_t pack_f16(float lo, float hi) { uint32_t r; asm("cvt.rn.f16x2.f32 %0, %1, %2;" : "=r"(r) : "f"(hi), "f"(lo)); return r; }
__device__ __forceinline__ uint32_t pack_bf16(float lo, float hi) { uint32_t r; asm("cvt.rn.bf16x2.f32 %0, %1, %2;" : "=r"(r) : "f"(hi), "f"(lo)); return r; }
__device__ __forceinline__ float bf_lo(uint32_t v) { return __uint_as_float(v << 16); }
__device__ __forceinline__ float bf_hi(uint32_t v) { return __uint_as_float(v & 0xFFFF0000u); }
__device__ __forceinline__ float bfr(float x) { return __uint_as_float(pack_bf16(0.f, x)); }
__device__ __forceinline__ uint32_t badd2(uint32_t a, uint32_t b) { uint32_t r; asm("add.rn.bf16x2 %0, %1, %2;" : "=r"(r) : "r"(a), "r"(b)); return r; }
__device__ __forceinline__ uint32_t bmul2(uint32_t a, uint32_t b) { uint32_t r; asm("mul.rn.bf16x2 %0, %1, %2;" : "=r"(r) : "r"(a), "r"(b)); return r; }
__device__ __forceinline__ uint32_t hadd2(uint32_t a, uint32_t b) { uint32_t r; asm("add.rn.f16x2 %0, %1, %2;" : "=r"(r) : "r"(a), "r"(b)); return r; }
__device__ __forceinline__ uint32_t hmul2(uint32_t a, uint32_t b) { uint32_t r; asm("mul.rn.f16x2 %0, %1, %2;" : "=r"(r) : "r"(a), "r"(b)); return r; }
__device__ __forceinline__ uint32_t hfma2(uint32_t a, uint32_t b, uint32_t c) { uint32_t r; asm("fma.rn.f16x2 %0, %1, %2, %3;" : "=r"(r) : "r"(a), "r"(b), "r"(c)); return r; }
__device__ __forceinline__ uint32_t hneg2(uint32_t a) { uint32_t r; asm("neg.f16x2 %0, %1;" : "=r"(r) : "r"(a)); return r; }
__device__ __forceinline__ float rcpf(float x) { float r; asm("rcp.approx.ftz.f32 %0, %1;" : "=f"(r) : "f"(x)); return r; }
__device__ __forceinline__ float sqrta(float x) { float r; asm("sqrt.approx.ftz.f32 %0, %1;" : "=f"(r) : "f"(x)); return r; }
__device__ __forceinline__ float ex2f(float x) { float r; asm("ex2.approx.ftz.f32 %0, %1;" : "=f"(r) : "f"(x)); return r; }
__device__ __forceinline__ void st_async4(uint32_t a, uint32_t x, uint32_t y, uint32_t z, uint32_t w, uint32_t mb) {
    asm volatile("st.async.shared::cluster.mbarrier::complete_tx::bytes.v4.u32 [%0], {%1,%2,%3,%4}, [%5];" :: "r"(a), "r"(x), "r"(y), "r"(z), "r"(w), "r"(mb) : "memory"); }
__device__ __forceinline__ void st_async1(uint32_t a, uint32_t x, uint32_t mb) {
    asm volatile("st.async.shared::cluster.mbarrier::complete_tx::bytes.u32 [%0], %1, [%2];" :: "r"(a), "r"(x), "r"(mb) : "memory"); }
__device__ __forceinline__ unsigned ld_rlx(const void* p) { unsigned v; asm volatile("ld.relaxed.gpu.global.u32 %0, [%1];" : "=r"(v) : "l"(p) : "memory"); return v; }
__device__ __forceinline__ unsigned ld_acq(const void* p) { unsigned v; asm volatile("ld.acquire.gpu.global.u32 %0, [%1];" : "=r"(v) : "l"(p) : "memory"); return v; }
__device__ __forceinline__ uint2 ld_rlx64(const void* p) { unsigned long long v; asm volatile("ld.relaxed.gpu.global.u64 %0, [%1];" : "=l"(v) : "l"(p) : "memory"); return make_uint2((unsigned)v, (unsigned)(v >> 32)); }
__device__ __forceinline__ void st_rlx128(void* p, uint32_t x, uint32_t y, uint32_t z, uint32_t w) {
    asm volatile("st.relaxed.gpu.global.v2.u64 [%0], {%1,%2};" :: "l"(p), "l"((unsigned long long)x | ((unsigned long long)y << 32)), "l"((unsigned long long)z | ((unsigned long long)w << 32)) : "memory"); }
__device__ __forceinline__ uint4 ld_rlx128(const void* p) { unsigned long long a, b; asm volatile("ld.relaxed.gpu.global.v2.u64 {%0,%1}, [%2];" : "=l"(a), "=l"(b) : "l"(p) : "memory"); return make_uint4((unsigned)a, (unsigned)(a >> 32), (unsigned)b, (unsigned)(b >> 32)); }
__device__ __forceinline__ void tma2d(uint32_t dst, const CUtensorMap* tm, int x, int y, uint32_t mb) {
    asm volatile("cp.async.bulk.tensor.2d.shared::cluster.global.mbarrier::complete_tx::bytes [%0], [%1, {%3, %4}], [%2];"
                 :: "r"(dst), "l"(tm), "r"(mb), "r"(x), "r"(y) : "memory");
}
__device__ __forceinline__ void cmul(float& xr, float& xi, float ar, float ai, float br, float bi) {
    const float r = fmaf(ar, br, -ai * bi), i = fmaf(ar, bi, ai * br); xr = r; xi = i;
}
__device__ __forceinline__ void csq(float& xr, float& xi, float ar, float ai) {
    const float r = fmaf(ar, ar, -ai * ai), i = (ar + ar) * ai; xr = r; xi = i;
}
__device__ __forceinline__ void cexp_s(float& zr, float& zi, float e2, float turns) {
    const float mag = ex2f(e2), r = (turns - rintf(turns)) * 6.283185307179586f;
    zr = mag * __cosf(r); zi = mag * __sinf(r);
}
__device__ __forceinline__ uint32_t ln_stats(float s1, float s2) {
    const float m = s1 * (1.f / D_);
    const float var = fmaxf(fmaf(s2, 1.f / D_, -m * m), 0.f);
    return pack_bf16(m, sqrta(bfr(bfr(var) + 1e-5f)));
}
__device__ __forceinline__ uint32_t rsplit(float rs) { const float h = bfr(rs); return pack_bf16(h, rs - h); }
__device__ __forceinline__ uint32_t norm2(uint32_t v, uint32_t mx, uint32_t hl) {
    uint32_t r;
    asm("{ .reg .b16 m, h, l, x; .reg .b32 m2, h2, l2, d, t; mov.b32 {m, x}, %2; mov.b32 {h, l}, %3; mov.b32 m2, {m, m}; mov.b32 h2, {h, h}; mov.b32 l2, {l, l};\n"
        "sub.rn.bf16x2 d, %1, m2; mul.rn.bf16x2 t, d, l2; fma.rn.bf16x2 %0, d, h2, t; }" : "=r"(r) : "r"(v), "r"(mx), "r"(hl));
    return r;
}
template <int N, int S>
__device__ __forceinline__ uint32_t rank4(uint32_t a, uint32_t key) {
    uint32_t r0 = 0, r1 = 0, r2 = 0, r3 = 0;
#pragma unroll
    for (int i = 0; i < N; i++) {
        const uint4 o = lds128(a + i * S);
        r0 += (key - o.x) >> 31; r1 += (key - o.y) >> 31; r2 += (key - o.z) >> 31; r3 += (key - o.w) >> 31;
    }
    return (r0 + r1) + (r2 + r3);
}
typedef uint32_t H2C;
__device__ __forceinline__ H2C splat(float r, float i) { return pack_f16(r, i); }
__device__ __forceinline__ void hcmul(uint32_t& xr, uint32_t& xi, uint32_t R, uint32_t I, H2C m) {
    asm("{ .reg .b16 a, b; .reg .b32 a2, b2, t; mov.b32 {a, b}, %4; mov.b32 a2, {a, a}; mov.b32 b2, {b, b};\n"
        "mul.rn.f16x2 t, %3, b2; neg.f16x2 t, t; fma.rn.f16x2 %0, %2, a2, t; mul.rn.f16x2 t, %3, a2; fma.rn.f16x2 %1, %2, b2, t; }"
        : "=&r"(xr), "=r"(xi) : "r"(R), "r"(I), "r"(m));
}
__device__ __forceinline__ void expand4(uint32_t are, uint32_t aim, uint32_t R0, uint32_t R1, uint32_t I0, uint32_t I1, H2C m4) {
    uint32_t R2, I2, R3, I3;
    hcmul(R2, I2, R0, I0, m4); hcmul(R3, I3, R1, I1, m4);
    sts128(are, R0, R1, R2, R3);
    sts128(aim, I0, I1, I2, I3);
}
__device__ __forceinline__ void expand8(uint32_t are, uint32_t aim, float sr, float si, float m1r, float m1i, float m2r, float m2i, H2C m4) {
    float r1, i1, r2, i2, r3, i3;
    cmul(r1, i1, sr, si, m1r, m1i); cmul(r2, i2, sr, si, m2r, m2i); cmul(r3, i3, r1, i1, m2r, m2i);
    expand4(are, aim, pack_f16(sr, r1), pack_f16(r2, r3), pack_f16(si, i1), pack_f16(i2, i3), m4);
}
__device__ __forceinline__ void put16(uint32_t a, uint32_t v) { sts16(a, v); sts16(a + 6, v); }

struct Params {
    const unsigned short *logdt, *dskip, *prm6[6], *x, *wr;
    __nv_bfloat16* out;
    Scratch* gs;
    unsigned zero;
};
__device__ __forceinline__ uint32_t tslot(uint32_t t) { return (t & 7) * 32 + ((t >> 4) & 24) + ((t >> 8) & 6) + ((t >> 6) & 1); }
#define CP(x) ((x) | zero)
#define PIN(x) asm volatile("or.b32 %0, %0, %1;" : "+r"(x) : "r"(zero))
__device__ __forceinline__ void wgmma32(float (&d)[4][4], const uint32_t (&a)[4], uint32_t dlo) {
    asm volatile("{ .reg .b64 ds; mov.b64 ds, {%20, %21};\n"
                 "wgmma.mma_async.sync.aligned.m64n32k16.f32.f16.f16 {%0,%1,%2,%3,%4,%5,%6,%7,%8,%9,%10,%11,%12,%13,%14,%15}, {%16,%17,%18,%19}, ds, 1, 1, 1, 0; }"
        : "+f"(d[0][0]), "+f"(d[0][1]), "+f"(d[0][2]), "+f"(d[0][3]), "+f"(d[1][0]), "+f"(d[1][1]), "+f"(d[1][2]), "+f"(d[1][3]),
          "+f"(d[2][0]), "+f"(d[2][1]), "+f"(d[2][2]), "+f"(d[2][3]), "+f"(d[3][0]), "+f"(d[3][1]), "+f"(d[3][2]), "+f"(d[3][3])
        : "r"(a[0]), "r"(a[1]), "r"(a[2]), "r"(a[3]), "r"(dlo), "n"(128 >> 4));
}

__global__ void __cluster_dims__(CS, 1, 1) __launch_bounds__(NTHR, 1)
fused_kernel(const __grid_constant__ Params prm, const __grid_constant__ CUtensorMap tmG, const __grid_constant__ CUtensorMap tmU,
             const __grid_constant__ CUtensorMap tmD, const __grid_constant__ CUtensorMap tmO, const __grid_constant__ CUtensorMap tmX, const __grid_constant__ CUtensorMap tmH)
{
    extern __shared__ __align__(1024) unsigned char smem[];
    const int tid = threadIdx.x, lane = tid & 31, warp = __shfl_sync(~0u, tid >> 5, 0);
    const int c = blockIdx.x >> 3, q = blockIdx.x & 7;
    const int nslot = (c < NCL - 1) ? 5 : 2;
    const int d0 = 40 * c;
    const uint32_t sb = opaque((uint32_t)__cvta_generic_to_shared(smem));
    const uint32_t mb = sb + SM_MB;
    Scratch& g_s = *prm.gs;
    const unsigned& zero = prm.zero;
    STAMP(0);

    if (warp >= 20) {
        unsigned epoch = 0;
        if (warp == 20) {
            if (lane == 0) {
#pragma unroll
                for (int i = 0; i < 13; i++)
                    asm volatile("mbarrier.init.shared::cta.b64 [%0], %1;" :: "r"(mb + i * 8), "r"((i == MB_R || i < 5) ? 2 : i == MB_Y ? 1 + 4 * nslot : 1) : "memory");
                asm volatile("fence.mbarrier_init.release.cluster;" ::: "memory");
                arm(mb + MB_W1 * 8, 92160); arm(mb + MB_W2 * 8, nslot * 9216); arm(mb + MB_KEY * 8, 256); arm(mb + MB_GU * 8, nslot * 1024); arm(mb + MB_T * 8, 576 * XW);
                const int bytes = max(min(18, L_ - 18 * (int)blockIdx.x), 1) * (D_ * 2);
                arm(mb + MB_R * 8, bytes);
            }
            __syncwarp();
        } else if (warp == 22) {
            epoch = ld_rlx(&g_s.epoch);
            if (lane < 18 ? 18 * c + lane < 256 : lane < 31) (lane < 18 ? &g_s.acc[256 * q + 18 * c] : &g_s.fin[13 * (int)blockIdx.x - 18])[lane] = make_float4(0.f, 0.f, 0.f, 0.f);
        } else if (warp == 23 && lane == 0) asm volatile("prefetch.tensormap [%0];" :: "l"(&tmX) : "memory");
        asm volatile("barrier.cluster.arrive.relaxed.aligned;" ::: "memory");
        bar_sync(12, NTHR);
        uint4 wv = make_uint4(0, 0, 0, 0), wv2, wv3;
        if (warp == 22) {
            if (lane == 0) { sts32(sb + SM_SC + 28, epoch); asm volatile("mbarrier.arrive.shared::cta.b64 _, [%0];" :: "r"(mb + MB_R * 8) : "memory"); }
            epoch++;
            asm volatile("fence.acq_rel.gpu;" ::: "memory");
            __syncwarp();
            if (lane == 0) asm volatile("red.relaxed.gpu.global.add.u32 [%0], 1;" :: "l"(&g_s.zcnt) : "memory");
            STAMP(1);
            wv2 = ldg128((const uint4*)prm.wr + lane); wv3 = ldg128((const uint4*)prm.wr + 32 + lane);
            if (lane < 8) wv = ldg128((const uint4*)prm.wr + 64 + lane);
            if (lane < 5) {
                uint4 v = make_uint4(0, 0, 0, 0);
                if (lane < nslot) v = ldg128((const uint4*)(prm.wr + d0) + lane);
                sts128(sb + SM_DW + lane * 16, v.x, v.y, v.z, v.w);
            }
            __syncwarp();
            if (lane < 5) asm volatile("mbarrier.arrive.shared::cta.b64 _, [%0];" :: "r"(mb + (MB_X + lane) * 8) : "memory");
        }
        if (warp == 21) {
            if (lane == 0) { asm volatile("prefetch.tensormap [%0];" :: "l"(&tmG) : "memory"); asm volatile("prefetch.tensormap [%0];" :: "l"(&tmU) : "memory"); asm volatile("prefetch.tensormap [%0];" :: "l"(&tmD) : "memory"); }
            __syncwarp();
            bar_sync(15, 672);
            asm volatile("fence.proxy.async.shared::cta;" ::: "memory");
#pragma unroll 1
            for (int i = 0; i < 24; i++) {
                if (lane == 0) tma2d(sb + SM_WG + i * 3840, i < 12 ? &tmG : &tmU, 320 * c + 8 * nslot * q, 48 * (i < 12 ? i : i - 12), mb + MB_W1 * 8);
            }
            STAMP(1);
            return;
        }
        if (warp == 20) {
            if (lane == 0) {
                asm volatile("cp.async.bulk.shared::cluster.global.mbarrier::complete_tx::bytes [%0], [%1], %2, [%3];"
                             :: "r"(sb + SM_ROW), "l"(prm.x + min(18 * (int)blockIdx.x, L_ - 1) * D_), "r"(max(min(18, L_ - 18 * (int)blockIdx.x), 1) * (D_ * 2)), "r"(mb + MB_R * 8) : "memory");
            }
            __syncwarp();
            mbar_wait(mb + MB_R * 8);
            if (lane == 0) {
                asm volatile("cp.async.bulk.tensor.5d.shared::cluster.global.mbarrier::complete_tx::bytes [%0], [%1, {%3, %4, %5, %5, %5}], [%2];"
                             :: "r"(sb + SM_XTL), "l"(&tmX), "r"(mb + MB_T * 8), "r"(d0 & ~15), "r"(8 * q), "r"(0) : "memory");
            }
            STAMP(6);
        }
        asm volatile("barrier.cluster.wait.aligned;" ::: "memory");
        bar_sync(13, 608);
        asm volatile("fence.proxy.async.shared::cta;" ::: "memory");
        {
            const int idx = lane * 3 + max(warp - 21, 0), sl = nslot - 1 - (idx >> 3), pe = (idx + q + 1) & 7;
            if (sl >= 0) {
                if (pe == q) arm(mb + (MB_X + sl) * 8, 7 * 512);
                else {
                    const uint32_t rb_ = mapa(sb, pe);
                    asm volatile("cp.async.bulk.shared::cluster.shared::cta.mbarrier::complete_tx::bytes [%0], [%1], 512, [%2];"
                                 :: "r"(rb_ + SM_U + 128 + q * UP + sl * US), "r"(sb + SM_XT + 128 + (q & 3) * 16 + pe * YP + sl * YS), "r"(rb_ + SM_MB + (MB_X + sl) * 8) : "memory");
                }
            }
        }
        STAMP(1);
        if (warp == 20 && lane == 0) { asm volatile("prefetch.tensormap [%0];" :: "l"(&tmO) : "memory"); asm volatile("prefetch.tensormap [%0];" :: "l"(&tmH) : "memory"); }
        if (warp == 22) {
            __syncwarp();
            mbar_wait(mb + (MB_X + 1) * 8);
            const uint32_t old = (epoch & 1) ? 0u : 0x40004000u;
#pragma unroll
            for (int t = 0; t < 2; t++)
                if ((lane & 7) < 6) g_s.cand[((q * 8 + 4 * t + (lane >> 3)) * NCL + c) * 6 + (lane & 7)] = make_uint4(old, old, old, old);
            float a[4] = {0.f, 0.f, 0.f, 0.f};
            const uint32_t one = 0x3F803F80u;
            mma_bf16(a, one, one, one, one, wv.x, wv.y);  mma_bf16(a, one, one, one, one, wv.z, wv.w);
            mma_bf16(a, one, one, one, one, wv2.x, wv2.y); mma_bf16(a, one, one, one, one, wv2.z, wv2.w);
            mma_bf16(a, one, one, one, one, wv3.x, wv3.y); mma_bf16(a, one, one, one, one, wv3.z, wv3.w);
            float s = a[0] + a[1];
            s += __shfl_xor_sync(~0u, s, 1); s += __shfl_xor_sync(~0u, s, 2);
            stsf(sb + SM_SC + 24, s);
            __syncwarp();
            if (lane == 0) {
                int n = 0;
                while ((int)(ld_acq(&g_s.zcnt) - epoch * NCTA) < 0 && ++n < SPIN_LIMIT) __nanosleep(200);
                arm(mb + MB_Y * 8, 8 * 512 * nslot);
                if (blockIdx.x == 0) g_s.epoch = epoch;
            }
            STAMP(2);
            return;
        }
        if (warp == 23) {
#pragma unroll 1
            for (int kk = nslot - 1; kk >= 0; kk--) {
                __syncwarp();
                bar_sync(6 + kk, 160);
                if (lane == 0) { asm volatile("fence.proxy.async.shared::cta;" ::: "memory"); tma2d(sb + SM_FAR + kk * FAR_SZ, &tmD, 72 * q, 320 * c + 64 * kk, mb + MB_W2 * 8); }
            }
            return;
        }
        __syncwarp();
        bar_sync(14, 672);
        if (lane == 0) {
            asm volatile("fence.proxy.async.shared::cta;" ::: "memory");
            asm volatile("cp.async.bulk.tensor.5d.global.shared::cta.bulk_group [%0, {%2, %4, %4, %4, %3}], [%1];" :: "l"(&tmH), "r"(sb + SM_XT + 16384), "r"(d0 + ((c & 1) ? 0 : 32)), "r"(8 * q), "r"(0) : "memory");
            asm volatile("cp.async.bulk.tensor.5d.global.shared::cta.bulk_group [%0, {%2, %4, %4, %4, %3}], [%1];" :: "l"(&tmO), "r"(sb + SM_XT), "r"(d0 + (c & 1) * 8), "r"(8 * q), "r"(0) : "memory");
            asm volatile("cp.async.bulk.commit_group;" ::: "memory");
            asm volatile("cp.async.bulk.wait_group 0;" ::: "memory");
            asm volatile("fence.proxy.async.global;" ::: "memory");
            asm volatile("mbarrier.arrive.shared::cta.b64 _, [%0];" :: "r"(mb + MB_OUT * 8) : "memory");
        }
        STAMP(2);
        return;
    }

    const int g = lane >> 2, cq = lane & 3;
    const int k = warp >> 2, wq = warp & 3;
    const int trow = 18 * blockIdx.x + warp;
    const bool rowact = warp < 18 && trow < L_;
    const int dch = min(d0 + 8 * k + q, D_ - 1);
    uint32_t pv[6];
    const uint32_t pofs = opaque((dch * 128 + wq * 32 + lane) * 2);
#pragma unroll
    for (int i = 0; i < 6; i++) pv[i] = ldg16((const char*)prm.prm6[i] + pofs);
    const uint32_t pLdt = ldg16(prm.logdt + dch), pD = ldg16(prm.dskip + dch);
    const int tn = 16 * (warp & 15) + g;
    uint32_t xa[5], xb[5];
    asm volatile("barrier.cluster.arrive.relaxed.aligned;" ::: "memory");
    uint4* const st1p = &g_s.st1[(((trow >> 3) & 7) * 256 + ((trow >> 6) & 31) * 8 + (trow & 7)) * 2 + (lane >> 2)];
    const bool pub = rowact && (lane & 0x1B) == 0;
    if (pub) st_rlx128(st1p, 0, 0, 0, 0);
    {
        const uint32_t za = sb + SM_P + tid * 16;
        sts128(za, 0, 0, 0, 0);
        if (tid < (SM_MISC - SM_P) / 16 - 640) sts128(za + 10240, 0, 0, 0, 0);
        if (N_Z == 0) sts128(sb + ((wq & 2) ? SM_U : SM_XT + (q & 3) * 16) + ((tid >> 3) & 7) * ((wq & 2) ? UP : YP) + k * YS + (lane & 7) * 16, 0, 0, 0, 0);
        if (N_Z == 1 || (N_Z == 2 && wq < 2)) sts128(sb + SM_U + ((tid >> 3) & 7) * UP + k * US + (lane & 7) * 16, 0, 0, 0, 0);
    }
    bar_sync(12, NTHR);
    const uint32_t dep = lds32(sb + SM_P);
#define PV(x) __uint_as_float(__byte_perm(dep, x, 0x5410))
    STAMP(1);
    const uint32_t fb = sb + SM_FAR + k * FAR_SZ;
    const uint32_t pn = sb + SM_PN + k * PN_SZ, pf = sb + SM_PF + k * PF_SZ;
    unsigned epoch;
    {
        const uint32_t kb = fb + wq * 3072;
        const uint32_t kl = kb + lane * 16;
        uint32_t Af[4][4];
        float sr, si, z1r, z1i, z2r, z2i, z4r, z4i, hr, hi_;
        {
            const float dt = bfr(ex2f(PV(pLdt) * 1.4426950408889634f));
            const float e2 = dt * PV(pv[0]) * 1.4426950408889634f, an = dt * PV(pv[1]);
            float ar, ai, br, bi, cr, ci, dr, di;
            { const float m = ex2f(e2 * 8.f); ar = m * __cosf(an * 8.f); ai = m * __sinf(an * 8.f); }
            csq(br, bi, ar, ai); csq(cr, ci, br, bi); csq(dr, di, cr, ci);
            const H2C m4 = splat(cr, ci);
            {
                float r3, i3;
                cmul(r3, i3, ar, ai, br, bi);
                expand4(kl, kl + 1024, pack_f16(1.f, ar), pack_f16(br, r3), pack_f16(0.f, ai), pack_f16(bi, i3), m4);
            }
            expand8(kl + 512, kl + 1536, dr, di, ar, ai, br, bi, m4);
            { const float m = ex2f(e2); z1r = m * __cosf(an); z1i = -m * __sinf(an); }
            cexp_s(hr, hi_, e2 * 128.f, an * (-128.f * 0.15915494309189535f));
            csq(z2r, z2i, z1r, z1i); csq(z4r, z4i, z2r, z2i);
            const uint32_t dep2 = lds32(sb + SM_P + 4);
#define PW(x) __uint_as_float(__byte_perm(dep2, x, 0x5410))
            cmul(sr, si, PW(pv[4]), PW(pv[5]), dt * PW(pv[2]), dt * PW(pv[3]));
            const unsigned E = min(max(__reduce_max_sync(~0u, __float_as_uint(fmaxf(fmaxf(fabsf(sr), fabsf(si)), fabsf(PW(pD)) * (1.f / 8192.f)))) >> 23, 1u), 253u);
            const float sc = __uint_as_float((254u - E) << 23);
            sr *= sc; si *= -sc;
            sts64(sb + SM_KG + warp * 8, E, __reduce_add_sync(~0u, __float2int_rn(sr * 16777216.f)));
            if (N_D) stsf(sb + SM_DW + 96 + k * 4, PW(pD));
        }
        __syncwarp();
#pragma unroll
        for (int ks = 0; ks < 4; ks++) ldsm4t(Af[ks], kb + (lane >> 3) * 512 + (lane & 7) * 16 + ks * 128);
        STAMP(2);
        const uint32_t la = kb + ((lane >> 3) & 1) * 512 + (lane >> 4) * 128 + (lane & 7) * 16;
        uint32_t kp[5][2], b0[4], b1[4], b2[4], b3[4], c0[4], c1[4], c2[4], c3[4];
        auto mm2 = [&](int t, uint32_t (&b0)[4], uint32_t (&b1)[4], uint32_t (&b2)[4], uint32_t (&b3)[4]) {
            float a0[4] = {0.f, 0.f, 0.f, 0.f}, a1[4] = {0.f, 0.f, 0.f, 0.f};
            mma_f16(a0, Af[0], b0[0], b0[1]); mma_f16(a1, Af[0], b2[0], b2[1]); mma_f16(a0, Af[1], b0[2], b0[3]); mma_f16(a1, Af[1], b2[2], b2[3]);
            mma_f16(a0, Af[2], b1[0], b1[1]); mma_f16(a1, Af[2], b3[0], b3[1]); mma_f16(a0, Af[3], b1[2], b1[3]); mma_f16(a1, Af[3], b3[2], b3[3]);
            kp[t][0] = pack_f16(a0[1], a0[0]); kp[t][1] = pack_f16(a0[3], a0[2]); kp[t + 1][0] = pack_f16(a1[1], a1[0]); kp[t + 1][1] = pack_f16(a1[3], a1[2]);
        };
        auto ln1 = [&]() {
        mbar_wait(mb + MB_R * 8);
        epoch = lds32(sb + SM_SC + 28) + 1;
        {
            const uint32_t ra = sb + SM_ROW + warp * (D_ * 2);
            const uint4 r0 = lds128(ra + lane * 16), r1 = lds128(ra + 512 + lane * 16);
            const uint32_t rx[9] = {r0.x, r0.y, r0.z, r0.w, r1.x, r1.y, r1.z, r1.w, lds32(ra + 1024 + lane * 4)};
            float a0 = bf_lo(rx[0]), a1 = bf_hi(rx[0]), c0 = a0 * a0, c1 = a1 * a1;
#pragma unroll
            for (int i = 1; i < 9; i++) { const float l = bf_lo(rx[i]), h = bf_hi(rx[i]); a0 += l; a1 += h; c0 = fmaf(l, l, c0); c1 = fmaf(h, h, c1); }
            a0 += a1; c0 += c1;
            float s1 = ((lane & 1) ? c0 : a0) + __shfl_xor_sync(~0u, (lane & 1) ? a0 : c0, 1);
#pragma unroll
            for (int o = 2; o < 32; o <<= 1) s1 += __shfl_xor_sync(~0u, s1, o);
            const float s2 = __shfl_xor_sync(~0u, s1, 1);
            const uint32_t ms = ln_stats(s1, s2);
            const uint32_t p0 = __byte_perm(ms, epoch | 0x8000u, 0x5410), p1 = rsplit(rcpf(bf_hi(ms)));
            if (pub) st_rlx128(st1p, p0, p1, p0, p1);
        }
        mbar_wait(mb + MB_R * 8);
        STAMP(1);
        };
        const uint4* sp = &g_s.st1[(256 * q + tn) * 2];
        uint2 sa, sc;
        auto poll = [&]() { sa = ld_rlx64(sp); sc = ld_rlx64(sp + 16); };
        auto norm = [&]() {
        STAMP(3);
        if (warp < 16) {
            uint32_t va[5], vc[5];
            poll();
            mbar_wait(mb + MB_T * 8);
            {
                const uint32_t xt = sb + SM_XTL + (c & 1) * 16 + (72 * wq + 18 * k + g) * (2 * XW);
                uint4 a4 = lds128(xt + cq * 16), b4 = lds128(xt + cq * 16 + 18 * XW);
                va[0] = a4.x; va[1] = a4.y; va[2] = a4.z; va[3] = a4.w; va[4] = lds32(xt + 64 + cq * 4);
                vc[0] = b4.x; vc[1] = b4.y; vc[2] = b4.z; vc[3] = b4.w; vc[4] = lds32(xt + (64 + 18 * XW) + cq * 4);
            }
            const int d4 = 2 * (lane >> 3) + (lane & 1), d1_ = lane & 7;
            const uint32_t own = SM_U + 128 + q * (UP - YP), oth = SM_XT + 128 + (q & 3) * 16;
            uint32_t a4 = sb + warp * 32 + d4 * YP + (d4 == q ? own : oth) + ((lane & 7) >> 1) * YS;
            uint32_t a1 = sb + warp * 32 + d1_ * YP + (d1_ == q ? own : oth) + 4 * YS + (lane & 8) * 2;
            PIN(a4); PIN(a1);
            uint32_t tag = __byte_perm(epoch | 0x8000u, 0, 0x1010);
            PIN(tag);
            mbar_wait(mb + MB_T * 8);
            int n = 0;
            while (__byte_perm(sa.x, sc.x, 0x7632) != tag && ++n < SPIN_LIMIT) poll();
            STAMP(4);
#pragma unroll
            for (int i = 0; i < 5; i++) {
                va[i] = norm2(va[i], sa.x, sa.y); va[i] = pack_f16(bf_lo(va[i]), bf_hi(va[i]));
                vc[i] = norm2(vc[i], sc.x, sc.y); vc[i] = pack_f16(bf_lo(vc[i]), bf_hi(vc[i]));
            }
            stsm4t(a4, va[0], va[1], va[2], va[3]); stsm4t(a4 + 16, vc[0], vc[1], vc[2], vc[3]); stsm2t(a1, va[4], vc[4]);
            bar_arrive(13, 608);
            {
            const uint32_t xh = sb + SM_XTL + (c & 1) * 16 + (9 * g + 144 * (warp & 1) + (warp >> 1)) * (2 * XW);
            const uint4 c4 = lds128(xh + cq * 16), d4_ = lds128(xh + cq * 16 + 144 * XW);
            xa[0] = c4.x; xa[1] = c4.y; xa[2] = c4.z; xa[3] = c4.w; xa[4] = lds32(xh + 64 + cq * 4);
            xb[0] = d4_.x; xb[1] = d4_.y; xb[2] = d4_.z; xb[3] = d4_.w; xb[4] = lds32(xh + (64 + 144 * XW) + cq * 4);
            }
        }
        STAMP(5);
        __syncwarp();
        if (PRE4 >= 0) { ldsm4t(c0, la); ldsm4t(c2, la + 1024); }
        if (PRE4 > 0) { ldsm4t(c1, la + 256); ldsm4t(c3, la + 1280); }
        bar_sync(15, 672);
        Af[0][0] |= lds32(sb + SM_P);
        };
        cmul(sr, si, sr, si, z1r, z1i);
        {
            const H2C h4 = splat(z4r, z4i);
            expand8(kl, kl + 512, sr, si, z1r, z1i, z2r, z2i, h4);
            cmul(sr, si, sr, si, hr, hi_);
            expand8(kl + 1024, kl + 1536, sr, si, z1r, z1i, z2r, z2i, h4);
        }
        __syncwarp();
        ldsm4t(b0, la); ldsm4t(b1, la + 256); ldsm4t(b2, la + 1024); ldsm4t(b3, la + 1280);
        cmul(z1r, z1i, z1r, z1i, hr, hi_);
        cmul(sr, si, sr, si, z1r, z1i);
        if (!T_L18 || warp < 18) ln1();
        expand8(kl, kl + 512, sr, si, z2r, z2i, z4r, z4i, splat(hr, hi_));
        csq(z1r, z1i, z1r, z1i);
        cmul(sr, si, sr, si, z1r, z1i);
        csq(z2r, z2i, hr, hi_);
        expand8(kl + 1024, kl + 1536, sr, si, z4r, z4i, hr, hi_, splat(z2r, z2i));
        csq(z1r, z1i, z1r, z1i);
        cmul(sr, si, sr, si, z1r, z1i);
        csq(z4r, z4i, z2r, z2i);
        expand8(kl + 2048, kl + 2560, sr, si, hr, hi_, z2r, z2i, splat(z4r, z4i));
        norm();
        if (PRE4 < 0) { ldsm4t(c0, la); ldsm4t(c2, la + 1024); }
        if (PRE4 <= 0) { ldsm4t(c1, la + 256); ldsm4t(c3, la + 1280); }
        mm2(0, b0, b1, b2, b3);
        mm2(2, c0, c1, c2, c3);
        ldsm4t(b0, la + 2048); ldsm4t(b1, la + 2304);
#pragma unroll
        for (int t = 0; t < 4; t++) sts64(kb + lane * 8 + 1024 + t * 256, kp[t][0], kp[t][1]);
        {
            float a0[4] = {0.f, 0.f, 0.f, 0.f}, a1[4] = {0.f, 0.f, 0.f, 0.f};
            mma_f16(a0, Af[0], b0[0], b0[1]); mma_f16(a1, Af[1], b0[2], b0[3]); mma_f16(a0, Af[2], b1[0], b1[1]); mma_f16(a1, Af[3], b1[2], b1[3]);
            sts64(kb + lane * 8 + 2048, pack_f16(a0[1] + a1[1], a0[0] + a1[0]), pack_f16(a0[3] + a1[3], a0[2] + a1[2]));
        }
        bar_sync(1 + k, 128);
        const uint4 m01 = lds128(sb + SM_KG + k * 32), m23 = lds128(sb + SM_KG + k * 32 + 16);
        const unsigned Em = max(max(m01.x, m01.z), max(m23.x, m23.z));
        const float f0 = __uint_as_float(max((int)(127 + m01.x - Em), 0) << 23), f1 = __uint_as_float(max((int)(127 + m01.z - Em), 0) << 23),
                    f2 = __uint_as_float(max((int)(127 + m23.x - Em), 0) << 23), f3 = __uint_as_float(max((int)(127 + m23.z - Em), 0) << 23);
        const uint32_t r0 = pack_f16(f0, f0), r1 = pack_f16(f1, f1), r2 = pack_f16(f2, f2), r3 = pack_f16(f3, f3);
        const int tq = (wq + k) & 3;
        const uint32_t ra = fb + lane * 8 + tq * 256 + 1024;
        const uint2 p0 = lds64(ra), p1 = lds64(ra + 3072), p2 = lds64(ra + 6144), p3 = lds64(ra + 9216);
        uint32_t w0 = hadd2(hfma2(p0.x, r0, hmul2(p1.x, r1)), hfma2(p2.x, r2, hmul2(p3.x, r3)));
        uint32_t w1 = hadd2(hfma2(p0.y, r0, hmul2(p1.y, r1)), hfma2(p2.y, r2, hmul2(p3.y, r3)));
        const bool last = lane == 31;
        uint32_t w4 = 0;
        if (tq < 2) {
            const uint32_t rc = fb + lane * 8 + tq * 4 + 2048;
            w4 = hmul2(hadd2(hfma2(lds32(rc), r0, hmul2(lds32(rc + 3072), r1)), hfma2(lds32(rc + 6144), r2, hmul2(lds32(rc + 9216), r3))), 0x18001800u);
        }
        if (T_EB) asm volatile("bar.sync %0, 128;" :: "r"(1 + k + ((w0 & w1 & w4) & zero)) : "memory");
        if (tq < 2) {
            const uint32_t ph = pf + (P_H7 + 16 * tq) + (g & 1) * (2 * P_HS) + cq * 64 + (g >> 1) * 4;
            put16(ph, w4 >> 16); put16(ph + 32, w4);
            const uint32_t pa = pn + (4 + 512 * tq) + lane * 8;
            sts16(pa, w0 >> 16); sts32(pa + 4, w0); sts16(pa + 10, w0);
            sts16(pa + 256, w1 >> 16); sts32(pa + 260, w1); sts16(pa + 266, w1);
            if (last) {
                sts32(sb + SM_SC + k * 4, Em * 0x00800080u);
                put16(tq ? pa + 264 : pn,
                      tq ? w1 : pack_f16(((float)(int)m01.y * f0 + (float)(int)m01.w * f1 + (float)(int)m23.y * f2 + (float)(int)m23.w * f3) * (1.f / 16777216.f)
                                         + (N_D ? ldsf(sb + SM_DW + 96 + k * 4) : __uint_as_float(pD << 16)) * __uint_as_float((254u - Em) << 23), 0.f));
            }
        } else if (tq == 2) {
            const uint32_t pa = pn + 258 * 4 + (cq & 1) * 16 + (cq >> 1) * 512 + g * 32;
            if (last) { put16(pf, hmul2(w1, 0x18001800u)); w1 = hadd2(w1, hneg2(__byte_perm(w1, 0, 0x1010))); }
            const uint32_t b0 = __byte_perm(w0, 0, 0x1010), b1 = __byte_perm(w1, 0, 0x1010);
            sts16(pa, w0 >> 16); sts32(pa + 4, w0); sts64(pa + 8, b0, b0); sts16(pa + 18, w0);
            sts16(pa + 256, w1 >> 16); sts32(pa + 260, w1); sts64(pa + 264, b1, b1); sts16(pa + 274, w1);
        } else {
            const uint32_t pa = pf + ((g & 1) ? 3 * P_GS : P_GS) + cq * 32 + (g >> 1) * 4;
            const uint32_t pb = pa + ((g & 1) ? 4 - 3 * P_GS : P_GS);
            w0 = hmul2(w0, 0x18001800u); w1 = hmul2(w1, 0x18001800u);
            put16(pa, w0 >> 16); put16(pb, w0); put16(pa + 16, w1 >> 16); put16(pb + 16, w1);
            if (last) put16(pf + P_H7 + P_HS, w1);
        }
        if (T_EB) __syncwarp(); else bar_sync(1 + k, 128);
    }
    STAMP(6);

    asm volatile("barrier.cluster.wait.aligned;" ::: "memory");
    mbar_wait(mb + (MB_X + (k < nslot ? k : 0)) * 8);
    STAMP(7);
    if (k < nslot) {
        const int role = (wq + k) & 3;
        const uint32_t ub = sb + SM_U + k * US + 128;
        if (role) {
            const int r = (3 - role) * 32 + lane;
            const uint32_t a1 = ub + (r & 3) * (2 * UP) + (r >> 2) * 16, a0 = a1 + ((r & 3) ? -2 * UP : 6 * UP - 16);
            const uint4 q0 = lds128(a0), q1 = lds128(a0 + UP), q2 = lds128(a1), q3 = lds128(a1 + UP);
            const uint32_t U[16] = {q0.x, q0.y, q0.z, q0.w, q1.x, q1.y, q1.z, q1.w, q2.x, q2.y, q2.z, q2.w, q3.x, q3.y, q3.z, q3.w};
            uint32_t V[14], Q[14], R4[12], T[8];
#pragma unroll
            for (int i = 2; i < 14; i++) { V[i] = __byte_perm(U[i], U[i + 1], 0x5432); Q[i] = hadd2(U[i], V[i]); }
#pragma unroll
            for (int i = 2; i < 12; i++) R4[i] = hadd2(Q[i], Q[i + 1]);
            const uint32_t rb = fb + r * 16;
#pragma unroll
            for (int i = 0; i < 8; i++) T[i] = hadd2(V[5 + i], Q[6 + i]);
            sts128(rb + F_E3, T[0], T[1], T[2], T[3]); sts128(rb + F_O3 + 16, T[4], T[5], T[6], T[7]);
#pragma unroll
            for (int i = 0; i < 8; i++) T[i] = hadd2(R4[3 + i], U[5 + i]);
            sts128(rb + F_O5, T[0], T[1], T[2], T[3]); sts128(rb + F_E5, T[4], T[5], T[6], T[7]);
            if (role != 1) {
#pragma unroll
                for (int i = 0; i < 8; i++) T[i] = hadd2(T[i], hadd2(V[2 + i], V[5 + i]));
                sts128(rb + F_E7, T[0], T[1], T[2], T[3]); sts128(rb + F_O7, T[4], T[5], T[6], T[7]);
#pragma unroll
                for (int i = 0; i < 8; i++) T[i] = hadd2(R4[2 + i], hadd2(R4[4 + i], U[6 + i]));
                sts128(rb + F_O9, T[0], T[1], T[2], T[3]); sts128(rb + F_E9 + 16, T[4], T[5], T[6], T[7]);
                sts128(rb + F_E2, Q[6], Q[7], Q[8], Q[9]); sts128(rb + F_O2, Q[10], Q[11], Q[12], Q[13]);
            }
        } else if (lane < 8) {
            uint32_t v[5];
#pragma unroll
            for (int i = 0; i < 5; i++) { const int t = 6 + lane + i; v[i] = lds16(ub + 23 * 16 + (t < 16 ? (6 + (t >> 3)) * UP : 16) + (t & 7) * 2); }
            const uint32_t s = hadd2(hadd2(hadd2(v[0], v[1]), hadd2(v[2], v[3])), v[4]);
            sts16(fb + F_O5 + 96 * 16 + lane * 2, s);
            sts32(fb + (lane < 4 ? F_O3 : F_E9 - 16) + lane * 4, 0);
        }
        bar_sync(1 + k, 128);
        float acc[4][4];
        uint32_t Q[4][4];
        {
            const int h = role & 1, part = role >> 1;
            const uint32_t po = pf + (g - 2 * cq) * 4;
            float fa[7][4];
#pragma unroll
            for (int a = 0; a < 7; a++) fa[a][0] = fa[a][1] = fa[a][2] = fa[a][3] = 0.f;
            uint32_t B[3][4];
            Q[0][2] = tid & zero;
#pragma unroll 1
            for (int s = 2 * part + 1; s >= 2 * part; s--) {
#pragma unroll
                for (int i = 0; i < 3; i++) { Q[i][0] = lds32(po + s * P_GS + i * 64); Q[i][1] = lds32(po + s * P_GS + (i * 64 + 32)); }
                const uint32_t ba = fb + lane * 16 + ((s & 1) * F_E3 + (part == h ? 0 : F_O5 + h * 16));
#pragma unroll
                for (int i = 0; i < 3; i++) ldsm4t(B[i], ba + i * 512);
#pragma unroll
                for (int i = 0; i < 3; i++) { Q[i][3] = CP(Q[i][0]); if (i) Q[i][2] = CP(Q[i - 1][1]); }
#pragma unroll
                for (int dl = 0; dl < 3; dl++)
#pragma unroll
                    for (int ap = 0; ap < 6 - dl; ap++) mma_f16(fa[ap + 1 + dl], Q[dl], B[ap >> 1][2 * (ap & 1)], B[ap >> 1][2 * (ap & 1) + 1]);
            }
#pragma unroll 1
            for (int s = role; s == 1; s++) {
                ldsm2t(B[0][0], B[0][1], fb + ((lane & 15) == 15 ? F_O5 : F_O3));
#pragma unroll
                for (int dl = 0; dl < 3; dl++) mma_f16(fa[dl], Q[dl], B[0][0], B[0][1]);
            }
#pragma unroll 1
            for (int s = part; s <= 2 * part; s++) {
#pragma unroll
                for (int i = 0; i < 4; i++) { Q[i][0] = lds32(po + s * P_HS + (P_H7 + i * 64)); Q[i][1] = lds32(po + s * P_HS + (P_H7 + i * 64 + 32)); }
                const uint32_t ba = fb + lane * 16 + (F_E7 + s * 1024 + h * F_H);
                ldsm4t(B[0], ba); ldsm4t(B[1], ba + 512);
#pragma unroll
                for (int i = 0; i < 4; i++) { Q[i][3] = CP(Q[i][0]); if (i) Q[i][2] = CP(Q[i - 1][1]); }
#pragma unroll
                for (int dl = 0; dl < 4; dl++) {
#pragma unroll
                    for (int ap = 0; ap < 4 - dl; ap++) mma_f16(fa[ap + 3 + dl], Q[dl], B[ap >> 1][2 * (ap & 1)], B[ap >> 1][2 * (ap & 1) + 1]);
                    if (s == 1) break;
                }
            }
            const uint32_t da = fb + role * 2048 + (lane & 3) * 512 + (((lane >> 2) ^ ((lane & 3) * 2)) << 4);
            bar_sync(1 + k, 128);
            stsm4(da, 0u, 0u, pack_f16(fa[0][0], fa[0][1]), pack_f16(fa[0][2], fa[0][3]));
#pragma unroll
            for (int i = 1; i < 4; i++)
                stsm4(da + i * 128, pack_f16(fa[2 * i - 1][0], fa[2 * i - 1][1]), pack_f16(fa[2 * i - 1][2], fa[2 * i - 1][3]),
                      pack_f16(fa[2 * i][0], fa[2 * i][1]), pack_f16(fa[2 * i][2], fa[2 * i][3]));
            Q[0][0] = (g == 2 * cq) ? 0x6000u : ((g == 2 * cq + 1) ? 0x60000000u : 0u);
            Q[0][1] = Q[0][0] & zero; Q[0][2] = lane & zero; Q[0][3] = CP(Q[0][0]);
            const uint32_t ra = fb + (lane >> 3) * 2048 + wq * 512 + (((lane & 7) ^ (wq * 2)) << 4);
            bar_sync(1 + k, 128);
#pragma unroll
            for (int i = 0; i < 4; i++) {
                ldsm4(B[0], ra + i * 128);
                mma_f16_z(acc[i], Q[0], hadd2(B[0][0], B[0][2]), hadd2(B[0][1], B[0][3]));
            }
        }
        bar_arrive(6 + k, 160);
        STAMP(8);
        const uint32_t inv = lds32(sb + SM_SC + k * 4);
        uint32_t yd = mapa(sb, 2 * wq) + (SM_XT + 128 + q * YP + k * YS + (k >> 2) * (q >> 1) * 16) + lane * 16;
        PIN(yd);
        {
            uint32_t pp = pn + (16 * (wq - 3) + g - 2 * cq) * 4;
            uint32_t dlo = (((ub + 6 * UP) & 0x3FFFF) >> 4) | ((UP >> 4) << 16);
            uint32_t R[4][4];
            auto loadQ = [&](uint32_t (&X)[4][4], uint32_t prev) {
#pragma unroll
                for (int i = 0; i < 4; i++) { X[i][0] = lds32(pp + i * 64); X[i][1] = lds32(pp + i * 64 + 32); }
                X[0][2] = CP(prev);
#pragma unroll
                for (int i = 0; i < 4; i++) { X[i][3] = CP(X[i][0]); if (i) X[i][2] = CP(X[i - 1][1]); }
                pp += 256;
            };
            auto issue = [&](uint32_t (&X)[4][4]) {
                asm volatile("wgmma.fence.sync.aligned;" ::: "memory");
#pragma unroll
                for (int i = 0; i < 4; i++) wgmma32(acc, X[i], dlo - i * (2 * UP >> 4));
                asm volatile("wgmma.commit_group.sync.aligned;" ::: "memory");
                dlo -= 1;
            };
            loadQ(Q, 0);
#pragma unroll 1
            for (int dl = 0; dl < 4; dl++) {
                issue(Q);
                asm volatile("wgmma.wait_group.sync.aligned 1;" ::: "memory");
                loadQ(R, Q[3][1]);
                issue(R);
                asm volatile("wgmma.wait_group.sync.aligned 1;" ::: "memory");
                loadQ(Q, R[3][1]);
            }
            issue(Q);
            asm volatile("wgmma.wait_group.sync.aligned 0;" ::: "memory");
        }
        const uint32_t pstep = mapa(sb, 1) - mapa(sb, 0), ym = mapa(mb + MB_Y * 8, 2 * wq);
#pragma unroll
        for (int e = 0; e < 2; e++)
            st_async4(yd + e * pstep, bmul2(pack_bf16(acc[0][2 * e], acc[0][2 * e + 1]), inv), bmul2(pack_bf16(acc[1][2 * e], acc[1][2 * e + 1]), inv),
                      bmul2(pack_bf16(acc[2][2 * e], acc[2][2 * e + 1]), inv), bmul2(pack_bf16(acc[3][2 * e], acc[3][2 * e + 1]), inv), ym + e * pstep);
        if (lane == 0) asm volatile("mbarrier.arrive.shared::cta.b64 _, [%0];" :: "r"(mb + MB_Y * 8) : "memory");
    }
    STAMP(9);
    uint32_t ha[5], hb[5];
    if (warp < 16) {
        const uint4 wk = lds128(sb + SM_DW + cq * 16);
        uint32_t sel[5] = {wk.x, wk.y, wk.z, wk.w, lds32(sb + SM_DW + 64 + cq * 4)}, sel2[5];
#pragma unroll
        for (int i = 0; i < 5; i++) {
            if (!(g & 1)) sel[i] = 0x3F803F80u;
            sel2[i] = sel[i]; PIN(sel2[i]);
        }
        const uint32_t y4 = sb + SM_XT + 128 + warp * 32 + (2 * (lane >> 3) + (lane & 1)) * YP + ((lane & 7) >> 1) * YS;
        const uint32_t y1 = sb + SM_XT + 128 + warp * 32 + (lane & 7) * YP + 4 * YS + (lane & 8) * 2 + (lane & 6) * 8;
        uint32_t ao = (256 * q + tn) * 16, hta = sb + SM_HT + tn * 80;
        PIN(ao); PIN(hta);
        mbar_wait(mb + MB_Y * 8);
        STAMP(10);
        float ca[4] = {0.f, 0.f, 0.f, 0.f}, cb[4] = {0.f, 0.f, 0.f, 0.f};
        {
            uint32_t ya[4], yb[4], yc, yd;
            ldsm4t(ya, y4); ldsm4t(yb, y4 + 16); ldsm2t(yc, yd, y1);
#pragma unroll
            for (int i = 0; i < 4; i++) { ha[i] = badd2(xa[i], ya[i]); hb[i] = badd2(xb[i], yb[i]); }
            ha[4] = badd2(xa[4], yc); hb[4] = badd2(xb[4], yd);
        }
        if (nslot != 5) {
            ha[4] = hb[4] = 0;
            if (cq >= 2) ha[0] = ha[1] = ha[2] = ha[3] = hb[0] = hb[1] = hb[2] = hb[3] = 0;
        }
#pragma unroll
        for (int i = 0; i < 5; i++) { mma_bf16_k8(ca, ha[i], sel[i], ha[i]); mma_bf16_k8(cb, hb[i], sel2[i], hb[i]); }
        if (!(g & 1)) { ca[1] = ca[0]; cb[1] = cb[0]; }
        if (cq == (g >> 1)) {
            asm volatile("red.relaxed.gpu.global.add.v4.f32 [%0], {%1,%2,%3,%4};" :: "l"((char*)g_s.acc + ao), "f"(1.0f), "f"(ca[1]), "f"(ca[2]), "f"(ca[3]) : "memory");
            asm volatile("red.relaxed.gpu.global.add.v4.f32 [%0], {%1,%2,%3,%4};" :: "l"((char*)g_s.acc + ao + 128), "f"(1.0f), "f"(cb[1]), "f"(cb[2]), "f"(cb[3]) : "memory");
        }
        sts128(hta + cq * 16, ha[0], ha[1], ha[2], ha[3]); sts32(hta + 64 + cq * 4, ha[4]);
        sts128(hta + cq * 16 + 640, hb[0], hb[1], hb[2], hb[3]); sts32(hta + 704 + cq * 4, hb[4]);
        STAMP(11);
    }
    const int kq = warp / 5, mt = warp - 5 * kq;
    const int mi = lane >> 3, mr = lane & 7;
    const unsigned tk = (unsigned)tid / 72u, ck = tid - tk * 72;
    uint32_t A[9][4];
    auto loadA = [&]() {
        mbar_wait(mb + MB_W1 * 8);
        const uint32_t aa = sb + (mi & 1) * SM_WU + (8 * (mi >> 1) + mr) * 80 + (144 * 80 * kq + mt * 16);
#pragma unroll
        for (int s = 0; s < 9; s++) ldsm4t(A[s], aa + s * 1280);
    };
    const uint32_t par = N_P ? ((lds32(sb + SM_SC + 28) & 1) ? 0u : 0x40004000u) : ((epoch & 1) ? 0x40004000u : 0u);
    uint32_t pk0 = mapa(sb, 2 * cq), go = (ck / 5u + ck) * 16, co = ((q * 8 * NCL + c) * 6 + cq) * 16;
    PIN(pk0); PIN(go); PIN(co);
    if (warp < 8) {
        const float wsum = ldsf(sb + SM_SC + 24);
        const uint32_t idx = 2047 - (512 * ((tid >> 1) & 3) + 128 * ((tid >> 3) & 3) + 64 * (tid & 1) + 8 * q + warp);
        uint4 s; int n = 0;
        do { s = ld_rlx128(&g_s.acc[256 * q + tid]); } while (__uint_as_float(s.x) != (float)NCL && ++n < SPIN_LIMIT);
        STAMP(16);
        const uint32_t ox = __shfl_xor_sync(~0u, (lane & 1) ? s.z : s.w, 1);
        const uint32_t ms = ln_stats(__uint_as_float((lane & 1) ? ox : s.z), __uint_as_float(s.y));
        const float rs = rcpf(bf_hi(ms));
        const uint32_t rb = pack_bf16(0.f, fmaf(-bf_lo(ms), wsum, __uint_as_float((lane & 1) ? s.w : ox)) * rs);
        const uint32_t key = (((rb ^ (((int)rb >> 31) | 0x80000000u)) >> 16) << 11) | idx;
        sts32(sb + SM_KEY + tid * 4, key);
        __syncwarp();
        const uint32_t rank = rank4<8, 16>(sb + SM_KEY + warp * 128, key);
        if (rank < 8) sts32(sb + SM_CAND + warp * 32 + rank * 4, key);
        sts64(sb + SM_ST + tid * 8, ms, rsplit(rs));
    } else { if (T_W4) mbar_wait(mb + MB_Y * 8); loadA(); }
    if (warp < 16) {
        STAMP(17);
        bar_sync(12, 512);
        STAMP(18);
        if (warp < 8) {
            const uint32_t mk = lds32(sb + SM_CAND + (tid >> 2) * 4);
            uint32_t rank = rank4<4, 64>(sb + SM_CAND + cq * 16, mk);
            rank += __shfl_xor_sync(~0u, rank, 1); rank += __shfl_xor_sync(~0u, rank, 2);
            if (rank < 8) {
                const uint32_t pk1 = pk0 + (mapa(sb, 1) - mapa(sb, 0));
                st_async1(pk0 + (SM_RK + q * 32) + rank * 4, mk, pk0 + (SM_MB + MB_KEY * 8));
                st_async1(pk1 + (SM_RK + q * 32) + rank * 4, mk, pk1 + (SM_MB + MB_KEY * 8));
                const uint32_t t = tslot(~mk);
                const uint2 sv = lds64(sb + SM_ST + t * 8);
                const uint4 hv = lds128(sb + SM_HT + t * 80 + cq * 16);
                const uint32_t h4 = lds32(sb + SM_HT + t * 80 + 64 + cq * 4);
                const uint32_t rr = bmul2(sv.y, 0x3C803C80u);
                char* const dp = (char*)g_s.cand + (co + rank * 1440);
                st_rlx128(dp, (norm2(hv.x, sv.x, rr) & 0xBFFFBFFFu) | par, (norm2(hv.y, sv.x, rr) & 0xBFFFBFFFu) | par,
                          (norm2(hv.z, sv.x, rr) & 0xBFFFBFFFu) | par, (norm2(hv.w, sv.x, rr) & 0xBFFFBFFFu) | par);
                asm volatile("st.relaxed.gpu.global.u32 [%0], %1;" :: "l"((char*)g_s.cand + (co + rank * 1440 + 64 - cq * 12)), "r"((norm2(h4, sv.x, rr) & 0xBFFFBFFFu) | par) : "memory");
            }
            __syncwarp();
        }
        {
            const uint2 sa = lds64(sb + SM_ST + tn * 8), sbb = lds64(sb + SM_ST + tn * 8 + 64);
#pragma unroll
            for (int i = 0; i < 5; i++) { ha[i] = badd2(ha[i], norm2(ha[i], sa.x, sa.y)); hb[i] = badd2(hb[i], norm2(hb[i], sbb.x, sbb.y)); }
            const bool hf = (c & 1) && cq == 0;
            const uint32_t o16 = sb + SM_XT + (hf ? 16384 + tn * 16 : tn * 64 + (cq - (c & 1)) * 16), o4 = sb + SM_XT + ((c & 1) ? tn * 64 + 48 : 16384 + tn * 16) + cq * 4;
            sts128(o16, ha[0], ha[1], ha[2], ha[3]); sts32(o4, ha[4]);
            sts128(o16 + (hf ? 128 : 512), hb[0], hb[1], hb[2], hb[3]); sts32(o4 + ((c & 1) ? 512 : 128), hb[4]);
        }
        if (warp >= 8) {
            STAMP(19);
            mbar_wait(mb + MB_KEY * 8);
            STAMP(20);
            const uint32_t mk = lds32(sb + SM_RK - 256 + (tid >> 2) * 4);
            uint32_t rank = rank4<4, 64>(sb + SM_RK + cq * 16, mk);
            rank += __shfl_xor_sync(~0u, rank, 1); rank += __shfl_xor_sync(~0u, rank, 2);
            if (rank < 8) sts64(sb + SM_SEL + rank * 8, mk, ((tid >> 2) - 64) * 1440);
        }
    }
    bar_sync(11, 640);
    STAMP(12);

    const char* gp = (const char*)g_s.cand + (go + lds32(sb + SM_SEL + 4 + (tk & 7) * 8));
    uint4 hv = ld_rlx128(gp);
    if (warp < 8) loadA();
    const bool red = warp < 6;
    const uint32_t ft = red ? (unsigned)tid / 24u : (unsigned)(tid >> 4) & 7u, fj = red ? 24 * q + tid - ft * 24 : d0 / 3 + (lane & 15);
    const uint32_t key = lds32(sb + SM_SEL + ft * 8), k16 = key << 5;
    float sig = bfr(rcpf(1.f + ex2f(__uint_as_float((k16 ^ (~((int)k16 >> 31) | 0x80000000u)) & 0xFFFF0000u) * -1.4426950408889634f)));
    uint32_t ra2 = sb + SM_RED2 + tid * 12 + ft * 16, fo = (ft * 192 + fj) * 16, oo = ((~key & 2047) * D_ + 3 * fj) * 2;
    uint32_t bx = sb + SM_XS + mr * 1168 + mi * 16 + 288 * kq, gd = mapa(sb, kq * (8 / NRED)) + (SM_GU + (q * nslot + mt) * 128) + lane * 4;
    PIN(ra2); PIN(fo); PIN(oo); PIN(bx); PIN(gd);
    asm volatile("" : "+f"(sig));
    {
        if (warp < 18) {
            int n = 0;
            while ((((hv.x ^ par) | (hv.y ^ par) | (hv.z ^ par) | (hv.w ^ par)) & 0x40004000u) && ++n < SPIN_LIMIT) hv = ld_rlx128(gp);
            sts128(sb + SM_XS + tk * 16 + tid * 16, hv.x ^ par, hv.y ^ par, hv.z ^ par, hv.w ^ par);
        }
    }
    bar_sync(14, 672);
    STAMP(13);
    {
        float c0[4] = {0.f, 0.f, 0.f, 0.f}, c1[4] = {0.f, 0.f, 0.f, 0.f}, c2[4] = {0.f, 0.f, 0.f, 0.f};
        uint32_t b[5][4];
#pragma unroll
        for (int s = 0; s < 4; s++) ldsm4(b[s], bx + s * 64);
        asm volatile("ldmatrix.sync.aligned.m8n8.x2.shared.b16 {%0,%1}, [%2];" : "=r"(b[4][0]), "=r"(b[4][1]) : "r"(bx + 256) : "memory");
        mma_bf16(c0, A[0][0], A[0][1], A[0][2], A[0][3], b[0][0], b[0][1]);
        mma_bf16(c1, A[1][0], A[1][1], A[1][2], A[1][3], b[0][2], b[0][3]);
        mma_bf16(c2, A[2][0], A[2][1], A[2][2], A[2][3], b[1][0], b[1][1]);
        mma_bf16(c0, A[3][0], A[3][1], A[3][2], A[3][3], b[1][2], b[1][3]);
        mma_bf16(c1, A[4][0], A[4][1], A[4][2], A[4][3], b[2][0], b[2][1]);
        mma_bf16(c2, A[5][0], A[5][1], A[5][2], A[5][3], b[2][2], b[2][3]);
        mma_bf16(c0, A[6][0], A[6][1], A[6][2], A[6][3], b[3][0], b[3][1]);
        mma_bf16(c1, A[7][0], A[7][1], A[7][2], A[7][3], b[3][2], b[3][3]);
        mma_bf16(c2, A[8][0], A[8][1], A[8][2], A[8][3], b[4][0], b[4][1]);
        sts128f(sb + SM_RED + tid * 16, c0[0] + c1[0] + c2[0], c0[1] + c1[1] + c2[1], c0[2] + c1[2] + c2[2], c0[3] + c1[3] + c2[3]);
    }
    bar_sync(1 + mt, 128);
    STAMP(21);
    if (mt < nslot && kq < NRED) {
        const uint32_t ra = sb + SM_RED + mt * 512 + lane * 16;
        const float4 p0 = lds128f(ra), p1 = lds128f(ra + 2560), p2 = lds128f(ra + 5120), p3 = lds128f(ra + 7680);
        const float g0 = bfr(((p0.x + p1.x) + (p2.x + p3.x)) * 64.f), g1 = bfr(((p0.y + p1.y) + (p2.y + p3.y)) * 64.f);
        const uint32_t sg = pack_bf16(g0 * rcpf(1.f + ex2f(g0 * -1.4426950408889634f)), g1 * rcpf(1.f + ex2f(g1 * -1.4426950408889634f)));
        const uint32_t gu = bmul2(sg, pack_bf16(((p0.z + p1.z) + (p2.z + p3.z)) * 64.f, ((p0.w + p1.w) + (p2.w + p3.w)) * 64.f));
        const uint32_t pstep = mapa(sb, 1) - mapa(sb, 0), gm = mapa(mb + MB_GU * 8, kq * (8 / NRED));
#pragma unroll
        for (int i = 0; i < 8 / NRED; i++) st_async1(gd + i * pstep, gu, gm + i * pstep);
    }
    mbar_wait(mb + MB_W2 * 8);
    {
        const uint32_t aa = sb + (8 * (mi >> 1) + mr) * 144 + (mi & 1) * 16 + (SM_FAR + 2304 * kq + mt * 32);
#pragma unroll
        for (int s = 0; s < 5; s++) ldsm4t(A[s], aa + s * FAR_SZ);
    }
    {
        uint32_t ba = sb + (SM_GU + 256 * kq) + (lane & 15) * 16 + (lane >> 4) * 1024, wa = sb + (SM_RED2 + kq * 2432 + mt * 64) + g * 4 + cq * 608;
        PIN(ba); PIN(wa);
        STAMP(22);
        mbar_wait(mb + MB_GU * 8);
        STAMP(23);
        float c0[4] = {0.f, 0.f, 0.f, 0.f}, c1[4] = {0.f, 0.f, 0.f, 0.f}, c2[4] = {0.f, 0.f, 0.f, 0.f};
        uint32_t b[2][4], b8, b9;
        ldsm4t(b[0], ba); ldsm4t(b[1], ba + 2048); ldsm2t(b8, b9, ba + 4096);
        mma_bf16(c0, A[0][0], A[0][1], A[0][2], A[0][3], b[0][0], b[0][1]);
        mma_bf16(c1, A[1][0], A[1][1], A[1][2], A[1][3], b[0][2], b[0][3]);
        if (nslot == 5) {
            mma_bf16(c2, A[4][0], A[4][1], A[4][2], A[4][3], b8, b9);
            mma_bf16(c0, A[2][0], A[2][1], A[2][2], A[2][3], b[1][0], b[1][1]);
            mma_bf16(c1, A[3][0], A[3][1], A[3][2], A[3][3], b[1][2], b[1][3]);
        }
        stsf(wa, c0[0] + c1[0] + c2[0]); stsf(wa + 304, c0[1] + c1[1] + c2[1]);
        if (mt < 4) { stsf(wa + 32, c0[2] + c1[2] + c2[2]); stsf(wa + 336, c0[3] + c1[3] + c2[3]); }
    }
    if (warp < 10) {
        float v[3], cnt = 3.f;
        if (red) {
            bar_sync(6, 640);
            STAMP(14);
#pragma unroll
            for (int i = 0; i < 3; i++) v[i] = ((ldsf(ra2 + i * 4) + ldsf(ra2 + i * 4 + 2432)) + (ldsf(ra2 + i * 4 + 4864) + ldsf(ra2 + i * 4 + 7296))) * sig;
        } else {
            bar_arrive(6, 640);
            cnt = 0.f;
#pragma unroll
            for (int i = 0; i < 3; i++) {
                const uint32_t cl = 3 * fj + i - d0;
                const bool ok = cl < 8 * nslot && ((~key >> 3) & 7) == q;
                const uint32_t cf = cl - (c & 1) * 8;
                v[i] = ok ? __uint_as_float(lds16(sb + SM_XT + (cf < 32 ? tslot(~key) * 64 + cf * 2 : 16384 + tslot(~key) * 16 + (cl & 7) * 2)) << 16) : 0.f;
                if (ok) cnt += 1.f;
            }
            mbar_wait(mb + MB_OUT * 8);
        }
        if (cnt != 0.f) {
            float x, y, z, w;
            asm volatile("atom.relaxed.gpu.global.add.v4.f32 {%0,%1,%2,%3}, [%4], {%5,%6,%7,%8};" : "=f"(x), "=f"(y), "=f"(z), "=f"(w)
                         : "l"((char*)g_s.fin + fo), "f"(v[0]), "f"(v[1]), "f"(v[2]), "f"(cnt) : "memory");
            if (w + cnt == 3.f * (NCL + 1)) {
                __nv_bfloat16* op = (__nv_bfloat16*)((char*)prm.out + oo);
                op[0] = __float2bfloat16(x + v[0]); op[1] = __float2bfloat16(y + v[1]); op[2] = __float2bfloat16(z + v[2]);
            }
        }
    } else bar_arrive(6, 640);
    STAMP(15);
}

typedef __nv_bfloat16 bf16;
__device__ bf16 f_n[L_ * D_], f_h[L_ * D_];
__device__ float f_k[D_ * L_], f_r[L_], f_gu[8 * F_];
__device__ int f_idx[8];
__device__ __forceinline__ float b2f(bf16 v) { return __bfloat162float(v); }
__global__ void fb_ln(const bf16* in, const bf16* wr, bf16* out) {
    const int t = blockIdx.x * 8 + (threadIdx.x >> 5), lane = threadIdx.x & 31;
    const bf16* r = (in ? in : f_h) + t * D_;
    float s1 = 0.f, s2 = 0.f, s3 = 0.f;
    for (int i = lane; i < D_; i += 32) s1 += b2f(r[i]);
    for (int o = 16; o; o >>= 1) s1 += __shfl_xor_sync(~0u, s1, o);
    for (int i = lane; i < D_; i += 32) { const float d = b2f(r[i]) - s1 / D_; s2 += d * d; }
    for (int o = 16; o; o >>= 1) s2 += __shfl_xor_sync(~0u, s2, o);
    const float m = bfr(s1 / D_), sd = bfr(sqrtf(bfr(bfr(s2 / D_) + 1e-5f)));
    for (int i = lane; i < D_; i += 32) {
        const float v = bfr(bfr(b2f(r[i]) - m) / sd);
        f_n[t * D_ + i] = __float2bfloat16(v);
        if (!in) { s3 += v * b2f(wr[i]); out[t * D_ + i] = __float2bfloat16(b2f(r[i]) + v); }
    }
    for (int o = 16; o; o >>= 1) s3 += __shfl_xor_sync(~0u, s3, o);
    f_r[t] = bfr(s3);
}
__global__ void fb_taps(Params p) {
    const int d = blockIdx.x >> 3, l = (blockIdx.x & 7) * 256 + threadIdx.x;
    const float dt = bfr(expf(bf_lo(p.logdt[d]))), lf = bfr((float)l);
    float k = 0.f;
    for (int n = d * 128; n < d * 128 + 128; n++) {
        float wr, wi, sn, cs;
        cmul(wr, wi, bf_lo(p.prm6[4][n]), bf_lo(p.prm6[5][n]), dt * bf_lo(p.prm6[2][n]), dt * bf_lo(p.prm6[3][n]));
        sincosf(dt * bf_lo(p.prm6[1][n]) * lf, &sn, &cs);
        k += expf(dt * bf_lo(p.prm6[0][n]) * lf) * (wr * cs - wi * sn);
    }
    f_k[l * D_ + d] = k;
}
__global__ void fb_conv(Params p) {
    const int t = blockIdx.x, d = threadIdx.x;
    float y = 0.f;
    for (int l = 0; l <= t; l++) y += f_k[l * D_ + d] * b2f(f_n[(t - l) * D_ + d]);
    f_h[t * D_ + d] = __float2bfloat16(bf_lo(p.x[t * D_ + d]) + bfr(bfr(y) + bfr(b2f(f_n[t * D_ + d]) * bf_lo(p.dskip[d]))));
}
__global__ void fb_top() {
    const int t = blockIdx.x * 256 + threadIdx.x;
    int rank = 0;
    for (int j = 0; j < L_; j++) rank += f_r[j] > f_r[t] || (f_r[j] == f_r[t] && j < t);
    if (rank < 8) f_idx[rank] = t;
}
__global__ void fb_ffn1(const bf16* wg, const bf16* wu) {
    const int f = blockIdx.x * 256 + threadIdx.x, j = blockIdx.y;
    float g = 0.f, u = 0.f;
    for (int i = 0; i < D_; i++) { const float v = b2f(f_n[f_idx[j] * D_ + i]); g += v * b2f(wg[i * F_ + f]); u += v * b2f(wu[i * F_ + f]); }
    g = bfr(g);
    f_gu[j * F_ + f] = bfr(bfr(g / (1.f + expf(-g))) * bfr(u));
}
__global__ void fb_ffn2(const bf16* wd, bf16* out) {
    const int d = threadIdx.x, j = blockIdx.x, t = f_idx[j];
    float y = 0.f;
    for (int f = 0; f < F_; f++) y += f_gu[j * F_ + f] * b2f(wd[f * D_ + d]);
    out[t * D_ + d] = __float2bfloat16(b2f(f_h[t * D_ + d]) + bfr(b2f(f_n[t * D_ + d]) + bfr(bfr(y) * bfr(1.f / (1.f + expf(-f_r[t]))))));
}

typedef CUresult (*EncodeFn)(CUtensorMap*, CUtensorMapDataType, cuuint32_t, void*, const cuuint64_t*, const cuuint64_t*,
                             const cuuint32_t*, const cuuint32_t*, CUtensorMapInterleave, CUtensorMapSwizzle,
                             CUtensorMapL2promotion, CUtensorMapFloatOOBfill);

void make_map(EncodeFn fn, CUtensorMap* tm, const void* p, int cols, int rows, int bc, int br) {
    cuuint64_t dims[2] = {(cuuint64_t)cols, (cuuint64_t)rows};
    cuuint64_t strides[1] = {(cuuint64_t)cols * 2};
    cuuint32_t box[2] = {(cuuint32_t)bc, (cuuint32_t)br};
    cuuint32_t es[2] = {1, 1};
    fn(tm, CU_TENSOR_MAP_DATA_TYPE_BFLOAT16, 2, const_cast<void*>(p), dims, strides, box, es, CU_TENSOR_MAP_INTERLEAVE_NONE,
       CU_TENSOR_MAP_SWIZZLE_NONE, CU_TENSOR_MAP_L2_PROMOTION_L2_128B, CU_TENSOR_MAP_FLOAT_OOB_FILL_NONE);
}

void make_map3(EncodeFn fn, CUtensorMap* tm, const void* p) {
    cuuint64_t dims[5] = {(cuuint64_t)D_, 64, 2, 4, 4};
    cuuint64_t strides[4] = {(cuuint64_t)D_ * 2, (cuuint64_t)D_ * 128, (cuuint64_t)D_ * 1024, (cuuint64_t)D_ * 256};
    cuuint32_t box[5] = {XW, 9, 2, 4, 4};
    cuuint32_t es[5] = {1, 1, 1, 1, 1};
    fn(tm, CU_TENSOR_MAP_DATA_TYPE_BFLOAT16, 5, const_cast<void*>(p), dims, strides, box, es, CU_TENSOR_MAP_INTERLEAVE_NONE,
       CU_TENSOR_MAP_SWIZZLE_NONE, CU_TENSOR_MAP_L2_PROMOTION_NONE, CU_TENSOR_MAP_FLOAT_OOB_FILL_NONE);
}

void make_map5(EncodeFn fn, CUtensorMap* tm, const void* p, int bc) {
    cuuint64_t dims[5] = {(cuuint64_t)D_, 2, 4, 4, 64};
    cuuint64_t strides[4] = {(cuuint64_t)D_ * 128, (cuuint64_t)D_ * 1024, (cuuint64_t)D_ * 256, (cuuint64_t)D_ * 2};
    cuuint32_t box[5] = {(cuuint32_t)bc, 2, 4, 4, 8};
    cuuint32_t es[5] = {1, 1, 1, 1, 1};
    fn(tm, CU_TENSOR_MAP_DATA_TYPE_BFLOAT16, 5, const_cast<void*>(p), dims, strides, box, es, CU_TENSOR_MAP_INTERLEAVE_NONE,
       CU_TENSOR_MAP_SWIZZLE_NONE, CU_TENSOR_MAP_L2_PROMOTION_NONE, CU_TENSOR_MAP_FLOAT_OOB_FILL_NONE);
}

}

extern "C" void kernel_launch(void* const* d_in, const int* in_sizes, int n_in, void* d_out, int out_size) {
    (void)in_sizes; (void)n_in; (void)out_size;
    void* fp = nullptr;
    cudaDriverEntryPointQueryResult qr;
    cudaGetDriverEntryPoint("cuTensorMapEncodeTiled", &fp, cudaEnableDefault, &qr);
    EncodeFn fn = (EncodeFn)fp;
    CUtensorMap tmG, tmU, tmD, tmO, tmX, tmH;
    make_map3(fn, &tmX, d_in[0]);
    make_map(fn, &tmG, d_in[11], F_, D_, 40, 48);
    make_map(fn, &tmU, d_in[12], F_, D_, 40, 48);
    make_map(fn, &tmD, d_in[13], D_, F_, 72, 64);
    make_map5(fn, &tmO, d_out, 32);
    make_map5(fn, &tmH, d_out, 8);
    Params p;
    p.x = (const unsigned short*)d_in[0];
    for (int i = 0; i < 6; i++) p.prm6[i] = (const unsigned short*)d_in[1 + i];
    p.logdt = (const unsigned short*)d_in[7]; p.dskip = (const unsigned short*)d_in[8];
    p.wr = (const unsigned short*)d_in[10];
    p.out = (__nv_bfloat16*)d_out;
    p.zero = 0;
    cudaGetSymbolAddress((void**)&p.gs, g_s);
    cudaFuncSetAttribute(fused_kernel, cudaFuncAttributeMaxDynamicSharedMemorySize, SM_TOTAL);
    static int nclusters = -1;
    if (nclusters < 0) {
        cudaLaunchConfig_t cfg = {};
        cudaLaunchAttribute at;
        at.id = cudaLaunchAttributeClusterDimension; at.val.clusterDim.x = CS; at.val.clusterDim.y = 1; at.val.clusterDim.z = 1;
        cfg.gridDim = dim3(NCTA); cfg.blockDim = dim3(NTHR); cfg.dynamicSmemBytes = SM_TOTAL; cfg.attrs = &at; cfg.numAttrs = 1;
        if (cudaOccupancyMaxActiveClusters(&nclusters, fused_kernel, &cfg) != cudaSuccess) { (void)cudaGetLastError(); nclusters = NCL; }
    }
    if (nclusters >= NCL && !FORCE_FALLBACK) {
        fused_kernel<<<NCTA, NTHR, SM_TOTAL>>>(p, tmG, tmU, tmD, tmO, tmX, tmH);
        return;
    }
    fb_ln<<<L_ / 8, 256>>>((const bf16*)d_in[0], nullptr, nullptr);
    fb_taps<<<D_ * 8, 256>>>(p);
    fb_conv<<<L_, D_>>>(p);
    fb_ln<<<L_ / 8, 256>>>(nullptr, (const bf16*)d_in[10], p.out);
    fb_top<<<L_ / 256, 256>>>();
    fb_ffn1<<<dim3(F_ / 256, 8), 256>>>((const bf16*)d_in[11], (const bf16*)d_in[12]);
    fb_ffn2<<<8, D_>>>((const bf16*)d_in[13], p.out);
}
```

```cpp
#include <cuda_runtime.h>
#include <cuda_bf16.h>
#include <cuda_fp16.h>
#include <cuda.h>
#include <stdint.h>

namespace {

constexpr int L_ = 2048, D_ = 576, F_ = 4608;
constexpr int NCL = 15, CS = 8, NCTA = NCL * CS, NTHR = 768;
#define FORCE_FALLBACK 0
constexpr int XW = 48, NRED = 2;
constexpr int SPIN_LIMIT = 1 << 22;

constexpr int SM_WG   = 0;
constexpr int SM_WU   = 46080;
constexpr int YP = 3392, YS = 656;
constexpr int UP = 3280, US = 656;
constexpr int SM_XT   = 92160;
constexpr int SM_U    = SM_XT + 8 * YP;
constexpr int SM_FAR  = SM_U + 8 * UP;
constexpr int FAR_SZ  = 12416;
constexpr int F_E5 = 0, F_O5 = 1536, F_E3 = 3088, F_O3 = 4624, F_E7 = 6176, F_E2 = F_E7 + 1024, F_E9 = F_E7 + 2048,
              F_H = 3088, F_O7 = F_E7 + F_H, F_O2 = F_E2 + F_H, F_O9 = F_E9 + F_H;
constexpr int SM_P    = SM_FAR + 5 * FAR_SZ;
constexpr int PN_SZ = 584 * 4, SM_PN = SM_P + 64 * 4;
constexpr int P_GS = 48 * 4, P_H7 = 192 * 4, P_HS = 72 * 4;
constexpr int PF_SZ = (192 + 216) * 4, SM_PF = SM_PN + 5 * PN_SZ + 32;
constexpr int SM_MISC = SM_PF + 5 * PF_SZ;
constexpr int SM_ST   = SM_MISC;
constexpr int SM_RK   = SM_ST + 2048;
constexpr int SM_SEL  = SM_RK + 256;
constexpr int SM_KG   = SM_SEL + 64;
constexpr int SM_SC   = SM_KG + 160;
constexpr int SM_DW   = SM_SC + 32;
constexpr int SM_MB   = SM_DW + 160;
constexpr int SM_TOTAL = SM_MB + 128;
constexpr int SM_ROW  = SM_XT - 20736;
constexpr int SM_XTL  = SM_ROW - 576 * XW;
constexpr int SM_RED2 = SM_WG;
constexpr int SM_HT   = SM_P - 512;
constexpr int SM_KEY  = SM_FAR + 10240 + 128;
constexpr int SM_CAND = SM_KEY + 1024;
constexpr int SM_XS   = SM_U;
constexpr int SM_GU   = SM_XS + 9344;
constexpr int SM_RED  = SM_GU + 5632;
static_assert(F_O9 + 1024 <= FAR_SZ && FAR_SZ % 128 == 0, "far overflow");
static_assert(SM_RED + 10240 <= SM_FAR && SM_HT + 20496 <= SM_MISC, "alias overflow");
static_assert(SM_TOTAL <= 232448, "smem overflow");
static_assert(SM_FAR % 128 == 0 && SM_XT % 128 == 0 && SM_XTL % 128 == 0 && SM_P % 16 == 0 && SM_MISC % 16 == 0 && SM_MB % 8 == 0, "align");

enum { MB_X = 0, MB_W1 = 5, MB_W2 = 6, MB_KEY = 7, MB_GU = 8, MB_Y = 9, MB_OUT = 10, MB_T = 11, MB_R = 12 };

struct __align__(128) Scratch {
    unsigned epoch, zcnt, pad[30];
    uint4  st1[L_ * 2];
    float4 acc[L_];
    uint4  cand[64 * NCL * 6];
    float4 fin[8 * 192 + 24];
};
__device__ Scratch g_s;
#define STAMP(i)

__device__ __forceinline__ uint32_t mapa(uint32_t a, uint32_t r) { uint32_t d; asm("mapa.shared::cluster.u32 %0, %1, %2;" : "=r"(d) : "r"(a), "r"(r)); return d; }
__device__ __forceinline__ void mbar_wait(uint32_t mb) {
    asm volatile("{ .reg .pred p, q; .reg .u32 n; mov.u32 n, 0;\n"
                 "W_%=: mbarrier.try_wait.parity.shared::cta.b64 p, [%0], 0; add.u32 n, n, 1; setp.lt.and.u32 q, n, 65536, !p; @q bra W_%=; }" :: "r"(mb) : "memory");
}
__device__ __forceinline__ void arm(uint32_t mb, uint32_t bytes) { asm volatile("mbarrier.arrive.expect_tx.shared::cta.b64 _, [%0], %1;" :: "r"(mb), "r"(bytes) : "memory"); }
__device__ __forceinline__ void bar_sync(int id, int n) { asm volatile("bar.sync %0, %1;" :: "r"(id), "r"(n) : "memory"); }
__device__ __forceinline__ void bar_arrive(int id, int n) { asm volatile("bar.arrive %0, %1;" :: "r"(id), "r"(n) : "memory"); }
__device__ __forceinline__ uint32_t lds16(uint32_t a) { unsigned short v; asm volatile("ld.shared.u16 %0, [%1];" : "=h"(v) : "r"(a) : "memory"); return v; }
__device__ __forceinline__ uint32_t lds32(uint32_t a) { uint32_t v; asm volatile("ld.shared.u32 %0, [%1];" : "=r"(v) : "r"(a) : "memory"); return v; }
__device__ __forceinline__ uint2 lds64(uint32_t a) { uint2 v; asm volatile("ld.shared.v2.u32 {%0,%1}, [%2];" : "=r"(v.x), "=r"(v.y) : "r"(a) : "memory"); return v; }
__device__ __forceinline__ float ldsf(uint32_t a) { float v; asm volatile("ld.shared.f32 %0, [%1];" : "=f"(v) : "r"(a) : "memory"); return v; }
__device__ __forceinline__ uint4 lds128(uint32_t a) { uint4 v; asm volatile("ld.shared.v4.u32 {%0,%1,%2,%3}, [%4];" : "=r"(v.x), "=r"(v.y), "=r"(v.z), "=r"(v.w) : "r"(a) : "memory"); return v; }
__device__ __forceinline__ float4 lds128f(uint32_t a) { float4 v; asm volatile("ld.shared.v4.f32 {%0,%1,%2,%3}, [%4];" : "=f"(v.x), "=f"(v.y), "=f"(v.z), "=f"(v.w) : "r"(a) : "memory"); return v; }
__device__ __forceinline__ void sts16(uint32_t a, uint32_t v) { asm volatile("{ .reg .b16 l, h; mov.b32 {l, h}, %1; st.shared.b16 [%0], l; }" :: "r"(a), "r"(v) : "memory"); }
__device__ __forceinline__ void sts32(uint32_t a, uint32_t v) { asm volatile("st.shared.u32 [%0], %1;" :: "r"(a), "r"(v) : "memory"); }
__device__ __forceinline__ void sts64(uint32_t a, uint32_t x, uint32_t y) { asm volatile("st.shared.v2.u32 [%0], {%1,%2};" :: "r"(a), "r"(x), "r"(y) : "memory"); }
__device__ __forceinline__ void stsf(uint32_t a, float v) { asm volatile("st.shared.f32 [%0], %1;" :: "r"(a), "f"(v) : "memory"); }
__device__ __forceinline__ void sts128(uint32_t a, uint32_t x, uint32_t y, uint32_t z, uint32_t w) { asm volatile("st.shared.v4.u32 [%0], {%1,%2,%3,%4};" :: "r"(a), "r"(x), "r"(y), "r"(z), "r"(w) : "memory"); }
__device__ __forceinline__ void sts128f(uint32_t a, float x, float y, float z, float w) { asm volatile("st.shared.v4.f32 [%0], {%1,%2,%3,%4};" :: "r"(a), "f"(x), "f"(y), "f"(z), "f"(w) : "memory"); }
__device__ __forceinline__ void ldsm4(uint32_t (&r)[4], uint32_t a) { asm volatile("ldmatrix.sync.aligned.m8n8.x4.shared.b16 {%0,%1,%2,%3}, [%4];" : "=r"(r[0]), "=r"(r[1]), "=r"(r[2]), "=r"(r[3]) : "r"(a) : "memory"); }
__device__ __forceinline__ void ldsm4t(uint32_t (&r)[4], uint32_t a) { asm volatile("ldmatrix.sync.aligned.m8n8.x4.trans.shared.b16 {%0,%1,%2,%3}, [%4];" : "=r"(r[0]), "=r"(r[1]), "=r"(r[2]), "=r"(r[3]) : "r"(a) : "memory"); }
__device__ __forceinline__ void ldsm2t(uint32_t& r0, uint32_t& r1, uint32_t a) { asm volatile("ldmatrix.sync.aligned.m8n8.x2.trans.shared.b16 {%0,%1}, [%2];" : "=r"(r0), "=r"(r1) : "r"(a) : "memory"); }
__device__ __forceinline__ void stsm4t(uint32_t a, uint32_t r0, uint32_t r1, uint32_t r2, uint32_t r3) { asm volatile("stmatrix.sync.aligned.m8n8.x4.trans.shared.b16 [%0], {%1,%2,%3,%4};" :: "r"(a), "r"(r0), "r"(r1), "r"(r2), "r"(r3) : "memory"); }
__device__ __forceinline__ void stsm4(uint32_t a, uint32_t r0, uint32_t r1, uint32_t r2, uint32_t r3) { asm volatile("stmatrix.sync.aligned.m8n8.x4.shared.b16 [%0], {%1,%2,%3,%4};" :: "r"(a), "r"(r0), "r"(r1), "r"(r2), "r"(r3) : "memory"); }
__device__ __forceinline__ void stsm2t(uint32_t a, uint32_t r0, uint32_t r1) { asm volatile("stmatrix.sync.aligned.m8n8.x2.trans.shared.b16 [%0], {%1,%2};" :: "r"(a), "r"(r0), "r"(r1) : "memory"); }
__device__ __forceinline__ uint4 ldg128(const void* p) { uint4 v; asm volatile("ld.global.nc.v4.u32 {%0,%1,%2,%3}, [%4];" : "=r"(v.x), "=r"(v.y), "=r"(v.z), "=r"(v.w) : "l"(p)); return v; }
__device__ __forceinline__ uint32_t ldg16(const void* p) { unsigned short v; asm volatile("ld.global.nc.u16 %0, [%1];" : "=h"(v) : "l"(p)); return v; }
__device__ __forceinline__ uint32_t opaque(uint32_t v) { uint32_t r; asm volatile("mov.b32 %0, %1;" : "=r"(r) : "r"(v)); return r; }
__device__ __forceinline__ void mma_f16(float (&d)[4], const uint32_t (&a)[4], uint32_t b0, uint32_t b1) {
    asm volatile("mma.sync.aligned.m16n8k16.row.col.f32.f16.f16.f32 {%0,%1,%2,%3}, {%4,%5,%6,%7}, {%8,%9}, {%0,%1,%2,%3};"
        : "+f"(d[0]), "+f"(d[1]), "+f"(d[2]), "+f"(d[3]) : "r"(a[0]), "r"(a[1]), "r"(a[2]), "r"(a[3]), "r"(b0), "r"(b1));
}
__device__ __forceinline__ void mma_f16_z(float (&d)[4], const uint32_t (&a)[4], uint32_t b0, uint32_t b1) {
    asm volatile("mma.sync.aligned.m16n8k16.row.col.f32.f16.f16.f32 {%0,%1,%2,%3}, {%4,%5,%6,%7}, {%8,%9}, {%10,%10,%10,%10};"
        : "=f"(d[0]), "=f"(d[1]), "=f"(d[2]), "=f"(d[3]) : "r"(a[0]), "r"(a[1]), "r"(a[2]), "r"(a[3]), "r"(b0), "r"(b1), "f"(0.f));
}
__device__ __forceinline__ void mma_bf16(float (&d)[4], uint32_t a0, uint32_t a1, uint32_t a2, uint32_t a3, uint32_t b0, uint32_t b1) {
    asm volatile("mma.sync.aligned.m16n8k16.row.col.f32.bf16.bf16.f32 {%0,%1,%2,%3}, {%4,%5,%6,%7}, {%8,%9}, {%0,%1,%2,%3};"
        : "+f"(d[0]), "+f"(d[1]), "+f"(d[2]), "+f"(d[3]) : "r"(a0), "r"(a1), "r"(a2), "r"(a3), "r"(b0), "r"(b1));
}
__device__ __forceinline__ void mma_bf16_k8(float (&d)[4], uint32_t a0, uint32_t a1, uint32_t b0) {
    asm volatile("mma.sync.aligned.m16n8k8.row.col.f32.bf16.bf16.f32 {%0,%1,%2,%3}, {%4,%5}, {%6}, {%0,%1,%2,%3};"
        : "+f"(d[0]), "+f"(d[1]), "+f"(d[2]), "+f"(d[3]) : "r"(a0), "r"(a1), "r"(b0));
}
__device__ __forceinline__ uint32_t pack_f16(float lo, float hi) { uint32_t r; asm("cvt.rn.f16x2.f32 %0, %1, %2;" : "=r"(r) : "f"(hi), "f"(lo)); return r; }
__device__ __forceinline__ uint32_t pack_bf16(float lo, float hi) { uint32_t r; asm("cvt.rn.bf16x2.f32 %0, %1, %2;" : "=r"(r) : "f"(hi), "f"(lo)); return r; }
__device__ __forceinline__ float bf_lo(uint32_t v) { return __uint_as_float(v << 16); }
__device__ __forceinline__ float bf_hi(uint32_t v) { return __uint_as_float(v & 0xFFFF0000u); }
__device__ __forceinline__ float bfr(float x) { return __uint_as_float(pack_bf16(0.f, x)); }
__device__ __forceinline__ uint32_t badd2(uint32_t a, uint32_t b) { uint32_t r; asm("add.rn.bf16x2 %0, %1, %2;" : "=r"(r) : "r"(a), "r"(b)); return r; }
__device__ __forceinline__ uint32_t bmul2(uint32_t a, uint32_t b) { uint32_t r; asm("mul.rn.bf16x2 %0, %1, %2;" : "=r"(r) : "r"(a), "r"(b)); return r; }
__device__ __forceinline__ uint32_t hadd2(uint32_t a, uint32_t b) { uint32_t r; asm("add.rn.f16x2 %0, %1, %2;" : "=r"(r) : "r"(a), "r"(b)); return r; }
__device__ __forceinline__ uint32_t hmul2(uint32_t a, uint32_t b) { uint32_t r; asm("mul.rn.f16x2 %0, %1, %2;" : "=r"(r) : "r"(a), "r"(b)); return r; }
__device__ __forceinline__ uint32_t hfma2(uint32_t a, uint32_t b, uint32_t c) { uint32_t r; asm("fma.rn.f16x2 %0, %1, %2, %3;" : "=r"(r) : "r"(a), "r"(b), "r"(c)); return r; }
__device__ __forceinline__ uint32_t hneg2(uint32_t a) { uint32_t r; asm("neg.f16x2 %0, %1;" : "=r"(r) : "r"(a)); return r; }
__device__ __forceinline__ float rcpf(float x) { float r; asm("rcp.approx.ftz.f32 %0, %1;" : "=f"(r) : "f"(x)); return r; }
__device__ __forceinline__ float sqrta(float x) { float r; asm("sqrt.approx.ftz.f32 %0, %1;" : "=f"(r) : "f"(x)); return r; }
__device__ __forceinline__ float ex2f(float x) { float r; asm("ex2.approx.ftz.f32 %0, %1;" : "=f"(r) : "f"(x)); return r; }
__device__ __forceinline__ void st_async4(uint32_t a, uint32_t x, uint32_t y, uint32_t z, uint32_t w, uint32_t mb) {
    asm volatile("st.async.shared::cluster.mbarrier::complete_tx::bytes.v4.u32 [%0], {%1,%2,%3,%4}, [%5];" :: "r"(a), "r"(x), "r"(y), "r"(z), "r"(w), "r"(mb) : "memory"); }
__device__ __forceinline__ void st_async1(uint32_t a, uint32_t x, uint32_t mb) {
    asm volatile("st.async.shared::cluster.mbarrier::complete_tx::bytes.u32 [%0], %1, [%2];" :: "r"(a), "r"(x), "r"(mb) : "memory"); }
__device__ __forceinline__ unsigned ld_rlx(const void* p) { unsigned v; asm volatile("ld.relaxed.gpu.global.u32 %0, [%1];" : "=r"(v) : "l"(p) : "memory"); return v; }
__device__ __forceinline__ unsigned ld_acq(const void* p) { unsigned v; asm volatile("ld.acquire.gpu.global.u32 %0, [%1];" : "=r"(v) : "l"(p) : "memory"); return v; }
__device__ __forceinline__ uint2 ld_rlx64(const void* p) { unsigned long long v; asm volatile("ld.relaxed.gpu.global.u64 %0, [%1];" : "=l"(v) : "l"(p) : "memory"); return make_uint2((unsigned)v, (unsigned)(v >> 32)); }
__device__ __forceinline__ void st_rlx128(void* p, uint32_t x, uint32_t y, uint32_t z, uint32_t w) {
    asm volatile("st.relaxed.gpu.global.v2.u64 [%0], {%1,%2};" :: "l"(p), "l"((unsigned long long)x | ((unsigned long long)y << 32)), "l"((unsigned long long)z | ((unsigned long long)w << 32)) : "memory"); }
__device__ __forceinline__ uint4 ld_rlx128(const void* p) { unsigned long long a, b; asm volatile("ld.relaxed.gpu.global.v2.u64 {%0,%1}, [%2];" : "=l"(a), "=l"(b) : "l"(p) : "memory"); return make_uint4((unsigned)a, (unsigned)(a >> 32), (unsigned)b, (unsigned)(b >> 32)); }
__device__ __forceinline__ void tma2d(uint32_t dst, const CUtensorMap* tm, int x, int y, uint32_t mb) {
    asm volatile("cp.async.bulk.tensor.2d.shared::cluster.global.mbarrier::complete_tx::bytes [%0], [%1, {%3, %4}], [%2];"
                 :: "r"(dst), "l"(tm), "r"(mb), "r"(x), "r"(y) : "memory");
}
__device__ __forceinline__ void cmul(float& xr, float& xi, float ar, float ai, float br, float bi) {
    const float r = fmaf(ar, br, -ai * bi), i = fmaf(ar, bi, ai * br); xr = r; xi = i;
}
__device__ __forceinline__ void csq(float& xr, float& xi, float ar, float ai) {
    const float r = fmaf(ar, ar, -ai * ai), i = (ar + ar) * ai; xr = r; xi = i;
}
__device__ __forceinline__ void cexp_s(float& zr, float& zi, float e2, float turns) {
    const float mag = ex2f(e2), r = (turns - rintf(turns)) * 6.283185307179586f;
    zr = mag * __cosf(r); zi = mag * __sinf(r);
}
__device__ __forceinline__ uint32_t ln_stats(float s1, float s2) {
    const float m = s1 * (1.f / D_);
    const float var = fmaxf(fmaf(s2, 1.f / D_, -m * m), 0.f);
    return pack_bf16(m, sqrta(bfr(bfr(var) + 1e-5f)));
}
__device__ __forceinline__ uint32_t rsplit(float rs) { const float h = bfr(rs); return pack_bf16(h, rs - h); }
__device__ __forceinline__ uint32_t norm2(uint32_t v, uint32_t mx, uint32_t hl) {
    uint32_t r;
    asm("{ .reg .b16 m, h, l, x; .reg .b32 m2, h2, l2, d, t; mov.b32 {m, x}, %2; mov.b32 {h, l}, %3; mov.b32 m2, {m, m}; mov.b32 h2, {h, h}; mov.b32 l2, {l, l};\n"
        "sub.rn.bf16x2 d, %1, m2; mul.rn.bf16x2 t, d, l2; fma.rn.bf16x2 %0, d, h2, t; }" : "=r"(r) : "r"(v), "r"(mx), "r"(hl));
    return r;
}
template <int N, int S>
__device__ __forceinline__ uint32_t rank4(uint32_t a, uint32_t key) {
    uint32_t r0 = 0, r1 = 0, r2 = 0, r3 = 0;
#pragma unroll
    for (int i = 0; i < N; i++) {
        const uint4 o = lds128(a + i * S);
        r0 += (key - o.x) >> 31; r1 += (key - o.y) >> 31; r2 += (key - o.z) >> 31; r3 += (key - o.w) >> 31;
    }
    return (r0 + r1) + (r2 + r3);
}
typedef uint32_t H2C;
__device__ __forceinline__ H2C splat(float r, float i) { return pack_f16(r, i); }
__device__ __forceinline__ void hcmul(uint32_t& xr, uint32_t& xi, uint32_t R, uint32_t I, H2C m) {
    asm("{ .reg .b16 a, b; .reg .b32 a2, b2, t; mov.b32 {a, b}, %4; mov.b32 a2, {a, a}; mov.b32 b2, {b, b};\n"
        "mul.rn.f16x2 t, %3, b2; neg.f16x2 t, t; fma.rn.f16x2 %0, %2, a2, t; mul.rn.f16x2 t, %3, a2; fma.rn.f16x2 %1, %2, b2, t; }"
        : "=&r"(xr), "=r"(xi) : "r"(R), "r"(I), "r"(m));
}
__device__ __forceinline__ void expand4(uint32_t are, uint32_t aim, uint32_t R0, uint32_t R1, uint32_t I0, uint32_t I1, H2C m4) {
    uint32_t R2, I2, R3, I3;
    hcmul(R2, I2, R0, I0, m4); hcmul(R3, I3, R1, I1, m4);
    sts128(are, R0, R1, R2, R3);
    sts128(aim, I0, I1, I2, I3);
}
__device__ __forceinline__ void expand8(uint32_t are, uint32_t aim, float sr, float si, float m1r, float m1i, float m2r, float m2i, H2C m4) {
    float r1, i1, r2, i2, r3, i3;
    cmul(r1, i1, sr, si, m1r, m1i); cmul(r2, i2, sr, si, m2r, m2i); cmul(r3, i3, r1, i1, m2r, m2i);
    expand4(are, aim, pack_f16(sr, r1), pack_f16(r2, r3), pack_f16(si, i1), pack_f16(i2, i3), m4);
}
__device__ __forceinline__ void put16(uint32_t a, uint32_t v) { sts16(a, v); sts16(a + 6, v); }

struct Params {
    const unsigned short *logdt, *dskip, *prm6[6], *x, *wr;
    __nv_bfloat16* out;
    Scratch* gs;
    unsigned zero;
};
__device__ __forceinline__ uint32_t tslot(uint32_t t) { return (t & 7) * 32 + ((t >> 4) & 24) + ((t >> 8) & 6) + ((t >> 6) & 1); }
#define CP(x) ((x) | zero)
#define PIN(x) asm volatile("or.b32 %0, %0, %1;" : "+r"(x) : "r"(zero))
__device__ __forceinline__ void wgmma32(float (&d)[4][4], const uint32_t (&a)[4], uint32_t dlo) {
    asm volatile("{ .reg .b64 ds; mov.b64 ds, {%20, %21};\n"
                 "wgmma.mma_async.sync.aligned.m64n32k16.f32.f16.f16 {%0,%1,%2,%3,%4,%5,%6,%7,%8,%9,%10,%11,%12,%13,%14,%15}, {%16,%17,%18,%19}, ds, 1, 1, 1, 0; }"
        : "+f"(d[0][0]), "+f"(d[0][1]), "+f"(d[0][2]), "+f"(d[0][3]), "+f"(d[1][0]), "+f"(d[1][1]), "+f"(d[1][2]), "+f"(d[1][3]),
          "+f"(d[2][0]), "+f"(d[2][1]), "+f"(d[2][2]), "+f"(d[2][3]), "+f"(d[3][0]), "+f"(d[3][1]), "+f"(d[3][2]), "+f"(d[3][3])
        : "r"(a[0]), "r"(a[1]), "r"(a[2]), "r"(a[3]), "r"(dlo), "n"(128 >> 4));
}

__global__ void __cluster_dims__(CS, 1, 1) __launch_bounds__(NTHR, 1)
fused_kernel(const __grid_constant__ Params prm, const __grid_constant__ CUtensorMap tmG, const __grid_constant__ CUtensorMap tmU,
             const __grid_constant__ CUtensorMap tmD, const __grid_constant__ CUtensorMap tmO, const __grid_constant__ CUtensorMap tmX, const __grid_constant__ CUtensorMap tmH)
{
    extern __shared__ __align__(1024) unsigned char smem[];
    const int tid = threadIdx.x, lane = tid & 31, warp = __shfl_sync(~0u, tid >> 5, 0);
    const int c = blockIdx.x >> 3, q = blockIdx.x & 7;
    const int nslot = (c < NCL - 1) ? 5 : 2;
    const int d0 = 40 * c;
    const uint32_t sb = opaque((uint32_t)__cvta_generic_to_shared(smem));
    const uint32_t mb = sb + SM_MB;
    Scratch& g_s = *prm.gs;
    const unsigned& zero = prm.zero;
    STAMP(0);

    if (warp >= 20) {
        unsigned epoch = 0;
        if (warp == 20) {
            if (lane == 0) {
#pragma unroll
                for (int i = 0; i < 13; i++)
                    asm volatile("mbarrier.init.shared::cta.b64 [%0], %1;" :: "r"(mb + i * 8), "r"((i == MB_R || i < 5) ? 2 : i == MB_Y ? 1 + 4 * nslot : 1) : "memory");
                asm volatile("fence.mbarrier_init.release.cluster;" ::: "memory");
                arm(mb + MB_W1 * 8, 92160); arm(mb + MB_W2 * 8, nslot * 9216); arm(mb + MB_KEY * 8, 256); arm(mb + MB_GU * 8, nslot * 1024); arm(mb + MB_T * 8, 576 * XW);
                const int bytes = max(min(18, L_ - 18 * (int)blockIdx.x), 1) * (D_ * 2);
                arm(mb + MB_R * 8, bytes);
            }
            __syncwarp();
        } else if (warp == 22) {
            epoch = ld_rlx(&g_s.epoch);
            if (lane < 18 ? 18 * c + lane < 256 : lane < 31) (lane < 18 ? &g_s.acc[256 * q + 18 * c] : &g_s.fin[13 * (int)blockIdx.x - 18])[lane] = make_float4(0.f, 0.f, 0.f, 0.f);
        } else if (warp == 23 && lane == 0) asm volatile("prefetch.tensormap [%0];" :: "l"(&tmX) : "memory");
        asm volatile("barrier.cluster.arrive.relaxed.aligned;" ::: "memory");
        bar_sync(12, NTHR);
        uint4 wv = make_uint4(0, 0, 0, 0), wv2, wv3;
        if (warp == 22) {
            if (lane == 0) { sts32(sb + SM_SC + 28, epoch); asm volatile("mbarrier.arrive.shared::cta.b64 _, [%0];" :: "r"(mb + MB_R * 8) : "memory"); }
            epoch++;
            asm volatile("fence.acq_rel.gpu;" ::: "memory");
            __syncwarp();
            if (lane == 0) asm volatile("red.relaxed.gpu.global.add.u32 [%0], 1;" :: "l"(&g_s.zcnt) : "memory");
            STAMP(1);
            wv2 = ldg128((const uint4*)prm.wr + lane); wv3 = ldg128((const uint4*)prm.wr + 32 + lane);
            if (lane < 8) wv = ldg128((const uint4*)prm.wr + 64 + lane);
            if (lane < 5) {
                uint4 v = make_uint4(0, 0, 0, 0);
                if (lane < nslot) v = ldg128((const uint4*)(prm.wr + d0) + lane);
                sts128(sb + SM_DW + lane * 16, v.x, v.y, v.z, v.w);
            }
            __syncwarp();
            if (lane < 5) asm volatile("mbarrier.arrive.shared::cta.b64 _, [%0];" :: "r"(mb + (MB_X + lane) * 8) : "memory");
        }
        if (warp == 21) {
            if (lane == 0) { asm volatile("prefetch.tensormap [%0];" :: "l"(&tmG) : "memory"); asm volatile("prefetch.tensormap [%0];" :: "l"(&tmU) : "memory"); asm volatile("prefetch.tensormap [%0];" :: "l"(&tmD) : "memory"); }
            __syncwarp();
            bar_sync(15, 672);
            asm volatile("fence.proxy.async.shared::cta;" ::: "memory");
#pragma unroll 1
            for (int i = 0; i < 24; i++) {
                if (lane == 0) tma2d(sb + SM_WG + i * 3840, i < 12 ? &tmG : &tmU, 320 * c + 8 * nslot * q, 48 * (i < 12 ? i : i - 12), mb + MB_W1 * 8);
            }
            STAMP(1);
            return;
        }
        if (warp == 20) {
            if (lane == 0) {
                asm volatile("cp.async.bulk.shared::cluster.global.mbarrier::complete_tx::bytes [%0], [%1], %2, [%3];"
                             :: "r"(sb + SM_ROW), "l"(prm.x + min(18 * (int)blockIdx.x, L_ - 1) * D_), "r"(max(min(18, L_ - 18 * (int)blockIdx.x), 1) * (D_ * 2)), "r"(mb + MB_R * 8) : "memory");
            }
            __syncwarp();
            mbar_wait(mb + MB_R * 8);
            if (lane == 0) {
                asm volatile("cp.async.bulk.tensor.5d.shared::cluster.global.mbarrier::complete_tx::bytes [%0], [%1, {%3, %4, %5, %5, %5}], [%2];"
                             :: "r"(sb + SM_XTL), "l"(&tmX), "r"(mb + MB_T * 8), "r"(d0 & ~15), "r"(8 * q), "r"(0) : "memory");
            }
            STAMP(6);
        }
        asm volatile("barrier.cluster.wait.aligned;" ::: "memory");
        bar_sync(13, 608);
        asm volatile("fence.proxy.async.shared::cta;" ::: "memory");
        {
            const int idx = lane * 3 + max(warp - 21, 0), sl = nslot - 1 - (idx >> 3), pe = (idx + q + 1) & 7;
            if (sl >= 0) {
                if (pe == q) arm(mb + (MB_X + sl) * 8, 7 * 512);
                else {
                    const uint32_t rb_ = mapa(sb, pe);
                    asm volatile("cp.async.bulk.shared::cluster.shared::cta.mbarrier::complete_tx::bytes [%0], [%1], 512, [%2];"
                                 :: "r"(rb_ + SM_U + 128 + q * UP + sl * US), "r"(sb + SM_XT + 128 + (q & 3) * 16 + pe * YP + sl * YS), "r"(rb_ + SM_MB + (MB_X + sl) * 8) : "memory");
                }
            }
        }
        STAMP(1);
        if (warp == 20 && lane == 0) { asm volatile("prefetch.tensormap [%0];" :: "l"(&tmO) : "memory"); asm volatile("prefetch.tensormap [%0];" :: "l"(&tmH) : "memory"); }
        if (warp == 22) {
            __syncwarp();
            mbar_wait(mb + (MB_X + 1) * 8);
            const uint32_t old = (epoch & 1) ? 0u : 0x40004000u;
#pragma unroll
            for (int t = 0; t < 2; t++)
                if ((lane & 7) < 6) g_s.cand[((q * 8 + 4 * t + (lane >> 3)) * NCL + c) * 6 + (lane & 7)] = make_uint4(old, old, old, old);
            float a[4] = {0.f, 0.f, 0.f, 0.f};
            const uint32_t one = 0x3F803F80u;
            mma_bf16(a, one, one, one, one, wv.x, wv.y);  mma_bf16(a, one, one, one, one, wv.z, wv.w);
            mma_bf16(a, one, one, one, one, wv2.x, wv2.y); mma_bf16(a, one, one, one, one, wv2.z, wv2.w);
            mma_bf16(a, one, one, one, one, wv3.x, wv3.y); mma_bf16(a, one, one, one, one, wv3.z, wv3.w);
            float s = a[0] + a[1];
            s += __shfl_xor_sync(~0u, s, 1); s += __shfl_xor_sync(~0u, s, 2);
            stsf(sb + SM_SC + 24, s);
            __syncwarp();
            if (lane == 0) {
                int n = 0;
                while ((int)(ld_acq(&g_s.zcnt) - epoch * NCTA) < 0 && ++n < SPIN_LIMIT) __nanosleep(200);
                arm(mb + MB_Y * 8, 8 * 512 * nslot);
                if (blockIdx.x == 0) g_s.epoch = epoch;
            }
            STAMP(2);
            return;
        }
        if (warp == 23) {
#pragma unroll 1
            for (int kk = nslot - 1; kk >= 0; kk--) {
                __syncwarp();
                bar_sync(6 + kk, 160);
                if (lane == 0) { asm volatile("fence.proxy.async.shared::cta;" ::: "memory"); tma2d(sb + SM_FAR + kk * FAR_SZ, &tmD, 72 * q, 320 * c + 64 * kk, mb + MB_W2 * 8); }
            }
            return;
        }
        __syncwarp();
        bar_sync(14, 672);
        if (lane == 0) {
            asm volatile("fence.proxy.async.shared::cta;" ::: "memory");
            asm volatile("cp.async.bulk.tensor.5d.global.shared::cta.bulk_group [%0, {%2, %4, %4, %4, %3}], [%1];" :: "l"(&tmH), "r"(sb + SM_XT + 16384), "r"(d0 + ((c & 1) ? 0 : 32)), "r"(8 * q), "r"(0) : "memory");
            asm volatile("cp.async.bulk.tensor.5d.global.shared::cta.bulk_group [%0, {%2, %4, %4, %4, %3}], [%1];" :: "l"(&tmO), "r"(sb + SM_XT), "r"(d0 + (c & 1) * 8), "r"(8 * q), "r"(0) : "memory");
            asm volatile("cp.async.bulk.commit_group;" ::: "memory");
            asm volatile("cp.async.bulk.wait_group 0;" ::: "memory");
            asm volatile("fence.proxy.async.global;" ::: "memory");
            asm volatile("mbarrier.arrive.shared::cta.b64 _, [%0];" :: "r"(mb + MB_OUT * 8) : "memory");
        }
        STAMP(2);
        return;
    }

    const int g = lane >> 2, cq = lane & 3;
    const int k = warp >> 2, wq = warp & 3;
    const int trow = 18 * blockIdx.x + warp;
    const bool rowact = warp < 18 && trow < L_;
    const int dch = min(d0 + 8 * k + q, D_ - 1);
    uint32_t pv[6];
    const uint32_t pofs = opaque((dch * 128 + wq * 32 + lane) * 2);
#pragma unroll
    for (int i = 0; i < 6; i++) pv[i] = ldg16((const char*)prm.prm6[i] + pofs);
    const uint32_t pLdt = ldg16(prm.logdt + dch), pD = ldg16(prm.dskip + dch);
    const int tn = 16 * (warp & 15) + g;
    uint32_t xa[5], xb[5];
    asm volatile("barrier.cluster.arrive.relaxed.aligned;" ::: "memory");
    uint4* const st1p = &g_s.st1[(((trow >> 3) & 7) * 256 + ((trow >> 6) & 31) * 8 + (trow & 7)) * 2 + (lane >> 2)];
    const bool pub = rowact && (lane & 0x1B) == 0;
    if (pub) st_rlx128(st1p, 0, 0, 0, 0);
    {
        const uint32_t za = sb + SM_P + tid * 16;
        sts128(za, 0, 0, 0, 0);
        if (tid < (SM_MISC - SM_P) / 16 - 640) sts128(za + 10240, 0, 0, 0, 0);
        sts128(sb + ((wq & 2) ? SM_U : SM_XT + (q & 3) * 16) + ((tid >> 3) & 7) * ((wq & 2) ? UP : YP) + k * YS + (lane & 7) * 16, 0, 0, 0, 0);
    }
    bar_sync(12, NTHR);
    const uint32_t dep = lds32(sb + SM_P);
#define PV(x) __uint_as_float(__byte_perm(dep, x, 0x5410))
    STAMP(1);
    const uint32_t fb = sb + SM_FAR + k * FAR_SZ;
    const uint32_t pn = sb + SM_PN + k * PN_SZ, pf = sb + SM_PF + k * PF_SZ;
    unsigned epoch;
    {
        const uint32_t kb = fb + wq * 3072;
        const uint32_t kl = kb + lane * 16;
        uint32_t Af[4][4];
        float sr, si, z1r, z1i, z2r, z2i, z4r, z4i, hr, hi_;
        {
            const float dt = bfr(ex2f(PV(pLdt) * 1.4426950408889634f));
            const float e2 = dt * PV(pv[0]) * 1.4426950408889634f, an = dt * PV(pv[1]);
            float ar, ai, br, bi, cr, ci, dr, di;
            { const float m = ex2f(e2 * 8.f); ar = m * __cosf(an * 8.f); ai = m * __sinf(an * 8.f); }
            csq(br, bi, ar, ai); csq(cr, ci, br, bi); csq(dr, di, cr, ci);
            const H2C m4 = splat(cr, ci);
            {
                float r3, i3;
                cmul(r3, i3, ar, ai, br, bi);
                expand4(kl, kl + 1024, pack_f16(1.f, ar), pack_f16(br, r3), pack_f16(0.f, ai), pack_f16(bi, i3), m4);
            }
            expand8(kl + 512, kl + 1536, dr, di, ar, ai, br, bi, m4);
            { const float m = ex2f(e2); z1r = m * __cosf(an); z1i = -m * __sinf(an); }
            cexp_s(hr, hi_, e2 * 128.f, an * (-128.f * 0.15915494309189535f));
            csq(z2r, z2i, z1r, z1i); csq(z4r, z4i, z2r, z2i);
            const uint32_t dep2 = lds32(sb + SM_P + 4);
#define PW(x) __uint_as_float(__byte_perm(dep2, x, 0x5410))
            cmul(sr, si, PW(pv[4]), PW(pv[5]), dt * PW(pv[2]), dt * PW(pv[3]));
            const unsigned E = min(max(__reduce_max_sync(~0u, __float_as_uint(fmaxf(fmaxf(fabsf(sr), fabsf(si)), fabsf(PW(pD)) * (1.f / 8192.f)))) >> 23, 1u), 253u);
            const float sc = __uint_as_float((254u - E) << 23);
            sr *= sc; si *= -sc;
            sts64(sb + SM_KG + warp * 8, E, __reduce_add_sync(~0u, __float2int_rn(sr * 16777216.f)));
            stsf(sb + SM_DW + 96 + k * 4, PW(pD));
        }
        __syncwarp();
#pragma unroll
        for (int ks = 0; ks < 4; ks++) ldsm4t(Af[ks], kb + (lane >> 3) * 512 + (lane & 7) * 16 + ks * 128);
        STAMP(2);
        const uint32_t la = kb + ((lane >> 3) & 1) * 512 + (lane >> 4) * 128 + (lane & 7) * 16;
        uint32_t kp[5][2], b0[4], b1[4], b2[4], b3[4], c0[4], c1[4], c2[4], c3[4];
        auto mm2 = [&](int t, uint32_t (&b0)[4], uint32_t (&b1)[4], uint32_t (&b2)[4], uint32_t (&b3)[4]) {
            float a0[4] = {0.f, 0.f, 0.f, 0.f}, a1[4] = {0.f, 0.f, 0.f, 0.f};
            mma_f16(a0, Af[0], b0[0], b0[1]); mma_f16(a1, Af[0], b2[0], b2[1]); mma_f16(a0, Af[1], b0[2], b0[3]); mma_f16(a1, Af[1], b2[2], b2[3]);
            mma_f16(a0, Af[2], b1[0], b1[1]); mma_f16(a1, Af[2], b3[0], b3[1]); mma_f16(a0, Af[3], b1[2], b1[3]); mma_f16(a1, Af[3], b3[2], b3[3]);
            kp[t][0] = pack_f16(a0[1], a0[0]); kp[t][1] = pack_f16(a0[3], a0[2]); kp[t + 1][0] = pack_f16(a1[1], a1[0]); kp[t + 1][1] = pack_f16(a1[3], a1[2]);
        };
        auto ln1 = [&]() {
        mbar_wait(mb + MB_R * 8);
        epoch = lds32(sb + SM_SC + 28) + 1;
        {
            const uint32_t ra = sb + SM_ROW + warp * (D_ * 2);
            const uint4 r0 = lds128(ra + lane * 16), r1 = lds128(ra + 512 + lane * 16);
            const uint32_t rx[9] = {r0.x, r0.y, r0.z, r0.w, r1.x, r1.y, r1.z, r1.w, lds32(ra + 1024 + lane * 4)};
            float a0 = bf_lo(rx[0]), a1 = bf_hi(rx[0]), c0 = a0 * a0, c1 = a1 * a1;
#pragma unroll
            for (int i = 1; i < 9; i++) { const float l = bf_lo(rx[i]), h = bf_hi(rx[i]); a0 += l; a1 += h; c0 = fmaf(l, l, c0); c1 = fmaf(h, h, c1); }
            a0 += a1; c0 += c1;
            float s1 = ((lane & 1) ? c0 : a0) + __shfl_xor_sync(~0u, (lane & 1) ? a0 : c0, 1);
#pragma unroll
            for (int o = 2; o < 32; o <<= 1) s1 += __shfl_xor_sync(~0u, s1, o);
            const float s2 = __shfl_xor_sync(~0u, s1, 1);
            const uint32_t ms = ln_stats(s1, s2);
            const uint32_t p0 = __byte_perm(ms, epoch | 0x8000u, 0x5410), p1 = rsplit(rcpf(bf_hi(ms)));
            if (pub) st_rlx128(st1p, p0, p1, p0, p1);
        }
        mbar_wait(mb + MB_R * 8);
        STAMP(1);
        };
        const uint4* sp = &g_s.st1[(256 * q + tn) * 2];
        uint2 sa, sc;
        auto poll = [&]() { sa = ld_rlx64(sp); sc = ld_rlx64(sp + 16); };
        auto norm = [&]() {
        STAMP(3);
        if (warp < 16) {
            uint32_t va[5], vc[5];
            poll();
            mbar_wait(mb + MB_T * 8);
            {
                const uint32_t xt = sb + SM_XTL + (c & 1) * 16 + (72 * wq + 18 * k + g) * (2 * XW);
                uint4 a4 = lds128(xt + cq * 16), b4 = lds128(xt + cq * 16 + 18 * XW);
                va[0] = a4.x; va[1] = a4.y; va[2] = a4.z; va[3] = a4.w; va[4] = lds32(xt + 64 + cq * 4);
                vc[0] = b4.x; vc[1] = b4.y; vc[2] = b4.z; vc[3] = b4.w; vc[4] = lds32(xt + (64 + 18 * XW) + cq * 4);
            }
            const int d4 = 2 * (lane >> 3) + (lane & 1), d1_ = lane & 7;
            const uint32_t own = SM_U + 128 + q * (UP - YP), oth = SM_XT + 128 + (q & 3) * 16;
            uint32_t a4 = sb + warp * 32 + d4 * YP + (d4 == q ? own : oth) + ((lane & 7) >> 1) * YS;
            uint32_t a1 = sb + warp * 32 + d1_ * YP + (d1_ == q ? own : oth) + 4 * YS + (lane & 8) * 2;
            PIN(a4); PIN(a1);
            uint32_t tag = __byte_perm(epoch | 0x8000u, 0, 0x1010);
            PIN(tag);
            mbar_wait(mb + MB_T * 8);
            int n = 0;
            while (__byte_perm(sa.x, sc.x, 0x7632) != tag && ++n < SPIN_LIMIT) poll();
            STAMP(4);
#pragma unroll
            for (int i = 0; i < 5; i++) {
                va[i] = norm2(va[i], sa.x, sa.y); va[i] = pack_f16(bf_lo(va[i]), bf_hi(va[i]));
                vc[i] = norm2(vc[i], sc.x, sc.y); vc[i] = pack_f16(bf_lo(vc[i]), bf_hi(vc[i]));
            }
            stsm4t(a4, va[0], va[1], va[2], va[3]); stsm4t(a4 + 16, vc[0], vc[1], vc[2], vc[3]); stsm2t(a1, va[4], vc[4]);
            bar_arrive(13, 608);
            {
            const uint32_t xh = sb + SM_XTL + (c & 1) * 16 + (9 * g + 144 * (warp & 1) + (warp >> 1)) * (2 * XW);
            const uint4 c4 = lds128(xh + cq * 16), d4_ = lds128(xh + cq * 16 + 144 * XW);
            xa[0] = c4.x; xa[1] = c4.y; xa[2] = c4.z; xa[3] = c4.w; xa[4] = lds32(xh + 64 + cq * 4);
            xb[0] = d4_.x; xb[1] = d4_.y; xb[2] = d4_.z; xb[3] = d4_.w; xb[4] = lds32(xh + (64 + 144 * XW) + cq * 4);
            }
        }
        STAMP(5);
        __syncwarp();
        bar_sync(15, 672);
        Af[0][0] |= lds32(sb + SM_P);
        };
        cmul(sr, si, sr, si, z1r, z1i);
        {
            const H2C h4 = splat(z4r, z4i);
            expand8(kl, kl + 512, sr, si, z1r, z1i, z2r, z2i, h4);
            cmul(sr, si, sr, si, hr, hi_);
            expand8(kl + 1024, kl + 1536, sr, si, z1r, z1i, z2r, z2i, h4);
        }
        __syncwarp();
        ldsm4t(b0, la); ldsm4t(b1, la + 256); ldsm4t(b2, la + 1024); ldsm4t(b3, la + 1280);
        cmul(z1r, z1i, z1r, z1i, hr, hi_);
        cmul(sr, si, sr, si, z1r, z1i);
        ln1();
        expand8(kl, kl + 512, sr, si, z2r, z2i, z4r, z4i, splat(hr, hi_));
        csq(z1r, z1i, z1r, z1i);
        cmul(sr, si, sr, si, z1r, z1i);
        csq(z2r, z2i, hr, hi_);
        expand8(kl + 1024, kl + 1536, sr, si, z4r, z4i, hr, hi_, splat(z2r, z2i));
        csq(z1r, z1i, z1r, z1i);
        cmul(sr, si, sr, si, z1r, z1i);
        csq(z4r, z4i, z2r, z2i);
        expand8(kl + 2048, kl + 2560, sr, si, hr, hi_, z2r, z2i, splat(z4r, z4i));
        norm();
        ldsm4t(c0, la); ldsm4t(c2, la + 1024); ldsm4t(c1, la + 256); ldsm4t(c3, la + 1280);
        mm2(0, b0, b1, b2, b3);
        mm2(2, c0, c1, c2, c3);
        ldsm4t(b0, la + 2048); ldsm4t(b1, la + 2304);
#pragma unroll
        for (int t = 0; t < 4; t++) sts64(kb + lane * 8 + 1024 + t * 256, kp[t][0], kp[t][1]);
        {
            float a0[4] = {0.f, 0.f, 0.f, 0.f}, a1[4] = {0.f, 0.f, 0.f, 0.f};
            mma_f16(a0, Af[0], b0[0], b0[1]); mma_f16(a1, Af[1], b0[2], b0[3]); mma_f16(a0, Af[2], b1[0], b1[1]); mma_f16(a1, Af[3], b1[2], b1[3]);
            sts64(kb + lane * 8 + 2048, pack_f16(a0[1] + a1[1], a0[0] + a1[0]), pack_f16(a0[3] + a1[3], a0[2] + a1[2]));
        }
        bar_sync(1 + k, 128);
        const uint4 m01 = lds128(sb + SM_KG + k * 32), m23 = lds128(sb + SM_KG + k * 32 + 16);
        const unsigned Em = max(max(m01.x, m01.z), max(m23.x, m23.z));
        const float f0 = __uint_as_float(max((int)(127 + m01.x - Em), 0) << 23), f1 = __uint_as_float(max((int)(127 + m01.z - Em), 0) << 23),
                    f2 = __uint_as_float(max((int)(127 + m23.x - Em), 0) << 23), f3 = __uint_as_float(max((int)(127 + m23.z - Em), 0) << 23);
        const uint32_t r0 = pack_f16(f0, f0), r1 = pack_f16(f1, f1), r2 = pack_f16(f2, f2), r3 = pack_f16(f3, f3);
        const int tq = (wq + k) & 3;
        const uint32_t ra = fb + lane * 8 + tq * 256 + 1024;
        const uint2 p0 = lds64(ra), p1 = lds64(ra + 3072), p2 = lds64(ra + 6144), p3 = lds64(ra + 9216);
        uint32_t w0 = hadd2(hfma2(p0.x, r0, hmul2(p1.x, r1)), hfma2(p2.x, r2, hmul2(p3.x, r3)));
        uint32_t w1 = hadd2(hfma2(p0.y, r0, hmul2(p1.y, r1)), hfma2(p2.y, r2, hmul2(p3.y, r3)));
        const bool last = lane == 31;
        uint32_t w4 = 0;
        if (tq < 2) {
            const uint32_t rc = fb + lane * 8 + tq * 4 + 2048;
            w4 = hmul2(hadd2(hfma2(lds32(rc), r0, hmul2(lds32(rc + 3072), r1)), hfma2(lds32(rc + 6144), r2, hmul2(lds32(rc + 9216), r3))), 0x18001800u);
        }
        if (tq < 2) {
            const uint32_t ph = pf + (P_H7 + 16 * tq) + (g & 1) * (2 * P_HS) + cq * 64 + (g >> 1) * 4;
            put16(ph, w4 >> 16); put16(ph + 32, w4);
            const uint32_t pa = pn + (4 + 512 * tq) + lane * 8;
            sts16(pa, w0 >> 16); sts32(pa + 4, w0); sts16(pa + 10, w0);
            sts16(pa + 256, w1 >> 16); sts32(pa + 260, w1); sts16(pa + 266, w1);
            if (last) {
                sts32(sb + SM_SC + k * 4, Em * 0x00800080u);
                put16(tq ? pa + 264 : pn,
                      tq ? w1 : pack_f16(((float)(int)m01.y * f0 + (float)(int)m01.w * f1 + (float)(int)m23.y * f2 + (float)(int)m23.w * f3) * (1.f / 16777216.f)
                                         + ldsf(sb + SM_DW + 96 + k * 4) * __uint_as_float((254u - Em) << 23), 0.f));
            }
        } else if (tq == 2) {
            const uint32_t pa = pn + 258 * 4 + (cq & 1) * 16 + (cq >> 1) * 512 + g * 32;
            if (last) { put16(pf, hmul2(w1, 0x18001800u)); w1 = hadd2(w1, hneg2(__byte_perm(w1, 0, 0x1010))); }
            const uint32_t b0 = __byte_perm(w0, 0, 0x1010), b1 = __byte_perm(w1, 0, 0x1010);
            sts16(pa, w0 >> 16); sts32(pa + 4, w0); sts64(pa + 8, b0, b0); sts16(pa + 18, w0);
            sts16(pa + 256, w1 >> 16); sts32(pa + 260, w1); sts64(pa + 264, b1, b1); sts16(pa + 274, w1);
        } else {
            const uint32_t pa = pf + ((g & 1) ? 3 * P_GS : P_GS) + cq * 32 + (g >> 1) * 4;
            const uint32_t pb = pa + ((g & 1) ? 4 - 3 * P_GS : P_GS);
            w0 = hmul2(w0, 0x18001800u); w1 = hmul2(w1, 0x18001800u);
            put16(pa, w0 >> 16); put16(pb, w0); put16(pa + 16, w1 >> 16); put16(pb + 16, w1);
            if (last) put16(pf + P_H7 + P_HS, w1);
        }
        bar_sync(1 + k, 128);
    }
    STAMP(6);

    asm volatile("barrier.cluster.wait.aligned;" ::: "memory");
    mbar_wait(mb + (MB_X + (k < nslot ? k : 0)) * 8);
    STAMP(7);
    if (k < nslot) {
        const int role = (wq + k) & 3;
        const uint32_t ub = sb + SM_U + k * US + 128;
        if (role) {
            const int r = (3 - role) * 32 + lane;
            const uint32_t a1 = ub + (r & 3) * (2 * UP) + (r >> 2) * 16, a0 = a1 + ((r & 3) ? -2 * UP : 6 * UP - 16);
            const uint4 q0 = lds128(a0), q1 = lds128(a0 + UP), q2 = lds128(a1), q3 = lds128(a1 + UP);
            const uint32_t U[16] = {q0.x, q0.y, q0.z, q0.w, q1.x, q1.y, q1.z, q1.w, q2.x, q2.y, q2.z, q2.w, q3.x, q3.y, q3.z, q3.w};
            uint32_t V[14], Q[14], R4[12], T[8];
#pragma unroll
            for (int i = 2; i < 14; i++) { V[i] = __byte_perm(U[i], U[i + 1], 0x5432); Q[i] = hadd2(U[i], V[i]); }
#pragma unroll
            for (int i = 2; i < 12; i++) R4[i] = hadd2(Q[i], Q[i + 1]);
            const uint32_t rb = fb + r * 16;
#pragma unroll
            for (int i = 0; i < 8; i++) T[i] = hadd2(V[5 + i], Q[6 + i]);
            sts128(rb + F_E3, T[0], T[1], T[2], T[3]); sts128(rb + F_O3 + 16, T[4], T[5], T[6], T[7]);
#pragma unroll
            for (int i = 0; i < 8; i++) T[i] = hadd2(R4[3 + i], U[5 + i]);
            sts128(rb + F_O5, T[0], T[1], T[2], T[3]); sts128(rb + F_E5, T[4], T[5], T[6], T[7]);
            if (role != 1) {
#pragma unroll
                for (int i = 0; i < 8; i++) T[i] = hadd2(T[i], hadd2(V[2 + i], V[5 + i]));
                sts128(rb + F_E7, T[0], T[1], T[2], T[3]); sts128(rb + F_O7, T[4], T[5], T[6], T[7]);
#pragma unroll
                for (int i = 0; i < 8; i++) T[i] = hadd2(R4[2 + i], hadd2(R4[4 + i], U[6 + i]));
                sts128(rb + F_O9, T[0], T[1], T[2], T[3]); sts128(rb + F_E9 + 16, T[4], T[5], T[6], T[7]);
                sts128(rb + F_E2, Q[6], Q[7], Q[8], Q[9]); sts128(rb + F_O2, Q[10], Q[11], Q[12], Q[13]);
            }
        } else if (lane < 8) {
            uint32_t v[5];
#pragma unroll
            for (int i = 0; i < 5; i++) { const int t = 6 + lane + i; v[i] = lds16(ub + 23 * 16 + (t < 16 ? (6 + (t >> 3)) * UP : 16) + (t & 7) * 2); }
            const uint32_t s = hadd2(hadd2(hadd2(v[0], v[1]), hadd2(v[2], v[3])), v[4]);
            sts16(fb + F_O5 + 96 * 16 + lane * 2, s);
            sts32(fb + (lane < 4 ? F_O3 : F_E9 - 16) + lane * 4, 0);
        }
        bar_sync(1 + k, 128);
        float acc[4][4];
        uint32_t Q[4][4];
        {
            const int h = role & 1, part = role >> 1;
            const uint32_t po = pf + (g - 2 * cq) * 4;
            float fa[7][4];
#pragma unroll
            for (int a = 0; a < 7; a++) fa[a][0] = fa[a][1] = fa[a][2] = fa[a][3] = 0.f;
            uint32_t B[3][4];
            Q[0][2] = tid & zero;
#pragma unroll 1
            for (int s = 2 * part + 1; s >= 2 * part; s--) {
#pragma unroll
                for (int i = 0; i < 3; i++) { Q[i][0] = lds32(po + s * P_GS + i * 64); Q[i][1] = lds32(po + s * P_GS + (i * 64 + 32)); }
                const uint32_t ba = fb + lane * 16 + ((s & 1) * F_E3 + (part == h ? 0 : F_O5 + h * 16));
#pragma unroll
                for (int i = 0; i < 3; i++) ldsm4t(B[i], ba + i * 512);
#pragma unroll
                for (int i = 0; i < 3; i++) { Q[i][3] = CP(Q[i][0]); if (i) Q[i][2] = CP(Q[i - 1][1]); }
#pragma unroll
                for (int dl = 0; dl < 3; dl++)
#pragma unroll
                    for (int ap = 0; ap < 6 - dl; ap++) mma_f16(fa[ap + 1 + dl], Q[dl], B[ap >> 1][2 * (ap & 1)], B[ap >> 1][2 * (ap & 1) + 1]);
            }
#pragma unroll 1
            for (int s = role; s == 1; s++) {
                ldsm2t(B[0][0], B[0][1], fb + ((lane & 15) == 15 ? F_O5 : F_O3));
#pragma unroll
                for (int dl = 0; dl < 3; dl++) mma_f16(fa[dl], Q[dl], B[0][0], B[0][1]);
            }
#pragma unroll 1
            for (int s = part; s <= 2 * part; s++) {
#pragma unroll
                for (int i = 0; i < 4; i++) { Q[i][0] = lds32(po + s * P_HS + (P_H7 + i * 64)); Q[i][1] = lds32(po + s * P_HS + (P_H7 + i * 64 + 32)); }
                const uint32_t ba = fb + lane * 16 + (F_E7 + s * 1024 + h * F_H);
                ldsm4t(B[0], ba); ldsm4t(B[1], ba + 512);
#pragma unroll
                for (int i = 0; i < 4; i++) { Q[i][3] = CP(Q[i][0]); if (i) Q[i][2] = CP(Q[i - 1][1]); }
#pragma unroll
                for (int dl = 0; dl < 4; dl++) {
#pragma unroll
                    for (int ap = 0; ap < 4 - dl; ap++) mma_f16(fa[ap + 3 + dl], Q[dl], B[ap >> 1][2 * (ap & 1)], B[ap >> 1][2 * (ap & 1) + 1]);
                    if (s == 1) break;
                }
            }
            const uint32_t da = fb + role * 2048 + (lane & 3) * 512 + (((lane >> 2) ^ ((lane & 3) * 2)) << 4);
            bar_sync(1 + k, 128);
            stsm4(da, 0u, 0u, pack_f16(fa[0][0], fa[0][1]), pack_f16(fa[0][2], fa[0][3]));
#pragma unroll
            for (int i = 1; i < 4; i++)
                stsm4(da + i * 128, pack_f16(fa[2 * i - 1][0], fa[2 * i - 1][1]), pack_f16(fa[2 * i - 1][2], fa[2 * i - 1][3]),
                      pack_f16(fa[2 * i][0], fa[2 * i][1]), pack_f16(fa[2 * i][2], fa[2 * i][3]));
            Q[0][0] = (g == 2 * cq) ? 0x6000u : ((g == 2 * cq + 1) ? 0x60000000u : 0u);
            Q[0][1] = Q[0][0] & zero; Q[0][2] = lane & zero; Q[0][3] = CP(Q[0][0]);
            const uint32_t ra = fb + (lane >> 3) * 2048 + wq * 512 + (((lane & 7) ^ (wq * 2)) << 4);
            bar_sync(1 + k, 128);
#pragma unroll
            for (int i = 0; i < 4; i++) {
                ldsm4(B[0], ra + i * 128);
                mma_f16_z(acc[i], Q[0], hadd2(B[0][0], B[0][2]), hadd2(B[0][1], B[0][3]));
            }
        }
        bar_arrive(6 + k, 160);
        STAMP(8);
        const uint32_t inv = lds32(sb + SM_SC + k * 4);
        uint32_t yd = mapa(sb, 2 * wq) + (SM_XT + 128 + q * YP + k * YS + (k >> 2) * (q >> 1) * 16) + lane * 16;
        PIN(yd);
        {
            uint32_t pp = pn + (16 * (wq - 3) + g - 2 * cq) * 4;
            uint32_t dlo = (((ub + 6 * UP) & 0x3FFFF) >> 4) | ((UP >> 4) << 16);
            uint32_t R[4][4];
            auto loadQ = [&](uint32_t (&X)[4][4], uint32_t prev) {
#pragma unroll
                for (int i = 0; i < 4; i++) { X[i][0] = lds32(pp + i * 64); X[i][1] = lds32(pp + i * 64 + 32); }
                X[0][2] = CP(prev);
#pragma unroll
                for (int i = 0; i < 4; i++) { X[i][3] = CP(X[i][0]); if (i) X[i][2] = CP(X[i - 1][1]); }
                pp += 256;
            };
            auto issue = [&](uint32_t (&X)[4][4]) {
                asm volatile("wgmma.fence.sync.aligned;" ::: "memory");
#pragma unroll
                for (int i = 0; i < 4; i++) wgmma32(acc, X[i], dlo - i * (2 * UP >> 4));
                asm volatile("wgmma.commit_group.sync.aligned;" ::: "memory");
                dlo -= 1;
            };
            loadQ(Q, 0);
#pragma unroll 1
            for (int dl = 0; dl < 4; dl++) {
                issue(Q);
                asm volatile("wgmma.wait_group.sync.aligned 1;" ::: "memory");
                loadQ(R, Q[3][1]);
                issue(R);
                asm volatile("wgmma.wait_group.sync.aligned 1;" ::: "memory");
                loadQ(Q, R[3][1]);
            }
            issue(Q);
            asm volatile("wgmma.wait_group.sync.aligned 0;" ::: "memory");
        }
        const uint32_t pstep = mapa(sb, 1) - mapa(sb, 0), ym = mapa(mb + MB_Y * 8, 2 * wq);
#pragma unroll
        for (int e = 0; e < 2; e++)
            st_async4(yd + e * pstep, bmul2(pack_bf16(acc[0][2 * e], acc[0][2 * e + 1]), inv), bmul2(pack_bf16(acc[1][2 * e], acc[1][2 * e + 1]), inv),
                      bmul2(pack_bf16(acc[2][2 * e], acc[2][2 * e + 1]), inv), bmul2(pack_bf16(acc[3][2 * e], acc[3][2 * e + 1]), inv), ym + e * pstep);
        if (lane == 0) asm volatile("mbarrier.arrive.shared::cta.b64 _, [%0];" :: "r"(mb + MB_Y * 8) : "memory");
    }
    STAMP(9);
    uint32_t ha[5], hb[5];
    if (warp < 16) {
        const uint4 wk = lds128(sb + SM_DW + cq * 16);
        uint32_t sel[5] = {wk.x, wk.y, wk.z, wk.w, lds32(sb + SM_DW + 64 + cq * 4)}, sel2[5];
#pragma unroll
        for (int i = 0; i < 5; i++) {
            if (!(g & 1)) sel[i] = 0x3F803F80u;
            sel2[i] = sel[i]; PIN(sel2[i]);
        }
        const uint32_t y4 = sb + SM_XT + 128 + warp * 32 + (2 * (lane >> 3) + (lane & 1)) * YP + ((lane & 7) >> 1) * YS;
        const uint32_t y1 = sb + SM_XT + 128 + warp * 32 + (lane & 7) * YP + 4 * YS + (lane & 8) * 2 + (lane & 6) * 8;
        uint32_t ao = (256 * q + tn) * 16, hta = sb + SM_HT + tn * 80;
        PIN(ao); PIN(hta);
        mbar_wait(mb + MB_Y * 8);
        STAMP(10);
        float ca[4] = {0.f, 0.f, 0.f, 0.f}, cb[4] = {0.f, 0.f, 0.f, 0.f};
        {
            uint32_t ya[4], yb[4], yc, yd;
            ldsm4t(ya, y4); ldsm4t(yb, y4 + 16); ldsm2t(yc, yd, y1);
#pragma unroll
            for (int i = 0; i < 4; i++) { ha[i] = badd2(xa[i], ya[i]); hb[i] = badd2(xb[i], yb[i]); }
            ha[4] = badd2(xa[4], yc); hb[4] = badd2(xb[4], yd);
        }
        if (nslot != 5) {
            ha[4] = hb[4] = 0;
            if (cq >= 2) ha[0] = ha[1] = ha[2] = ha[3] = hb[0] = hb[1] = hb[2] = hb[3] = 0;
        }
#pragma unroll
        for (int i = 0; i < 5; i++) { mma_bf16_k8(ca, ha[i], sel[i], ha[i]); mma_bf16_k8(cb, hb[i], sel2[i], hb[i]); }
        if (!(g & 1)) { ca[1] = ca[0]; cb[1] = cb[0]; }
        if (cq == (g >> 1)) {
            asm volatile("red.relaxed.gpu.global.add.v4.f32 [%0], {%1,%2,%3,%4};" :: "l"((char*)g_s.acc + ao), "f"(1.0f), "f"(ca[1]), "f"(ca[2]), "f"(ca[3]) : "memory");
            asm volatile("red.relaxed.gpu.global.add.v4.f32 [%0], {%1,%2,%3,%4};" :: "l"((char*)g_s.acc + ao + 128), "f"(1.0f), "f"(cb[1]), "f"(cb[2]), "f"(cb[3]) : "memory");
        }
        sts128(hta + cq * 16, ha[0], ha[1], ha[2], ha[3]); sts32(hta + 64 + cq * 4, ha[4]);
        sts128(hta + cq * 16 + 640, hb[0], hb[1], hb[2], hb[3]); sts32(hta + 704 + cq * 4, hb[4]);
        STAMP(11);
    }
    const int kq = warp / 5, mt = warp - 5 * kq;
    const int mi = lane >> 3, mr = lane & 7;
    const unsigned tk = (unsigned)tid / 72u, ck = tid - tk * 72;
    uint32_t A[9][4];
    auto loadA = [&]() {
        mbar_wait(mb + MB_W1 * 8);
        const uint32_t aa = sb + (mi & 1) * SM_WU + (8 * (mi >> 1) + mr) * 80 + (144 * 80 * kq + mt * 16);
#pragma unroll
        for (int s = 0; s < 9; s++) ldsm4t(A[s], aa + s * 1280);
    };
    const uint32_t par = (lds32(sb + SM_SC + 28) & 1) ? 0u : 0x40004000u;
    uint32_t pk0 = mapa(sb, 2 * cq), go = (ck / 5u + ck) * 16, co = ((q * 8 * NCL + c) * 6 + cq) * 16;
    PIN(pk0); PIN(go); PIN(co);
    if (warp < 8) {
        const float wsum = ldsf(sb + SM_SC + 24);
        const uint32_t idx = 2047 - (512 * ((tid >> 1) & 3) + 128 * ((tid >> 3) & 3) + 64 * (tid & 1) + 8 * q + warp);
        uint4 s; int n = 0;
        do { s = ld_rlx128(&g_s.acc[256 * q + tid]); } while (__uint_as_float(s.x) != (float)NCL && ++n < SPIN_LIMIT);
        STAMP(16);
        const uint32_t ox = __shfl_xor_sync(~0u, (lane & 1) ? s.z : s.w, 1);
        const uint32_t ms = ln_stats(__uint_as_float((lane & 1) ? ox : s.z), __uint_as_float(s.y));
        const float rs = rcpf(bf_hi(ms));
        const uint32_t rb = pack_bf16(0.f, fmaf(-bf_lo(ms), wsum, __uint_as_float((lane & 1) ? s.w : ox)) * rs);
        const uint32_t key = (((rb ^ (((int)rb >> 31) | 0x80000000u)) >> 16) << 11) | idx;
        sts32(sb + SM_KEY + tid * 4, key);
        __syncwarp();
        const uint32_t rank = rank4<8, 16>(sb + SM_KEY + warp * 128, key);
        if (rank < 8) sts32(sb + SM_CAND + warp * 32 + rank * 4, key);
        sts64(sb + SM_ST + tid * 8, ms, rsplit(rs));
    } else { mbar_wait(mb + MB_Y * 8); loadA(); }
    if (warp < 16) {
        STAMP(17);
        bar_sync(12, 512);
        STAMP(18);
        if (warp < 8) {
            const uint32_t mk = lds32(sb + SM_CAND + (tid >> 2) * 4);
            uint32_t rank = rank4<4, 64>(sb + SM_CAND + cq * 16, mk);
            rank += __shfl_xor_sync(~0u, rank, 1); rank += __shfl_xor_sync(~0u, rank, 2);
            if (rank < 8) {
                const uint32_t pk1 = pk0 + (mapa(sb, 1) - mapa(sb, 0));
                st_async1(pk0 + (SM_RK + q * 32) + rank * 4, mk, pk0 + (SM_MB + MB_KEY * 8));
                st_async1(pk1 + (SM_RK + q * 32) + rank * 4, mk, pk1 + (SM_MB + MB_KEY * 8));
                const uint32_t t = tslot(~mk);
                const uint2 sv = lds64(sb + SM_ST + t * 8);
                const uint4 hv = lds128(sb + SM_HT + t * 80 + cq * 16);
                const uint32_t h4 = lds32(sb + SM_HT + t * 80 + 64 + cq * 4);
                const uint32_t rr = bmul2(sv.y, 0x3C803C80u);
                char* const dp = (char*)g_s.cand + (co + rank * 1440);
                st_rlx128(dp, (norm2(hv.x, sv.x, rr) & 0xBFFFBFFFu) | par, (norm2(hv.y, sv.x, rr) & 0xBFFFBFFFu) | par,
                          (norm2(hv.z, sv.x, rr) & 0xBFFFBFFFu) | par, (norm2(hv.w, sv.x, rr) & 0xBFFFBFFFu) | par);
                asm volatile("st.relaxed.gpu.global.u32 [%0], %1;" :: "l"((char*)g_s.cand + (co + rank * 1440 + 64 - cq * 12)), "r"((norm2(h4, sv.x, rr) & 0xBFFFBFFFu) | par) : "memory");
            }
            __syncwarp();
        }
        {
            const uint2 sa = lds64(sb + SM_ST + tn * 8), sbb = lds64(sb + SM_ST + tn * 8 + 64);
#pragma unroll
            for (int i = 0; i < 5; i++) { ha[i] = badd2(ha[i], norm2(ha[i], sa.x, sa.y)); hb[i] = badd2(hb[i], norm2(hb[i], sbb.x, sbb.y)); }
            const bool hf = (c & 1) && cq == 0;
            const uint32_t o16 = sb + SM_XT + (hf ? 16384 + tn * 16 : tn * 64 + (cq - (c & 1)) * 16), o4 = sb + SM_XT + ((c & 1) ? tn * 64 + 48 : 16384 + tn * 16) + cq * 4;
            sts128(o16, ha[0], ha[1], ha[2], ha[3]); sts32(o4, ha[4]);
            sts128(o16 + (hf ? 128 : 512), hb[0], hb[1], hb[2], hb[3]); sts32(o4 + ((c & 1) ? 512 : 128), hb[4]);
        }
        if (warp >= 8) {
            STAMP(19);
            mbar_wait(mb + MB_KEY * 8);
            STAMP(20);
            const uint32_t mk = lds32(sb + SM_RK - 256 + (tid >> 2) * 4);
            uint32_t rank = rank4<4, 64>(sb + SM_RK + cq * 16, mk);
            rank += __shfl_xor_sync(~0u, rank, 1); rank += __shfl_xor_sync(~0u, rank, 2);
            if (rank < 8) sts64(sb + SM_SEL + rank * 8, mk, ((tid >> 2) - 64) * 1440);
        }
    }
    bar_sync(11, 640);
    STAMP(12);

    const char* gp = (const char*)g_s.cand + (go + lds32(sb + SM_SEL + 4 + (tk & 7) * 8));
    uint4 hv = ld_rlx128(gp);
    if (warp < 8) loadA();
    const bool red = warp < 6;
    const uint32_t ft = red ? (unsigned)tid / 24u : (unsigned)(tid >> 4) & 7u, fj = red ? 24 * q + tid - ft * 24 : d0 / 3 + (lane & 15);
    const uint32_t key = lds32(sb + SM_SEL + ft * 8), k16 = key << 5;
    float sig = bfr(rcpf(1.f + ex2f(__uint_as_float((k16 ^ (~((int)k16 >> 31) | 0x80000000u)) & 0xFFFF0000u) * -1.4426950408889634f)));
    uint32_t ra2 = sb + SM_RED2 + tid * 12 + ft * 16, fo = (ft * 192 + fj) * 16, oo = ((~key & 2047) * D_ + 3 * fj) * 2;
    uint32_t bx = sb + SM_XS + mr * 1168 + mi * 16 + 288 * kq, gd = mapa(sb, kq * (8 / NRED)) + (SM_GU + (q * nslot + mt) * 128) + lane * 4;
    PIN(ra2); PIN(fo); PIN(oo); PIN(bx); PIN(gd);
    asm volatile("" : "+f"(sig));
    {
        if (warp < 18) {
            int n = 0;
            while ((((hv.x ^ par) | (hv.y ^ par) | (hv.z ^ par) | (hv.w ^ par)) & 0x40004000u) && ++n < SPIN_LIMIT) hv = ld_rlx128(gp);
            sts128(sb + SM_XS + tk * 16 + tid * 16, hv.x ^ par, hv.y ^ par, hv.z ^ par, hv.w ^ par);
        }
    }
    bar_sync(14, 672);
    STAMP(13);
    {
        float c0[4] = {0.f, 0.f, 0.f, 0.f}, c1[4] = {0.f, 0.f, 0.f, 0.f}, c2[4] = {0.f, 0.f, 0.f, 0.f};
        uint32_t b[5][4];
#pragma unroll
        for (int s = 0; s < 4; s++) ldsm4(b[s], bx + s * 64);
        asm volatile("ldmatrix.sync.aligned.m8n8.x2.shared.b16 {%0,%1}, [%2];" : "=r"(b[4][0]), "=r"(b[4][1]) : "r"(bx + 256) : "memory");
        mma_bf16(c0, A[0][0], A[0][1], A[0][2], A[0][3], b[0][0], b[0][1]);
        mma_bf16(c1, A[1][0], A[1][1], A[1][2], A[1][3], b[0][2], b[0][3]);
        mma_bf16(c2, A[2][0], A[2][1], A[2][2], A[2][3], b[1][0], b[1][1]);
        mma_bf16(c0, A[3][0], A[3][1], A[3][2], A[3][3], b[1][2], b[1][3]);
        mma_bf16(c1, A[4][0], A[4][1], A[4][2], A[4][3], b[2][0], b[2][1]);
        mma_bf16(c2, A[5][0], A[5][1], A[5][2], A[5][3], b[2][2], b[2][3]);
        mma_bf16(c0, A[6][0], A[6][1], A[6][2], A[6][3], b[3][0], b[3][1]);
        mma_bf16(c1, A[7][0], A[7][1], A[7][2], A[7][3], b[3][2], b[3][3]);
        mma_bf16(c2, A[8][0], A[8][1], A[8][2], A[8][3], b[4][0], b[4][1]);
        sts128f(sb + SM_RED + tid * 16, c0[0] + c1[0] + c2[0], c0[1] + c1[1] + c2[1], c0[2] + c1[2] + c2[2], c0[3] + c1[3] + c2[3]);
    }
    bar_sync(1 + mt, 128);
    STAMP(21);
    if (mt < nslot && kq < NRED) {
        const uint32_t ra = sb + SM_RED + mt * 512 + lane * 16;
        const float4 p0 = lds128f(ra), p1 = lds128f(ra + 2560), p2 = lds128f(ra + 5120), p3 = lds128f(ra + 7680);
        const float g0 = bfr(((p0.x + p1.x) + (p2.x + p3.x)) * 64.f), g1 = bfr(((p0.y + p1.y) + (p2.y + p3.y)) * 64.f);
        const uint32_t sg = pack_bf16(g0 * rcpf(1.f + ex2f(g0 * -1.4426950408889634f)), g1 * rcpf(1.f + ex2f(g1 * -1.4426950408889634f)));
        const uint32_t gu = bmul2(sg, pack_bf16(((p0.z + p1.z) + (p2.z + p3.z)) * 64.f, ((p0.w + p1.w) + (p2.w + p3.w)) * 64.f));
        const uint32_t pstep = mapa(sb, 1) - mapa(sb, 0), gm = mapa(mb + MB_GU * 8, kq * (8 / NRED));
#pragma unroll
        for (int i = 0; i < 8 / NRED; i++) st_async1(gd + i * pstep, gu, gm + i * pstep);
    }
    mbar_wait(mb + MB_W2 * 8);
    {
        const uint32_t aa = sb + (8 * (mi >> 1) + mr) * 144 + (mi & 1) * 16 + (SM_FAR + 2304 * kq + mt * 32);
#pragma unroll
        for (int s = 0; s < 5; s++) ldsm4t(A[s], aa + s * FAR_SZ);
    }
    {
        uint32_t ba = sb + (SM_GU + 256 * kq) + (lane & 15) * 16 + (lane >> 4) * 1024, wa = sb + (SM_RED2 + kq * 2432 + mt * 64) + g * 4 + cq * 608;
        PIN(ba); PIN(wa);
        STAMP(22);
        mbar_wait(mb + MB_GU * 8);
        STAMP(23);
        float c0[4] = {0.f, 0.f, 0.f, 0.f}, c1[4] = {0.f, 0.f, 0.f, 0.f}, c2[4] = {0.f, 0.f, 0.f, 0.f};
        uint32_t b[2][4], b8, b9;
        ldsm4t(b[0], ba); ldsm4t(b[1], ba + 2048); ldsm2t(b8, b9, ba + 4096);
        mma_bf16(c0, A[0][0], A[0][1], A[0][2], A[0][3], b[0][0], b[0][1]);
        mma_bf16(c1, A[1][0], A[1][1], A[1][2], A[1][3], b[0][2], b[0][3]);
        if (nslot == 5) {
            mma_bf16(c2, A[4][0], A[4][1], A[4][2], A[4][3], b8, b9);
            mma_bf16(c0, A[2][0], A[2][1], A[2][2], A[2][3], b[1][0], b[1][1]);
            mma_bf16(c1, A[3][0], A[3][1], A[3][2], A[3][3], b[1][2], b[1][3]);
        }
        stsf(wa, c0[0] + c1[0] + c2[0]); stsf(wa + 304, c0[1] + c1[1] + c2[1]);
        if (mt < 4) { stsf(wa + 32, c0[2] + c1[2] + c2[2]); stsf(wa + 336, c0[3] + c1[3] + c2[3]); }
    }
    if (warp < 10) {
        float v[3], cnt = 3.f;
        if (red) {
            bar_sync(6, 640);
            STAMP(14);
#pragma unroll
            for (int i = 0; i < 3; i++) v[i] = ((ldsf(ra2 + i * 4) + ldsf(ra2 + i * 4 + 2432)) + (ldsf(ra2 + i * 4 + 4864) + ldsf(ra2 + i * 4 + 7296))) * sig;
        } else {
            bar_arrive(6, 640);
            cnt = 0.f;
#pragma unroll
            for (int i = 0; i < 3; i++) {
                const uint32_t cl = 3 * fj + i - d0;
                const bool ok = cl < 8 * nslot && ((~key >> 3) & 7) == q;
                const uint32_t cf = cl - (c & 1) * 8;
                v[i] = ok ? __uint_as_float(lds16(sb + SM_XT + (cf < 32 ? tslot(~key) * 64 + cf * 2 : 16384 + tslot(~key) * 16 + (cl & 7) * 2)) << 16) : 0.f;
                if (ok) cnt += 1.f;
            }
            mbar_wait(mb + MB_OUT * 8);
        }
        if (cnt != 0.f) {
            float x, y, z, w;
            asm volatile("atom.relaxed.gpu.global.add.v4.f32 {%0,%1,%2,%3}, [%4], {%5,%6,%7,%8};" : "=f"(x), "=f"(y), "=f"(z), "=f"(w)
                         : "l"((char*)g_s.fin + fo), "f"(v[0]), "f"(v[1]), "f"(v[2]), "f"(cnt) : "memory");
            if (w + cnt == 3.f * (NCL + 1)) {
                __nv_bfloat16* op = (__nv_bfloat16*)((char*)prm.out + oo);
                op[0] = __float2bfloat16(x + v[0]); op[1] = __float2bfloat16(y + v[1]); op[2] = __float2bfloat16(z + v[2]);
            }
        }
    } else bar_arrive(6, 640);
    STAMP(15);
}

typedef __nv_bfloat16 bf16;
__device__ bf16 f_n[L_ * D_], f_h[L_ * D_];
__device__ float f_k[D_ * L_], f_r[L_], f_gu[8 * F_];
__device__ int f_idx[8];
__device__ __forceinline__ float b2f(bf16 v) { return __bfloat162float(v); }
__global__ void fb_ln(const bf16* in, const bf16* wr, bf16* out) {
    const int t = blockIdx.x * 8 + (threadIdx.x >> 5), lane = threadIdx.x & 31;
    const bf16* r = (in ? in : f_h) + t * D_;
    float s1 = 0.f, s2 = 0.f, s3 = 0.f;
    for (int i = lane; i < D_; i += 32) s1 += b2f(r[i]);
    for (int o = 16; o; o >>= 1) s1 += __shfl_xor_sync(~0u, s1, o);
    for (int i = lane; i < D_; i += 32) { const float d = b2f(r[i]) - s1 / D_; s2 += d * d; }
    for (int o = 16; o; o >>= 1) s2 += __shfl_xor_sync(~0u, s2, o);
    const float m = bfr(s1 / D_), sd = bfr(sqrtf(bfr(bfr(s2 / D_) + 1e-5f)));
    for (int i = lane; i < D_; i += 32) {
        const float v = bfr(bfr(b2f(r[i]) - m) / sd);
        f_n[t * D_ + i] = __float2bfloat16(v);
        if (!in) { s3 += v * b2f(wr[i]); out[t * D_ + i] = __float2bfloat16(b2f(r[i]) + v); }
    }
    for (int o = 16; o; o >>= 1) s3 += __shfl_xor_sync(~0u, s3, o);
    f_r[t] = bfr(s3);
}
__global__ void fb_taps(Params p) {
    const int d = blockIdx.x >> 3, l = (blockIdx.x & 7) * 256 + threadIdx.x;
    const float dt = bfr(expf(bf_lo(p.logdt[d]))), lf = bfr((float)l);
    float k = 0.f;
    for (int n = d * 128; n < d * 128 + 128; n++) {
        float wr, wi, sn, cs;
        cmul(wr, wi, bf_lo(p.prm6[4][n]), bf_lo(p.prm6[5][n]), dt * bf_lo(p.prm6[2][n]), dt * bf_lo(p.prm6[3][n]));
        sincosf(dt * bf_lo(p.prm6[1][n]) * lf, &sn, &cs);
        k += expf(dt * bf_lo(p.prm6[0][n]) * lf) * (wr * cs - wi * sn);
    }
    f_k[l * D_ + d] = k;
}
__global__ void fb_conv(Params p) {
    const int t = blockIdx.x, d = threadIdx.x;
    float y = 0.f;
    for (int l = 0; l <= t; l++) y += f_k[l * D_ + d] * b2f(f_n[(t - l) * D_ + d]);
    f_h[t * D_ + d] = __float2bfloat16(bf_lo(p.x[t * D_ + d]) + bfr(bfr(y) + bfr(b2f(f_n[t * D_ + d]) * bf_lo(p.dskip[d]))));
}
__global__ void fb_top() {
    const int t = blockIdx.x * 256 + threadIdx.x;
    int rank = 0;
    for (int j = 0; j < L_; j++) rank += f_r[j] > f_r[t] || (f_r[j] == f_r[t] && j < t);
    if (rank < 8) f_idx[rank] = t;
}
__global__ void fb_ffn1(const bf16* wg, const bf16* wu) {
    const int f = blockIdx.x * 256 + threadIdx.x, j = blockIdx.y;
    float g = 0.f, u = 0.f;
    for (int i = 0; i < D_; i++) { const float v = b2f(f_n[f_idx[j] * D_ + i]); g += v * b2f(wg[i * F_ + f]); u += v * b2f(wu[i * F_ + f]); }
    g = bfr(g);
    f_gu[j * F_ + f] = bfr(bfr(g / (1.f + expf(-g))) * bfr(u));
}
__global__ void fb_ffn2(const bf16* wd, bf16* out) {
    const int d = threadIdx.x, j = blockIdx.x, t = f_idx[j];
    float y = 0.f;
    for (int f = 0; f < F_; f++) y += f_gu[j * F_ + f] * b2f(wd[f * D_ + d]);
    out[t * D_ + d] = __float2bfloat16(b2f(f_h[t * D_ + d]) + bfr(b2f(f_n[t * D_ + d]) + bfr(bfr(y) * bfr(1.f / (1.f + expf(-f_r[t]))))));
}

typedef CUresult (*EncodeFn)(CUtensorMap*, CUtensorMapDataType, cuuint32_t, void*, const cuuint64_t*, const cuuint64_t*,
                             const cuuint32_t*, const cuuint32_t*, CUtensorMapInterleave, CUtensorMapSwizzle,
                             CUtensorMapL2promotion, CUtensorMapFloatOOBfill);

void make_map(EncodeFn fn, CUtensorMap* tm, const void* p, int cols, int rows, int bc, int br) {
    cuuint64_t dims[2] = {(cuuint64_t)cols, (cuuint64_t)rows};
    cuuint64_t strides[1] = {(cuuint64_t)cols * 2};
    cuuint32_t box[2] = {(cuuint32_t)bc, (cuuint32_t)br};
    cuuint32_t es[2] = {1, 1};
    fn(tm, CU_TENSOR_MAP_DATA_TYPE_BFLOAT16, 2, const_cast<void*>(p), dims, strides, box, es, CU_TENSOR_MAP_INTERLEAVE_NONE,
       CU_TENSOR_MAP_SWIZZLE_NONE, CU_TENSOR_MAP_L2_PROMOTION_L2_128B, CU_TENSOR_MAP_FLOAT_OOB_FILL_NONE);
}

void make_map3(EncodeFn fn, CUtensorMap* tm, const void* p) {
    cuuint64_t dims[5] = {(cuuint64_t)D_, 64, 2, 4, 4};
    cuuint64_t strides[4] = {(cuuint64_t)D_ * 2, (cuuint64_t)D_ * 128, (cuuint64_t)D_ * 1024, (cuuint64_t)D_ * 256};
    cuuint32_t box[5] = {XW, 9, 2, 4, 4};
    cuuint32_t es[5] = {1, 1, 1, 1, 1};
    fn(tm, CU_TENSOR_MAP_DATA_TYPE_BFLOAT16, 5, const_cast<void*>(p), dims, strides, box, es, CU_TENSOR_MAP_INTERLEAVE_NONE,
       CU_TENSOR_MAP_SWIZZLE_NONE, CU_TENSOR_MAP_L2_PROMOTION_NONE, CU_TENSOR_MAP_FLOAT_OOB_FILL_NONE);
}

void make_map5(EncodeFn fn, CUtensorMap* tm, const void* p, int bc) {
    cuuint64_t dims[5] = {(cuuint64_t)D_, 2, 4, 4, 64};
    cuuint64_t strides[4] = {(cuuint64_t)D_ * 128, (cuuint64_t)D_ * 1024, (cuuint64_t)D_ * 256, (cuuint64_t)D_ * 2};
    cuuint32_t box[5] = {(cuuint32_t)bc, 2, 4, 4, 8};
    cuuint32_t es[5] = {1, 1, 1, 1, 1};
    fn(tm, CU_TENSOR_MAP_DATA_TYPE_BFLOAT16, 5, const_cast<void*>(p), dims, strides, box, es, CU_TENSOR_MAP_INTERLEAVE_NONE,
       CU_TENSOR_MAP_SWIZZLE_NONE, CU_TENSOR_MAP_L2_PROMOTION_NONE, CU_TENSOR_MAP_FLOAT_OOB_FILL_NONE);
}

}

extern "C" void kernel_launch(void* const* d_in, const int* in_sizes, int n_in, void* d_out, int out_size) {
    (void)in_sizes; (void)n_in; (void)out_size;
    void* fp = nullptr;
    cudaDriverEntryPointQueryResult qr;
    cudaGetDriverEntryPoint("cuTensorMapEncodeTiled", &fp, cudaEnableDefault, &qr);
    EncodeFn fn = (EncodeFn)fp;
    CUtensorMap tmG, tmU, tmD, tmO, tmX, tmH;
    make_map3(fn, &tmX, d_in[0]);
    make_map(fn, &tmG, d_in[11], F_, D_, 40, 48);
    make_map(fn, &tmU, d_in[12], F_, D_, 40, 48);
    make_map(fn, &tmD, d_in[13], D_, F_, 72, 64);
    make_map5(fn, &tmO, d_out, 32);
    make_map5(fn, &tmH, d_out, 8);
    Params p;
    p.x = (const unsigned short*)d_in[0];
    for (int i = 0; i < 6; i++) p.prm6[i] = (const unsigned short*)d_in[1 + i];
    p.logdt = (const unsigned short*)d_in[7]; p.dskip = (const unsigned short*)d_in[8];
    p.wr = (const unsigned short*)d_in[10];
    p.out = (__nv_bfloat16*)d_out;
    p.zero = 0;
    cudaGetSymbolAddress((void**)&p.gs, g_s);
    cudaFuncSetAttribute(fused_kernel, cudaFuncAttributeMaxDynamicSharedMemorySize, SM_TOTAL);
    static int nclusters = -1;
    if (nclusters < 0) {
        cudaLaunchConfig_t cfg = {};
        cudaLaunchAttribute at;
        at.id = cudaLaunchAttributeClusterDimension; at.val.clusterDim.x = CS; at.val.clusterDim.y = 1; at.val.clusterDim.z = 1;
        cfg.gridDim = dim3(NCTA); cfg.blockDim = dim3(NTHR); cfg.dynamicSmemBytes = SM_TOTAL; cfg.attrs = &at; cfg.numAttrs = 1;
        if (cudaOccupancyMaxActiveClusters(&nclusters, fused_kernel, &cfg) != cudaSuccess) { (void)cudaGetLastError(); nclusters = NCL; }
    }
    if (nclusters >= NCL && !FORCE_FALLBACK) {
        fused_kernel<<<NCTA, NTHR, SM_TOTAL>>>(p, tmG, tmU, tmD, tmO, tmX, tmH);
        return;
    }
    fb_ln<<<L_ / 8, 256>>>((const bf16*)d_in[0], nullptr, nullptr);
    fb_taps<<<D_ * 8, 256>>>(p);
    fb_conv<<<L_, D_>>>(p);
    fb_ln<<<L_ / 8, 256>>>(nullptr, (const bf16*)d_in[10], p.out);
    fb_top<<<L_ / 256, 256>>>();
    fb_ffn1<<<dim3(F_ / 256, 8), 256>>>((const bf16*)d_in[11], (const bf16*)d_in[12]);
    fb_ffn2<<<8, D_>>>((const bf16*)d_in[13], p.out);
}
```

```cpp
#include <cuda_runtime.h>
#include <cuda_bf16.h>
#include <cuda_fp16.h>
#include <cuda.h>
#include <stdint.h>

namespace {

constexpr int L_ = 2048, D_ = 576, F_ = 4608;
constexpr int NCL = 15, CS = 8, NCTA = NCL * CS, NTHR = 768;
#define FORCE_FALLBACK 0
constexpr int XW = 48, NRED = 2;
constexpr int SPIN_LIMIT = 1 << 22;

constexpr int SM_WG   = 0;
constexpr int SM_WU   = 46080;
constexpr int YP = 3392, YS = 656;
constexpr int UP = 3280, US = 656;
constexpr int SM_XT   = 92160;
constexpr int SM_U    = SM_XT + 8 * YP;
constexpr int SM_FAR  = SM_U + 8 * UP;
constexpr int FAR_SZ  = 12416;
constexpr int F_E5 = 0, F_O5 = 1536, F_E3 = 3088, F_O3 = 4624, F_E7 = 6176, F_E2 = F_E7 + 1024, F_E9 = F_E7 + 2048,
              F_H = 3088, F_O7 = F_E7 + F_H, F_O2 = F_E2 + F_H, F_O9 = F_E9 + F_H;
constexpr int SM_P    = SM_FAR + 5 * FAR_SZ;
constexpr int PN_SZ = 584 * 4, SM_PN = SM_P + 64 * 4;
constexpr int P_GS = 48 * 4, P_H7 = 192 * 4, P_HS = 72 * 4;
constexpr int PF_SZ = (192 + 216) * 4, SM_PF = SM_PN + 5 * PN_SZ + 32;
constexpr int SM_MISC = SM_PF + 5 * PF_SZ;
constexpr int SM_ST   = SM_MISC;
constexpr int SM_RK   = SM_ST + 2048;
constexpr int SM_SEL  = SM_RK + 256;
constexpr int SM_KG   = SM_SEL + 64;
constexpr int SM_SC   = SM_KG + 160;
constexpr int SM_DW   = SM_SC + 32;
constexpr int SM_MB   = SM_DW + 160;
constexpr int SM_TOTAL = SM_MB + 128;
constexpr int SM_ROW  = SM_XT - 20736;
constexpr int SM_XTL  = SM_ROW - 576 * XW;
constexpr int SM_RED2 = SM_WG;
constexpr int SM_HT   = SM_P - 512;
constexpr int SM_KEY  = SM_FAR + 10240 + 128;
constexpr int SM_CAND = SM_KEY + 1024;
constexpr int SM_XS   = SM_U;
constexpr int SM_GU   = SM_XS + 9344;
constexpr int SM_RED  = SM_GU + 5632;
static_assert(F_O9 + 1024 <= FAR_SZ && FAR_SZ % 128 == 0, "far overflow");
static_assert(SM_RED + 10240 <= SM_FAR && SM_HT + 20496 <= SM_MISC, "alias overflow");
static_assert(SM_TOTAL <= 232448, "smem overflow");
static_assert(SM_FAR % 128 == 0 && SM_XT % 128 == 0 && SM_XTL % 128 == 0 && SM_P % 16 == 0 && SM_MISC % 16 == 0 && SM_MB % 8 == 0, "align");

enum { MB_X = 0, MB_W1 = 5, MB_W2 = 6, MB_KEY = 7, MB_GU = 8, MB_Y = 9, MB_OUT = 10, MB_T = 11, MB_R = 12 };

struct __align__(128) Scratch {
    unsigned epoch, zcnt, pad[30];
    uint4  st1[L_ * 2];
    float4 acc[L_];
    uint4  cand[64 * NCL * 6];
    float4 fin[8 * 192 + 24];
};
__device__ Scratch g_s;
#define STAMP(i)

__device__ __forceinline__ uint32_t mapa(uint32_t a, uint32_t r) { uint32_t d; asm("mapa.shared::cluster.u32 %0, %1, %2;" : "=r"(d) : "r"(a), "r"(r)); return d; }
__device__ __forceinline__ void mbar_wait(uint32_t mb) {
    asm volatile("{ .reg .pred p, q; .reg .u32 n; mov.u32 n, 0;\n"
                 "W_%=: mbarrier.try_wait.parity.shared::cta.b64 p, [%0], 0; add.u32 n, n, 1; setp.lt.and.u32 q, n, 65536, !p; @q bra W_%=; }" :: "r"(mb) : "memory");
}
__device__ __forceinline__ void arm(uint32_t mb, uint32_t bytes) { asm volatile("mbarrier.arrive.expect_tx.shared::cta.b64 _, [%0], %1;" :: "r"(mb), "r"(bytes) : "memory"); }
__device__ __forceinline__ void bar_sync(int id, int n) { asm volatile("bar.sync %0, %1;" :: "r"(id), "r"(n) : "memory"); }
__device__ __forceinline__ void bar_arrive(int id, int n) { asm volatile("bar.arrive %0, %1;" :: "r"(id), "r"(n) : "memory"); }
__device__ __forceinline__ uint32_t lds16(uint32_t a) { unsigned short v; asm volatile("ld.shared.u16 %0, [%1];" : "=h"(v) : "r"(a) : "memory"); return v; }
__device__ __forceinline__ uint32_t lds32(uint32_t a) { uint32_t v; asm volatile("ld.shared.u32 %0, [%1];" : "=r"(v) : "r"(a) : "memory"); return v; }
__device__ __forceinline__ uint2 lds64(uint32_t a) { uint2 v; asm volatile("ld.shared.v2.u32 {%0,%1}, [%2];" : "=r"(v.x), "=r"(v.y) : "r"(a) : "memory"); return v; }
__device__ __forceinline__ float ldsf(uint32_t a) { float v; asm volatile("ld.shared.f32 %0, [%1];" : "=f"(v) : "r"(a) : "memory"); return v; }
__device__ __forceinline__ uint4 lds128(uint32_t a) { uint4 v; asm volatile("ld.shared.v4.u32 {%0,%1,%2,%3}, [%4];" : "=r"(v.x), "=r"(v.y), "=r"(v.z), "=r"(v.w) : "r"(a) : "memory"); return v; }
__device__ __forceinline__ float4 lds128f(uint32_t a) { float4 v; asm volatile("ld.shared.v4.f32 {%0,%1,%2,%3}, [%4];" : "=f"(v.x), "=f"(v.y), "=f"(v.z), "=f"(v.w) : "r"(a) : "memory"); return v; }
__device__ __forceinline__ void sts16(uint32_t a, uint32_t v) { asm volatile("{ .reg .b16 l, h; mov.b32 {l, h}, %1; st.shared.b16 [%0], l; }" :: "r"(a), "r"(v) : "memory"); }
__device__ __forceinline__ void sts32(uint32_t a, uint32_t v) { asm volatile("st.shared.u32 [%0], %1;" :: "r"(a), "r"(v) : "memory"); }
__device__ __forceinline__ void sts64(uint32_t a, uint32_t x, uint32_t y) { asm volatile("st.shared.v2.u32 [%0], {%1,%2};" :: "r"(a), "r"(x), "r"(y) : "memory"); }
__device__ __forceinline__ void stsf(uint32_t a, float v) { asm volatile("st.shared.f32 [%0], %1;" :: "r"(a), "f"(v) : "memory"); }
__device__ __forceinline__ void sts128(uint32_t a, uint32_t x, uint32_t y, uint32_t z, uint32_t w) { asm volatile("st.shared.v4.u32 [%0], {%1,%2,%3,%4};" :: "r"(a), "r"(x), "r"(y), "r"(z), "r"(w) : "memory"); }
__device__ __forceinline__ void sts128f(uint32_t a, float x, float y, float z, float w) { asm volatile("st.shared.v4.f32 [%0], {%1,%2,%3,%4};" :: "r"(a), "f"(x), "f"(y), "f"(z), "f"(w) : "memory"); }
__device__ __forceinline__ void ldsm4(uint32_t (&r)[4], uint32_t a) { asm volatile("ldmatrix.sync.aligned.m8n8.x4.shared.b16 {%0,%1,%2,%3}, [%4];" : "=r"(r[0]), "=r"(r[1]), "=r"(r[2]), "=r"(r[3]) : "r"(a) : "memory"); }
__device__ __forceinline__ void ldsm4t(uint32_t (&r)[4], uint32_t a) { asm volatile("ldmatrix.sync.aligned.m8n8.x4.trans.shared.b16 {%0,%1,%2,%3}, [%4];" : "=r"(r[0]), "=r"(r[1]), "=r"(r[2]), "=r"(r[3]) : "r"(a) : "memory"); }
__device__ __forceinline__ void ldsm2t(uint32_t& r0, uint32_t& r1, uint32_t a) { asm volatile("ldmatrix.sync.aligned.m8n8.x2.trans.shared.b16 {%0,%1}, [%2];" : "=r"(r0), "=r"(r1) : "r"(a) : "memory"); }
__device__ __forceinline__ void stsm4t(uint32_t a, uint32_t r0, uint32_t r1, uint32_t r2, uint32_t r3) { asm volatile("stmatrix.sync.aligned.m8n8.x4.trans.shared.b16 [%0], {%1,%2,%3,%4};" :: "r"(a), "r"(r0), "r"(r1), "r"(r2), "r"(r3) : "memory"); }
__device__ __forceinline__ void stsm4(uint32_t a, uint32_t r0, uint32_t r1, uint32_t r2, uint32_t r3) { asm volatile("stmatrix.sync.aligned.m8n8.x4.shared.b16 [%0], {%1,%2,%3,%4};" :: "r"(a), "r"(r0), "r"(r1), "r"(r2), "r"(r3) : "memory"); }
__device__ __forceinline__ void stsm2t(uint32_t a, uint32_t r0, uint32_t r1) { asm volatile("stmatrix.sync.aligned.m8n8.x2.trans.shared.b16 [%0], {%1,%2};" :: "r"(a), "r"(r0), "r"(r1) : "memory"); }
__device__ __forceinline__ uint4 ldg128(const void* p) { uint4 v; asm volatile("ld.global.nc.v4.u32 {%0,%1,%2,%3}, [%4];" : "=r"(v.x), "=r"(v.y), "=r"(v.z), "=r"(v.w) : "l"(p)); return v; }
__device__ __forceinline__ uint32_t ldg16(const void* p) { unsigned short v; asm volatile("ld.global.nc.u16 %0, [%1];" : "=h"(v) : "l"(p)); return v; }
__device__ __forceinline__ uint32_t opaque(uint32_t v) { uint32_t r; asm volatile("mov.b32 %0, %1;" : "=r"(r) : "r"(v)); return r; }
__device__ __forceinline__ void mma_f16(float (&d)[4], const uint32_t (&a)[4], uint32_t b0, uint32_t b1) {
    asm volatile("mma.sync.aligned.m16n8k16.row.col.f32.f16.f16.f32 {%0,%1,%2,%3}, {%4,%5,%6,%7}, {%8,%9}, {%0,%1,%2,%3};"
        : "+f"(d[0]), "+f"(d[1]), "+f"(d[2]), "+f"(d[3]) : "r"(a[0]), "r"(a[1]), "r"(a[2]), "r"(a[3]), "r"(b0), "r"(b1));
}
__device__ __forceinline__ void mma_f16_z(float (&d)[4], const uint32_t (&a)[4], uint32_t b0, uint32_t b1) {
    asm volatile("mma.sync.aligned.m16n8k16.row.col.f32.f16.f16.f32 {%0,%1,%2,%3}, {%4,%5,%6,%7}, {%8,%9}, {%10,%10,%10,%10};"
        : "=f"(d[0]), "=f"(d[1]), "=f"(d[2]), "=f"(d[3]) : "r"(a[0]), "r"(a[1]), "r"(a[2]), "r"(a[3]), "r"(b0), "r"(b1), "f"(0.f));
}
__device__ __forceinline__ void mma_bf16(float (&d)[4], uint32_t a0, uint32_t a1, uint32_t a2, uint32_t a3, uint32_t b0, uint32_t b1) {
    asm volatile("mma.sync.aligned.m16n8k16.row.col.f32.bf16.bf16.f32 {%0,%1,%2,%3}, {%4,%5,%6,%7}, {%8,%9}, {%0,%1,%2,%3};"
        : "+f"(d[0]), "+f"(d[1]), "+f"(d[2]), "+f"(d[3]) : "r"(a0), "r"(a1), "r"(a2), "r"(a3), "r"(b0), "r"(b1));
}
__device__ __forceinline__ void mma_bf16_k8(float (&d)[4], uint32_t a0, uint32_t a1, uint32_t b0) {
    asm volatile("mma.sync.aligned.m16n8k8.row.col.f32.bf16.bf16.f32 {%0,%1,%2,%3}, {%4,%5}, {%6}, {%0,%1,%2,%3};"
        : "+f"(d[0]), "+f"(d[1]), "+f"(d[2]), "+f"(d[3]) : "r"(a0), "r"(a1), "r"(b0));
}
__device__ __forceinline__ uint32_t pack_f16(float lo, float hi) { uint32_t r; asm("cvt.rn.f16x2.f32 %0, %1, %2;" : "=r"(r) : "f"(hi), "f"(lo)); return r; }
__device__ __forceinline__ uint32_t pack_bf16(float lo, float hi) { uint32_t r; asm("cvt.rn.bf16x2.f32 %0, %1, %2;" : "=r"(r) : "f"(hi), "f"(lo)); return r; }
__device__ __forceinline__ float bf_lo(uint32_t v) { return __uint_as_float(v << 16); }
__device__ __forceinline__ float bf_hi(uint32_t v) { return __uint_as_float(v & 0xFFFF0000u); }
__device__ __forceinline__ float bfr(float x) { return __uint_as_float(pack_bf16(0.f, x)); }
__device__ __forceinline__ uint32_t badd2(uint32_t a, uint32_t b) { uint32_t r; asm("add.rn.bf16x2 %0, %1, %2;" : "=r"(r) : "r"(a), "r"(b)); return r; }
__device__ __forceinline__ uint32_t bmul2(uint32_t a, uint32_t b) { uint32_t r; asm("mul.rn.bf16x2 %0, %1, %2;" : "=r"(r) : "r"(a), "r"(b)); return r; }
__device__ __forceinline__ uint32_t hadd2(uint32_t a, uint32_t b) { uint32_t r; asm("add.rn.f16x2 %0, %1, %2;" : "=r"(r) : "r"(a), "r"(b)); return r; }
__device__ __forceinline__ uint32_t hmul2(uint32_t a, uint32_t b) { uint32_t r; asm("mul.rn.f16x2 %0, %1, %2;" : "=r"(r) : "r"(a), "r"(b)); return r; }
__device__ __forceinline__ uint32_t hfma2(uint32_t a, uint32_t b, uint32_t c) { uint32_t r; asm("fma.rn.f16x2 %0, %1, %2, %3;" : "=r"(r) : "r"(a), "r"(b), "r"(c)); return r; }
__device__ __forceinline__ uint32_t hneg2(uint32_t a) { uint32_t r; asm("neg.f16x2 %0, %1;" : "=r"(r) : "r"(a)); return r; }
__device__ __forceinline__ float rcpf(float x) { float r; asm("rcp.approx.ftz.f32 %0, %1;" : "=f"(r) : "f"(x)); return r; }
__device__ __forceinline__ float sqrta(float x) { float r; asm("sqrt.approx.ftz.f32 %0, %1;" : "=f"(r) : "f"(x)); return r; }
__device__ __forceinline__ float ex2f(float x) { float r; asm("ex2.approx.ftz.f32 %0, %1;" : "=f"(r) : "f"(x)); return r; }
__device__ __forceinline__ void st_async4(uint32_t a, uint32_t x, uint32_t y, uint32_t z, uint32_t w, uint32_t mb) {
    asm volatile("st.async.shared::cluster.mbarrier::complete_tx::bytes.v4.u32 [%0], {%1,%2,%3,%4}, [%5];" :: "r"(a), "r"(x), "r"(y), "r"(z), "r"(w), "r"(mb) : "memory"); }
__device__ __forceinline__ void st_async1(uint32_t a, uint32_t x, uint32_t mb) {
    asm volatile("st.async.shared::cluster.mbarrier::complete_tx::bytes.u32 [%0], %1, [%2];" :: "r"(a), "r"(x), "r"(mb) : "memory"); }
__device__ __forceinline__ unsigned ld_rlx(const void* p) { unsigned v; asm volatile("ld.relaxed.gpu.global.u32 %0, [%1];" : "=r"(v) : "l"(p) : "memory"); return v; }
__device__ __forceinline__ unsigned ld_acq(const void* p) { unsigned v; asm volatile("ld.acquire.gpu.global.u32 %0, [%1];" : "=r"(v) : "l"(p) : "memory"); return v; }
__device__ __forceinline__ uint2 ld_rlx64(const void* p) { unsigned long long v; asm volatile("ld.relaxed.gpu.global.u64 %0, [%1];" : "=l"(v) : "l"(p) : "memory"); return make_uint2((unsigned)v, (unsigned)(v >> 32)); }
__device__ __forceinline__ void st_rlx128(void* p, uint32_t x, uint32_t y, uint32_t z, uint32_t w) {
    asm volatile("st.relaxed.gpu.global.v2.u64 [%0], {%1,%2};" :: "l"(p), "l"((unsigned long long)x | ((unsigned long long)y << 32)), "l"((unsigned long long)z | ((unsigned long long)w << 32)) : "memory"); }
__device__ __forceinline__ uint4 ld_rlx128(const void* p) { unsigned long long a, b; asm volatile("ld.relaxed.gpu.global.v2.u64 {%0,%1}, [%2];" : "=l"(a), "=l"(b) : "l"(p) : "memory"); return make_uint4((unsigned)a, (unsigned)(a >> 32), (unsigned)b, (unsigned)(b >> 32)); }
__device__ __forceinline__ void tma2d(uint32_t dst, const CUtensorMap* tm, int x, int y, uint32_t mb) {
    asm volatile("cp.async.bulk.tensor.2d.shared::cluster.global.mbarrier::complete_tx::bytes [%0], [%1, {%3, %4}], [%2];"
                 :: "r"(dst), "l"(tm), "r"(mb), "r"(x), "r"(y) : "memory");
}
__device__ __forceinline__ void cmul(float& xr, float& xi, float ar, float ai, float br, float bi) {
    const float r = fmaf(ar, br, -ai * bi), i = fmaf(ar, bi, ai * br); xr = r; xi = i;
}
__device__ __forceinline__ void csq(float& xr, float& xi, float ar, float ai) {
    const float r = fmaf(ar, ar, -ai * ai), i = (ar + ar) * ai; xr = r; xi = i;
}
__device__ __forceinline__ void cexp_s(float& zr, float& zi, float e2, float turns) {
    const float mag = ex2f(e2), r = (turns - rintf(turns)) * 6.283185307179586f;
    zr = mag * __cosf(r); zi = mag * __sinf(r);
}
__device__ __forceinline__ uint32_t ln_stats(float s1, float s2) {
    const float m = s1 * (1.f / D_);
    const float var = fmaxf(fmaf(s2, 1.f / D_, -m * m), 0.f);
    return pack_bf16(m, sqrta(bfr(bfr(var) + 1e-5f)));
}
__device__ __forceinline__ uint32_t rsplit(float rs) { const float h = bfr(rs); return pack_bf16(h, rs - h); }
__device__ __forceinline__ uint32_t norm2(uint32_t v, uint32_t mx, uint32_t hl) {
    uint32_t r;
    asm("{ .reg .b16 m, h, l, x; .reg .b32 m2, h2, l2, d, t; mov.b32 {m, x}, %2; mov.b32 {h, l}, %3; mov.b32 m2, {m, m}; mov.b32 h2, {h, h}; mov.b32 l2, {l, l};\n"
        "sub.rn.bf16x2 d, %1, m2; mul.rn.bf16x2 t, d, l2; fma.rn.bf16x2 %0, d, h2, t; }" : "=r"(r) : "r"(v), "r"(mx), "r"(hl));
    return r;
}
template <int N, int S>
__device__ __forceinline__ uint32_t rank4(uint32_t a, uint32_t key) {
    uint32_t r0 = 0, r1 = 0, r2 = 0, r3 = 0;
#pragma unroll
    for (int i = 0; i < N; i++) {
        const uint4 o = lds128(a + i * S);
        r0 += (key - o.x) >> 31; r1 += (key - o.y) >> 31; r2 += (key - o.z) >> 31; r3 += (key - o.w) >> 31;
    }
    return (r0 + r1) + (r2 + r3);
}
typedef uint32_t H2C;
__device__ __forceinline__ H2C splat(float r, float i) { return pack_f16(r, i); }
__device__ __forceinline__ void hcmul(uint32_t& xr, uint32_t& xi, uint32_t R, uint32_t I, H2C m) {
    asm("{ .reg .b16 a, b; .reg .b32 a2, b2, t; mov.b32 {a, b}, %4; mov.b32 a2, {a, a}; mov.b32 b2, {b, b};\n"
        "mul.rn.f16x2 t, %3, b2; neg.f16x2 t, t; fma.rn.f16x2 %0, %2, a2, t; mul.rn.f16x2 t, %3, a2; fma.rn.f16x2 %1, %2, b2, t; }"
        : "=&r"(xr), "=r"(xi) : "r"(R), "r"(I), "r"(m));
}
__device__ __forceinline__ void expand4(uint32_t are, uint32_t aim, uint32_t R0, uint32_t R1, uint32_t I0, uint32_t I1, H2C m4) {
    uint32_t R2, I2, R3, I3;
    hcmul(R2, I2, R0, I0, m4); hcmul(R3, I3, R1, I1, m4);
    sts128(are, R0, R1, R2, R3);
    sts128(aim, I0, I1, I2, I3);
}
__device__ __forceinline__ void expand8(uint32_t are, uint32_t aim, float sr, float si, float m1r, float m1i, float m2r, float m2i, H2C m4) {
    float r1, i1, r2, i2, r3, i3;
    cmul(r1, i1, sr, si, m1r, m1i); cmul(r2, i2, sr, si, m2r, m2i); cmul(r3, i3, r1, i1, m2r, m2i);
    expand4(are, aim, pack_f16(sr, r1), pack_f16(r2, r3), pack_f16(si, i1), pack_f16(i2, i3), m4);
}
__device__ __forceinline__ void put16(uint32_t a, uint32_t v) { sts16(a, v); sts16(a + 6, v); }

struct Params {
    const unsigned short *logdt, *dskip, *prm6[6], *x, *wr;
    __nv_bfloat16* out;
    Scratch* gs;
    unsigned zero;
};
__device__ __forceinline__ uint32_t tslot(uint32_t t) { return (t & 7) * 32 + ((t >> 4) & 24) + ((t >> 8) & 6) + ((t >> 6) & 1); }
#define CP(x) ((x) | zero)
#define PIN(x) asm volatile("or.b32 %0, %0, %1;" : "+r"(x) : "r"(zero))
__device__ __forceinline__ void wgmma32(float (&d)[4][4], const uint32_t (&a)[4], uint32_t dlo) {
    asm volatile("{ .reg .b64 ds; mov.b64 ds, {%20, %21};\n"
                 "wgmma.mma_async.sync.aligned.m64n32k16.f32.f16.f16 {%0,%1,%2,%3,%4,%5,%6,%7,%8,%9,%10,%11,%12,%13,%14,%15}, {%16,%17,%18,%19}, ds, 1, 1, 1, 0; }"
        : "+f"(d[0][0]), "+f"(d[0][1]), "+f"(d[0][2]), "+f"(d[0][3]), "+f"(d[1][0]), "+f"(d[1][1]), "+f"(d[1][2]), "+f"(d[1][3]),
          "+f"(d[2][0]), "+f"(d[2][1]), "+f"(d[2][2]), "+f"(d[2][3]), "+f"(d[3][0]), "+f"(d[3][1]), "+f"(d[3][2]), "+f"(d[3][3])
        : "r"(a[0]), "r"(a[1]), "r"(a[2]), "r"(a[3]), "r"(dlo), "n"(128 >> 4));
}

__global__ void __cluster_dims__(CS, 1, 1) __launch_bounds__(NTHR, 1)
fused_kernel(const __grid_constant__ Params prm, const __grid_constant__ CUtensorMap tmG, const __grid_constant__ CUtensorMap tmU,
             const __grid_constant__ CUtensorMap tmD, const __grid_constant__ CUtensorMap tmO, const __grid_constant__ CUtensorMap tmX, const __grid_constant__ CUtensorMap tmH)
{
    extern __shared__ __align__(1024) unsigned char smem[];
    const int tid = threadIdx.x, lane = tid & 31, warp = __shfl_sync(~0u, tid >> 5, 0);
    const int c = blockIdx.x >> 3, q = blockIdx.x & 7;
    const int nslot = (c < NCL - 1) ? 5 : 2;
    const int d0 = 40 * c;
    const uint32_t sb = opaque((uint32_t)__cvta_generic_to_shared(smem));
    const uint32_t mb = sb + SM_MB;
    Scratch& g_s = *prm.gs;
    const unsigned& zero = prm.zero;
    STAMP(0);

    if (warp >= 20) {
        unsigned epoch = 0;
        if (warp == 20) {
            if (lane == 0) {
#pragma unroll
                for (int i = 0; i < 13; i++)
                    asm volatile("mbarrier.init.shared::cta.b64 [%0], %1;" :: "r"(mb + i * 8), "r"((i == MB_R || i < 5) ? 2 : i == MB_Y ? 1 + 4 * nslot : 1) : "memory");
                asm volatile("fence.mbarrier_init.release.cluster;" ::: "memory");
                arm(mb + MB_W1 * 8, 92160); arm(mb + MB_W2 * 8, nslot * 9216); arm(mb + MB_KEY * 8, 256); arm(mb + MB_GU * 8, nslot * 1024); arm(mb + MB_T * 8, 576 * XW);
                const int bytes = max(min(18, L_ - 18 * (int)blockIdx.x), 1) * (D_ * 2);
                arm(mb + MB_R * 8, bytes);
            }
            __syncwarp();
        } else if (warp == 22) {
            epoch = ld_rlx(&g_s.epoch);
            if (lane < 18 ? 18 * c + lane < 256 : lane < 31) (lane < 18 ? &g_s.acc[256 * q + 18 * c] : &g_s.fin[13 * (int)blockIdx.x - 18])[lane] = make_float4(0.f, 0.f, 0.f, 0.f);
        } else if (warp == 23 && lane == 0) asm volatile("prefetch.tensormap [%0];" :: "l"(&tmX) : "memory");
        asm volatile("barrier.cluster.arrive.relaxed.aligned;" ::: "memory");
        bar_sync(12, NTHR);
        uint4 wv = make_uint4(0, 0, 0, 0), wv2, wv3;
        if (warp == 22) {
            if (lane == 0) { sts32(sb + SM_SC + 28, epoch); asm volatile("mbarrier.arrive.shared::cta.b64 _, [%0];" :: "r"(mb + MB_R * 8) : "memory"); }
            epoch++;
            asm volatile("fence.acq_rel.gpu;" ::: "memory");
            __syncwarp();
            if (lane == 0) asm volatile("red.relaxed.gpu.global.add.u32 [%0], 1;" :: "l"(&g_s.zcnt) : "memory");
            STAMP(1);
            wv2 = ldg128((const uint4*)prm.wr + lane); wv3 = ldg128((const uint4*)prm.wr + 32 + lane);
            if (lane < 8) wv = ldg128((const uint4*)prm.wr + 64 + lane);
            if (lane < 5) {
                uint4 v = make_uint4(0, 0, 0, 0);
                if (lane < nslot) v = ldg128((const uint4*)(prm.wr + d0) + lane);
                sts128(sb + SM_DW + lane * 16, v.x, v.y, v.z, v.w);
            }
            __syncwarp();
            if (lane < 5) asm volatile("mbarrier.arrive.shared::cta.b64 _, [%0];" :: "r"(mb + (MB_X + lane) * 8) : "memory");
        }
        if (warp == 21) {
            if (lane == 0) { asm volatile("prefetch.tensormap [%0];" :: "l"(&tmG) : "memory"); asm volatile("prefetch.tensormap [%0];" :: "l"(&tmU) : "memory"); asm volatile("prefetch.tensormap [%0];" :: "l"(&tmD) : "memory"); }
            __syncwarp();
            bar_sync(15, 672);
            asm volatile("fence.proxy.async.shared::cta;" ::: "memory");
#pragma unroll 1
            for (int i = 0; i < 24; i++) {
                if (lane == 0) tma2d(sb + SM_WG + i * 3840, i < 12 ? &tmG : &tmU, 320 * c + 8 * nslot * q, 48 * (i < 12 ? i : i - 12), mb + MB_W1 * 8);
            }
            STAMP(1);
            return;
        }
        if (warp == 20) {
            if (lane == 0) {
                asm volatile("cp.async.bulk.shared::cluster.global.mbarrier::complete_tx::bytes [%0], [%1], %2, [%3];"
                             :: "r"(sb + SM_ROW), "l"(prm.x + min(18 * (int)blockIdx.x, L_ - 1) * D_), "r"(max(min(18, L_ - 18 * (int)blockIdx.x), 1) * (D_ * 2)), "r"(mb + MB_R * 8) : "memory");
            }
            __syncwarp();
            mbar_wait(mb + MB_R * 8);
            if (lane == 0) {
                asm volatile("cp.async.bulk.tensor.5d.shared::cluster.global.mbarrier::complete_tx::bytes [%0], [%1, {%3, %4, %5, %5, %5}], [%2];"
                             :: "r"(sb + SM_XTL), "l"(&tmX), "r"(mb + MB_T * 8), "r"(d0 & ~15), "r"(8 * q), "r"(0) : "memory");
            }
            STAMP(6);
        }
        asm volatile("barrier.cluster.wait.aligned;" ::: "memory");
        bar_sync(13, 608);
        asm volatile("fence.proxy.async.shared::cta;" ::: "memory");
        {
            const int idx = lane * 3 + max(warp - 21, 0), sl = nslot - 1 - (idx >> 3), pe = (idx + q + 1) & 7;
            if (sl >= 0) {
                if (pe == q) arm(mb + (MB_X + sl) * 8, 7 * 512);
                else {
                    const uint32_t rb_ = mapa(sb, pe);
                    asm volatile("cp.async.bulk.shared::cluster.shared::cta.mbarrier::complete_tx::bytes [%0], [%1], 512, [%2];"
                                 :: "r"(rb_ + SM_U + 128 + q * UP + sl * US), "r"(sb + SM_XT + 128 + (q & 3) * 16 + pe * YP + sl * YS), "r"(rb_ + SM_MB + (MB_X + sl) * 8) : "memory");
                }
            }
        }
        STAMP(1);
        if (warp == 20 && lane == 0) { asm volatile("prefetch.tensormap [%0];" :: "l"(&tmO) : "memory"); asm volatile("prefetch.tensormap [%0];" :: "l"(&tmH) : "memory"); }
        if (warp == 22) {
            __syncwarp();
            mbar_wait(mb + (MB_X + 1) * 8);
            const uint32_t old = (epoch & 1) ? 0u : 0x40004000u;
#pragma unroll
            for (int t = 0; t < 2; t++)
                if ((lane & 7) < 6) g_s.cand[((q * 8 + 4 * t + (lane >> 3)) * NCL + c) * 6 + (lane & 7)] = make_uint4(old, old, old, old);
            float a[4] = {0.f, 0.f, 0.f, 0.f};
            const uint32_t one = 0x3F803F80u;
            mma_bf16(a, one, one, one, one, wv.x, wv.y);  mma_bf16(a, one, one, one, one, wv.z, wv.w);
            mma_bf16(a, one, one, one, one, wv2.x, wv2.y); mma_bf16(a, one, one, one, one, wv2.z, wv2.w);
            mma_bf16(a, one, one, one, one, wv3.x, wv3.y); mma_bf16(a, one, one, one, one, wv3.z, wv3.w);
            float s = a[0] + a[1];
            s += __shfl_xor_sync(~0u, s, 1); s += __shfl_xor_sync(~0u, s, 2);
            stsf(sb + SM_SC + 24, s);
            __syncwarp();
            if (lane == 0) {
                int n = 0;
                while ((int)(ld_acq(&g_s.zcnt) - epoch * NCTA) < 0 && ++n < SPIN_LIMIT) __nanosleep(200);
                arm(mb + MB_Y * 8, 8 * 512 * nslot);
                if (blockIdx.x == 0) g_s.epoch = epoch;
            }
            STAMP(2);
            return;
        }
        if (warp == 23) {
#pragma unroll 1
            for (int kk = nslot - 1; kk >= 0; kk--) {
                __syncwarp();
                bar_sync(6 + kk, 160);
                if (lane == 0) { asm volatile("fence.proxy.async.shared::cta;" ::: "memory"); tma2d(sb + SM_FAR + kk * FAR_SZ, &tmD, 72 * q, 320 * c + 64 * kk, mb + MB_W2 * 8); }
            }
            return;
        }
        __syncwarp();
        bar_sync(14, 672);
        if (lane == 0) {
            asm volatile("fence.proxy.async.shared::cta;" ::: "memory");
            asm volatile("cp.async.bulk.tensor.5d.global.shared::cta.bulk_group [%0, {%2, %4, %4, %4, %3}], [%1];" :: "l"(&tmH), "r"(sb + SM_XT + 16384), "r"(d0 + ((c & 1) ? 0 : 32)), "r"(8 * q), "r"(0) : "memory");
            asm volatile("cp.async.bulk.tensor.5d.global.shared::cta.bulk_group [%0, {%2, %4, %4, %4, %3}], [%1];" :: "l"(&tmO), "r"(sb + SM_XT), "r"(d0 + (c & 1) * 8), "r"(8 * q), "r"(0) : "memory");
            asm volatile("cp.async.bulk.commit_group;" ::: "memory");
            asm volatile("cp.async.bulk.wait_group 0;" ::: "memory");
            asm volatile("fence.proxy.async.global;" ::: "memory");
            asm volatile("mbarrier.arrive.shared::cta.b64 _, [%0];" :: "r"(mb + MB_OUT * 8) : "memory");
        }
        STAMP(2);
        return;
    }

    const int g = lane >> 2, cq = lane & 3;
    const int k = warp >> 2, wq = warp & 3;
    const int trow = 18 * blockIdx.x + warp;
    const bool rowact = warp < 18 && trow < L_;
    const int dch = min(d0 + 8 * k + q, D_ - 1);
    uint32_t pv[6];
    const uint32_t pofs = opaque((dch * 128 + wq * 32 + lane) * 2);
#pragma unroll
    for (int i = 0; i < 6; i++) pv[i] = ldg16((const char*)prm.prm6[i] + pofs);
    const uint32_t pLdt = ldg16(prm.logdt + dch), pD = ldg16(prm.dskip + dch);
    const int tn = 16 * (warp & 15) + g;
    uint32_t xa[5], xb[5];
    asm volatile("barrier.cluster.arrive.relaxed.aligned;" ::: "memory");
    uint4* const st1p = &g_s.st1[(((trow >> 3) & 7) * 256 + ((trow >> 6) & 31) * 8 + (trow & 7)) * 2 + (lane >> 2)];
    const bool pub = rowact && (lane & 0x1B) == 0;
    if (pub) st_rlx128(st1p, 0, 0, 0, 0);
    {
        const uint32_t za = sb + SM_P + tid * 16;
        sts128(za, 0, 0, 0, 0);
        if (tid < (SM_MISC - SM_P) / 16 - 640) sts128(za + 10240, 0, 0, 0, 0);
        sts128(sb + ((wq & 2) ? SM_U : SM_XT + (q & 3) * 16) + ((tid >> 3) & 7) * ((wq & 2) ? UP : YP) + k * YS + (lane & 7) * 16, 0, 0, 0, 0);
    }
    bar_sync(12, NTHR);
    const uint32_t dep = lds32(sb + SM_P);
#define PV(x) __uint_as_float(__byte_perm(dep, x, 0x5410))
    STAMP(1);
    const uint32_t fb = sb + SM_FAR + k * FAR_SZ;
    const uint32_t pn = sb + SM_PN + k * PN_SZ, pf = sb + SM_PF + k * PF_SZ;
    unsigned epoch;
    {
        const uint32_t kb = fb + wq * 3072;
        const uint32_t kl = kb + lane * 16;
        uint32_t Af[4][4];
        float sr, si, z1r, z1i, z2r, z2i, z4r, z4i, hr, hi_;
        {
            const float dt = bfr(ex2f(PV(pLdt) * 1.4426950408889634f));
            const float e2 = dt * PV(pv[0]) * 1.4426950408889634f, an = dt * PV(pv[1]);
            float ar, ai, br, bi, cr, ci, dr, di;
            { const float m = ex2f(e2 * 8.f); ar = m * __cosf(an * 8.f); ai = m * __sinf(an * 8.f); }
            csq(br, bi, ar, ai); csq(cr, ci, br, bi); csq(dr, di, cr, ci);
            const H2C m4 = splat(cr, ci);
            {
                float r3, i3;
                cmul(r3, i3, ar, ai, br, bi);
                expand4(kl, kl + 1024, pack_f16(1.f, ar), pack_f16(br, r3), pack_f16(0.f, ai), pack_f16(bi, i3), m4);
            }
            expand8(kl + 512, kl + 1536, dr, di, ar, ai, br, bi, m4);
            { const float m = ex2f(e2); z1r = m * __cosf(an); z1i = -m * __sinf(an); }
            cexp_s(hr, hi_, e2 * 128.f, an * (-128.f * 0.15915494309189535f));
            csq(z2r, z2i, z1r, z1i); csq(z4r, z4i, z2r, z2i);
            const uint32_t dep2 = lds32(sb + SM_P + 4);
#define PW(x) __uint_as_float(__byte_perm(dep2, x, 0x5410))
            cmul(sr, si, PW(pv[4]), PW(pv[5]), dt * PW(pv[2]), dt * PW(pv[3]));
            const unsigned E = min(max(__reduce_max_sync(~0u, __float_as_uint(fmaxf(fmaxf(fabsf(sr), fabsf(si)), fabsf(PW(pD)) * (1.f / 8192.f)))) >> 23, 1u), 253u);
            const float sc = __uint_as_float((254u - E) << 23);
            sr *= sc; si *= -sc;
            sts64(sb + SM_KG + warp * 8, E, __reduce_add_sync(~0u, __float2int_rn(sr * 16777216.f)));
            stsf(sb + SM_DW + 96 + k * 4, PW(pD));
        }
        __syncwarp();
#pragma unroll
        for (int ks = 0; ks < 4; ks++) ldsm4t(Af[ks], kb + (lane >> 3) * 512 + (lane & 7) * 16 + ks * 128);
        STAMP(2);
        const uint32_t la = kb + ((lane >> 3) & 1) * 512 + (lane >> 4) * 128 + (lane & 7) * 16;
        uint32_t kp[5][2], b0[4], b1[4], b2[4], b3[4], c0[4], c1[4], c2[4], c3[4];
        auto mm2 = [&](int t, uint32_t (&b0)[4], uint32_t (&b1)[4], uint32_t (&b2)[4], uint32_t (&b3)[4]) {
            float a0[4] = {0.f, 0.f, 0.f, 0.f}, a1[4] = {0.f, 0.f, 0.f, 0.f};
            mma_f16(a0, Af[0], b0[0], b0[1]); mma_f16(a1, Af[0], b2[0], b2[1]); mma_f16(a0, Af[1], b0[2], b0[3]); mma_f16(a1, Af[1], b2[2], b2[3]);
            mma_f16(a0, Af[2], b1[0], b1[1]); mma_f16(a1, Af[2], b3[0], b3[1]); mma_f16(a0, Af[3], b1[2], b1[3]); mma_f16(a1, Af[3], b3[2], b3[3]);
            kp[t][0] = pack_f16(a0[1], a0[0]); kp[t][1] = pack_f16(a0[3], a0[2]); kp[t + 1][0] = pack_f16(a1[1], a1[0]); kp[t + 1][1] = pack_f16(a1[3], a1[2]);
        };
        auto ln1 = [&]() {
        mbar_wait(mb + MB_R * 8);
        epoch = lds32(sb + SM_SC + 28) + 1;
        {
            const uint32_t ra = sb + SM_ROW + warp * (D_ * 2);
            const uint4 r0 = lds128(ra + lane * 16), r1 = lds128(ra + 512 + lane * 16);
            const uint32_t rx[9] = {r0.x, r0.y, r0.z, r0.w, r1.x, r1.y, r1.z, r1.w, lds32(ra + 1024 + lane * 4)};
            float a0 = bf_lo(rx[0]), a1 = bf_hi(rx[0]), c0 = a0 * a0, c1 = a1 * a1;
#pragma unroll
            for (int i = 1; i < 9; i++) { const float l = bf_lo(rx[i]), h = bf_hi(rx[i]); a0 += l; a1 += h; c0 = fmaf(l, l, c0); c1 = fmaf(h, h, c1); }
            a0 += a1; c0 += c1;
            float s1 = ((lane & 1) ? c0 : a0) + __shfl_xor_sync(~0u, (lane & 1) ? a0 : c0, 1);
#pragma unroll
            for (int o = 2; o < 32; o <<= 1) s1 += __shfl_xor_sync(~0u, s1, o);
            const float s2 = __shfl_xor_sync(~0u, s1, 1);
            const uint32_t ms = ln_stats(s1, s2);
            const uint32_t p0 = __byte_perm(ms, epoch | 0x8000u, 0x5410), p1 = rsplit(rcpf(bf_hi(ms)));
            if (pub) st_rlx128(st1p, p0, p1, p0, p1);
        }
        mbar_wait(mb + MB_R * 8);
        STAMP(1);
        };
        const uint4* sp = &g_s.st1[(256 * q + tn) * 2];
        uint2 sa, sc;
        auto poll = [&]() { sa = ld_rlx64(sp); sc = ld_rlx64(sp + 16); };
        auto norm = [&]() {
        STAMP(3);
        if (warp < 16) {
            uint32_t va[5], vc[5];
            poll();
            mbar_wait(mb + MB_T * 8);
            {
                const uint32_t xt = sb + SM_XTL + (c & 1) * 16 + (72 * wq + 18 * k + g) * (2 * XW);
                uint4 a4 = lds128(xt + cq * 16), b4 = lds128(xt + cq * 16 + 18 * XW);
                va[0] = a4.x; va[1] = a4.y; va[2] = a4.z; va[3] = a4.w; va[4] = lds32(xt + 64 + cq * 4);
                vc[0] = b4.x; vc[1] = b4.y; vc[2] = b4.z; vc[3] = b4.w; vc[4] = lds32(xt + (64 + 18 * XW) + cq * 4);
            }
            const int d4 = 2 * (lane >> 3) + (lane & 1), d1_ = lane & 7;
            const uint32_t own = SM_U + 128 + q * (UP - YP), oth = SM_XT + 128 + (q & 3) * 16;
            uint32_t a4 = sb + warp * 32 + d4 * YP + (d4 == q ? own : oth) + ((lane & 7) >> 1) * YS;
            uint32_t a1 = sb + warp * 32 + d1_ * YP + (d1_ == q ? own : oth) + 4 * YS + (lane & 8) * 2;
            PIN(a4); PIN(a1);
            uint32_t tag = __byte_perm(epoch | 0x8000u, 0, 0x1010);
            PIN(tag);
            mbar_wait(mb + MB_T * 8);
            int n = 0;
            while (__byte_perm(sa.x, sc.x, 0x7632) != tag && ++n < SPIN_LIMIT) poll();
            STAMP(4);
#pragma unroll
            for (int i = 0; i < 5; i++) {
                va[i] = norm2(va[i], sa.x, sa.y); va[i] = pack_f16(bf_lo(va[i]), bf_hi(va[i]));
                vc[i] = norm2(vc[i], sc.x, sc.y); vc[i] = pack_f16(bf_lo(vc[i]), bf_hi(vc[i]));
            }
            stsm4t(a4, va[0], va[1], va[2], va[3]); stsm4t(a4 + 16, vc[0], vc[1], vc[2], vc[3]); stsm2t(a1, va[4], vc[4]);
            bar_arrive(13, 608);
            {
            const uint32_t xh = sb + SM_XTL + (c & 1) * 16 + (9 * g + 144 * (warp & 1) + (warp >> 1)) * (2 * XW);
            const uint4 c4 = lds128(xh + cq * 16), d4_ = lds128(xh + cq * 16 + 144 * XW);
            xa[0] = c4.x; xa[1] = c4.y; xa[2] = c4.z; xa[3] = c4.w; xa[4] = lds32(xh + 64 + cq * 4);
            xb[0] = d4_.x; xb[1] = d4_.y; xb[2] = d4_.z; xb[3] = d4_.w; xb[4] = lds32(xh + (64 + 144 * XW) + cq * 4);
            }
        }
        STAMP(5);
        __syncwarp();
        bar_sync(15, 672);
        Af[0][0] |= lds32(sb + SM_P);
        };
        cmul(sr, si, sr, si, z1r, z1i);
        {
            const H2C h4 = splat(z4r, z4i);
            expand8(kl, kl + 512, sr, si, z1r, z1i, z2r, z2i, h4);
            cmul(sr, si, sr, si, hr, hi_);
            expand8(kl + 1024, kl + 1536, sr, si, z1r, z1i, z2r, z2i, h4);
        }
        __syncwarp();
        ldsm4t(b0, la); ldsm4t(b1, la + 256); ldsm4t(b2, la + 1024); ldsm4t(b3, la + 1280);
        cmul(z1r, z1i, z1r, z1i, hr, hi_);
        cmul(sr, si, sr, si, z1r, z1i);
        ln1();
        expand8(kl, kl + 512, sr, si, z2r, z2i, z4r, z4i, splat(hr, hi_));
        csq(z1r, z1i, z1r, z1i);
        cmul(sr, si, sr, si, z1r, z1i);
        csq(z2r, z2i, hr, hi_);
        expand8(kl + 1024, kl + 1536, sr, si, z4r, z4i, hr, hi_, splat(z2r, z2i));
        csq(z1r, z1i, z1r, z1i);
        cmul(sr, si, sr, si, z1r, z1i);
        csq(z4r, z4i, z2r, z2i);
        expand8(kl + 2048, kl + 2560, sr, si, hr, hi_, z2r, z2i, splat(z4r, z4i));
        norm();
        ldsm4t(c0, la); ldsm4t(c2, la + 1024); ldsm4t(c1, la + 256); ldsm4t(c3, la + 1280);
        mm2(0, b0, b1, b2, b3);
        mm2(2, c0, c1, c2, c3);
        ldsm4t(b0, la + 2048); ldsm4t(b1, la + 2304);
#pragma unroll
        for (int t = 0; t < 4; t++) sts64(kb + lane * 8 + 1024 + t * 256, kp[t][0], kp[t][1]);
        {
            float a0[4] = {0.f, 0.f, 0.f, 0.f}, a1[4] = {0.f, 0.f, 0.f, 0.f};
            mma_f16(a0, Af[0], b0[0], b0[1]); mma_f16(a1, Af[1], b0[2], b0[3]); mma_f16(a0, Af[2], b1[0], b1[1]); mma_f16(a1, Af[3], b1[2], b1[3]);
            sts64(kb + lane * 8 + 2048, pack_f16(a0[1] + a1[1], a0[0] + a1[0]), pack_f16(a0[3] + a1[3], a0[2] + a1[2]));
        }
        bar_sync(1 + k, 128);
        const uint4 m01 = lds128(sb + SM_KG + k * 32), m23 = lds128(sb + SM_KG + k * 32 + 16);
        const unsigned Em = max(max(m01.x, m01.z), max(m23.x, m23.z));
        const float f0 = __uint_as_float(max((int)(127 + m01.x - Em), 0) << 23), f1 = __uint_as_float(max((int)(127 + m01.z - Em), 0) << 23),
                    f2 = __uint_as_float(max((int)(127 + m23.x - Em), 0) << 23), f3 = __uint_as_float(max((int)(127 + m23.z - Em), 0) << 23);
        const uint32_t r0 = pack_f16(f0, f0), r1 = pack_f16(f1, f1), r2 = pack_f16(f2, f2), r3 = pack_f16(f3, f3);
        const int tq = (wq + k) & 3;
        const uint32_t ra = fb + lane * 8 + tq * 256 + 1024;
        const uint2 p0 = lds64(ra), p1 = lds64(ra + 3072), p2 = lds64(ra + 6144), p3 = lds64(ra + 9216);
        uint32_t w0 = hadd2(hfma2(p0.x, r0, hmul2(p1.x, r1)), hfma2(p2.x, r2, hmul2(p3.x, r3)));
        uint32_t w1 = hadd2(hfma2(p0.y, r0, hmul2(p1.y, r1)), hfma2(p2.y, r2, hmul2(p3.y, r3)));
        const bool last = lane == 31;
        uint32_t w4 = 0;
        if (tq < 2) {
            const uint32_t rc = fb + lane * 8 + tq * 4 + 2048;
            w4 = hmul2(hadd2(hfma2(lds32(rc), r0, hmul2(lds32(rc + 3072), r1)), hfma2(lds32(rc + 6144), r2, hmul2(lds32(rc + 9216), r3))), 0x18001800u);
        }
        if (tq < 2) {
            const uint32_t ph = pf + (P_H7 + 16 * tq) + (g & 1) * (2 * P_HS) + cq * 64 + (g >> 1) * 4;
            put16(ph, w4 >> 16); put16(ph + 32, w4);
            const uint32_t pa = pn + (4 + 512 * tq) + lane * 8;
            sts16(pa, w0 >> 16); sts32(pa + 4, w0); sts16(pa + 10, w0);
            sts16(pa + 256, w1 >> 16); sts32(pa + 260, w1); sts16(pa + 266, w1);
            if (last) {
                sts32(sb + SM_SC + k * 4, Em * 0x00800080u);
                put16(tq ? pa + 264 : pn,
                      tq ? w1 : pack_f16(((float)(int)m01.y * f0 + (float)(int)m01.w * f1 + (float)(int)m23.y * f2 + (float)(int)m23.w * f3) * (1.f / 16777216.f)
                                         + ldsf(sb + SM_DW + 96 + k * 4) * __uint_as_float((254u - Em) << 23), 0.f));
            }
        } else if (tq == 2) {
            const uint32_t pa = pn + 258 * 4 + (cq & 1) * 16 + (cq >> 1) * 512 + g * 32;
            if (last) { put16(pf, hmul2(w1, 0x18001800u)); w1 = hadd2(w1, hneg2(__byte_perm(w1, 0, 0x1010))); }
            const uint32_t b0 = __byte_perm(w0, 0, 0x1010), b1 = __byte_perm(w1, 0, 0x1010);
            sts16(pa, w0 >> 16); sts32(pa + 4, w0); sts64(pa + 8, b0, b0); sts16(pa + 18, w0);
            sts16(pa + 256, w1 >> 16); sts32(pa + 260, w1); sts64(pa + 264, b1, b1); sts16(pa + 274, w1);
        } else {
            const uint32_t pa = pf + ((g & 1) ? 3 * P_GS : P_GS) + cq * 32 + (g >> 1) * 4;
            const uint32_t pb = pa + ((g & 1) ? 4 - 3 * P_GS : P_GS);
            w0 = hmul2(w0, 0x18001800u); w1 = hmul2(w1, 0x18001800u);
            put16(pa, w0 >> 16); put16(pb, w0); put16(pa + 16, w1 >> 16); put16(pb + 16, w1);
            if (last) put16(pf + P_H7 + P_HS, w1);
        }
        bar_sync(1 + k, 128);
    }
    STAMP(6);

    asm volatile("barrier.cluster.wait.aligned;" ::: "memory");
    mbar_wait(mb + (MB_X + (k < nslot ? k : 0)) * 8);
    STAMP(7);
    if (k < nslot) {
        const int role = (wq + k) & 3;
        const uint32_t ub = sb + SM_U + k * US + 128;
        if (role) {
            const int r = (3 - role) * 32 + lane;
            const uint32_t a1 = ub + (r & 3) * (2 * UP) + (r >> 2) * 16, a0 = a1 + ((r & 3) ? -2 * UP : 6 * UP - 16);
            const uint4 q0 = lds128(a0), q1 = lds128(a0 + UP), q2 = lds128(a1), q3 = lds128(a1 + UP);
            const uint32_t U[16] = {q0.x, q0.y, q0.z, q0.w, q1.x, q1.y, q1.z, q1.w, q2.x, q2.y, q2.z, q2.w, q3.x, q3.y, q3.z, q3.w};
            uint32_t V[14], Q[14], R4[12], T[8];
#pragma unroll
            for (int i = 2; i < 14; i++) { V[i] = __byte_perm(U[i], U[i + 1], 0x5432); Q[i] = hadd2(U[i], V[i]); }
#pragma unroll
            for (int i = 2; i < 12; i++) R4[i] = hadd2(Q[i], Q[i + 1]);
            const uint32_t rb = fb + r * 16;
#pragma unroll
            for (int i = 0; i < 8; i++) T[i] = hadd2(V[5 + i], Q[6 + i]);
            sts128(rb + F_E3, T[0], T[1], T[2], T[3]); sts128(rb + F_O3 + 16, T[4], T[5], T[6], T[7]);
#pragma unroll
            for (int i = 0; i < 8; i++) T[i] = hadd2(R4[3 + i], U[5 + i]);
            sts128(rb + F_O5, T[0], T[1], T[2], T[3]); sts128(rb + F_E5, T[4], T[5], T[6], T[7]);
            if (role != 1) {
#pragma unroll
                for (int i = 0; i < 8; i++) T[i] = hadd2(T[i], hadd2(V[2 + i], V[5 + i]));
                sts128(rb + F_E7, T[0], T[1], T[2], T[3]); sts128(rb + F_O7, T[4], T[5], T[6], T[7]);
#pragma unroll
                for (int i = 0; i < 8; i++) T[i] = hadd2(R4[2 + i], hadd2(R4[4 + i], U[6 + i]));
                sts128(rb + F_O9, T[0], T[1], T[2], T[3]); sts128(rb + F_E9 + 16, T[4], T[5], T[6], T[7]);
                sts128(rb + F_E2, Q[6], Q[7], Q[8], Q[9]); sts128(rb + F_O2, Q[10], Q[11], Q[12], Q[13]);
            }
        } else if (lane < 8) {
            uint32_t v[5];
#pragma unroll
            for (int i = 0; i < 5; i++) { const int t = 6 + lane + i; v[i] = lds16(ub + 23 * 16 + (t < 16 ? (6 + (t >> 3)) * UP : 16) + (t & 7) * 2); }
            const uint32_t s = hadd2(hadd2(hadd2(v[0], v[1]), hadd2(v[2], v[3])), v[4]);
            sts16(fb + F_O5 + 96 * 16 + lane * 2, s);
            sts32(fb + (lane < 4 ? F_O3 : F_E9 - 16) + lane * 4, 0);
        }
        bar_sync(1 + k, 128);
        float acc[4][4];
        uint32_t Q[4][4];
        {
            const int h = role & 1, part = role >> 1;
            const uint32_t po = pf + (g - 2 * cq) * 4;
            float fa[7][4];
#pragma unroll
            for (int a = 0; a < 7; a++) fa[a][0] = fa[a][1] = fa[a][2] = fa[a][3] = 0.f;
            uint32_t B[3][4];
            Q[0][2] = tid & zero;
#pragma unroll 1
            for (int s = 2 * part + 1; s >= 2 * part; s--) {
#pragma unroll
                for (int i = 0; i < 3; i++) { Q[i][0] = lds32(po + s * P_GS + i * 64); Q[i][1] = lds32(po + s * P_GS + (i * 64 + 32)); }
                const uint32_t ba = fb + lane * 16 + ((s & 1) * F_E3 + (part == h ? 0 : F_O5 + h * 16));
#pragma unroll
                for (int i = 0; i < 3; i++) ldsm4t(B[i], ba + i * 512);
#pragma unroll
                for (int i = 0; i < 3; i++) { Q[i][3] = CP(Q[i][0]); if (i) Q[i][2] = CP(Q[i - 1][1]); }
#pragma unroll
                for (int dl = 0; dl < 3; dl++)
#pragma unroll
                    for (int ap = 0; ap < 6 - dl; ap++) mma_f16(fa[ap + 1 + dl], Q[dl], B[ap >> 1][2 * (ap & 1)], B[ap >> 1][2 * (ap & 1) + 1]);
            }
#pragma unroll 1
            for (int s = role; s == 1; s++) {
                ldsm2t(B[0][0], B[0][1], fb + ((lane & 15) == 15 ? F_O5 : F_O3));
#pragma unroll
                for (int dl = 0; dl < 3; dl++) mma_f16(fa[dl], Q[dl], B[0][0], B[0][1]);
            }
#pragma unroll 1
            for (int s = part; s <= 2 * part; s++) {
#pragma unroll
                for (int i = 0; i < 4; i++) { Q[i][0] = lds32(po + s * P_HS + (P_H7 + i * 64)); Q[i][1] = lds32(po + s * P_HS + (P_H7 + i * 64 + 32)); }
                const uint32_t ba = fb + lane * 16 + (F_E7 + s * 1024 + h * F_H);
                ldsm4t(B[0], ba); ldsm4t(B[1], ba + 512);
#pragma unroll
                for (int i = 0; i < 4; i++) { Q[i][3] = CP(Q[i][0]); if (i) Q[i][2] = CP(Q[i - 1][1]); }
#pragma unroll
                for (int dl = 0; dl < 4; dl++) {
#pragma unroll
                    for (int ap = 0; ap < 4 - dl; ap++) mma_f16(fa[ap + 3 + dl], Q[dl], B[ap >> 1][2 * (ap & 1)], B[ap >> 1][2 * (ap & 1) + 1]);
                    if (s == 1) break;
                }
            }
            const uint32_t da = fb + role * 2048 + (lane & 3) * 512 + (((lane >> 2) ^ ((lane & 3) * 2)) << 4);
            bar_sync(1 + k, 128);
            stsm4(da, 0u, 0u, pack_f16(fa[0][0], fa[0][1]), pack_f16(fa[0][2], fa[0][3]));
#pragma unroll
            for (int i = 1; i < 4; i++)
                stsm4(da + i * 128, pack_f16(fa[2 * i - 1][0], fa[2 * i - 1][1]), pack_f16(fa[2 * i - 1][2], fa[2 * i - 1][3]),
                      pack_f16(fa[2 * i][0], fa[2 * i][1]), pack_f16(fa[2 * i][2], fa[2 * i][3]));
            Q[0][0] = (g == 2 * cq) ? 0x6000u : ((g == 2 * cq + 1) ? 0x60000000u : 0u);
            Q[0][1] = Q[0][0] & zero; Q[0][2] = lane & zero; Q[0][3] = CP(Q[0][0]);
            const uint32_t ra = fb + (lane >> 3) * 2048 + wq * 512 + (((lane & 7) ^ (wq * 2)) << 4);
            bar_sync(1 + k, 128);
#pragma unroll
            for (int i = 0; i < 4; i++) {
                ldsm4(B[0], ra + i * 128);
                mma_f16_z(acc[i], Q[0], hadd2(B[0][0], B[0][2]), hadd2(B[0][1], B[0][3]));
            }
        }
        bar_arrive(6 + k, 160);
        STAMP(8);
        const uint32_t inv = lds32(sb + SM_SC + k * 4);
        uint32_t yd = mapa(sb, 2 * wq) + (SM_XT + 128 + q * YP + k * YS + (k >> 2) * (q >> 1) * 16) + lane * 16;
        PIN(yd);
        {
            uint32_t pp = pn + (16 * (wq - 3) + g - 2 * cq) * 4;
            uint32_t dlo = (((ub + 6 * UP) & 0x3FFFF) >> 4) | ((UP >> 4) << 16);
            uint32_t R[4][4];
            auto loadQ = [&](uint32_t (&X)[4][4], uint32_t prev) {
#pragma unroll
                for (int i = 0; i < 4; i++) { X[i][0] = lds32(pp + i * 64); X[i][1] = lds32(pp + i * 64 + 32); }
                X[0][2] = CP(prev);
#pragma unroll
                for (int i = 0; i < 4; i++) { X[i][3] = CP(X[i][0]); if (i) X[i][2] = CP(X[i - 1][1]); }
                pp += 256;
            };
            auto issue = [&](uint32_t (&X)[4][4]) {
                asm volatile("wgmma.fence.sync.aligned;" ::: "memory");
#pragma unroll
                for (int i = 0; i < 4; i++) wgmma32(acc, X[i], dlo - i * (2 * UP >> 4));
                asm volatile("wgmma.commit_group.sync.aligned;" ::: "memory");
                dlo -= 1;
            };
            loadQ(Q, 0);
#pragma unroll 1
            for (int dl = 0; dl < 4; dl++) {
                issue(Q);
                asm volatile("wgmma.wait_group.sync.aligned 1;" ::: "memory");
                loadQ(R, Q[3][1]);
                issue(R);
                asm volatile("wgmma.wait_group.sync.aligned 1;" ::: "memory");
                loadQ(Q, R[3][1]);
            }
            issue(Q);
            asm volatile("wgmma.wait_group.sync.aligned 0;" ::: "memory");
        }
        const uint32_t pstep = mapa(sb, 1) - mapa(sb, 0), ym = mapa(mb + MB_Y * 8, 2 * wq);
#pragma unroll
        for (int e = 0; e < 2; e++)
            st_async4(yd + e * pstep, bmul2(pack_bf16(acc[0][2 * e], acc[0][2 * e + 1]), inv), bmul2(pack_bf16(acc[1][2 * e], acc[1][2 * e + 1]), inv),
                      bmul2(pack_bf16(acc[2][2 * e], acc[2][2 * e + 1]), inv), bmul2(pack_bf16(acc[3][2 * e], acc[3][2 * e + 1]), inv), ym + e * pstep);
        if (lane == 0) asm volatile("mbarrier.arrive.shared::cta.b64 _, [%0];" :: "r"(mb + MB_Y * 8) : "memory");
    }
    STAMP(9);
    uint32_t ha[5], hb[5];
    if (warp < 16) {
        const uint4 wk = lds128(sb + SM_DW + cq * 16);
        uint32_t sel[5] = {wk.x, wk.y, wk.z, wk.w, lds32(sb + SM_DW + 64 + cq * 4)}, sel2[5];
#pragma unroll
        for (int i = 0; i < 5; i++) {
            if (!(g & 1)) sel[i] = 0x3F803F80u;
            sel2[i] = sel[i]; PIN(sel2[i]);
        }
        const uint32_t y4 = sb + SM_XT + 128 + warp * 32 + (2 * (lane >> 3) + (lane & 1)) * YP + ((lane & 7) >> 1) * YS;
        const uint32_t y1 = sb + SM_XT + 128 + warp * 32 + (lane & 7) * YP + 4 * YS + (lane & 8) * 2 + (lane & 6) * 8;
        uint32_t ao = (256 * q + tn) * 16, hta = sb + SM_HT + tn * 80;
        PIN(ao); PIN(hta);
        mbar_wait(mb + MB_Y * 8);
        STAMP(10);
        float ca[4] = {0.f, 0.f, 0.f, 0.f}, cb[4] = {0.f, 0.f, 0.f, 0.f};
        {
            uint32_t ya[4], yb[4], yc, yd;
            ldsm4t(ya, y4); ldsm4t(yb, y4 + 16); ldsm2t(yc, yd, y1);
#pragma unroll
            for (int i = 0; i < 4; i++) { ha[i] = badd2(xa[i], ya[i]); hb[i] = badd2(xb[i], yb[i]); }
            ha[4] = badd2(xa[4], yc); hb[4] = badd2(xb[4], yd);
        }
        if (nslot != 5) {
            ha[4] = hb[4] = 0;
            if (cq >= 2) ha[0] = ha[1] = ha[2] = ha[3] = hb[0] = hb[1] = hb[2] = hb[3] = 0;
        }
#pragma unroll
        for (int i = 0; i < 5; i++) { mma_bf16_k8(ca, ha[i], sel[i], ha[i]); mma_bf16_k8(cb, hb[i], sel2[i], hb[i]); }
        if (!(g & 1)) { ca[1] = ca[0]; cb[1] = cb[0]; }
        if (cq == (g >> 1)) {
            asm volatile("red.relaxed.gpu.global.add.v4.f32 [%0], {%1,%2,%3,%4};" :: "l"((char*)g_s.acc + ao), "f"(1.0f), "f"(ca[1]), "f"(ca[2]), "f"(ca[3]) : "memory");
            asm volatile("red.relaxed.gpu.global.add.v4.f32 [%0], {%1,%2,%3,%4};" :: "l"((char*)g_s.acc + ao + 128), "f"(1.0f), "f"(cb[1]), "f"(cb[2]), "f"(cb[3]) : "memory");
        }
        sts128(hta + cq * 16, ha[0], ha[1], ha[2], ha[3]); sts32(hta + 64 + cq * 4, ha[4]);
        sts128(hta + cq * 16 + 640, hb[0], hb[1], hb[2], hb[3]); sts32(hta + 704 + cq * 4, hb[4]);
        STAMP(11);
    }
    const int kq = warp / 5, mt = warp - 5 * kq;
    const int mi = lane >> 3, mr = lane & 7;
    const unsigned tk = (unsigned)tid / 72u, ck = tid - tk * 72;
    uint32_t A[9][4];
    auto loadA = [&]() {
        mbar_wait(mb + MB_W1 * 8);
        const uint32_t aa = sb + (mi & 1) * SM_WU + (8 * (mi >> 1) + mr) * 80 + (144 * 80 * kq + mt * 16);
#pragma unroll
        for (int s = 0; s < 9; s++) ldsm4t(A[s], aa + s * 1280);
    };
    const uint32_t par = (lds32(sb + SM_SC + 28) & 1) ? 0u : 0x40004000u;
    uint32_t pk0 = mapa(sb, 2 * cq), go = (ck / 5u + ck) * 16, co = ((q * 8 * NCL + c) * 6 + cq) * 16;
    PIN(pk0); PIN(go); PIN(co);
    if (warp < 8) {
        const float wsum = ldsf(sb + SM_SC + 24);
        const uint32_t idx = 2047 - (512 * ((tid >> 1) & 3) + 128 * ((tid >> 3) & 3) + 64 * (tid & 1) + 8 * q + warp);
        uint4 s; int n = 0;
        do { s = ld_rlx128(&g_s.acc[256 * q + tid]); } while (__uint_as_float(s.x) != (float)NCL && ++n < SPIN_LIMIT);
        STAMP(16);
        const uint32_t ox = __shfl_xor_sync(~0u, (lane & 1) ? s.z : s.w, 1);
        const uint32_t ms = ln_stats(__uint_as_float((lane & 1) ? ox : s.z), __uint_as_float(s.y));
        const float rs = rcpf(bf_hi(ms));
        const uint32_t rb = pack_bf16(0.f, fmaf(-bf_lo(ms), wsum, __uint_as_float((lane & 1) ? s.w : ox)) * rs);
        const uint32_t key = (((rb ^ (((int)rb >> 31) | 0x80000000u)) >> 16) << 11) | idx;
        sts32(sb + SM_KEY + tid * 4, key);
        __syncwarp();
        const uint32_t rank = rank4<8, 16>(sb + SM_KEY + warp * 128, key);
        asm volatile("{ .reg .pred p; setp.lt.u32 p, %0, 8; @p st.shared.u32 [%1], %2; }" :: "r"(rank), "r"(sb + SM_CAND + warp * 32 + rank * 4), "r"(key) : "memory");
        sts64(sb + SM_ST + tid * 8, ms, rsplit(rs));
    } else { mbar_wait(mb + MB_Y * 8); loadA(); }
    if (warp < 16) {
        STAMP(17);
        bar_sync(12, 512);
        STAMP(18);
        if (warp < 8) {
            const uint32_t mk = lds32(sb + SM_CAND + (tid >> 2) * 4);
            uint32_t rank = rank4<4, 64>(sb + SM_CAND + cq * 16, mk);
            rank += __shfl_xor_sync(~0u, rank, 1); rank += __shfl_xor_sync(~0u, rank, 2);
            if (rank < 8) {
                const uint32_t pk1 = pk0 + (mapa(sb, 1) - mapa(sb, 0));
                st_async1(pk0 + (SM_RK + q * 32) + rank * 4, mk, pk0 + (SM_MB + MB_KEY * 8));
                st_async1(pk1 + (SM_RK + q * 32) + rank * 4, mk, pk1 + (SM_MB + MB_KEY * 8));
                const uint32_t t = tslot(~mk | ((pk1 + rank * 4) & zero));
                const uint2 sv = lds64(sb + SM_ST + t * 8);
                const uint4 hv = lds128(sb + SM_HT + t * 80 + cq * 16);
                const uint32_t h4 = lds32(sb + SM_HT + t * 80 + 64 + cq * 4);
                const uint32_t rr = bmul2(sv.y, 0x3C803C80u);
                char* const dp = (char*)g_s.cand + (co + rank * 1440);
                st_rlx128(dp, (norm2(hv.x, sv.x, rr) & 0xBFFFBFFFu) | par, (norm2(hv.y, sv.x, rr) & 0xBFFFBFFFu) | par,
                          (norm2(hv.z, sv.x, rr) & 0xBFFFBFFFu) | par, (norm2(hv.w, sv.x, rr) & 0xBFFFBFFFu) | par);
                asm volatile("st.relaxed.gpu.global.u32 [%0], %1;" :: "l"((char*)g_s.cand + (co + rank * 1440 + 64 - cq * 12)), "r"((norm2(h4, sv.x, rr) & 0xBFFFBFFFu) | par) : "memory");
            }
            __syncwarp();
        }
        {
            const uint2 sa = lds64(sb + SM_ST + tn * 8), sbb = lds64(sb + SM_ST + tn * 8 + 64);
#pragma unroll
            for (int i = 0; i < 5; i++) { ha[i] = badd2(ha[i], norm2(ha[i], sa.x, sa.y)); hb[i] = badd2(hb[i], norm2(hb[i], sbb.x, sbb.y)); }
            const bool hf = (c & 1) && cq == 0;
            const uint32_t o16 = sb + SM_XT + (hf ? 16384 + tn * 16 : tn * 64 + (cq - (c & 1)) * 16), o4 = sb + SM_XT + ((c & 1) ? tn * 64 + 48 : 16384 + tn * 16) + cq * 4;
            sts128(o16, ha[0], ha[1], ha[2], ha[3]); sts32(o4, ha[4]);
            sts128(o16 + (hf ? 128 : 512), hb[0], hb[1], hb[2], hb[3]); sts32(o4 + ((c & 1) ? 512 : 128), hb[4]);
        }
        if (warp >= 8) {
            STAMP(19);
            mbar_wait(mb + MB_KEY * 8);
            STAMP(20);
            const uint32_t mk = lds32(sb + SM_RK - 256 + (tid >> 2) * 4);
            uint32_t rank = rank4<4, 64>(sb + SM_RK + cq * 16, mk);
            rank += __shfl_xor_sync(~0u, rank, 1); rank += __shfl_xor_sync(~0u, rank, 2);
            if (rank < 8) sts64(sb + SM_SEL + rank * 8, mk, ((tid >> 2) - 64) * 1440);
        }
    }
    bar_sync(11, 640);
    STAMP(12);

    const char* gp = (const char*)g_s.cand + (go + lds32(sb + SM_SEL + 4 + (tk & 7) * 8));
    uint4 hv = ld_rlx128(gp);
    if (warp < 8) loadA();
    const bool red = warp < 6;
    const uint32_t ft = red ? (unsigned)tid / 24u : (unsigned)(tid >> 4) & 7u, fj = red ? 24 * q + tid - ft * 24 : d0 / 3 + (lane & 15);
    const uint32_t key = lds32(sb + SM_SEL + ft * 8), k16 = key << 5;
    float sig = bfr(rcpf(1.f + ex2f(__uint_as_float((k16 ^ (~((int)k16 >> 31) | 0x80000000u)) & 0xFFFF0000u) * -1.4426950408889634f)));
    uint32_t ra2 = sb + SM_RED2 + tid * 12 + ft * 16, fo = (ft * 192 + fj) * 16, oo = ((~key & 2047) * D_ + 3 * fj) * 2;
    uint32_t bx = sb + SM_XS + mr * 1168 + mi * 16 + 288 * kq, gd = mapa(sb, kq * (8 / NRED)) + (SM_GU + (q * nslot + mt) * 128) + lane * 4;
    PIN(ra2); PIN(fo); PIN(oo); PIN(bx); PIN(gd);
    asm volatile("" : "+f"(sig));
    {
        if (warp < 18) {
            int n = 0;
            while (true) {
                sts128(sb + SM_XS + tk * 16 + tid * 16, hv.x ^ par, hv.y ^ par, hv.z ^ par, hv.w ^ par);
                if (!__any_sync(~0u, ((hv.x ^ par) | (hv.y ^ par) | (hv.z ^ par) | (hv.w ^ par)) & 0x40004000u) || ++n >= SPIN_LIMIT) break;
                hv = ld_rlx128(gp);
            }
        }
    }
    bar_sync(14, 672);
    STAMP(13);
    {
        float c0[4] = {0.f, 0.f, 0.f, 0.f}, c1[4] = {0.f, 0.f, 0.f, 0.f}, c2[4] = {0.f, 0.f, 0.f, 0.f};
        uint32_t b[5][4];
#pragma unroll
        for (int s = 0; s < 4; s++) ldsm4(b[s], bx + s * 64);
        asm volatile("ldmatrix.sync.aligned.m8n8.x2.shared.b16 {%0,%1}, [%2];" : "=r"(b[4][0]), "=r"(b[4][1]) : "r"(bx + 256) : "memory");
        mma_bf16(c0, A[0][0], A[0][1], A[0][2], A[0][3], b[0][0], b[0][1]);
        mma_bf16(c1, A[1][0], A[1][1], A[1][2], A[1][3], b[0][2], b[0][3]);
        mma_bf16(c2, A[2][0], A[2][1], A[2][2], A[2][3], b[1][0], b[1][1]);
        mma_bf16(c0, A[3][0], A[3][1], A[3][2], A[3][3], b[1][2], b[1][3]);
        mma_bf16(c1, A[4][0], A[4][1], A[4][2], A[4][3], b[2][0], b[2][1]);
        mma_bf16(c2, A[5][0], A[5][1], A[5][2], A[5][3], b[2][2], b[2][3]);
        mma_bf16(c0, A[6][0], A[6][1], A[6][2], A[6][3], b[3][0], b[3][1]);
        mma_bf16(c1, A[7][0], A[7][1], A[7][2], A[7][3], b[3][2], b[3][3]);
        mma_bf16(c2, A[8][0], A[8][1], A[8][2], A[8][3], b[4][0], b[4][1]);
        sts128f(sb + SM_RED + tid * 16, c0[0] + c1[0] + c2[0], c0[1] + c1[1] + c2[1], c0[2] + c1[2] + c2[2], c0[3] + c1[3] + c2[3]);
    }
    bar_sync(1 + mt, 128);
    STAMP(21);
    if (mt < nslot && kq < NRED) {
        const uint32_t ra = sb + SM_RED + mt * 512 + lane * 16;
        const float4 p0 = lds128f(ra), p1 = lds128f(ra + 2560), p2 = lds128f(ra + 5120), p3 = lds128f(ra + 7680);
        const float g0 = bfr(((p0.x + p1.x) + (p2.x + p3.x)) * 64.f), g1 = bfr(((p0.y + p1.y) + (p2.y + p3.y)) * 64.f);
        const uint32_t sg = pack_bf16(g0 * rcpf(1.f + ex2f(g0 * -1.4426950408889634f)), g1 * rcpf(1.f + ex2f(g1 * -1.4426950408889634f)));
        const uint32_t gu = bmul2(sg, pack_bf16(((p0.z + p1.z) + (p2.z + p3.z)) * 64.f, ((p0.w + p1.w) + (p2.w + p3.w)) * 64.f));
        const uint32_t pstep = mapa(sb, 1) - mapa(sb, 0), gm = mapa(mb + MB_GU * 8, kq * (8 / NRED));
#pragma unroll
        for (int i = 0; i < 8 / NRED; i++) st_async1(gd + i * pstep, gu, gm + i * pstep);
    }
    mbar_wait(mb + MB_W2 * 8);
    {
        const uint32_t aa = sb + (8 * (mi >> 1) + mr) * 144 + (mi & 1) * 16 + (SM_FAR + 2304 * kq + mt * 32);
#pragma unroll
        for (int s = 0; s < 5; s++) ldsm4t(A[s], aa + s * FAR_SZ);
    }
    {
        uint32_t ba = sb + (SM_GU + 256 * kq) + (lane & 15) * 16 + (lane >> 4) * 1024, wa = sb + (SM_RED2 + kq * 2432 + mt * 64) + g * 4 + cq * 608;
        PIN(ba); PIN(wa);
        STAMP(22);
        mbar_wait(mb + MB_GU * 8);
        STAMP(23);
        float c0[4] = {0.f, 0.f, 0.f, 0.f}, c1[4] = {0.f, 0.f, 0.f, 0.f}, c2[4] = {0.f, 0.f, 0.f, 0.f};
        uint32_t b[2][4], b8, b9;
        ldsm4t(b[0], ba); ldsm4t(b[1], ba + 2048); ldsm2t(b8, b9, ba + 4096);
        mma_bf16(c0, A[0][0], A[0][1], A[0][2], A[0][3], b[0][0], b[0][1]);
        mma_bf16(c1, A[1][0], A[1][1], A[1][2], A[1][3], b[0][2], b[0][3]);
        if (nslot == 5) {
            mma_bf16(c2, A[4][0], A[4][1], A[4][2], A[4][3], b8, b9);
            mma_bf16(c0, A[2][0], A[2][1], A[2][2], A[2][3], b[1][0], b[1][1]);
            mma_bf16(c1, A[3][0], A[3][1], A[3][2], A[3][3], b[1][2], b[1][3]);
        }
        stsf(wa, c0[0] + c1[0] + c2[0]); stsf(wa + 304, c0[1] + c1[1] + c2[1]);
        if (mt < 4) { stsf(wa + 32, c0[2] + c1[2] + c2[2]); stsf(wa + 336, c0[3] + c1[3] + c2[3]); }
    }
    if (warp < 10) {
        float v[3], cnt = 3.f;
        if (red) {
            bar_sync(6, 640);
            STAMP(14);
#pragma unroll
            for (int i = 0; i < 3; i++) v[i] = ((ldsf(ra2 + i * 4) + ldsf(ra2 + i * 4 + 2432)) + (ldsf(ra2 + i * 4 + 4864) + ldsf(ra2 + i * 4 + 7296))) * sig;
        } else {
            bar_arrive(6, 640);
            cnt = 0.f;
#pragma unroll
            for (int i = 0; i < 3; i++) {
                const uint32_t cl = 3 * fj + i - d0;
                const bool ok = cl < 8 * nslot && ((~key >> 3) & 7) == q;
                const uint32_t cf = cl - (c & 1) * 8;
                v[i] = ok ? __uint_as_float(lds16(sb + SM_XT + (cf < 32 ? tslot(~key) * 64 + cf * 2 : 16384 + tslot(~key) * 16 + (cl & 7) * 2)) << 16) : 0.f;
                if (ok) cnt += 1.f;
            }
            mbar_wait(mb + MB_OUT * 8);
        }
        if (cnt != 0.f) {
            float x, y, z, w;
            asm volatile("atom.relaxed.gpu.global.add.v4.f32 {%0,%1,%2,%3}, [%4], {%5,%6,%7,%8};" : "=f"(x), "=f"(y), "=f"(z), "=f"(w)
                         : "l"((char*)g_s.fin + fo), "f"(v[0]), "f"(v[1]), "f"(v[2]), "f"(cnt) : "memory");
            if (w + cnt == 3.f * (NCL + 1)) {
                __nv_bfloat16* op = (__nv_bfloat16*)((char*)prm.out + oo);
                op[0] = __float2bfloat16(x + v[0]); op[1] = __float2bfloat16(y + v[1]); op[2] = __float2bfloat16(z + v[2]);
            }
        }
    } else bar_arrive(6, 640);
    STAMP(15);
}

typedef __nv_bfloat16 bf16;
__device__ bf16 f_n[L_ * D_], f_h[L_ * D_];
__device__ float f_k[D_ * L_], f_r[L_], f_gu[8 * F_];
__device__ int f_idx[8];
__device__ __forceinline__ float b2f(bf16 v) { return __bfloat162float(v); }
__global__ void fb_ln(const bf16* in, const bf16* wr, bf16* out) {
    const int t = blockIdx.x * 8 + (threadIdx.x >> 5), lane = threadIdx.x & 31;
    const bf16* r = (in ? in : f_h) + t * D_;
    float s1 = 0.f, s2 = 0.f, s3 = 0.f;
    for (int i = lane; i < D_; i += 32) s1 += b2f(r[i]);
    for (int o = 16; o; o >>= 1) s1 += __shfl_xor_sync(~0u, s1, o);
    for (int i = lane; i < D_; i += 32) { const float d = b2f(r[i]) - s1 / D_; s2 += d * d; }
    for (int o = 16; o; o >>= 1) s2 += __shfl_xor_sync(~0u, s2, o);
    const float m = bfr(s1 / D_), sd = bfr(sqrtf(bfr(bfr(s2 / D_) + 1e-5f)));
    for (int i = lane; i < D_; i += 32) {
        const float v = bfr(bfr(b2f(r[i]) - m) / sd);
        f_n[t * D_ + i] = __float2bfloat16(v);
        if (!in) { s3 += v * b2f(wr[i]); out[t * D_ + i] = __float2bfloat16(b2f(r[i]) + v); }
    }
    for (int o = 16; o; o >>= 1) s3 += __shfl_xor_sync(~0u, s3, o);
    f_r[t] = bfr(s3);
}
__global__ void fb_taps(Params p) {
    const int d = blockIdx.x >> 3, l = (blockIdx.x & 7) * 256 + threadIdx.x;
    const float dt = bfr(expf(bf_lo(p.logdt[d]))), lf = bfr((float)l);
    float k = 0.f;
    for (int n = d * 128; n < d * 128 + 128; n++) {
        float wr, wi, sn, cs;
        cmul(wr, wi, bf_lo(p.prm6[4][n]), bf_lo(p.prm6[5][n]), dt * bf_lo(p.prm6[2][n]), dt * bf_lo(p.prm6[3][n]));
        sincosf(dt * bf_lo(p.prm6[1][n]) * lf, &sn, &cs);
        k += expf(dt * bf_lo(p.prm6[0][n]) * lf) * (wr * cs - wi * sn);
    }
    f_k[l * D_ + d] = k;
}
__global__ void fb_conv(Params p) {
    const int t = blockIdx.x, d = threadIdx.x;
    float y = 0.f;
    for (int l = 0; l <= t; l++) y += f_k[l * D_ + d] * b2f(f_n[(t - l) * D_ + d]);
    f_h[t * D_ + d] = __float2bfloat16(bf_lo(p.x[t * D_ + d]) + bfr(bfr(y) + bfr(b2f(f_n[t * D_ + d]) * bf_lo(p.dskip[d]))));
}
__global__ void fb_top() {
    const int t = blockIdx.x * 256 + threadIdx.x;
    int rank = 0;
    for (int j = 0; j < L_; j++) rank += f_r[j] > f_r[t] || (f_r[j] == f_r[t] && j < t);
    if (rank < 8) f_idx[rank] = t;
}
__global__ void fb_ffn1(const bf16* wg, const bf16* wu) {
    const int f = blockIdx.x * 256 + threadIdx.x, j = blockIdx.y;
    float g = 0.f, u = 0.f;
    for (int i = 0; i < D_; i++) { const float v = b2f(f_n[f_idx[j] * D_ + i]); g += v * b2f(wg[i * F_ + f]); u += v * b2f(wu[i * F_ + f]); }
    g = bfr(g);
    f_gu[j * F_ + f] = bfr(bfr(g / (1.f + expf(-g))) * bfr(u));
}
__global__ void fb_ffn2(const bf16* wd, bf16* out) {
    const int d = threadIdx.x, j = blockIdx.x, t = f_idx[j];
    float y = 0.f;
    for (int f = 0; f < F_; f++) y += f_gu[j * F_ + f] * b2f(wd[f * D_ + d]);
    out[t * D_ + d] = __float2bfloat16(b2f(f_h[t * D_ + d]) + bfr(b2f(f_n[t * D_ + d]) + bfr(bfr(y) * bfr(1.f / (1.f + expf(-f_r[t]))))));
}

typedef CUresult (*EncodeFn)(CUtensorMap*, CUtensorMapDataType, cuuint32_t, void*, const cuuint64_t*, const cuuint64_t*,
                             const cuuint32_t*, const cuuint32_t*, CUtensorMapInterleave, CUtensorMapSwizzle,
                             CUtensorMapL2promotion, CUtensorMapFloatOOBfill);

void make_map(EncodeFn fn, CUtensorMap* tm, const void* p, int cols, int rows, int bc, int br) {
    cuuint64_t dims[2] = {(cuuint64_t)cols, (cuuint64_t)rows};
    cuuint64_t strides[1] = {(cuuint64_t)cols * 2};
    cuuint32_t box[2] = {(cuuint32_t)bc, (cuuint32_t)br};
    cuuint32_t es[2] = {1, 1};
    fn(tm, CU_TENSOR_MAP_DATA_TYPE_BFLOAT16, 2, const_cast<void*>(p), dims, strides, box, es, CU_TENSOR_MAP_INTERLEAVE_NONE,
       CU_TENSOR_MAP_SWIZZLE_NONE, CU_TENSOR_MAP_L2_PROMOTION_L2_128B, CU_TENSOR_MAP_FLOAT_OOB_FILL_NONE);
}

void make_map3(EncodeFn fn, CUtensorMap* tm, const void* p) {
    cuuint64_t dims[5] = {(cuuint64_t)D_, 64, 2, 4, 4};
    cuuint64_t strides[4] = {(cuuint64_t)D_ * 2, (cuuint64_t)D_ * 128, (cuuint64_t)D_ * 1024, (cuuint64_t)D_ * 256};
    cuuint32_t box[5] = {XW, 9, 2, 4, 4};
    cuuint32_t es[5] = {1, 1, 1, 1, 1};
    fn(tm, CU_TENSOR_MAP_DATA_TYPE_BFLOAT16, 5, const_cast<void*>(p), dims, strides, box, es, CU_TENSOR_MAP_INTERLEAVE_NONE,
       CU_TENSOR_MAP_SWIZZLE_NONE, CU_TENSOR_MAP_L2_PROMOTION_NONE, CU_TENSOR_MAP_FLOAT_OOB_FILL_NONE);
}

void make_map5(EncodeFn fn, CUtensorMap* tm, const void* p, int bc) {
    cuuint64_t dims[5] = {(cuuint64_t)D_, 2, 4, 4, 64};
    cuuint64_t strides[4] = {(cuuint64_t)D_ * 128, (cuuint64_t)D_ * 1024, (cuuint64_t)D_ * 256, (cuuint64_t)D_ * 2};
    cuuint32_t box[5] = {(cuuint32_t)bc, 2, 4, 4, 8};
    cuuint32_t es[5] = {1, 1, 1, 1, 1};
    fn(tm, CU_TENSOR_MAP_DATA_TYPE_BFLOAT16, 5, const_cast<void*>(p), dims, strides, box, es, CU_TENSOR_MAP_INTERLEAVE_NONE,
       CU_TENSOR_MAP_SWIZZLE_NONE, CU_TENSOR_MAP_L2_PROMOTION_NONE, CU_TENSOR_MAP_FLOAT_OOB_FILL_NONE);
}

}

extern "C" void kernel_launch(void* const* d_in, const int* in_sizes, int n_in, void* d_out, int out_size) {
    (void)in_sizes; (void)n_in; (void)out_size;
    void* fp = nullptr;
    cudaDriverEntryPointQueryResult qr;
    cudaGetDriverEntryPoint("cuTensorMapEncodeTiled", &fp, cudaEnableDefault, &qr);
    EncodeFn fn = (EncodeFn)fp;
    CUtensorMap tmG, tmU, tmD, tmO, tmX, tmH;
    make_map3(fn, &tmX, d_in[0]);
    make_map(fn, &tmG, d_in[11], F_, D_, 40, 48);
    make_map(fn, &tmU, d_in[12], F_, D_, 40, 48);
    make_map(fn, &tmD, d_in[13], D_, F_, 72, 64);
    make_map5(fn, &tmO, d_out, 32);
    make_map5(fn, &tmH, d_out, 8);
    Params p;
    p.x = (const unsigned short*)d_in[0];
    for (int i = 0; i < 6; i++) p.prm6[i] = (const unsigned short*)d_in[1 + i];
    p.logdt = (const unsigned short*)d_in[7]; p.dskip = (const unsigned short*)d_in[8];
    p.wr = (const unsigned short*)d_in[10];
    p.out = (__nv_bfloat16*)d_out;
    p.zero = 0;
    cudaGetSymbolAddress((void**)&p.gs, g_s);
    cudaFuncSetAttribute(fused_kernel, cudaFuncAttributeMaxDynamicSharedMemorySize, SM_TOTAL);
    static int nclusters = -1;
    if (nclusters < 0) {
        cudaLaunchConfig_t cfg = {};
        cudaLaunchAttribute at;
        at.id = cudaLaunchAttributeClusterDimension; at.val.clusterDim.x = CS; at.val.clusterDim.y = 1; at.val.clusterDim.z = 1;
        cfg.gridDim = dim3(NCTA); cfg.blockDim = dim3(NTHR); cfg.dynamicSmemBytes = SM_TOTAL; cfg.attrs = &at; cfg.numAttrs = 1;
        if (cudaOccupancyMaxActiveClusters(&nclusters, fused_kernel, &cfg) != cudaSuccess) { (void)cudaGetLastError(); nclusters = NCL; }
    }
    if (nclusters >= NCL && !FORCE_FALLBACK) {
        fused_kernel<<<NCTA, NTHR, SM_TOTAL>>>(p, tmG, tmU, tmD, tmO, tmX, tmH);
        return;
    }
    fb_ln<<<L_ / 8, 256>>>((const bf16*)d_in[0], nullptr, nullptr);
    fb_taps<<<D_ * 8, 256>>>(p);
    fb_conv<<<L_, D_>>>(p);
    fb_ln<<<L_ / 8, 256>>>(nullptr, (const bf16*)d_in[10], p.out);
    fb_top<<<L_ / 256, 256>>>();
    fb_ffn1<<<dim3(F_ / 256, 8), 256>>>((const bf16*)d_in[11], (const bf16*)d_in[12]);
    fb_ffn2<<<8, D_>>>((const bf16*)d_in[13], p.out);
}
```

```cpp
#include <cuda_runtime.h>
#include <cuda_bf16.h>
#include <cuda_fp16.h>
#include <cuda.h>
#include <stdint.h>

namespace {

constexpr int L_ = 2048, D_ = 576, F_ = 4608;
constexpr int NCL = 15, CS = 8, NCTA = NCL * CS, NTHR = 768;
#define FORCE_FALLBACK 0
constexpr int XW = 48, NRED = 2;
constexpr int SPIN_LIMIT = 1 << 22;

constexpr int SM_WG   = 0;
constexpr int SM_WU   = 46080;
constexpr int YP = 3392, YS = 656;
constexpr int UP = 3280, US = 656;
constexpr int SM_XT   = 92160;
constexpr int SM_U    = SM_XT + 8 * YP;
constexpr int SM_FAR  = SM_U + 8 * UP;
constexpr int FAR_SZ  = 12416;
constexpr int F_E5 = 0, F_O5 = 1536, F_E3 = 3088, F_O3 = 4624, F_E7 = 6176, F_E2 = F_E7 + 1024, F_E9 = F_E7 + 2048,
              F_H = 3088, F_O7 = F_E7 + F_H, F_O2 = F_E2 + F_H, F_O9 = F_E9 + F_H;
constexpr int SM_P    = SM_FAR + 5 * FAR_SZ;
constexpr int PN_SZ = 584 * 4, SM_PN = SM_P + 64 * 4;
constexpr int P_GS = 48 * 4, P_H7 = 192 * 4, P_HS = 72 * 4;
constexpr int PF_SZ = (192 + 216) * 4, SM_PF = SM_PN + 5 * PN_SZ + 32;
constexpr int SM_MISC = SM_PF + 5 * PF_SZ;
constexpr int SM_ST   = SM_MISC;
constexpr int SM_RK   = SM_ST + 2048;
constexpr int SM_SEL  = SM_RK + 256;
constexpr int SM_KG   = SM_SEL + 64;
constexpr int SM_SC   = SM_KG + 160;
constexpr int SM_DW   = SM_SC + 32;
constexpr int SM_MB   = SM_DW + 160;
constexpr int SM_TOTAL = SM_MB + 128;
constexpr int SM_ROW  = SM_XT - 20736;
constexpr int SM_XTL  = SM_ROW - 576 * XW;
constexpr int SM_RED2 = SM_WG;
constexpr int SM_HT   = SM_P - 512;
constexpr int SM_KEY  = SM_FAR + 10240 + 128;
constexpr int SM_CAND = SM_KEY + 1024;
constexpr int SM_XS   = SM_U;
constexpr int SM_GU   = SM_XS + 9344;
constexpr int SM_RED  = SM_GU + 5632;
static_assert(F_O9 + 1024 <= FAR_SZ && FAR_SZ % 128 == 0, "far overflow");
static_assert(SM_RED + 10240 <= SM_FAR && SM_HT + 20496 <= SM_MISC, "alias overflow");
static_assert(SM_TOTAL <= 232448, "smem overflow");
static_assert(SM_FAR % 128 == 0 && SM_XT % 128 == 0 && SM_XTL % 128 == 0 && SM_P % 16 == 0 && SM_MISC % 16 == 0 && SM_MB % 8 == 0, "align");

enum { MB_X = 0, MB_W1 = 5, MB_W2 = 6, MB_KEY = 7, MB_GU = 8, MB_Y = 9, MB_OUT = 10, MB_T = 11, MB_R = 12 };

struct __align__(128) Scratch {
    unsigned epoch, zcnt, pad[30];
    uint4  st1[L_ * 2];
    float4 acc[L_];
    uint4  cand[64 * NCL * 6];
    float4 fin[8 * 192 + 24];
};
__device__ Scratch g_s;
#define STAMP(i)

__device__ __forceinline__ uint32_t mapa(uint32_t a, uint32_t r) { uint32_t d; asm("mapa.shared::cluster.u32 %0, %1, %2;" : "=r"(d) : "r"(a), "r"(r)); return d; }
__device__ __forceinline__ void mbar_wait(uint32_t mb) {
    asm volatile("{ .reg .pred p, q; .reg .u32 n; mov.u32 n, 0;\n"
                 "W_%=: mbarrier.try_wait.parity.shared::cta.b64 p, [%0], 0; add.u32 n, n, 1; setp.lt.and.u32 q, n, 65536, !p; @q bra W_%=; }" :: "r"(mb) : "memory");
}
__device__ __forceinline__ void arm(uint32_t mb, uint32_t bytes) { asm volatile("mbarrier.arrive.expect_tx.shared::cta.b64 _, [%0], %1;" :: "r"(mb), "r"(bytes) : "memory"); }
__device__ __forceinline__ void bar_sync(int id, int n) { asm volatile("bar.sync %0, %1;" :: "r"(id), "r"(n) : "memory"); }
__device__ __forceinline__ void bar_arrive(int id, int n) { asm volatile("bar.arrive %0, %1;" :: "r"(id), "r"(n) : "memory"); }
__device__ __forceinline__ uint32_t lds16(uint32_t a) { unsigned short v; asm volatile("ld.shared.u16 %0, [%1];" : "=h"(v) : "r"(a) : "memory"); return v; }
__device__ __forceinline__ uint32_t lds32(uint32_t a) { uint32_t v; asm volatile("ld.shared.u32 %0, [%1];" : "=r"(v) : "r"(a) : "memory"); return v; }
__device__ __forceinline__ uint2 lds64(uint32_t a) { uint2 v; asm volatile("ld.shared.v2.u32 {%0,%1}, [%2];" : "=r"(v.x), "=r"(v.y) : "r"(a) : "memory"); return v; }
__device__ __forceinline__ float ldsf(uint32_t a) { float v; asm volatile("ld.shared.f32 %0, [%1];" : "=f"(v) : "r"(a) : "memory"); return v; }
__device__ __forceinline__ uint4 lds128(uint32_t a) { uint4 v; asm volatile("ld.shared.v4.u32 {%0,%1,%2,%3}, [%4];" : "=r"(v.x), "=r"(v.y), "=r"(v.z), "=r"(v.w) : "r"(a) : "memory"); return v; }
__device__ __forceinline__ float4 lds128f(uint32_t a) { float4 v; asm volatile("ld.shared.v4.f32 {%0,%1,%2,%3}, [%4];" : "=f"(v.x), "=f"(v.y), "=f"(v.z), "=f"(v.w) : "r"(a) : "memory"); return v; }
__device__ __forceinline__ void sts16(uint32_t a, uint32_t v) { asm volatile("{ .reg .b16 l, h; mov.b32 {l, h}, %1; st.shared.b16 [%0], l; }" :: "r"(a), "r"(v) : "memory"); }
__device__ __forceinline__ void sts32(uint32_t a, uint32_t v) { asm volatile("st.shared.u32 [%0], %1;" :: "r"(a), "r"(v) : "memory"); }
__device__ __forceinline__ void sts64(uint32_t a, uint32_t x, uint32_t y) { asm volatile("st.shared.v2.u32 [%0], {%1,%2};" :: "r"(a), "r"(x), "r"(y) : "memory"); }
__device__ __forceinline__ void stsf(uint32_t a, float v) { asm volatile("st.shared.f32 [%0], %1;" :: "r"(a), "f"(v) : "memory"); }
__device__ __forceinline__ void sts128(uint32_t a, uint32_t x, uint32_t y, uint32_t z, uint32_t w) { asm volatile("st.shared.v4.u32 [%0], {%1,%2,%3,%4};" :: "r"(a), "r"(x), "r"(y), "r"(z), "r"(w) : "memory"); }
__device__ __forceinline__ void sts128f(uint32_t a, float x, float y, float z, float w) { asm volatile("st.shared.v4.f32 [%0], {%1,%2,%3,%4};" :: "r"(a), "f"(x), "f"(y), "f"(z), "f"(w) : "memory"); }
__device__ __forceinline__ void ldsm4(uint32_t (&r)[4], uint32_t a) { asm volatile("ldmatrix.sync.aligned.m8n8.x4.shared.b16 {%0,%1,%2,%3}, [%4];" : "=r"(r[0]), "=r"(r[1]), "=r"(r[2]), "=r"(r[3]) : "r"(a) : "memory"); }
__device__ __forceinline__ void ldsm4t(uint32_t (&r)[4], uint32_t a) { asm volatile("ldmatrix.sync.aligned.m8n8.x4.trans.shared.b16 {%0,%1,%2,%3}, [%4];" : "=r"(r[0]), "=r"(r[1]), "=r"(r[2]), "=r"(r[3]) : "r"(a) : "memory"); }
__device__ __forceinline__ void ldsm2t(uint32_t& r0, uint32_t& r1, uint32_t a) { asm volatile("ldmatrix.sync.aligned.m8n8.x2.trans.shared.b16 {%0,%1}, [%2];" : "=r"(r0), "=r"(r1) : "r"(a) : "memory"); }
__device__ __forceinline__ void stsm4t(uint32_t a, uint32_t r0, uint32_t r1, uint32_t r2, uint32_t r3) { asm volatile("stmatrix.sync.aligned.m8n8.x4.trans.shared.b16 [%0], {%1,%2,%3,%4};" :: "r"(a), "r"(r0), "r"(r1), "r"(r2), "r"(r3) : "memory"); }
__device__ __forceinline__ void stsm4(uint32_t a, uint32_t r0, uint32_t r1, uint32_t r2, uint32_t r3) { asm volatile("stmatrix.sync.aligned.m8n8.x4.shared.b16 [%0], {%1,%2,%3,%4};" :: "r"(a), "r"(r0), "r"(r1), "r"(r2), "r"(r3) : "memory"); }
__device__ __forceinline__ void stsm2t(uint32_t a, uint32_t r0, uint32_t r1) { asm volatile("stmatrix.sync.aligned.m8n8.x2.trans.shared.b16 [%0], {%1,%2};" :: "r"(a), "r"(r0), "r"(r1) : "memory"); }
__device__ __forceinline__ uint4 ldg128(const void* p) { uint4 v; asm volatile("ld.global.nc.v4.u32 {%0,%1,%2,%3}, [%4];" : "=r"(v.x), "=r"(v.y), "=r"(v.z), "=r"(v.w) : "l"(p)); return v; }
__device__ __forceinline__ uint32_t ldg16(const void* p) { unsigned short v; asm volatile("ld.global.nc.u16 %0, [%1];" : "=h"(v) : "l"(p)); return v; }
__device__ __forceinline__ uint32_t opaque(uint32_t v) { uint32_t r; asm volatile("mov.b32 %0, %1;" : "=r"(r) : "r"(v)); return r; }
__device__ __forceinline__ void mma_f16(float (&d)[4], const uint32_t (&a)[4], uint32_t b0, uint32_t b1) {
    asm volatile("mma.sync.aligned.m16n8k16.row.col.f32.f16.f16.f32 {%0,%1,%2,%3}, {%4,%5,%6,%7}, {%8,%9}, {%0,%1,%2,%3};"
        : "+f"(d[0]), "+f"(d[1]), "+f"(d[2]), "+f"(d[3]) : "r"(a[0]), "r"(a[1]), "r"(a[2]), "r"(a[3]), "r"(b0), "r"(b1));
}
__device__ __forceinline__ void mma_f16_z(float (&d)[4], const uint32_t (&a)[4], uint32_t b0, uint32_t b1) {
    asm volatile("mma.sync.aligned.m16n8k16.row.col.f32.f16.f16.f32 {%0,%1,%2,%3}, {%4,%5,%6,%7}, {%8,%9}, {%10,%10,%10,%10};"
        : "=f"(d[0]), "=f"(d[1]), "=f"(d[2]), "=f"(d[3]) : "r"(a[0]), "r"(a[1]), "r"(a[2]), "r"(a[3]), "r"(b0), "r"(b1), "f"(0.f));
}
__device__ __forceinline__ void mma_bf16(float (&d)[4], uint32_t a0, uint32_t a1, uint32_t a2, uint32_t a3, uint32_t b0, uint32_t b1) {
    asm volatile("mma.sync.aligned.m16n8k16.row.col.f32.bf16.bf16.f32 {%0,%1,%2,%3}, {%4,%5,%6,%7}, {%8,%9}, {%0,%1,%2,%3};"
        : "+f"(d[0]), "+f"(d[1]), "+f"(d[2]), "+f"(d[3]) : "r"(a0), "r"(a1), "r"(a2), "r"(a3), "r"(b0), "r"(b1));
}
__device__ __forceinline__ void mma_bf16_k8(float (&d)[4], uint32_t a0, uint32_t a1, uint32_t b0) {
    asm volatile("mma.sync.aligned.m16n8k8.row.col.f32.bf16.bf16.f32 {%0,%1,%2,%3}, {%4,%5}, {%6}, {%0,%1,%2,%3};"
        : "+f"(d[0]), "+f"(d[1]), "+f"(d[2]), "+f"(d[3]) : "r"(a0), "r"(a1), "r"(b0));
}
__device__ __forceinline__ uint32_t pack_f16(float lo, float hi) { uint32_t r; asm("cvt.rn.f16x2.f32 %0, %1, %2;" : "=r"(r) : "f"(hi), "f"(lo)); return r; }
__device__ __forceinline__ uint32_t pack_bf16(float lo, float hi) { uint32_t r; asm("cvt.rn.bf16x2.f32 %0, %1, %2;" : "=r"(r) : "f"(hi), "f"(lo)); return r; }
__device__ __forceinline__ float bf_lo(uint32_t v) { return __uint_as_float(v << 16); }
__device__ __forceinline__ float bf_hi(uint32_t v) { return __uint_as_float(v & 0xFFFF0000u); }
__device__ __forceinline__ float bfr(float x) { return __uint_as_float(pack_bf16(0.f, x)); }
__device__ __forceinline__ uint32_t badd2(uint32_t a, uint32_t b) { uint32_t r; asm("add.rn.bf16x2 %0, %1, %2;" : "=r"(r) : "r"(a), "r"(b)); return r; }
__device__ __forceinline__ uint32_t bmul2(uint32_t a, uint32_t b) { uint32_t r; asm("mul.rn.bf16x2 %0, %1, %2;" : "=r"(r) : "r"(a), "r"(b)); return r; }
__device__ __forceinline__ uint32_t hadd2(uint32_t a, uint32_t b) { uint32_t r; asm("add.rn.f16x2 %0, %1, %2;" : "=r"(r) : "r"(a), "r"(b)); return r; }
__device__ __forceinline__ uint32_t hmul2(uint32_t a, uint32_t b) { uint32_t r; asm("mul.rn.f16x2 %0, %1, %2;" : "=r"(r) : "r"(a), "r"(b)); return r; }
__device__ __forceinline__ uint32_t hfma2(uint32_t a, uint32_t b, uint32_t c) { uint32_t r; asm("fma.rn.f16x2 %0, %1, %2, %3;" : "=r"(r) : "r"(a), "r"(b), "r"(c)); return r; }
__device__ __forceinline__ uint32_t hneg2(uint32_t a) { uint32_t r; asm("neg.f16x2 %0, %1;" : "=r"(r) : "r"(a)); return r; }
__device__ __forceinline__ float rcpf(float x) { float r; asm("rcp.approx.ftz.f32 %0, %1;" : "=f"(r) : "f"(x)); return r; }
__device__ __forceinline__ float sqrta(float x) { float r; asm("sqrt.approx.ftz.f32 %0, %1;" : "=f"(r) : "f"(x)); return r; }
__device__ __forceinline__ float ex2f(float x) { float r; asm("ex2.approx.ftz.f32 %0, %1;" : "=f"(r) : "f"(x)); return r; }
__device__ __forceinline__ void st_async4(uint32_t a, uint32_t x, uint32_t y, uint32_t z, uint32_t w, uint32_t mb) {
    asm volatile("st.async.shared::cluster.mbarrier::complete_tx::bytes.v4.u32 [%0], {%1,%2,%3,%4}, [%5];" :: "r"(a), "r"(x), "r"(y), "r"(z), "r"(w), "r"(mb) : "memory"); }
__device__ __forceinline__ void st_async1(uint32_t a, uint32_t x, uint32_t mb) {
    asm volatile("st.async.shared::cluster.mbarrier::complete_tx::bytes.u32 [%0], %1, [%2];" :: "r"(a), "r"(x), "r"(mb) : "memory"); }
__device__ __forceinline__ unsigned ld_rlx(const void* p) { unsigned v; asm volatile("ld.relaxed.gpu.global.u32 %0, [%1];" : "=r"(v) : "l"(p) : "memory"); return v; }
__device__ __forceinline__ unsigned ld_acq(const void* p) { unsigned v; asm volatile("ld.acquire.gpu.global.u32 %0, [%1];" : "=r"(v) : "l"(p) : "memory"); return v; }
__device__ __forceinline__ uint2 ld_rlx64(const void* p) { unsigned long long v; asm volatile("ld.relaxed.gpu.global.u64 %0, [%1];" : "=l"(v) : "l"(p) : "memory"); return make_uint2((unsigned)v, (unsigned)(v >> 32)); }
__device__ __forceinline__ void st_rlx128(void* p, uint32_t x, uint32_t y, uint32_t z, uint32_t w) {
    asm volatile("st.relaxed.gpu.global.v2.u64 [%0], {%1,%2};" :: "l"(p), "l"((unsigned long long)x | ((unsigned long long)y << 32)), "l"((unsigned long long)z | ((unsigned long long)w << 32)) : "memory"); }
__device__ __forceinline__ uint4 ld_rlx128(const void* p) { unsigned long long a, b; asm volatile("ld.relaxed.gpu.global.v2.u64 {%0,%1}, [%2];" : "=l"(a), "=l"(b) : "l"(p) : "memory"); return make_uint4((unsigned)a, (unsigned)(a >> 32), (unsigned)b, (unsigned)(b >> 32)); }
__device__ __forceinline__ void tma2d(uint32_t dst, const CUtensorMap* tm, int x, int y, uint32_t mb) {
    asm volatile("cp.async.bulk.tensor.2d.shared::cluster.global.mbarrier::complete_tx::bytes [%0], [%1, {%3, %4}], [%2];"
                 :: "r"(dst), "l"(tm), "r"(mb), "r"(x), "r"(y) : "memory");
}
__device__ __forceinline__ void cmul(float& xr, float& xi, float ar, float ai, float br, float bi) {
    const float r = fmaf(ar, br, -ai * bi), i = fmaf(ar, bi, ai * br); xr = r; xi = i;
}
__device__ __forceinline__ void csq(float& xr, float& xi, float ar, float ai) {
    const float r = fmaf(ar, ar, -ai * ai), i = (ar + ar) * ai; xr = r; xi = i;
}
__device__ __forceinline__ void cexp_s(float& zr, float& zi, float e2, float turns) {
    const float mag = ex2f(e2), r = (turns - rintf(turns)) * 6.283185307179586f;
    zr = mag * __cosf(r); zi = mag * __sinf(r);
}
__device__ __forceinline__ uint32_t ln_stats(float s1, float s2) {
    const float m = s1 * (1.f / D_);
    const float var = fmaxf(fmaf(s2, 1.f / D_, -m * m), 0.f);
    return pack_bf16(m, sqrta(bfr(bfr(var) + 1e-5f)));
}
__device__ __forceinline__ uint32_t rsplit(float rs) { const float h = bfr(rs); return pack_bf16(h, rs - h); }
__device__ __forceinline__ uint32_t norm2(uint32_t v, uint32_t mx, uint32_t hl) {
    uint32_t r;
    asm("{ .reg .b16 m, h, l, x; .reg .b32 m2, h2, l2, d, t; mov.b32 {m, x}, %2; mov.b32 {h, l}, %3; mov.b32 m2, {m, m}; mov.b32 h2, {h, h}; mov.b32 l2, {l, l};\n"
        "sub.rn.bf16x2 d, %1, m2; mul.rn.bf16x2 t, d, l2; fma.rn.bf16x2 %0, d, h2, t; }" : "=r"(r) : "r"(v), "r"(mx), "r"(hl));
    return r;
}
template <int N, int S>
__device__ __forceinline__ uint32_t rank4(uint32_t a, uint32_t key) {
    uint32_t r0 = 0, r1 = 0, r2 = 0, r3 = 0;
#pragma unroll
    for (int i = 0; i < N; i++) {
        const uint4 o = lds128(a + i * S);
        r0 += (key - o.x) >> 31; r1 += (key - o.y) >> 31; r2 += (key - o.z) >> 31; r3 += (key - o.w) >> 31;
    }
    return (r0 + r1) + (r2 + r3);
}
typedef uint32_t H2C;
__device__ __forceinline__ H2C splat(float r, float i) { return pack_f16(r, i); }
__device__ __forceinline__ void hcmul(uint32_t& xr, uint32_t& xi, uint32_t R, uint32_t I, H2C m) {
    asm("{ .reg .b16 a, b; .reg .b32 a2, b2, t; mov.b32 {a, b}, %4; mov.b32 a2, {a, a}; mov.b32 b2, {b, b};\n"
        "mul.rn.f16x2 t, %3, b2; neg.f16x2 t, t; fma.rn.f16x2 %0, %2, a2, t; mul.rn.f16x2 t, %3, a2; fma.rn.f16x2 %1, %2, b2, t; }"
        : "=&r"(xr), "=r"(xi) : "r"(R), "r"(I), "r"(m));
}
__device__ __forceinline__ void expand4(uint32_t are, uint32_t aim, uint32_t R0, uint32_t R1, uint32_t I0, uint32_t I1, H2C m4) {
    uint32_t R2, I2, R3, I3;
    hcmul(R2, I2, R0, I0, m4); hcmul(R3, I3, R1, I1, m4);
    sts128(are, R0, R1, R2, R3);
    sts128(aim, I0, I1, I2, I3);
}
__device__ __forceinline__ void expand8(uint32_t are, uint32_t aim, float sr, float si, float m1r, float m1i, float m2r, float m2i, H2C m4) {
    float r1, i1, r2, i2, r3, i3;
    cmul(r1, i1, sr, si, m1r, m1i); cmul(r2, i2, sr, si, m2r, m2i); cmul(r3, i3, r1, i1, m2r, m2i);
    expand4(are, aim, pack_f16(sr, r1), pack_f16(r2, r3), pack_f16(si, i1), pack_f16(i2, i3), m4);
}
__device__ __forceinline__ void put16(uint32_t a, uint32_t v) { sts16(a, v); sts16(a + 6, v); }

struct Params {
    const unsigned short *logdt, *dskip, *prm6[6], *x, *wr;
    __nv_bfloat16* out;
    Scratch* gs;
    unsigned zero;
};
__device__ __forceinline__ uint32_t tslot(uint32_t t) { return (t & 7) * 32 + ((t >> 4) & 24) + ((t >> 8) & 6) + ((t >> 6) & 1); }
#define CP(x) ((x) | zero)
#define PIN(x) asm volatile("or.b32 %0, %0, %1;" : "+r"(x) : "r"(zero))
__device__ __forceinline__ void wgmma32(float (&d)[4][4], const uint32_t (&a)[4], uint32_t dlo) {
    asm volatile("{ .reg .b64 ds; mov.b64 ds, {%20, %21};\n"
                 "wgmma.mma_async.sync.aligned.m64n32k16.f32.f16.f16 {%0,%1,%2,%3,%4,%5,%6,%7,%8,%9,%10,%11,%12,%13,%14,%15}, {%16,%17,%18,%19}, ds, 1, 1, 1, 0; }"
        : "+f"(d[0][0]), "+f"(d[0][1]), "+f"(d[0][2]), "+f"(d[0][3]), "+f"(d[1][0]), "+f"(d[1][1]), "+f"(d[1][2]), "+f"(d[1][3]),
          "+f"(d[2][0]), "+f"(d[2][1]), "+f"(d[2][2]), "+f"(d[2][3]), "+f"(d[3][0]), "+f"(d[3][1]), "+f"(d[3][2]), "+f"(d[3][3])
        : "r"(a[0]), "r"(a[1]), "r"(a[2]), "r"(a[3]), "r"(dlo), "n"(128 >> 4));
}

__device__ __forceinline__ void finish(const Params& prm, uint32_t fo, uint32_t oo, const float (&v)[3], float cnt) {
    float x, y, z, w;
    asm volatile("atom.relaxed.gpu.global.add.v4.f32 {%0,%1,%2,%3}, [%4], {%5,%6,%7,%8};" : "=f"(x), "=f"(y), "=f"(z), "=f"(w)
                 : "l"((char*)prm.gs->fin + fo), "f"(v[0]), "f"(v[1]), "f"(v[2]), "f"(cnt) : "memory");
    if (w + cnt == 3.f * (NCL + 1)) {
        __nv_bfloat16* op = (__nv_bfloat16*)((char*)prm.out + oo);
        op[0] = __float2bfloat16(x + v[0]); op[1] = __float2bfloat16(y + v[1]); op[2] = __float2bfloat16(z + v[2]);
    }
}

__global__ void __cluster_dims__(CS, 1, 1) __launch_bounds__(NTHR, 1)
fused_kernel(const __grid_constant__ Params prm, const __grid_constant__ CUtensorMap tmG, const __grid_constant__ CUtensorMap tmU,
             const __grid_constant__ CUtensorMap tmD, const __grid_constant__ CUtensorMap tmO, const __grid_constant__ CUtensorMap tmX, const __grid_constant__ CUtensorMap tmH)
{
    extern __shared__ __align__(1024) unsigned char smem[];
    const int tid = threadIdx.x, lane = tid & 31, warp = __shfl_sync(~0u, tid >> 5, 0);
    const int c = blockIdx.x >> 3, q = blockIdx.x & 7;
    const int nslot = (c < NCL - 1) ? 5 : 2;
    const int d0 = 40 * c;
    const uint32_t sb = opaque((uint32_t)__cvta_generic_to_shared(smem));
    const uint32_t mb = sb + SM_MB;
    Scratch& g_s = *prm.gs;
    const unsigned& zero = prm.zero;
    STAMP(0);

    if (warp >= 20) {
        unsigned epoch = 0;
        if (warp == 20) {
            if (lane == 0) {
#pragma unroll
                for (int i = 0; i < 13; i++)
                    asm volatile("mbarrier.init.shared::cta.b64 [%0], %1;" :: "r"(mb + i * 8), "r"((i == MB_R || i < 5) ? 2 : i == MB_Y ? 1 + 4 * nslot : 1) : "memory");
                asm volatile("fence.mbarrier_init.release.cluster;" ::: "memory");
                arm(mb + MB_W1 * 8, 92160); arm(mb + MB_W2 * 8, nslot * 9216); arm(mb + MB_KEY * 8, 256); arm(mb + MB_GU * 8, nslot * 1024); arm(mb + MB_T * 8, 576 * XW);
                const int bytes = max(min(18, L_ - 18 * (int)blockIdx.x), 1) * (D_ * 2);
                arm(mb + MB_R * 8, bytes);
            }
            __syncwarp();
        } else if (warp == 22) {
            epoch = ld_rlx(&g_s.epoch);
            if (lane < 18 ? 18 * c + lane < 256 : lane < 31) (lane < 18 ? &g_s.acc[256 * q + 18 * c] : &g_s.fin[13 * (int)blockIdx.x - 18])[lane] = make_float4(0.f, 0.f, 0.f, 0.f);
        } else if (warp == 23 && lane == 0) asm volatile("prefetch.tensormap [%0];" :: "l"(&tmX) : "memory");
        asm volatile("barrier.cluster.arrive.relaxed.aligned;" ::: "memory");
        bar_sync(12, NTHR);
        uint4 wv = make_uint4(0, 0, 0, 0), wv2, wv3;
        if (warp == 22) {
            if (lane == 0) { sts32(sb + SM_SC + 28, epoch); asm volatile("mbarrier.arrive.shared::cta.b64 _, [%0];" :: "r"(mb + MB_R * 8) : "memory"); }
            epoch++;
            asm volatile("fence.acq_rel.gpu;" ::: "memory");
            __syncwarp();
            if (lane == 0) asm volatile("red.relaxed.gpu.global.add.u32 [%0], 1;" :: "l"(&g_s.zcnt) : "memory");
            STAMP(1);
            wv2 = ldg128((const uint4*)prm.wr + lane); wv3 = ldg128((const uint4*)prm.wr + 32 + lane);
            if (lane < 8) wv = ldg128((const uint4*)prm.wr + 64 + lane);
            if (lane < 5) {
                uint4 v = make_uint4(0, 0, 0, 0);
                if (lane < nslot) v = ldg128((const uint4*)(prm.wr + d0) + lane);
                sts128(sb + SM_DW + lane * 16, v.x, v.y, v.z, v.w);
            }
            __syncwarp();
            if (lane < 5) asm volatile("mbarrier.arrive.shared::cta.b64 _, [%0];" :: "r"(mb + (MB_X + lane) * 8) : "memory");
        }
        if (warp == 21) {
            if (lane == 0) { asm volatile("prefetch.tensormap [%0];" :: "l"(&tmG) : "memory"); asm volatile("prefetch.tensormap [%0];" :: "l"(&tmU) : "memory"); asm volatile("prefetch.tensormap [%0];" :: "l"(&tmD) : "memory"); }
            __syncwarp();
            bar_sync(15, 672);
            asm volatile("fence.proxy.async.shared::cta;" ::: "memory");
#pragma unroll 1
            for (int i = 0; i < 24; i++) {
                if (lane == 0) tma2d(sb + SM_WG + i * 3840, i < 12 ? &tmG : &tmU, 320 * c + 8 * nslot * q, 48 * (i < 12 ? i : i - 12), mb + MB_W1 * 8);
            }
            STAMP(1);
        } else {
        if (warp == 20) {
            if (lane == 0) {
                asm volatile("cp.async.bulk.shared::cluster.global.mbarrier::complete_tx::bytes [%0], [%1], %2, [%3];"
                             :: "r"(sb + SM_ROW), "l"(prm.x + min(18 * (int)blockIdx.x, L_ - 1) * D_), "r"(max(min(18, L_ - 18 * (int)blockIdx.x), 1) * (D_ * 2)), "r"(mb + MB_R * 8) : "memory");
            }
            __syncwarp();
            mbar_wait(mb + MB_R * 8);
            if (lane == 0) {
                asm volatile("cp.async.bulk.tensor.5d.shared::cluster.global.mbarrier::complete_tx::bytes [%0], [%1, {%3, %4, %5, %5, %5}], [%2];"
                             :: "r"(sb + SM_XTL), "l"(&tmX), "r"(mb + MB_T * 8), "r"(d0 & ~15), "r"(8 * q), "r"(0) : "memory");
            }
            STAMP(6);
        }
        asm volatile("barrier.cluster.wait.aligned;" ::: "memory");
        bar_sync(13, 608);
        asm volatile("fence.proxy.async.shared::cta;" ::: "memory");
        {
            const int idx = lane * 3 + max(warp - 21, 0), sl = nslot - 1 - (idx >> 3), pe = (idx + q + 1) & 7;
            if (sl >= 0) {
                if (pe == q) arm(mb + (MB_X + sl) * 8, 7 * 512);
                else {
                    const uint32_t rb_ = mapa(sb, pe);
                    asm volatile("cp.async.bulk.shared::cluster.shared::cta.mbarrier::complete_tx::bytes [%0], [%1], 512, [%2];"
                                 :: "r"(rb_ + SM_U + 128 + q * UP + sl * US), "r"(sb + SM_XT + 128 + (q & 3) * 16 + pe * YP + sl * YS), "r"(rb_ + SM_MB + (MB_X + sl) * 8) : "memory");
                }
            }
        }
        STAMP(1);
        if (warp == 20 && lane == 0) { asm volatile("prefetch.tensormap [%0];" :: "l"(&tmO) : "memory"); asm volatile("prefetch.tensormap [%0];" :: "l"(&tmH) : "memory"); }
        if (warp == 22) {
            __syncwarp();
            mbar_wait(mb + (MB_X + 1) * 8);
            const uint32_t old = (epoch & 1) ? 0u : 0x40004000u;
#pragma unroll
            for (int t = 0; t < 2; t++)
                if ((lane & 7) < 6) g_s.cand[((q * 8 + 4 * t + (lane >> 3)) * NCL + c) * 6 + (lane & 7)] = make_uint4(old, old, old, old);
            float a[4] = {0.f, 0.f, 0.f, 0.f};
            const uint32_t one = 0x3F803F80u;
            mma_bf16(a, one, one, one, one, wv.x, wv.y);  mma_bf16(a, one, one, one, one, wv.z, wv.w);
            mma_bf16(a, one, one, one, one, wv2.x, wv2.y); mma_bf16(a, one, one, one, one, wv2.z, wv2.w);
            mma_bf16(a, one, one, one, one, wv3.x, wv3.y); mma_bf16(a, one, one, one, one, wv3.z, wv3.w);
            float s = a[0] + a[1];
            s += __shfl_xor_sync(~0u, s, 1); s += __shfl_xor_sync(~0u, s, 2);
            stsf(sb + SM_SC + 24, s);
            __syncwarp();
            if (lane == 0) {
                int n = 0;
                while ((int)(ld_acq(&g_s.zcnt) - epoch * NCTA) < 0 && ++n < SPIN_LIMIT) __nanosleep(200);
                arm(mb + MB_Y * 8, 8 * 512 * nslot);
                if (blockIdx.x == 0) g_s.epoch = epoch;
            }
            STAMP(2);
        }
        if (warp == 23) {
#pragma unroll 1
            for (int kk = nslot - 1; kk >= 0; kk--) {
                __syncwarp();
                bar_sync(6 + kk, 160);
                if (lane == 0) { asm volatile("fence.proxy.async.shared::cta;" ::: "memory"); tma2d(sb + SM_FAR + kk * FAR_SZ, &tmD, 72 * q, 320 * c + 64 * kk, mb + MB_W2 * 8); }
            }
        }
        }
        __syncwarp();
        bar_sync(14, 768);
        if (tid == 640) {
            asm volatile("fence.proxy.async.shared::cta;" ::: "memory");
            asm volatile("cp.async.bulk.tensor.5d.global.shared::cta.bulk_group [%0, {%2, %4, %4, %4, %3}], [%1];" :: "l"(&tmH), "r"(sb + SM_XT + 16384), "r"(d0 + ((c & 1) ? 0 : 32)), "r"(8 * q), "r"(0) : "memory");
            asm volatile("cp.async.bulk.tensor.5d.global.shared::cta.bulk_group [%0, {%2, %4, %4, %4, %3}], [%1];" :: "l"(&tmO), "r"(sb + SM_XT), "r"(d0 + (c & 1) * 8), "r"(8 * q), "r"(0) : "memory");
            asm volatile("cp.async.bulk.commit_group;" ::: "memory");
        }
        __syncwarp();
        const uint32_t ft = (tid >> 4) & 7, fj = d0 / 3 + (lane & 15), tok = ~lds32(sb + SM_SEL + ft * 8) & 2047;
        float v[3], cnt = 0.f;
#pragma unroll
        for (int i = 0; i < 3; i++) {
            const uint32_t cl = 3 * fj + i - d0, cf = cl - (c & 1) * 8;
            const bool ok = cl < 8 * nslot && ((tok >> 3) & 7) == q;
            const uint32_t u = lds16(sb + SM_XT + (cf < 32 ? tslot(tok) * 64 + cf * 2 : 16384 + tslot(tok) * 16 + (cl & 7) * 2));
            v[i] = ok ? __uint_as_float(u << 16) : 0.f;
            if (ok) cnt += 1.f;
        }
        if (tid == 640) {
            asm volatile("cp.async.bulk.wait_group 0;" ::: "memory");
            asm volatile("fence.proxy.async.global;" ::: "memory");
            asm volatile("mbarrier.arrive.shared::cta.b64 _, [%0];" :: "r"(mb + MB_OUT * 8) : "memory");
        }
        __syncwarp();
        mbar_wait(mb + MB_OUT * 8);
        STAMP(5);
        if (cnt != 0.f) finish(prm, (ft * 192 + fj) * 16, (tok * D_ + 3 * fj) * 2, v, cnt);
        return;
    }

    const int g = lane >> 2, cq = lane & 3;
    const int k = warp >> 2, wq = warp & 3;
    const int trow = 18 * blockIdx.x + warp;
    const bool rowact = warp < 18 && trow < L_;
    const int dch = min(d0 + 8 * k + q, D_ - 1);
    uint32_t pv[6];
    const uint32_t pofs = opaque((dch * 128 + wq * 32 + lane) * 2);
#pragma unroll
    for (int i = 0; i < 6; i++) pv[i] = ldg16((const char*)prm.prm6[i] + pofs);
    const uint32_t pLdt = ldg16(prm.logdt + dch), pD = ldg16(prm.dskip + dch);
    const int tn = 16 * (warp & 15) + g;
    uint32_t xa[5], xb[5];
    asm volatile("barrier.cluster.arrive.relaxed.aligned;" ::: "memory");
    uint4* const st1p = &g_s.st1[(((trow >> 3) & 7) * 256 + ((trow >> 6) & 31) * 8 + (trow & 7)) * 2 + (lane >> 2)];
    const bool pub = rowact && (lane & 0x1B) == 0;
    if (pub) st_rlx128(st1p, 0, 0, 0, 0);
    {
        const uint32_t za = sb + SM_P + tid * 16;
        sts128(za, 0, 0, 0, 0);
        if (tid < (SM_MISC - SM_P) / 16 - 640) sts128(za + 10240, 0, 0, 0, 0);
        sts128(sb + ((wq & 2) ? SM_U : SM_XT + (q & 3) * 16) + ((tid >> 3) & 7) * ((wq & 2) ? UP : YP) + k * YS + (lane & 7) * 16, 0, 0, 0, 0);
    }
    bar_sync(12, NTHR);
    const uint32_t dep = lds32(sb + SM_P);
#define PV(x) __uint_as_float(__byte_perm(dep, x, 0x5410))
    STAMP(1);
    const uint32_t fb = sb + SM_FAR + k * FAR_SZ;
    const uint32_t pn = sb + SM_PN + k * PN_SZ, pf = sb + SM_PF + k * PF_SZ;
    unsigned epoch;
    {
        const uint32_t kb = fb + wq * 3072;
        const uint32_t kl = kb + lane * 16;
        uint32_t Af[4][4];
        float sr, si, z1r, z1i, z2r, z2i, z4r, z4i, hr, hi_;
        {
            const float dt = bfr(ex2f(PV(pLdt) * 1.4426950408889634f));
            const float e2 = dt * PV(pv[0]) * 1.4426950408889634f, an = dt * PV(pv[1]);
            float ar, ai, br, bi, cr, ci, dr, di;
            { const float m = ex2f(e2 * 8.f); ar = m * __cosf(an * 8.f); ai = m * __sinf(an * 8.f); }
            csq(br, bi, ar, ai); csq(cr, ci, br, bi); csq(dr, di, cr, ci);
            const H2C m4 = splat(cr, ci);
            {
                float r3, i3;
                cmul(r3, i3, ar, ai, br, bi);
                expand4(kl, kl + 1024, pack_f16(1.f, ar), pack_f16(br, r3), pack_f16(0.f, ai), pack_f16(bi, i3), m4);
            }
            expand8(kl + 512, kl + 1536, dr, di, ar, ai, br, bi, m4);
            { const float m = ex2f(e2); z1r = m * __cosf(an); z1i = -m * __sinf(an); }
            cexp_s(hr, hi_, e2 * 128.f, an * (-128.f * 0.15915494309189535f));
            csq(z2r, z2i, z1r, z1i); csq(z4r, z4i, z2r, z2i);
            const uint32_t dep2 = lds32(sb + SM_P + 4);
#define PW(x) __uint_as_float(__byte_perm(dep2, x, 0x5410))
            cmul(sr, si, PW(pv[4]), PW(pv[5]), dt * PW(pv[2]), dt * PW(pv[3]));
            const unsigned E = min(max(__reduce_max_sync(~0u, __float_as_uint(fmaxf(fmaxf(fabsf(sr), fabsf(si)), fabsf(PW(pD)) * (1.f / 8192.f)))) >> 23, 1u), 253u);
            const float sc = __uint_as_float((254u - E) << 23);
            sr *= sc; si *= -sc;
            sts64(sb + SM_KG + warp * 8, E, __reduce_add_sync(~0u, __float2int_rn(sr * 16777216.f)));
        }
        __syncwarp();
#pragma unroll
        for (int ks = 0; ks < 4; ks++) ldsm4t(Af[ks], kb + (lane >> 3) * 512 + (lane & 7) * 16 + ks * 128);
        STAMP(2);
        const uint32_t la = kb + ((lane >> 3) & 1) * 512 + (lane >> 4) * 128 + (lane & 7) * 16;
        uint32_t b0[4], b1[4], b2[4], b3[4];
        auto ln1 = [&]() {
        mbar_wait(mb + MB_R * 8);
        epoch = lds32(sb + SM_SC + 28) + 1;
        {
            const uint32_t ra = sb + SM_ROW + warp * (D_ * 2);
            const uint4 r0 = lds128(ra + lane * 16), r1 = lds128(ra + 512 + lane * 16);
            const uint32_t rx[9] = {r0.x, r0.y, r0.z, r0.w, r1.x, r1.y, r1.z, r1.w, lds32(ra + 1024 + lane * 4)};
            float a0 = bf_lo(rx[0]), a1 = bf_hi(rx[0]), c0 = a0 * a0, c1 = a1 * a1;
#pragma unroll
            for (int i = 1; i < 9; i++) { const float l = bf_lo(rx[i]), h = bf_hi(rx[i]); a0 += l; a1 += h; c0 = fmaf(l, l, c0); c1 = fmaf(h, h, c1); }
            a0 += a1; c0 += c1;
            float s1 = ((lane & 1) ? c0 : a0) + __shfl_xor_sync(~0u, (lane & 1) ? a0 : c0, 1);
#pragma unroll
            for (int o = 2; o < 32; o <<= 1) s1 += __shfl_xor_sync(~0u, s1, o);
            const float s2 = __shfl_xor_sync(~0u, s1, 1);
            const uint32_t ms = ln_stats(s1, s2);
            const uint32_t p0 = __byte_perm(ms, epoch | 0x8000u, 0x5410), p1 = rsplit(rcpf(bf_hi(ms)));
            if (pub) st_rlx128(st1p, p0, p1, p0, p1);
        }
        mbar_wait(mb + MB_R * 8);
        STAMP(1);
        };
        const uint4* sp = &g_s.st1[(256 * q + tn) * 2];
        uint2 sa, sc;
        auto poll = [&]() { sa = ld_rlx64(sp); sc = ld_rlx64(sp + 16); };
        auto norm = [&]() {
        STAMP(3);
        if (warp < 16) {
            uint32_t va[5], vc[5];
            poll();
            mbar_wait(mb + MB_T * 8);
            {
                const uint32_t xt = sb + SM_XTL + (c & 1) * 16 + (72 * wq + 18 * k + g) * (2 * XW);
                uint4 a4 = lds128(xt + cq * 16), b4 = lds128(xt + cq * 16 + 18 * XW);
                va[0] = a4.x; va[1] = a4.y; va[2] = a4.z; va[3] = a4.w; va[4] = lds32(xt + 64 + cq * 4);
                vc[0] = b4.x; vc[1] = b4.y; vc[2] = b4.z; vc[3] = b4.w; vc[4] = lds32(xt + (64 + 18 * XW) + cq * 4);
            }
            const int d4 = 2 * (lane >> 3) + (lane & 1), d1_ = lane & 7;
            const uint32_t own = SM_U + 128 + q * (UP - YP), oth = SM_XT + 128 + (q & 3) * 16;
            uint32_t a4 = sb + warp * 32 + d4 * YP + (d4 == q ? own : oth) + ((lane & 7) >> 1) * YS;
            uint32_t a1 = sb + warp * 32 + d1_ * YP + (d1_ == q ? own : oth) + 4 * YS + (lane & 8) * 2;
            PIN(a4); PIN(a1);
            uint32_t tag = __byte_perm(epoch | 0x8000u, 0, 0x1010);
            PIN(tag);
            mbar_wait(mb + MB_T * 8);
            int n = 0;
            while (__byte_perm(sa.x, sc.x, 0x7632) != tag && ++n < SPIN_LIMIT) poll();
            STAMP(4);
#pragma unroll
            for (int i = 0; i < 5; i++) {
                va[i] = norm2(va[i], sa.x, sa.y); va[i] = pack_f16(bf_lo(va[i]), bf_hi(va[i]));
                vc[i] = norm2(vc[i], sc.x, sc.y); vc[i] = pack_f16(bf_lo(vc[i]), bf_hi(vc[i]));
            }
            stsm4t(a4, va[0], va[1], va[2], va[3]); stsm4t(a4 + 16, vc[0], vc[1], vc[2], vc[3]); stsm2t(a1, va[4], vc[4]);
            bar_arrive(13, 608);
            {
            const uint32_t xh = sb + SM_XTL + (c & 1) * 16 + (9 * g + 144 * (warp & 1) + (warp >> 1)) * (2 * XW);
            const uint4 c4 = lds128(xh + cq * 16), d4_ = lds128(xh + cq * 16 + 144 * XW);
            xa[0] = c4.x; xa[1] = c4.y; xa[2] = c4.z; xa[3] = c4.w; xa[4] = lds32(xh + 64 + cq * 4);
            xb[0] = d4_.x; xb[1] = d4_.y; xb[2] = d4_.z; xb[3] = d4_.w; xb[4] = lds32(xh + (64 + 144 * XW) + cq * 4);
            }
        }
        STAMP(5);
        __syncwarp();
        bar_sync(15, 672);
        Af[0][0] |= lds32(sb + SM_P);
        };
        cmul(sr, si, sr, si, z1r, z1i);
        {
            const H2C h4 = splat(z4r, z4i);
            expand8(kl, kl + 512, sr, si, z1r, z1i, z2r, z2i, h4);
            cmul(sr, si, sr, si, hr, hi_);
            expand8(kl + 1024, kl + 1536, sr, si, z1r, z1i, z2r, z2i, h4);
        }
        __syncwarp();
        ldsm4t(b0, la); ldsm4t(b1, la + 256); ldsm4t(b2, la + 1024); ldsm4t(b3, la + 1280);
        cmul(z1r, z1i, z1r, z1i, hr, hi_);
        cmul(sr, si, sr, si, z1r, z1i);
        expand8(kl, kl + 512, sr, si, z2r, z2i, z4r, z4i, splat(hr, hi_));
        ln1();
        csq(z1r, z1i, z1r, z1i);
        cmul(sr, si, sr, si, z1r, z1i);
        csq(z2r, z2i, hr, hi_);
        expand8(kl + 1024, kl + 1536, sr, si, z4r, z4i, hr, hi_, splat(z2r, z2i));
        csq(z1r, z1i, z1r, z1i);
        cmul(sr, si, sr, si, z1r, z1i);
        csq(z4r, z4i, z2r, z2i);
        expand8(kl + 2048, kl + 2560, sr, si, hr, hi_, z2r, z2i, splat(z4r, z4i));
        norm();
        {
            uint32_t c0[4], c1[4], c2[4], c3[4], e0[4], e1[4];
            float t[6][4];
            ldsm4t(c0, la); ldsm4t(c2, la + 1024);
            mma_f16_z(t[0], Af[0], b0[0], b0[1]);
            const uint32_t lb = la | (__float_as_uint(t[0][0]) & zero);
            mma_f16_z(t[1], Af[0], b2[0], b2[1]); mma_f16_z(t[2], Af[0], c0[0], c0[1]); mma_f16_z(t[3], Af[0], c2[0], c2[1]);
            ldsm4t(e0, lb + 2048); ldsm4t(c1, lb + 256); ldsm4t(c3, lb + 1280); ldsm4t(e1, lb + 2304);
            mma_f16(t[0], Af[1], b0[2], b0[3]); mma_f16(t[1], Af[1], b2[2], b2[3]); mma_f16(t[2], Af[1], c0[2], c0[3]); mma_f16(t[3], Af[1], c2[2], c2[3]);
            mma_f16(t[0], Af[2], b1[0], b1[1]); mma_f16(t[1], Af[2], b3[0], b3[1]);
            mma_f16_z(t[4], Af[0], e0[0], e0[1]); mma_f16_z(t[5], Af[1], e0[2], e0[3]);
            mma_f16(t[2], Af[2], c1[0], c1[1]); mma_f16(t[3], Af[2], c3[0], c3[1]);
            mma_f16(t[4], Af[2], e1[0], e1[1]); mma_f16(t[5], Af[3], e1[2], e1[3]);
            mma_f16(t[0], Af[3], b1[2], b1[3]); mma_f16(t[1], Af[3], b3[2], b3[3]); mma_f16(t[2], Af[3], c1[2], c1[3]); mma_f16(t[3], Af[3], c3[2], c3[3]);
#pragma unroll
            for (int i = 0; i < 4; i++) sts64(kb + lane * 8 + 1024 + i * 256, pack_f16(t[i][1], t[i][0]), pack_f16(t[i][3], t[i][2]));
            sts64(kb + lane * 8 + 2048, pack_f16(t[4][1] + t[5][1], t[4][0] + t[5][0]), pack_f16(t[4][3] + t[5][3], t[4][2] + t[5][2]));
        }
        bar_sync(1 + k, 128);
        const uint4 m01 = lds128(sb + SM_KG + k * 32), m23 = lds128(sb + SM_KG + k * 32 + 16);
        const unsigned Em = max(max(m01.x, m01.z), max(m23.x, m23.z));
        const float f0 = __uint_as_float(max((int)(127 + m01.x - Em), 0) << 23), f1 = __uint_as_float(max((int)(127 + m01.z - Em), 0) << 23),
                    f2 = __uint_as_float(max((int)(127 + m23.x - Em), 0) << 23), f3 = __uint_as_float(max((int)(127 + m23.z - Em), 0) << 23);
        const uint32_t r0 = pack_f16(f0, f0), r1 = pack_f16(f1, f1), r2 = pack_f16(f2, f2), r3 = pack_f16(f3, f3);
        const int tq = (wq + k) & 3;
        const uint32_t ra = fb + lane * 8 + tq * 256 + 1024;
        const uint2 p0 = lds64(ra), p1 = lds64(ra + 3072), p2 = lds64(ra + 6144), p3 = lds64(ra + 9216);
        uint32_t w0 = hadd2(hfma2(p0.x, r0, hmul2(p1.x, r1)), hfma2(p2.x, r2, hmul2(p3.x, r3)));
        uint32_t w1 = hadd2(hfma2(p0.y, r0, hmul2(p1.y, r1)), hfma2(p2.y, r2, hmul2(p3.y, r3)));
        const bool last = lane == 31;
        uint32_t w4 = 0;
        if (tq < 2) {
            const uint32_t rc = fb + lane * 8 + tq * 4 + 2048;
            w4 = hmul2(hadd2(hfma2(lds32(rc), r0, hmul2(lds32(rc + 3072), r1)), hfma2(lds32(rc + 6144), r2, hmul2(lds32(rc + 9216), r3))), 0x18001800u);
        }
        if (tq < 2) {
            const uint32_t ph = pf + (P_H7 + 16 * tq) + (g & 1) * (2 * P_HS) + cq * 64 + (g >> 1) * 4;
            put16(ph, w4 >> 16); put16(ph + 32, w4);
            const uint32_t pa = pn + (4 + 512 * tq) + lane * 8;
            sts16(pa, w0 >> 16); sts32(pa + 4, w0); sts16(pa + 10, w0);
            sts16(pa + 256, w1 >> 16); sts32(pa + 260, w1); sts16(pa + 266, w1);
            if (last) {
                sts32(sb + SM_SC + k * 4, Em * 0x00800080u);
                put16(tq ? pa + 264 : pn,
                      tq ? w1 : pack_f16(((float)(int)m01.y * f0 + (float)(int)m01.w * f1 + (float)(int)m23.y * f2 + (float)(int)m23.w * f3) * (1.f / 16777216.f)
                                         + __uint_as_float(pD << 16) * __uint_as_float((254u - Em) << 23), 0.f));
            }
        } else if (tq == 2) {
            const uint32_t pa = pn + 258 * 4 + (cq & 1) * 16 + (cq >> 1) * 512 + g * 32;
            if (last) { put16(pf, hmul2(w1, 0x18001800u)); w1 = hadd2(w1, hneg2(__byte_perm(w1, 0, 0x1010))); }
            const uint32_t b0 = __byte_perm(w0, 0, 0x1010), b1 = __byte_perm(w1, 0, 0x1010);
            sts16(pa, w0 >> 16); sts32(pa + 4, w0); sts64(pa + 8, b0, b0); sts16(pa + 18, w0);
            sts16(pa + 256, w1 >> 16); sts32(pa + 260, w1); sts64(pa + 264, b1, b1); sts16(pa + 274, w1);
        } else {
            const uint32_t pa = pf + ((g & 1) ? 3 * P_GS : P_GS) + cq * 32 + (g >> 1) * 4;
            const uint32_t pb = pa + ((g & 1) ? 4 - 3 * P_GS : P_GS);
            w0 = hmul2(w0, 0x18001800u); w1 = hmul2(w1, 0x18001800u);
            put16(pa, w0 >> 16); put16(pb, w0); put16(pa + 16, w1 >> 16); put16(pb + 16, w1);
            if (last) put16(pf + P_H7 + P_HS, w1);
        }
        bar_sync(1 + k, 128);
    }
    STAMP(6);

    asm volatile("barrier.cluster.wait.aligned;" ::: "memory");
    mbar_wait(mb + (MB_X + (k < nslot ? k : 0)) * 8);
    STAMP(7);
    if (k < nslot) {
        const int role = (wq + k) & 3;
        const uint32_t ub = sb + SM_U + k * US + 128;
        if (role) {
            const int r = (3 - role) * 32 + lane;
            const uint32_t a1 = ub + (r & 3) * (2 * UP) + (r >> 2) * 16, a0 = a1 + ((r & 3) ? -2 * UP : 6 * UP - 16);
            const uint4 q0 = lds128(a0), q1 = lds128(a0 + UP), q2 = lds128(a1), q3 = lds128(a1 + UP);
            const uint32_t U[16] = {q0.x, q0.y, q0.z, q0.w, q1.x, q1.y, q1.z, q1.w, q2.x, q2.y, q2.z, q2.w, q3.x, q3.y, q3.z, q3.w};
            uint32_t V[14], Q[14], R4[12], T[8];
#pragma unroll
            for (int i = 2; i < 14; i++) { V[i] = __byte_perm(U[i], U[i + 1], 0x5432); Q[i] = hadd2(U[i], V[i]); }
#pragma unroll
            for (int i = 2; i < 12; i++) R4[i] = hadd2(Q[i], Q[i + 1]);
            const uint32_t rb = fb + r * 16;
#pragma unroll
            for (int i = 0; i < 8; i++) T[i] = hadd2(V[5 + i], Q[6 + i]);
            sts128(rb + F_E3, T[0], T[1], T[2], T[3]); sts128(rb + F_O3 + 16, T[4], T[5], T[6], T[7]);
#pragma unroll
            for (int i = 0; i < 8; i++) T[i] = hadd2(R4[3 + i], U[5 + i]);
            sts128(rb + F_O5, T[0], T[1], T[2], T[3]); sts128(rb + F_E5, T[4], T[5], T[6], T[7]);
            if (role != 1) {
#pragma unroll
                for (int i = 0; i < 8; i++) T[i] = hadd2(T[i], hadd2(V[2 + i], V[5 + i]));
                sts128(rb + F_E7, T[0], T[1], T[2], T[3]); sts128(rb + F_O7, T[4], T[5], T[6], T[7]);
#pragma unroll
                for (int i = 0; i < 8; i++) T[i] = hadd2(R4[2 + i], hadd2(R4[4 + i], U[6 + i]));
                sts128(rb + F_O9, T[0], T[1], T[2], T[3]); sts128(rb + F_E9 + 16, T[4], T[5], T[6], T[7]);
                sts128(rb + F_E2, Q[6], Q[7], Q[8], Q[9]); sts128(rb + F_O2, Q[10], Q[11], Q[12], Q[13]);
            }
        } else if (lane < 8) {
            uint32_t v[5];
#pragma unroll
            for (int i = 0; i < 5; i++) { const int t = 6 + lane + i; v[i] = lds16(ub + 23 * 16 + (t < 16 ? (6 + (t >> 3)) * UP : 16) + (t & 7) * 2); }
            const uint32_t s = hadd2(hadd2(hadd2(v[0], v[1]), hadd2(v[2], v[3])), v[4]);
            sts16(fb + F_O5 + 96 * 16 + lane * 2, s);
            sts32(fb + (lane < 4 ? F_O3 : F_E9 - 16) + lane * 4, 0);
        }
        bar_sync(1 + k, 128);
        float acc[4][4];
        uint32_t Q[4][4];
        {
            const int h = role & 1, part = role >> 1;
            const uint32_t po = pf + (g - 2 * cq) * 4;
            float fa[7][4];
#pragma unroll
            for (int a = 0; a < 7; a++) fa[a][0] = fa[a][1] = fa[a][2] = fa[a][3] = 0.f;
            uint32_t B[3][4];
            Q[0][2] = tid & zero;
#pragma unroll 1
            for (int s = 2 * part + 1; s >= 2 * part; s--) {
#pragma unroll
                for (int i = 0; i < 3; i++) { Q[i][0] = lds32(po + s * P_GS + i * 64); Q[i][1] = lds32(po + s * P_GS + (i * 64 + 32)); }
                const uint32_t ba = fb + lane * 16 + ((s & 1) * F_E3 + (part == h ? 0 : F_O5 + h * 16));
#pragma unroll
                for (int i = 0; i < 3; i++) ldsm4t(B[i], ba + i * 512);
#pragma unroll
                for (int i = 0; i < 3; i++) { Q[i][3] = CP(Q[i][0]); if (i) Q[i][2] = CP(Q[i - 1][1]); }
#pragma unroll
                for (int dl = 0; dl < 3; dl++)
#pragma unroll
                    for (int ap = 0; ap < 6 - dl; ap++) mma_f16(fa[ap + 1 + dl], Q[dl], B[ap >> 1][2 * (ap & 1)], B[ap >> 1][2 * (ap & 1) + 1]);
            }
#pragma unroll 1
            for (int s = role; s == 1; s++) {
                ldsm2t(B[0][0], B[0][1], fb + ((lane & 15) == 15 ? F_O5 : F_O3));
#pragma unroll
                for (int dl = 0; dl < 3; dl++) mma_f16(fa[dl], Q[dl], B[0][0], B[0][1]);
            }
#pragma unroll 1
            for (int s = part; s <= 2 * part; s++) {
#pragma unroll
                for (int i = 0; i < 4; i++) { Q[i][0] = lds32(po + s * P_HS + (P_H7 + i * 64)); Q[i][1] = lds32(po + s * P_HS + (P_H7 + i * 64 + 32)); }
                const uint32_t ba = fb + lane * 16 + (F_E7 + s * 1024 + h * F_H);
                ldsm4t(B[0], ba); ldsm4t(B[1], ba + 512);
#pragma unroll
                for (int i = 0; i < 4; i++) { Q[i][3] = CP(Q[i][0]); if (i) Q[i][2] = CP(Q[i - 1][1]); }
#pragma unroll
                for (int dl = 0; dl < 4; dl++) {
#pragma unroll
                    for (int ap = 0; ap < 4 - dl; ap++) mma_f16(fa[ap + 3 + dl], Q[dl], B[ap >> 1][2 * (ap & 1)], B[ap >> 1][2 * (ap & 1) + 1]);
                    if (s == 1) break;
                }
            }
            const uint32_t da = fb + role * 2048 + (lane & 3) * 512 + (((lane >> 2) ^ ((lane & 3) * 2)) << 4);
            bar_sync(1 + k, 128);
            stsm4(da, 0u, 0u, pack_f16(fa[0][0], fa[0][1]), pack_f16(fa[0][2], fa[0][3]));
#pragma unroll
            for (int i = 1; i < 4; i++)
                stsm4(da + i * 128, pack_f16(fa[2 * i - 1][0], fa[2 * i - 1][1]), pack_f16(fa[2 * i - 1][2], fa[2 * i - 1][3]),
                      pack_f16(fa[2 * i][0], fa[2 * i][1]), pack_f16(fa[2 * i][2], fa[2 * i][3]));
            Q[0][0] = (g == 2 * cq) ? 0x6000u : ((g == 2 * cq + 1) ? 0x60000000u : 0u);
            Q[0][1] = Q[0][0] & zero; Q[0][2] = lane & zero; Q[0][3] = CP(Q[0][0]);
            const uint32_t ra = fb + (lane >> 3) * 2048 + wq * 512 + (((lane & 7) ^ (wq * 2)) << 4);
            bar_sync(1 + k, 128);
#pragma unroll
            for (int i = 0; i < 4; i++) {
                ldsm4(B[0], ra + i * 128);
                mma_f16_z(acc[i], Q[0], hadd2(B[0][0], B[0][2]), hadd2(B[0][1], B[0][3]));
            }
        }
        bar_arrive(6 + k, 160);
        STAMP(8);
        const uint32_t inv = lds32(sb + SM_SC + k * 4);
        uint32_t yd = mapa(sb, 2 * wq) + (SM_XT + 128 + q * YP + k * YS + (k >> 2) * (q >> 1) * 16) + lane * 16;
        PIN(yd);
        {
            uint32_t pp = pn + (16 * (wq - 3) + g - 2 * cq) * 4;
            uint32_t dlo = (((ub + 6 * UP) & 0x3FFFF) >> 4) | ((UP >> 4) << 16);
            uint32_t R[4][4];
            auto loadQ = [&](uint32_t (&X)[4][4], uint32_t prev) {
#pragma unroll
                for (int i = 0; i < 4; i++) { X[i][0] = lds32(pp + i * 64); X[i][1] = lds32(pp + i * 64 + 32); }
                X[0][2] = CP(prev);
#pragma unroll
                for (int i = 0; i < 4; i++) { X[i][3] = CP(X[i][0]); if (i) X[i][2] = CP(X[i - 1][1]); }
                pp += 256;
            };
            auto issue = [&](uint32_t (&X)[4][4]) {
                asm volatile("wgmma.fence.sync.aligned;" ::: "memory");
#pragma unroll
                for (int i = 0; i < 4; i++) wgmma32(acc, X[i], dlo - i * (2 * UP >> 4));
                asm volatile("wgmma.commit_group.sync.aligned;" ::: "memory");
                dlo -= 1;
            };
            loadQ(Q, 0);
#pragma unroll 1
            for (int dl = 0; dl < 4; dl++) {
                issue(Q);
                asm volatile("wgmma.wait_group.sync.aligned 1;" ::: "memory");
                loadQ(R, Q[3][1]);
                issue(R);
                asm volatile("wgmma.wait_group.sync.aligned 1;" ::: "memory");
                loadQ(Q, R[3][1]);
            }
            issue(Q);
            asm volatile("wgmma.wait_group.sync.aligned 0;" ::: "memory");
        }
        const uint32_t pstep = mapa(sb, 1) - mapa(sb, 0), ym = mapa(mb + MB_Y * 8, 2 * wq);
#pragma unroll
        for (int e = 0; e < 2; e++)
            st_async4(yd + e * pstep, bmul2(pack_bf16(acc[0][2 * e], acc[0][2 * e + 1]), inv), bmul2(pack_bf16(acc[1][2 * e], acc[1][2 * e + 1]), inv),
                      bmul2(pack_bf16(acc[2][2 * e], acc[2][2 * e + 1]), inv), bmul2(pack_bf16(acc[3][2 * e], acc[3][2 * e + 1]), inv), ym + e * pstep);
        if (lane == 0) asm volatile("mbarrier.arrive.shared::cta.b64 _, [%0];" :: "r"(mb + MB_Y * 8) : "memory");
    }
    STAMP(9);
    uint32_t ha[5], hb[5];
    if (warp < 16) {
        const uint4 wk = lds128(sb + SM_DW + cq * 16);
        uint32_t sel[5] = {wk.x, wk.y, wk.z, wk.w, lds32(sb + SM_DW + 64 + cq * 4)}, sel2[5];
#pragma unroll
        for (int i = 0; i < 5; i++) {
            if (!(g & 1)) sel[i] = 0x3F803F80u;
            sel2[i] = sel[i]; PIN(sel2[i]);
        }
        const uint32_t y4 = sb + SM_XT + 128 + warp * 32 + (2 * (lane >> 3) + (lane & 1)) * YP + ((lane & 7) >> 1) * YS;
        const uint32_t y1 = sb + SM_XT + 128 + warp * 32 + (lane & 7) * YP + 4 * YS + (lane & 8) * 2 + (lane & 6) * 8;
        uint32_t ao = (256 * q + tn) * 16, hta = sb + SM_HT + tn * 80;
        PIN(ao); PIN(hta);
        mbar_wait(mb + MB_Y * 8);
        STAMP(10);
        float ca[4] = {0.f, 0.f, 0.f, 0.f}, cb[4] = {0.f, 0.f, 0.f, 0.f};
        {
            uint32_t ya[4], yb[4], yc, yd;
            ldsm4t(ya, y4); ldsm4t(yb, y4 + 16); ldsm2t(yc, yd, y1);
#pragma unroll
            for (int i = 0; i < 4; i++) { ha[i] = badd2(xa[i], ya[i]); hb[i] = badd2(xb[i], yb[i]); }
            ha[4] = badd2(xa[4], yc); hb[4] = badd2(xb[4], yd);
        }
        if (nslot != 5) {
            ha[4] = hb[4] = 0;
            if (cq >= 2) ha[0] = ha[1] = ha[2] = ha[3] = hb[0] = hb[1] = hb[2] = hb[3] = 0;
        }
#pragma unroll
        for (int i = 0; i < 5; i++) { mma_bf16_k8(ca, ha[i], sel[i], ha[i]); mma_bf16_k8(cb, hb[i], sel2[i], hb[i]); }
        if (!(g & 1)) { ca[1] = ca[0]; cb[1] = cb[0]; }
        if (cq == (g >> 1)) {
            asm volatile("red.relaxed.gpu.global.add.v4.f32 [%0], {%1,%2,%3,%4};" :: "l"((char*)g_s.acc + ao), "f"(1.0f), "f"(ca[1]), "f"(ca[2]), "f"(ca[3]) : "memory");
            asm volatile("red.relaxed.gpu.global.add.v4.f32 [%0], {%1,%2,%3,%4};" :: "l"((char*)g_s.acc + ao + 128), "f"(1.0f), "f"(cb[1]), "f"(cb[2]), "f"(cb[3]) : "memory");
        }
        sts128(hta + cq * 16, ha[0], ha[1], ha[2], ha[3]); sts32(hta + 64 + cq * 4, ha[4]);
        sts128(hta + cq * 16 + 640, hb[0], hb[1], hb[2], hb[3]); sts32(hta + 704 + cq * 4, hb[4]);
        STAMP(11);
    }
    const int kq = warp / 5, mt = warp - 5 * kq;
    const int mi = lane >> 3, mr = lane & 7;
    const unsigned tk = (unsigned)tid / 72u, ck = tid - tk * 72;
    uint32_t A[9][4];
    auto loadA = [&]() {
        mbar_wait(mb + MB_W1 * 8);
        const uint32_t aa = sb + (mi & 1) * SM_WU + (8 * (mi >> 1) + mr) * 80 + (144 * 80 * kq + mt * 16);
#pragma unroll
        for (int s = 0; s < 9; s++) ldsm4t(A[s], aa + s * 1280);
    };
    const uint32_t par = (lds32(sb + SM_SC + 28) & 1) ? 0u : 0x40004000u;
    uint32_t pk0 = mapa(sb, 2 * cq), go = (ck / 5u + ck) * 16, co = ((q * 8 * NCL + c) * 6 + cq) * 16;
    PIN(pk0); PIN(go); PIN(co);
    if (warp < 8) {
        const float wsum = ldsf(sb + SM_SC + 24);
        const uint32_t idx = 2047 - (512 * ((tid >> 1) & 3) + 128 * ((tid >> 3) & 3) + 64 * (tid & 1) + 8 * q + warp);
        uint4 s; int n = 0;
        do { s = ld_rlx128(&g_s.acc[256 * q + tid]); } while (__uint_as_float(s.x) != (float)NCL && ++n < SPIN_LIMIT);
        STAMP(16);
        const uint32_t ox = __shfl_xor_sync(~0u, (lane & 1) ? s.z : s.w, 1);
        const uint32_t ms = ln_stats(__uint_as_float((lane & 1) ? ox : s.z), __uint_as_float(s.y));
        const float rs = rcpf(bf_hi(ms));
        const uint32_t rb = pack_bf16(0.f, fmaf(-bf_lo(ms), wsum, __uint_as_float((lane & 1) ? s.w : ox)) * rs);
        const uint32_t key = (((rb ^ (((int)rb >> 31) | 0x80000000u)) >> 16) << 11) | idx;
        sts32(sb + SM_KEY + tid * 4, key);
        __syncwarp();
        const uint32_t rank = rank4<8, 16>(sb + SM_KEY + warp * 128, key);
        asm volatile("{ .reg .pred p; setp.lt.u32 p, %0, 8; @p st.shared.u32 [%1], %2; }" :: "r"(rank), "r"(sb + SM_CAND + warp * 32 + rank * 4), "r"(key) : "memory");
        sts64(sb + SM_ST + tid * 8, ms, rsplit(rs));
    } else { mbar_wait(mb + MB_Y * 8); loadA(); }
    if (warp < 16) {
        STAMP(17);
        bar_sync(12, 512);
        STAMP(18);
        if (warp < 8) {
            const uint32_t mk = lds32(sb + SM_CAND + (tid >> 2) * 4);
            uint32_t rank = rank4<4, 64>(sb + SM_CAND + cq * 16, mk);
            rank += __shfl_xor_sync(~0u, rank, 1); rank += __shfl_xor_sync(~0u, rank, 2);
            if (rank < 8) {
                const uint32_t pk1 = pk0 + (mapa(sb, 1) - mapa(sb, 0));
                st_async1(pk0 + (SM_RK + q * 32) + rank * 4, mk, pk0 + (SM_MB + MB_KEY * 8));
                st_async1(pk1 + (SM_RK + q * 32) + rank * 4, mk, pk1 + (SM_MB + MB_KEY * 8));
                const uint32_t t = tslot(~mk | ((pk1 + rank * 4) & zero));
                const uint2 sv = lds64(sb + SM_ST + t * 8);
                const uint4 hv = lds128(sb + SM_HT + t * 80 + cq * 16);
                const uint32_t h4 = lds32(sb + SM_HT + t * 80 + 64 + cq * 4);
                const uint32_t rr = bmul2(sv.y, 0x3C803C80u);
                char* const dp = (char*)g_s.cand + (co + rank * 1440);
                st_rlx128(dp, (norm2(hv.x, sv.x, rr) & 0xBFFFBFFFu) | par, (norm2(hv.y, sv.x, rr) & 0xBFFFBFFFu) | par,
                          (norm2(hv.z, sv.x, rr) & 0xBFFFBFFFu) | par, (norm2(hv.w, sv.x, rr) & 0xBFFFBFFFu) | par);
                asm volatile("st.relaxed.gpu.global.u32 [%0], %1;" :: "l"((char*)g_s.cand + (co + rank * 1440 + 64 - cq * 12)), "r"((norm2(h4, sv.x, rr) & 0xBFFFBFFFu) | par) : "memory");
            }
            __syncwarp();
        }
        {
            const uint2 sa = lds64(sb + SM_ST + tn * 8), sbb = lds64(sb + SM_ST + tn * 8 + 64);
#pragma unroll
            for (int i = 0; i < 5; i++) { ha[i] = badd2(ha[i], norm2(ha[i], sa.x, sa.y)); hb[i] = badd2(hb[i], norm2(hb[i], sbb.x, sbb.y)); }
            const bool hf = (c & 1) && cq == 0;
            const uint32_t o16 = sb + SM_XT + (hf ? 16384 + tn * 16 : tn * 64 + (cq - (c & 1)) * 16), o4 = sb + SM_XT + ((c & 1) ? tn * 64 + 48 : 16384 + tn * 16) + cq * 4;
            sts128(o16, ha[0], ha[1], ha[2], ha[3]); sts32(o4, ha[4]);
            sts128(o16 + (hf ? 128 : 512), hb[0], hb[1], hb[2], hb[3]); sts32(o4 + ((c & 1) ? 512 : 128), hb[4]);
        }
        if (warp >= 8) {
            STAMP(19);
            mbar_wait(mb + MB_KEY * 8);
            STAMP(20);
            const uint32_t mk = lds32(sb + SM_RK - 256 + (tid >> 2) * 4);
            uint32_t rank = rank4<4, 64>(sb + SM_RK + cq * 16, mk);
            rank += __shfl_xor_sync(~0u, rank, 1); rank += __shfl_xor_sync(~0u, rank, 2);
            if (rank < 8) sts64(sb + SM_SEL + rank * 8, mk, ((tid >> 2) - 64) * 1440);
        }
    }
    bar_sync(11, 640);
    STAMP(12);

    const char* gp = (const char*)g_s.cand + (go + lds32(sb + SM_SEL + 4 + (tk & 7) * 8));
    uint4 hv = ld_rlx128(gp);
    if (warp < 8) loadA();
    const uint32_t ft = (unsigned)tid / 24u, fj = 24 * q + tid - ft * 24;
    const uint32_t key = lds32(sb + SM_SEL + (ft & 7) * 8), k16 = key << 5;
    float sig = bfr(rcpf(1.f + ex2f(__uint_as_float((k16 ^ (~((int)k16 >> 31) | 0x80000000u)) & 0xFFFF0000u) * -1.4426950408889634f)));
    uint32_t ra2 = sb + SM_RED2 + tid * 12 + ft * 16, fo = (ft * 192 + fj) * 16, oo = ((~key & 2047) * D_ + 3 * fj) * 2;
    uint32_t bx = sb + SM_XS + mr * 1168 + mi * 16 + 288 * kq, gd = mapa(sb, kq * (8 / NRED)) + (SM_GU + (q * nslot + mt) * 128) + lane * 4;
    PIN(ra2); PIN(fo); PIN(oo); PIN(bx); PIN(gd);
    asm volatile("" : "+f"(sig));
    {
        if (warp < 18) {
            int n = 0;
            while (true) {
                sts128(sb + SM_XS + tk * 16 + tid * 16, hv.x ^ par, hv.y ^ par, hv.z ^ par, hv.w ^ par);
                if (!__any_sync(~0u, ((hv.x ^ par) | (hv.y ^ par) | (hv.z ^ par) | (hv.w ^ par)) & 0x40004000u) || ++n >= SPIN_LIMIT) break;
                hv = ld_rlx128(gp);
            }
        }
    }
    bar_sync(14, 768);
    STAMP(13);
    {
        float c0[4] = {0.f, 0.f, 0.f, 0.f}, c1[4] = {0.f, 0.f, 0.f, 0.f}, c2[4] = {0.f, 0.f, 0.f, 0.f};
        uint32_t b[5][4];
#pragma unroll
        for (int s = 0; s < 4; s++) ldsm4(b[s], bx + s * 64);
        asm volatile("ldmatrix.sync.aligned.m8n8.x2.shared.b16 {%0,%1}, [%2];" : "=r"(b[4][0]), "=r"(b[4][1]) : "r"(bx + 256) : "memory");
        mma_bf16(c0, A[0][0], A[0][1], A[0][2], A[0][3], b[0][0], b[0][1]);
        mma_bf16(c1, A[1][0], A[1][1], A[1][2], A[1][3], b[0][2], b[0][3]);
        mma_bf16(c2, A[2][0], A[2][1], A[2][2], A[2][3], b[1][0], b[1][1]);
        mma_bf16(c0, A[3][0], A[3][1], A[3][2], A[3][3], b[1][2], b[1][3]);
        mma_bf16(c1, A[4][0], A[4][1], A[4][2], A[4][3], b[2][0], b[2][1]);
        mma_bf16(c2, A[5][0], A[5][1], A[5][2], A[5][3], b[2][2], b[2][3]);
        mma_bf16(c0, A[6][0], A[6][1], A[6][2], A[6][3], b[3][0], b[3][1]);
        mma_bf16(c1, A[7][0], A[7][1], A[7][2], A[7][3], b[3][2], b[3][3]);
        mma_bf16(c2, A[8][0], A[8][1], A[8][2], A[8][3], b[4][0], b[4][1]);
        sts128f(sb + SM_RED + tid * 16, c0[0] + c1[0] + c2[0], c0[1] + c1[1] + c2[1], c0[2] + c1[2] + c2[2], c0[3] + c1[3] + c2[3]);
    }
    bar_sync(1 + mt, 128);
    STAMP(21);
    if (mt < nslot && kq < NRED) {
        const uint32_t ra = sb + SM_RED + mt * 512 + lane * 16;
        const float4 p0 = lds128f(ra), p1 = lds128f(ra + 2560), p2 = lds128f(ra + 5120), p3 = lds128f(ra + 7680);
        const float g0 = bfr(((p0.x + p1.x) + (p2.x + p3.x)) * 64.f), g1 = bfr(((p0.y + p1.y) + (p2.y + p3.y)) * 64.f);
        const uint32_t sg = pack_bf16(g0 * rcpf(1.f + ex2f(g0 * -1.4426950408889634f)), g1 * rcpf(1.f + ex2f(g1 * -1.4426950408889634f)));
        const uint32_t gu = bmul2(sg, pack_bf16(((p0.z + p1.z) + (p2.z + p3.z)) * 64.f, ((p0.w + p1.w) + (p2.w + p3.w)) * 64.f));
        const uint32_t pstep = mapa(sb, 1) - mapa(sb, 0), gm = mapa(mb + MB_GU * 8, kq * (8 / NRED));
#pragma unroll
        for (int i = 0; i < 8 / NRED; i++) st_async1(gd + i * pstep, gu, gm + i * pstep);
    }
    mbar_wait(mb + MB_W2 * 8);
    {
        const uint32_t aa = sb + (8 * (mi >> 1) + mr) * 144 + (mi & 1) * 16 + (SM_FAR + 2304 * kq + mt * 32);
#pragma unroll
        for (int s = 0; s < 5; s++) ldsm4t(A[s], aa + s * FAR_SZ);
    }
    {
        uint32_t ba = sb + (SM_GU + 256 * kq) + (lane & 15) * 16 + (lane >> 4) * 1024, wa = sb + (SM_RED2 + kq * 2432 + mt * 64) + g * 4 + cq * 608;
        PIN(ba); PIN(wa);
        STAMP(22);
        mbar_wait(mb + MB_GU * 8);
        STAMP(23);
        float c0[4] = {0.f, 0.f, 0.f, 0.f}, c1[4] = {0.f, 0.f, 0.f, 0.f}, c2[4] = {0.f, 0.f, 0.f, 0.f};
        uint32_t b[2][4], b8, b9;
        ldsm4t(b[0], ba); ldsm4t(b[1], ba + 2048); ldsm2t(b8, b9, ba + 4096);
        mma_bf16(c0, A[0][0], A[0][1], A[0][2], A[0][3], b[0][0], b[0][1]);
        mma_bf16(c1, A[1][0], A[1][1], A[1][2], A[1][3], b[0][2], b[0][3]);
        if (nslot == 5) {
            mma_bf16(c2, A[4][0], A[4][1], A[4][2], A[4][3], b8, b9);
            mma_bf16(c0, A[2][0], A[2][1], A[2][2], A[2][3], b[1][0], b[1][1]);
            mma_bf16(c1, A[3][0], A[3][1], A[3][2], A[3][3], b[1][2], b[1][3]);
        }
        stsf(wa, c0[0] + c1[0] + c2[0]); stsf(wa + 304, c0[1] + c1[1] + c2[1]);
        if (mt < 4) { stsf(wa + 32, c0[2] + c1[2] + c2[2]); stsf(wa + 336, c0[3] + c1[3] + c2[3]); }
    }
    if (warp < 6) {
        float v[3];
        bar_sync(6, 640);
        STAMP(14);
#pragma unroll
        for (int i = 0; i < 3; i++) v[i] = ((ldsf(ra2 + i * 4) + ldsf(ra2 + i * 4 + 2432)) + (ldsf(ra2 + i * 4 + 4864) + ldsf(ra2 + i * 4 + 7296))) * sig;
        finish(prm, fo, oo, v, 3.f);
    } else bar_arrive(6, 640);
    STAMP(15);
}

typedef __nv_bfloat16 bf16;
__device__ bf16 f_n[L_ * D_], f_h[L_ * D_];
__device__ float f_k[D_ * L_], f_r[L_], f_gu[8 * F_];
__device__ int f_idx[8];
__device__ __forceinline__ float b2f(bf16 v) { return __bfloat162float(v); }
__global__ void fb_ln(const bf16* in, const bf16* wr, bf16* out) {
    const int t = blockIdx.x * 8 + (threadIdx.x >> 5), lane = threadIdx.x & 31;
    const bf16* r = (in ? in : f_h) + t * D_;
    float s1 = 0.f, s2 = 0.f, s3 = 0.f;
    for (int i = lane; i < D_; i += 32) s1 += b2f(r[i]);
    for (int o = 16; o; o >>= 1) s1 += __shfl_xor_sync(~0u, s1, o);
    for (int i = lane; i < D_; i += 32) { const float d = b2f(r[i]) - s1 / D_; s2 += d * d; }
    for (int o = 16; o; o >>= 1) s2 += __shfl_xor_sync(~0u, s2, o);
    const float m = bfr(s1 / D_), sd = bfr(sqrtf(bfr(bfr(s2 / D_) + 1e-5f)));
    for (int i = lane; i < D_; i += 32) {
        const float v = bfr(bfr(b2f(r[i]) - m) / sd);
        f_n[t * D_ + i] = __float2bfloat16(v);
        if (!in) { s3 += v * b2f(wr[i]); out[t * D_ + i] = __float2bfloat16(b2f(r[i]) + v); }
    }
    for (int o = 16; o; o >>= 1) s3 += __shfl_xor_sync(~0u, s3, o);
    f_r[t] = bfr(s3);
}
__global__ void fb_taps(Params p) {
    const int d = blockIdx.x >> 3, l = (blockIdx.x & 7) * 256 + threadIdx.x;
    const float dt = bfr(expf(bf_lo(p.logdt[d]))), lf = bfr((float)l);
    float k = 0.f;
    for (int n = d * 128; n < d * 128 + 128; n++) {
        float wr, wi, sn, cs;
        cmul(wr, wi, bf_lo(p.prm6[4][n]), bf_lo(p.prm6[5][n]), dt * bf_lo(p.prm6[2][n]), dt * bf_lo(p.prm6[3][n]));
        sincosf(dt * bf_lo(p.prm6[1][n]) * lf, &sn, &cs);
        k += expf(dt * bf_lo(p.prm6[0][n]) * lf) * (wr * cs - wi * sn);
    }
    f_k[l * D_ + d] = k;
}
__global__ void fb_conv(Params p) {
    const int t = blockIdx.x, d = threadIdx.x;
    float y = 0.f;
    for (int l = 0; l <= t; l++) y += f_k[l * D_ + d] * b2f(f_n[(t - l) * D_ + d]);
    f_h[t * D_ + d] = __float2bfloat16(bf_lo(p.x[t * D_ + d]) + bfr(bfr(y) + bfr(b2f(f_n[t * D_ + d]) * bf_lo(p.dskip[d]))));
}
__global__ void fb_top() {
    const int t = blockIdx.x * 256 + threadIdx.x;
    int rank = 0;
    for (int j = 0; j < L_; j++) rank += f_r[j] > f_r[t] || (f_r[j] == f_r[t] && j < t);
    if (rank < 8) f_idx[rank] = t;
}
__global__ void fb_ffn1(const bf16* wg, const bf16* wu) {
    const int f = blockIdx.x * 256 + threadIdx.x, j = blockIdx.y;
    float g = 0.f, u = 0.f;
    for (int i = 0; i < D_; i++) { const float v = b2f(f_n[f_idx[j] * D_ + i]); g += v * b2f(wg[i * F_ + f]); u += v * b2f(wu[i * F_ + f]); }
    g = bfr(g);
    f_gu[j * F_ + f] = bfr(bfr(g / (1.f + expf(-g))) * bfr(u));
}
__global__ void fb_ffn2(const bf16* wd, bf16* out) {
    const int d = threadIdx.x, j = blockIdx.x, t = f_idx[j];
    float y = 0.f;
    for (int f = 0; f < F_; f++) y += f_gu[j * F_ + f] * b2f(wd[f * D_ + d]);
    out[t * D_ + d] = __float2bfloat16(b2f(f_h[t * D_ + d]) + bfr(b2f(f_n[t * D_ + d]) + bfr(bfr(y) * bfr(1.f / (1.f + expf(-f_r[t]))))));
}

typedef CUresult (*EncodeFn)(CUtensorMap*, CUtensorMapDataType, cuuint32_t, void*, const cuuint64_t*, const cuuint64_t*,
                             const cuuint32_t*, const cuuint32_t*, CUtensorMapInterleave, CUtensorMapSwizzle,
                             CUtensorMapL2promotion, CUtensorMapFloatOOBfill);

void make_map(EncodeFn fn, CUtensorMap* tm, const void* p, int cols, int rows, int bc, int br) {
    cuuint64_t dims[2] = {(cuuint64_t)cols, (cuuint64_t)rows};
    cuuint64_t strides[1] = {(cuuint64_t)cols * 2};
    cuuint32_t box[2] = {(cuuint32_t)bc, (cuuint32_t)br};
    cuuint32_t es[2] = {1, 1};
    fn(tm, CU_TENSOR_MAP_DATA_TYPE_BFLOAT16, 2, const_cast<void*>(p), dims, strides, box, es, CU_TENSOR_MAP_INTERLEAVE_NONE,
       CU_TENSOR_MAP_SWIZZLE_NONE, CU_TENSOR_MAP_L2_PROMOTION_L2_128B, CU_TENSOR_MAP_FLOAT_OOB_FILL_NONE);
}

void make_map3(EncodeFn fn, CUtensorMap* tm, const void* p) {
    cuuint64_t dims[5] = {(cuuint64_t)D_, 64, 2, 4, 4};
    cuuint64_t strides[4] = {(cuuint64_t)D_ * 2, (cuuint64_t)D_ * 128, (cuuint64_t)D_ * 1024, (cuuint64_t)D_ * 256};
    cuuint32_t box[5] = {XW, 9, 2, 4, 4};
    cuuint32_t es[5] = {1, 1, 1, 1, 1};
    fn(tm, CU_TENSOR_MAP_DATA_TYPE_BFLOAT16, 5, const_cast<void*>(p), dims, strides, box, es, CU_TENSOR_MAP_INTERLEAVE_NONE,
       CU_TENSOR_MAP_SWIZZLE_NONE, CU_TENSOR_MAP_L2_PROMOTION_NONE, CU_TENSOR_MAP_FLOAT_OOB_FILL_NONE);
}

void make_map5(EncodeFn fn, CUtensorMap* tm, const void* p, int bc) {
    cuuint64_t dims[5] = {(cuuint64_t)D_, 2, 4, 4, 64};
    cuuint64_t strides[4] = {(cuuint64_t)D_ * 128, (cuuint64_t)D_ * 1024, (cuuint64_t)D_ * 256, (cuuint64_t)D_ * 2};
    cuuint32_t box[5] = {(cuuint32_t)bc, 2, 4, 4, 8};
    cuuint32_t es[5] = {1, 1, 1, 1, 1};
    fn(tm, CU_TENSOR_MAP_DATA_TYPE_BFLOAT16, 5, const_cast<void*>(p), dims, strides, box, es, CU_TENSOR_MAP_INTERLEAVE_NONE,
       CU_TENSOR_MAP_SWIZZLE_NONE, CU_TENSOR_MAP_L2_PROMOTION_NONE, CU_TENSOR_MAP_FLOAT_OOB_FILL_NONE);
}

}

extern "C" void kernel_launch(void* const* d_in, const int* in_sizes, int n_in, void* d_out, int out_size) {
    (void)in_sizes; (void)n_in; (void)out_size;
    void* fp = nullptr;
    cudaDriverEntryPointQueryResult qr;
    cudaGetDriverEntryPoint("cuTensorMapEncodeTiled", &fp, cudaEnableDefault, &qr);
    EncodeFn fn = (EncodeFn)fp;
    CUtensorMap tmG, tmU, tmD, tmO, tmX, tmH;
    make_map3(fn, &tmX, d_in[0]);
    make_map(fn, &tmG, d_in[11], F_, D_, 40, 48);
    make_map(fn, &tmU, d_in[12], F_, D_, 40, 48);
    make_map(fn, &tmD, d_in[13], D_, F_, 72, 64);
    make_map5(fn, &tmO, d_out, 32);
    make_map5(fn, &tmH, d_out, 8);
    Params p;
    p.x = (const unsigned short*)d_in[0];
    for (int i = 0; i < 6; i++) p.prm6[i] = (const unsigned short*)d_in[1 + i];
    p.logdt = (const unsigned short*)d_in[7]; p.dskip = (const unsigned short*)d_in[8];
    p.wr = (const unsigned short*)d_in[10];
    p.out = (__nv_bfloat16*)d_out;
    p.zero = 0;
    cudaGetSymbolAddress((void**)&p.gs, g_s);
    cudaFuncSetAttribute(fused_kernel, cudaFuncAttributeMaxDynamicSharedMemorySize, SM_TOTAL);
    static int nclusters = -1;
    if (nclusters < 0) {
        cudaLaunchConfig_t cfg = {};
        cudaLaunchAttribute at;
        at.id = cudaLaunchAttributeClusterDimension; at.val.clusterDim.x = CS; at.val.clusterDim.y = 1; at.val.clusterDim.z = 1;
        cfg.gridDim = dim3(NCTA); cfg.blockDim = dim3(NTHR); cfg.dynamicSmemBytes = SM_TOTAL; cfg.attrs = &at; cfg.numAttrs = 1;
        if (cudaOccupancyMaxActiveClusters(&nclusters, fused_kernel, &cfg) != cudaSuccess) { (void)cudaGetLastError(); nclusters = NCL; }
    }
    if (nclusters >= NCL && !FORCE_FALLBACK) {
        fused_kernel<<<NCTA, NTHR, SM_TOTAL>>>(p, tmG, tmU, tmD, tmO, tmX, tmH);
        return;
    }
    fb_ln<<<L_ / 8, 256>>>((const bf16*)d_in[0], nullptr, nullptr);
    fb_taps<<<D_ * 8, 256>>>(p);
    fb_conv<<<L_, D_>>>(p);
    fb_ln<<<L_ / 8, 256>>>(nullptr, (const bf16*)d_in[10], p.out);
    fb_top<<<L_ / 256, 256>>>();
    fb_ffn1<<<dim3(F_ / 256, 8), 256>>>((const bf16*)d_in[11], (const bf16*)d_in[12]);
    fb_ffn2<<<8, D_>>>((const bf16*)d_in[13], p.out);
}
```

```cpp
#include <cuda_runtime.h>
#include <cuda_bf16.h>
#include <cuda_fp16.h>
#include <cuda.h>
#include <stdint.h>

namespace {

constexpr int L_ = 2048, D_ = 576, F_ = 4608;
constexpr int NCL = 15, CS = 8, NCTA = NCL * CS, NTHR = 768;
#define FORCE_FALLBACK 0
constexpr int XW = 48, NRED = 2;
constexpr int SPIN_LIMIT = 1 << 22;

constexpr int SM_WG   = 0;
constexpr int SM_WU   = 46080;
constexpr int YP = 3392, YS = 656;
constexpr int UP = 3280, US = 656;
constexpr int SM_XT   = 92160;
constexpr int SM_U    = SM_XT + 8 * YP;
constexpr int SM_FAR  = SM_U + 8 * UP;
constexpr int FAR_SZ  = 12416;
constexpr int F_E5 = 0, F_O5 = 1536, F_E3 = 3088, F_O3 = 4624, F_E7 = 6176, F_E2 = F_E7 + 1024, F_E9 = F_E7 + 2048,
              F_H = 3088, F_O7 = F_E7 + F_H, F_O2 = F_E2 + F_H, F_O9 = F_E9 + F_H;
constexpr int SM_P    = SM_FAR + 5 * FAR_SZ;
constexpr int PN_SZ = 584 * 4, SM_PN = SM_P + 65 * 4;
constexpr int P_GS = 50 * 4, P_H7 = 200 * 4, P_HS = 74 * 4;
constexpr int PF_SZ = (200 + 222) * 4, SM_PF = SM_PN + 5 * PN_SZ + 36;
constexpr int SM_MISC = SM_PF + 5 * PF_SZ;
constexpr int SM_ST   = SM_MISC;
constexpr int SM_RK   = SM_ST + 2048;
constexpr int SM_SEL  = SM_RK + 256;
constexpr int SM_KG   = SM_SEL + 64;
constexpr int SM_SC   = SM_KG + 160;
constexpr int SM_DW   = SM_SC + 32;
constexpr int SM_MB   = SM_DW + 160;
constexpr int SM_TOTAL = SM_MB + 128;
constexpr int SM_ROW  = SM_XT - 20736;
constexpr int SM_XTL  = SM_ROW - 576 * XW;
constexpr int SM_RED2 = SM_WG;
constexpr int SM_HT   = SM_P - 512;
constexpr int SM_KEY  = SM_FAR + 10240 + 128;
constexpr int SM_CAND = SM_KEY + 1024;
constexpr int SM_XS   = SM_U;
constexpr int SM_GU   = SM_XS + 9344;
constexpr int SM_RED  = SM_GU + 5632;
static_assert(F_O9 + 1024 <= FAR_SZ && FAR_SZ % 128 == 0, "far overflow");
static_assert(SM_RED + 10240 <= SM_FAR && SM_HT + 20496 <= SM_MISC, "alias overflow");
static_assert(SM_TOTAL <= 232448, "smem overflow");
static_assert(SM_FAR % 128 == 0 && SM_XT % 128 == 0 && SM_XTL % 128 == 0 && SM_P % 16 == 0 && SM_MISC % 16 == 0 && SM_MB % 8 == 0, "align");

enum { MB_X = 0, MB_W1 = 5, MB_W2 = 6, MB_KEY = 7, MB_GU = 8, MB_Y = 9, MB_OUT = 10, MB_T = 11, MB_R = 12 };

struct __align__(128) Scratch {
    unsigned epoch, zcnt, pad[30];
    uint4  st1[L_ * 2];
    float4 acc[L_];
    uint4  cand[64 * NCL * 6];
    float4 fin[8 * 192 + 24];
};
__device__ Scratch g_s;
#define STAMP(i)

__device__ __forceinline__ uint32_t mapa(uint32_t a, uint32_t r) { uint32_t d; asm("mapa.shared::cluster.u32 %0, %1, %2;" : "=r"(d) : "r"(a), "r"(r)); return d; }
__device__ __forceinline__ void mbar_wait(uint32_t mb) {
    asm volatile("{ .reg .pred p, q; .reg .u32 n; mov.u32 n, 0;\n"
                 "W_%=: mbarrier.try_wait.parity.shared::cta.b64 p, [%0], 0; add.u32 n, n, 1; setp.lt.and.u32 q, n, 65536, !p; @q bra W_%=; }" :: "r"(mb) : "memory");
}
__device__ __forceinline__ void arm(uint32_t mb, uint32_t bytes) { asm volatile("mbarrier.arrive.expect_tx.shared::cta.b64 _, [%0], %1;" :: "r"(mb), "r"(bytes) : "memory"); }
__device__ __forceinline__ void bar_sync(int id, int n) { asm volatile("bar.sync %0, %1;" :: "r"(id), "r"(n) : "memory"); }
__device__ __forceinline__ void bar_arrive(int id, int n) { asm volatile("bar.arrive %0, %1;" :: "r"(id), "r"(n) : "memory"); }
__device__ __forceinline__ uint32_t lds16(uint32_t a) { unsigned short v; asm volatile("ld.shared.u16 %0, [%1];" : "=h"(v) : "r"(a) : "memory"); return v; }
__device__ __forceinline__ uint32_t lds32(uint32_t a) { uint32_t v; asm volatile("ld.shared.u32 %0, [%1];" : "=r"(v) : "r"(a) : "memory"); return v; }
__device__ __forceinline__ uint2 lds64(uint32_t a) { uint2 v; asm volatile("ld.shared.v2.u32 {%0,%1}, [%2];" : "=r"(v.x), "=r"(v.y) : "r"(a) : "memory"); return v; }
__device__ __forceinline__ float ldsf(uint32_t a) { float v; asm volatile("ld.shared.f32 %0, [%1];" : "=f"(v) : "r"(a) : "memory"); return v; }
__device__ __forceinline__ uint4 lds128(uint32_t a) { uint4 v; asm volatile("ld.shared.v4.u32 {%0,%1,%2,%3}, [%4];" : "=r"(v.x), "=r"(v.y), "=r"(v.z), "=r"(v.w) : "r"(a) : "memory"); return v; }
__device__ __forceinline__ float4 lds128f(uint32_t a) { float4 v; asm volatile("ld.shared.v4.f32 {%0,%1,%2,%3}, [%4];" : "=f"(v.x), "=f"(v.y), "=f"(v.z), "=f"(v.w) : "r"(a) : "memory"); return v; }
__device__ __forceinline__ void sts16(uint32_t a, uint32_t v) { asm volatile("{ .reg .b16 l, h; mov.b32 {l, h}, %1; st.shared.b16 [%0], l; }" :: "r"(a), "r"(v) : "memory"); }
__device__ __forceinline__ void sts32(uint32_t a, uint32_t v) { asm volatile("st.shared.u32 [%0], %1;" :: "r"(a), "r"(v) : "memory"); }
__device__ __forceinline__ void sts64(uint32_t a, uint32_t x, uint32_t y) { asm volatile("st.shared.v2.u32 [%0], {%1,%2};" :: "r"(a), "r"(x), "r"(y) : "memory"); }
__device__ __forceinline__ void stsf(uint32_t a, float v) { asm volatile("st.shared.f32 [%0], %1;" :: "r"(a), "f"(v) : "memory"); }
__device__ __forceinline__ void sts128(uint32_t a, uint32_t x, uint32_t y, uint32_t z, uint32_t w) { asm volatile("st.shared.v4.u32 [%0], {%1,%2,%3,%4};" :: "r"(a), "r"(x), "r"(y), "r"(z), "r"(w) : "memory"); }
__device__ __forceinline__ void sts128f(uint32_t a, float x, float y, float z, float w) { asm volatile("st.shared.v4.f32 [%0], {%1,%2,%3,%4};" :: "r"(a), "f"(x), "f"(y), "f"(z), "f"(w) : "memory"); }
__device__ __forceinline__ void ldsm4(uint32_t (&r)[4], uint32_t a) { asm volatile("ldmatrix.sync.aligned.m8n8.x4.shared.b16 {%0,%1,%2,%3}, [%4];" : "=r"(r[0]), "=r"(r[1]), "=r"(r[2]), "=r"(r[3]) : "r"(a) : "memory"); }
__device__ __forceinline__ void ldsm4t(uint32_t (&r)[4], uint32_t a) { asm volatile("ldmatrix.sync.aligned.m8n8.x4.trans.shared.b16 {%0,%1,%2,%3}, [%4];" : "=r"(r[0]), "=r"(r[1]), "=r"(r[2]), "=r"(r[3]) : "r"(a) : "memory"); }
__device__ __forceinline__ void ldsm2t(uint32_t& r0, uint32_t& r1, uint32_t a) { asm volatile("ldmatrix.sync.aligned.m8n8.x2.trans.shared.b16 {%0,%1}, [%2];" : "=r"(r0), "=r"(r1) : "r"(a) : "memory"); }
__device__ __forceinline__ void stsm4t(uint32_t a, uint32_t r0, uint32_t r1, uint32_t r2, uint32_t r3) { asm volatile("stmatrix.sync.aligned.m8n8.x4.trans.shared.b16 [%0], {%1,%2,%3,%4};" :: "r"(a), "r"(r0), "r"(r1), "r"(r2), "r"(r3) : "memory"); }
__device__ __forceinline__ void stsm4(uint32_t a, uint32_t r0, uint32_t r1, uint32_t r2, uint32_t r3) { asm volatile("stmatrix.sync.aligned.m8n8.x4.shared.b16 [%0], {%1,%2,%3,%4};" :: "r"(a), "r"(r0), "r"(r1), "r"(r2), "r"(r3) : "memory"); }
__device__ __forceinline__ void stsm2(uint32_t a, uint32_t r0, uint32_t r1) { asm volatile("stmatrix.sync.aligned.m8n8.x2.shared.b16 [%0], {%1,%2};" :: "r"(a), "r"(r0), "r"(r1) : "memory"); }
__device__ __forceinline__ void stsm2t(uint32_t a, uint32_t r0, uint32_t r1) { asm volatile("stmatrix.sync.aligned.m8n8.x2.trans.shared.b16 [%0], {%1,%2};" :: "r"(a), "r"(r0), "r"(r1) : "memory"); }
__device__ __forceinline__ uint4 ldg128(const void* p) { uint4 v; asm volatile("ld.global.nc.v4.u32 {%0,%1,%2,%3}, [%4];" : "=r"(v.x), "=r"(v.y), "=r"(v.z), "=r"(v.w) : "l"(p)); return v; }
__device__ __forceinline__ uint32_t ldg16(const void* p) { unsigned short v; asm volatile("ld.global.nc.u16 %0, [%1];" : "=h"(v) : "l"(p)); return v; }
__device__ __forceinline__ uint32_t opaque(uint32_t v) { uint32_t r; asm volatile("mov.b32 %0, %1;" : "=r"(r) : "r"(v)); return r; }
__device__ __forceinline__ void mma_f16(float (&d)[4], const uint32_t (&a)[4], uint32_t b0, uint32_t b1) {
    asm volatile("mma.sync.aligned.m16n8k16.row.col.f32.f16.f16.f32 {%0,%1,%2,%3}, {%4,%5,%6,%7}, {%8,%9}, {%0,%1,%2,%3};"
        : "+f"(d[0]), "+f"(d[1]), "+f"(d[2]), "+f"(d[3]) : "r"(a[0]), "r"(a[1]), "r"(a[2]), "r"(a[3]), "r"(b0), "r"(b1));
}
__device__ __forceinline__ void mma_f16_z(float (&d)[4], const uint32_t (&a)[4], uint32_t b0, uint32_t b1) {
    asm volatile("mma.sync.aligned.m16n8k16.row.col.f32.f16.f16.f32 {%0,%1,%2,%3}, {%4,%5,%6,%7}, {%8,%9}, {%10,%10,%10,%10};"
        : "=f"(d[0]), "=f"(d[1]), "=f"(d[2]), "=f"(d[3]) : "r"(a[0]), "r"(a[1]), "r"(a[2]), "r"(a[3]), "r"(b0), "r"(b1), "f"(0.f));
}
__device__ __forceinline__ void mma_bf16(float (&d)[4], uint32_t a0, uint32_t a1, uint32_t a2, uint32_t a3, uint32_t b0, uint32_t b1) {
    asm volatile("mma.sync.aligned.m16n8k16.row.col.f32.bf16.bf16.f32 {%0,%1,%2,%3}, {%4,%5,%6,%7}, {%8,%9}, {%0,%1,%2,%3};"
        : "+f"(d[0]), "+f"(d[1]), "+f"(d[2]), "+f"(d[3]) : "r"(a0), "r"(a1), "r"(a2), "r"(a3), "r"(b0), "r"(b1));
}
__device__ __forceinline__ void mma_bf16_k8(float (&d)[4], uint32_t a0, uint32_t a1, uint32_t b0) {
    asm volatile("mma.sync.aligned.m16n8k8.row.col.f32.bf16.bf16.f32 {%0,%1,%2,%3}, {%4,%5}, {%6}, {%0,%1,%2,%3};"
        : "+f"(d[0]), "+f"(d[1]), "+f"(d[2]), "+f"(d[3]) : "r"(a0), "r"(a1), "r"(b0));
}
__device__ __forceinline__ uint32_t pack_f16(float lo, float hi) { uint32_t r; asm("cvt.rn.f16x2.f32 %0, %1, %2;" : "=r"(r) : "f"(hi), "f"(lo)); return r; }
__device__ __forceinline__ uint32_t pack_bf16(float lo, float hi) { uint32_t r; asm("cvt.rn.bf16x2.f32 %0, %1, %2;" : "=r"(r) : "f"(hi), "f"(lo)); return r; }
__device__ __forceinline__ float bf_lo(uint32_t v) { return __uint_as_float(v << 16); }
__device__ __forceinline__ float bf_hi(uint32_t v) { return __uint_as_float(v & 0xFFFF0000u); }
__device__ __forceinline__ float bfr(float x) { return __uint_as_float(pack_bf16(0.f, x)); }
__device__ __forceinline__ uint32_t badd2(uint32_t a, uint32_t b) { uint32_t r; asm("add.rn.bf16x2 %0, %1, %2;" : "=r"(r) : "r"(a), "r"(b)); return r; }
__device__ __forceinline__ uint32_t bmul2(uint32_t a, uint32_t b) { uint32_t r; asm("mul.rn.bf16x2 %0, %1, %2;" : "=r"(r) : "r"(a), "r"(b)); return r; }
__device__ __forceinline__ uint32_t hadd2(uint32_t a, uint32_t b) { uint32_t r; asm("add.rn.f16x2 %0, %1, %2;" : "=r"(r) : "r"(a), "r"(b)); return r; }
__device__ __forceinline__ uint32_t hmul2(uint32_t a, uint32_t b) { uint32_t r; asm("mul.rn.f16x2 %0, %1, %2;" : "=r"(r) : "r"(a), "r"(b)); return r; }
__device__ __forceinline__ uint32_t hfma2(uint32_t a, uint32_t b, uint32_t c) { uint32_t r; asm("fma.rn.f16x2 %0, %1, %2, %3;" : "=r"(r) : "r"(a), "r"(b), "r"(c)); return r; }
__device__ __forceinline__ uint32_t hneg2(uint32_t a) { uint32_t r; asm("neg.f16x2 %0, %1;" : "=r"(r) : "r"(a)); return r; }
__device__ __forceinline__ float rcpf(float x) { float r; asm("rcp.approx.ftz.f32 %0, %1;" : "=f"(r) : "f"(x)); return r; }
__device__ __forceinline__ float sqrta(float x) { float r; asm("sqrt.approx.ftz.f32 %0, %1;" : "=f"(r) : "f"(x)); return r; }
__device__ __forceinline__ float ex2f(float x) { float r; asm("ex2.approx.ftz.f32 %0, %1;" : "=f"(r) : "f"(x)); return r; }
__device__ __forceinline__ void st_async4(uint32_t a, uint32_t x, uint32_t y, uint32_t z, uint32_t w, uint32_t mb) {
    asm volatile("st.async.shared::cluster.mbarrier::complete_tx::bytes.v4.u32 [%0], {%1,%2,%3,%4}, [%5];" :: "r"(a), "r"(x), "r"(y), "r"(z), "r"(w), "r"(mb) : "memory"); }
__device__ __forceinline__ void st_async1(uint32_t a, uint32_t x, uint32_t mb) {
    asm volatile("st.async.shared::cluster.mbarrier::complete_tx::bytes.u32 [%0], %1, [%2];" :: "r"(a), "r"(x), "r"(mb) : "memory"); }
__device__ __forceinline__ unsigned ld_rlx(const void* p) { unsigned v; asm volatile("ld.relaxed.gpu.global.u32 %0, [%1];" : "=r"(v) : "l"(p) : "memory"); return v; }
__device__ __forceinline__ unsigned ld_acq(const void* p) { unsigned v; asm volatile("ld.acquire.gpu.global.u32 %0, [%1];" : "=r"(v) : "l"(p) : "memory"); return v; }
__device__ __forceinline__ uint2 ld_rlx64(const void* p) { unsigned long long v; asm volatile("ld.relaxed.gpu.global.u64 %0, [%1];" : "=l"(v) : "l"(p) : "memory"); return make_uint2((unsigned)v, (unsigned)(v >> 32)); }
__device__ __forceinline__ void st_rlx128(void* p, uint32_t x, uint32_t y, uint32_t z, uint32_t w) {
    asm volatile("st.relaxed.gpu.global.v2.u64 [%0], {%1,%2};" :: "l"(p), "l"((unsigned long long)x | ((unsigned long long)y << 32)), "l"((unsigned long long)z | ((unsigned long long)w << 32)) : "memory"); }
__device__ __forceinline__ uint4 ld_rlx128(const void* p) { unsigned long long a, b; asm volatile("ld.relaxed.gpu.global.v2.u64 {%0,%1}, [%2];" : "=l"(a), "=l"(b) : "l"(p) : "memory"); return make_uint4((unsigned)a, (unsigned)(a >> 32), (unsigned)b, (unsigned)(b >> 32)); }
__device__ __forceinline__ void tma2d(uint32_t dst, const CUtensorMap* tm, int x, int y, uint32_t mb) {
    asm volatile("cp.async.bulk.tensor.2d.shared::cluster.global.mbarrier::complete_tx::bytes [%0], [%1, {%3, %4}], [%2];"
                 :: "r"(dst), "l"(tm), "r"(mb), "r"(x), "r"(y) : "memory");
}
__device__ __forceinline__ void cmul(float& xr, float& xi, float ar, float ai, float br, float bi) {
    const float r = fmaf(ar, br, -ai * bi), i = fmaf(ar, bi, ai * br); xr = r; xi = i;
}
__device__ __forceinline__ void csq(float& xr, float& xi, float ar, float ai) {
    const float r = fmaf(ar, ar, -ai * ai), i = (ar + ar) * ai; xr = r; xi = i;
}
__device__ __forceinline__ void cexp_s(float& zr, float& zi, float e2, float turns) {
    const float mag = ex2f(e2), r = (turns - rintf(turns)) * 6.283185307179586f;
    zr = mag * __cosf(r); zi = mag * __sinf(r);
}
__device__ __forceinline__ uint32_t ln_stats(float s1, float s2) {
    const float m = s1 * (1.f / D_);
    const float var = fmaxf(fmaf(s2, 1.f / D_, -m * m), 0.f);
    return pack_bf16(m, sqrta(bfr(bfr(var) + 1e-5f)));
}
__device__ __forceinline__ uint32_t rsplit(float rs) { const float h = bfr(rs); return pack_bf16(h, rs - h); }
__device__ __forceinline__ uint32_t norm2(uint32_t v, uint32_t mx, uint32_t hl) {
    uint32_t r;
    asm("{ .reg .b16 m, h, l, x; .reg .b32 m2, h2, l2, d, t; mov.b32 {m, x}, %2; mov.b32 {h, l}, %3; mov.b32 m2, {m, m}; mov.b32 h2, {h, h}; mov.b32 l2, {l, l};\n"
        "sub.rn.bf16x2 d, %1, m2; mul.rn.bf16x2 t, d, l2; fma.rn.bf16x2 %0, d, h2, t; }" : "=r"(r) : "r"(v), "r"(mx), "r"(hl));
    return r;
}
template <int N, int S>
__device__ __forceinline__ uint32_t rank4(uint32_t a, uint32_t key) {
    uint32_t r0 = 0, r1 = 0, r2 = 0, r3 = 0;
#pragma unroll
    for (int i = 0; i < N; i++) {
        const uint4 o = lds128(a + i * S);
        r0 += (key - o.x) >> 31; r1 += (key - o.y) >> 31; r2 += (key - o.z) >> 31; r3 += (key - o.w) >> 31;
    }
    return (r0 + r1) + (r2 + r3);
}
typedef uint32_t H2C;
__device__ __forceinline__ H2C splat(float r, float i) { return pack_f16(r, i); }
__device__ __forceinline__ void hcmul(uint32_t& xr, uint32_t& xi, uint32_t R, uint32_t I, H2C m) {
    asm("{ .reg .b16 a, b; .reg .b32 a2, b2, t; mov.b32 {a, b}, %4; mov.b32 a2, {a, a}; mov.b32 b2, {b, b};\n"
        "mul.rn.f16x2 t, %3, b2; neg.f16x2 t, t; fma.rn.f16x2 %0, %2, a2, t; mul.rn.f16x2 t, %3, a2; fma.rn.f16x2 %1, %2, b2, t; }"
        : "=&r"(xr), "=r"(xi) : "r"(R), "r"(I), "r"(m));
}
__device__ __forceinline__ void expand4(uint32_t are, uint32_t aim, uint32_t R0, uint32_t R1, uint32_t I0, uint32_t I1, H2C m4) {
    uint32_t R2, I2, R3, I3;
    hcmul(R2, I2, R0, I0, m4); hcmul(R3, I3, R1, I1, m4);
    sts128(are, R0, R1, R2, R3);
    sts128(aim, I0, I1, I2, I3);
}
__device__ __forceinline__ void expand8(uint32_t are, uint32_t aim, float sr, float si, float m1r, float m1i, float m2r, float m2i, H2C m4) {
    float r1, i1, r2, i2, r3, i3;
    cmul(r1, i1, sr, si, m1r, m1i); cmul(r2, i2, sr, si, m2r, m2i); cmul(r3, i3, r1, i1, m2r, m2i);
    expand4(are, aim, pack_f16(sr, r1), pack_f16(r2, r3), pack_f16(si, i1), pack_f16(i2, i3), m4);
}
__device__ __forceinline__ void put16(uint32_t a, uint32_t v) { sts16(a, v); sts16(a + 6, v); }

struct Params {
    const unsigned short *logdt, *dskip, *prm6[6], *x, *wr;
    __nv_bfloat16* out;
    Scratch* gs;
    unsigned zero;
};
__device__ __forceinline__ uint32_t tslot(uint32_t t) { return (t & 7) * 32 + ((t >> 4) & 24) + ((t >> 8) & 6) + ((t >> 6) & 1); }
#define CP(x) ((x) | zero)
#define PIN(x) asm volatile("or.b32 %0, %0, %1;" : "+r"(x) : "r"(zero))
__device__ __forceinline__ void wgmma32(float (&d)[4][4], const uint32_t (&a)[4], uint32_t dlo) {
    asm volatile("{ .reg .b64 ds; mov.b64 ds, {%20, %21};\n"
                 "wgmma.mma_async.sync.aligned.m64n32k16.f32.f16.f16 {%0,%1,%2,%3,%4,%5,%6,%7,%8,%9,%10,%11,%12,%13,%14,%15}, {%16,%17,%18,%19}, ds, 1, 1, 1, 0; }"
        : "+f"(d[0][0]), "+f"(d[0][1]), "+f"(d[0][2]), "+f"(d[0][3]), "+f"(d[1][0]), "+f"(d[1][1]), "+f"(d[1][2]), "+f"(d[1][3]),
          "+f"(d[2][0]), "+f"(d[2][1]), "+f"(d[2][2]), "+f"(d[2][3]), "+f"(d[3][0]), "+f"(d[3][1]), "+f"(d[3][2]), "+f"(d[3][3])
        : "r"(a[0]), "r"(a[1]), "r"(a[2]), "r"(a[3]), "r"(dlo), "n"(128 >> 4));
}

__device__ __forceinline__ void finish(const Params& prm, uint32_t fo, uint32_t oo, const float (&v)[3], float cnt) {
    float x, y, z, w;
    asm volatile("atom.relaxed.gpu.global.add.v4.f32 {%0,%1,%2,%3}, [%4], {%5,%6,%7,%8};" : "=f"(x), "=f"(y), "=f"(z), "=f"(w)
                 : "l"((char*)prm.gs->fin + fo), "f"(v[0]), "f"(v[1]), "f"(v[2]), "f"(cnt) : "memory");
    if (w + cnt == 3.f * (NCL + 1)) {
        __nv_bfloat16* op = (__nv_bfloat16*)((char*)prm.out + oo);
        op[0] = __float2bfloat16(x + v[0]); op[1] = __float2bfloat16(y + v[1]); op[2] = __float2bfloat16(z + v[2]);
    }
}

__global__ void __cluster_dims__(CS, 1, 1) __launch_bounds__(NTHR, 1)
fused_kernel(const __grid_constant__ Params prm, const __grid_constant__ CUtensorMap tmG, const __grid_constant__ CUtensorMap tmU,
             const __grid_constant__ CUtensorMap tmD, const __grid_constant__ CUtensorMap tmO, const __grid_constant__ CUtensorMap tmX, const __grid_constant__ CUtensorMap tmH)
{
    extern __shared__ __align__(1024) unsigned char smem[];
    const int tid = threadIdx.x, lane = tid & 31, warp = __shfl_sync(~0u, tid >> 5, 0);
    const int c = blockIdx.x >> 3, q = blockIdx.x & 7;
    const int nslot = (c < NCL - 1) ? 5 : 2;
    const int d0 = 40 * c;
    const uint32_t sb = opaque((uint32_t)__cvta_generic_to_shared(smem));
    const uint32_t mb = sb + SM_MB;
    Scratch& g_s = *prm.gs;
    const unsigned& zero = prm.zero;
    STAMP(0);

    if (warp >= 20) {
        unsigned epoch = 0;
        if (warp == 20) {
            if (lane == 0) {
#pragma unroll
                for (int i = 0; i < 13; i++)
                    asm volatile("mbarrier.init.shared::cta.b64 [%0], %1;" :: "r"(mb + i * 8), "r"((i == MB_R || i < 5) ? 2 : i == MB_Y ? 1 + 4 * nslot : 1) : "memory");
                asm volatile("fence.mbarrier_init.release.cluster;" ::: "memory");
                arm(mb + MB_W1 * 8, 92160); arm(mb + MB_W2 * 8, nslot * 9216); arm(mb + MB_KEY * 8, 256); arm(mb + MB_GU * 8, nslot * 1024); arm(mb + MB_T * 8, 576 * XW);
                const int bytes = max(min(18, L_ - 18 * (int)blockIdx.x), 1) * (D_ * 2);
                arm(mb + MB_R * 8, bytes);
            }
            __syncwarp();
        } else if (warp == 22) {
            epoch = ld_rlx(&g_s.epoch);
            if (lane < 18 ? 18 * c + lane < 256 : lane < 31) (lane < 18 ? &g_s.acc[256 * q + 18 * c] : &g_s.fin[13 * (int)blockIdx.x - 18])[lane] = make_float4(0.f, 0.f, 0.f, 0.f);
        } else if (warp == 23 && lane == 0) asm volatile("prefetch.tensormap [%0];" :: "l"(&tmX) : "memory");
        asm volatile("barrier.cluster.arrive.relaxed.aligned;" ::: "memory");
        bar_sync(12, NTHR);
        uint4 wv = make_uint4(0, 0, 0, 0), wv2, wv3;
        if (warp == 22) {
            if (lane == 0) { sts32(sb + SM_SC + 28, epoch); asm volatile("mbarrier.arrive.shared::cta.b64 _, [%0];" :: "r"(mb + MB_R * 8) : "memory"); }
            epoch++;
            asm volatile("fence.acq_rel.gpu;" ::: "memory");
            __syncwarp();
            if (lane == 0) asm volatile("red.relaxed.gpu.global.add.u32 [%0], 1;" :: "l"(&g_s.zcnt) : "memory");
            STAMP(1);
            wv2 = ldg128((const uint4*)prm.wr + lane); wv3 = ldg128((const uint4*)prm.wr + 32 + lane);
            if (lane < 8) wv = ldg128((const uint4*)prm.wr + 64 + lane);
            if (lane < 5) {
                uint4 v = make_uint4(0, 0, 0, 0);
                if (lane < nslot) v = ldg128((const uint4*)(prm.wr + d0) + lane);
                sts128(sb + SM_DW + lane * 16, v.x, v.y, v.z, v.w);
            }
            __syncwarp();
            if (lane < 5) asm volatile("mbarrier.arrive.shared::cta.b64 _, [%0];" :: "r"(mb + (MB_X + lane) * 8) : "memory");
        }
        if (warp == 21) {
            if (lane == 0) { asm volatile("prefetch.tensormap [%0];" :: "l"(&tmG) : "memory"); asm volatile("prefetch.tensormap [%0];" :: "l"(&tmU) : "memory"); asm volatile("prefetch.tensormap [%0];" :: "l"(&tmD) : "memory"); }
            __syncwarp();
            bar_sync(15, 672);
            asm volatile("fence.proxy.async.shared::cta;" ::: "memory");
#pragma unroll 1
            for (int i = 0; i < 24; i++) {
                if (lane == 0) tma2d(sb + SM_WG + i * 3840, i < 12 ? &tmG : &tmU, 320 * c + 8 * nslot * q, 48 * (i < 12 ? i : i - 12), mb + MB_W1 * 8);
            }
            STAMP(1);
        } else {
        if (warp == 20) {
            if (lane == 0) {
                asm volatile("cp.async.bulk.shared::cluster.global.mbarrier::complete_tx::bytes [%0], [%1], %2, [%3];"
                             :: "r"(sb + SM_ROW), "l"(prm.x + min(18 * (int)blockIdx.x, L_ - 1) * D_), "r"(max(min(18, L_ - 18 * (int)blockIdx.x), 1) * (D_ * 2)), "r"(mb + MB_R * 8) : "memory");
            }
            __syncwarp();
            mbar_wait(mb + MB_R * 8);
            if (lane == 0) {
                asm volatile("cp.async.bulk.tensor.5d.shared::cluster.global.mbarrier::complete_tx::bytes [%0], [%1, {%3, %4, %5, %5, %5}], [%2];"
                             :: "r"(sb + SM_XTL), "l"(&tmX), "r"(mb + MB_T * 8), "r"(d0 & ~15), "r"(8 * q), "r"(0) : "memory");
            }
            STAMP(6);
        }
        asm volatile("barrier.cluster.wait.aligned;" ::: "memory");
        bar_sync(13, 608);
        asm volatile("fence.proxy.async.shared::cta;" ::: "memory");
        {
            const int idx = lane * 3 + max(warp - 21, 0), sl = nslot - 1 - (idx >> 3), pe = (idx + q + 1) & 7;
            if (sl >= 0) {
                if (pe == q) arm(mb + (MB_X + sl) * 8, 7 * 512);
                else {
                    const uint32_t rb_ = mapa(sb, pe);
                    asm volatile("cp.async.bulk.shared::cluster.shared::cta.mbarrier::complete_tx::bytes [%0], [%1], 512, [%2];"
                                 :: "r"(rb_ + SM_U + 128 + q * UP + sl * US), "r"(sb + SM_XT + 128 + (q & 3) * 16 + pe * YP + sl * YS), "r"(rb_ + SM_MB + (MB_X + sl) * 8) : "memory");
                }
            }
        }
        STAMP(1);
        if (warp == 20 && lane == 0) { asm volatile("prefetch.tensormap [%0];" :: "l"(&tmO) : "memory"); asm volatile("prefetch.tensormap [%0];" :: "l"(&tmH) : "memory"); }
        if (warp == 22) {
            __syncwarp();
            mbar_wait(mb + (MB_X + 1) * 8);
            const uint32_t old = (epoch & 1) ? 0u : 0x40004000u;
#pragma unroll
            for (int t = 0; t < 2; t++)
                if ((lane & 7) < 6) g_s.cand[((q * 8 + 4 * t + (lane >> 3)) * NCL + c) * 6 + (lane & 7)] = make_uint4(old, old, old, old);
            float a[4] = {0.f, 0.f, 0.f, 0.f};
            const uint32_t one = 0x3F803F80u;
            mma_bf16(a, one, one, one, one, wv.x, wv.y);  mma_bf16(a, one, one, one, one, wv.z, wv.w);
            mma_bf16(a, one, one, one, one, wv2.x, wv2.y); mma_bf16(a, one, one, one, one, wv2.z, wv2.w);
            mma_bf16(a, one, one, one, one, wv3.x, wv3.y); mma_bf16(a, one, one, one, one, wv3.z, wv3.w);
            float s = a[0] + a[1];
            s += __shfl_xor_sync(~0u, s, 1); s += __shfl_xor_sync(~0u, s, 2);
            stsf(sb + SM_SC + 24, s);
            __syncwarp();
            if (lane == 0) {
                int n = 0;
                while ((int)(ld_acq(&g_s.zcnt) - epoch * NCTA) < 0 && ++n < SPIN_LIMIT) __nanosleep(200);
                arm(mb + MB_Y * 8, 8 * 512 * nslot);
                if (blockIdx.x == 0) g_s.epoch = epoch;
            }
            STAMP(2);
        }
        if (warp == 23) {
#pragma unroll 1
            for (int kk = nslot - 1; kk >= 0; kk--) {
                __syncwarp();
                bar_sync(6 + kk, 160);
                if (lane == 0) { asm volatile("fence.proxy.async.shared::cta;" ::: "memory"); tma2d(sb + SM_FAR + kk * FAR_SZ, &tmD, 72 * q, 320 * c + 64 * kk, mb + MB_W2 * 8); }
            }
        }
        }
        __syncwarp();
        bar_sync(14, 768);
        if (tid == 640) {
            asm volatile("fence.proxy.async.shared::cta;" ::: "memory");
            asm volatile("cp.async.bulk.tensor.5d.global.shared::cta.bulk_group [%0, {%2, %4, %4, %4, %3}], [%1];" :: "l"(&tmH), "r"(sb + SM_XT + 16384), "r"(d0 + ((c & 1) ? 0 : 32)), "r"(8 * q), "r"(0) : "memory");
            asm volatile("cp.async.bulk.tensor.5d.global.shared::cta.bulk_group [%0, {%2, %4, %4, %4, %3}], [%1];" :: "l"(&tmO), "r"(sb + SM_XT), "r"(d0 + (c & 1) * 8), "r"(8 * q), "r"(0) : "memory");
            asm volatile("cp.async.bulk.commit_group;" ::: "memory");
        }
        __syncwarp();
        const uint32_t ft = (tid >> 4) & 7, fj = d0 / 3 + (lane & 15), tok = ~lds32(sb + SM_SEL + ft * 8) & 2047;
        float v[3], cnt = 0.f;
#pragma unroll
        for (int i = 0; i < 3; i++) {
            const uint32_t cl = 3 * fj + i - d0, cf = cl - (c & 1) * 8;
            const bool ok = cl < 8 * nslot && ((tok >> 3) & 7) == q;
            const uint32_t u = lds16(sb + SM_XT + (cf < 32 ? tslot(tok) * 64 + cf * 2 : 16384 + tslot(tok) * 16 + (cl & 7) * 2));
            v[i] = ok ? __uint_as_float(u << 16) : 0.f;
            if (ok) cnt += 1.f;
        }
        if (tid == 640) {
            asm volatile("cp.async.bulk.wait_group 0;" ::: "memory");
            asm volatile("fence.proxy.async.global;" ::: "memory");
            asm volatile("mbarrier.arrive.shared::cta.b64 _, [%0];" :: "r"(mb + MB_OUT * 8) : "memory");
        }
        __syncwarp();
        mbar_wait(mb + MB_OUT * 8);
        STAMP(5);
        if (cnt != 0.f) finish(prm, (ft * 192 + fj) * 16, (tok * D_ + 3 * fj) * 2, v, cnt);
        return;
    }

    const int g = lane >> 2, cq = lane & 3;
    const int k = warp >> 2, wq = warp & 3;
    const int trow = 18 * blockIdx.x + warp;
    const bool rowact = warp < 18 && trow < L_;
    const int dch = min(d0 + 8 * k + q, D_ - 1);
    uint32_t pv[6];
    const uint32_t pofs = opaque((dch * 128 + wq * 32 + lane) * 2);
#pragma unroll
    for (int i = 0; i < 6; i++) pv[i] = ldg16((const char*)prm.prm6[i] + pofs);
    const uint32_t pLdt = ldg16(prm.logdt + dch), pD = ldg16(prm.dskip + dch);
    const int tn = 16 * (warp & 15) + g;
    uint32_t xa[5], xb[5];
    asm volatile("barrier.cluster.arrive.relaxed.aligned;" ::: "memory");
    uint4* const st1p = &g_s.st1[(((trow >> 3) & 7) * 256 + ((trow >> 6) & 31) * 8 + (trow & 7)) * 2 + (lane >> 2)];
    const bool pub = rowact && (lane & 0x1B) == 0;
    if (pub) st_rlx128(st1p, 0, 0, 0, 0);
    {
        const uint32_t za = sb + SM_P + tid * 16;
        sts128(za, 0, 0, 0, 0);
        if (tid < (SM_MISC - SM_P) / 16 - 640) sts128(za + 10240, 0, 0, 0, 0);
        sts128(sb + ((wq & 2) ? SM_U : SM_XT + (q & 3) * 16) + ((tid >> 3) & 7) * ((wq & 2) ? UP : YP) + k * YS + (lane & 7) * 16, 0, 0, 0, 0);
    }
    bar_sync(12, NTHR);
    const uint32_t dep = lds32(sb + SM_P);
#define PV(x) __uint_as_float(__byte_perm(dep, x, 0x5410))
    STAMP(1);
    const uint32_t fb = sb + SM_FAR + k * FAR_SZ;
    const uint32_t pn = sb + SM_PN + k * PN_SZ, pf = sb + SM_PF + k * PF_SZ;
    unsigned epoch;
    {
        const uint32_t kb = fb + wq * 3072;
        const uint32_t kl = kb + lane * 16;
        uint32_t Af[4][4];
        float sr, si, z1r, z1i, z2r, z2i, z4r, z4i, hr, hi_;
        {
            const float dt = bfr(ex2f(PV(pLdt) * 1.4426950408889634f));
            const float e2 = dt * PV(pv[0]) * 1.4426950408889634f, an = dt * PV(pv[1]);
            float ar, ai, br, bi, cr, ci, dr, di;
            { const float m = ex2f(e2 * 8.f); ar = m * __cosf(an * 8.f); ai = m * __sinf(an * 8.f); }
            csq(br, bi, ar, ai); csq(cr, ci, br, bi); csq(dr, di, cr, ci);
            const H2C m4 = splat(cr, ci);
            {
                float r3, i3;
                cmul(r3, i3, ar, ai, br, bi);
                expand4(kl, kl + 1024, pack_f16(1.f, ar), pack_f16(br, r3), pack_f16(0.f, ai), pack_f16(bi, i3), m4);
            }
            expand8(kl + 512, kl + 1536, dr, di, ar, ai, br, bi, m4);
            { const float m = ex2f(e2); z1r = m * __cosf(an); z1i = -m * __sinf(an); }
            cexp_s(hr, hi_, e2 * 128.f, an * (-128.f * 0.15915494309189535f));
            csq(z2r, z2i, z1r, z1i); csq(z4r, z4i, z2r, z2i);
            const uint32_t dep2 = lds32(sb + SM_P + 4);
#define PW(x) __uint_as_float(__byte_perm(dep2, x, 0x5410))
            cmul(sr, si, PW(pv[4]), PW(pv[5]), dt * PW(pv[2]), dt * PW(pv[3]));
            const unsigned E = min(max(__reduce_max_sync(~0u, __float_as_uint(fmaxf(fmaxf(fabsf(sr), fabsf(si)), fabsf(PW(pD)) * (1.f / 8192.f)))) >> 23, 1u), 253u);
            const float sc = __uint_as_float((254u - E) << 23);
            sr *= sc; si *= -sc;
            sts64(sb + SM_KG + warp * 8, E, __reduce_add_sync(~0u, __float2int_rn(sr * 16777216.f)));
            stsf(sb + SM_DW + 96 + k * 4, PW(pD));
        }
        __syncwarp();
#pragma unroll
        for (int ks = 0; ks < 4; ks++) ldsm4t(Af[ks], kb + (lane >> 3) * 512 + (lane & 7) * 16 + ks * 128);
        STAMP(2);
        const uint32_t la = kb + ((lane >> 3) & 1) * 512 + (lane >> 4) * 128 + (lane & 7) * 16;
        uint32_t b0[4], b1[4], b2[4], b3[4];
        auto ln1 = [&]() {
        mbar_wait(mb + MB_R * 8);
        epoch = lds32(sb + SM_SC + 28) + 1;
        {
            const uint32_t ra = sb + SM_ROW + warp * (D_ * 2);
            const uint4 r0 = lds128(ra + lane * 16), r1 = lds128(ra + 512 + lane * 16);
            const uint32_t rx[9] = {r0.x, r0.y, r0.z, r0.w, r1.x, r1.y, r1.z, r1.w, lds32(ra + 1024 + lane * 4)};
            float a0 = bf_lo(rx[0]), a1 = bf_hi(rx[0]), c0 = a0 * a0, c1 = a1 * a1;
#pragma unroll
            for (int i = 1; i < 9; i++) { const float l = bf_lo(rx[i]), h = bf_hi(rx[i]); a0 += l; a1 += h; c0 = fmaf(l, l, c0); c1 = fmaf(h, h, c1); }
            a0 += a1; c0 += c1;
            float s1 = ((lane & 1) ? c0 : a0) + __shfl_xor_sync(~0u, (lane & 1) ? a0 : c0, 1);
#pragma unroll
            for (int o = 2; o < 32; o <<= 1) s1 += __shfl_xor_sync(~0u, s1, o);
            const float s2 = __shfl_xor_sync(~0u, s1, 1);
            const uint32_t ms = ln_stats(s1, s2);
            const uint32_t p0 = __byte_perm(ms, epoch | 0x8000u, 0x5410), p1 = rsplit(rcpf(bf_hi(ms)));
            if (pub) st_rlx128(st1p, p0, p1, p0, p1);
        }
        mbar_wait(mb + MB_R * 8);
        STAMP(1);
        };
        const uint4* sp = &g_s.st1[(256 * q + tn) * 2];
        uint2 sa, sc;
        auto poll = [&]() { sa = ld_rlx64(sp); sc = ld_rlx64(sp + 16); };
        auto norm = [&]() {
        STAMP(3);
        if (warp < 16) {
            uint32_t va[5], vc[5];
            poll();
            mbar_wait(mb + MB_T * 8);
            {
                const uint32_t xt = sb + SM_XTL + (c & 1) * 16 + (72 * wq + 18 * k + g) * (2 * XW);
                uint4 a4 = lds128(xt + cq * 16), b4 = lds128(xt + cq * 16 + 18 * XW);
                va[0] = a4.x; va[1] = a4.y; va[2] = a4.z; va[3] = a4.w; va[4] = lds32(xt + 64 + cq * 4);
                vc[0] = b4.x; vc[1] = b4.y; vc[2] = b4.z; vc[3] = b4.w; vc[4] = lds32(xt + (64 + 18 * XW) + cq * 4);
            }
            const int d4 = 2 * (lane >> 3) + (lane & 1), d1_ = lane & 7;
            const uint32_t own = SM_U + 128 + q * (UP - YP), oth = SM_XT + 128 + (q & 3) * 16;
            uint32_t a4 = sb + warp * 32 + d4 * YP + (d4 == q ? own : oth) + ((lane & 7) >> 1) * YS;
            uint32_t a1 = sb + warp * 32 + d1_ * YP + (d1_ == q ? own : oth) + 4 * YS + (lane & 8) * 2;
            PIN(a4); PIN(a1);
            uint32_t tag = __byte_perm(epoch | 0x8000u, 0, 0x1010);
            PIN(tag);
            mbar_wait(mb + MB_T * 8);
            int n = 0;
            while (__byte_perm(sa.x, sc.x, 0x7632) != tag && ++n < SPIN_LIMIT) poll();
            STAMP(4);
#pragma unroll
            for (int i = 0; i < 5; i++) {
                va[i] = norm2(va[i], sa.x, sa.y); va[i] = pack_f16(bf_lo(va[i]), bf_hi(va[i]));
                vc[i] = norm2(vc[i], sc.x, sc.y); vc[i] = pack_f16(bf_lo(vc[i]), bf_hi(vc[i]));
            }
            stsm4t(a4, va[0], va[1], va[2], va[3]); stsm4t(a4 + 16, vc[0], vc[1], vc[2], vc[3]); stsm2t(a1, va[4], vc[4]);
            bar_arrive(13, 608);
            {
            const uint32_t xh = sb + SM_XTL + (c & 1) * 16 + (9 * g + 144 * (warp & 1) + (warp >> 1)) * (2 * XW);
            const uint4 c4 = lds128(xh + cq * 16), d4_ = lds128(xh + cq * 16 + 144 * XW);
            xa[0] = c4.x; xa[1] = c4.y; xa[2] = c4.z; xa[3] = c4.w; xa[4] = lds32(xh + 64 + cq * 4);
            xb[0] = d4_.x; xb[1] = d4_.y; xb[2] = d4_.z; xb[3] = d4_.w; xb[4] = lds32(xh + (64 + 144 * XW) + cq * 4);
            }
        }
        STAMP(5);
        __syncwarp();
        bar_sync(15, 672);
        Af[0][0] |= lds32(sb + SM_P);
        };
        cmul(sr, si, sr, si, z1r, z1i);
        {
            const H2C h4 = splat(z4r, z4i);
            expand8(kl, kl + 512, sr, si, z1r, z1i, z2r, z2i, h4);
            cmul(sr, si, sr, si, hr, hi_);
            expand8(kl + 1024, kl + 1536, sr, si, z1r, z1i, z2r, z2i, h4);
        }
        __syncwarp();
        ldsm4t(b0, la); ldsm4t(b1, la + 256); ldsm4t(b2, la + 1024); ldsm4t(b3, la + 1280);
        cmul(z1r, z1i, z1r, z1i, hr, hi_);
        cmul(sr, si, sr, si, z1r, z1i);
        expand8(kl, kl + 512, sr, si, z2r, z2i, z4r, z4i, splat(hr, hi_));
        ln1();
        csq(z1r, z1i, z1r, z1i);
        cmul(sr, si, sr, si, z1r, z1i);
        csq(z2r, z2i, hr, hi_);
        expand8(kl + 1024, kl + 1536, sr, si, z4r, z4i, hr, hi_, splat(z2r, z2i));
        csq(z1r, z1i, z1r, z1i);
        cmul(sr, si, sr, si, z1r, z1i);
        csq(z4r, z4i, z2r, z2i);
        expand8(kl + 2048, kl + 2560, sr, si, hr, hi_, z2r, z2i, splat(z4r, z4i));
        norm();
        {
            uint32_t c0[4], c1[4], c2[4], c3[4], e0[4], e1[4];
            float t[6][4];
            ldsm4t(c0, la); ldsm4t(c2, la + 1024);
            mma_f16_z(t[0], Af[0], b0[0], b0[1]);
            const uint32_t lb = la | (__float_as_uint(t[0][0]) & zero);
            mma_f16_z(t[1], Af[0], b2[0], b2[1]); mma_f16_z(t[2], Af[0], c0[0], c0[1]); mma_f16_z(t[3], Af[0], c2[0], c2[1]);
            ldsm4t(e0, lb + 2048); ldsm4t(c1, lb + 256); ldsm4t(c3, lb + 1280); ldsm4t(e1, lb + 2304);
            mma_f16(t[0], Af[1], b0[2], b0[3]); mma_f16(t[1], Af[1], b2[2], b2[3]); mma_f16(t[2], Af[1], c0[2], c0[3]); mma_f16(t[3], Af[1], c2[2], c2[3]);
            mma_f16(t[0], Af[2], b1[0], b1[1]); mma_f16(t[1], Af[2], b3[0], b3[1]);
            mma_f16_z(t[4], Af[0], e0[0], e0[1]); mma_f16_z(t[5], Af[1], e0[2], e0[3]);
            mma_f16(t[2], Af[2], c1[0], c1[1]); mma_f16(t[3], Af[2], c3[0], c3[1]);
            mma_f16(t[4], Af[2], e1[0], e1[1]); mma_f16(t[5], Af[3], e1[2], e1[3]);
            mma_f16(t[0], Af[3], b1[2], b1[3]); mma_f16(t[1], Af[3], b3[2], b3[3]); mma_f16(t[2], Af[3], c1[2], c1[3]); mma_f16(t[3], Af[3], c3[2], c3[3]);
            stsm4(kl + 1024, pack_f16(t[0][0], t[0][1]), pack_f16(t[0][2], t[0][3]), pack_f16(t[1][0], t[1][1]), pack_f16(t[1][2], t[1][3]));
            stsm2(kl + 1536, pack_f16(t[2][0], t[2][1]), pack_f16(t[2][2], t[2][3]));
            sts64(kb + lane * 8 + 1792, pack_f16(t[3][1], t[3][0]), pack_f16(t[3][3], t[3][2]));
            sts64(kb + lane * 8 + 2048, pack_f16(t[4][1] + t[5][1], t[4][0] + t[5][0]), pack_f16(t[4][3] + t[5][3], t[4][2] + t[5][2]));
        }
        bar_sync(1 + k, 128);
        const uint4 m01 = lds128(sb + SM_KG + k * 32), m23 = lds128(sb + SM_KG + k * 32 + 16);
        const unsigned Em = max(max(m01.x, m01.z), max(m23.x, m23.z));
        const float f0 = __uint_as_float(max((int)(127 + m01.x - Em), 0) << 23), f1 = __uint_as_float(max((int)(127 + m01.z - Em), 0) << 23),
                    f2 = __uint_as_float(max((int)(127 + m23.x - Em), 0) << 23), f3 = __uint_as_float(max((int)(127 + m23.z - Em), 0) << 23);
        const uint32_t r0 = pack_f16(f0, f0), r1 = pack_f16(f1, f1), r2 = pack_f16(f2, f2), r3 = pack_f16(f3, f3);
        const int tq = (wq + k) & 3;
        const uint32_t ra = fb + lane * 8 + (tq == 1 ? 2048 : tq * 256 + 1024);
        auto comb = [&](uint32_t a, uint32_t& x, uint32_t& y) {
            const uint2 p0 = lds64(a), p1 = lds64(a + 3072), p2 = lds64(a + 6144), p3 = lds64(a + 9216);
            x = hadd2(hfma2(p0.x, r0, hmul2(p1.x, r1)), hfma2(p2.x, r2, hmul2(p3.x, r3)));
            y = hadd2(hfma2(p0.y, r0, hmul2(p1.y, r1)), hfma2(p2.y, r2, hmul2(p3.y, r3)));
        };
        uint32_t w0, w1;
        comb(ra, w0, w1);
        const bool last = lane == 31;
        if (tq == 0) {
            uint32_t v0, v1;
            comb(ra + 256, v0, v1);
            const uint32_t n0 = __shfl_sync(~0u, lane ? w0 : v0, lane + 1);
            uint32_t n1 = __shfl_sync(~0u, v0, lane + 1);
            if (last) n1 = v1 >> 16;
            sts128(pn + 12 + lane * 16, __byte_perm(w1, w0, 0x7610), __byte_perm(w1, 0, 0x1032), __byte_perm(n0, w1, 0x7610), __byte_perm(n0, 0, 0x1032));
            sts128(pn + 524 + lane * 16, __byte_perm(v1, v0, 0x7610), __byte_perm(v1, 0, 0x1032), __byte_perm(n1, v1, 0x7610), __byte_perm(n1, 0, 0x1032));
            if (lane == 0) {
                sts32(sb + SM_SC + k * 4, Em * 0x00800080u);
                const uint32_t t0 = pack_f16(((float)(int)m01.y * f0 + (float)(int)m01.w * f1 + (float)(int)m23.y * f2 + (float)(int)m23.w * f3) * (1.f / 16777216.f)
                                         + ldsf(sb + SM_DW + 96 + k * 4) * __uint_as_float((254u - Em) << 23), 0.f);
                sts128(pn - 4, 0, t0, __byte_perm(w0, t0, 0x5410), __byte_perm(w0, 0, 0x1032));
            }
        } else if (tq == 1) {
            const uint32_t ph = pf + P_H7 + (g & 1) * (2 * P_HS) + cq * 64 + (g >> 1) * 4 + (cq & 2) * 16, sw = (cq & 2) ? 0x3210 : 0x1032;
            w0 = __byte_perm(hmul2(w0, 0x18001800u), 0, sw); w1 = __byte_perm(hmul2(w1, 0x18001800u), 0, sw);
            const uint32_t pi = ph + 32 - (cq & 2) * 32;
            put16(ph, w0); put16(pi, w0 >> 16); put16(ph + 16, w1); put16(pi + 16, w1 >> 16);
        } else if (tq == 2) {
            uint32_t n = __shfl_sync(~0u, w0, lane == 30 ? 1 : lane + 2);
            if (last) { put16(pf, hmul2(w1, 0x18001800u) >> 16); w1 = hadd2(w1, hneg2(__byte_perm(w1, 0, 0x3232))); n = 0; }
            const bool od = lane & 1;
            const uint32_t pa = pn + 1036 + (lane >> 1) * 32 + (od ? 528 : 0), pb = pa + (od ? -16 : 16);
            const uint32_t u0 = od ? w1 : w0, x0 = od ? n : w1, u1 = od ? w0 : w1, x1 = od ? w1 : n;
            const uint32_t b0 = __byte_perm(u0, 0, 0x3232), b1 = __byte_perm(u1, 0, 0x3232);
            sts128(pa, __byte_perm(u0, 0, 0x1032), b0, b0, __byte_perm(x0, u0, 0x7610));
            sts128(pb, __byte_perm(u1, 0, 0x1032), b1, b1, __byte_perm(x1, u1, 0x7610));
        } else {
            const uint32_t pa = pf + ((g & 1) ? 3 * P_GS : P_GS) + cq * 32 + (g >> 1) * 4;
            const uint32_t pb = pa + ((g & 1) ? 4 - 3 * P_GS : P_GS);
            w0 = hmul2(w0, 0x18001800u); w1 = hmul2(w1, 0x18001800u);
            put16(pa, w0 >> 16); put16(pb, w0); put16(pa + 16, w1 >> 16); put16(pb + 16, w1);
            if (last) put16(pf + P_H7 + P_HS, w1);
        }
        bar_sync(1 + k, 128);
        if (tq == 2 && lane == 0) sts16(pn + 258 * 4, w0);
    }
    STAMP(6);

    asm volatile("barrier.cluster.wait.aligned;" ::: "memory");
    mbar_wait(mb + (MB_X + (k < nslot ? k : 0)) * 8);
    STAMP(7);
    if (k < nslot) {
        const int role = (wq + k) & 3;
        const uint32_t ub = sb + SM_U + k * US + 128;
        if (role) {
            const int r = (3 - role) * 32 + lane;
            const uint32_t a1 = ub + (r & 3) * (2 * UP) + (r >> 2) * 16, a0 = a1 + ((r & 3) ? -2 * UP : 6 * UP - 16);
            const uint4 q0 = lds128(a0), q1 = lds128(a0 + UP), q2 = lds128(a1), q3 = lds128(a1 + UP);
            const uint32_t U[16] = {q0.x, q0.y, q0.z, q0.w, q1.x, q1.y, q1.z, q1.w, q2.x, q2.y, q2.z, q2.w, q3.x, q3.y, q3.z, q3.w};
            uint32_t V[14], Q[14], R4[12], T[8];
#pragma unroll
            for (int i = 2; i < 14; i++) { V[i] = __byte_perm(U[i], U[i + 1], 0x5432); Q[i] = hadd2(U[i], V[i]); }
#pragma unroll
            for (int i = 2; i < 12; i++) R4[i] = hadd2(Q[i], Q[i + 1]);
            const uint32_t rb = fb + r * 16;
#pragma unroll
            for (int i = 0; i < 8; i++) T[i] = hadd2(V[5 + i], Q[6 + i]);
            sts128(rb + F_E3, T[0], T[1], T[2], T[3]); sts128(rb + F_O3 + 16, T[4], T[5], T[6], T[7]);
#pragma unroll
            for (int i = 0; i < 8; i++) T[i] = hadd2(R4[3 + i], U[5 + i]);
            sts128(rb + F_O5, T[0], T[1], T[2], T[3]); sts128(rb + F_E5, T[4], T[5], T[6], T[7]);
            if (role != 1) {
#pragma unroll
                for (int i = 0; i < 8; i++) T[i] = hadd2(T[i], hadd2(V[2 + i], V[5 + i]));
                sts128(rb + F_E7, T[0], T[1], T[2], T[3]); sts128(rb + F_O7, T[4], T[5], T[6], T[7]);
#pragma unroll
                for (int i = 0; i < 8; i++) T[i] = hadd2(R4[2 + i], hadd2(R4[4 + i], U[6 + i]));
                sts128(rb + F_O9, T[0], T[1], T[2], T[3]); sts128(rb + F_E9 + 16, T[4], T[5], T[6], T[7]);
                sts128(rb + F_E2, Q[6], Q[7], Q[8], Q[9]); sts128(rb + F_O2, Q[10], Q[11], Q[12], Q[13]);
            }
        } else if (lane < 8) {
            uint32_t v[5];
#pragma unroll
            for (int i = 0; i < 5; i++) { const int t = 6 + lane + i; v[i] = lds16(ub + 23 * 16 + (t < 16 ? (6 + (t >> 3)) * UP : 16) + (t & 7) * 2); }
            const uint32_t s = hadd2(hadd2(hadd2(v[0], v[1]), hadd2(v[2], v[3])), v[4]);
            sts16(fb + F_O5 + 96 * 16 + lane * 2, s);
            sts32(fb + (lane < 4 ? F_O3 : F_E9 - 16) + lane * 4, 0);
        }
        bar_sync(1 + k, 128);
        float acc[4][4];
        uint32_t Q[4][4];
        {
            const int h = role & 1, part = role >> 1;
            const uint32_t po = pf + (g - 2 * cq) * 4;
            float fa[7][4];
#pragma unroll
            for (int a = 0; a < 7; a++) fa[a][0] = fa[a][1] = fa[a][2] = fa[a][3] = 0.f;
            uint32_t B[3][4];
            Q[0][2] = tid & zero;
#pragma unroll 1
            for (int s = 2 * part + 1; s >= 2 * part; s--) {
#pragma unroll
                for (int i = 0; i < 3; i++) { Q[i][0] = lds32(po + s * P_GS + i * 64); Q[i][1] = lds32(po + s * P_GS + (i * 64 + 32)); }
                const uint32_t ba = fb + lane * 16 + ((s & 1) * F_E3 + (part == h ? 0 : F_O5 + h * 16));
#pragma unroll
                for (int i = 0; i < 3; i++) ldsm4t(B[i], ba + i * 512);
#pragma unroll
                for (int i = 0; i < 3; i++) { Q[i][3] = CP(Q[i][0]); if (i) Q[i][2] = CP(Q[i - 1][1]); }
#pragma unroll
                for (int dl = 0; dl < 3; dl++)
#pragma unroll
                    for (int ap = 0; ap < 6 - dl; ap++) mma_f16(fa[ap + 1 + dl], Q[dl], B[ap >> 1][2 * (ap & 1)], B[ap >> 1][2 * (ap & 1) + 1]);
            }
#pragma unroll 1
            for (int s = role; s == 1; s++) {
                ldsm2t(B[0][0], B[0][1], fb + ((lane & 15) == 15 ? F_O5 : F_O3));
#pragma unroll
                for (int dl = 0; dl < 3; dl++) mma_f16(fa[dl], Q[dl], B[0][0], B[0][1]);
            }
#pragma unroll 1
            for (int s = part; s <= 2 * part; s++) {
#pragma unroll
                for (int i = 0; i < 4; i++) { Q[i][0] = lds32(po + s * P_HS + (P_H7 + i * 64)); Q[i][1] = lds32(po + s * P_HS + (P_H7 + i * 64 + 32)); }
                const uint32_t ba = fb + lane * 16 + (F_E7 + s * 1024 + h * F_H);
                ldsm4t(B[0], ba); ldsm4t(B[1], ba + 512);
#pragma unroll
                for (int i = 0; i < 4; i++) { Q[i][3] = CP(Q[i][0]); if (i) Q[i][2] = CP(Q[i - 1][1]); }
#pragma unroll
                for (int dl = 0; dl < 4; dl++) {
#pragma unroll
                    for (int ap = 0; ap < 4 - dl; ap++) mma_f16(fa[ap + 3 + dl], Q[dl], B[ap >> 1][2 * (ap & 1)], B[ap >> 1][2 * (ap & 1) + 1]);
                    if (s == 1) break;
                }
            }
            const uint32_t da = fb + role * 2048 + (lane & 3) * 512 + (((lane >> 2) ^ ((lane & 3) * 2)) << 4);
            bar_sync(1 + k, 128);
            stsm4(da, 0u, 0u, pack_f16(fa[0][0], fa[0][1]), pack_f16(fa[0][2], fa[0][3]));
#pragma unroll
            for (int i = 1; i < 4; i++)
                stsm4(da + i * 128, pack_f16(fa[2 * i - 1][0], fa[2 * i - 1][1]), pack_f16(fa[2 * i - 1][2], fa[2 * i - 1][3]),
                      pack_f16(fa[2 * i][0], fa[2 * i][1]), pack_f16(fa[2 * i][2], fa[2 * i][3]));
            Q[0][0] = (g == 2 * cq) ? 0x6000u : ((g == 2 * cq + 1) ? 0x60000000u : 0u);
            Q[0][1] = Q[0][0] & zero; Q[0][2] = lane & zero; Q[0][3] = CP(Q[0][0]);
            const uint32_t ra = fb + (lane >> 3) * 2048 + wq * 512 + (((lane & 7) ^ (wq * 2)) << 4);
            bar_sync(1 + k, 128);
#pragma unroll
            for (int i = 0; i < 4; i++) {
                ldsm4(B[0], ra + i * 128);
                mma_f16_z(acc[i], Q[0], hadd2(B[0][0], B[0][2]), hadd2(B[0][1], B[0][3]));
            }
        }
        bar_arrive(6 + k, 160);
        STAMP(8);
        const uint32_t inv = lds32(sb + SM_SC + k * 4);
        uint32_t yd = mapa(sb, 2 * wq) + (SM_XT + 128 + q * YP + k * YS + (k >> 2) * (q >> 1) * 16) + lane * 16;
        PIN(yd);
        {
            uint32_t pp = pn + (16 * (wq - 3) + g - 2 * cq) * 4;
            uint32_t dlo = (((ub + 6 * UP) & 0x3FFFF) >> 4) | ((UP >> 4) << 16);
            uint32_t R[4][4];
            auto loadQ = [&](uint32_t (&X)[4][4], uint32_t prev) {
#pragma unroll
                for (int i = 0; i < 4; i++) { X[i][0] = lds32(pp + i * 64); X[i][1] = lds32(pp + i * 64 + 32); }
                X[0][2] = CP(prev);
#pragma unroll
                for (int i = 0; i < 4; i++) { X[i][3] = CP(X[i][0]); if (i) X[i][2] = CP(X[i - 1][1]); }
                pp += 256;
            };
            auto issue = [&](uint32_t (&X)[4][4]) {
                asm volatile("wgmma.fence.sync.aligned;" ::: "memory");
#pragma unroll
                for (int i = 0; i < 4; i++) wgmma32(acc, X[i], dlo - i * (2 * UP >> 4));
                asm volatile("wgmma.commit_group.sync.aligned;" ::: "memory");
                dlo -= 1;
            };
            loadQ(Q, 0);
#pragma unroll 1
            for (int dl = 0; dl < 4; dl++) {
                issue(Q);
                asm volatile("wgmma.wait_group.sync.aligned 1;" ::: "memory");
                loadQ(R, Q[3][1]);
                issue(R);
                asm volatile("wgmma.wait_group.sync.aligned 1;" ::: "memory");
                loadQ(Q, R[3][1]);
            }
            issue(Q);
            asm volatile("wgmma.wait_group.sync.aligned 0;" ::: "memory");
        }
        const uint32_t pstep = mapa(sb, 1) - mapa(sb, 0), ym = mapa(mb + MB_Y * 8, 2 * wq);
#pragma unroll
        for (int e = 0; e < 2; e++)
            st_async4(yd + e * pstep, bmul2(pack_bf16(acc[0][2 * e], acc[0][2 * e + 1]), inv), bmul2(pack_bf16(acc[1][2 * e], acc[1][2 * e + 1]), inv),
                      bmul2(pack_bf16(acc[2][2 * e], acc[2][2 * e + 1]), inv), bmul2(pack_bf16(acc[3][2 * e], acc[3][2 * e + 1]), inv), ym + e * pstep);
        if (lane == 0) asm volatile("mbarrier.arrive.shared::cta.b64 _, [%0];" :: "r"(mb + MB_Y * 8) : "memory");
    }
    STAMP(9);
    uint32_t ha[5], hb[5];
    if (warp < 16) {
        const uint4 wk = lds128(sb + SM_DW + cq * 16);
        uint32_t sel[5] = {wk.x, wk.y, wk.z, wk.w, lds32(sb + SM_DW + 64 + cq * 4)}, sel2[5];
#pragma unroll
        for (int i = 0; i < 5; i++) {
            if (!(g & 1)) sel[i] = 0x3F803F80u;
            sel2[i] = sel[i]; PIN(sel2[i]);
        }
        const uint32_t y4 = sb + SM_XT + 128 + warp * 32 + (2 * (lane >> 3) + (lane & 1)) * YP + ((lane & 7) >> 1) * YS;
        const uint32_t y1 = sb + SM_XT + 128 + warp * 32 + (lane & 7) * YP + 4 * YS + (lane & 8) * 2 + (lane & 6) * 8;
        uint32_t ao = (256 * q + tn) * 16, hta = sb + SM_HT + tn * 80;
        PIN(ao); PIN(hta);
        mbar_wait(mb + MB_Y * 8);
        STAMP(10);
        float ca[4] = {0.f, 0.f, 0.f, 0.f}, cb[4] = {0.f, 0.f, 0.f, 0.f};
        {
            uint32_t ya[4], yb[4], yc, yd;
            ldsm4t(ya, y4); ldsm4t(yb, y4 + 16); ldsm2t(yc, yd, y1);
#pragma unroll
            for (int i = 0; i < 4; i++) { ha[i] = badd2(xa[i], ya[i]); hb[i] = badd2(xb[i], yb[i]); }
            ha[4] = badd2(xa[4], yc); hb[4] = badd2(xb[4], yd);
        }
        if (nslot != 5) {
            ha[4] = hb[4] = 0;
            if (cq >= 2) ha[0] = ha[1] = ha[2] = ha[3] = hb[0] = hb[1] = hb[2] = hb[3] = 0;
        }
#pragma unroll
        for (int i = 0; i < 5; i++) { mma_bf16_k8(ca, ha[i], sel[i], ha[i]); mma_bf16_k8(cb, hb[i], sel2[i], hb[i]); }
        if (!(g & 1)) { ca[1] = ca[0]; cb[1] = cb[0]; }
        if (cq == (g >> 1)) {
            asm volatile("red.relaxed.gpu.global.add.v4.f32 [%0], {%1,%2,%3,%4};" :: "l"((char*)g_s.acc + ao), "f"(1.0f), "f"(ca[1]), "f"(ca[2]), "f"(ca[3]) : "memory");
            asm volatile("red.relaxed.gpu.global.add.v4.f32 [%0], {%1,%2,%3,%4};" :: "l"((char*)g_s.acc + ao + 128), "f"(1.0f), "f"(cb[1]), "f"(cb[2]), "f"(cb[3]) : "memory");
        }
        sts128(hta + cq * 16, ha[0], ha[1], ha[2], ha[3]); sts32(hta + 64 + cq * 4, ha[4]);
        sts128(hta + cq * 16 + 640, hb[0], hb[1], hb[2], hb[3]); sts32(hta + 704 + cq * 4, hb[4]);
        STAMP(11);
    }
    const int kq = warp / 5, mt = warp - 5 * kq;
    const int mi = lane >> 3, mr = lane & 7;
    const unsigned tk = (unsigned)tid / 72u, ck = tid - tk * 72;
    uint32_t A[9][4];
    auto loadA = [&]() {
        mbar_wait(mb + MB_W1 * 8);
        const uint32_t aa = sb + (mi & 1) * SM_WU + (8 * (mi >> 1) + mr) * 80 + (144 * 80 * kq + mt * 16);
#pragma unroll
        for (int s = 0; s < 9; s++) ldsm4t(A[s], aa + s * 1280);
    };
    const uint32_t par = (lds32(sb + SM_SC + 28) & 1) ? 0u : 0x40004000u;
    uint32_t pk0 = mapa(sb, 2 * cq), go = (ck / 5u + ck) * 16, co = ((q * 8 * NCL + c) * 6 + cq) * 16;
    PIN(pk0); PIN(go); PIN(co);
    if (warp < 8) {
        const float wsum = ldsf(sb + SM_SC + 24);
        const uint32_t idx = 2047 - (512 * ((tid >> 1) & 3) + 128 * ((tid >> 3) & 3) + 64 * (tid & 1) + 8 * q + warp);
        uint4 s; int n = 0;
        do { s = ld_rlx128(&g_s.acc[256 * q + tid]); } while (__uint_as_float(s.x) != (float)NCL && ++n < SPIN_LIMIT);
        STAMP(16);
        const uint32_t ox = __shfl_xor_sync(~0u, (lane & 1) ? s.z : s.w, 1);
        const uint32_t ms = ln_stats(__uint_as_float((lane & 1) ? ox : s.z), __uint_as_float(s.y));
        const float rs = rcpf(bf_hi(ms));
        const uint32_t rb = pack_bf16(0.f, fmaf(-bf_lo(ms), wsum, __uint_as_float((lane & 1) ? s.w : ox)) * rs);
        const uint32_t key = (((rb ^ (((int)rb >> 31) | 0x80000000u)) >> 16) << 11) | idx;
        sts32(sb + SM_KEY + tid * 4, key);
        __syncwarp();
        const uint32_t rank = rank4<8, 16>(sb + SM_KEY + warp * 128, key);
        asm volatile("{ .reg .pred p; setp.lt.u32 p, %0, 8; @p st.shared.u32 [%1], %2; }" :: "r"(rank), "r"(sb + SM_CAND + warp * 32 + rank * 4), "r"(key) : "memory");
        sts64(sb + SM_ST + tid * 8, ms, rsplit(rs));
    } else { mbar_wait(mb + MB_Y * 8); loadA(); }
    if (warp < 16) {
        STAMP(17);
        bar_sync(12, 512);
        STAMP(18);
        if (warp < 8) {
            const uint32_t mk = lds32(sb + SM_CAND + (tid >> 2) * 4);
            uint32_t rank = rank4<4, 64>(sb + SM_CAND + cq * 16, mk);
            rank += __shfl_xor_sync(~0u, rank, 1); rank += __shfl_xor_sync(~0u, rank, 2);
            if (rank < 8) {
                const uint32_t pk1 = pk0 + (mapa(sb, 1) - mapa(sb, 0));
                st_async1(pk0 + (SM_RK + q * 32) + rank * 4, mk, pk0 + (SM_MB + MB_KEY * 8));
                st_async1(pk1 + (SM_RK + q * 32) + rank * 4, mk, pk1 + (SM_MB + MB_KEY * 8));
                const uint32_t t = tslot(~mk | ((pk1 + rank * 4) & zero));
                const uint2 sv = lds64(sb + SM_ST + t * 8);
                const uint4 hv = lds128(sb + SM_HT + t * 80 + cq * 16);
                const uint32_t h4 = lds32(sb + SM_HT + t * 80 + 64 + cq * 4);
                const uint32_t rr = bmul2(sv.y, 0x3C803C80u);
                char* const dp = (char*)g_s.cand + (co + rank * 1440);
                st_rlx128(dp, (norm2(hv.x, sv.x, rr) & 0xBFFFBFFFu) | par, (norm2(hv.y, sv.x, rr) & 0xBFFFBFFFu) | par,
                          (norm2(hv.z, sv.x, rr) & 0xBFFFBFFFu) | par, (norm2(hv.w, sv.x, rr) & 0xBFFFBFFFu) | par);
                asm volatile("st.relaxed.gpu.global.u32 [%0], %1;" :: "l"((char*)g_s.cand + (co + rank * 1440 + 64 - cq * 12)), "r"((norm2(h4, sv.x, rr) & 0xBFFFBFFFu) | par) : "memory");
            }
            __syncwarp();
        }
        {
            const uint2 sa = lds64(sb + SM_ST + tn * 8), sbb = lds64(sb + SM_ST + tn * 8 + 64);
#pragma unroll
            for (int i = 0; i < 5; i++) { ha[i] = badd2(ha[i], norm2(ha[i], sa.x, sa.y)); hb[i] = badd2(hb[i], norm2(hb[i], sbb.x, sbb.y)); }
            const bool hf = (c & 1) && cq == 0;
            const uint32_t o16 = sb + SM_XT + (hf ? 16384 + tn * 16 : tn * 64 + (cq - (c & 1)) * 16), o4 = sb + SM_XT + ((c & 1) ? tn * 64 + 48 : 16384 + tn * 16) + cq * 4;
            sts128(o16, ha[0], ha[1], ha[2], ha[3]); sts32(o4, ha[4]);
            sts128(o16 + (hf ? 128 : 512), hb[0], hb[1], hb[2], hb[3]); sts32(o4 + ((c & 1) ? 512 : 128), hb[4]);
        }
        if (warp >= 8) {
            STAMP(19);
            mbar_wait(mb + MB_KEY * 8);
            STAMP(20);
            const uint32_t mk = lds32(sb + SM_RK - 256 + (tid >> 2) * 4);
            uint32_t rank = rank4<4, 64>(sb + SM_RK + cq * 16, mk);
            rank += __shfl_xor_sync(~0u, rank, 1); rank += __shfl_xor_sync(~0u, rank, 2);
            if (rank < 8) sts64(sb + SM_SEL + rank * 8, mk, ((tid >> 2) - 64) * 1440);
        }
    }
    bar_sync(11, 640);
    STAMP(12);

    const char* gp = (const char*)g_s.cand + (go + lds32(sb + SM_SEL + 4 + (tk & 7) * 8));
    uint4 hv = ld_rlx128(gp);
    if (warp < 8) loadA();
    const uint32_t ft = (unsigned)tid / 24u, fj = 24 * q + tid - ft * 24;
    const uint32_t key = lds32(sb + SM_SEL + (ft & 7) * 8), k16 = key << 5;
    float sig = bfr(rcpf(1.f + ex2f(__uint_as_float((k16 ^ (~((int)k16 >> 31) | 0x80000000u)) & 0xFFFF0000u) * -1.4426950408889634f)));
    uint32_t ra2 = sb + SM_RED2 + tid * 12 + ft * 16, fo = (ft * 192 + fj) * 16, oo = ((~key & 2047) * D_ + 3 * fj) * 2;
    uint32_t bx = sb + SM_XS + mr * 1168 + mi * 16 + 288 * kq, gd = mapa(sb, kq * (8 / NRED)) + (SM_GU + (q * nslot + mt) * 128) + lane * 4;
    PIN(ra2); PIN(fo); PIN(oo); PIN(bx); PIN(gd);
    asm volatile("" : "+f"(sig));
    {
        if (warp < 18) {
            int n = 0;
            while (true) {
                sts128(sb + SM_XS + tk * 16 + tid * 16, hv.x ^ par, hv.y ^ par, hv.z ^ par, hv.w ^ par);
                if (!__any_sync(~0u, ((hv.x ^ par) | (hv.y ^ par) | (hv.z ^ par) | (hv.w ^ par)) & 0x40004000u) || ++n >= SPIN_LIMIT) break;
                hv = ld_rlx128(gp);
            }
        }
    }
    bar_sync(14, 768);
    STAMP(13);
    {
        float c0[4] = {0.f, 0.f, 0.f, 0.f}, c1[4] = {0.f, 0.f, 0.f, 0.f}, c2[4] = {0.f, 0.f, 0.f, 0.f};
        uint32_t b[5][4];
#pragma unroll
        for (int s = 0; s < 4; s++) ldsm4(b[s], bx + s * 64);
        asm volatile("ldmatrix.sync.aligned.m8n8.x2.shared.b16 {%0,%1}, [%2];" : "=r"(b[4][0]), "=r"(b[4][1]) : "r"(bx + 256) : "memory");
        mma_bf16(c0, A[0][0], A[0][1], A[0][2], A[0][3], b[0][0], b[0][1]);
        mma_bf16(c1, A[1][0], A[1][1], A[1][2], A[1][3], b[0][2], b[0][3]);
        mma_bf16(c2, A[2][0], A[2][1], A[2][2], A[2][3], b[1][0], b[1][1]);
        mma_bf16(c0, A[3][0], A[3][1], A[3][2], A[3][3], b[1][2], b[1][3]);
        mma_bf16(c1, A[4][0], A[4][1], A[4][2], A[4][3], b[2][0], b[2][1]);
        mma_bf16(c2, A[5][0], A[5][1], A[5][2], A[5][3], b[2][2], b[2][3]);
        mma_bf16(c0, A[6][0], A[6][1], A[6][2], A[6][3], b[3][0], b[3][1]);
        mma_bf16(c1, A[7][0], A[7][1], A[7][2], A[7][3], b[3][2], b[3][3]);
        mma_bf16(c2, A[8][0], A[8][1], A[8][2], A[8][3], b[4][0], b[4][1]);
        sts128f(sb + SM_RED + tid * 16, c0[0] + c1[0] + c2[0], c0[1] + c1[1] + c2[1], c0[2] + c1[2] + c2[2], c0[3] + c1[3] + c2[3]);
    }
    bar_sync(1 + mt, 128);
    STAMP(21);
    if (mt < nslot && kq < NRED) {
        const uint32_t ra = sb + SM_RED + mt * 512 + lane * 16;
        const float4 p0 = lds128f(ra), p1 = lds128f(ra + 2560), p2 = lds128f(ra + 5120), p3 = lds128f(ra + 7680);
        const float g0 = bfr(((p0.x + p1.x) + (p2.x + p3.x)) * 64.f), g1 = bfr(((p0.y + p1.y) + (p2.y + p3.y)) * 64.f);
        const uint32_t sg = pack_bf16(g0 * rcpf(1.f + ex2f(g0 * -1.4426950408889634f)), g1 * rcpf(1.f + ex2f(g1 * -1.4426950408889634f)));
        const uint32_t gu = bmul2(sg, pack_bf16(((p0.z + p1.z) + (p2.z + p3.z)) * 64.f, ((p0.w + p1.w) + (p2.w + p3.w)) * 64.f));
        const uint32_t pstep = mapa(sb, 1) - mapa(sb, 0), gm = mapa(mb + MB_GU * 8, kq * (8 / NRED));
#pragma unroll
        for (int i = 0; i < 8 / NRED; i++) st_async1(gd + i * pstep, gu, gm + i * pstep);
    }
    mbar_wait(mb + MB_W2 * 8);
    {
        const uint32_t aa = sb + (8 * (mi >> 1) + mr) * 144 + (mi & 1) * 16 + (SM_FAR + 2304 * kq + mt * 32);
#pragma unroll
        for (int s = 0; s < 5; s++) ldsm4t(A[s], aa + s * FAR_SZ);
    }
    {
        uint32_t ba = sb + (SM_GU + 256 * kq) + (lane & 15) * 16 + (lane >> 4) * 1024, wa = sb + (SM_RED2 + kq * 2432 + mt * 64) + g * 4 + cq * 608;
        PIN(ba); PIN(wa);
        STAMP(22);
        mbar_wait(mb + MB_GU * 8);
        STAMP(23);
        float c0[4] = {0.f, 0.f, 0.f, 0.f}, c1[4] = {0.f, 0.f, 0.f, 0.f}, c2[4] = {0.f, 0.f, 0.f, 0.f};
        uint32_t b[2][4], b8, b9;
        ldsm4t(b[0], ba); ldsm4t(b[1], ba + 2048); ldsm2t(b8, b9, ba + 4096);
        mma_bf16(c0, A[0][0], A[0][1], A[0][2], A[0][3], b[0][0], b[0][1]);
        mma_bf16(c1, A[1][0], A[1][1], A[1][2], A[1][3], b[0][2], b[0][3]);
        if (nslot == 5) {
            mma_bf16(c2, A[4][0], A[4][1], A[4][2], A[4][3], b8, b9);
            mma_bf16(c0, A[2][0], A[2][1], A[2][2], A[2][3], b[1][0], b[1][1]);
            mma_bf16(c1, A[3][0], A[3][1], A[3][2], A[3][3], b[1][2], b[1][3]);
        }
        stsf(wa, c0[0] + c1[0] + c2[0]); stsf(wa + 304, c0[1] + c1[1] + c2[1]);
        if (mt < 4) { stsf(wa + 32, c0[2] + c1[2] + c2[2]); stsf(wa + 336, c0[3] + c1[3] + c2[3]); }
    }
    if (warp < 6) {
        float v[3];
        bar_sync(6, 640);
        STAMP(14);
#pragma unroll
        for (int i = 0; i < 3; i++) v[i] = ((ldsf(ra2 + i * 4) + ldsf(ra2 + i * 4 + 2432)) + (ldsf(ra2 + i * 4 + 4864) + ldsf(ra2 + i * 4 + 7296))) * sig;
        finish(prm, fo, oo, v, 3.f);
    } else bar_arrive(6, 640);
    STAMP(15);
}

typedef __nv_bfloat16 bf16;
__device__ bf16 f_n[L_ * D_], f_h[L_ * D_];
__device__ float f_k[D_ * L_], f_r[L_], f_gu[8 * F_];
__device__ int f_idx[8];
__device__ __forceinline__ float b2f(bf16 v) { return __bfloat162float(v); }
__global__ void fb_ln(const bf16* in, const bf16* wr, bf16* out) {
    const int t = blockIdx.x * 8 + (threadIdx.x >> 5), lane = threadIdx.x & 31;
    const bf16* r = (in ? in : f_h) + t * D_;
    float s1 = 0.f, s2 = 0.f, s3 = 0.f;
    for (int i = lane; i < D_; i += 32) s1 += b2f(r[i]);
    for (int o = 16; o; o >>= 1) s1 += __shfl_xor_sync(~0u, s1, o);
    for (int i = lane; i < D_; i += 32) { const float d = b2f(r[i]) - s1 / D_; s2 += d * d; }
    for (int o = 16; o; o >>= 1) s2 += __shfl_xor_sync(~0u, s2, o);
    const float m = bfr(s1 / D_), sd = bfr(sqrtf(bfr(bfr(s2 / D_) + 1e-5f)));
    for (int i = lane; i < D_; i += 32) {
        const float v = bfr(bfr(b2f(r[i]) - m) / sd);
        f_n[t * D_ + i] = __float2bfloat16(v);
        if (!in) { s3 += v * b2f(wr[i]); out[t * D_ + i] = __float2bfloat16(b2f(r[i]) + v); }
    }
    for (int o = 16; o; o >>= 1) s3 += __shfl_xor_sync(~0u, s3, o);
    f_r[t] = bfr(s3);
}
__global__ void fb_taps(Params p) {
    const int d = blockIdx.x >> 3, l = (blockIdx.x & 7) * 256 + threadIdx.x;
    const float dt = bfr(expf(bf_lo(p.logdt[d]))), lf = bfr((float)l);
    float k = 0.f;
    for (int n = d * 128; n < d * 128 + 128; n++) {
        float wr, wi, sn, cs;
        cmul(wr, wi, bf_lo(p.prm6[4][n]), bf_lo(p.prm6[5][n]), dt * bf_lo(p.prm6[2][n]), dt * bf_lo(p.prm6[3][n]));
        sincosf(dt * bf_lo(p.prm6[1][n]) * lf, &sn, &cs);
        k += expf(dt * bf_lo(p.prm6[0][n]) * lf) * (wr * cs - wi * sn);
    }
    f_k[l * D_ + d] = k;
}
__global__ void fb_conv(Params p) {
    const int t = blockIdx.x, d = threadIdx.x;
    float y = 0.f;
    for (int l = 0; l <= t; l++) y += f_k[l * D_ + d] * b2f(f_n[(t - l) * D_ + d]);
    f_h[t * D_ + d] = __float2bfloat16(bf_lo(p.x[t * D_ + d]) + bfr(bfr(y) + bfr(b2f(f_n[t * D_ + d]) * bf_lo(p.dskip[d]))));
}
__global__ void fb_top() {
    const int t = blockIdx.x * 256 + threadIdx.x;
    int rank = 0;
    for (int j = 0; j < L_; j++) rank += f_r[j] > f_r[t] || (f_r[j] == f_r[t] && j < t);
    if (rank < 8) f_idx[rank] = t;
}
__global__ void fb_ffn1(const bf16* wg, const bf16* wu) {
    const int f = blockIdx.x * 256 + threadIdx.x, j = blockIdx.y;
    float g = 0.f, u = 0.f;
    for (int i = 0; i < D_; i++) { const float v = b2f(f_n[f_idx[j] * D_ + i]); g += v * b2f(wg[i * F_ + f]); u += v * b2f(wu[i * F_ + f]); }
    g = bfr(g);
    f_gu[j * F_ + f] = bfr(bfr(g / (1.f + expf(-g))) * bfr(u));
}
__global__ void fb_ffn2(const bf16* wd, bf16* out) {
    const int d = threadIdx.x, j = blockIdx.x, t = f_idx[j];
    float y = 0.f;
    for (int f = 0; f < F_; f++) y += f_gu[j * F_ + f] * b2f(wd[f * D_ + d]);
    out[t * D_ + d] = __float2bfloat16(b2f(f_h[t * D_ + d]) + bfr(b2f(f_n[t * D_ + d]) + bfr(bfr(y) * bfr(1.f / (1.f + expf(-f_r[t]))))));
}

typedef CUresult (*EncodeFn)(CUtensorMap*, CUtensorMapDataType, cuuint32_t, void*, const cuuint64_t*, const cuuint64_t*,
                             const cuuint32_t*, const cuuint32_t*, CUtensorMapInterleave, CUtensorMapSwizzle,
                             CUtensorMapL2promotion, CUtensorMapFloatOOBfill);

void make_map(EncodeFn fn, CUtensorMap* tm, const void* p, int cols, int rows, int bc, int br) {
    cuuint64_t dims[2] = {(cuuint64_t)cols, (cuuint64_t)rows};
    cuuint64_t strides[1] = {(cuuint64_t)cols * 2};
    cuuint32_t box[2] = {(cuuint32_t)bc, (cuuint32_t)br};
    cuuint32_t es[2] = {1, 1};
    fn(tm, CU_TENSOR_MAP_DATA_TYPE_BFLOAT16, 2, const_cast<void*>(p), dims, strides, box, es, CU_TENSOR_MAP_INTERLEAVE_NONE,
       CU_TENSOR_MAP_SWIZZLE_NONE, CU_TENSOR_MAP_L2_PROMOTION_L2_128B, CU_TENSOR_MAP_FLOAT_OOB_FILL_NONE);
}

void make_map3(EncodeFn fn, CUtensorMap* tm, const void* p) {
    cuuint64_t dims[5] = {(cuuint64_t)D_, 64, 2, 4, 4};
    cuuint64_t strides[4] = {(cuuint64_t)D_ * 2, (cuuint64_t)D_ * 128, (cuuint64_t)D_ * 1024, (cuuint64_t)D_ * 256};
    cuuint32_t box[5] = {XW, 9, 2, 4, 4};
    cuuint32_t es[5] = {1, 1, 1, 1, 1};
    fn(tm, CU_TENSOR_MAP_DATA_TYPE_BFLOAT16, 5, const_cast<void*>(p), dims, strides, box, es, CU_TENSOR_MAP_INTERLEAVE_NONE,
       CU_TENSOR_MAP_SWIZZLE_NONE, CU_TENSOR_MAP_L2_PROMOTION_NONE, CU_TENSOR_MAP_FLOAT_OOB_FILL_NONE);
}

void make_map5(EncodeFn fn, CUtensorMap* tm, const void* p, int bc) {
    cuuint64_t dims[5] = {(cuuint64_t)D_, 2, 4, 4, 64};
    cuuint64_t strides[4] = {(cuuint64_t)D_ * 128, (cuuint64_t)D_ * 1024, (cuuint64_t)D_ * 256, (cuuint64_t)D_ * 2};
    cuuint32_t box[5] = {(cuuint32_t)bc, 2, 4, 4, 8};
    cuuint32_t es[5] = {1, 1, 1, 1, 1};
    fn(tm, CU_TENSOR_MAP_DATA_TYPE_BFLOAT16, 5, const_cast<void*>(p), dims, strides, box, es, CU_TENSOR_MAP_INTERLEAVE_NONE,
       CU_TENSOR_MAP_SWIZZLE_NONE, CU_TENSOR_MAP_L2_PROMOTION_NONE, CU_TENSOR_MAP_FLOAT_OOB_FILL_NONE);
}

}

extern "C" void kernel_launch(void* const* d_in, const int* in_sizes, int n_in, void* d_out, int out_size) {
    (void)in_sizes; (void)n_in; (void)out_size;
    void* fp = nullptr;
    cudaDriverEntryPointQueryResult qr;
    cudaGetDriverEntryPoint("cuTensorMapEncodeTiled", &fp, cudaEnableDefault, &qr);
    EncodeFn fn = (EncodeFn)fp;
    CUtensorMap tmG, tmU, tmD, tmO, tmX, tmH;
    make_map3(fn, &tmX, d_in[0]);
    make_map(fn, &tmG, d_in[11], F_, D_, 40, 48);
    make_map(fn, &tmU, d_in[12], F_, D_, 40, 48);
    make_map(fn, &tmD, d_in[13], D_, F_, 72, 64);
    make_map5(fn, &tmO, d_out, 32);
    make_map5(fn, &tmH, d_out, 8);
    Params p;
    p.x = (const unsigned short*)d_in[0];
    for (int i = 0; i < 6; i++) p.prm6[i] = (const unsigned short*)d_in[1 + i];
    p.logdt = (const unsigned short*)d_in[7]; p.dskip = (const unsigned short*)d_in[8];
    p.wr = (const unsigned short*)d_in[10];
    p.out = (__nv_bfloat16*)d_out;
    p.zero = 0;
    cudaGetSymbolAddress((void**)&p.gs, g_s);
    cudaFuncSetAttribute(fused_kernel, cudaFuncAttributeMaxDynamicSharedMemorySize, SM_TOTAL);
    static int nclusters = -1;
    if (nclusters < 0) {
        cudaLaunchConfig_t cfg = {};
        cudaLaunchAttribute at;
        at.id = cudaLaunchAttributeClusterDimension; at.val.clusterDim.x = CS; at.val.clusterDim.y = 1; at.val.clusterDim.z = 1;
        cfg.gridDim = dim3(NCTA); cfg.blockDim = dim3(NTHR); cfg.dynamicSmemBytes = SM_TOTAL; cfg.attrs = &at; cfg.numAttrs = 1;
        if (cudaOccupancyMaxActiveClusters(&nclusters, fused_kernel, &cfg) != cudaSuccess) { (void)cudaGetLastError(); nclusters = NCL; }
    }
    if (nclusters >= NCL && !FORCE_FALLBACK) {
        fused_kernel<<<NCTA, NTHR, SM_TOTAL>>>(p, tmG, tmU, tmD, tmO, tmX, tmH);
        return;
    }
    fb_ln<<<L_ / 8, 256>>>((const bf16*)d_in[0], nullptr, nullptr);
    fb_taps<<<D_ * 8, 256>>>(p);
    fb_conv<<<L_, D_>>>(p);
    fb_ln<<<L_ / 8, 256>>>(nullptr, (const bf16*)d_in[10], p.out);
    fb_top<<<L_ / 256, 256>>>();
    fb_ffn1<<<dim3(F_ / 256, 8), 256>>>((const bf16*)d_in[11], (const bf16*)d_in[12]);
    fb_ffn2<<<8, D_>>>((const bf16*)d_in[13], p.out);
}
```

```cpp
#include <cuda_runtime.h>
#include <cuda_bf16.h>
#include <cuda_fp16.h>
#include <cuda.h>
#include <stdint.h>

namespace {

constexpr int L_ = 2048, D_ = 576, F_ = 4608;
constexpr int NCL = 15, CS = 8, NCTA = NCL * CS, NTHR = 768;
#define FORCE_FALLBACK 0
constexpr int XW = 48, NRED = 2;
constexpr int SPIN_LIMIT = 1 << 22;

constexpr int SM_WG   = 0;
constexpr int SM_WU   = 46080;
constexpr int YP = 3392, YS = 656;
constexpr int UP = 3280, US = 656;
constexpr int SM_XT   = 92160;
constexpr int SM_U    = SM_XT + 8 * YP;
constexpr int SM_FAR  = SM_U + 8 * UP;
constexpr int FAR_SZ  = 12416;
constexpr int F_E5 = 0, F_O5 = 1536, F_E3 = 3088, F_O3 = 4624, F_E7 = 6176, F_E2 = F_E7 + 1024, F_E9 = F_E7 + 2048,
              F_H = 3088, F_O7 = F_E7 + F_H, F_O2 = F_E2 + F_H, F_O9 = F_E9 + F_H;
constexpr int SM_P    = SM_FAR + 5 * FAR_SZ;
constexpr int PN_SZ = 584 * 4, SM_PN = SM_P + 65 * 4;
constexpr int P_GS = 50 * 4, P_H7 = 200 * 4, P_HS = 74 * 4;
constexpr int PF_SZ = (200 + 222) * 4, SM_PF = SM_PN + 5 * PN_SZ + 36;
constexpr int SM_MISC = SM_PF + 5 * PF_SZ;
constexpr int SM_ST   = SM_MISC;
constexpr int SM_RK   = SM_ST + 2048;
constexpr int SM_SEL  = SM_RK + 256;
constexpr int SM_KG   = SM_SEL + 64;
constexpr int SM_SC   = SM_KG + 160;
constexpr int SM_DW   = SM_SC + 32;
constexpr int SM_MB   = SM_DW + 160;
constexpr int SM_TOTAL = SM_MB + 128;
constexpr int SM_ROW  = SM_XT - 20736;
constexpr int SM_XTL  = SM_ROW - 576 * XW;
constexpr int SM_RED2 = SM_WG;
constexpr int SM_HT   = SM_P - 512;
constexpr int SM_KEY  = SM_FAR + 10240 + 128;
constexpr int SM_CAND = SM_KEY + 1024;
constexpr int SM_XS   = SM_U;
constexpr int SM_GU   = SM_XS + 9344;
constexpr int SM_RED  = SM_GU + 5632;
static_assert(F_O9 + 1024 <= FAR_SZ && FAR_SZ % 128 == 0, "far overflow");
static_assert(SM_RED + 10240 <= SM_FAR && SM_HT + 20496 <= SM_MISC, "alias overflow");
static_assert(SM_TOTAL <= 232448, "smem overflow");
static_assert(SM_FAR % 128 == 0 && SM_XT % 128 == 0 && SM_XTL % 128 == 0 && SM_P % 16 == 0 && SM_MISC % 16 == 0 && SM_MB % 8 == 0, "align");

enum { MB_X = 0, MB_W1 = 5, MB_W2 = 6, MB_KEY = 7, MB_GU = 8, MB_Y = 9, MB_OUT = 10, MB_T = 11, MB_R = 12 };

struct __align__(128) Scratch {
    unsigned epoch, zcnt, pad[30];
    uint4  st1[L_ * 2];
    float4 acc[L_];
    uint4  cand[64 * NCL * 6];
    float4 fin[8 * 192 + 24];
};
__device__ Scratch g_s;
#define STAMP(i)

__device__ __forceinline__ uint32_t mapa(uint32_t a, uint32_t r) { uint32_t d; asm("mapa.shared::cluster.u32 %0, %1, %2;" : "=r"(d) : "r"(a), "r"(r)); return d; }
__device__ __forceinline__ void mbar_wait(uint32_t mb) {
    asm volatile("{ .reg .pred p, q; .reg .u32 n; mov.u32 n, 0;\n"
                 "W_%=: mbarrier.try_wait.parity.shared::cta.b64 p, [%0], 0; add.u32 n, n, 1; setp.lt.and.u32 q, n, 65536, !p; @q bra W_%=; }" :: "r"(mb) : "memory");
}
__device__ __forceinline__ void arm(uint32_t mb, uint32_t bytes) { asm volatile("mbarrier.arrive.expect_tx.shared::cta.b64 _, [%0], %1;" :: "r"(mb), "r"(bytes) : "memory"); }
__device__ __forceinline__ void bar_sync(int id, int n) { asm volatile("bar.sync %0, %1;" :: "r"(id), "r"(n) : "memory"); }
__device__ __forceinline__ void bar_arrive(int id, int n) { asm volatile("bar.arrive %0, %1;" :: "r"(id), "r"(n) : "memory"); }
__device__ __forceinline__ uint32_t lds16(uint32_t a) { unsigned short v; asm volatile("ld.shared.u16 %0, [%1];" : "=h"(v) : "r"(a) : "memory"); return v; }
__device__ __forceinline__ uint32_t lds32(uint32_t a) { uint32_t v; asm volatile("ld.shared.u32 %0, [%1];" : "=r"(v) : "r"(a) : "memory"); return v; }
__device__ __forceinline__ uint2 lds64(uint32_t a) { uint2 v; asm volatile("ld.shared.v2.u32 {%0,%1}, [%2];" : "=r"(v.x), "=r"(v.y) : "r"(a) : "memory"); return v; }
__device__ __forceinline__ float ldsf(uint32_t a) { float v; asm volatile("ld.shared.f32 %0, [%1];" : "=f"(v) : "r"(a) : "memory"); return v; }
__device__ __forceinline__ uint4 lds128(uint32_t a) { uint4 v; asm volatile("ld.shared.v4.u32 {%0,%1,%2,%3}, [%4];" : "=r"(v.x), "=r"(v.y), "=r"(v.z), "=r"(v.w) : "r"(a) : "memory"); return v; }
__device__ __forceinline__ float4 lds128f(uint32_t a) { float4 v; asm volatile("ld.shared.v4.f32 {%0,%1,%2,%3}, [%4];" : "=f"(v.x), "=f"(v.y), "=f"(v.z), "=f"(v.w) : "r"(a) : "memory"); return v; }
__device__ __forceinline__ void sts16(uint32_t a, uint32_t v) { asm volatile("{ .reg .b16 l, h; mov.b32 {l, h}, %1; st.shared.b16 [%0], l; }" :: "r"(a), "r"(v) : "memory"); }
__device__ __forceinline__ void sts32(uint32_t a, uint32_t v) { asm volatile("st.shared.u32 [%0], %1;" :: "r"(a), "r"(v) : "memory"); }
__device__ __forceinline__ void sts64(uint32_t a, uint32_t x, uint32_t y) { asm volatile("st.shared.v2.u32 [%0], {%1,%2};" :: "r"(a), "r"(x), "r"(y) : "memory"); }
__device__ __forceinline__ void stsf(uint32_t a, float v) { asm volatile("st.shared.f32 [%0], %1;" :: "r"(a), "f"(v) : "memory"); }
__device__ __forceinline__ void sts128(uint32_t a, uint32_t x, uint32_t y, uint32_t z, uint32_t w) { asm volatile("st.shared.v4.u32 [%0], {%1,%2,%3,%4};" :: "r"(a), "r"(x), "r"(y), "r"(z), "r"(w) : "memory"); }
__device__ __forceinline__ void sts128f(uint32_t a, float x, float y, float z, float w) { asm volatile("st.shared.v4.f32 [%0], {%1,%2,%3,%4};" :: "r"(a), "f"(x), "f"(y), "f"(z), "f"(w) : "memory"); }
__device__ __forceinline__ void ldsm4(uint32_t (&r)[4], uint32_t a) { asm volatile("ldmatrix.sync.aligned.m8n8.x4.shared.b16 {%0,%1,%2,%3}, [%4];" : "=r"(r[0]), "=r"(r[1]), "=r"(r[2]), "=r"(r[3]) : "r"(a) : "memory"); }
__device__ __forceinline__ void ldsm4t(uint32_t (&r)[4], uint32_t a) { asm volatile("ldmatrix.sync.aligned.m8n8.x4.trans.shared.b16 {%0,%1,%2,%3}, [%4];" : "=r"(r[0]), "=r"(r[1]), "=r"(r[2]), "=r"(r[3]) : "r"(a) : "memory"); }
__device__ __forceinline__ void ldsm2t(uint32_t& r0, uint32_t& r1, uint32_t a) { asm volatile("ldmatrix.sync.aligned.m8n8.x2.trans.shared.b16 {%0,%1}, [%2];" : "=r"(r0), "=r"(r1) : "r"(a) : "memory"); }
__device__ __forceinline__ void stsm4t(uint32_t a, uint32_t r0, uint32_t r1, uint32_t r2, uint32_t r3) { asm volatile("stmatrix.sync.aligned.m8n8.x4.trans.shared.b16 [%0], {%1,%2,%3,%4};" :: "r"(a), "r"(r0), "r"(r1), "r"(r2), "r"(r3) : "memory"); }
__device__ __forceinline__ void stsm4(uint32_t a, uint32_t r0, uint32_t r1, uint32_t r2, uint32_t r3) { asm volatile("stmatrix.sync.aligned.m8n8.x4.shared.b16 [%0], {%1,%2,%3,%4};" :: "r"(a), "r"(r0), "r"(r1), "r"(r2), "r"(r3) : "memory"); }
__device__ __forceinline__ void stsm2(uint32_t a, uint32_t r0, uint32_t r1) { asm volatile("stmatrix.sync.aligned.m8n8.x2.shared.b16 [%0], {%1,%2};" :: "r"(a), "r"(r0), "r"(r1) : "memory"); }
__device__ __forceinline__ void stsm2t(uint32_t a, uint32_t r0, uint32_t r1) { asm volatile("stmatrix.sync.aligned.m8n8.x2.trans.shared.b16 [%0], {%1,%2};" :: "r"(a), "r"(r0), "r"(r1) : "memory"); }
__device__ __forceinline__ uint4 ldg128(const void* p) { uint4 v; asm volatile("ld.global.nc.v4.u32 {%0,%1,%2,%3}, [%4];" : "=r"(v.x), "=r"(v.y), "=r"(v.z), "=r"(v.w) : "l"(p)); return v; }
__device__ __forceinline__ uint32_t ldg16(const void* p) { unsigned short v; asm volatile("ld.global.nc.u16 %0, [%1];" : "=h"(v) : "l"(p)); return v; }
__device__ __forceinline__ uint32_t opaque(uint32_t v) { uint32_t r; asm volatile("mov.b32 %0, %1;" : "=r"(r) : "r"(v)); return r; }
__device__ __forceinline__ void mma_f16(float (&d)[4], const uint32_t (&a)[4], uint32_t b0, uint32_t b1) {
    asm volatile("mma.sync.aligned.m16n8k16.row.col.f32.f16.f16.f32 {%0,%1,%2,%3}, {%4,%5,%6,%7}, {%8,%9}, {%0,%1,%2,%3};"
        : "+f"(d[0]), "+f"(d[1]), "+f"(d[2]), "+f"(d[3]) : "r"(a[0]), "r"(a[1]), "r"(a[2]), "r"(a[3]), "r"(b0), "r"(b1));
}
__device__ __forceinline__ void mma_f16_z(float (&d)[4], const uint32_t (&a)[4], uint32_t b0, uint32_t b1) {
    asm volatile("mma.sync.aligned.m16n8k16.row.col.f32.f16.f16.f32 {%0,%1,%2,%3}, {%4,%5,%6,%7}, {%8,%9}, {%10,%10,%10,%10};"
        : "=f"(d[0]), "=f"(d[1]), "=f"(d[2]), "=f"(d[3]) : "r"(a[0]), "r"(a[1]), "r"(a[2]), "r"(a[3]), "r"(b0), "r"(b1), "f"(0.f));
}
__device__ __forceinline__ void mma_bf16(float (&d)[4], uint32_t a0, uint32_t a1, uint32_t a2, uint32_t a3, uint32_t b0, uint32_t b1) {
    asm volatile("mma.sync.aligned.m16n8k16.row.col.f32.bf16.bf16.f32 {%0,%1,%2,%3}, {%4,%5,%6,%7}, {%8,%9}, {%0,%1,%2,%3};"
        : "+f"(d[0]), "+f"(d[1]), "+f"(d[2]), "+f"(d[3]) : "r"(a0), "r"(a1), "r"(a2), "r"(a3), "r"(b0), "r"(b1));
}
__device__ __forceinline__ void mma_bf16_k8(float (&d)[4], uint32_t a0, uint32_t a1, uint32_t b0) {
    asm volatile("mma.sync.aligned.m16n8k8.row.col.f32.bf16.bf16.f32 {%0,%1,%2,%3}, {%4,%5}, {%6}, {%0,%1,%2,%3};"
        : "+f"(d[0]), "+f"(d[1]), "+f"(d[2]), "+f"(d[3]) : "r"(a0), "r"(a1), "r"(b0));
}
__device__ __forceinline__ uint32_t pack_f16(float lo, float hi) { uint32_t r; asm("cvt.rn.f16x2.f32 %0, %1, %2;" : "=r"(r) : "f"(hi), "f"(lo)); return r; }
__device__ __forceinline__ uint32_t pack_bf16(float lo, float hi) { uint32_t r; asm("cvt.rn.bf16x2.f32 %0, %1, %2;" : "=r"(r) : "f"(hi), "f"(lo)); return r; }
__device__ __forceinline__ float bf_lo(uint32_t v) { return __uint_as_float(v << 16); }
__device__ __forceinline__ float bf_hi(uint32_t v) { return __uint_as_float(v & 0xFFFF0000u); }
__device__ __forceinline__ float bfr(float x) { return __uint_as_float(pack_bf16(0.f, x)); }
__device__ __forceinline__ uint32_t badd2(uint32_t a, uint32_t b) { uint32_t r; asm("add.rn.bf16x2 %0, %1, %2;" : "=r"(r) : "r"(a), "r"(b)); return r; }
__device__ __forceinline__ uint32_t bmul2(uint32_t a, uint32_t b) { uint32_t r; asm("mul.rn.bf16x2 %0, %1, %2;" : "=r"(r) : "r"(a), "r"(b)); return r; }
__device__ __forceinline__ uint32_t hadd2(uint32_t a, uint32_t b) { uint32_t r; asm("add.rn.f16x2 %0, %1, %2;" : "=r"(r) : "r"(a), "r"(b)); return r; }
__device__ __forceinline__ uint32_t hmul2(uint32_t a, uint32_t b) { uint32_t r; asm("mul.rn.f16x2 %0, %1, %2;" : "=r"(r) : "r"(a), "r"(b)); return r; }
__device__ __forceinline__ uint32_t hfma2(uint32_t a, uint32_t b, uint32_t c) { uint32_t r; asm("fma.rn.f16x2 %0, %1, %2, %3;" : "=r"(r) : "r"(a), "r"(b), "r"(c)); return r; }
__device__ __forceinline__ uint32_t hneg2(uint32_t a) { uint32_t r; asm("neg.f16x2 %0, %1;" : "=r"(r) : "r"(a)); return r; }
__device__ __forceinline__ float rcpf(float x) { float r; asm("rcp.approx.ftz.f32 %0, %1;" : "=f"(r) : "f"(x)); return r; }
__device__ __forceinline__ float sqrta(float x) { float r; asm("sqrt.approx.ftz.f32 %0, %1;" : "=f"(r) : "f"(x)); return r; }
__device__ __forceinline__ float ex2f(float x) { float r; asm("ex2.approx.ftz.f32 %0, %1;" : "=f"(r) : "f"(x)); return r; }
__device__ __forceinline__ void st_async4(uint32_t a, uint32_t x, uint32_t y, uint32_t z, uint32_t w, uint32_t mb) {
    asm volatile("st.async.shared::cluster.mbarrier::complete_tx::bytes.v4.u32 [%0], {%1,%2,%3,%4}, [%5];" :: "r"(a), "r"(x), "r"(y), "r"(z), "r"(w), "r"(mb) : "memory"); }
__device__ __forceinline__ void st_async1(uint32_t a, uint32_t x, uint32_t mb) {
    asm volatile("st.async.shared::cluster.mbarrier::complete_tx::bytes.u32 [%0], %1, [%2];" :: "r"(a), "r"(x), "r"(mb) : "memory"); }
__device__ __forceinline__ unsigned ld_rlx(const void* p) { unsigned v; asm volatile("ld.relaxed.gpu.global.u32 %0, [%1];" : "=r"(v) : "l"(p) : "memory"); return v; }
__device__ __forceinline__ unsigned ld_acq(const void* p) { unsigned v; asm volatile("ld.acquire.gpu.global.u32 %0, [%1];" : "=r"(v) : "l"(p) : "memory"); return v; }
__device__ __forceinline__ uint2 ld_rlx64(const void* p) { unsigned long long v; asm volatile("ld.relaxed.gpu.global.u64 %0, [%1];" : "=l"(v) : "l"(p) : "memory"); return make_uint2((unsigned)v, (unsigned)(v >> 32)); }
__device__ __forceinline__ void st_rlx128(void* p, uint32_t x, uint32_t y, uint32_t z, uint32_t w) {
    asm volatile("st.relaxed.gpu.global.v2.u64 [%0], {%1,%2};" :: "l"(p), "l"((unsigned long long)x | ((unsigned long long)y << 32)), "l"((unsigned long long)z | ((unsigned long long)w << 32)) : "memory"); }
__device__ __forceinline__ uint4 ld_rlx128(const void* p) { unsigned long long a, b; asm volatile("ld.relaxed.gpu.global.v2.u64 {%0,%1}, [%2];" : "=l"(a), "=l"(b) : "l"(p) : "memory"); return make_uint4((unsigned)a, (unsigned)(a >> 32), (unsigned)b, (unsigned)(b >> 32)); }
__device__ __forceinline__ void tma2d(uint32_t dst, const CUtensorMap* tm, int x, int y, uint32_t mb) {
    asm volatile("cp.async.bulk.tensor.2d.shared::cluster.global.mbarrier::complete_tx::bytes [%0], [%1, {%3, %4}], [%2];"
                 :: "r"(dst), "l"(tm), "r"(mb), "r"(x), "r"(y) : "memory");
}
__device__ __forceinline__ void cmul(float& xr, float& xi, float ar, float ai, float br, float bi) {
    const float r = fmaf(ar, br, -ai * bi), i = fmaf(ar, bi, ai * br); xr = r; xi = i;
}
__device__ __forceinline__ void csq(float& xr, float& xi, float ar, float ai) {
    const float r = fmaf(ar, ar, -ai * ai), i = (ar + ar) * ai; xr = r; xi = i;
}
__device__ __forceinline__ void cexp_s(float& zr, float& zi, float e2, float turns) {
    const float mag = ex2f(e2), r = (turns - rintf(turns)) * 6.283185307179586f;
    zr = mag * __cosf(r); zi = mag * __sinf(r);
}
__device__ __forceinline__ uint32_t ln_stats(float s1, float s2) {
    const float m = s1 * (1.f / D_);
    const float var = fmaxf(fmaf(s2, 1.f / D_, -m * m), 0.f);
    return pack_bf16(m, sqrta(bfr(bfr(var) + 1e-5f)));
}
__device__ __forceinline__ uint32_t rsplit(float rs) { const float h = bfr(rs); return pack_bf16(h, rs - h); }
__device__ __forceinline__ uint32_t norm2(uint32_t v, uint32_t mx, uint32_t hl) {
    uint32_t r;
    asm("{ .reg .b16 m, h, l, x; .reg .b32 m2, h2, l2, d, t; mov.b32 {m, x}, %2; mov.b32 {h, l}, %3; mov.b32 m2, {m, m}; mov.b32 h2, {h, h}; mov.b32 l2, {l, l};\n"
        "sub.rn.bf16x2 d, %1, m2; mul.rn.bf16x2 t, d, l2; fma.rn.bf16x2 %0, d, h2, t; }" : "=r"(r) : "r"(v), "r"(mx), "r"(hl));
    return r;
}
template <int N, int S>
__device__ __forceinline__ uint32_t rank4(uint32_t a, uint32_t key) {
    uint32_t r0 = 0, r1 = 0, r2 = 0, r3 = 0;
#pragma unroll
    for (int i = 0; i < N; i++) {
        const uint4 o = lds128(a + i * S);
        r0 += (key - o.x) >> 31; r1 += (key - o.y) >> 31; r2 += (key - o.z) >> 31; r3 += (key - o.w) >> 31;
    }
    return (r0 + r1) + (r2 + r3);
}
typedef uint32_t H2C;
__device__ __forceinline__ H2C splat(float r, float i) { return pack_f16(r, i); }
__device__ __forceinline__ void hcmul(uint32_t& xr, uint32_t& xi, uint32_t R, uint32_t I, H2C m) {
    asm("{ .reg .b16 a, b; .reg .b32 a2, b2, t; mov.b32 {a, b}, %4; mov.b32 a2, {a, a}; mov.b32 b2, {b, b};\n"
        "mul.rn.f16x2 t, %3, b2; neg.f16x2 t, t; fma.rn.f16x2 %0, %2, a2, t; mul.rn.f16x2 t, %3, a2; fma.rn.f16x2 %1, %2, b2, t; }"
        : "=&r"(xr), "=r"(xi) : "r"(R), "r"(I), "r"(m));
}
__device__ __forceinline__ void expand4(uint32_t are, uint32_t aim, uint32_t R0, uint32_t R1, uint32_t I0, uint32_t I1, H2C m4) {
    uint32_t R2, I2, R3, I3;
    hcmul(R2, I2, R0, I0, m4); hcmul(R3, I3, R1, I1, m4);
    sts128(are, R0, R1, R2, R3);
    sts128(aim, I0, I1, I2, I3);
}
__device__ __forceinline__ void expand8(uint32_t are, uint32_t aim, float sr, float si, float m1r, float m1i, float m2r, float m2i, H2C m4) {
    float r1, i1, r2, i2, r3, i3;
    cmul(r1, i1, sr, si, m1r, m1i); cmul(r2, i2, sr, si, m2r, m2i); cmul(r3, i3, r1, i1, m2r, m2i);
    expand4(are, aim, pack_f16(sr, r1), pack_f16(r2, r3), pack_f16(si, i1), pack_f16(i2, i3), m4);
}
__device__ __forceinline__ void put16(uint32_t a, uint32_t v) { sts16(a, v); sts16(a + 6, v); }

struct Params {
    const unsigned short *logdt, *dskip, *prm6[6], *x, *wr;
    __nv_bfloat16* out;
    Scratch* gs;
    unsigned zero;
};
__device__ __forceinline__ uint32_t tslot(uint32_t t) { return (t & 7) * 32 + ((t >> 4) & 24) + ((t >> 8) & 6) + ((t >> 6) & 1); }
#define CP(x) ((x) | zero)
#define PIN(x) asm volatile("or.b32 %0, %0, %1;" : "+r"(x) : "r"(zero))
__device__ __forceinline__ void wgmma32(float (&d)[4][4], const uint32_t (&a)[4], uint32_t dlo) {
    asm volatile("{ .reg .b64 ds; mov.b64 ds, {%20, %21};\n"
                 "wgmma.mma_async.sync.aligned.m64n32k16.f32.f16.f16 {%0,%1,%2,%3,%4,%5,%6,%7,%8,%9,%10,%11,%12,%13,%14,%15}, {%16,%17,%18,%19}, ds, 1, 1, 1, 0; }"
        : "+f"(d[0][0]), "+f"(d[0][1]), "+f"(d[0][2]), "+f"(d[0][3]), "+f"(d[1][0]), "+f"(d[1][1]), "+f"(d[1][2]), "+f"(d[1][3]),
          "+f"(d[2][0]), "+f"(d[2][1]), "+f"(d[2][2]), "+f"(d[2][3]), "+f"(d[3][0]), "+f"(d[3][1]), "+f"(d[3][2]), "+f"(d[3][3])
        : "r"(a[0]), "r"(a[1]), "r"(a[2]), "r"(a[3]), "r"(dlo), "n"(128 >> 4));
}

__device__ __forceinline__ void finish(const Params& prm, uint32_t fo, uint32_t oo, const float (&v)[3], float cnt) {
    float x, y, z, w;
    asm volatile("atom.relaxed.gpu.global.add.v4.f32 {%0,%1,%2,%3}, [%4], {%5,%6,%7,%8};" : "=f"(x), "=f"(y), "=f"(z), "=f"(w)
                 : "l"((char*)prm.gs->fin + fo), "f"(v[0]), "f"(v[1]), "f"(v[2]), "f"(cnt) : "memory");
    if (w + cnt == 3.f * (NCL + 1)) {
        __nv_bfloat16* op = (__nv_bfloat16*)((char*)prm.out + oo);
        op[0] = __float2bfloat16(x + v[0]); op[1] = __float2bfloat16(y + v[1]); op[2] = __float2bfloat16(z + v[2]);
    }
}

__global__ void __cluster_dims__(CS, 1, 1) __launch_bounds__(NTHR, 1)
fused_kernel(const __grid_constant__ Params prm, const __grid_constant__ CUtensorMap tmG, const __grid_constant__ CUtensorMap tmU,
             const __grid_constant__ CUtensorMap tmD, const __grid_constant__ CUtensorMap tmO, const __grid_constant__ CUtensorMap tmX, const __grid_constant__ CUtensorMap tmH)
{
    extern __shared__ __align__(1024) unsigned char smem[];
    const int tid = threadIdx.x, lane = tid & 31, warp = __shfl_sync(~0u, tid >> 5, 0);
    const int c = blockIdx.x >> 3, q = blockIdx.x & 7;
    const int nslot = (c < NCL - 1) ? 5 : 2;
    const int d0 = 40 * c;
    const uint32_t sb = opaque((uint32_t)__cvta_generic_to_shared(smem));
    const uint32_t mb = sb + SM_MB;
    Scratch& g_s = *prm.gs;
    const unsigned& zero = prm.zero;
    STAMP(0);

    if (warp >= 20) {
        unsigned epoch = 0;
        if (warp == 20) {
            if (lane == 0) {
#pragma unroll
                for (int i = 0; i < 13; i++)
                    asm volatile("mbarrier.init.shared::cta.b64 [%0], %1;" :: "r"(mb + i * 8), "r"((i == MB_R || i < 5) ? 2 : i == MB_Y ? 1 + 4 * nslot : 1) : "memory");
                asm volatile("fence.mbarrier_init.release.cluster;" ::: "memory");
                arm(mb + MB_W1 * 8, 92160); arm(mb + MB_W2 * 8, nslot * 9216); arm(mb + MB_KEY * 8, 256); arm(mb + MB_GU * 8, nslot * 1024); arm(mb + MB_T * 8, 576 * XW);
                const int bytes = max(min(18, L_ - 18 * (int)blockIdx.x), 1) * (D_ * 2);
                arm(mb + MB_R * 8, bytes);
            }
            __syncwarp();
        } else if (warp == 22) {
            epoch = ld_rlx(&g_s.epoch);
            if (lane < 18 ? 18 * c + lane < 256 : lane < 31) (lane < 18 ? &g_s.acc[256 * q + 18 * c] : &g_s.fin[13 * (int)blockIdx.x - 18])[lane] = make_float4(0.f, 0.f, 0.f, 0.f);
        } else if (warp == 23 && lane == 0) asm volatile("prefetch.tensormap [%0];" :: "l"(&tmX) : "memory");
        asm volatile("barrier.cluster.arrive.relaxed.aligned;" ::: "memory");
        bar_sync(12, NTHR);
        uint4 wv = make_uint4(0, 0, 0, 0), wv2, wv3;
        if (warp == 22) {
            if (lane == 0) { sts32(sb + SM_SC + 28, epoch); asm volatile("mbarrier.arrive.shared::cta.b64 _, [%0];" :: "r"(mb + MB_R * 8) : "memory"); }
            epoch++;
            asm volatile("fence.acq_rel.gpu;" ::: "memory");
            __syncwarp();
            if (lane == 0) asm volatile("red.relaxed.gpu.global.add.u32 [%0], 1;" :: "l"(&g_s.zcnt) : "memory");
            STAMP(1);
            wv2 = ldg128((const uint4*)prm.wr + lane); wv3 = ldg128((const uint4*)prm.wr + 32 + lane);
            if (lane < 8) wv = ldg128((const uint4*)prm.wr + 64 + lane);
            if (lane < 5) {
                uint4 v = make_uint4(0, 0, 0, 0);
                if (lane < nslot) v = ldg128((const uint4*)(prm.wr + d0) + lane);
                sts128(sb + SM_DW + lane * 16, v.x, v.y, v.z, v.w);
            }
            __syncwarp();
            if (lane < 5) asm volatile("mbarrier.arrive.shared::cta.b64 _, [%0];" :: "r"(mb + (MB_X + lane) * 8) : "memory");
        }
        if (warp == 21) {
            if (lane == 0) { asm volatile("prefetch.tensormap [%0];" :: "l"(&tmG) : "memory"); asm volatile("prefetch.tensormap [%0];" :: "l"(&tmU) : "memory"); asm volatile("prefetch.tensormap [%0];" :: "l"(&tmD) : "memory"); }
            __syncwarp();
            bar_sync(15, 672);
            asm volatile("fence.proxy.async.shared::cta;" ::: "memory");
#pragma unroll 1
            for (int i = 0; i < 24; i++) {
                if (lane == 0) tma2d(sb + SM_WG + i * 3840, i < 12 ? &tmG : &tmU, 320 * c + 8 * nslot * q, 48 * (i < 12 ? i : i - 12), mb + MB_W1 * 8);
            }
            STAMP(1);
        } else {
        if (warp == 20) {
            if (lane == 0) {
                asm volatile("cp.async.bulk.shared::cluster.global.mbarrier::complete_tx::bytes [%0], [%1], %2, [%3];"
                             :: "r"(sb + SM_ROW), "l"(prm.x + min(18 * (int)blockIdx.x, L_ - 1) * D_), "r"(max(min(18, L_ - 18 * (int)blockIdx.x), 1) * (D_ * 2)), "r"(mb + MB_R * 8) : "memory");
            }
            __syncwarp();
            mbar_wait(mb + MB_R * 8);
            if (lane == 0) {
                asm volatile("cp.async.bulk.tensor.5d.shared::cluster.global.mbarrier::complete_tx::bytes [%0], [%1, {%3, %4, %5, %5, %5}], [%2];"
                             :: "r"(sb + SM_XTL), "l"(&tmX), "r"(mb + MB_T * 8), "r"(d0 & ~15), "r"(8 * q), "r"(0) : "memory");
            }
            STAMP(6);
        }
        asm volatile("barrier.cluster.wait.aligned;" ::: "memory");
        bar_sync(13, 608);
        asm volatile("fence.proxy.async.shared::cta;" ::: "memory");
        {
            const int idx = lane * 3 + max(warp - 21, 0), sl = nslot - 1 - (idx >> 3), pe = (idx + q + 1) & 7;
            if (sl >= 0) {
                if (pe == q) arm(mb + (MB_X + sl) * 8, 7 * 512);
                else {
                    const uint32_t rb_ = mapa(sb, pe);
                    asm volatile("cp.async.bulk.shared::cluster.shared::cta.mbarrier::complete_tx::bytes [%0], [%1], 512, [%2];"
                                 :: "r"(rb_ + SM_U + 128 + q * UP + sl * US), "r"(sb + SM_XT + 128 + (q & 3) * 16 + pe * YP + sl * YS), "r"(rb_ + SM_MB + (MB_X + sl) * 8) : "memory");
                }
            }
        }
        STAMP(1);
        if (warp == 20 && lane == 0) { asm volatile("prefetch.tensormap [%0];" :: "l"(&tmO) : "memory"); asm volatile("prefetch.tensormap [%0];" :: "l"(&tmH) : "memory"); }
        if (warp == 22) {
            __syncwarp();
            mbar_wait(mb + (MB_X + 1) * 8);
            const uint32_t old = (epoch & 1) ? 0u : 0x40004000u;
#pragma unroll
            for (int t = 0; t < 2; t++)
                if ((lane & 7) < 6) g_s.cand[((q * 8 + 4 * t + (lane >> 3)) * NCL + c) * 6 + (lane & 7)] = make_uint4(old, old, old, old);
            float a[4] = {0.f, 0.f, 0.f, 0.f};
            const uint32_t one = 0x3F803F80u;
            mma_bf16(a, one, one, one, one, wv.x, wv.y);  mma_bf16(a, one, one, one, one, wv.z, wv.w);
            mma_bf16(a, one, one, one, one, wv2.x, wv2.y); mma_bf16(a, one, one, one, one, wv2.z, wv2.w);
            mma_bf16(a, one, one, one, one, wv3.x, wv3.y); mma_bf16(a, one, one, one, one, wv3.z, wv3.w);
            float s = a[0] + a[1];
            s += __shfl_xor_sync(~0u, s, 1); s += __shfl_xor_sync(~0u, s, 2);
            stsf(sb + SM_SC + 24, s);
            __syncwarp();
            if (lane == 0) {
                int n = 0;
                while ((int)(ld_acq(&g_s.zcnt) - epoch * NCTA) < 0 && ++n < SPIN_LIMIT) __nanosleep(200);
                arm(mb + MB_Y * 8, 8 * 512 * nslot);
                if (blockIdx.x == 0) g_s.epoch = epoch;
            }
            STAMP(2);
        }
        if (warp == 23) {
#pragma unroll 1
            for (int kk = nslot - 1; kk >= 0; kk--) {
                __syncwarp();
                bar_sync(6 + kk, 160);
                if (lane == 0) { asm volatile("fence.proxy.async.shared::cta;" ::: "memory"); tma2d(sb + SM_FAR + kk * FAR_SZ, &tmD, 72 * q, 320 * c + 64 * kk, mb + MB_W2 * 8); }
            }
        }
        }
        __syncwarp();
        bar_sync(14, 768);
        if (tid == 640) {
            asm volatile("fence.proxy.async.shared::cta;" ::: "memory");
            asm volatile("cp.async.bulk.tensor.5d.global.shared::cta.bulk_group [%0, {%2, %4, %4, %4, %3}], [%1];" :: "l"(&tmH), "r"(sb + SM_XT + 16384), "r"(d0 + ((c & 1) ? 0 : 32)), "r"(8 * q), "r"(0) : "memory");
            asm volatile("cp.async.bulk.tensor.5d.global.shared::cta.bulk_group [%0, {%2, %4, %4, %4, %3}], [%1];" :: "l"(&tmO), "r"(sb + SM_XT), "r"(d0 + (c & 1) * 8), "r"(8 * q), "r"(0) : "memory");
            asm volatile("cp.async.bulk.commit_group;" ::: "memory");
        }
        __syncwarp();
        const uint32_t ft = (tid >> 4) & 7, fj = d0 / 3 + (lane & 15), tok = ~lds32(sb + SM_SEL + ft * 8) & 2047;
        float v[3], cnt = 0.f;
#pragma unroll
        for (int i = 0; i < 3; i++) {
            const uint32_t cl = 3 * fj + i - d0, cf = cl - (c & 1) * 8;
            const bool ok = cl < 8 * nslot && ((tok >> 3) & 7) == q;
            const uint32_t u = lds16(sb + SM_XT + (cf < 32 ? tslot(tok) * 64 + cf * 2 : 16384 + tslot(tok) * 16 + (cl & 7) * 2));
            v[i] = ok ? __uint_as_float(u << 16) : 0.f;
            if (ok) cnt += 1.f;
        }
        if (tid == 640) {
            asm volatile("cp.async.bulk.wait_group 0;" ::: "memory");
            asm volatile("fence.proxy.async.global;" ::: "memory");
            asm volatile("mbarrier.arrive.shared::cta.b64 _, [%0];" :: "r"(mb + MB_OUT * 8) : "memory");
        }
        __syncwarp();
        mbar_wait(mb + MB_OUT * 8);
        STAMP(5);
        if (cnt != 0.f) finish(prm, (ft * 192 + fj) * 16, (tok * D_ + 3 * fj) * 2, v, cnt);
        return;
    }

    const int g = lane >> 2, cq = lane & 3;
    const int k = warp >> 2, wq = warp & 3;
    const int trow = 18 * blockIdx.x + warp;
    const bool rowact = warp < 18 && trow < L_;
    const int dch = min(d0 + 8 * k + q, D_ - 1);
    uint32_t pv[6];
    const uint32_t pofs = opaque((dch * 128 + wq * 32 + lane) * 2);
#pragma unroll
    for (int i = 0; i < 6; i++) pv[i] = ldg16((const char*)prm.prm6[i] + pofs);
    const uint32_t pLdt = ldg16(prm.logdt + dch), pD = ldg16(prm.dskip + dch);
    const int tn = 16 * (warp & 15) + g;
    uint32_t xa[5], xb[5];
    asm volatile("barrier.cluster.arrive.relaxed.aligned;" ::: "memory");
    uint4* const st1p = &g_s.st1[(((trow >> 3) & 7) * 256 + ((trow >> 6) & 31) * 8 + (trow & 7)) * 2 + (lane >> 2)];
    const bool pub = rowact && (lane & 0x1B) == 0;
    if (pub) st_rlx128(st1p, 0, 0, 0, 0);
    {
        const uint32_t za = sb + SM_P + tid * 16;
        sts128(za, 0, 0, 0, 0);
        if (tid < (SM_MISC - SM_P) / 16 - 640) sts128(za + 10240, 0, 0, 0, 0);
        sts128(sb + ((wq & 2) ? SM_U : SM_XT + (q & 3) * 16) + ((tid >> 3) & 7) * ((wq & 2) ? UP : YP) + k * YS + (lane & 7) * 16, 0, 0, 0, 0);
    }
    bar_sync(12, NTHR);
    const uint32_t dep = lds32(sb + SM_P);
#define PV(x) __uint_as_float(__byte_perm(dep, x, 0x5410))
    STAMP(1);
    const uint32_t fb = sb + SM_FAR + k * FAR_SZ;
    const uint32_t pn = sb + SM_PN + k * PN_SZ, pf = sb + SM_PF + k * PF_SZ;
    unsigned epoch;
    {
        const uint32_t kb = fb + wq * 3072;
        const uint32_t kl = kb + lane * 16;
        uint32_t Af[4][4];
        float sr, si, z1r, z1i, z2r, z2i, z4r, z4i, hr, hi_;
        {
            const float dt = bfr(ex2f(PV(pLdt) * 1.4426950408889634f));
            const float e2 = dt * PV(pv[0]) * 1.4426950408889634f, an = dt * PV(pv[1]);
            float ar, ai, br, bi, cr, ci, dr, di;
            { const float m = ex2f(e2 * 8.f); ar = m * __cosf(an * 8.f); ai = m * __sinf(an * 8.f); }
            csq(br, bi, ar, ai); csq(cr, ci, br, bi); csq(dr, di, cr, ci);
            const H2C m4 = splat(cr, ci);
            {
                float r3, i3;
                cmul(r3, i3, ar, ai, br, bi);
                expand4(kl, kl + 1024, pack_f16(1.f, ar), pack_f16(br, r3), pack_f16(0.f, ai), pack_f16(bi, i3), m4);
            }
            expand8(kl + 512, kl + 1536, dr, di, ar, ai, br, bi, m4);
            { const float m = ex2f(e2); z1r = m * __cosf(an); z1i = -m * __sinf(an); }
            cexp_s(hr, hi_, e2 * 128.f, an * (-128.f * 0.15915494309189535f));
            csq(z2r, z2i, z1r, z1i); csq(z4r, z4i, z2r, z2i);
            const uint32_t dep2 = lds32(sb + SM_P + 4);
#define PW(x) __uint_as_float(__byte_perm(dep2, x, 0x5410))
            cmul(sr, si, PW(pv[4]), PW(pv[5]), dt * PW(pv[2]), dt * PW(pv[3]));
            const unsigned E = min(max(__reduce_max_sync(~0u, __float_as_uint(fmaxf(fmaxf(fabsf(sr), fabsf(si)), fabsf(PW(pD)) * (1.f / 8192.f)))) >> 23, 1u), 253u);
            const float sc = __uint_as_float((254u - E) << 23);
            sr *= sc; si *= -sc;
            sts64(sb + SM_KG + warp * 8, E, __reduce_add_sync(~0u, __float2int_rn(sr * 16777216.f)));
            stsf(sb + SM_DW + 96 + k * 4, PW(pD));
        }
        __syncwarp();
#pragma unroll
        for (int ks = 0; ks < 4; ks++) ldsm4t(Af[ks], kb + (lane >> 3) * 512 + (lane & 7) * 16 + ks * 128);
        STAMP(2);
        const uint32_t la = kb + ((lane >> 3) & 1) * 512 + (lane >> 4) * 128 + (lane & 7) * 16;
        uint32_t b0[4], b1[4], b2[4], b3[4];
        auto ln1 = [&]() {
        mbar_wait(mb + MB_R * 8);
        epoch = lds32(sb + SM_SC + 28) + 1;
        {
            const uint32_t ra = sb + SM_ROW + warp * (D_ * 2);
            const uint4 r0 = lds128(ra + lane * 16), r1 = lds128(ra + 512 + lane * 16);
            const uint32_t rx[9] = {r0.x, r0.y, r0.z, r0.w, r1.x, r1.y, r1.z, r1.w, lds32(ra + 1024 + lane * 4)};
            float a0 = bf_lo(rx[0]), a1 = bf_hi(rx[0]), c0 = a0 * a0, c1 = a1 * a1;
#pragma unroll
            for (int i = 1; i < 9; i++) { const float l = bf_lo(rx[i]), h = bf_hi(rx[i]); a0 += l; a1 += h; c0 = fmaf(l, l, c0); c1 = fmaf(h, h, c1); }
            a0 += a1; c0 += c1;
            float s1 = ((lane & 1) ? c0 : a0) + __shfl_xor_sync(~0u, (lane & 1) ? a0 : c0, 1);
#pragma unroll
            for (int o = 2; o < 32; o <<= 1) s1 += __shfl_xor_sync(~0u, s1, o);
            const float s2 = __shfl_xor_sync(~0u, s1, 1);
            const uint32_t ms = ln_stats(s1, s2);
            const uint32_t p0 = __byte_perm(ms, epoch | 0x8000u, 0x5410), p1 = rsplit(rcpf(bf_hi(ms)));
            if (pub) st_rlx128(st1p, p0, p1, p0, p1);
        }
        mbar_wait(mb + MB_R * 8);
        STAMP(1);
        };
        const uint4* sp = &g_s.st1[(256 * q + tn) * 2];
        uint2 sa, sc;
        auto poll = [&]() { sa = ld_rlx64(sp); sc = ld_rlx64(sp + 16); };
        auto norm = [&]() {
        STAMP(3);
        if (warp < 16) {
            uint32_t va[5], vc[5];
            poll();
            mbar_wait(mb + MB_T * 8);
            {
                const uint32_t xt = sb + SM_XTL + (c & 1) * 16 + (72 * wq + 18 * k + g) * (2 * XW);
                uint4 a4 = lds128(xt + cq * 16), b4 = lds128(xt + cq * 16 + 18 * XW);
                va[0] = a4.x; va[1] = a4.y; va[2] = a4.z; va[3] = a4.w; va[4] = lds32(xt + 64 + cq * 4);
                vc[0] = b4.x; vc[1] = b4.y; vc[2] = b4.z; vc[3] = b4.w; vc[4] = lds32(xt + (64 + 18 * XW) + cq * 4);
            }
            const int d4 = 2 * (lane >> 3) + (lane & 1), d1_ = lane & 7;
            const uint32_t own = SM_U + 128 + q * (UP - YP), oth = SM_XT + 128 + (q & 3) * 16;
            uint32_t a4 = sb + warp * 32 + d4 * YP + (d4 == q ? own : oth) + ((lane & 7) >> 1) * YS;
            uint32_t a1 = sb + warp * 32 + d1_ * YP + (d1_ == q ? own : oth) + 4 * YS + (lane & 8) * 2;
            PIN(a4); PIN(a1);
            uint32_t tag = __byte_perm(epoch | 0x8000u, 0, 0x1010);
            PIN(tag);
            mbar_wait(mb + MB_T * 8);
            int n = 0;
            while (__byte_perm(sa.x, sc.x, 0x7632) != tag && ++n < SPIN_LIMIT) poll();
            STAMP(4);
#pragma unroll
            for (int i = 0; i < 5; i++) {
                va[i] = norm2(va[i], sa.x, sa.y); va[i] = pack_f16(bf_lo(va[i]), bf_hi(va[i]));
                vc[i] = norm2(vc[i], sc.x, sc.y); vc[i] = pack_f16(bf_lo(vc[i]), bf_hi(vc[i]));
            }
            stsm4t(a4, va[0], va[1], va[2], va[3]); stsm4t(a4 + 16, vc[0], vc[1], vc[2], vc[3]); stsm2t(a1, va[4], vc[4]);
            bar_arrive(13, 608);
            {
            const uint32_t xh = sb + SM_XTL + (c & 1) * 16 + (9 * g + 144 * (warp & 1) + (warp >> 1)) * (2 * XW);
            const uint4 c4 = lds128(xh + cq * 16), d4_ = lds128(xh + cq * 16 + 144 * XW);
            xa[0] = c4.x; xa[1] = c4.y; xa[2] = c4.z; xa[3] = c4.w; xa[4] = lds32(xh + 64 + cq * 4);
            xb[0] = d4_.x; xb[1] = d4_.y; xb[2] = d4_.z; xb[3] = d4_.w; xb[4] = lds32(xh + (64 + 144 * XW) + cq * 4);
            }
        }
        STAMP(5);
        __syncwarp();
        bar_sync(15, 672);
        Af[0][0] |= lds32(sb + SM_P);
        };
        cmul(sr, si, sr, si, z1r, z1i);
        {
            const H2C h4 = splat(z4r, z4i);
            expand8(kl, kl + 512, sr, si, z1r, z1i, z2r, z2i, h4);
            cmul(sr, si, sr, si, hr, hi_);
            expand8(kl + 1024, kl + 1536, sr, si, z1r, z1i, z2r, z2i, h4);
        }
        __syncwarp();
        ldsm4t(b0, la); ldsm4t(b1, la + 256); ldsm4t(b2, la + 1024); ldsm4t(b3, la + 1280);
        cmul(z1r, z1i, z1r, z1i, hr, hi_);
        cmul(sr, si, sr, si, z1r, z1i);
        expand8(kl, kl + 512, sr, si, z2r, z2i, z4r, z4i, splat(hr, hi_));
        ln1();
        csq(z1r, z1i, z1r, z1i);
        cmul(sr, si, sr, si, z1r, z1i);
        csq(z2r, z2i, hr, hi_);
        expand8(kl + 1024, kl + 1536, sr, si, z4r, z4i, hr, hi_, splat(z2r, z2i));
        csq(z1r, z1i, z1r, z1i);
        cmul(sr, si, sr, si, z1r, z1i);
        csq(z4r, z4i, z2r, z2i);
        expand8(kl + 2048, kl + 2560, sr, si, hr, hi_, z2r, z2i, splat(z4r, z4i));
        norm();
        {
            uint32_t c0[4], c1[4], c2[4], c3[4], e0[4], e1[4];
            float t[6][4];
            ldsm4t(c0, la); ldsm4t(c2, la + 1024);
            mma_f16_z(t[0], Af[0], b0[0], b0[1]);
            const uint32_t lb = la | (__float_as_uint(t[0][0]) & zero);
            mma_f16_z(t[1], Af[0], b2[0], b2[1]); mma_f16_z(t[2], Af[0], c0[0], c0[1]); mma_f16_z(t[3], Af[0], c2[0], c2[1]);
            ldsm4t(e0, lb + 2048); ldsm4t(c1, lb + 256); ldsm4t(c3, lb + 1280); ldsm4t(e1, lb + 2304);
            mma_f16(t[0], Af[1], b0[2], b0[3]); mma_f16(t[1], Af[1], b2[2], b2[3]); mma_f16(t[2], Af[1], c0[2], c0[3]); mma_f16(t[3], Af[1], c2[2], c2[3]);
            mma_f16(t[0], Af[2], b1[0], b1[1]); mma_f16(t[1], Af[2], b3[0], b3[1]);
            mma_f16_z(t[4], Af[0], e0[0], e0[1]); mma_f16_z(t[5], Af[1], e0[2], e0[3]);
            mma_f16(t[2], Af[2], c1[0], c1[1]); mma_f16(t[3], Af[2], c3[0], c3[1]);
            mma_f16(t[4], Af[2], e1[0], e1[1]); mma_f16(t[5], Af[3], e1[2], e1[3]);
            mma_f16(t[0], Af[3], b1[2], b1[3]); mma_f16(t[1], Af[3], b3[2], b3[3]); mma_f16(t[2], Af[3], c1[2], c1[3]); mma_f16(t[3], Af[3], c3[2], c3[3]);
            stsm4(kl + 1024, pack_f16(t[0][0], t[0][1]), pack_f16(t[0][2], t[0][3]), pack_f16(t[1][0], t[1][1]), pack_f16(t[1][2], t[1][3]));
            stsm2(kl + 1536, pack_f16(t[2][0], t[2][1]), pack_f16(t[2][2], t[2][3]));
            sts64(kb + lane * 8 + 1792, pack_f16(t[3][1], t[3][0]), pack_f16(t[3][3], t[3][2]));
            sts64(kb + lane * 8 + 2048, pack_f16(t[4][1] + t[5][1], t[4][0] + t[5][0]), pack_f16(t[4][3] + t[5][3], t[4][2] + t[5][2]));
        }
        bar_sync(1 + k, 128);
        const uint4 m01 = lds128(sb + SM_KG + k * 32), m23 = lds128(sb + SM_KG + k * 32 + 16);
        const unsigned Em = max(max(m01.x, m01.z), max(m23.x, m23.z));
        const float f0 = __uint_as_float(max((int)(127 + m01.x - Em), 0) << 23), f1 = __uint_as_float(max((int)(127 + m01.z - Em), 0) << 23),
                    f2 = __uint_as_float(max((int)(127 + m23.x - Em), 0) << 23), f3 = __uint_as_float(max((int)(127 + m23.z - Em), 0) << 23);
        const uint32_t r0 = pack_f16(f0, f0), r1 = pack_f16(f1, f1), r2 = pack_f16(f2, f2), r3 = pack_f16(f3, f3);
        const int tq = (wq + k) & 3;
        const uint32_t ra = fb + lane * 8 + (tq == 1 ? 2048 : tq * 256 + 1024);
        auto comb = [&](uint32_t a, uint32_t& x, uint32_t& y) {
            const uint2 p0 = lds64(a), p1 = lds64(a + 3072), p2 = lds64(a + 6144), p3 = lds64(a + 9216);
            x = hadd2(hfma2(p0.x, r0, hmul2(p1.x, r1)), hfma2(p2.x, r2, hmul2(p3.x, r3)));
            y = hadd2(hfma2(p0.y, r0, hmul2(p1.y, r1)), hfma2(p2.y, r2, hmul2(p3.y, r3)));
        };
        uint32_t w0, w1;
        comb(ra, w0, w1);
        const bool last = lane == 31;
        if (tq == 0) {
            uint32_t v0, v1;
            comb(ra + 256, v0, v1);
            const uint32_t n0 = __shfl_sync(~0u, lane ? w0 : v0, lane + 1);
            uint32_t n1 = __shfl_sync(~0u, v0, lane + 1);
            if (last) n1 = v1 >> 16;
            sts128(pn + 12 + lane * 16, __byte_perm(w1, w0, 0x7610), __byte_perm(w1, 0, 0x1032), __byte_perm(n0, w1, 0x7610), __byte_perm(n0, 0, 0x1032));
            sts128(pn + 524 + lane * 16, __byte_perm(v1, v0, 0x7610), __byte_perm(v1, 0, 0x1032), __byte_perm(n1, v1, 0x7610), __byte_perm(n1, 0, 0x1032));
            if (lane == 0) {
                sts32(sb + SM_SC + k * 4, Em * 0x00800080u);
                const uint32_t t0 = pack_f16(((float)(int)m01.y * f0 + (float)(int)m01.w * f1 + (float)(int)m23.y * f2 + (float)(int)m23.w * f3) * (1.f / 16777216.f)
                                         + ldsf(sb + SM_DW + 96 + k * 4) * __uint_as_float((254u - Em) << 23), 0.f);
                sts128(pn - 4, 0, t0, __byte_perm(w0, t0, 0x5410), __byte_perm(w0, 0, 0x1032));
            }
        } else if (tq == 1) {
            const uint32_t ph = pf + P_H7 + (g & 1) * (2 * P_HS) + cq * 64 + (g >> 1) * 4 + (cq & 2) * 16, sw = (cq & 2) ? 0x3210 : 0x1032;
            w0 = __byte_perm(hmul2(w0, 0x18001800u), 0, sw); w1 = __byte_perm(hmul2(w1, 0x18001800u), 0, sw);
            const uint32_t pi = ph + 32 - (cq & 2) * 32;
            put16(ph, w0); put16(pi, w0 >> 16); put16(ph + 16, w1); put16(pi + 16, w1 >> 16);
        } else if (tq == 2) {
            uint32_t n = __shfl_sync(~0u, w0, lane == 30 ? 1 : lane + 2);
            if (last) { put16(pf, hmul2(w1, 0x18001800u) >> 16); w1 = hadd2(w1, hneg2(__byte_perm(w1, 0, 0x3232))); n = 0; }
            const bool od = lane & 1;
            const uint32_t pa = pn + 1036 + (lane >> 1) * 32 + (od ? 528 : 0), pb = pa + (od ? -16 : 16);
            const uint32_t u0 = od ? w1 : w0, x0 = od ? n : w1, u1 = od ? w0 : w1, x1 = od ? w1 : n;
            const uint32_t b0 = __byte_perm(u0, 0, 0x3232), b1 = __byte_perm(u1, 0, 0x3232);
            sts128(pa, __byte_perm(u0, 0, 0x1032), b0, b0, __byte_perm(x0, u0, 0x7610));
            sts128(pb, __byte_perm(u1, 0, 0x1032), b1, b1, __byte_perm(x1, u1, 0x7610));
        } else {
            const uint32_t pa = pf + ((g & 1) ? 3 * P_GS : P_GS) + cq * 32 + (g >> 1) * 4;
            const uint32_t pb = pa + ((g & 1) ? 4 - 3 * P_GS : P_GS);
            w0 = hmul2(w0, 0x18001800u); w1 = hmul2(w1, 0x18001800u);
            put16(pa, w0 >> 16); put16(pb, w0); put16(pa + 16, w1 >> 16); put16(pb + 16, w1);
            if (last) put16(pf + P_H7 + P_HS, w1);
        }
        bar_sync(1 + k, 128);
        if (tq == 2 && lane == 0) sts16(pn + 258 * 4, w0);
    }
    STAMP(6);

    asm volatile("barrier.cluster.wait.aligned;" ::: "memory");
    mbar_wait(mb + (MB_X + (k < nslot ? k : 0)) * 8);
    STAMP(7);
    if (k < nslot) {
        const int role = (wq + k) & 3;
        const uint32_t ub = sb + SM_U + k * US + 128;
        if (role) {
            const int r = (3 - role) * 32 + lane;
            const uint32_t a1 = ub + (r & 3) * (2 * UP) + (r >> 2) * 16, a0 = a1 + ((r & 3) ? -2 * UP : 6 * UP - 16);
            const uint4 q0 = lds128(a0), q1 = lds128(a0 + UP), q2 = lds128(a1), q3 = lds128(a1 + UP);
            const uint32_t U[16] = {q0.x, q0.y, q0.z, q0.w, q1.x, q1.y, q1.z, q1.w, q2.x, q2.y, q2.z, q2.w, q3.x, q3.y, q3.z, q3.w};
            uint32_t V[14], Q[14], R4[12], T[8];
#pragma unroll
            for (int i = 2; i < 14; i++) { V[i] = __byte_perm(U[i], U[i + 1], 0x5432); Q[i] = hadd2(U[i], V[i]); }
#pragma unroll
            for (int i = 2; i < 12; i++) R4[i] = hadd2(Q[i], Q[i + 1]);
            const uint32_t rb = fb + r * 16;
#pragma unroll
            for (int i = 0; i < 8; i++) T[i] = hadd2(V[5 + i], Q[6 + i]);
            sts128(rb + F_E3, T[0], T[1], T[2], T[3]); sts128(rb + F_O3 + 16, T[4], T[5], T[6], T[7]);
#pragma unroll
            for (int i = 0; i < 8; i++) T[i] = hadd2(R4[3 + i], U[5 + i]);
            sts128(rb + F_O5, T[0], T[1], T[2], T[3]); sts128(rb + F_E5, T[4], T[5], T[6], T[7]);
            if (role != 1) {
#pragma unroll
                for (int i = 0; i < 8; i++) T[i] = hadd2(T[i], hadd2(V[2 + i], V[5 + i]));
                sts128(rb + F_E7, T[0], T[1], T[2], T[3]); sts128(rb + F_O7, T[4], T[5], T[6], T[7]);
#pragma unroll
                for (int i = 0; i < 8; i++) T[i] = hadd2(R4[2 + i], hadd2(R4[4 + i], U[6 + i]));
                sts128(rb + F_O9, T[0], T[1], T[2], T[3]); sts128(rb + F_E9 + 16, T[4], T[5], T[6], T[7]);
                sts128(rb + F_E2, Q[6], Q[7], Q[8], Q[9]); sts128(rb + F_O2, Q[10], Q[11], Q[12], Q[13]);
            }
        } else if (lane < 8) {
            uint32_t v[5];
#pragma unroll
            for (int i = 0; i < 5; i++) { const int t = 6 + lane + i; v[i] = lds16(ub + 23 * 16 + (t < 16 ? (6 + (t >> 3)) * UP : 16) + (t & 7) * 2); }
            const uint32_t s = hadd2(hadd2(hadd2(v[0], v[1]), hadd2(v[2], v[3])), v[4]);
            sts16(fb + F_O5 + 96 * 16 + lane * 2, s);
            sts32(fb + (lane < 4 ? F_O3 : F_E9 - 16) + lane * 4, 0);
        }
        bar_sync(1 + k, 128);
        float acc[4][4];
        uint32_t Q[4][4];
        {
            const int h = role & 1, part = role >> 1;
            const uint32_t po = pf + (g - 2 * cq) * 4;
            float fa[7][4];
#pragma unroll
            for (int a = 1; a < 7; a++) fa[a][0] = fa[a][1] = fa[a][2] = fa[a][3] = 0.f;
            uint32_t B[3][4];
            Q[0][2] = tid & zero; Q[2][1] = lane & zero;
#pragma unroll 1
            for (int s = 2 * part + 1; s >= 2 * part; s--) {
#pragma unroll
                for (int i = 0; i < 3; i++) { Q[i][0] = lds32(po + s * P_GS + i * 64); if (i < 2) Q[i][1] = lds32(po + s * P_GS + (i * 64 + 32)); }
                const uint32_t ba = fb + lane * 16 + ((s & 1) * F_E3 + (part == h ? 0 : F_O5 + h * 16));
#pragma unroll
                for (int i = 0; i < 3; i++) ldsm4t(B[i], ba + i * 512);
#pragma unroll
                for (int i = 0; i < 3; i++) { Q[i][3] = CP(Q[i][0]); if (i) Q[i][2] = CP(Q[i - 1][1]); }
#pragma unroll
                for (int dl = 0; dl < 3; dl++)
#pragma unroll
                    for (int ap = 0; ap < 6 - dl; ap++) mma_f16(fa[ap + 1 + dl], Q[dl], B[ap >> 1][2 * (ap & 1)], B[ap >> 1][2 * (ap & 1) + 1]);
            }
#pragma unroll 1
            for (int s = role; s == 1; s++) {
                ldsm2t(B[0][0], B[0][1], fb + ((lane & 15) == 15 ? F_O5 : F_O3));
#pragma unroll
                for (int dl = 1; dl < 3; dl++) mma_f16(fa[dl], Q[dl], B[0][0], B[0][1]);
            }
#pragma unroll 1
            for (int s = part; s <= 2 * part; s++) {
#pragma unroll
                for (int i = 0; i < 4; i++) { Q[i][0] = lds32(po + s * P_HS + (P_H7 + i * 64)); Q[i][1] = lds32(po + s * P_HS + (P_H7 + i * 64 + 32)); }
                const uint32_t ba = fb + lane * 16 + (F_E7 + s * 1024 + h * F_H);
                ldsm4t(B[0], ba); ldsm4t(B[1], ba + 512);
#pragma unroll
                for (int i = 0; i < 4; i++) { Q[i][3] = CP(Q[i][0]); if (i) Q[i][2] = CP(Q[i - 1][1]); }
#pragma unroll
                for (int dl = 0; dl < 4; dl++) {
#pragma unroll
                    for (int ap = 0; ap < 4 - dl; ap++) mma_f16(fa[ap + 3 + dl], Q[dl], B[ap >> 1][2 * (ap & 1)], B[ap >> 1][2 * (ap & 1) + 1]);
                    if (s == 1) break;
                }
            }
            const uint32_t da = fb + role * 2048 + (lane & 3) * 512 + (((lane >> 2) ^ ((lane & 3) * 2)) << 4);
            bar_sync(1 + k, 128);
#pragma unroll
            for (int i = 1; i < 4; i++)
                stsm4(da + i * 128, pack_f16(fa[2 * i - 1][0], fa[2 * i - 1][1]), pack_f16(fa[2 * i - 1][2], fa[2 * i - 1][3]),
                      pack_f16(fa[2 * i][0], fa[2 * i][1]), pack_f16(fa[2 * i][2], fa[2 * i][3]));
            Q[0][0] = (g == 2 * cq) ? 0x6000u : ((g == 2 * cq + 1) ? 0x60000000u : 0u);
            Q[0][1] = Q[0][0] & zero; Q[0][2] = lane & zero; Q[0][3] = CP(Q[0][0]);
            const uint32_t ra = fb + (lane >> 3) * 2048 + wq * 512 + (((lane & 7) ^ (wq * 2)) << 4);
            acc[0][0] = acc[0][1] = acc[0][2] = acc[0][3] = 0.f;
            if (wq == 3) {
                const uint32_t uw = lds32(ub), kw = lds32(pf);
                const float2 uf = __half22float2(*(const __half2*)&uw);
                if ((lane | 4) == 31) acc[0][3] = (lane == 31 ? uf.x + uf.y : uf.x) * (__low2float(*(const __half2*)&kw) * 512.f);
            }
            bar_sync(1 + k, 128);
#pragma unroll
            for (int i = 1; i < 4; i++) {
                ldsm4(B[0], ra + i * 128);
                mma_f16_z(acc[i], Q[0], hadd2(B[0][0], B[0][2]), hadd2(B[0][1], B[0][3]));
            }
        }
        bar_arrive(6 + k, 160);
        STAMP(8);
        const uint32_t inv = lds32(sb + SM_SC + k * 4);
        uint32_t yd = mapa(sb, 2 * wq) + (SM_XT + 128 + q * YP + k * YS + (k >> 2) * (q >> 1) * 16) + lane * 16;
        PIN(yd);
        {
            uint32_t pp = pn + (16 * (wq - 3) + g - 2 * cq) * 4;
            uint32_t dlo = (((ub + 6 * UP) & 0x3FFFF) >> 4) | ((UP >> 4) << 16);
            uint32_t R[4][4];
            auto loadQ = [&](uint32_t (&X)[4][4], uint32_t prev) {
#pragma unroll
                for (int i = 0; i < 4; i++) { X[i][0] = lds32(pp + i * 64); X[i][1] = lds32(pp + i * 64 + 32); }
                X[0][2] = CP(prev);
#pragma unroll
                for (int i = 0; i < 4; i++) { X[i][3] = CP(X[i][0]); if (i) X[i][2] = CP(X[i - 1][1]); }
                pp += 256;
            };
            auto issue = [&](uint32_t (&X)[4][4]) {
                asm volatile("wgmma.fence.sync.aligned;" ::: "memory");
#pragma unroll
                for (int i = 0; i < 4; i++) wgmma32(acc, X[i], dlo - i * (2 * UP >> 4));
                asm volatile("wgmma.commit_group.sync.aligned;" ::: "memory");
                dlo -= 1;
            };
            loadQ(Q, 0);
#pragma unroll 1
            for (int dl = 0; dl < 4; dl++) {
                issue(Q);
                asm volatile("wgmma.wait_group.sync.aligned 1;" ::: "memory");
                loadQ(R, Q[3][1]);
                issue(R);
                asm volatile("wgmma.wait_group.sync.aligned 1;" ::: "memory");
                loadQ(Q, R[3][1]);
            }
            issue(Q);
            asm volatile("wgmma.wait_group.sync.aligned 0;" ::: "memory");
        }
        const uint32_t pstep = mapa(sb, 1) - mapa(sb, 0), ym = mapa(mb + MB_Y * 8, 2 * wq);
#pragma unroll
        for (int e = 0; e < 2; e++)
            st_async4(yd + e * pstep, bmul2(pack_bf16(acc[0][2 * e], acc[0][2 * e + 1]), inv), bmul2(pack_bf16(acc[1][2 * e], acc[1][2 * e + 1]), inv),
                      bmul2(pack_bf16(acc[2][2 * e], acc[2][2 * e + 1]), inv), bmul2(pack_bf16(acc[3][2 * e], acc[3][2 * e + 1]), inv), ym + e * pstep);
        if (lane == 0) asm volatile("mbarrier.arrive.shared::cta.b64 _, [%0];" :: "r"(mb + MB_Y * 8) : "memory");
    }
    STAMP(9);
    uint32_t ha[5], hb[5];
    if (warp < 16) {
        const uint4 wk = lds128(sb + SM_DW + cq * 16);
        uint32_t sel[5] = {wk.x, wk.y, wk.z, wk.w, lds32(sb + SM_DW + 64 + cq * 4)}, sel2[5];
#pragma unroll
        for (int i = 0; i < 5; i++) {
            if (!(g & 1)) sel[i] = 0x3F803F80u;
            sel2[i] = sel[i]; PIN(sel2[i]);
        }
        const uint32_t y4 = sb + SM_XT + 128 + warp * 32 + (2 * (lane >> 3) + (lane & 1)) * YP + ((lane & 7) >> 1) * YS;
        const uint32_t y1 = sb + SM_XT + 128 + warp * 32 + (lane & 7) * YP + 4 * YS + (lane & 8) * 2 + (lane & 6) * 8;
        uint32_t ao = (256 * q + tn) * 16, hta = sb + SM_HT + tn * 80;
        PIN(ao); PIN(hta);
        mbar_wait(mb + MB_Y * 8);
        STAMP(10);
        float ca[4] = {0.f, 0.f, 0.f, 0.f}, cb[4] = {0.f, 0.f, 0.f, 0.f};
        {
            uint32_t ya[4], yb[4], yc, yd;
            ldsm4t(ya, y4); ldsm4t(yb, y4 + 16); ldsm2t(yc, yd, y1);
#pragma unroll
            for (int i = 0; i < 4; i++) { ha[i] = badd2(xa[i], ya[i]); hb[i] = badd2(xb[i], yb[i]); }
            ha[4] = badd2(xa[4], yc); hb[4] = badd2(xb[4], yd);
        }
        if (nslot != 5) {
            ha[4] = hb[4] = 0;
            if (cq >= 2) ha[0] = ha[1] = ha[2] = ha[3] = hb[0] = hb[1] = hb[2] = hb[3] = 0;
        }
#pragma unroll
        for (int i = 0; i < 5; i++) { mma_bf16_k8(ca, ha[i], sel[i], ha[i]); mma_bf16_k8(cb, hb[i], sel2[i], hb[i]); }
        if (!(g & 1)) { ca[1] = ca[0]; cb[1] = cb[0]; }
        if (cq == (g >> 1)) {
            asm volatile("red.relaxed.gpu.global.add.v4.f32 [%0], {%1,%2,%3,%4};" :: "l"((char*)g_s.acc + ao), "f"(1.0f), "f"(ca[1]), "f"(ca[2]), "f"(ca[3]) : "memory");
            asm volatile("red.relaxed.gpu.global.add.v4.f32 [%0], {%1,%2,%3,%4};" :: "l"((char*)g_s.acc + ao + 128), "f"(1.0f), "f"(cb[1]), "f"(cb[2]), "f"(cb[3]) : "memory");
        }
        sts128(hta + cq * 16, ha[0], ha[1], ha[2], ha[3]); sts32(hta + 64 + cq * 4, ha[4]);
        sts128(hta + cq * 16 + 640, hb[0], hb[1], hb[2], hb[3]); sts32(hta + 704 + cq * 4, hb[4]);
        STAMP(11);
    }
    const int kq = warp / 5, mt = warp - 5 * kq;
    const int mi = lane >> 3, mr = lane & 7;
    const unsigned tk = (unsigned)tid / 72u, ck = tid - tk * 72;
    uint32_t A[9][4];
    auto loadA = [&]() {
        mbar_wait(mb + MB_W1 * 8);
        const uint32_t aa = sb + (mi & 1) * SM_WU + (8 * (mi >> 1) + mr) * 80 + (144 * 80 * kq + mt * 16);
#pragma unroll
        for (int s = 0; s < 9; s++) ldsm4t(A[s], aa + s * 1280);
    };
    const uint32_t par = (lds32(sb + SM_SC + 28) & 1) ? 0u : 0x40004000u;
    uint32_t pk0 = mapa(sb, 2 * cq), go = (ck / 5u + ck) * 16, co = ((q * 8 * NCL + c) * 6 + cq) * 16;
    PIN(pk0); PIN(go); PIN(co);
    if (warp < 8) {
        const float wsum = ldsf(sb + SM_SC + 24);
        const uint32_t idx = 2047 - (512 * ((tid >> 1) & 3) + 128 * ((tid >> 3) & 3) + 64 * (tid & 1) + 8 * q + warp);
        uint4 s; int n = 0;
        do { s = ld_rlx128(&g_s.acc[256 * q + tid]); } while (__uint_as_float(s.x) != (float)NCL && ++n < SPIN_LIMIT);
        STAMP(16);
        const uint32_t ox = __shfl_xor_sync(~0u, (lane & 1) ? s.z : s.w, 1);
        const uint32_t ms = ln_stats(__uint_as_float((lane & 1) ? ox : s.z), __uint_as_float(s.y));
        const float rs = rcpf(bf_hi(ms));
        const uint32_t rb = pack_bf16(0.f, fmaf(-bf_lo(ms), wsum, __uint_as_float((lane & 1) ? s.w : ox)) * rs);
        const uint32_t key = (((rb ^ (((int)rb >> 31) | 0x80000000u)) >> 16) << 11) | idx;
        sts32(sb + SM_KEY + tid * 4, key);
        __syncwarp();
        const uint32_t rank = rank4<8, 16>(sb + SM_KEY + warp * 128, key);
        asm volatile("{ .reg .pred p; setp.lt.u32 p, %0, 8; @p st.shared.u32 [%1], %2; }" :: "r"(rank), "r"(sb + SM_CAND + warp * 32 + rank * 4), "r"(key) : "memory");
        sts64(sb + SM_ST + tid * 8, ms, rsplit(rs));
    } else { mbar_wait(mb + MB_Y * 8); loadA(); }
    if (warp < 16) {
        STAMP(17);
        bar_sync(12, 512);
        STAMP(18);
        if (warp < 8) {
            const uint32_t mk = lds32(sb + SM_CAND + (tid >> 2) * 4);
            uint32_t rank = rank4<4, 64>(sb + SM_CAND + cq * 16, mk);
            rank += __shfl_xor_sync(~0u, rank, 1); rank += __shfl_xor_sync(~0u, rank, 2);
            if (rank < 8) {
                const uint32_t pk1 = pk0 + (mapa(sb, 1) - mapa(sb, 0));
                st_async1(pk0 + (SM_RK + q * 32) + rank * 4, mk, pk0 + (SM_MB + MB_KEY * 8));
                st_async1(pk1 + (SM_RK + q * 32) + rank * 4, mk, pk1 + (SM_MB + MB_KEY * 8));
                const uint32_t t = tslot(~mk | ((pk1 + rank * 4) & zero));
                const uint2 sv = lds64(sb + SM_ST + t * 8);
                const uint4 hv = lds128(sb + SM_HT + t * 80 + cq * 16);
                const uint32_t h4 = lds32(sb + SM_HT + t * 80 + 64 + cq * 4);
                const uint32_t rr = bmul2(sv.y, 0x3C803C80u);
                char* const dp = (char*)g_s.cand + (co + rank * 1440);
                st_rlx128(dp, (norm2(hv.x, sv.x, rr) & 0xBFFFBFFFu) | par, (norm2(hv.y, sv.x, rr) & 0xBFFFBFFFu) | par,
                          (norm2(hv.z, sv.x, rr) & 0xBFFFBFFFu) | par, (norm2(hv.w, sv.x, rr) & 0xBFFFBFFFu) | par);
                asm volatile("st.relaxed.gpu.global.u32 [%0], %1;" :: "l"((char*)g_s.cand + (co + rank * 1440 + 64 - cq * 12)), "r"((norm2(h4, sv.x, rr) & 0xBFFFBFFFu) | par) : "memory");
            }
            __syncwarp();
        }
        {
            const uint2 sa = lds64(sb + SM_ST + tn * 8), sbb = lds64(sb + SM_ST + tn * 8 + 64);
#pragma unroll
            for (int i = 0; i < 5; i++) { ha[i] = badd2(ha[i], norm2(ha[i], sa.x, sa.y)); hb[i] = badd2(hb[i], norm2(hb[i], sbb.x, sbb.y)); }
            const bool hf = (c & 1) && cq == 0;
            const uint32_t o16 = sb + SM_XT + (hf ? 16384 + tn * 16 : tn * 64 + (cq - (c & 1)) * 16), o4 = sb + SM_XT + ((c & 1) ? tn * 64 + 48 : 16384 + tn * 16) + cq * 4;
            sts128(o16, ha[0], ha[1], ha[2], ha[3]); sts32(o4, ha[4]);
            sts128(o16 + (hf ? 128 : 512), hb[0], hb[1], hb[2], hb[3]); sts32(o4 + ((c & 1) ? 512 : 128), hb[4]);
        }
        if (warp >= 8) {
            STAMP(19);
            mbar_wait(mb + MB_KEY * 8);
            STAMP(20);
            const uint32_t mk = lds32(sb + SM_RK - 256 + (tid >> 2) * 4);
            uint32_t rank = rank4<4, 64>(sb + SM_RK + cq * 16, mk);
            rank += __shfl_xor_sync(~0u, rank, 1); rank += __shfl_xor_sync(~0u, rank, 2);
            if (rank < 8) sts64(sb + SM_SEL + rank * 8, mk, ((tid >> 2) - 64) * 1440);
        }
    }
    bar_sync(11, 640);
    STAMP(12);

    const char* gp = (const char*)g_s.cand + (go + lds32(sb + SM_SEL + 4 + (tk & 7) * 8));
    uint4 hv = ld_rlx128(gp);
    if (warp < 8) loadA();
    const uint32_t ft = (unsigned)tid / 24u, fj = 24 * q + tid - ft * 24;
    const uint32_t key = lds32(sb + SM_SEL + (ft & 7) * 8), k16 = key << 5;
    float sig = bfr(rcpf(1.f + ex2f(__uint_as_float((k16 ^ (~((int)k16 >> 31) | 0x80000000u)) & 0xFFFF0000u) * -1.4426950408889634f)));
    uint32_t ra2 = sb + SM_RED2 + tid * 12 + ft * 16, fo = (ft * 192 + fj) * 16, oo = ((~key & 2047) * D_ + 3 * fj) * 2;
    uint32_t bx = sb + SM_XS + mr * 1168 + mi * 16 + 288 * kq, gd = mapa(sb, kq * (8 / NRED)) + (SM_GU + (q * nslot + mt) * 128) + lane * 4;
    PIN(ra2); PIN(fo); PIN(oo); PIN(bx); PIN(gd);
    asm volatile("" : "+f"(sig));
    {
        if (warp < 18) {
            int n = 0;
            while (true) {
                sts128(sb + SM_XS + tk * 16 + tid * 16, hv.x ^ par, hv.y ^ par, hv.z ^ par, hv.w ^ par);
                if (!__any_sync(~0u, ((hv.x ^ par) | (hv.y ^ par) | (hv.z ^ par) | (hv.w ^ par)) & 0x40004000u) || ++n >= SPIN_LIMIT) break;
                hv = ld_rlx128(gp);
            }
        }
    }
    bar_sync(14, 768);
    STAMP(13);
    {
        float c0[4] = {0.f, 0.f, 0.f, 0.f}, c1[4] = {0.f, 0.f, 0.f, 0.f}, c2[4] = {0.f, 0.f, 0.f, 0.f};
        uint32_t b[5][4];
#pragma unroll
        for (int s = 0; s < 4; s++) ldsm4(b[s], bx + s * 64);
        asm volatile("ldmatrix.sync.aligned.m8n8.x2.shared.b16 {%0,%1}, [%2];" : "=r"(b[4][0]), "=r"(b[4][1]) : "r"(bx + 256) : "memory");
        mma_bf16(c0, A[0][0], A[0][1], A[0][2], A[0][3], b[0][0], b[0][1]);
        mma_bf16(c1, A[1][0], A[1][1], A[1][2], A[1][3], b[0][2], b[0][3]);
        mma_bf16(c2, A[2][0], A[2][1], A[2][2], A[2][3], b[1][0], b[1][1]);
        mma_bf16(c0, A[3][0], A[3][1], A[3][2], A[3][3], b[1][2], b[1][3]);
        mma_bf16(c1, A[4][0], A[4][1], A[4][2], A[4][3], b[2][0], b[2][1]);
        mma_bf16(c2, A[5][0], A[5][1], A[5][2], A[5][3], b[2][2], b[2][3]);
        mma_bf16(c0, A[6][0], A[6][1], A[6][2], A[6][3], b[3][0], b[3][1]);
        mma_bf16(c1, A[7][0], A[7][1], A[7][2], A[7][3], b[3][2], b[3][3]);
        mma_bf16(c2, A[8][0], A[8][1], A[8][2], A[8][3], b[4][0], b[4][1]);
        sts128f(sb + SM_RED + tid * 16, c0[0] + c1[0] + c2[0], c0[1] + c1[1] + c2[1], c0[2] + c1[2] + c2[2], c0[3] + c1[3] + c2[3]);
    }
    bar_sync(1 + mt, 128);
    STAMP(21);
    if (mt < nslot && kq < NRED) {
        const uint32_t ra = sb + SM_RED + mt * 512 + lane * 16;
        const float4 p0 = lds128f(ra), p1 = lds128f(ra + 2560), p2 = lds128f(ra + 5120), p3 = lds128f(ra + 7680);
        const float g0 = bfr(((p0.x + p1.x) + (p2.x + p3.x)) * 64.f), g1 = bfr(((p0.y + p1.y) + (p2.y + p3.y)) * 64.f);
        const uint32_t sg = pack_bf16(g0 * rcpf(1.f + ex2f(g0 * -1.4426950408889634f)), g1 * rcpf(1.f + ex2f(g1 * -1.4426950408889634f)));
        const uint32_t gu = bmul2(sg, pack_bf16(((p0.z + p1.z) + (p2.z + p3.z)) * 64.f, ((p0.w + p1.w) + (p2.w + p3.w)) * 64.f));
        const uint32_t pstep = mapa(sb, 1) - mapa(sb, 0), gm = mapa(mb + MB_GU * 8, kq * (8 / NRED));
#pragma unroll
        for (int i = 0; i < 8 / NRED; i++) st_async1(gd + i * pstep, gu, gm + i * pstep);
    }
    mbar_wait(mb + MB_W2 * 8);
    {
        const uint32_t aa = sb + (8 * (mi >> 1) + mr) * 144 + (mi & 1) * 16 + (SM_FAR + 2304 * kq + mt * 32);
#pragma unroll
        for (int s = 0; s < 5; s++) ldsm4t(A[s], aa + s * FAR_SZ);
    }
    {
        uint32_t ba = sb + (SM_GU + 256 * kq) + (lane & 15) * 16 + (lane >> 4) * 1024, wa = sb + (SM_RED2 + kq * 2432 + mt * 64) + g * 4 + cq * 608;
        PIN(ba); PIN(wa);
        STAMP(22);
        mbar_wait(mb + MB_GU * 8);
        STAMP(23);
        float c0[4] = {0.f, 0.f, 0.f, 0.f}, c1[4] = {0.f, 0.f, 0.f, 0.f}, c2[4] = {0.f, 0.f, 0.f, 0.f};
        uint32_t b[2][4], b8, b9;
        ldsm4t(b[0], ba); ldsm4t(b[1], ba + 2048); ldsm2t(b8, b9, ba + 4096);
        mma_bf16(c0, A[0][0], A[0][1], A[0][2], A[0][3], b[0][0], b[0][1]);
        mma_bf16(c1, A[1][0], A[1][1], A[1][2], A[1][3], b[0][2], b[0][3]);
        if (nslot == 5) {
            mma_bf16(c2, A[4][0], A[4][1], A[4][2], A[4][3], b8, b9);
            mma_bf16(c0, A[2][0], A[2][1], A[2][2], A[2][3], b[1][0], b[1][1]);
            mma_bf16(c1, A[3][0], A[3][1], A[3][2], A[3][3], b[1][2], b[1][3]);
        }
        stsf(wa, c0[0] + c1[0] + c2[0]); stsf(wa + 304, c0[1] + c1[1] + c2[1]);
        if (mt < 4) { stsf(wa + 32, c0[2] + c1[2] + c2[2]); stsf(wa + 336, c0[3] + c1[3] + c2[3]); }
    }
    if (warp < 6) {
        float v[3];
        bar_sync(6, 640);
        STAMP(14);
#pragma unroll
        for (int i = 0; i < 3; i++) v[i] = ((ldsf(ra2 + i * 4) + ldsf(ra2 + i * 4 + 2432)) + (ldsf(ra2 + i * 4 + 4864) + ldsf(ra2 + i * 4 + 7296))) * sig;
        finish(prm, fo, oo, v, 3.f);
    } else bar_arrive(6, 640);
    STAMP(15);
}

typedef __nv_bfloat16 bf16;
__device__ bf16 f_n[L_ * D_], f_h[L_ * D_];
__device__ float f_k[D_ * L_], f_r[L_], f_gu[8 * F_];
__device__ int f_idx[8];
__device__ __forceinline__ float b2f(bf16 v) { return __bfloat162float(v); }
__global__ void fb_ln(const bf16* in, const bf16* wr, bf16* out) {
    const int t = blockIdx.x * 8 + (threadIdx.x >> 5), lane = threadIdx.x & 31;
    const bf16* r = (in ? in : f_h) + t * D_;
    float s1 = 0.f, s2 = 0.f, s3 = 0.f;
    for (int i = lane; i < D_; i += 32) s1 += b2f(r[i]);
    for (int o = 16; o; o >>= 1) s1 += __shfl_xor_sync(~0u, s1, o);
    for (int i = lane; i < D_; i += 32) { const float d = b2f(r[i]) - s1 / D_; s2 += d * d; }
    for (int o = 16; o; o >>= 1) s2 += __shfl_xor_sync(~0u, s2, o);
    const float m = bfr(s1 / D_), sd = bfr(sqrtf(bfr(bfr(s2 / D_) + 1e-5f)));
    for (int i = lane; i < D_; i += 32) {
        const float v = bfr(bfr(b2f(r[i]) - m) / sd);
        f_n[t * D_ + i] = __float2bfloat16(v);
        if (!in) { s3 += v * b2f(wr[i]); out[t * D_ + i] = __float2bfloat16(b2f(r[i]) + v); }
    }
    for (int o = 16; o; o >>= 1) s3 += __shfl_xor_sync(~0u, s3, o);
    f_r[t] = bfr(s3);
}
__global__ void fb_taps(Params p) {
    const int d = blockIdx.x >> 3, l = (blockIdx.x & 7) * 256 + threadIdx.x;
    const float dt = bfr(expf(bf_lo(p.logdt[d]))), lf = bfr((float)l);
    float k = 0.f;
    for (int n = d * 128; n < d * 128 + 128; n++) {
        float wr, wi, sn, cs;
        cmul(wr, wi, bf_lo(p.prm6[4][n]), bf_lo(p.prm6[5][n]), dt * bf_lo(p.prm6[2][n]), dt * bf_lo(p.prm6[3][n]));
        sincosf(dt * bf_lo(p.prm6[1][n]) * lf, &sn, &cs);
        k += expf(dt * bf_lo(p.prm6[0][n]) * lf) * (wr * cs - wi * sn);
    }
    f_k[l * D_ + d] = k;
}
__global__ void fb_conv(Params p) {
    const int t = blockIdx.x, d = threadIdx.x;
    float y = 0.f;
    for (int l = 0; l <= t; l++) y += f_k[l * D_ + d] * b2f(f_n[(t - l) * D_ + d]);
    f_h[t * D_ + d] = __float2bfloat16(bf_lo(p.x[t * D_ + d]) + bfr(bfr(y) + bfr(b2f(f_n[t * D_ + d]) * bf_lo(p.dskip[d]))));
}
__global__ void fb_top() {
    const int t = blockIdx.x * 256 + threadIdx.x;
    int rank = 0;
    for (int j = 0; j < L_; j++) rank += f_r[j] > f_r[t] || (f_r[j] == f_r[t] && j < t);
    if (rank < 8) f_idx[rank] = t;
}
__global__ void fb_ffn1(const bf16* wg, const bf16* wu) {
    const int f = blockIdx.x * 256 + threadIdx.x, j = blockIdx.y;
    float g = 0.f, u = 0.f;
    for (int i = 0; i < D_; i++) { const float v = b2f(f_n[f_idx[j] * D_ + i]); g += v * b2f(wg[i * F_ + f]); u += v * b2f(wu[i * F_ + f]); }
    g = bfr(g);
    f_gu[j * F_ + f] = bfr(bfr(g / (1.f + expf(-g))) * bfr(u));
}
__global__ void fb_ffn2(const bf16* wd, bf16* out) {
    const int d = threadIdx.x, j = blockIdx.x, t = f_idx[j];
    float y = 0.f;
    for (int f = 0; f < F_; f++) y += f_gu[j * F_ + f] * b2f(wd[f * D_ + d]);
    out[t * D_ + d] = __float2bfloat16(b2f(f_h[t * D_ + d]) + bfr(b2f(f_n[t * D_ + d]) + bfr(bfr(y) * bfr(1.f / (1.f + expf(-f_r[t]))))));
}

typedef CUresult (*EncodeFn)(CUtensorMap*, CUtensorMapDataType, cuuint32_t, void*, const cuuint64_t*, const cuuint64_t*,
                             const cuuint32_t*, const cuuint32_t*, CUtensorMapInterleave, CUtensorMapSwizzle,
                             CUtensorMapL2promotion, CUtensorMapFloatOOBfill);

void make_map(EncodeFn fn, CUtensorMap* tm, const void* p, int cols, int rows, int bc, int br) {
    cuuint64_t dims[2] = {(cuuint64_t)cols, (cuuint64_t)rows};
    cuuint64_t strides[1] = {(cuuint64_t)cols * 2};
    cuuint32_t box[2] = {(cuuint32_t)bc, (cuuint32_t)br};
    cuuint32_t es[2] = {1, 1};
    fn(tm, CU_TENSOR_MAP_DATA_TYPE_BFLOAT16, 2, const_cast<void*>(p), dims, strides, box, es, CU_TENSOR_MAP_INTERLEAVE_NONE,
       CU_TENSOR_MAP_SWIZZLE_NONE, CU_TENSOR_MAP_L2_PROMOTION_L2_128B, CU_TENSOR_MAP_FLOAT_OOB_FILL_NONE);
}

void make_map3(EncodeFn fn, CUtensorMap* tm, const void* p) {
    cuuint64_t dims[5] = {(cuuint64_t)D_, 64, 2, 4, 4};
    cuuint64_t strides[4] = {(cuuint64_t)D_ * 2, (cuuint64_t)D_ * 128, (cuuint64_t)D_ * 1024, (cuuint64_t)D_ * 256};
    cuuint32_t box[5] = {XW, 9, 2, 4, 4};
    cuuint32_t es[5] = {1, 1, 1, 1, 1};
    fn(tm, CU_TENSOR_MAP_DATA_TYPE_BFLOAT16, 5, const_cast<void*>(p), dims, strides, box, es, CU_TENSOR_MAP_INTERLEAVE_NONE,
       CU_TENSOR_MAP_SWIZZLE_NONE, CU_TENSOR_MAP_L2_PROMOTION_NONE, CU_TENSOR_MAP_FLOAT_OOB_FILL_NONE);
}

void make_map5(EncodeFn fn, CUtensorMap* tm, const void* p, int bc) {
    cuuint64_t dims[5] = {(cuuint64_t)D_, 2, 4, 4, 64};
    cuuint64_t strides[4] = {(cuuint64_t)D_ * 128, (cuuint64_t)D_ * 1024, (cuuint64_t)D_ * 256, (cuuint64_t)D_ * 2};
    cuuint32_t box[5] = {(cuuint32_t)bc, 2, 4, 4, 8};
    cuuint32_t es[5] = {1, 1, 1, 1, 1};
    fn(tm, CU_TENSOR_MAP_DATA_TYPE_BFLOAT16, 5, const_cast<void*>(p), dims, strides, box, es, CU_TENSOR_MAP_INTERLEAVE_NONE,
       CU_TENSOR_MAP_SWIZZLE_NONE, CU_TENSOR_MAP_L2_PROMOTION_NONE, CU_TENSOR_MAP_FLOAT_OOB_FILL_NONE);
}

}

extern "C" void kernel_launch(void* const* d_in, const int* in_sizes, int n_in, void* d_out, int out_size) {
    (void)in_sizes; (void)n_in; (void)out_size;
    void* fp = nullptr;
    cudaDriverEntryPointQueryResult qr;
    cudaGetDriverEntryPoint("cuTensorMapEncodeTiled", &fp, cudaEnableDefault, &qr);
    EncodeFn fn = (EncodeFn)fp;
    CUtensorMap tmG, tmU, tmD, tmO, tmX, tmH;
    make_map3(fn, &tmX, d_in[0]);
    make_map(fn, &tmG, d_in[11], F_, D_, 40, 48);
    make_map(fn, &tmU, d_in[12], F_, D_, 40, 48);
    make_map(fn, &tmD, d_in[13], D_, F_, 72, 64);
    make_map5(fn, &tmO, d_out, 32);
    make_map5(fn, &tmH, d_out, 8);
    Params p;
    p.x = (const unsigned short*)d_in[0];
    for (int i = 0; i < 6; i++) p.prm6[i] = (const unsigned short*)d_in[1 + i];
    p.logdt = (const unsigned short*)d_in[7]; p.dskip = (const unsigned short*)d_in[8];
    p.wr = (const unsigned short*)d_in[10];
    p.out = (__nv_bfloat16*)d_out;
    p.zero = 0;
    cudaGetSymbolAddress((void**)&p.gs, g_s);
    cudaFuncSetAttribute(fused_kernel, cudaFuncAttributeMaxDynamicSharedMemorySize, SM_TOTAL);
    static int nclusters = -1;
    if (nclusters < 0) {
        cudaLaunchConfig_t cfg = {};
        cudaLaunchAttribute at;
        at.id = cudaLaunchAttributeClusterDimension; at.val.clusterDim.x = CS; at.val.clusterDim.y = 1; at.val.clusterDim.z = 1;
        cfg.gridDim = dim3(NCTA); cfg.blockDim = dim3(NTHR); cfg.dynamicSmemBytes = SM_TOTAL; cfg.attrs = &at; cfg.numAttrs = 1;
        if (cudaOccupancyMaxActiveClusters(&nclusters, fused_kernel, &cfg) != cudaSuccess) { (void)cudaGetLastError(); nclusters = NCL; }
    }
    if (nclusters >= NCL && !FORCE_FALLBACK) {
        fused_kernel<<<NCTA, NTHR, SM_TOTAL>>>(p, tmG, tmU, tmD, tmO, tmX, tmH);
        return;
    }
    fb_ln<<<L_ / 8, 256>>>((const bf16*)d_in[0], nullptr, nullptr);
    fb_taps<<<D_ * 8, 256>>>(p);
    fb_conv<<<L_, D_>>>(p);
    fb_ln<<<L_ / 8, 256>>>(nullptr, (const bf16*)d_in[10], p.out);
    fb_top<<<L_ / 256, 256>>>();
    fb_ffn1<<<dim3(F_ / 256, 8), 256>>>((const bf16*)d_in[11], (const bf16*)d_in[12]);
    fb_ffn2<<<8, D_>>>((const bf16*)d_in[13], p.out);
}
```

```cpp
#include <cuda_runtime.h>
#include <cuda_bf16.h>
#include <cuda_fp16.h>
#include <cuda.h>
#include <stdint.h>

namespace {

constexpr int L_ = 2048, D_ = 576, F_ = 4608;
constexpr int NCL = 15, CS = 8, NCTA = NCL * CS, NTHR = 768;
#define FORCE_FALLBACK 0
constexpr int XW = 48, NRED = 2;
constexpr int SPIN_LIMIT = 1 << 22;

constexpr int SM_WG   = 0;
constexpr int SM_WU   = 46080;
constexpr int YP = 3392, YS = 656;
constexpr int UP = 3280, US = 656;
constexpr int SM_XT   = 92160;
constexpr int SM_U    = SM_XT + 8 * YP;
constexpr int SM_FAR  = SM_U + 8 * UP;
constexpr int FAR_SZ  = 12416;
constexpr int F_E5 = 0, F_O5 = 1536, F_E3 = 3088, F_O3 = 4624, F_E7 = 6176, F_E2 = F_E7 + 1024, F_E9 = F_E7 + 2048,
              F_H = 3088, F_O7 = F_E7 + F_H, F_O2 = F_E2 + F_H, F_O9 = F_E9 + F_H;
constexpr int SM_P    = SM_FAR + 5 * FAR_SZ;
constexpr int PN_SZ = 584 * 4, SM_PN = SM_P + 65 * 4;
constexpr int P_GS = 50 * 4, P_H7 = 200 * 4, P_HS = 74 * 4;
constexpr int PF_SZ = (200 + 222) * 4, SM_PF = SM_PN + 5 * PN_SZ + 36;
constexpr int SM_MISC = SM_PF + 5 * PF_SZ;
constexpr int SM_ST   = SM_MISC;
constexpr int SM_RK   = SM_ST + 2048;
constexpr int SM_SEL  = SM_RK + 256;
constexpr int SM_KG   = SM_SEL + 64;
constexpr int SM_SC   = SM_KG + 160;
constexpr int SM_DW   = SM_SC + 32;
constexpr int SM_MB   = SM_DW + 160;
constexpr int SM_TOTAL = SM_MB + 128;
constexpr int SM_ROW  = SM_XT - 20736;
constexpr int SM_XTL  = SM_ROW - 576 * XW;
constexpr int SM_RED2 = SM_WG;
constexpr int SM_HT   = SM_P - 512;
constexpr int SM_KEY  = SM_FAR + 10240 + 128;
constexpr int SM_CAND = SM_KEY + 1024;
constexpr int SM_XS   = SM_U;
constexpr int SM_GU   = SM_XS + 9344;
constexpr int SM_RED  = SM_GU + 5632;
static_assert(F_O9 + 1024 <= FAR_SZ && FAR_SZ % 128 == 0, "far overflow");
static_assert(SM_RED + 10240 <= SM_FAR && SM_HT + 20496 <= SM_MISC, "alias overflow");
static_assert(SM_TOTAL <= 232448, "smem overflow");
static_assert(SM_FAR % 128 == 0 && SM_XT % 128 == 0 && SM_XTL % 128 == 0 && SM_P % 16 == 0 && SM_MISC % 16 == 0 && SM_MB % 8 == 0, "align");

enum { MB_X = 0, MB_W1 = 5, MB_W2 = 6, MB_KEY = 7, MB_GU = 8, MB_Y = 9, MB_OUT = 10, MB_T = 11, MB_R = 12 };

struct __align__(128) Scratch {
    unsigned epoch, zcnt, pad[30];
    uint4  st1[L_ * 2];
    float4 acc[L_];
    uint4  cand[64 * NCL * 6];
    float4 fin[8 * 192 + 24];
};
__device__ Scratch g_s;
#define STAMP(i)

__device__ __forceinline__ uint32_t mapa(uint32_t a, uint32_t r) { uint32_t d; asm("mapa.shared::cluster.u32 %0, %1, %2;" : "=r"(d) : "r"(a), "r"(r)); return d; }
__device__ __forceinline__ void mbar_wait(uint32_t mb) {
    asm volatile("{ .reg .pred p, q; .reg .u32 n; mov.u32 n, 0;\n"
                 "W_%=: mbarrier.try_wait.parity.shared::cta.b64 p, [%0], 0; add.u32 n, n, 1; setp.lt.and.u32 q, n, 65536, !p; @q bra W_%=; }" :: "r"(mb) : "memory");
}
__device__ __forceinline__ void arm(uint32_t mb, uint32_t bytes) { asm volatile("mbarrier.arrive.expect_tx.shared::cta.b64 _, [%0], %1;" :: "r"(mb), "r"(bytes) : "memory"); }
__device__ __forceinline__ void bar_sync(int id, int n) { asm volatile("bar.sync %0, %1;" :: "r"(id), "r"(n) : "memory"); }
__device__ __forceinline__ void bar_arrive(int id, int n) { asm volatile("bar.arrive %0, %1;" :: "r"(id), "r"(n) : "memory"); }
__device__ __forceinline__ uint32_t lds16(uint32_t a) { unsigned short v; asm volatile("ld.shared.u16 %0, [%1];" : "=h"(v) : "r"(a) : "memory"); return v; }
__device__ __forceinline__ uint32_t lds32(uint32_t a) { uint32_t v; asm volatile("ld.shared.u32 %0, [%1];" : "=r"(v) : "r"(a) : "memory"); return v; }
__device__ __forceinline__ uint2 lds64(uint32_t a) { uint2 v; asm volatile("ld.shared.v2.u32 {%0,%1}, [%2];" : "=r"(v.x), "=r"(v.y) : "r"(a) : "memory"); return v; }
__device__ __forceinline__ float ldsf(uint32_t a) { float v; asm volatile("ld.shared.f32 %0, [%1];" : "=f"(v) : "r"(a) : "memory"); return v; }
__device__ __forceinline__ uint4 lds128(uint32_t a) { uint4 v; asm volatile("ld.shared.v4.u32 {%0,%1,%2,%3}, [%4];" : "=r"(v.x), "=r"(v.y), "=r"(v.z), "=r"(v.w) : "r"(a) : "memory"); return v; }
__device__ __forceinline__ float4 lds128f(uint32_t a) { float4 v; asm volatile("ld.shared.v4.f32 {%0,%1,%2,%3}, [%4];" : "=f"(v.x), "=f"(v.y), "=f"(v.z), "=f"(v.w) : "r"(a) : "memory"); return v; }
__device__ __forceinline__ void sts16(uint32_t a, uint32_t v) { asm volatile("{ .reg .b16 l, h; mov.b32 {l, h}, %1; st.shared.b16 [%0], l; }" :: "r"(a), "r"(v) : "memory"); }
__device__ __forceinline__ void sts32(uint32_t a, uint32_t v) { asm volatile("st.shared.u32 [%0], %1;" :: "r"(a), "r"(v) : "memory"); }
__device__ __forceinline__ void sts64(uint32_t a, uint32_t x, uint32_t y) { asm volatile("st.shared.v2.u32 [%0], {%1,%2};" :: "r"(a), "r"(x), "r"(y) : "memory"); }
__device__ __forceinline__ void stsf(uint32_t a, float v) { asm volatile("st.shared.f32 [%0], %1;" :: "r"(a), "f"(v) : "memory"); }
__device__ __forceinline__ void sts128(uint32_t a, uint32_t x, uint32_t y, uint32_t z, uint32_t w) { asm volatile("st.shared.v4.u32 [%0], {%1,%2,%3,%4};" :: "r"(a), "r"(x), "r"(y), "r"(z), "r"(w) : "memory"); }
__device__ __forceinline__ void sts128f(uint32_t a, float x, float y, float z, float w) { asm volatile("st.shared.v4.f32 [%0], {%1,%2,%3,%4};" :: "r"(a), "f"(x), "f"(y), "f"(z), "f"(w) : "memory"); }
__device__ __forceinline__ void ldsm4(uint32_t (&r)[4], uint32_t a) { asm volatile("ldmatrix.sync.aligned.m8n8.x4.shared.b16 {%0,%1,%2,%3}, [%4];" : "=r"(r[0]), "=r"(r[1]), "=r"(r[2]), "=r"(r[3]) : "r"(a) : "memory"); }
__device__ __forceinline__ void ldsm4t(uint32_t (&r)[4], uint32_t a) { asm volatile("ldmatrix.sync.aligned.m8n8.x4.trans.shared.b16 {%0,%1,%2,%3}, [%4];" : "=r"(r[0]), "=r"(r[1]), "=r"(r[2]), "=r"(r[3]) : "r"(a) : "memory"); }
__device__ __forceinline__ void ldsm2t(uint32_t& r0, uint32_t& r1, uint32_t a) { asm volatile("ldmatrix.sync.aligned.m8n8.x2.trans.shared.b16 {%0,%1}, [%2];" : "=r"(r0), "=r"(r1) : "r"(a) : "memory"); }
__device__ __forceinline__ void stsm4t(uint32_t a, uint32_t r0, uint32_t r1, uint32_t r2, uint32_t r3) { asm volatile("stmatrix.sync.aligned.m8n8.x4.trans.shared.b16 [%0], {%1,%2,%3,%4};" :: "r"(a), "r"(r0), "r"(r1), "r"(r2), "r"(r3) : "memory"); }
__device__ __forceinline__ void stsm4(uint32_t a, uint32_t r0, uint32_t r1, uint32_t r2, uint32_t r3) { asm volatile("stmatrix.sync.aligned.m8n8.x4.shared.b16 [%0], {%1,%2,%3,%4};" :: "r"(a), "r"(r0), "r"(r1), "r"(r2), "r"(r3) : "memory"); }
__device__ __forceinline__ void stsm2(uint32_t a, uint32_t r0, uint32_t r1) { asm volatile("stmatrix.sync.aligned.m8n8.x2.shared.b16 [%0], {%1,%2};" :: "r"(a), "r"(r0), "r"(r1) : "memory"); }
__device__ __forceinline__ void stsm2t(uint32_t a, uint32_t r0, uint32_t r1) { asm volatile("stmatrix.sync.aligned.m8n8.x2.trans.shared.b16 [%0], {%1,%2};" :: "r"(a), "r"(r0), "r"(r1) : "memory"); }
__device__ __forceinline__ uint4 ldg128(const void* p) { uint4 v; asm volatile("ld.global.nc.v4.u32 {%0,%1,%2,%3}, [%4];" : "=r"(v.x), "=r"(v.y), "=r"(v.z), "=r"(v.w) : "l"(p)); return v; }
__device__ __forceinline__ uint32_t ldg16(const void* p) { unsigned short v; asm volatile("ld.global.nc.u16 %0, [%1];" : "=h"(v) : "l"(p)); return v; }
__device__ __forceinline__ uint32_t opaque(uint32_t v) { uint32_t r; asm volatile("mov.b32 %0, %1;" : "=r"(r) : "r"(v)); return r; }
__device__ __forceinline__ void mma_f16(float (&d)[4], const uint32_t (&a)[4], uint32_t b0, uint32_t b1) {
    asm volatile("mma.sync.aligned.m16n8k16.row.col.f32.f16.f16.f32 {%0,%1,%2,%3}, {%4,%5,%6,%7}, {%8,%9}, {%0,%1,%2,%3};"
        : "+f"(d[0]), "+f"(d[1]), "+f"(d[2]), "+f"(d[3]) : "r"(a[0]), "r"(a[1]), "r"(a[2]), "r"(a[3]), "r"(b0), "r"(b1));
}
__device__ __forceinline__ void mma_f16_z(float (&d)[4], const uint32_t (&a)[4], uint32_t b0, uint32_t b1) {
    asm volatile("mma.sync.aligned.m16n8k16.row.col.f32.f16.f16.f32 {%0,%1,%2,%3}, {%4,%5,%6,%7}, {%8,%9}, {%10,%10,%10,%10};"
        : "=f"(d[0]), "=f"(d[1]), "=f"(d[2]), "=f"(d[3]) : "r"(a[0]), "r"(a[1]), "r"(a[2]), "r"(a[3]), "r"(b0), "r"(b1), "f"(0.f));
}
__device__ __forceinline__ void mma_bf16(float (&d)[4], uint32_t a0, uint32_t a1, uint32_t a2, uint32_t a3, uint32_t b0, uint32_t b1) {
    asm volatile("mma.sync.aligned.m16n8k16.row.col.f32.bf16.bf16.f32 {%0,%1,%2,%3}, {%4,%5,%6,%7}, {%8,%9}, {%0,%1,%2,%3};"
        : "+f"(d[0]), "+f"(d[1]), "+f"(d[2]), "+f"(d[3]) : "r"(a0), "r"(a1), "r"(a2), "r"(a3), "r"(b0), "r"(b1));
}
__device__ __forceinline__ void mma_bf16_k8(float (&d)[4], uint32_t a0, uint32_t a1, uint32_t b0) {
    asm volatile("mma.sync.aligned.m16n8k8.row.col.f32.bf16.bf16.f32 {%0,%1,%2,%3}, {%4,%5}, {%6}, {%0,%1,%2,%3};"
        : "+f"(d[0]), "+f"(d[1]), "+f"(d[2]), "+f"(d[3]) : "r"(a0), "r"(a1), "r"(b0));
}
__device__ __forceinline__ uint32_t pack_f16(float lo, float hi) { uint32_t r; asm("cvt.rn.f16x2.f32 %0, %1, %2;" : "=r"(r) : "f"(hi), "f"(lo)); return r; }
__device__ __forceinline__ uint32_t pack_bf16(float lo, float hi) { uint32_t r; asm("cvt.rn.bf16x2.f32 %0, %1, %2;" : "=r"(r) : "f"(hi), "f"(lo)); return r; }
__device__ __forceinline__ float bf_lo(uint32_t v) { return __uint_as_float(v << 16); }
__device__ __forceinline__ float bf_hi(uint32_t v) { return __uint_as_float(v & 0xFFFF0000u); }
__device__ __forceinline__ float bfr(float x) { return __uint_as_float(pack_bf16(0.f, x)); }
__device__ __forceinline__ uint32_t badd2(uint32_t a, uint32_t b) { uint32_t r; asm("add.rn.bf16x2 %0, %1, %2;" : "=r"(r) : "r"(a), "r"(b)); return r; }
__device__ __forceinline__ uint32_t bmul2(uint32_t a, uint32_t b) { uint32_t r; asm("mul.rn.bf16x2 %0, %1, %2;" : "=r"(r) : "r"(a), "r"(b)); return r; }
__device__ __forceinline__ uint32_t hadd2(uint32_t a, uint32_t b) { uint32_t r; asm("add.rn.f16x2 %0, %1, %2;" : "=r"(r) : "r"(a), "r"(b)); return r; }
__device__ __forceinline__ uint32_t hmul2(uint32_t a, uint32_t b) { uint32_t r; asm("mul.rn.f16x2 %0, %1, %2;" : "=r"(r) : "r"(a), "r"(b)); return r; }
__device__ __forceinline__ uint32_t hfma2(uint32_t a, uint32_t b, uint32_t c) { uint32_t r; asm("fma.rn.f16x2 %0, %1, %2, %3;" : "=r"(r) : "r"(a), "r"(b), "r"(c)); return r; }
__device__ __forceinline__ uint32_t hneg2(uint32_t a) { uint32_t r; asm("neg.f16x2 %0, %1;" : "=r"(r) : "r"(a)); return r; }
__device__ __forceinline__ float rcpf(float x) { float r; asm("rcp.approx.ftz.f32 %0, %1;" : "=f"(r) : "f"(x)); return r; }
__device__ __forceinline__ float sqrta(float x) { float r; asm("sqrt.approx.ftz.f32 %0, %1;" : "=f"(r) : "f"(x)); return r; }
__device__ __forceinline__ float ex2f(float x) { float r; asm("ex2.approx.ftz.f32 %0, %1;" : "=f"(r) : "f"(x)); return r; }
__device__ __forceinline__ void st_async4(uint32_t a, uint32_t x, uint32_t y, uint32_t z, uint32_t w, uint32_t mb) {
    asm volatile("st.async.shared::cluster.mbarrier::complete_tx::bytes.v4.u32 [%0], {%1,%2,%3,%4}, [%5];" :: "r"(a), "r"(x), "r"(y), "r"(z), "r"(w), "r"(mb) : "memory"); }
__device__ __forceinline__ void st_async1(uint32_t a, uint32_t x, uint32_t mb) {
    asm volatile("st.async.shared::cluster.mbarrier::complete_tx::bytes.u32 [%0], %1, [%2];" :: "r"(a), "r"(x), "r"(mb) : "memory"); }
__device__ __forceinline__ unsigned ld_rlx(const void* p) { unsigned v; asm volatile("ld.relaxed.gpu.global.u32 %0, [%1];" : "=r"(v) : "l"(p) : "memory"); return v; }
__device__ __forceinline__ unsigned ld_acq(const void* p) { unsigned v; asm volatile("ld.acquire.gpu.global.u32 %0, [%1];" : "=r"(v) : "l"(p) : "memory"); return v; }
__device__ __forceinline__ uint2 ld_rlx64(const void* p) { unsigned long long v; asm volatile("ld.relaxed.gpu.global.u64 %0, [%1];" : "=l"(v) : "l"(p) : "memory"); return make_uint2((unsigned)v, (unsigned)(v >> 32)); }
__device__ __forceinline__ void st_rlx128(void* p, uint32_t x, uint32_t y, uint32_t z, uint32_t w) {
    asm volatile("st.relaxed.gpu.global.v2.u64 [%0], {%1,%2};" :: "l"(p), "l"((unsigned long long)x | ((unsigned long long)y << 32)), "l"((unsigned long long)z | ((unsigned long long)w << 32)) : "memory"); }
__device__ __forceinline__ uint4 ld_rlx128(const void* p) { unsigned long long a, b; asm volatile("ld.relaxed.gpu.global.v2.u64 {%0,%1}, [%2];" : "=l"(a), "=l"(b) : "l"(p) : "memory"); return make_uint4((unsigned)a, (unsigned)(a >> 32), (unsigned)b, (unsigned)(b >> 32)); }
__device__ __forceinline__ void tma2d(uint32_t dst, const CUtensorMap* tm, int x, int y, uint32_t mb) {
    asm volatile("cp.async.bulk.tensor.2d.shared::cluster.global.mbarrier::complete_tx::bytes [%0], [%1, {%3, %4}], [%2];"
                 :: "r"(dst), "l"(tm), "r"(mb), "r"(x), "r"(y) : "memory");
}
__device__ __forceinline__ void cmul(float& xr, float& xi, float ar, float ai, float br, float bi) {
    const float r = fmaf(ar, br, -ai * bi), i = fmaf(ar, bi, ai * br); xr = r; xi = i;
}
__device__ __forceinline__ void csq(float& xr, float& xi, float ar, float ai) {
    const float r = fmaf(ar, ar, -ai * ai), i = (ar + ar) * ai; xr = r; xi = i;
}
__device__ __forceinline__ void cexp_s(float& zr, float& zi, float e2, float turns) {
    const float mag = ex2f(e2), r = (turns - rintf(turns)) * 6.283185307179586f;
    zr = mag * __cosf(r); zi = mag * __sinf(r);
}
__device__ __forceinline__ uint32_t ln_stats(float s1, float s2) {
    const float m = s1 * (1.f / D_);
    const float var = fmaxf(fmaf(s2, 1.f / D_, -m * m), 0.f);
    return pack_bf16(m, sqrta(bfr(bfr(var) + 1e-5f)));
}
__device__ __forceinline__ uint32_t rsplit(float rs) { const float h = bfr(rs); return pack_bf16(h, rs - h); }
__device__ __forceinline__ uint32_t norm2(uint32_t v, uint32_t mx, uint32_t hl) {
    uint32_t r;
    asm("{ .reg .b16 m, h, l, x; .reg .b32 m2, h2, l2, d, t; mov.b32 {m, x}, %2; mov.b32 {h, l}, %3; mov.b32 m2, {m, m}; mov.b32 h2, {h, h}; mov.b32 l2, {l, l};\n"
        "sub.rn.bf16x2 d, %1, m2; mul.rn.bf16x2 t, d, l2; fma.rn.bf16x2 %0, d, h2, t; }" : "=r"(r) : "r"(v), "r"(mx), "r"(hl));
    return r;
}
template <int N, int S>
__device__ __forceinline__ uint32_t rank4(uint32_t a, uint32_t key) {
    uint32_t r0 = 0, r1 = 0, r2 = 0, r3 = 0;
#pragma unroll
    for (int i = 0; i < N; i++) {
        const uint4 o = lds128(a + i * S);
        r0 += (key - o.x) >> 31; r1 += (key - o.y) >> 31; r2 += (key - o.z) >> 31; r3 += (key - o.w) >> 31;
    }
    return (r0 + r1) + (r2 + r3);
}
typedef uint32_t H2C;
__device__ __forceinline__ H2C splat(float r, float i) { return pack_f16(r, i); }
__device__ __forceinline__ void hcmul(uint32_t& xr, uint32_t& xi, uint32_t R, uint32_t I, H2C m) {
    asm("{ .reg .b16 a, b; .reg .b32 a2, b2, t; mov.b32 {a, b}, %4; mov.b32 a2, {a, a}; mov.b32 b2, {b, b};\n"
        "mul.rn.f16x2 t, %3, b2; neg.f16x2 t, t; fma.rn.f16x2 %0, %2, a2, t; mul.rn.f16x2 t, %3, a2; fma.rn.f16x2 %1, %2, b2, t; }"
        : "=&r"(xr), "=r"(xi) : "r"(R), "r"(I), "r"(m));
}
__device__ __forceinline__ void expand4(uint32_t are, uint32_t aim, uint32_t R0, uint32_t R1, uint32_t I0, uint32_t I1, H2C m4) {
    uint32_t R2, I2, R3, I3;
    hcmul(R2, I2, R0, I0, m4); hcmul(R3, I3, R1, I1, m4);
    sts128(are, R0, R1, R2, R3);
    sts128(aim, I0, I1, I2, I3);
}
__device__ __forceinline__ void expand8(uint32_t are, uint32_t aim, float sr, float si, float m1r, float m1i, float m2r, float m2i, H2C m4) {
    float r1, i1, r2, i2, r3, i3;
    cmul(r1, i1, sr, si, m1r, m1i); cmul(r2, i2, sr, si, m2r, m2i); cmul(r3, i3, r1, i1, m2r, m2i);
    expand4(are, aim, pack_f16(sr, r1), pack_f16(r2, r3), pack_f16(si, i1), pack_f16(i2, i3), m4);
}
__device__ __forceinline__ void put16(uint32_t a, uint32_t v) { sts16(a, v); sts16(a + 6, v); }

struct Params {
    const unsigned short *logdt, *dskip, *prm6[6], *x, *wr;
    __nv_bfloat16* out;
    Scratch* gs;
    unsigned zero;
};
__device__ __forceinline__ uint32_t tslot(uint32_t t) { return (t & 7) * 32 + ((t >> 4) & 24) + ((t >> 8) & 6) + ((t >> 6) & 1); }
#define CP(x) ((x) | zero)
#define PIN(x) asm volatile("or.b32 %0, %0, %1;" : "+r"(x) : "r"(zero))
__device__ __forceinline__ void wgmma32(float (&d)[4][4], const uint32_t (&a)[4], uint32_t dlo) {
    asm volatile("{ .reg .b64 ds; mov.b64 ds, {%20, %21};\n"
                 "wgmma.mma_async.sync.aligned.m64n32k16.f32.f16.f16 {%0,%1,%2,%3,%4,%5,%6,%7,%8,%9,%10,%11,%12,%13,%14,%15}, {%16,%17,%18,%19}, ds, 1, 1, 1, 0; }"
        : "+f"(d[0][0]), "+f"(d[0][1]), "+f"(d[0][2]), "+f"(d[0][3]), "+f"(d[1][0]), "+f"(d[1][1]), "+f"(d[1][2]), "+f"(d[1][3]),
          "+f"(d[2][0]), "+f"(d[2][1]), "+f"(d[2][2]), "+f"(d[2][3]), "+f"(d[3][0]), "+f"(d[3][1]), "+f"(d[3][2]), "+f"(d[3][3])
        : "r"(a[0]), "r"(a[1]), "r"(a[2]), "r"(a[3]), "r"(dlo), "n"(128 >> 4));
}

__device__ __forceinline__ void finish(const Params& prm, uint32_t fo, uint32_t oo, const float (&v)[3], float cnt) {
    float x, y, z, w;
    asm volatile("atom.relaxed.gpu.global.add.v4.f32 {%0,%1,%2,%3}, [%4], {%5,%6,%7,%8};" : "=f"(x), "=f"(y), "=f"(z), "=f"(w)
                 : "l"((char*)prm.gs->fin + fo), "f"(v[0]), "f"(v[1]), "f"(v[2]), "f"(cnt) : "memory");
    if (w + cnt == 3.f * (NCL + 1)) {
        __nv_bfloat16* op = (__nv_bfloat16*)((char*)prm.out + oo);
        op[0] = __float2bfloat16(x + v[0]); op[1] = __float2bfloat16(y + v[1]); op[2] = __float2bfloat16(z + v[2]);
    }
}

__global__ void __cluster_dims__(CS, 1, 1) __launch_bounds__(NTHR, 1)
fused_kernel(const __grid_constant__ Params prm, const __grid_constant__ CUtensorMap tmG, const __grid_constant__ CUtensorMap tmU,
             const __grid_constant__ CUtensorMap tmD, const __grid_constant__ CUtensorMap tmO, const __grid_constant__ CUtensorMap tmX, const __grid_constant__ CUtensorMap tmH)
{
    extern __shared__ __align__(1024) unsigned char smem[];
    const int tid = threadIdx.x, lane = tid & 31, warp = __shfl_sync(~0u, tid >> 5, 0);
    const int c = blockIdx.x >> 3, q = blockIdx.x & 7;
    const int nslot = (c < NCL - 1) ? 5 : 2;
    const int d0 = 40 * c;
    const uint32_t sb = opaque((uint32_t)__cvta_generic_to_shared(smem));
    const uint32_t mb = sb + SM_MB;
    Scratch& g_s = *prm.gs;
    const unsigned& zero = prm.zero;
    STAMP(0);

    if (warp >= 20) {
        unsigned epoch = 0;
        if (warp == 20) {
            if (lane == 0) {
#pragma unroll
                for (int i = 0; i < 13; i++)
                    asm volatile("mbarrier.init.shared::cta.b64 [%0], %1;" :: "r"(mb + i * 8), "r"((i == MB_R || i < 5) ? 2 : i == MB_Y ? 1 + 4 * nslot : 1) : "memory");
                asm volatile("fence.mbarrier_init.release.cluster;" ::: "memory");
                arm(mb + MB_W1 * 8, 92160); arm(mb + MB_W2 * 8, nslot * 9216); arm(mb + MB_KEY * 8, 256); arm(mb + MB_GU * 8, nslot * 1024); arm(mb + MB_T * 8, 576 * XW);
                const int bytes = max(min(18, L_ - 18 * (int)blockIdx.x), 1) * (D_ * 2);
                arm(mb + MB_R * 8, bytes);
            }
            __syncwarp();
        } else if (warp == 22) {
            epoch = ld_rlx(&g_s.epoch);
            if (lane < 18 ? 18 * c + lane < 256 : lane < 31) (lane < 18 ? &g_s.acc[256 * q + 18 * c] : &g_s.fin[13 * (int)blockIdx.x - 18])[lane] = make_float4(0.f, 0.f, 0.f, 0.f);
        } else if (warp == 23 && lane == 0) asm volatile("prefetch.tensormap [%0];" :: "l"(&tmX) : "memory");
        asm volatile("barrier.cluster.arrive.relaxed.aligned;" ::: "memory");
        bar_sync(12, NTHR);
        uint4 wv = make_uint4(0, 0, 0, 0), wv2, wv3;
        if (warp == 22) {
            if (lane == 0) { sts32(sb + SM_SC + 28, epoch); asm volatile("mbarrier.arrive.shared::cta.b64 _, [%0];" :: "r"(mb + MB_R * 8) : "memory"); }
            epoch++;
            asm volatile("fence.acq_rel.gpu;" ::: "memory");
            __syncwarp();
            if (lane == 0) asm volatile("red.relaxed.gpu.global.add.u32 [%0], 1;" :: "l"(&g_s.zcnt) : "memory");
            STAMP(1);
            wv2 = ldg128((const uint4*)prm.wr + lane); wv3 = ldg128((const uint4*)prm.wr + 32 + lane);
            if (lane < 8) wv = ldg128((const uint4*)prm.wr + 64 + lane);
            if (lane < 5) {
                uint4 v = make_uint4(0, 0, 0, 0);
                if (lane < nslot) v = ldg128((const uint4*)(prm.wr + d0) + lane);
                sts128(sb + SM_DW + lane * 16, v.x, v.y, v.z, v.w);
            }
            __syncwarp();
            if (lane < 5) asm volatile("mbarrier.arrive.shared::cta.b64 _, [%0];" :: "r"(mb + (MB_X + lane) * 8) : "memory");
        }
        if (warp == 21) {
            if (lane == 0) { asm volatile("prefetch.tensormap [%0];" :: "l"(&tmG) : "memory"); asm volatile("prefetch.tensormap [%0];" :: "l"(&tmU) : "memory"); asm volatile("prefetch.tensormap [%0];" :: "l"(&tmD) : "memory"); }
            __syncwarp();
            bar_sync(15, 672);
            asm volatile("fence.proxy.async.shared::cta;" ::: "memory");
#pragma unroll 1
            for (int i = 0; i < 24; i++) {
                if (lane == 0) tma2d(sb + SM_WG + i * 3840, i < 12 ? &tmG : &tmU, 320 * c + 8 * nslot * q, 48 * (i < 12 ? i : i - 12), mb + MB_W1 * 8);
            }
            STAMP(1);
        } else {
        if (warp == 20) {
            if (lane == 0) {
                asm volatile("cp.async.bulk.shared::cluster.global.mbarrier::complete_tx::bytes [%0], [%1], %2, [%3];"
                             :: "r"(sb + SM_ROW), "l"(prm.x + min(18 * (int)blockIdx.x, L_ - 1) * D_), "r"(max(min(18, L_ - 18 * (int)blockIdx.x), 1) * (D_ * 2)), "r"(mb + MB_R * 8) : "memory");
            }
            __syncwarp();
            mbar_wait(mb + MB_R * 8);
            if (lane == 0) {
                asm volatile("cp.async.bulk.tensor.5d.shared::cluster.global.mbarrier::complete_tx::bytes [%0], [%1, {%3, %4, %5, %5, %5}], [%2];"
                             :: "r"(sb + SM_XTL), "l"(&tmX), "r"(mb + MB_T * 8), "r"(d0 & ~15), "r"(8 * q), "r"(0) : "memory");
            }
            STAMP(6);
        }
        asm volatile("barrier.cluster.wait.aligned;" ::: "memory");
        bar_sync(13, 608);
        asm volatile("fence.proxy.async.shared::cta;" ::: "memory");
        {
            const int idx = lane * 3 + max(warp - 21, 0), sl = nslot - 1 - (idx >> 3), pe = (idx + q + 1) & 7;
            if (sl >= 0) {
                if (pe == q) arm(mb + (MB_X + sl) * 8, 7 * 512);
                else {
                    const uint32_t rb_ = mapa(sb, pe);
                    asm volatile("cp.async.bulk.shared::cluster.shared::cta.mbarrier::complete_tx::bytes [%0], [%1], 512, [%2];"
                                 :: "r"(rb_ + SM_U + 128 + q * UP + sl * US), "r"(sb + SM_XT + 128 + (q & 3) * 16 + pe * YP + sl * YS), "r"(rb_ + SM_MB + (MB_X + sl) * 8) : "memory");
                }
            }
        }
        STAMP(1);
        if (warp == 20 && lane == 0) { asm volatile("prefetch.tensormap [%0];" :: "l"(&tmO) : "memory"); asm volatile("prefetch.tensormap [%0];" :: "l"(&tmH) : "memory"); }
        if (warp == 22) {
            __syncwarp();
            mbar_wait(mb + (MB_X + 1) * 8);
            const uint32_t old = (epoch & 1) ? 0u : 0x40004000u;
#pragma unroll
            for (int t = 0; t < 2; t++)
                if ((lane & 7) < 6) g_s.cand[((q * 8 + 4 * t + (lane >> 3)) * NCL + c) * 6 + (lane & 7)] = make_uint4(old, old, old, old);
            float a[4] = {0.f, 0.f, 0.f, 0.f};
            const uint32_t one = 0x3F803F80u;
            mma_bf16(a, one, one, one, one, wv.x, wv.y);  mma_bf16(a, one, one, one, one, wv.z, wv.w);
            mma_bf16(a, one, one, one, one, wv2.x, wv2.y); mma_bf16(a, one, one, one, one, wv2.z, wv2.w);
            mma_bf16(a, one, one, one, one, wv3.x, wv3.y); mma_bf16(a, one, one, one, one, wv3.z, wv3.w);
            float s = a[0] + a[1];
            s += __shfl_xor_sync(~0u, s, 1); s += __shfl_xor_sync(~0u, s, 2);
            stsf(sb + SM_SC + 24, s);
            __syncwarp();
            if (lane == 0) {
                int n = 0;
                while ((int)(ld_acq(&g_s.zcnt) - epoch * NCTA) < 0 && ++n < SPIN_LIMIT) __nanosleep(200);
                arm(mb + MB_Y * 8, 8 * 512 * nslot);
                if (blockIdx.x == 0) g_s.epoch = epoch;
            }
            STAMP(2);
        }
        if (warp == 23) {
#pragma unroll 1
            for (int kk = nslot - 1; kk >= 0; kk--) {
                __syncwarp();
                bar_sync(6 + kk, 160);
                if (lane == 0) { asm volatile("fence.proxy.async.shared::cta;" ::: "memory"); tma2d(sb + SM_FAR + kk * FAR_SZ, &tmD, 72 * q, 320 * c + 64 * kk, mb + MB_W2 * 8); }
            }
        }
        }
        __syncwarp();
        bar_sync(14, 768);
        if (tid == 640) {
            asm volatile("fence.proxy.async.shared::cta;" ::: "memory");
            asm volatile("cp.async.bulk.tensor.5d.global.shared::cta.bulk_group [%0, {%2, %4, %4, %4, %3}], [%1];" :: "l"(&tmH), "r"(sb + SM_XT + 16384), "r"(d0 + ((c & 1) ? 0 : 32)), "r"(8 * q), "r"(0) : "memory");
            asm volatile("cp.async.bulk.tensor.5d.global.shared::cta.bulk_group [%0, {%2, %4, %4, %4, %3}], [%1];" :: "l"(&tmO), "r"(sb + SM_XT), "r"(d0 + (c & 1) * 8), "r"(8 * q), "r"(0) : "memory");
            asm volatile("cp.async.bulk.commit_group;" ::: "memory");
        }
        __syncwarp();
        const uint32_t ft = (tid >> 4) & 7, fj = d0 / 3 + (lane & 15), tok = ~lds32(sb + SM_SEL + ft * 8) & 2047;
        float v[3], cnt = 0.f;
#pragma unroll
        for (int i = 0; i < 3; i++) {
            const uint32_t cl = 3 * fj + i - d0, cf = cl - (c & 1) * 8;
            const bool ok = cl < 8 * nslot && ((tok >> 3) & 7) == q;
            const uint32_t u = lds16(sb + SM_XT + (cf < 32 ? tslot(tok) * 64 + cf * 2 : 16384 + tslot(tok) * 16 + (cl & 7) * 2));
            v[i] = ok ? __uint_as_float(u << 16) : 0.f;
            if (ok) cnt += 1.f;
        }
        if (tid == 640) {
            asm volatile("cp.async.bulk.wait_group 0;" ::: "memory");
            asm volatile("fence.proxy.async.global;" ::: "memory");
            asm volatile("mbarrier.arrive.shared::cta.b64 _, [%0];" :: "r"(mb + MB_OUT * 8) : "memory");
        }
        __syncwarp();
        mbar_wait(mb + MB_OUT * 8);
        STAMP(5);
        if (cnt != 0.f) finish(prm, (ft * 192 + fj) * 16, (tok * D_ + 3 * fj) * 2, v, cnt);
        return;
    }

    const int g = lane >> 2, cq = lane & 3;
    const int k = warp >> 2, wq = warp & 3;
    const int trow = 18 * blockIdx.x + warp;
    const bool rowact = warp < 18 && trow < L_;
    const int dch = min(d0 + 8 * k + q, D_ - 1);
    uint32_t pv[6];
    const uint32_t pofs = opaque((dch * 128 + wq * 32 + lane) * 2);
#pragma unroll
    for (int i = 0; i < 6; i++) pv[i] = ldg16((const char*)prm.prm6[i] + pofs);
    const uint32_t pLdt = ldg16(prm.logdt + dch), pD = ldg16(prm.dskip + dch);
    const int tn = 16 * (warp & 15) + g;
    uint32_t xa[5], xb[5];
    asm volatile("barrier.cluster.arrive.relaxed.aligned;" ::: "memory");
    uint4* const st1p = &g_s.st1[(((trow >> 3) & 7) * 256 + ((trow >> 6) & 31) * 8 + (trow & 7)) * 2 + (lane >> 2)];
    const bool pub = rowact && (lane & 0x1B) == 0;
    if (pub) st_rlx128(st1p, 0, 0, 0, 0);
    {
        const uint32_t za = sb + SM_P + tid * 16;
        sts128(za, 0, 0, 0, 0);
        if (tid < (SM_MISC - SM_P) / 16 - 640) sts128(za + 10240, 0, 0, 0, 0);
        sts128(sb + ((wq & 2) ? SM_U : SM_XT + (q & 3) * 16) + ((tid >> 3) & 7) * ((wq & 2) ? UP : YP) + k * YS + (lane & 7) * 16, 0, 0, 0, 0);
    }
    bar_sync(12, NTHR);
    const uint32_t dep = lds32(sb + SM_P);
#define PV(x) __uint_as_float(__byte_perm(dep, x, 0x5410))
    STAMP(1);
    const uint32_t fb = sb + SM_FAR + k * FAR_SZ;
    const uint32_t pn = sb + SM_PN + k * PN_SZ, pf = sb + SM_PF + k * PF_SZ;
    unsigned epoch;
    {
        const uint32_t kb = fb + wq * 3072;
        const uint32_t kl = kb + lane * 16;
        uint32_t Af[4][4];
        float sr, si, z1r, z1i, z2r, z2i, z4r, z4i, hr, hi_;
        {
            const float dt = bfr(ex2f(PV(pLdt) * 1.4426950408889634f));
            const float e2 = dt * PV(pv[0]) * 1.4426950408889634f, an = dt * PV(pv[1]);
            float ar, ai, br, bi, cr, ci, dr, di;
            { const float m = ex2f(e2 * 8.f); ar = m * __cosf(an * 8.f); ai = m * __sinf(an * 8.f); }
            csq(br, bi, ar, ai); csq(cr, ci, br, bi); csq(dr, di, cr, ci);
            const H2C m4 = splat(cr, ci);
            {
                float r3, i3;
                cmul(r3, i3, ar, ai, br, bi);
                expand4(kl, kl + 1024, pack_f16(1.f, ar), pack_f16(br, r3), pack_f16(0.f, ai), pack_f16(bi, i3), m4);
            }
            expand8(kl + 512, kl + 1536, dr, di, ar, ai, br, bi, m4);
            { const float m = ex2f(e2); z1r = m * __cosf(an); z1i = -m * __sinf(an); }
            cexp_s(hr, hi_, e2 * 128.f, an * (-128.f * 0.15915494309189535f));
            csq(z2r, z2i, z1r, z1i); csq(z4r, z4i, z2r, z2i);
            const uint32_t dep2 = lds32(sb + SM_P + 4);
#define PW(x) __uint_as_float(__byte_perm(dep2, x, 0x5410))
            cmul(sr, si, PW(pv[4]), PW(pv[5]), dt * PW(pv[2]), dt * PW(pv[3]));
            const unsigned E = min(max(__reduce_max_sync(~0u, __float_as_uint(fmaxf(fmaxf(fabsf(sr), fabsf(si)), fabsf(PW(pD)) * (1.f / 8192.f)))) >> 23, 1u), 253u);
            const float sc = __uint_as_float((254u - E) << 23);
            sr *= sc; si *= -sc;
            sts64(sb + SM_KG + warp * 8, E, __reduce_add_sync(~0u, __float2int_rn(sr * 16777216.f)));
            stsf(sb + SM_DW + 96 + k * 4, PW(pD));
        }
        __syncwarp();
#pragma unroll
        for (int ks = 0; ks < 4; ks++) ldsm4t(Af[ks], kb + (lane >> 3) * 512 + (lane & 7) * 16 + ks * 128);
        STAMP(2);
        const uint32_t la = kb + ((lane >> 3) & 1) * 512 + (lane >> 4) * 128 + (lane & 7) * 16;
        uint32_t b0[4], b1[4], b2[4], b3[4];
        auto ln1 = [&]() {
        mbar_wait(mb + MB_R * 8);
        epoch = lds32(sb + SM_SC + 28) + 1;
        {
            const uint32_t ra = sb + SM_ROW + warp * (D_ * 2);
            const uint4 r0 = lds128(ra + lane * 16), r1 = lds128(ra + 512 + lane * 16);
            const uint32_t rx[9] = {r0.x, r0.y, r0.z, r0.w, r1.x, r1.y, r1.z, r1.w, lds32(ra + 1024 + lane * 4)};
            float a0 = bf_lo(rx[0]), a1 = bf_hi(rx[0]), c0 = a0 * a0, c1 = a1 * a1;
#pragma unroll
            for (int i = 1; i < 9; i++) { const float l = bf_lo(rx[i]), h = bf_hi(rx[i]); a0 += l; a1 += h; c0 = fmaf(l, l, c0); c1 = fmaf(h, h, c1); }
            a0 += a1; c0 += c1;
            float s1 = ((lane & 1) ? c0 : a0) + __shfl_xor_sync(~0u, (lane & 1) ? a0 : c0, 1);
#pragma unroll
            for (int o = 2; o < 32; o <<= 1) s1 += __shfl_xor_sync(~0u, s1, o);
            const float s2 = __shfl_xor_sync(~0u, s1, 1);
            const uint32_t ms = ln_stats(s1, s2);
            const uint32_t p0 = __byte_perm(ms, epoch | 0x8000u, 0x5410), p1 = rsplit(rcpf(bf_hi(ms)));
            if (pub) st_rlx128(st1p, p0, p1, p0, p1);
        }
        mbar_wait(mb + MB_R * 8);
        STAMP(1);
        };
        const uint4* sp = &g_s.st1[(256 * q + tn) * 2];
        uint2 sa, sc;
        auto poll = [&]() { sa = ld_rlx64(sp); sc = ld_rlx64(sp + 16); };
        auto norm = [&]() {
        STAMP(3);
        if (warp < 16) {
            uint32_t va[5], vc[5];
            poll();
            mbar_wait(mb + MB_T * 8);
            {
                const uint32_t xt = sb + SM_XTL + (c & 1) * 16 + (72 * wq + 18 * k + g) * (2 * XW);
                uint4 a4 = lds128(xt + cq * 16), b4 = lds128(xt + cq * 16 + 18 * XW);
                va[0] = a4.x; va[1] = a4.y; va[2] = a4.z; va[3] = a4.w; va[4] = lds32(xt + 64 + cq * 4);
                vc[0] = b4.x; vc[1] = b4.y; vc[2] = b4.z; vc[3] = b4.w; vc[4] = lds32(xt + (64 + 18 * XW) + cq * 4);
            }
            const int d4 = 2 * (lane >> 3) + (lane & 1), d1_ = lane & 7;
            const uint32_t own = SM_U + 128 + q * (UP - YP), oth = SM_XT + 128 + (q & 3) * 16;
            uint32_t a4 = sb + warp * 32 + d4 * YP + (d4 == q ? own : oth) + ((lane & 7) >> 1) * YS;
            uint32_t a1 = sb + warp * 32 + d1_ * YP + (d1_ == q ? own : oth) + 4 * YS + (lane & 8) * 2;
            PIN(a4); PIN(a1);
            uint32_t tag = __byte_perm(epoch | 0x8000u, 0, 0x1010);
            PIN(tag);
            mbar_wait(mb + MB_T * 8);
            int n = 0;
            while (__byte_perm(sa.x, sc.x, 0x7632) != tag && ++n < SPIN_LIMIT) poll();
            STAMP(4);
#pragma unroll
            for (int i = 0; i < 5; i++) {
                va[i] = norm2(va[i], sa.x, sa.y); va[i] = pack_f16(bf_lo(va[i]), bf_hi(va[i]));
                vc[i] = norm2(vc[i], sc.x, sc.y); vc[i] = pack_f16(bf_lo(vc[i]), bf_hi(vc[i]));
            }
            stsm4t(a4, va[0], va[1], va[2], va[3]); stsm4t(a4 + 16, vc[0], vc[1], vc[2], vc[3]); stsm2t(a1, va[4], vc[4]);
            bar_arrive(13, 608);
            {
            const uint32_t xh = sb + SM_XTL + (c & 1) * 16 + (9 * g + 144 * (warp & 1) + (warp >> 1)) * (2 * XW);
            const uint4 c4 = lds128(xh + cq * 16), d4_ = lds128(xh + cq * 16 + 144 * XW);
            xa[0] = c4.x; xa[1] = c4.y; xa[2] = c4.z; xa[3] = c4.w; xa[4] = lds32(xh + 64 + cq * 4);
            xb[0] = d4_.x; xb[1] = d4_.y; xb[2] = d4_.z; xb[3] = d4_.w; xb[4] = lds32(xh + (64 + 144 * XW) + cq * 4);
            }
        }
        STAMP(5);
        __syncwarp();
        bar_sync(15, 672);
        Af[0][0] |= lds32(sb + SM_P);
        };
        cmul(sr, si, sr, si, z1r, z1i);
        {
            const H2C h4 = splat(z4r, z4i);
            expand8(kl, kl + 512, sr, si, z1r, z1i, z2r, z2i, h4);
            cmul(sr, si, sr, si, hr, hi_);
            expand8(kl + 1024, kl + 1536, sr, si, z1r, z1i, z2r, z2i, h4);
        }
        __syncwarp();
        ldsm4t(b0, la); ldsm4t(b1, la + 256); ldsm4t(b2, la + 1024); ldsm4t(b3, la + 1280);
        cmul(z1r, z1i, z1r, z1i, hr, hi_);
        cmul(sr, si, sr, si, z1r, z1i);
        expand8(kl, kl + 512, sr, si, z2r, z2i, z4r, z4i, splat(hr, hi_));
        ln1();
        csq(z1r, z1i, z1r, z1i);
        cmul(sr, si, sr, si, z1r, z1i);
        csq(z2r, z2i, hr, hi_);
        expand8(kl + 1024, kl + 1536, sr, si, z4r, z4i, hr, hi_, splat(z2r, z2i));
        csq(z1r, z1i, z1r, z1i);
        cmul(sr, si, sr, si, z1r, z1i);
        csq(z4r, z4i, z2r, z2i);
        expand8(kl + 2048, kl + 2560, sr, si, hr, hi_, z2r, z2i, splat(z4r, z4i));
        norm();
        {
            uint32_t c0[4], c1[4], c2[4], c3[4], e0[4], e1[4];
            float t[6][4];
            ldsm4t(c0, la); ldsm4t(c2, la + 1024);
            mma_f16_z(t[0], Af[0], b0[0], b0[1]);
            const uint32_t lb = la | (__float_as_uint(t[0][0]) & zero);
            mma_f16_z(t[1], Af[0], b2[0], b2[1]); mma_f16_z(t[2], Af[0], c0[0], c0[1]); mma_f16_z(t[3], Af[0], c2[0], c2[1]);
            ldsm4t(e0, lb + 2048); ldsm4t(c1, lb + 256); ldsm4t(c3, lb + 1280); ldsm4t(e1, lb + 2304);
            mma_f16(t[0], Af[1], b0[2], b0[3]); mma_f16(t[1], Af[1], b2[2], b2[3]); mma_f16(t[2], Af[1], c0[2], c0[3]); mma_f16(t[3], Af[1], c2[2], c2[3]);
            mma_f16(t[0], Af[2], b1[0], b1[1]); mma_f16(t[1], Af[2], b3[0], b3[1]);
            mma_f16_z(t[4], Af[0], e0[0], e0[1]); mma_f16_z(t[5], Af[1], e0[2], e0[3]);
            mma_f16(t[2], Af[2], c1[0], c1[1]); mma_f16(t[3], Af[2], c3[0], c3[1]);
            mma_f16(t[4], Af[2], e1[0], e1[1]); mma_f16(t[5], Af[3], e1[2], e1[3]);
            mma_f16(t[0], Af[3], b1[2], b1[3]); mma_f16(t[1], Af[3], b3[2], b3[3]); mma_f16(t[2], Af[3], c1[2], c1[3]); mma_f16(t[3], Af[3], c3[2], c3[3]);
            stsm4(kl + 1024, pack_f16(t[0][0], t[0][1]), pack_f16(t[0][2], t[0][3]), pack_f16(t[1][0], t[1][1]), pack_f16(t[1][2], t[1][3]));
            stsm2(kl + 1536, pack_f16(t[2][0], t[2][1]), pack_f16(t[2][2], t[2][3]));
            sts64(kb + lane * 8 + 1792, pack_f16(t[3][1], t[3][0]), pack_f16(t[3][3], t[3][2]));
            sts64(kb + lane * 8 + 2048, pack_f16(t[4][1] + t[5][1], t[4][0] + t[5][0]), pack_f16(t[4][3] + t[5][3], t[4][2] + t[5][2]));
        }
        bar_sync(1 + k, 128);
        const uint4 m01 = lds128(sb + SM_KG + k * 32), m23 = lds128(sb + SM_KG + k * 32 + 16);
        const unsigned Em = max(max(m01.x, m01.z), max(m23.x, m23.z));
        const float f0 = __uint_as_float(max((int)(127 + m01.x - Em), 0) << 23), f1 = __uint_as_float(max((int)(127 + m01.z - Em), 0) << 23),
                    f2 = __uint_as_float(max((int)(127 + m23.x - Em), 0) << 23), f3 = __uint_as_float(max((int)(127 + m23.z - Em), 0) << 23);
        const uint32_t r0 = pack_f16(f0, f0), r1 = pack_f16(f1, f1), r2 = pack_f16(f2, f2), r3 = pack_f16(f3, f3);
        const int tq = (wq + k) & 3;
        const uint32_t ra = fb + lane * 8 + (tq == 1 ? 2048 : tq * 256 + 1024);
        auto comb = [&](uint32_t a, uint32_t& x, uint32_t& y) {
            const uint2 p0 = lds64(a), p1 = lds64(a + 3072), p2 = lds64(a + 6144), p3 = lds64(a + 9216);
            x = hadd2(hfma2(p0.x, r0, hmul2(p1.x, r1)), hfma2(p2.x, r2, hmul2(p3.x, r3)));
            y = hadd2(hfma2(p0.y, r0, hmul2(p1.y, r1)), hfma2(p2.y, r2, hmul2(p3.y, r3)));
        };
        uint32_t w0, w1;
        comb(ra, w0, w1);
        const bool last = lane == 31;
        if (tq == 0) {
            uint32_t v0, v1;
            comb(ra + 256, v0, v1);
            const uint32_t n0 = __shfl_sync(~0u, lane ? w0 : v0, lane + 1);
            uint32_t n1 = __shfl_sync(~0u, v0, lane + 1);
            if (last) n1 = v1 >> 16;
            sts128(pn + 12 + lane * 16, __byte_perm(w1, w0, 0x7610), __byte_perm(w1, 0, 0x1032), __byte_perm(n0, w1, 0x7610), __byte_perm(n0, 0, 0x1032));
            sts128(pn + 524 + lane * 16, __byte_perm(v1, v0, 0x7610), __byte_perm(v1, 0, 0x1032), __byte_perm(n1, v1, 0x7610), __byte_perm(n1, 0, 0x1032));
            if (lane == 0) {
                sts32(sb + SM_SC + k * 4, Em * 0x00800080u);
                const uint32_t t0 = pack_f16(((float)(int)m01.y * f0 + (float)(int)m01.w * f1 + (float)(int)m23.y * f2 + (float)(int)m23.w * f3) * (1.f / 16777216.f)
                                         + ldsf(sb + SM_DW + 96 + k * 4) * __uint_as_float((254u - Em) << 23), 0.f);
                sts128(pn - 4, 0, t0, __byte_perm(w0, t0, 0x5410), __byte_perm(w0, 0, 0x1032));
            }
        } else if (tq == 1) {
            const uint32_t ph = pf + P_H7 + (g & 1) * (2 * P_HS) + cq * 64 + (g >> 1) * 4 + (cq & 2) * 16, sw = (cq & 2) ? 0x3210 : 0x1032;
            w0 = __byte_perm(hmul2(w0, 0x18001800u), 0, sw); w1 = __byte_perm(hmul2(w1, 0x18001800u), 0, sw);
            const uint32_t pi = ph + 32 - (cq & 2) * 32;
            put16(ph, w0); put16(pi, w0 >> 16); put16(ph + 16, w1); put16(pi + 16, w1 >> 16);
        } else if (tq == 2) {
            uint32_t n = __shfl_sync(~0u, w0, lane == 30 ? 1 : lane + 2);
            if (last) { put16(pf, hmul2(w1, 0x18001800u) >> 16); w1 = hadd2(w1, hneg2(__byte_perm(w1, 0, 0x3232))); n = 0; }
            const bool od = lane & 1;
            const uint32_t pa = pn + 1036 + (lane >> 1) * 32 + (od ? 528 : 0), pb = pa + (od ? -16 : 16);
            const uint32_t u0 = od ? w1 : w0, x0 = od ? n : w1, u1 = od ? w0 : w1, x1 = od ? w1 : n;
            const uint32_t b0 = __byte_perm(u0, 0, 0x3232), b1 = __byte_perm(u1, 0, 0x3232);
            sts128(pa, __byte_perm(u0, 0, 0x1032), b0, b0, __byte_perm(x0, u0, 0x7610));
            sts128(pb, __byte_perm(u1, 0, 0x1032), b1, b1, __byte_perm(x1, u1, 0x7610));
        } else {
            const uint32_t pa = pf + ((g & 1) ? 3 * P_GS : P_GS) + cq * 32 + (g >> 1) * 4;
            const uint32_t pb = pa + ((g & 1) ? 4 - 3 * P_GS : P_GS);
            w0 = hmul2(w0, 0x18001800u); w1 = hmul2(w1, 0x18001800u);
            put16(pa, w0 >> 16); put16(pb, w0); put16(pa + 16, w1 >> 16); put16(pb + 16, w1);
            if (last) put16(pf + P_H7 + P_HS, w1);
        }
        bar_sync(1 + k, 128);
        if (tq == 2 && lane == 0) sts16(pn + 258 * 4, w0);
    }
    STAMP(6);

    asm volatile("barrier.cluster.wait.aligned;" ::: "memory");
    mbar_wait(mb + (MB_X + (k < nslot ? k : 0)) * 8);
    STAMP(7);
    if (k < nslot) {
        const int role = (wq + k) & 3;
        const uint32_t ub = sb + SM_U + k * US + 128;
        if (role) {
            const int r = (3 - role) * 32 + lane;
            const uint32_t a1 = ub + (r & 3) * (2 * UP) + (r >> 2) * 16, a0 = a1 + ((r & 3) ? -2 * UP : 6 * UP - 16);
            const uint4 q0 = lds128(a0), q1 = lds128(a0 + UP), q2 = lds128(a1), q3 = lds128(a1 + UP);
            const uint32_t U[16] = {q0.x, q0.y, q0.z, q0.w, q1.x, q1.y, q1.z, q1.w, q2.x, q2.y, q2.z, q2.w, q3.x, q3.y, q3.z, q3.w};
            uint32_t V[14], Q[14], R4[12], T[8];
#pragma unroll
            for (int i = 2; i < 14; i++) { V[i] = __byte_perm(U[i], U[i + 1], 0x5432); Q[i] = hadd2(U[i], V[i]); }
#pragma unroll
            for (int i = 2; i < 12; i++) R4[i] = hadd2(Q[i], Q[i + 1]);
            const uint32_t rb = fb + r * 16;
#pragma unroll
            for (int i = 0; i < 8; i++) T[i] = hadd2(V[5 + i], Q[6 + i]);
            sts128(rb + F_E3, T[0], T[1], T[2], T[3]); sts128(rb + F_O3 + 16, T[4], T[5], T[6], T[7]);
#pragma unroll
            for (int i = 0; i < 8; i++) T[i] = hadd2(R4[3 + i], U[5 + i]);
            sts128(rb + F_O5, T[0], T[1], T[2], T[3]); sts128(rb + F_E5, T[4], T[5], T[6], T[7]);
            if (role != 1) {
#pragma unroll
                for (int i = 0; i < 8; i++) T[i] = hadd2(T[i], hadd2(V[2 + i], V[5 + i]));
                sts128(rb + F_E7, T[0], T[1], T[2], T[3]); sts128(rb + F_O7, T[4], T[5], T[6], T[7]);
#pragma unroll
                for (int i = 0; i < 8; i++) T[i] = hadd2(R4[2 + i], hadd2(R4[4 + i], U[6 + i]));
                sts128(rb + F_O9, T[0], T[1], T[2], T[3]); sts128(rb + F_E9 + 16, T[4], T[5], T[6], T[7]);
                sts128(rb + F_E2, Q[6], Q[7], Q[8], Q[9]); sts128(rb + F_O2, Q[10], Q[11], Q[12], Q[13]);
            }
        } else if (lane < 8) {
            uint32_t v[5];
#pragma unroll
            for (int i = 0; i < 5; i++) { const int t = 6 + lane + i; v[i] = lds16(ub + 23 * 16 + (t < 16 ? (6 + (t >> 3)) * UP : 16) + (t & 7) * 2); }
            const uint32_t s = hadd2(hadd2(hadd2(v[0], v[1]), hadd2(v[2], v[3])), v[4]);
            sts16(fb + F_O5 + 96 * 16 + lane * 2, s);
            sts32(fb + (lane < 4 ? F_O3 : F_E9 - 16) + lane * 4, 0);
        }
        bar_sync(1 + k, 128);
        float acc[4][4];
        uint32_t Q[4][4];
        {
            const int h = role & 1, part = role >> 1;
            const uint32_t po = pf + (g - 2 * cq) * 4;
            float fa[7][4];
#pragma unroll
            for (int a = 1; a < 7; a++) fa[a][0] = fa[a][1] = fa[a][2] = fa[a][3] = 0.f;
            uint32_t B[3][4];
            Q[0][2] = tid & zero; Q[2][1] = lane & zero;
#pragma unroll 1
            for (int s = 2 * part + 1; s >= 2 * part; s--) {
#pragma unroll
                for (int i = 0; i < 3; i++) { Q[i][0] = lds32(po + s * P_GS + i * 64); if (i < 2) Q[i][1] = lds32(po + s * P_GS + (i * 64 + 32)); }
                const uint32_t ba = fb + lane * 16 + ((s & 1) * F_E3 + (part == h ? 0 : F_O5 + h * 16));
#pragma unroll
                for (int i = 0; i < 3; i++) ldsm4t(B[i], ba + i * 512);
#pragma unroll
                for (int i = 0; i < 3; i++) { Q[i][3] = CP(Q[i][0]); if (i) Q[i][2] = CP(Q[i - 1][1]); }
#pragma unroll
                for (int dl = 0; dl < 3; dl++)
#pragma unroll
                    for (int ap = 0; ap < 6 - dl; ap++) mma_f16(fa[ap + 1 + dl], Q[dl], B[ap >> 1][2 * (ap & 1)], B[ap >> 1][2 * (ap & 1) + 1]);
            }
#pragma unroll 1
            for (int s = role; s == 1; s++) {
                ldsm2t(B[0][0], B[0][1], fb + ((lane & 15) == 15 ? F_O5 : F_O3));
#pragma unroll
                for (int dl = 1; dl < 3; dl++) mma_f16(fa[dl], Q[dl], B[0][0], B[0][1]);
            }
#pragma unroll 1
            for (int s = part; s <= 2 * part; s++) {
#pragma unroll
                for (int i = 0; i < 4; i++) { Q[i][0] = lds32(po + s * P_HS + (P_H7 + i * 64)); Q[i][1] = lds32(po + s * P_HS + (P_H7 + i * 64 + 32)); }
                const uint32_t ba = fb + lane * 16 + (F_E7 + s * 1024 + h * F_H);
                ldsm4t(B[0], ba); ldsm4t(B[1], ba + 512);
#pragma unroll
                for (int i = 0; i < 4; i++) { Q[i][3] = CP(Q[i][0]); if (i) Q[i][2] = CP(Q[i - 1][1]); }
#pragma unroll
                for (int dl = 0; dl < 4; dl++) {
#pragma unroll
                    for (int ap = 0; ap < 4 - dl; ap++) mma_f16(fa[ap + 3 + dl], Q[dl], B[ap >> 1][2 * (ap & 1)], B[ap >> 1][2 * (ap & 1) + 1]);
                    if (s == 1) break;
                }
            }
            const uint32_t da = fb + role * 2048 + (lane & 3) * 512 + (((lane >> 2) ^ ((lane & 3) * 2)) << 4);
            bar_sync(1 + k, 128);
#pragma unroll
            for (int i = 1; i < 4; i++)
                stsm4(da + i * 128, pack_f16(fa[2 * i - 1][0], fa[2 * i - 1][1]), pack_f16(fa[2 * i - 1][2], fa[2 * i - 1][3]),
                      pack_f16(fa[2 * i][0], fa[2 * i][1]), pack_f16(fa[2 * i][2], fa[2 * i][3]));
            Q[0][0] = (g == 2 * cq) ? 0x6000u : ((g == 2 * cq + 1) ? 0x60000000u : 0u);
            Q[0][1] = Q[0][0] & zero; Q[0][2] = lane & zero; Q[0][3] = CP(Q[0][0]);
            const uint32_t ra = fb + (lane >> 3) * 2048 + wq * 512 + (((lane & 7) ^ (wq * 2)) << 4);
            acc[0][0] = acc[0][1] = acc[0][2] = acc[0][3] = 0.f;
            if (wq == 3) {
                const uint32_t uw = lds32(ub), kw = lds32(pf);
                const float2 uf = __half22float2(*(const __half2*)&uw);
                if ((lane | 4) == 31) acc[0][3] = (lane == 31 ? uf.x + uf.y : uf.x) * (__low2float(*(const __half2*)&kw) * 512.f);
            }
            bar_sync(1 + k, 128);
#pragma unroll
            for (int i = 1; i < 4; i++) {
                ldsm4(B[0], ra + i * 128);
                mma_f16_z(acc[i], Q[0], hadd2(B[0][0], B[0][2]), hadd2(B[0][1], B[0][3]));
            }
        }
        bar_arrive(6 + k, 160);
        STAMP(8);
        const uint32_t inv = lds32(sb + SM_SC + k * 4);
        uint32_t yd = mapa(sb, 2 * wq) + (SM_XT + 128 + q * YP + k * YS + (k >> 2) * (q >> 1) * 16) + lane * 16;
        PIN(yd);
        {
            uint32_t pp = pn + (16 * (wq - 3) + g - 2 * cq) * 4;
            uint32_t dlo = (((ub + 6 * UP) & 0x3FFFF) >> 4) | ((UP >> 4) << 16);
            uint32_t R[4][4];
            auto loadQ = [&](uint32_t (&X)[4][4], uint32_t prev) {
#pragma unroll
                for (int i = 0; i < 4; i++) { X[i][0] = lds32(pp + i * 64); X[i][1] = lds32(pp + i * 64 + 32); }
                X[0][2] = CP(prev);
#pragma unroll
                for (int i = 0; i < 4; i++) { X[i][3] = CP(X[i][0]); if (i) X[i][2] = CP(X[i - 1][1]); }
                pp += 256;
            };
            auto issue = [&](uint32_t (&X)[4][4]) {
                asm volatile("wgmma.fence.sync.aligned;" ::: "memory");
#pragma unroll
                for (int i = 0; i < 4; i++) wgmma32(acc, X[i], dlo - i * (2 * UP >> 4));
                asm volatile("wgmma.commit_group.sync.aligned;" ::: "memory");
                dlo -= 1;
            };
#pragma unroll
            for (int i = 0; i < 4; i++) {
                Q[i][0] = Q[i][1] = 0;
                if (wq + i >= 3) { Q[i][0] = lds32(pp + i * 64); Q[i][1] = lds32(pp + i * 64 + 32); }
            }
            Q[0][2] = CP(0);
#pragma unroll
            for (int i = 0; i < 4; i++) { Q[i][3] = CP(Q[i][0]); if (i) Q[i][2] = CP(Q[i - 1][1]); }
            pp += 256;
#pragma unroll 1
            for (int dl = 0; dl < 4; dl++) {
                issue(Q);
                asm volatile("wgmma.wait_group.sync.aligned 1;" ::: "memory");
                loadQ(R, Q[3][1]);
                issue(R);
                asm volatile("wgmma.wait_group.sync.aligned 1;" ::: "memory");
                loadQ(Q, R[3][1]);
            }
            issue(Q);
            asm volatile("wgmma.wait_group.sync.aligned 0;" ::: "memory");
        }
        const uint32_t pstep = mapa(sb, 1) - mapa(sb, 0), ym = mapa(mb + MB_Y * 8, 2 * wq);
#pragma unroll
        for (int e = 0; e < 2; e++)
            st_async4(yd + e * pstep, bmul2(pack_bf16(acc[0][2 * e], acc[0][2 * e + 1]), inv), bmul2(pack_bf16(acc[1][2 * e], acc[1][2 * e + 1]), inv),
                      bmul2(pack_bf16(acc[2][2 * e], acc[2][2 * e + 1]), inv), bmul2(pack_bf16(acc[3][2 * e], acc[3][2 * e + 1]), inv), ym + e * pstep);
        if (lane == 0) asm volatile("mbarrier.arrive.shared::cta.b64 _, [%0];" :: "r"(mb + MB_Y * 8) : "memory");
    }
    STAMP(9);
    uint32_t ha[5], hb[5];
    if (warp < 16) {
        const uint4 wk = lds128(sb + SM_DW + cq * 16);
        uint32_t sel[5] = {wk.x, wk.y, wk.z, wk.w, lds32(sb + SM_DW + 64 + cq * 4)}, sel2[5];
#pragma unroll
        for (int i = 0; i < 5; i++) {
            if (!(g & 1)) sel[i] = 0x3F803F80u;
            sel2[i] = sel[i]; PIN(sel2[i]);
        }
        const uint32_t y4 = sb + SM_XT + 128 + warp * 32 + (2 * (lane >> 3) + (lane & 1)) * YP + ((lane & 7) >> 1) * YS;
        const uint32_t y1 = sb + SM_XT + 128 + warp * 32 + (lane & 7) * YP + 4 * YS + (lane & 8) * 2 + (lane & 6) * 8;
        uint32_t ao = (256 * q + tn) * 16, hta = sb + SM_HT + tn * 80;
        PIN(ao); PIN(hta);
        mbar_wait(mb + MB_Y * 8);
        STAMP(10);
        float ca[4] = {0.f, 0.f, 0.f, 0.f}, cb[4] = {0.f, 0.f, 0.f, 0.f};
        {
            uint32_t ya[4], yb[4], yc, yd;
            ldsm4t(ya, y4); ldsm4t(yb, y4 + 16); ldsm2t(yc, yd, y1);
#pragma unroll
            for (int i = 0; i < 4; i++) { ha[i] = badd2(xa[i], ya[i]); hb[i] = badd2(xb[i], yb[i]); }
            ha[4] = badd2(xa[4], yc); hb[4] = badd2(xb[4], yd);
        }
        if (nslot != 5) {
            ha[4] = hb[4] = 0;
            if (cq >= 2) ha[0] = ha[1] = ha[2] = ha[3] = hb[0] = hb[1] = hb[2] = hb[3] = 0;
        }
#pragma unroll
        for (int i = 0; i < 5; i++) { mma_bf16_k8(ca, ha[i], sel[i], ha[i]); mma_bf16_k8(cb, hb[i], sel2[i], hb[i]); }
        if (!(g & 1)) { ca[1] = ca[0]; cb[1] = cb[0]; }
        if (cq == (g >> 1)) {
            asm volatile("red.relaxed.gpu.global.add.v4.f32 [%0], {%1,%2,%3,%4};" :: "l"((char*)g_s.acc + ao), "f"(1.0f), "f"(ca[1]), "f"(ca[2]), "f"(ca[3]) : "memory");
            asm volatile("red.relaxed.gpu.global.add.v4.f32 [%0], {%1,%2,%3,%4};" :: "l"((char*)g_s.acc + ao + 128), "f"(1.0f), "f"(cb[1]), "f"(cb[2]), "f"(cb[3]) : "memory");
        }
        sts128(hta + cq * 16, ha[0], ha[1], ha[2], ha[3]); sts32(hta + 64 + cq * 4, ha[4]);
        sts128(hta + cq * 16 + 640, hb[0], hb[1], hb[2], hb[3]); sts32(hta + 704 + cq * 4, hb[4]);
        STAMP(11);
    }
    const int kq = warp / 5, mt = warp - 5 * kq;
    const int mi = lane >> 3, mr = lane & 7;
    const unsigned tk = (unsigned)tid / 72u, ck = tid - tk * 72;
    uint32_t A[9][4];
    auto loadA = [&]() {
        mbar_wait(mb + MB_W1 * 8);
        const uint32_t aa = sb + (mi & 1) * SM_WU + (8 * (mi >> 1) + mr) * 80 + (144 * 80 * kq + mt * 16);
#pragma unroll
        for (int s = 0; s < 9; s++) ldsm4t(A[s], aa + s * 1280);
    };
    const uint32_t par = (lds32(sb + SM_SC + 28) & 1) ? 0u : 0x40004000u;
    uint32_t pk0 = mapa(sb, 2 * cq), go = (ck / 5u + ck) * 16, co = ((q * 8 * NCL + c) * 6 + cq) * 16;
    PIN(pk0); PIN(go); PIN(co);
    if (warp < 8) {
        const float wsum = ldsf(sb + SM_SC + 24);
        const uint32_t idx = 2047 - (512 * ((tid >> 1) & 3) + 128 * ((tid >> 3) & 3) + 64 * (tid & 1) + 8 * q + warp);
        uint4 s; int n = 0;
        do { s = ld_rlx128(&g_s.acc[256 * q + tid]); } while (__uint_as_float(s.x) != (float)NCL && ++n < SPIN_LIMIT);
        STAMP(16);
        const uint32_t ox = __shfl_xor_sync(~0u, (lane & 1) ? s.z : s.w, 1);
        const uint32_t ms = ln_stats(__uint_as_float((lane & 1) ? ox : s.z), __uint_as_float(s.y));
        const float rs = rcpf(bf_hi(ms));
        const uint32_t rb = pack_bf16(0.f, fmaf(-bf_lo(ms), wsum, __uint_as_float((lane & 1) ? s.w : ox)) * rs);
        const uint32_t key = (((rb ^ (((int)rb >> 31) | 0x80000000u)) >> 16) << 11) | idx;
        sts32(sb + SM_KEY + tid * 4, key);
        __syncwarp();
        const uint32_t rank = rank4<8, 16>(sb + SM_KEY + warp * 128, key);
        asm volatile("{ .reg .pred p; setp.lt.u32 p, %0, 8; @p st.shared.u32 [%1], %2; }" :: "r"(rank), "r"(sb + SM_CAND + warp * 32 + rank * 4), "r"(key) : "memory");
        sts64(sb + SM_ST + tid * 8, ms, rsplit(rs));
    } else { mbar_wait(mb + MB_Y * 8); loadA(); }
    if (warp < 16) {
        STAMP(17);
        bar_sync(12, 512);
        STAMP(18);
        if (warp < 8) {
            const uint32_t mk = lds32(sb + SM_CAND + (tid >> 2) * 4);
            uint32_t rank = rank4<4, 64>(sb + SM_CAND + cq * 16, mk);
            rank += __shfl_xor_sync(~0u, rank, 1); rank += __shfl_xor_sync(~0u, rank, 2);
            if (rank < 8) {
                const uint32_t pk1 = pk0 + (mapa(sb, 1) - mapa(sb, 0));
                st_async1(pk0 + (SM_RK + q * 32) + rank * 4, mk, pk0 + (SM_MB + MB_KEY * 8));
                st_async1(pk1 + (SM_RK + q * 32) + rank * 4, mk, pk1 + (SM_MB + MB_KEY * 8));
                const uint32_t t = tslot(~mk | ((pk1 + rank * 4) & zero));
                const uint2 sv = lds64(sb + SM_ST + t * 8);
                const uint4 hv = lds128(sb + SM_HT + t * 80 + cq * 16);
                const uint32_t h4 = lds32(sb + SM_HT + t * 80 + 64 + cq * 4);
                const uint32_t rr = bmul2(sv.y, 0x3C803C80u);
                char* const dp = (char*)g_s.cand + (co + rank * 1440);
                st_rlx128(dp, (norm2(hv.x, sv.x, rr) & 0xBFFFBFFFu) | par, (norm2(hv.y, sv.x, rr) & 0xBFFFBFFFu) | par,
                          (norm2(hv.z, sv.x, rr) & 0xBFFFBFFFu) | par, (norm2(hv.w, sv.x, rr) & 0xBFFFBFFFu) | par);
                asm volatile("st.relaxed.gpu.global.u32 [%0], %1;" :: "l"((char*)g_s.cand + (co + rank * 1440 + 64 - cq * 12)), "r"((norm2(h4, sv.x, rr) & 0xBFFFBFFFu) | par) : "memory");
            }
            __syncwarp();
        }
        {
            const uint2 sa = lds64(sb + SM_ST + tn * 8), sbb = lds64(sb + SM_ST + tn * 8 + 64);
#pragma unroll
            for (int i = 0; i < 5; i++) { ha[i] = badd2(ha[i], norm2(ha[i], sa.x, sa.y)); hb[i] = badd2(hb[i], norm2(hb[i], sbb.x, sbb.y)); }
            const bool hf = (c & 1) && cq == 0;
            const uint32_t o16 = sb + SM_XT + (hf ? 16384 + tn * 16 : tn * 64 + (cq - (c & 1)) * 16), o4 = sb + SM_XT + ((c & 1) ? tn * 64 + 48 : 16384 + tn * 16) + cq * 4;
            sts128(o16, ha[0], ha[1], ha[2], ha[3]); sts32(o4, ha[4]);
            sts128(o16 + (hf ? 128 : 512), hb[0], hb[1], hb[2], hb[3]); sts32(o4 + ((c & 1) ? 512 : 128), hb[4]);
        }
        if (warp >= 8) {
            STAMP(19);
            mbar_wait(mb + MB_KEY * 8);
            STAMP(20);
            const uint32_t mk = lds32(sb + SM_RK - 256 + (tid >> 2) * 4);
            uint32_t rank = rank4<4, 64>(sb + SM_RK + cq * 16, mk);
            rank += __shfl_xor_sync(~0u, rank, 1); rank += __shfl_xor_sync(~0u, rank, 2);
            if (rank < 8) sts64(sb + SM_SEL + rank * 8, mk, ((tid >> 2) - 64) * 1440);
        }
    }
    bar_sync(11, 640);
    STAMP(12);

    const char* gp = (const char*)g_s.cand + (go + lds32(sb + SM_SEL + 4 + (tk & 7) * 8));
    uint4 hv = ld_rlx128(gp);
    if (warp < 8) loadA();
    const uint32_t ft = (unsigned)tid / 24u, fj = 24 * q + tid - ft * 24;
    const uint32_t key = lds32(sb + SM_SEL + (ft & 7) * 8), k16 = key << 5;
    float sig = bfr(rcpf(1.f + ex2f(__uint_as_float((k16 ^ (~((int)k16 >> 31) | 0x80000000u)) & 0xFFFF0000u) * -1.4426950408889634f)));
    uint32_t ra2 = sb + SM_RED2 + tid * 12 + ft * 16, fo = (ft * 192 + fj) * 16, oo = ((~key & 2047) * D_ + 3 * fj) * 2;
    uint32_t bx = sb + SM_XS + mr * 1168 + mi * 16 + 288 * kq, gd = mapa(sb, kq * (8 / NRED)) + (SM_GU + (q * nslot + mt) * 128) + lane * 4;
    PIN(ra2); PIN(fo); PIN(oo); PIN(bx); PIN(gd);
    asm volatile("" : "+f"(sig));
    {
        if (warp < 18) {
            int n = 0;
            while (true) {
                sts128(sb + SM_XS + tk * 16 + tid * 16, hv.x ^ par, hv.y ^ par, hv.z ^ par, hv.w ^ par);
                if (!__any_sync(~0u, ((hv.x ^ par) | (hv.y ^ par) | (hv.z ^ par) | (hv.w ^ par)) & 0x40004000u) || ++n >= SPIN_LIMIT) break;
                hv = ld_rlx128(gp);
            }
        }
    }
    bar_sync(14, 768);
    STAMP(13);
    {
        float c0[4] = {0.f, 0.f, 0.f, 0.f}, c1[4] = {0.f, 0.f, 0.f, 0.f}, c2[4] = {0.f, 0.f, 0.f, 0.f};
        uint32_t b[5][4];
#pragma unroll
        for (int s = 0; s < 4; s++) ldsm4(b[s], bx + s * 64);
        asm volatile("ldmatrix.sync.aligned.m8n8.x2.shared.b16 {%0,%1}, [%2];" : "=r"(b[4][0]), "=r"(b[4][1]) : "r"(bx + 256) : "memory");
        mma_bf16(c0, A[0][0], A[0][1], A[0][2], A[0][3], b[0][0], b[0][1]);
        mma_bf16(c1, A[1][0], A[1][1], A[1][2], A[1][3], b[0][2], b[0][3]);
        mma_bf16(c2, A[2][0], A[2][1], A[2][2], A[2][3], b[1][0], b[1][1]);
        mma_bf16(c0, A[3][0], A[3][1], A[3][2], A[3][3], b[1][2], b[1][3]);
        mma_bf16(c1, A[4][0], A[4][1], A[4][2], A[4][3], b[2][0], b[2][1]);
        mma_bf16(c2, A[5][0], A[5][1], A[5][2], A[5][3], b[2][2], b[2][3]);
        mma_bf16(c0, A[6][0], A[6][1], A[6][2], A[6][3], b[3][0], b[3][1]);
        mma_bf16(c1, A[7][0], A[7][1], A[7][2], A[7][3], b[3][2], b[3][3]);
        mma_bf16(c2, A[8][0], A[8][1], A[8][2], A[8][3], b[4][0], b[4][1]);
        sts128f(sb + SM_RED + tid * 16, c0[0] + c1[0] + c2[0], c0[1] + c1[1] + c2[1], c0[2] + c1[2] + c2[2], c0[3] + c1[3] + c2[3]);
    }
    bar_sync(1 + mt, 128);
    STAMP(21);
    if (mt < nslot && kq < NRED) {
        const uint32_t ra = sb + SM_RED + mt * 512 + lane * 16;
        const float4 p0 = lds128f(ra), p1 = lds128f(ra + 2560), p2 = lds128f(ra + 5120), p3 = lds128f(ra + 7680);
        const float g0 = bfr(((p0.x + p1.x) + (p2.x + p3.x)) * 64.f), g1 = bfr(((p0.y + p1.y) + (p2.y + p3.y)) * 64.f);
        const uint32_t sg = pack_bf16(g0 * rcpf(1.f + ex2f(g0 * -1.4426950408889634f)), g1 * rcpf(1.f + ex2f(g1 * -1.4426950408889634f)));
        const uint32_t gu = bmul2(sg, pack_bf16(((p0.z + p1.z) + (p2.z + p3.z)) * 64.f, ((p0.w + p1.w) + (p2.w + p3.w)) * 64.f));
        const uint32_t pstep = mapa(sb, 1) - mapa(sb, 0), gm = mapa(mb + MB_GU * 8, kq * (8 / NRED));
#pragma unroll
        for (int i = 0; i < 8 / NRED; i++) st_async1(gd + i * pstep, gu, gm + i * pstep);
    }
    mbar_wait(mb + MB_W2 * 8);
    {
        const uint32_t aa = sb + (8 * (mi >> 1) + mr) * 144 + (mi & 1) * 16 + (SM_FAR + 2304 * kq + mt * 32);
#pragma unroll
        for (int s = 0; s < 5; s++) ldsm4t(A[s], aa + s * FAR_SZ);
    }
    {
        uint32_t ba = sb + (SM_GU + 256 * kq) + (lane & 15) * 16 + (lane >> 4) * 1024, wa = sb + (SM_RED2 + kq * 2432 + mt * 64) + g * 4 + cq * 608;
        PIN(ba); PIN(wa);
        STAMP(22);
        mbar_wait(mb + MB_GU * 8);
        STAMP(23);
        float c0[4] = {0.f, 0.f, 0.f, 0.f}, c1[4] = {0.f, 0.f, 0.f, 0.f}, c2[4] = {0.f, 0.f, 0.f, 0.f};
        uint32_t b[2][4], b8, b9;
        ldsm4t(b[0], ba); ldsm4t(b[1], ba + 2048); ldsm2t(b8, b9, ba + 4096);
        mma_bf16(c0, A[0][0], A[0][1], A[0][2], A[0][3], b[0][0], b[0][1]);
        mma_bf16(c1, A[1][0], A[1][1], A[1][2], A[1][3], b[0][2], b[0][3]);
        if (nslot == 5) {
            mma_bf16(c2, A[4][0], A[4][1], A[4][2], A[4][3], b8, b9);
            mma_bf16(c0, A[2][0], A[2][1], A[2][2], A[2][3], b[1][0], b[1][1]);
            mma_bf16(c1, A[3][0], A[3][1], A[3][2], A[3][3], b[1][2], b[1][3]);
        }
        stsf(wa, c0[0] + c1[0] + c2[0]); stsf(wa + 304, c0[1] + c1[1] + c2[1]);
        if (mt < 4) { stsf(wa + 32, c0[2] + c1[2] + c2[2]); stsf(wa + 336, c0[3] + c1[3] + c2[3]); }
    }
    if (warp < 6) {
        float v[3];
        bar_sync(6, 640);
        STAMP(14);
#pragma unroll
        for (int i = 0; i < 3; i++) v[i] = ((ldsf(ra2 + i * 4) + ldsf(ra2 + i * 4 + 2432)) + (ldsf(ra2 + i * 4 + 4864) + ldsf(ra2 + i * 4 + 7296))) * sig;
        finish(prm, fo, oo, v, 3.f);
    } else bar_arrive(6, 640);
    STAMP(15);
}

typedef __nv_bfloat16 bf16;
__device__ bf16 f_n[L_ * D_], f_h[L_ * D_];
__device__ float f_k[D_ * L_], f_r[L_], f_gu[8 * F_];
__device__ int f_idx[8];
__device__ __forceinline__ float b2f(bf16 v) { return __bfloat162float(v); }
__global__ void fb_ln(const bf16* in, const bf16* wr, bf16* out) {
    const int t = blockIdx.x * 8 + (threadIdx.x >> 5), lane = threadIdx.x & 31;
    const bf16* r = (in ? in : f_h) + t * D_;
    float s1 = 0.f, s2 = 0.f, s3 = 0.f;
    for (int i = lane; i < D_; i += 32) s1 += b2f(r[i]);
    for (int o = 16; o; o >>= 1) s1 += __shfl_xor_sync(~0u, s1, o);
    for (int i = lane; i < D_; i += 32) { const float d = b2f(r[i]) - s1 / D_; s2 += d * d; }
    for (int o = 16; o; o >>= 1) s2 += __shfl_xor_sync(~0u, s2, o);
    const float m = bfr(s1 / D_), sd = bfr(sqrtf(bfr(bfr(s2 / D_) + 1e-5f)));
    for (int i = lane; i < D_; i += 32) {
        const float v = bfr(bfr(b2f(r[i]) - m) / sd);
        f_n[t * D_ + i] = __float2bfloat16(v);
        if (!in) { s3 += v * b2f(wr[i]); out[t * D_ + i] = __float2bfloat16(b2f(r[i]) + v); }
    }
    for (int o = 16; o; o >>= 1) s3 += __shfl_xor_sync(~0u, s3, o);
    f_r[t] = bfr(s3);
}
__global__ void fb_taps(Params p) {
    const int d = blockIdx.x >> 3, l = (blockIdx.x & 7) * 256 + threadIdx.x;
    const float dt = bfr(expf(bf_lo(p.logdt[d]))), lf = bfr((float)l);
    float k = 0.f;
    for (int n = d * 128; n < d * 128 + 128; n++) {
        float wr, wi, sn, cs;
        cmul(wr, wi, bf_lo(p.prm6[4][n]), bf_lo(p.prm6[5][n]), dt * bf_lo(p.prm6[2][n]), dt * bf_lo(p.prm6[3][n]));
        sincosf(dt * bf_lo(p.prm6[1][n]) * lf, &sn, &cs);
        k += expf(dt * bf_lo(p.prm6[0][n]) * lf) * (wr * cs - wi * sn);
    }
    f_k[l * D_ + d] = k;
}
__global__ void fb_conv(Params p) {
    const int t = blockIdx.x, d = threadIdx.x;
    float y = 0.f;
    for (int l = 0; l <= t; l++) y += f_k[l * D_ + d] * b2f(f_n[(t - l) * D_ + d]);
    f_h[t * D_ + d] = __float2bfloat16(bf_lo(p.x[t * D_ + d]) + bfr(bfr(y) + bfr(b2f(f_n[t * D_ + d]) * bf_lo(p.dskip[d]))));
}
__global__ void fb_top() {
    const int t = blockIdx.x * 256 + threadIdx.x;
    int rank = 0;
    for (int j = 0; j < L_; j++) rank += f_r[j] > f_r[t] || (f_r[j] == f_r[t] && j < t);
    if (rank < 8) f_idx[rank] = t;
}
__global__ void fb_ffn1(const bf16* wg, const bf16* wu) {
    const int f = blockIdx.x * 256 + threadIdx.x, j = blockIdx.y;
    float g = 0.f, u = 0.f;
    for (int i = 0; i < D_; i++) { const float v = b2f(f_n[f_idx[j] * D_ + i]); g += v * b2f(wg[i * F_ + f]); u += v * b2f(wu[i * F_ + f]); }
    g = bfr(g);
    f_gu[j * F_ + f] = bfr(bfr(g / (1.f + expf(-g))) * bfr(u));
}
__global__ void fb_ffn2(const bf16* wd, bf16* out) {
    const int d = threadIdx.x, j = blockIdx.x, t = f_idx[j];
    float y = 0.f;
    for (int f = 0; f < F_; f++) y += f_gu[j * F_ + f] * b2f(wd[f * D_ + d]);
    out[t * D_ + d] = __float2bfloat16(b2f(f_h[t * D_ + d]) + bfr(b2f(f_n[t * D_ + d]) + bfr(bfr(y) * bfr(1.f / (1.f + expf(-f_r[t]))))));
}

typedef CUresult (*EncodeFn)(CUtensorMap*, CUtensorMapDataType, cuuint32_t, void*, const cuuint64_t*, const cuuint64_t*,
                             const cuuint32_t*, const cuuint32_t*, CUtensorMapInterleave, CUtensorMapSwizzle,
                             CUtensorMapL2promotion, CUtensorMapFloatOOBfill);

void make_map(EncodeFn fn, CUtensorMap* tm, const void* p, int cols, int rows, int bc, int br) {
    cuuint64_t dims[2] = {(cuuint64_t)cols, (cuuint64_t)rows};
    cuuint64_t strides[1] = {(cuuint64_t)cols * 2};
    cuuint32_t box[2] = {(cuuint32_t)bc, (cuuint32_t)br};
    cuuint32_t es[2] = {1, 1};
    fn(tm, CU_TENSOR_MAP_DATA_TYPE_BFLOAT16, 2, const_cast<void*>(p), dims, strides, box, es, CU_TENSOR_MAP_INTERLEAVE_NONE,
       CU_TENSOR_MAP_SWIZZLE_NONE, CU_TENSOR_MAP_L2_PROMOTION_L2_128B, CU_TENSOR_MAP_FLOAT_OOB_FILL_NONE);
}

void make_map3(EncodeFn fn, CUtensorMap* tm, const void* p) {
    cuuint64_t dims[5] = {(cuuint64_t)D_, 64, 2, 4, 4};
    cuuint64_t strides[4] = {(cuuint64_t)D_ * 2, (cuuint64_t)D_ * 128, (cuuint64_t)D_ * 1024, (cuuint64_t)D_ * 256};
    cuuint32_t box[5] = {XW, 9, 2, 4, 4};
    cuuint32_t es[5] = {1, 1, 1, 1, 1};
    fn(tm, CU_TENSOR_MAP_DATA_TYPE_BFLOAT16, 5, const_cast<void*>(p), dims, strides, box, es, CU_TENSOR_MAP_INTERLEAVE_NONE,
       CU_TENSOR_MAP_SWIZZLE_NONE, CU_TENSOR_MAP_L2_PROMOTION_NONE, CU_TENSOR_MAP_FLOAT_OOB_FILL_NONE);
}

void make_map5(EncodeFn fn, CUtensorMap* tm, const void* p, int bc) {
    cuuint64_t dims[5] = {(cuuint64_t)D_, 2, 4, 4, 64};
    cuuint64_t strides[4] = {(cuuint64_t)D_ * 128, (cuuint64_t)D_ * 1024, (cuuint64_t)D_ * 256, (cuuint64_t)D_ * 2};
    cuuint32_t box[5] = {(cuuint32_t)bc, 2, 4, 4, 8};
    cuuint32_t es[5] = {1, 1, 1, 1, 1};
    fn(tm, CU_TENSOR_MAP_DATA_TYPE_BFLOAT16, 5, const_cast<void*>(p), dims, strides, box, es, CU_TENSOR_MAP_INTERLEAVE_NONE,
       CU_TENSOR_MAP_SWIZZLE_NONE, CU_TENSOR_MAP_L2_PROMOTION_NONE, CU_TENSOR_MAP_FLOAT_OOB_FILL_NONE);
}

}

extern "C" void kernel_launch(void* const* d_in, const int* in_sizes, int n_in, void* d_out, int out_size) {
    (void)in_sizes; (void)n_in; (void)out_size;
    void* fp = nullptr;
    cudaDriverEntryPointQueryResult qr;
    cudaGetDriverEntryPoint("cuTensorMapEncodeTiled", &fp, cudaEnableDefault, &qr);
    EncodeFn fn = (EncodeFn)fp;
    CUtensorMap tmG, tmU, tmD, tmO, tmX, tmH;
    make_map3(fn, &tmX, d_in[0]);
    make_map(fn, &tmG, d_in[11], F_, D_, 40, 48);
    make_map(fn, &tmU, d_in[12], F_, D_, 40, 48);
    make_map(fn, &tmD, d_in[13], D_, F_, 72, 64);
    make_map5(fn, &tmO, d_out, 32);
    make_map5(fn, &tmH, d_out, 8);
    Params p;
    p.x = (const unsigned short*)d_in[0];
    for (int i = 0; i < 6; i++) p.prm6[i] = (const unsigned short*)d_in[1 + i];
    p.logdt = (const unsigned short*)d_in[7]; p.dskip = (const unsigned short*)d_in[8];
    p.wr = (const unsigned short*)d_in[10];
    p.out = (__nv_bfloat16*)d_out;
    p.zero = 0;
    cudaGetSymbolAddress((void**)&p.gs, g_s);
    cudaFuncSetAttribute(fused_kernel, cudaFuncAttributeMaxDynamicSharedMemorySize, SM_TOTAL);
    static int nclusters = -1;
    if (nclusters < 0) {
        cudaLaunchConfig_t cfg = {};
        cudaLaunchAttribute at;
        at.id = cudaLaunchAttributeClusterDimension; at.val.clusterDim.x = CS; at.val.clusterDim.y = 1; at.val.clusterDim.z = 1;
        cfg.gridDim = dim3(NCTA); cfg.blockDim = dim3(NTHR); cfg.dynamicSmemBytes = SM_TOTAL; cfg.attrs = &at; cfg.numAttrs = 1;
        if (cudaOccupancyMaxActiveClusters(&nclusters, fused_kernel, &cfg) != cudaSuccess) { (void)cudaGetLastError(); nclusters = NCL; }
    }
    if (nclusters >= NCL && !FORCE_FALLBACK) {
        fused_kernel<<<NCTA, NTHR, SM_TOTAL>>>(p, tmG, tmU, tmD, tmO, tmX, tmH);
        return;
    }
    fb_ln<<<L_ / 8, 256>>>((const bf16*)d_in[0], nullptr, nullptr);
    fb_taps<<<D_ * 8, 256>>>(p);
    fb_conv<<<L_, D_>>>(p);
    fb_ln<<<L_ / 8, 256>>>(nullptr, (const bf16*)d_in[10], p.out);
    fb_top<<<L_ / 256, 256>>>();
    fb_ffn1<<<dim3(F_ / 256, 8), 256>>>((const bf16*)d_in[11], (const bf16*)d_in[12]);
    fb_ffn2<<<8, D_>>>((const bf16*)d_in[13], p.out);
}
```

```cpp
#include <cuda_runtime.h>
#include <cuda_bf16.h>
#include <cuda_fp16.h>
#include <cuda.h>
#include <stdint.h>

namespace {

constexpr int L_ = 2048, D_ = 576, F_ = 4608;
constexpr int NCL = 15, CS = 8, NCTA = NCL * CS, NTHR = 768;
#define FORCE_FALLBACK 0
constexpr int XW = 48, NRED = 2;
constexpr int SPIN_LIMIT = 1 << 22;

constexpr int SM_WG   = 0;
constexpr int SM_WU   = 46080;
constexpr int YP = 3392, YS = 656;
constexpr int UP = 3280, US = 656;
constexpr int SM_XT   = 92160;
constexpr int SM_U    = SM_XT + 8 * YP;
constexpr int SM_FAR  = SM_U + 8 * UP;
constexpr int FAR_SZ  = 12416;
constexpr int F_E5 = 0, F_O5 = 1536, F_E3 = 3088, F_O3 = 4624, F_E7 = 6176, F_E2 = F_E7 + 1024, F_E9 = F_E7 + 2048,
              F_H = 3088, F_O7 = F_E7 + F_H, F_O2 = F_E2 + F_H, F_O9 = F_E9 + F_H;
constexpr int SM_P    = SM_FAR + 5 * FAR_SZ;
constexpr int PN_SZ = 584 * 4, SM_PN = SM_P + 65 * 4;
constexpr int P_GS = 50 * 4, P_H7 = 200 * 4, P_HS = 74 * 4;
constexpr int PF_SZ = (200 + 222) * 4, SM_PF = SM_PN + 5 * PN_SZ + 36;
constexpr int SM_MISC = SM_PF + 5 * PF_SZ;
constexpr int SM_ST   = SM_MISC;
constexpr int SM_RK   = SM_ST + 2048;
constexpr int SM_SEL  = SM_RK + 256;
constexpr int SM_KG   = SM_SEL + 64;
constexpr int SM_SC   = SM_KG + 160;
constexpr int SM_DW   = SM_SC + 32;
constexpr int SM_MB   = SM_DW + 160;
constexpr int SM_TOTAL = SM_MB + 128;
constexpr int SM_ROW  = SM_XT - 20736;
constexpr int SM_XTL  = SM_ROW - 576 * XW;
constexpr int SM_RED2 = SM_WG;
constexpr int SM_HT   = SM_P - 512;
constexpr int SM_KEY  = SM_FAR + 10240 + 128;
constexpr int SM_CAND = SM_KEY + 1024;
constexpr int SM_XS   = SM_U;
constexpr int SM_GU   = SM_XS + 9344;
constexpr int SM_RED  = SM_GU + 5632;
static_assert(F_O9 + 1024 <= FAR_SZ && FAR_SZ % 128 == 0, "far overflow");
static_assert(SM_RED + 10240 <= SM_FAR && SM_HT + 20496 <= SM_MISC, "alias overflow");
static_assert(SM_TOTAL <= 232448, "smem overflow");
static_assert(SM_FAR % 128 == 0 && SM_XT % 128 == 0 && SM_XTL % 128 == 0 && SM_P % 16 == 0 && SM_MISC % 16 == 0 && SM_MB % 8 == 0, "align");

enum { MB_X = 0, MB_W1 = 5, MB_W2 = 6, MB_KEY = 7, MB_GU = 8, MB_Y = 9, MB_OUT = 10, MB_T = 11, MB_R = 12 };

struct __align__(128) Scratch {
    unsigned epoch, zcnt, pad[30];
    uint4  st1[L_ * 2];
    float4 acc[L_];
    uint4  cand[64 * NCL * 6];
    float4 fin[8 * 192 + 24];
};
__device__ Scratch g_s;
#define STAMP(i)

__device__ __forceinline__ uint32_t mapa(uint32_t a, uint32_t r) { uint32_t d; asm("mapa.shared::cluster.u32 %0, %1, %2;" : "=r"(d) : "r"(a), "r"(r)); return d; }
__device__ __forceinline__ void mbar_wait(uint32_t mb) {
    asm volatile("{ .reg .pred p, q; .reg .u32 n; mov.u32 n, 0;\n"
                 "W_%=: mbarrier.try_wait.parity.shared::cta.b64 p, [%0], 0; add.u32 n, n, 1; setp.lt.and.u32 q, n, 65536, !p; @q bra W_%=; }" :: "r"(mb) : "memory");
}
__device__ __forceinline__ void arm(uint32_t mb, uint32_t bytes) { asm volatile("mbarrier.arrive.expect_tx.shared::cta.b64 _, [%0], %1;" :: "r"(mb), "r"(bytes) : "memory"); }
__device__ __forceinline__ void bar_sync(int id, int n) { asm volatile("bar.sync %0, %1;" :: "r"(id), "r"(n) : "memory"); }
__device__ __forceinline__ void bar_arrive(int id, int n) { asm volatile("bar.arrive %0, %1;" :: "r"(id), "r"(n) : "memory"); }
__device__ __forceinline__ uint32_t lds16(uint32_t a) { unsigned short v; asm volatile("ld.shared.u16 %0, [%1];" : "=h"(v) : "r"(a) : "memory"); return v; }
__device__ __forceinline__ uint32_t lds32(uint32_t a) { uint32_t v; asm volatile("ld.shared.u32 %0, [%1];" : "=r"(v) : "r"(a) : "memory"); return v; }
__device__ __forceinline__ uint2 lds64(uint32_t a) { uint2 v; asm volatile("ld.shared.v2.u32 {%0,%1}, [%2];" : "=r"(v.x), "=r"(v.y) : "r"(a) : "memory"); return v; }
__device__ __forceinline__ float ldsf(uint32_t a) { float v; asm volatile("ld.shared.f32 %0, [%1];" : "=f"(v) : "r"(a) : "memory"); return v; }
__device__ __forceinline__ uint4 lds128(uint32_t a) { uint4 v; asm volatile("ld.shared.v4.u32 {%0,%1,%2,%3}, [%4];" : "=r"(v.x), "=r"(v.y), "=r"(v.z), "=r"(v.w) : "r"(a) : "memory"); return v; }
__device__ __forceinline__ float4 lds128f(uint32_t a) { float4 v; asm volatile("ld.shared.v4.f32 {%0,%1,%2,%3}, [%4];" : "=f"(v.x), "=f"(v.y), "=f"(v.z), "=f"(v.w) : "r"(a) : "memory"); return v; }
__device__ __forceinline__ void sts16(uint32_t a, uint32_t v) { asm volatile("{ .reg .b16 l, h; mov.b32 {l, h}, %1; st.shared.b16 [%0], l; }" :: "r"(a), "r"(v) : "memory"); }
__device__ __forceinline__ void sts32(uint32_t a, uint32_t v) { asm volatile("st.shared.u32 [%0], %1;" :: "r"(a), "r"(v) : "memory"); }
__device__ __forceinline__ void sts64(uint32_t a, uint32_t x, uint32_t y) { asm volatile("st.shared.v2.u32 [%0], {%1,%2};" :: "r"(a), "r"(x), "r"(y) : "memory"); }
__device__ __forceinline__ void stsf(uint32_t a, float v) { asm volatile("st.shared.f32 [%0], %1;" :: "r"(a), "f"(v) : "memory"); }
__device__ __forceinline__ void sts128(uint32_t a, uint32_t x, uint32_t y, uint32_t z, uint32_t w) { asm volatile("st.shared.v4.u32 [%0], {%1,%2,%3,%4};" :: "r"(a), "r"(x), "r"(y), "r"(z), "r"(w) : "memory"); }
__device__ __forceinline__ void sts128f(uint32_t a, float x, float y, float z, float w) { asm volatile("st.shared.v4.f32 [%0], {%1,%2,%3,%4};" :: "r"(a), "f"(x), "f"(y), "f"(z), "f"(w) : "memory"); }
__device__ __forceinline__ void ldsm4(uint32_t (&r)[4], uint32_t a) { asm volatile("ldmatrix.sync.aligned.m8n8.x4.shared.b16 {%0,%1,%2,%3}, [%4];" : "=r"(r[0]), "=r"(r[1]), "=r"(r[2]), "=r"(r[3]) : "r"(a) : "memory"); }
__device__ __forceinline__ void ldsm4t(uint32_t (&r)[4], uint32_t a) { asm volatile("ldmatrix.sync.aligned.m8n8.x4.trans.shared.b16 {%0,%1,%2,%3}, [%4];" : "=r"(r[0]), "=r"(r[1]), "=r"(r[2]), "=r"(r[3]) : "r"(a) : "memory"); }
__device__ __forceinline__ void ldsm2t(uint32_t& r0, uint32_t& r1, uint32_t a) { asm volatile("ldmatrix.sync.aligned.m8n8.x2.trans.shared.b16 {%0,%1}, [%2];" : "=r"(r0), "=r"(r1) : "r"(a) : "memory"); }
__device__ __forceinline__ void stsm4t(uint32_t a, uint32_t r0, uint32_t r1, uint32_t r2, uint32_t r3) { asm volatile("stmatrix.sync.aligned.m8n8.x4.trans.shared.b16 [%0], {%1,%2,%3,%4};" :: "r"(a), "r"(r0), "r"(r1), "r"(r2), "r"(r3) : "memory"); }
__device__ __forceinline__ void stsm4(uint32_t a, uint32_t r0, uint32_t r1, uint32_t r2, uint32_t r3) { asm volatile("stmatrix.sync.aligned.m8n8.x4.shared.b16 [%0], {%1,%2,%3,%4};" :: "r"(a), "r"(r0), "r"(r1), "r"(r2), "r"(r3) : "memory"); }
__device__ __forceinline__ void stsm2(uint32_t a, uint32_t r0, uint32_t r1) { asm volatile("stmatrix.sync.aligned.m8n8.x2.shared.b16 [%0], {%1,%2};" :: "r"(a), "r"(r0), "r"(r1) : "memory"); }
__device__ __forceinline__ void stsm2t(uint32_t a, uint32_t r0, uint32_t r1) { asm volatile("stmatrix.sync.aligned.m8n8.x2.trans.shared.b16 [%0], {%1,%2};" :: "r"(a), "r"(r0), "r"(r1) : "memory"); }
__device__ __forceinline__ uint4 ldg128(const void* p) { uint4 v; asm volatile("ld.global.nc.v4.u32 {%0,%1,%2,%3}, [%4];" : "=r"(v.x), "=r"(v.y), "=r"(v.z), "=r"(v.w) : "l"(p)); return v; }
__device__ __forceinline__ uint32_t ldg16(const void* p) { unsigned short v; asm volatile("ld.global.nc.u16 %0, [%1];" : "=h"(v) : "l"(p)); return v; }
__device__ __forceinline__ uint32_t opaque(uint32_t v) { uint32_t r; asm volatile("mov.b32 %0, %1;" : "=r"(r) : "r"(v)); return r; }
__device__ __forceinline__ void mma_f16(float (&d)[4], const uint32_t (&a)[4], uint32_t b0, uint32_t b1) {
    asm volatile("mma.sync.aligned.m16n8k16.row.col.f32.f16.f16.f32 {%0,%1,%2,%3}, {%4,%5,%6,%7}, {%8,%9}, {%0,%1,%2,%3};"
        : "+f"(d[0]), "+f"(d[1]), "+f"(d[2]), "+f"(d[3]) : "r"(a[0]), "r"(a[1]), "r"(a[2]), "r"(a[3]), "r"(b0), "r"(b1));
}
__device__ __forceinline__ void mma_f16_z(float (&d)[4], const uint32_t (&a)[4], uint32_t b0, uint32_t b1) {
    asm volatile("mma.sync.aligned.m16n8k16.row.col.f32.f16.f16.f32 {%0,%1,%2,%3}, {%4,%5,%6,%7}, {%8,%9}, {%10,%10,%10,%10};"
        : "=f"(d[0]), "=f"(d[1]), "=f"(d[2]), "=f"(d[3]) : "r"(a[0]), "r"(a[1]), "r"(a[2]), "r"(a[3]), "r"(b0), "r"(b1), "f"(0.f));
}
__device__ __forceinline__ void mma_bf16(float (&d)[4], uint32_t a0, uint32_t a1, uint32_t a2, uint32_t a3, uint32_t b0, uint32_t b1) {
    asm volatile("mma.sync.aligned.m16n8k16.row.col.f32.bf16.bf16.f32 {%0,%1,%2,%3}, {%4,%5,%6,%7}, {%8,%9}, {%0,%1,%2,%3};"
        : "+f"(d[0]), "+f"(d[1]), "+f"(d[2]), "+f"(d[3]) : "r"(a0), "r"(a1), "r"(a2), "r"(a3), "r"(b0), "r"(b1));
}
__device__ __forceinline__ void mma_bf16_k8(float (&d)[4], uint32_t a0, uint32_t a1, uint32_t b0) {
    asm volatile("mma.sync.aligned.m16n8k8.row.col.f32.bf16.bf16.f32 {%0,%1,%2,%3}, {%4,%5}, {%6}, {%0,%1,%2,%3};"
        : "+f"(d[0]), "+f"(d[1]), "+f"(d[2]), "+f"(d[3]) : "r"(a0), "r"(a1), "r"(b0));
}
__device__ __forceinline__ uint32_t pack_f16(float lo, float hi) { uint32_t r; asm("cvt.rn.f16x2.f32 %0, %1, %2;" : "=r"(r) : "f"(hi), "f"(lo)); return r; }
__device__ __forceinline__ uint32_t pack_bf16(float lo, float hi) { uint32_t r; asm("cvt.rn.bf16x2.f32 %0, %1, %2;" : "=r"(r) : "f"(hi), "f"(lo)); return r; }
__device__ __forceinline__ float bf_lo(uint32_t v) { return __uint_as_float(v << 16); }
__device__ __forceinline__ float bf_hi(uint32_t v) { return __uint_as_float(v & 0xFFFF0000u); }
__device__ __forceinline__ float bfr(float x) { return __uint_as_float(pack_bf16(0.f, x)); }
__device__ __forceinline__ uint32_t badd2(uint32_t a, uint32_t b) { uint32_t r; asm("add.rn.bf16x2 %0, %1, %2;" : "=r"(r) : "r"(a), "r"(b)); return r; }
__device__ __forceinline__ uint32_t bmul2(uint32_t a, uint32_t b) { uint32_t r; asm("mul.rn.bf16x2 %0, %1, %2;" : "=r"(r) : "r"(a), "r"(b)); return r; }
__device__ __forceinline__ uint32_t hadd2(uint32_t a, uint32_t b) { uint32_t r; asm("add.rn.f16x2 %0, %1, %2;" : "=r"(r) : "r"(a), "r"(b)); return r; }
__device__ __forceinline__ uint32_t hmul2(uint32_t a, uint32_t b) { uint32_t r; asm("mul.rn.f16x2 %0, %1, %2;" : "=r"(r) : "r"(a), "r"(b)); return r; }
__device__ __forceinline__ uint32_t hfma2(uint32_t a, uint32_t b, uint32_t c) { uint32_t r; asm("fma.rn.f16x2 %0, %1, %2, %3;" : "=r"(r) : "r"(a), "r"(b), "r"(c)); return r; }
__device__ __forceinline__ uint32_t hneg2(uint32_t a) { uint32_t r; asm("neg.f16x2 %0, %1;" : "=r"(r) : "r"(a)); return r; }
__device__ __forceinline__ float rcpf(float x) { float r; asm("rcp.approx.ftz.f32 %0, %1;" : "=f"(r) : "f"(x)); return r; }
__device__ __forceinline__ float sqrta(float x) { float r; asm("sqrt.approx.ftz.f32 %0, %1;" : "=f"(r) : "f"(x)); return r; }
__device__ __forceinline__ float ex2f(float x) { float r; asm("ex2.approx.ftz.f32 %0, %1;" : "=f"(r) : "f"(x)); return r; }
__device__ __forceinline__ void st_async4(uint32_t a, uint32_t x, uint32_t y, uint32_t z, uint32_t w, uint32_t mb) {
    asm volatile("st.async.shared::cluster.mbarrier::complete_tx::bytes.v4.u32 [%0], {%1,%2,%3,%4}, [%5];" :: "r"(a), "r"(x), "r"(y), "r"(z), "r"(w), "r"(mb) : "memory"); }
__device__ __forceinline__ void st_async1(uint32_t a, uint32_t x, uint32_t mb) {
    asm volatile("st.async.shared::cluster.mbarrier::complete_tx::bytes.u32 [%0], %1, [%2];" :: "r"(a), "r"(x), "r"(mb) : "memory"); }
__device__ __forceinline__ unsigned ld_rlx(const void* p) { unsigned v; asm volatile("ld.relaxed.gpu.global.u32 %0, [%1];" : "=r"(v) : "l"(p) : "memory"); return v; }
__device__ __forceinline__ unsigned ld_acq(const void* p) { unsigned v; asm volatile("ld.acquire.gpu.global.u32 %0, [%1];" : "=r"(v) : "l"(p) : "memory"); return v; }
__device__ __forceinline__ uint2 ld_rlx64(const void* p) { unsigned long long v; asm volatile("ld.relaxed.gpu.global.u64 %0, [%1];" : "=l"(v) : "l"(p) : "memory"); return make_uint2((unsigned)v, (unsigned)(v >> 32)); }
__device__ __forceinline__ void st_rlx128(void* p, uint32_t x, uint32_t y, uint32_t z, uint32_t w) {
    asm volatile("st.relaxed.gpu.global.v2.u64 [%0], {%1,%2};" :: "l"(p), "l"((unsigned long long)x | ((unsigned long long)y << 32)), "l"((unsigned long long)z | ((unsigned long long)w << 32)) : "memory"); }
__device__ __forceinline__ uint4 ld_rlx128(const void* p) { unsigned long long a, b; asm volatile("ld.relaxed.gpu.global.v2.u64 {%0,%1}, [%2];" : "=l"(a), "=l"(b) : "l"(p) : "memory"); return make_uint4((unsigned)a, (unsigned)(a >> 32), (unsigned)b, (unsigned)(b >> 32)); }
__device__ __forceinline__ void tma2d(uint32_t dst, const CUtensorMap* tm, int x, int y, uint32_t mb) {
    asm volatile("cp.async.bulk.tensor.2d.shared::cluster.global.mbarrier::complete_tx::bytes [%0], [%1, {%3, %4}], [%2];"
                 :: "r"(dst), "l"(tm), "r"(mb), "r"(x), "r"(y) : "memory");
}
__device__ __forceinline__ void cmul(float& xr, float& xi, float ar, float ai, float br, float bi) {
    const float r = fmaf(ar, br, -ai * bi), i = fmaf(ar, bi, ai * br); xr = r; xi = i;
}
__device__ __forceinline__ void csq(float& xr, float& xi, float ar, float ai) {
    const float r = fmaf(ar, ar, -ai * ai), i = (ar + ar) * ai; xr = r; xi = i;
}
__device__ __forceinline__ void cexp_s(float& zr, float& zi, float e2, float turns) {
    const float mag = ex2f(e2), r = (turns - rintf(turns)) * 6.283185307179586f;
    zr = mag * __cosf(r); zi = mag * __sinf(r);
}
__device__ __forceinline__ uint32_t ln_stats(float s1, float s2) {
    const float m = s1 * (1.f / D_);
    const float var = fmaxf(fmaf(s2, 1.f / D_, -m * m), 0.f);
    return pack_bf16(m, sqrta(bfr(bfr(var) + 1e-5f)));
}
__device__ __forceinline__ uint32_t rsplit(float rs) { const float h = bfr(rs); return pack_bf16(h, rs - h); }
__device__ __forceinline__ uint32_t norm2(uint32_t v, uint32_t mx, uint32_t hl) {
    uint32_t r;
    asm("{ .reg .b16 m, h, l, x; .reg .b32 m2, h2, l2, d, t; mov.b32 {m, x}, %2; mov.b32 {h, l}, %3; mov.b32 m2, {m, m}; mov.b32 h2, {h, h}; mov.b32 l2, {l, l};\n"
        "sub.rn.bf16x2 d, %1, m2; mul.rn.bf16x2 t, d, l2; fma.rn.bf16x2 %0, d, h2, t; }" : "=r"(r) : "r"(v), "r"(mx), "r"(hl));
    return r;
}
template <int N, int S>
__device__ __forceinline__ uint32_t rank4(uint32_t a, uint32_t key) {
    uint32_t r0 = 0, r1 = 0, r2 = 0, r3 = 0;
#pragma unroll
    for (int i = 0; i < N; i++) {
        const uint4 o = lds128(a + i * S);
        r0 += (key - o.x) >> 31; r1 += (key - o.y) >> 31; r2 += (key - o.z) >> 31; r3 += (key - o.w) >> 31;
    }
    return (r0 + r1) + (r2 + r3);
}
typedef uint32_t H2C;
__device__ __forceinline__ H2C splat(float r, float i) { return pack_f16(r, i); }
__device__ __forceinline__ void hcmul(uint32_t& xr, uint32_t& xi, uint32_t R, uint32_t I, H2C m) {
    asm("{ .reg .b16 a, b; .reg .b32 a2, b2, t; mov.b32 {a, b}, %4; mov.b32 a2, {a, a}; mov.b32 b2, {b, b};\n"
        "mul.rn.f16x2 t, %3, b2; neg.f16x2 t, t; fma.rn.f16x2 %0, %2, a2, t; mul.rn.f16x2 t, %3, a2; fma.rn.f16x2 %1, %2, b2, t; }"
        : "=&r"(xr), "=r"(xi) : "r"(R), "r"(I), "r"(m));
}
__device__ __forceinline__ void expand4(uint32_t are, uint32_t aim, uint32_t R0, uint32_t R1, uint32_t I0, uint32_t I1, H2C m4) {
    uint32_t R2, I2, R3, I3;
    hcmul(R2, I2, R0, I0, m4); hcmul(R3, I3, R1, I1, m4);
    sts128(are, R0, R1, R2, R3);
    sts128(aim, I0, I1, I2, I3);
}
__device__ __forceinline__ void expand8(uint32_t are, uint32_t aim, float sr, float si, float m1r, float m1i, float m2r, float m2i, H2C m4) {
    float r1, i1, r2, i2, r3, i3;
    cmul(r1, i1, sr, si, m1r, m1i); cmul(r2, i2, sr, si, m2r, m2i); cmul(r3, i3, r1, i1, m2r, m2i);
    expand4(are, aim, pack_f16(sr, r1), pack_f16(r2, r3), pack_f16(si, i1), pack_f16(i2, i3), m4);
}
__device__ __forceinline__ void put16(uint32_t a, uint32_t v) { sts16(a, v); sts16(a + 6, v); }

struct Params {
    const unsigned short *logdt, *dskip, *prm6[6], *x, *wr;
    __nv_bfloat16* out;
    Scratch* gs;
    unsigned zero;
};
__device__ __forceinline__ uint32_t tslot(uint32_t t) { return (t & 7) * 32 + ((t >> 4) & 24) + ((t >> 8) & 6) + ((t >> 6) & 1); }
#define CP(x) ((x) | zero)
#define ZF(x) ((x) & zero)
#define PIN(x) asm volatile("or.b32 %0, %0, %1;" : "+r"(x) : "r"(zero))
__device__ __forceinline__ void wgmma32(float (&d)[4][4], const uint32_t (&a)[4], unsigned long long ds) {
    asm volatile("wgmma.mma_async.sync.aligned.m64n32k16.f32.f16.f16 {%0,%1,%2,%3,%4,%5,%6,%7,%8,%9,%10,%11,%12,%13,%14,%15}, {%16,%17,%18,%19}, %20, 1, 1, 1, 0;"
        : "+f"(d[0][0]), "+f"(d[0][1]), "+f"(d[0][2]), "+f"(d[0][3]), "+f"(d[1][0]), "+f"(d[1][1]), "+f"(d[1][2]), "+f"(d[1][3]),
          "+f"(d[2][0]), "+f"(d[2][1]), "+f"(d[2][2]), "+f"(d[2][3]), "+f"(d[3][0]), "+f"(d[3][1]), "+f"(d[3][2]), "+f"(d[3][3])
        : "r"(a[0]), "r"(a[1]), "r"(a[2]), "r"(a[3]), "l"(ds));
}

__device__ __forceinline__ void finish(const Params& prm, uint32_t fo, uint32_t oo, const float (&v)[3], float cnt) {
    float x, y, z, w;
    asm volatile("atom.relaxed.gpu.global.add.v4.f32 {%0,%1,%2,%3}, [%4], {%5,%6,%7,%8};" : "=f"(x), "=f"(y), "=f"(z), "=f"(w)
                 : "l"((char*)prm.gs->fin + fo), "f"(v[0]), "f"(v[1]), "f"(v[2]), "f"(cnt) : "memory");
    if (w + cnt == 3.f * (NCL + 1)) {
        __nv_bfloat16* op = (__nv_bfloat16*)((char*)prm.out + oo);
        op[0] = __float2bfloat16(x + v[0]); op[1] = __float2bfloat16(y + v[1]); op[2] = __float2bfloat16(z + v[2]);
    }
}

__global__ void __cluster_dims__(CS, 1, 1) __launch_bounds__(NTHR, 1)
fused_kernel(const __grid_constant__ Params prm, const __grid_constant__ CUtensorMap tmG, const __grid_constant__ CUtensorMap tmU,
             const __grid_constant__ CUtensorMap tmD, const __grid_constant__ CUtensorMap tmO, const __grid_constant__ CUtensorMap tmX, const __grid_constant__ CUtensorMap tmH)
{
    extern __shared__ __align__(1024) unsigned char smem[];
    const int tid = threadIdx.x, lane = tid & 31, warp = __shfl_sync(~0u, tid >> 5, 0);
    const int c = blockIdx.x >> 3, q = blockIdx.x & 7;
    const int nslot = (c < NCL - 1) ? 5 : 2;
    const int d0 = 40 * c;
    const uint32_t sb = opaque((uint32_t)__cvta_generic_to_shared(smem));
    const uint32_t mb = sb + SM_MB;
    Scratch& g_s = *prm.gs;
    const unsigned& zero = prm.zero;
    STAMP(0);

    if (warp >= 20) {
        unsigned epoch = 0;
        if (warp == 20) {
            if (lane == 0) {
#pragma unroll
                for (int i = 0; i < 13; i++)
                    asm volatile("mbarrier.init.shared::cta.b64 [%0], %1;" :: "r"(mb + i * 8), "r"((i == MB_R || i < 2) ? 2 : i < 5 ? (nslot + 1) / 3 : i == MB_Y ? 1 + 4 * nslot : 1) : "memory");
                asm volatile("fence.mbarrier_init.release.cluster;" ::: "memory");
                arm(mb + MB_W1 * 8, 92160); arm(mb + MB_W2 * 8, nslot * 9216); arm(mb + MB_KEY * 8, 256); arm(mb + MB_GU * 8, nslot * 1024); arm(mb + MB_T * 8, 576 * XW);
                const int bytes = max(min(18, L_ - 18 * (int)blockIdx.x), 1) * (D_ * 2);
                arm(mb + MB_R * 8, bytes);
            }
            __syncwarp();
        } else if (warp == 22) {
            epoch = ld_rlx(&g_s.epoch);
            if (lane < 18 ? 18 * c + lane < 256 : lane < 31) (lane < 18 ? &g_s.acc[256 * q + 18 * c] : &g_s.fin[13 * (int)blockIdx.x - 18])[lane] = make_float4(0.f, 0.f, 0.f, 0.f);
        } else if (warp == 23 && lane == 0) asm volatile("prefetch.tensormap [%0];" :: "l"(&tmX) : "memory");
        asm volatile("barrier.cluster.arrive.relaxed.aligned;" ::: "memory");
        bar_sync(12, NTHR);
        uint4 wv = make_uint4(0, 0, 0, 0), wv2, wv3;
        if (warp == 22) {
            if (lane == 0) { sts32(sb + SM_SC + 28, epoch); asm volatile("mbarrier.arrive.shared::cta.b64 _, [%0];" :: "r"(mb + MB_R * 8) : "memory"); }
            epoch++;
            asm volatile("fence.acq_rel.gpu;" ::: "memory");
            __syncwarp();
            if (lane == 0) asm volatile("red.relaxed.gpu.global.add.u32 [%0], 1;" :: "l"(&g_s.zcnt) : "memory");
            STAMP(1);
            wv2 = ldg128((const uint4*)prm.wr + lane); wv3 = ldg128((const uint4*)prm.wr + 32 + lane);
            if (lane < 8) wv = ldg128((const uint4*)prm.wr + 64 + lane);
            if (lane < 5) {
                uint4 v = make_uint4(0, 0, 0, 0);
                if (lane < nslot) v = ldg128((const uint4*)(prm.wr + d0) + lane);
                sts128(sb + SM_DW + lane * 16, v.x, v.y, v.z, v.w);
            }
            __syncwarp();
            if (lane < 5) asm volatile("mbarrier.arrive.shared::cta.b64 _, [%0];" :: "r"(mb + (MB_X + lane) * 8) : "memory");
        }
        if (warp == 21) {
            if (lane == 0) { asm volatile("prefetch.tensormap [%0];" :: "l"(&tmG) : "memory"); asm volatile("prefetch.tensormap [%0];" :: "l"(&tmU) : "memory"); asm volatile("prefetch.tensormap [%0];" :: "l"(&tmD) : "memory"); }
            __syncwarp();
            bar_sync(15, 672);
            asm volatile("fence.proxy.async.shared::cta;" ::: "memory");
#pragma unroll 1
            for (int i = 0; i < 24; i++) {
                if (lane == 0) tma2d(sb + SM_WG + i * 3840, i < 12 ? &tmG : &tmU, 320 * c + 8 * nslot * q, 48 * (i < 12 ? i : i - 12), mb + MB_W1 * 8);
            }
            STAMP(1);
        } else {
        if (warp == 20) {
            if (lane == 0) {
                asm volatile("cp.async.bulk.shared::cluster.global.mbarrier::complete_tx::bytes [%0], [%1], %2, [%3];"
                             :: "r"(sb + SM_ROW), "l"(prm.x + min(18 * (int)blockIdx.x, L_ - 1) * D_), "r"(max(min(18, L_ - 18 * (int)blockIdx.x), 1) * (D_ * 2)), "r"(mb + MB_R * 8) : "memory");
            }
            __syncwarp();
            mbar_wait(mb + MB_R * 8);
            if (lane == 0) {
                asm volatile("cp.async.bulk.tensor.5d.shared::cluster.global.mbarrier::complete_tx::bytes [%0], [%1, {%3, %4, %5, %5, %5}], [%2];"
                             :: "r"(sb + SM_XTL), "l"(&tmX), "r"(mb + MB_T * 8), "r"(d0 & ~15), "r"(8 * q), "r"(0) : "memory");
            }
            STAMP(6);
        }
        {
            const int idx = lane * 3 + max(warp - 21, 0), sl = nslot - 1 - (idx >> 3), pe = (idx + q + 1) & 7;
            const uint32_t rb_ = mapa(sb, pe);
            uint32_t cd = rb_ + SM_U + 128 + q * UP + sl * US, cs = sb + SM_XT + 128 + (q & 3) * 16 + pe * YP + sl * YS, cm = rb_ + SM_MB + (MB_X + sl) * 8;
            int act = sl < 0 ? 0 : pe == q ? -1 : 1;
            PIN(cd); PIN(cs); PIN(cm); PIN(act);
            asm volatile("barrier.cluster.wait.aligned;" ::: "memory");
            mbar_wait(mb + MB_R * 8);
            bar_sync(13, 608);
            asm volatile("fence.proxy.async.shared::cta;" ::: "memory");
            if (act < 0) arm(cm, 7 * 512);
            __syncwarp();
            if (act > 0)
                asm volatile("cp.async.bulk.shared::cluster.shared::cta.mbarrier::complete_tx::bytes [%0], [%1], 512, [%2];" :: "r"(cd), "r"(cs), "r"(cm) : "memory");
        }
        STAMP(1);
        if (warp == 20 && lane == 0) { asm volatile("prefetch.tensormap [%0];" :: "l"(&tmO) : "memory"); asm volatile("prefetch.tensormap [%0];" :: "l"(&tmH) : "memory"); }
        if (warp == 22) {
            __syncwarp();
            mbar_wait(mb + (MB_X + 1) * 8);
            const uint32_t old = (epoch & 1) ? 0u : 0x40004000u;
#pragma unroll
            for (int t = 0; t < 2; t++)
                if ((lane & 7) < 6) g_s.cand[((q * 8 + 4 * t + (lane >> 3)) * NCL + c) * 6 + (lane & 7)] = make_uint4(old, old, old, old);
            float a[4] = {0.f, 0.f, 0.f, 0.f};
            const uint32_t one = 0x3F803F80u;
            mma_bf16(a, one, one, one, one, wv.x, wv.y);  mma_bf16(a, one, one, one, one, wv.z, wv.w);
            mma_bf16(a, one, one, one, one, wv2.x, wv2.y); mma_bf16(a, one, one, one, one, wv2.z, wv2.w);
            mma_bf16(a, one, one, one, one, wv3.x, wv3.y); mma_bf16(a, one, one, one, one, wv3.z, wv3.w);
            float s = a[0] + a[1];
            s += __shfl_xor_sync(~0u, s, 1); s += __shfl_xor_sync(~0u, s, 2);
            stsf(sb + SM_SC + 24, s);
            __syncwarp();
            if (lane == 0) {
                int n = 0;
                while ((int)(ld_acq(&g_s.zcnt) - epoch * NCTA) < 0 && ++n < SPIN_LIMIT) __nanosleep(200);
                arm(mb + MB_Y * 8, 8 * 512 * nslot);
                if (blockIdx.x == 0) g_s.epoch = epoch;
            }
            STAMP(2);
        }
        if (warp == 23) {
#pragma unroll 1
            for (int kk = nslot - 1; kk >= 0; kk--) {
                __syncwarp();
                bar_sync(6 + kk, 160);
                if (lane == 0) { asm volatile("fence.proxy.async.shared::cta;" ::: "memory"); tma2d(sb + SM_FAR + kk * FAR_SZ, &tmD, 72 * q, 320 * c + 64 * kk, mb + MB_W2 * 8); }
            }
        }
        }
        __syncwarp();
        bar_sync(14, 768);
        if (tid == 640) {
            asm volatile("fence.proxy.async.shared::cta;" ::: "memory");
            asm volatile("cp.async.bulk.tensor.5d.global.shared::cta.bulk_group [%0, {%2, %4, %4, %4, %3}], [%1];" :: "l"(&tmH), "r"(sb + SM_XT + 16384), "r"(d0 + ((c & 1) ? 0 : 32)), "r"(8 * q), "r"(0) : "memory");
            asm volatile("cp.async.bulk.tensor.5d.global.shared::cta.bulk_group [%0, {%2, %4, %4, %4, %3}], [%1];" :: "l"(&tmO), "r"(sb + SM_XT), "r"(d0 + (c & 1) * 8), "r"(8 * q), "r"(0) : "memory");
            asm volatile("cp.async.bulk.commit_group;" ::: "memory");
        }
        __syncwarp();
        const uint32_t ft = (tid >> 4) & 7, fj = d0 / 3 + (lane & 15), tok = ~lds32(sb + SM_SEL + ft * 8) & 2047;
        float v[3], cnt = 0.f;
#pragma unroll
        for (int i = 0; i < 3; i++) {
            const uint32_t cl = 3 * fj + i - d0, cf = cl - (c & 1) * 8;
            const bool ok = cl < 8 * nslot && ((tok >> 3) & 7) == q;
            const uint32_t u = lds16(sb + SM_XT + (cf < 32 ? tslot(tok) * 64 + cf * 2 : 16384 + tslot(tok) * 16 + (cl & 7) * 2));
            v[i] = ok ? __uint_as_float(u << 16) : 0.f;
            if (ok) cnt += 1.f;
        }
        if (tid == 640) {
            asm volatile("cp.async.bulk.wait_group 0;" ::: "memory");
            asm volatile("fence.proxy.async.global;" ::: "memory");
            asm volatile("mbarrier.arrive.shared::cta.b64 _, [%0];" :: "r"(mb + MB_OUT * 8) : "memory");
        }
        __syncwarp();
        mbar_wait(mb + MB_OUT * 8);
        STAMP(5);
        if (cnt != 0.f) finish(prm, (ft * 192 + fj) * 16, (tok * D_ + 3 * fj) * 2, v, cnt);
        return;
    }

    const int g = lane >> 2, cq = lane & 3;
    const int k = warp >> 2, wq = warp & 3;
    const int trow = 18 * blockIdx.x + warp;
    const bool rowact = warp < 18 && trow < L_;
    const int dch = min(d0 + 8 * k + q, D_ - 1);
    uint32_t pv[6];
    const uint32_t pofs = opaque((dch * 128 + wq * 32 + lane) * 2);
#pragma unroll
    for (int i = 0; i < 6; i++) pv[i] = ldg16((const char*)prm.prm6[i] + pofs);
    const uint32_t pLdt = ldg16(prm.logdt + dch), pD = ldg16(prm.dskip + dch);
    const int tn = 16 * (warp & 15) + g;
    uint32_t xa[5], xb[5];
    asm volatile("barrier.cluster.arrive.relaxed.aligned;" ::: "memory");
    uint4* const st1p = &g_s.st1[(((trow >> 3) & 7) * 256 + ((trow >> 6) & 31) * 8 + (trow & 7)) * 2 + (lane >> 2)];
    const bool pub = rowact && (lane & 0x1B) == 0;
    if (pub) st_rlx128(st1p, 0, 0, 0, 0);
    {
        const uint32_t za = sb + SM_P + tid * 16;
        sts128(za, 0, 0, 0, 0);
        if (tid < (SM_MISC - SM_P) / 16 - 640) sts128(za + 10240, 0, 0, 0, 0);
        sts128(sb + SM_U + ((tid >> 3) & 7) * UP + k * US + (lane & 7) * 16, 0, 0, 0, 0);
    }
    bar_sync(12, NTHR);
    const uint32_t dep = lds32(sb + SM_P);
#define PV(x) __uint_as_float(__byte_perm(dep, x, 0x5410))
    STAMP(1);
    const uint32_t fb = sb + SM_FAR + k * FAR_SZ;
    const uint32_t pn = sb + SM_PN + k * PN_SZ, pf = sb + SM_PF + k * PF_SZ;
    unsigned epoch, t258;
    {
        const uint32_t kb = fb + wq * 3072;
        const uint32_t kl = kb + lane * 16;
        uint32_t Af[4][4];
        float sr, si, z1r, z1i, z2r, z2i, z4r, z4i, hr, hi_;
        {
            const float dt = bfr(ex2f(PV(pLdt) * 1.4426950408889634f));
            const float e2 = dt * PV(pv[0]) * 1.4426950408889634f, an = dt * PV(pv[1]);
            float ar, ai, br, bi, cr, ci, dr, di;
            { const float m = ex2f(e2 * 8.f); ar = m * __cosf(an * 8.f); ai = m * __sinf(an * 8.f); }
            csq(br, bi, ar, ai); csq(cr, ci, br, bi); csq(dr, di, cr, ci);
            const H2C m4 = splat(cr, ci);
            {
                float r3, i3;
                cmul(r3, i3, ar, ai, br, bi);
                expand4(kl, kl + 1024, pack_f16(1.f, ar), pack_f16(br, r3), pack_f16(0.f, ai), pack_f16(bi, i3), m4);
            }
            expand8(kl + 512, kl + 1536, dr, di, ar, ai, br, bi, m4);
            { const float m = ex2f(e2); z1r = m * __cosf(an); z1i = -m * __sinf(an); }
            cexp_s(hr, hi_, e2 * 128.f, an * (-128.f * 0.15915494309189535f));
            csq(z2r, z2i, z1r, z1i); csq(z4r, z4i, z2r, z2i);
            const uint32_t dep2 = lds32(sb + SM_P + 4);
#define PW(x) __uint_as_float(__byte_perm(dep2, x, 0x5410))
            cmul(sr, si, PW(pv[4]), PW(pv[5]), dt * PW(pv[2]), dt * PW(pv[3]));
            const unsigned E = min(max(__reduce_max_sync(~0u, __float_as_uint(fmaxf(fmaxf(fabsf(sr), fabsf(si)), fabsf(PW(pD)) * (1.f / 8192.f)))) >> 23, 1u), 253u);
            const float sc = __uint_as_float((254u - E) << 23);
            sr *= sc; si *= -sc;
            sts64(sb + SM_KG + warp * 8, E, __reduce_add_sync(~0u, __float2int_rn(sr * 16777216.f)));
            stsf(sb + SM_DW + 96 + k * 4, PW(pD));
        }
        __syncwarp();
#pragma unroll
        for (int ks = 0; ks < 4; ks++) ldsm4t(Af[ks], kb + (lane >> 3) * 512 + (lane & 7) * 16 + ks * 128);
        STAMP(2);
        const uint32_t la = kb + ((lane >> 3) & 1) * 512 + (lane >> 4) * 128 + (lane & 7) * 16;
        uint32_t b0[4], b1[4], b2[4], b3[4];
        auto ln1 = [&]() {
        mbar_wait(mb + MB_R * 8);
        epoch = lds32(sb + SM_SC + 28) + 1;
        {
            const uint32_t ra = sb + SM_ROW + warp * (D_ * 2);
            const uint4 r0 = lds128(ra + lane * 16), r1 = lds128(ra + 512 + lane * 16);
            const uint32_t rx[9] = {r0.x, r0.y, r0.z, r0.w, r1.x, r1.y, r1.z, r1.w, lds32(ra + 1024 + lane * 4)};
            float a0 = bf_lo(rx[0]), a1 = bf_hi(rx[0]), c0 = a0 * a0, c1 = a1 * a1;
#pragma unroll
            for (int i = 1; i < 9; i++) { const float l = bf_lo(rx[i]), h = bf_hi(rx[i]); a0 += l; a1 += h; c0 = fmaf(l, l, c0); c1 = fmaf(h, h, c1); }
            a0 += a1; c0 += c1;
            float s1 = ((lane & 1) ? c0 : a0) + __shfl_xor_sync(~0u, (lane & 1) ? a0 : c0, 1);
#pragma unroll
            for (int o = 2; o < 32; o <<= 1) s1 += __shfl_xor_sync(~0u, s1, o);
            const float s2 = __shfl_xor_sync(~0u, s1, 1);
            const uint32_t ms = ln_stats(s1, s2);
            const uint32_t p0 = __byte_perm(ms, epoch | 0x8000u, 0x5410), p1 = rsplit(rcpf(bf_hi(ms)));
            if (pub) st_rlx128(st1p, p0, p1, p0, p1);
        }
        mbar_wait(mb + MB_R * 8);
        STAMP(1);
        };
        const uint4* sp = &g_s.st1[(256 * q + tn) * 2];
        uint2 sa, sc;
        auto poll = [&]() { sa = ld_rlx64(sp); sc = ld_rlx64(sp + 16); };
        auto norm = [&]() {
        STAMP(3);
        if (warp < 16) {
            uint32_t va[5], vc[5];
            poll();
            mbar_wait(mb + MB_T * 8);
            {
                const uint32_t xt = sb + SM_XTL + (c & 1) * 16 + (36 * (warp & 7) + 9 * (warp >> 3) + g) * (2 * XW);
                uint4 a4 = lds128(xt + cq * 16), b4 = lds128(xt + cq * 16 + 36 * XW);
                va[0] = a4.x; va[1] = a4.y; va[2] = a4.z; va[3] = a4.w; va[4] = lds32(xt + 64 + cq * 4);
                vc[0] = b4.x; vc[1] = b4.y; vc[2] = b4.z; vc[3] = b4.w; vc[4] = lds32(xt + (64 + 36 * XW) + cq * 4);
            }
            const int d4 = 2 * (lane >> 3) + (lane & 1), d1_ = lane & 7;
            const uint32_t own = SM_U + 128 + q * (UP - YP), oth = SM_XT + 128 + (q & 3) * 16;
            uint32_t a4 = sb + warp * 32 + d4 * YP + (d4 == q ? own : oth) + ((lane & 7) >> 1) * YS;
            uint32_t a1 = sb + warp * 32 + d1_ * YP + (d1_ == q ? own : oth) + 4 * YS + (lane & 8) * 2;
            PIN(a4); PIN(a1);
            uint32_t tag = __byte_perm(epoch | 0x8000u, 0, 0x1010);
            PIN(tag);
            mbar_wait(mb + MB_T * 8);
            int n = 0;
            while (__byte_perm(sa.x, sc.x, 0x7632) != tag && ++n < SPIN_LIMIT) poll();
            STAMP(4);
#pragma unroll
            for (int i = 0; i < 5; i++) {
                va[i] = norm2(va[i], sa.x, sa.y); va[i] = pack_f16(bf_lo(va[i]), bf_hi(va[i]));
                vc[i] = norm2(vc[i], sc.x, sc.y); vc[i] = pack_f16(bf_lo(vc[i]), bf_hi(vc[i]));
            }
            stsm4t(a4, va[0], va[1], va[2], va[3]); stsm4t(a4 + 16, vc[0], vc[1], vc[2], vc[3]); stsm2t(a1, va[4], vc[4]);
            bar_arrive(13, 608);
            {
            const uint32_t xh = sb + SM_XTL + (c & 1) * 16 + (9 * __byte_perm(0x12100200, 0x13110301, g) + 72 * (warp & 1) + (warp >> 1)) * (2 * XW);
            const uint4 c4 = lds128(xh + cq * 16), d4_ = lds128(xh + cq * 16 + 72 * XW);
            xa[0] = c4.x; xa[1] = c4.y; xa[2] = c4.z; xa[3] = c4.w; xa[4] = lds32(xh + 64 + cq * 4);
            xb[0] = d4_.x; xb[1] = d4_.y; xb[2] = d4_.z; xb[3] = d4_.w; xb[4] = lds32(xh + (64 + 72 * XW) + cq * 4);
            }
        }
        STAMP(5);
        __syncwarp();
        bar_sync(15, 672);
        Af[0][0] |= lds32(sb + SM_P);
        };
        cmul(sr, si, sr, si, z1r, z1i);
        {
            const H2C h4 = splat(z4r, z4i);
            expand8(kl, kl + 512, sr, si, z1r, z1i, z2r, z2i, h4);
            cmul(sr, si, sr, si, hr, hi_);
            expand8(kl + 1024, kl + 1536, sr, si, z1r, z1i, z2r, z2i, h4);
        }
        __syncwarp();
        ldsm4t(b0, la); ldsm4t(b1, la + 256); ldsm4t(b2, la + 1024); ldsm4t(b3, la + 1280);
        cmul(z1r, z1i, z1r, z1i, hr, hi_);
        cmul(sr, si, sr, si, z1r, z1i);
        expand8(kl, kl + 512, sr, si, z2r, z2i, z4r, z4i, splat(hr, hi_));
        asm volatile("barrier.cluster.wait.aligned;" ::: "memory");
        ln1();
        csq(z1r, z1i, z1r, z1i);
        cmul(sr, si, sr, si, z1r, z1i);
        csq(z2r, z2i, hr, hi_);
        expand8(kl + 1024, kl + 1536, sr, si, z4r, z4i, hr, hi_, splat(z2r, z2i));
        csq(z1r, z1i, z1r, z1i);
        cmul(sr, si, sr, si, z1r, z1i);
        csq(z4r, z4i, z2r, z2i);
        expand8(kl + 2048, kl + 2560, sr, si, hr, hi_, z2r, z2i, splat(z4r, z4i));
        norm();
        {
            uint32_t c0[4], c1[4], c2[4], c3[4], e0[4], e1[4];
            float t[6][4];
            ldsm4t(c0, la); ldsm4t(c2, la + 1024);
            mma_f16_z(t[0], Af[0], b0[0], b0[1]);
            const uint32_t lb = la | (__float_as_uint(t[0][0]) & zero);
            mma_f16_z(t[1], Af[0], b2[0], b2[1]); mma_f16_z(t[2], Af[0], c0[0], c0[1]); mma_f16_z(t[3], Af[0], c2[0], c2[1]);
            ldsm4t(e0, lb + 2048); ldsm4t(c1, lb + 256); ldsm4t(c3, lb + 1280); ldsm4t(e1, lb + 2304);
            mma_f16(t[0], Af[1], b0[2], b0[3]); mma_f16(t[1], Af[1], b2[2], b2[3]); mma_f16(t[2], Af[1], c0[2], c0[3]); mma_f16(t[3], Af[1], c2[2], c2[3]);
            mma_f16(t[0], Af[2], b1[0], b1[1]); mma_f16(t[1], Af[2], b3[0], b3[1]);
            mma_f16_z(t[4], Af[0], e0[0], e0[1]); mma_f16_z(t[5], Af[1], e0[2], e0[3]);
            mma_f16(t[2], Af[2], c1[0], c1[1]); mma_f16(t[3], Af[2], c3[0], c3[1]);
            mma_f16(t[4], Af[2], e1[0], e1[1]); mma_f16(t[5], Af[3], e1[2], e1[3]);
            mma_f16(t[0], Af[3], b1[2], b1[3]); mma_f16(t[1], Af[3], b3[2], b3[3]); mma_f16(t[2], Af[3], c1[2], c1[3]); mma_f16(t[3], Af[3], c3[2], c3[3]);
            stsm4(kl + 1024, pack_f16(t[0][0], t[0][1]), pack_f16(t[0][2], t[0][3]), pack_f16(t[1][0], t[1][1]), pack_f16(t[1][2], t[1][3]));
            stsm2(kl + 1536, pack_f16(t[2][0], t[2][1]), pack_f16(t[2][2], t[2][3]));
            sts64(kb + lane * 8 + 1792, pack_f16(t[3][1], t[3][0]), pack_f16(t[3][3], t[3][2]));
            sts64(kb + lane * 8 + 2048, pack_f16(t[4][1] + t[5][1], t[4][0] + t[5][0]), pack_f16(t[4][3] + t[5][3], t[4][2] + t[5][2]));
        }
        bar_sync(1 + k, 128);
        const uint4 m01 = lds128(sb + SM_KG + k * 32), m23 = lds128(sb + SM_KG + k * 32 + 16);
        const unsigned Em = max(max(m01.x, m01.z), max(m23.x, m23.z));
        const float f0 = __uint_as_float(max((int)(127 + m01.x - Em), 0) << 23), f1 = __uint_as_float(max((int)(127 + m01.z - Em), 0) << 23),
                    f2 = __uint_as_float(max((int)(127 + m23.x - Em), 0) << 23), f3 = __uint_as_float(max((int)(127 + m23.z - Em), 0) << 23);
        const uint32_t r0 = pack_f16(f0, f0), r1 = pack_f16(f1, f1), r2 = pack_f16(f2, f2), r3 = pack_f16(f3, f3);
        const int tq = (wq + k + 2) & 3;
        const uint32_t ra = lane * 8 + opaque(fb + (tq == 1 ? 2048 : tq * 256 + 1024));
        auto comb = [&](uint32_t a, uint32_t& x, uint32_t& y) {
            const uint2 p0 = lds64(a), p1 = lds64(a + 3072), p2 = lds64(a + 6144), p3 = lds64(a + 9216);
            x = hadd2(hfma2(p0.x, r0, hmul2(p1.x, r1)), hfma2(p2.x, r2, hmul2(p3.x, r3)));
            y = hadd2(hfma2(p0.y, r0, hmul2(p1.y, r1)), hfma2(p2.y, r2, hmul2(p3.y, r3)));
        };
        uint32_t w0, w1;
        comb(ra, w0, w1);
        const bool last = lane == 31;
        if (tq == 0) {
            uint32_t v0, v1;
            comb(ra + 256, v0, v1);
            const uint32_t n0 = __shfl_sync(~0u, lane ? w0 : v0, lane + 1);
            uint32_t n1 = __shfl_sync(~0u, v0, lane + 1);
            if (last) n1 = v1 >> 16;
            sts128(pn + 12 + lane * 16, __byte_perm(w1, w0, 0x7610), __byte_perm(w1, 0, 0x1032), __byte_perm(n0, w1, 0x7610), __byte_perm(n0, 0, 0x1032));
            sts128(pn + 524 + lane * 16, __byte_perm(v1, v0, 0x7610), __byte_perm(v1, 0, 0x1032), __byte_perm(n1, v1, 0x7610), __byte_perm(n1, 0, 0x1032));
            if (lane == 0) {
                sts32(sb + SM_SC + k * 4, Em * 0x00800080u);
                const uint32_t t0 = pack_f16(((float)(int)m01.y * f0 + (float)(int)m01.w * f1 + (float)(int)m23.y * f2 + (float)(int)m23.w * f3) * (1.f / 16777216.f)
                                         + ldsf(sb + SM_DW + 96 + k * 4) * __uint_as_float((254u - Em) << 23), 0.f);
                sts128(pn - 4, 0, t0, __byte_perm(w0, t0, 0x5410), __byte_perm(w0, 0, 0x1032));
            }
        } else if (tq == 1) {
            const uint32_t ph = pf + P_H7 + (g & 1) * (2 * P_HS) + cq * 64 + (g >> 1) * 4 + (cq & 2) * 16, sw = (cq & 2) ? 0x3210 : 0x1032;
            w0 = __byte_perm(hmul2(w0, 0x18001800u), 0, sw); w1 = __byte_perm(hmul2(w1, 0x18001800u), 0, sw);
            const uint32_t pi = ph + 32 - (cq & 2) * 32;
            put16(ph, w0); put16(pi, w0 >> 16); put16(ph + 16, w1); put16(pi + 16, w1 >> 16);
        } else if (tq == 2) {
            uint32_t n = __shfl_sync(~0u, w0, lane == 30 ? 1 : lane + 2);
            if (last) { put16(pf, hmul2(w1, 0x18001800u) >> 16); w1 = hadd2(w1, hneg2(__byte_perm(w1, 0, 0x3232))); n = 0; }
            const bool od = lane & 1;
            const uint32_t pa = pn + 1036 + (lane >> 1) * 32 + (od ? 528 : 0), pb = pa + (od ? -16 : 16);
            const uint32_t u0 = od ? w1 : w0, x0 = od ? n : w1, u1 = od ? w0 : w1, x1 = od ? w1 : n;
            const uint32_t b0 = __byte_perm(u0, 0, 0x3232), b1 = __byte_perm(u1, 0, 0x3232);
            sts128(pa, __byte_perm(u0, 0, 0x1032), b0, b0, __byte_perm(x0, u0, 0x7610));
            sts128(pb, __byte_perm(u1, 0, 0x1032), b1, b1, __byte_perm(x1, u1, 0x7610));
        } else {
            const uint32_t pa = pf + ((g & 1) ? 3 * P_GS : P_GS) + cq * 32 + (g >> 1) * 4;
            const uint32_t pb = pa + ((g & 1) ? 4 - 3 * P_GS : P_GS);
            w0 = hmul2(w0, 0x18001800u); w1 = hmul2(w1, 0x18001800u);
            put16(pa, w0 >> 16); put16(pb, w0); put16(pa + 16, w1 >> 16); put16(pb + 16, w1);
            if (last) put16(pf + P_H7 + P_HS, w1);
        }
        bar_sync(1 + k, 128);
        t258 = w0;
    }
    STAMP(6);

    mbar_wait(mb + (MB_X + k) * 8);
    STAMP(7);
    if (k < nslot) {
        const int role = (wq + k) & 3;
        const uint32_t ub = sb + SM_U + k * US + 128;
        const uint32_t l16 = lane * 16, tz = opaque((lane & 28) - 8 * cq), tz4 = tz * 4;
        if (role) {
            const uint32_t al = cq * (2 * UP + 32) + tz4, au = opaque(ub + (3 - role) * 128), a1 = al + au, a0 = (cq ? al : al + (8 * UP - 16)) + au - 2 * UP;
            const uint4 q0 = lds128(a0), q1 = lds128(a0 + UP), q2 = lds128(a1), q3 = lds128(a1 + UP);
            const uint32_t U[16] = {q0.x, q0.y, q0.z, q0.w, q1.x, q1.y, q1.z, q1.w, q2.x, q2.y, q2.z, q2.w, q3.x, q3.y, q3.z, q3.w};
            uint32_t V[14], Q[14], R4[12], T[8];
#pragma unroll
            for (int i = 2; i < 14; i++) { V[i] = __byte_perm(U[i], U[i + 1], 0x5432); Q[i] = hadd2(U[i], V[i]); }
            const uint32_t rb = l16 + opaque(fb + (3 - role) * 512);
#pragma unroll
            for (int i = 0; i < 8; i++) T[i] = hadd2(V[5 + i], Q[6 + i]);
            sts128(rb + F_E3, T[0], T[1], T[2], T[3]); sts128(rb + F_O3 + 16, T[4], T[5], T[6], T[7]);
            asm volatile("{ .reg .pred p; setp.ne.u32 p, %10, 1; @p st.shared.v4.u32 [%0], {%2,%3,%4,%5}; @p st.shared.v4.u32 [%1], {%6,%7,%8,%9}; }"
                         :: "r"(rb + F_E2), "r"(rb + F_O2), "r"(Q[6]), "r"(Q[7]), "r"(Q[8]), "r"(Q[9]), "r"(Q[10]), "r"(Q[11]), "r"(Q[12]), "r"(Q[13]), "r"(role) : "memory");
#pragma unroll
            for (int i = 2; i < 12; i++) R4[i] = hadd2(Q[i], Q[i + 1]);
#pragma unroll
            for (int i = 0; i < 8; i++) T[i] = hadd2(R4[3 + i], U[5 + i]);
            sts128(rb + F_O5, T[0], T[1], T[2], T[3]); sts128(rb + F_E5, T[4], T[5], T[6], T[7]);
            if (role != 1) {
                uint32_t S[8];
#pragma unroll
                for (int i = 0; i < 8; i++) S[i] = hadd2(R4[2 + i], i < 7 ? T[i + 1] : hadd2(R4[11], U[13]));
                sts128(rb + F_O9, S[0], S[1], S[2], S[3]); sts128(rb + F_E9 + 16, S[4], S[5], S[6], S[7]);
#pragma unroll
                for (int i = 0; i < 8; i++) S[i] = hadd2(T[i], hadd2(V[2 + i], V[5 + i]));
                sts128(rb + F_E7, S[0], S[1], S[2], S[3]); sts128(rb + F_O7, S[4], S[5], S[6], S[7]);
            }
        } else if (lane == 0) {
            const uint4 m = lds128(ub + 23 * 16 + 7 * UP);
            const uint32_t U[6] = {lds32(ub + 23 * 16 + 6 * UP + 12), m.x, m.y, m.z, m.w, lds32(ub + 24 * 16)};
            uint32_t Q[5];
#pragma unroll
            for (int i = 0; i < 5; i++) Q[i] = hadd2(U[i], __byte_perm(U[i], U[i + 1], 0x5432));
            sts128(fb + F_O5 + 96 * 16, hadd2(hadd2(Q[0], Q[1]), U[2]), hadd2(hadd2(Q[1], Q[2]), U[3]), hadd2(hadd2(Q[2], Q[3]), U[4]), hadd2(hadd2(Q[3], Q[4]), U[5]));
            sts128(fb + F_O3, 0, 0, 0, 0); sts128(fb + F_E9, 0, 0, 0, 0);
            sts16(pn + 258 * 4, t258);
        }
        bar_sync(1 + k, 128);
        float acc[4][4];
        uint32_t Q[4][4];
        {
            const int h = role & 1, part = role >> 1;
            float fa[7][4];
            uint32_t B[3][4];
            const uint32_t po = tz + opaque(pf + part * (2 * P_GS)), ba = l16 + opaque(fb + (part == h ? 0 : F_O5 + h * 16));
#pragma unroll
            for (int s = 1; s >= 0; s--) {
#pragma unroll
                for (int i = 0; i < 3; i++) { Q[i][0] = lds32(po + (s * P_GS + i * 64)); if (i < 2) Q[i][1] = lds32(po + (s * P_GS + i * 64 + 32)); }
#pragma unroll
                for (int i = 0; i < 3; i++) ldsm4t(B[i], ba + (s * F_E3 + i * 512));
#pragma unroll
                for (int i = 0; i < 3; i++) { Q[i][3] = CP(Q[i][0]); if (i) Q[i][2] = CP(Q[i - 1][1]); }
                Q[0][2] = ZF(s ? tz : Q[0][0]); Q[2][1] = ZF(s ? l16 : Q[2][0]);
#pragma unroll
                for (int dl = 0; dl < 3; dl++)
#pragma unroll
                    for (int ap = 0; ap < 6 - dl; ap++) {
                        if (s == 1 && dl == 0) mma_f16_z(fa[ap + 1], Q[0], B[ap >> 1][2 * (ap & 1)], B[ap >> 1][2 * (ap & 1) + 1]);
                        else mma_f16(fa[ap + 1 + dl], Q[dl], B[ap >> 1][2 * (ap & 1)], B[ap >> 1][2 * (ap & 1) + 1]);
                    }
            }
#pragma unroll 1
            for (int s = role; s == 1; s++) {
                ldsm2t(B[0][0], B[0][1], fb + ((lane & 15) == 15 ? F_O5 : F_O3));
#pragma unroll
                for (int dl = 1; dl < 3; dl++) mma_f16(fa[dl], Q[dl], B[0][0], B[0][1]);
            }
            const uint32_t bh = l16 + opaque(fb + F_E7 + h * F_H + part * 2048), ph = tz + opaque(pf + P_H7 + part * (2 * P_HS));
#pragma unroll 1
            for (int s = part; s == 1; s++) {
                Q[2][1] = ZF(Q[2][3]); Q[2][2] = ZF(Q[2][2]); Q[2][0] = lds32(ph - P_HS);
                ldsm4t(B[0], bh - 1024); ldsm4t(B[1], bh - 512);
                Q[2][3] = CP(Q[2][0]);
#pragma unroll
                for (int ap = 0; ap < 4; ap++) mma_f16(fa[ap + 3], Q[2], B[ap >> 1][2 * (ap & 1)], B[ap >> 1][2 * (ap & 1) + 1]);
            }
            {
                Q[0][2] = ZF(tid);
#pragma unroll
                for (int i = 0; i < 4; i++) { Q[i][0] = lds32(ph + i * 64); Q[i][1] = lds32(ph + (i * 64 + 32)); }
                ldsm4t(B[0], bh); ldsm4t(B[1], bh + 512);
#pragma unroll
                for (int i = 0; i < 4; i++) { Q[i][3] = CP(Q[i][0]); if (i) Q[i][2] = CP(Q[i - 1][1]); }
#pragma unroll
                for (int dl = 0; dl < 4; dl++)
#pragma unroll
                    for (int ap = 0; ap < 4 - dl; ap++) mma_f16(fa[ap + 3 + dl], Q[dl], B[ap >> 1][2 * (ap & 1)], B[ap >> 1][2 * (ap & 1) + 1]);
            }
            const uint32_t da = (cq * 2048 + tz4) + opaque(fb + role * 128);
            bar_sync(1 + k, 128);
#pragma unroll
            for (int i = 1; i < 4; i++)
                stsm4(da + i * 512, pack_f16(fa[2 * i - 1][0], fa[2 * i - 1][1]), pack_f16(fa[2 * i - 1][2], fa[2 * i - 1][3]),
                      pack_f16(fa[2 * i][0], fa[2 * i][1]), pack_f16(fa[2 * i][2], fa[2 * i][3]));
            asm("shl.b32 %0, 0x6000, %1;" : "=r"(Q[0][0]) : "r"(tz4));
            Q[0][1] = ZF(Q[0][0]); Q[0][2] = ZF(tz4); Q[0][3] = CP(Q[0][0]);
            const uint32_t ra = l16 + opaque(fb + wq * 2016);
            acc[0][0] = acc[0][1] = acc[0][2] = acc[0][3] = 0.f;
            if (wq == 3) {
                const uint32_t uw = lds32(ub), kw = lds32(pf);
                const float2 uf = __half22float2(*(const __half2*)&uw);
                if ((lane | 4) == 31) acc[0][3] = (lane == 31 ? uf.x + uf.y : uf.x) * (__low2float(*(const __half2*)&kw) * 512.f);
            }
            bar_sync(1 + k, 128);
#pragma unroll
            for (int i = 1; i < 4; i++) {
                ldsm4(B[0], ra + i * 512);
                mma_f16_z(acc[i], Q[0], hadd2(B[0][0], B[0][2]), hadd2(B[0][1], B[0][3]));
            }
        }
        bar_arrive(6 + k, 160);
        STAMP(8);
        const uint32_t inv = lds32(opaque(sb + SM_SC + k * 4));
        const uint32_t yd = l16 + opaque(mapa(sb, 2 * wq) + (SM_XT + 128 + q * YP + k * YS + (k >> 2) * (q >> 1) * 16));
        {
            uint32_t pu = opaque(pn + 64 * (wq - 3));
#define pp (tz + pu)
            const uint32_t dlo = (((ub + 6 * UP) & 0x3FFFF) >> 4) | ((UP >> 4) << 16);
            uint32_t R[4][4];
            unsigned long long ds[4];
#pragma unroll
            for (int i = 0; i < 4; i++) asm volatile("mov.b64 %0, {%1, %2};" : "=l"(ds[i]) : "r"(dlo - i * (2 * UP >> 4)), "r"(8 | zero));
            auto loadQ = [&](uint32_t (&X)[4][4], uint32_t prev) {
#pragma unroll
                for (int i = 0; i < 4; i++) { X[i][0] = lds32(pp + i * 64); X[i][1] = lds32(pp + i * 64 + 32); }
                X[0][2] = CP(prev);
#pragma unroll
                for (int i = 0; i < 4; i++) { X[i][3] = CP(X[i][0]); if (i) X[i][2] = CP(X[i - 1][1]); }
                pu += 256;
            };
            auto issue = [&](uint32_t (&X)[4][4]) {
                asm volatile("wgmma.fence.sync.aligned;" ::: "memory");
#pragma unroll
                for (int i = 0; i < 4; i++) wgmma32(acc, X[i], ds[i]);
                asm volatile("wgmma.commit_group.sync.aligned;" ::: "memory");
#pragma unroll
                for (int i = 0; i < 4; i++) asm volatile("{ .reg .b32 l, h; mov.b64 {l, h}, %0; add.u32 l, l, %1; mov.b64 %0, {l, h}; }" : "+l"(ds[i]) : "r"(~zero));
            };
#pragma unroll
            for (int i = 0; i < 4; i++) {
                Q[i][0] = Q[i][1] = 0;
                if (wq + i >= 3) { Q[i][0] = lds32(pp + i * 64); Q[i][1] = lds32(pp + i * 64 + 32); }
            }
            Q[0][2] = CP(0);
#pragma unroll
            for (int i = 0; i < 4; i++) { Q[i][3] = CP(Q[i][0]); if (i) Q[i][2] = CP(Q[i - 1][1]); }
            pu += 256;
#pragma unroll 1
            for (int dl = 0; dl < 4; dl++) {
                issue(Q);
                asm volatile("wgmma.wait_group.sync.aligned 1;" ::: "memory");
                loadQ(R, Q[3][1]);
                issue(R);
                asm volatile("wgmma.wait_group.sync.aligned 1;" ::: "memory");
                loadQ(Q, R[3][1]);
            }
            issue(Q);
            asm volatile("wgmma.wait_group.sync.aligned 0;" ::: "memory");
        }
        const uint32_t pstep = mapa(sb, 1) - mapa(sb, 0), ym = mapa(mb + MB_Y * 8, 2 * wq);
#pragma unroll
        for (int e = 0; e < 2; e++)
            st_async4(yd + e * pstep, bmul2(pack_bf16(acc[0][2 * e], acc[0][2 * e + 1]), inv), bmul2(pack_bf16(acc[1][2 * e], acc[1][2 * e + 1]), inv),
                      bmul2(pack_bf16(acc[2][2 * e], acc[2][2 * e + 1]), inv), bmul2(pack_bf16(acc[3][2 * e], acc[3][2 * e + 1]), inv), ym + e * pstep);
        if (lane == 0) asm volatile("mbarrier.arrive.shared::cta.b64 _, [%0];" :: "r"(mb + MB_Y * 8) : "memory");
    }
    STAMP(9);
    uint32_t ha[5], hb[5];
    if (warp < 16) {
        const uint4 wk = lds128(sb + SM_DW + cq * 16);
        uint32_t sel[5] = {wk.x, wk.y, wk.z, wk.w, lds32(sb + SM_DW + 64 + cq * 4)}, sel2[5];
#pragma unroll
        for (int i = 0; i < 5; i++) {
            if (!(g & 1)) sel[i] = 0x3F803F80u;
            sel2[i] = sel[i]; PIN(sel2[i]);
        }
        const uint32_t y4 = sb + SM_XT + 128 + warp * 32 + (2 * (lane >> 3) + (lane & 1)) * YP + ((lane & 7) >> 1) * YS;
        const uint32_t y1 = sb + SM_XT + 128 + warp * 32 + (lane & 7) * YP + 4 * YS + (lane & 8) * 2 + (lane & 6) * 8;
        uint32_t ao = (256 * q + tn) * 16, hta = sb + SM_HT + tn * 80;
        PIN(ao); PIN(hta);
        mbar_wait(mb + MB_Y * 8);
        STAMP(10);
        float ca[4] = {0.f, 0.f, 0.f, 0.f}, cb[4] = {0.f, 0.f, 0.f, 0.f};
        {
            uint32_t ya[4], yb[4], yc, yd;
            ldsm4t(ya, y4); ldsm4t(yb, y4 + 16); ldsm2t(yc, yd, y1);
#pragma unroll
            for (int i = 0; i < 4; i++) { ha[i] = badd2(xa[i], ya[i]); hb[i] = badd2(xb[i], yb[i]); }
            ha[4] = badd2(xa[4], yc); hb[4] = badd2(xb[4], yd);
        }
        if (nslot != 5) {
            ha[4] = hb[4] = 0;
            if (cq >= 2) ha[0] = ha[1] = ha[2] = ha[3] = hb[0] = hb[1] = hb[2] = hb[3] = 0;
        }
#pragma unroll
        for (int i = 0; i < 5; i++) { mma_bf16_k8(ca, ha[i], sel[i], ha[i]); mma_bf16_k8(cb, hb[i], sel2[i], hb[i]); }
        if (!(g & 1)) { ca[1] = ca[0]; cb[1] = cb[0]; }
        if (cq == (g >> 1)) {
            asm volatile("red.relaxed.gpu.global.add.v4.f32 [%0], {%1,%2,%3,%4};" :: "l"((char*)g_s.acc + ao), "f"(1.0f), "f"(ca[1]), "f"(ca[2]), "f"(ca[3]) : "memory");
            asm volatile("red.relaxed.gpu.global.add.v4.f32 [%0], {%1,%2,%3,%4};" :: "l"((char*)g_s.acc + ao + 128), "f"(1.0f), "f"(cb[1]), "f"(cb[2]), "f"(cb[3]) : "memory");
        }
        sts128(hta + cq * 16, ha[0], ha[1], ha[2], ha[3]); sts32(hta + 64 + cq * 4, ha[4]);
        sts128(hta + cq * 16 + 640, hb[0], hb[1], hb[2], hb[3]); sts32(hta + 704 + cq * 4, hb[4]);
        STAMP(11);
    }
    const int kq = warp / 5, mt = warp - 5 * kq;
    const int mi = lane >> 3, mr = lane & 7;
    const unsigned tk = (unsigned)tid / 72u, ck = tid - tk * 72;
    uint32_t A[9][4];
    auto loadA = [&]() {
        mbar_wait(mb + MB_W1 * 8);
        const uint32_t aa = sb + (mi & 1) * SM_WU + (8 * (mi >> 1) + mr) * 80 + (144 * 80 * kq + mt * 16);
#pragma unroll
        for (int s = 0; s < 9; s++) ldsm4t(A[s], aa + s * 1280);
    };
    const uint32_t par = (lds32(sb + SM_SC + 28) & 1) ? 0u : 0x40004000u;
    uint32_t pk0 = mapa(sb, 2 * cq), go = (ck / 5u + ck) * 16, co = ((q * 8 * NCL + c) * 6 + cq) * 16;
    PIN(pk0); PIN(go); PIN(co);
    if (warp < 8) {
        const float wsum = ldsf(sb + SM_SC + 24);
        const uint32_t idx = 2047 - (512 * ((tid >> 1) & 3) + 128 * ((tid >> 3) & 3) + 64 * (tid & 1) + 8 * q + warp);
        uint4 s; int n = 0;
        do { s = ld_rlx128(&g_s.acc[256 * q + tid]); } while (__uint_as_float(s.x) != (float)NCL && ++n < SPIN_LIMIT);
        STAMP(16);
        const uint32_t ox = __shfl_xor_sync(~0u, (lane & 1) ? s.z : s.w, 1);
        const uint32_t ms = ln_stats(__uint_as_float((lane & 1) ? ox : s.z), __uint_as_float(s.y));
        const float rs = rcpf(bf_hi(ms));
        const uint32_t rb = pack_bf16(0.f, fmaf(-bf_lo(ms), wsum, __uint_as_float((lane & 1) ? s.w : ox)) * rs);
        const uint32_t key = (((rb ^ (((int)rb >> 31) | 0x80000000u)) >> 16) << 11) | idx;
        sts32(sb + SM_KEY + tid * 4, key);
        __syncwarp();
        const uint32_t rank = rank4<8, 16>(sb + SM_KEY + warp * 128, key);
        asm volatile("{ .reg .pred p; setp.lt.u32 p, %0, 8; @p st.shared.u32 [%1], %2; }" :: "r"(rank), "r"(sb + SM_CAND + warp * 32 + rank * 4), "r"(key) : "memory");
        sts64(sb + SM_ST + tid * 8, ms, rsplit(rs));
    } else { mbar_wait(mb + MB_Y * 8); loadA(); }
    if (warp < 16) {
        STAMP(17);
        bar_sync(12, 512);
        STAMP(18);
        if (warp < 8) {
            const uint32_t mk = lds32(sb + SM_CAND + (tid >> 2) * 4);
            uint32_t rank = rank4<4, 64>(sb + SM_CAND + cq * 16, mk);
            rank += __shfl_xor_sync(~0u, rank, 1); rank += __shfl_xor_sync(~0u, rank, 2);
            if (rank < 8) {
                const uint32_t pk1 = pk0 + (mapa(sb, 1) - mapa(sb, 0));
                st_async1(pk0 + (SM_RK + q * 32) + rank * 4, mk, pk0 + (SM_MB + MB_KEY * 8));
                st_async1(pk1 + (SM_RK + q * 32) + rank * 4, mk, pk1 + (SM_MB + MB_KEY * 8));
                const uint32_t t = tslot(~mk | ((pk1 + rank * 4) & zero));
                const uint2 sv = lds64(sb + SM_ST + t * 8);
                const uint4 hv = lds128(sb + SM_HT + t * 80 + cq * 16);
                const uint32_t h4 = lds32(sb + SM_HT + t * 80 + 64 + cq * 4);
                const uint32_t rr = bmul2(sv.y, 0x3C803C80u);
                char* const dp = (char*)g_s.cand + (co + rank * 1440);
                st_rlx128(dp, (norm2(hv.x, sv.x, rr) & 0xBFFFBFFFu) | par, (norm2(hv.y, sv.x, rr) & 0xBFFFBFFFu) | par,
                          (norm2(hv.z, sv.x, rr) & 0xBFFFBFFFu) | par, (norm2(hv.w, sv.x, rr) & 0xBFFFBFFFu) | par);
                asm volatile("st.relaxed.gpu.global.u32 [%0], %1;" :: "l"((char*)g_s.cand + (co + rank * 1440 + 64 - cq * 12)), "r"((norm2(h4, sv.x, rr) & 0xBFFFBFFFu) | par) : "memory");
            }
            __syncwarp();
        }
        {
            const uint2 sa = lds64(sb + SM_ST + tn * 8), sbb = lds64(sb + SM_ST + tn * 8 + 64);
#pragma unroll
            for (int i = 0; i < 5; i++) { ha[i] = badd2(ha[i], norm2(ha[i], sa.x, sa.y)); hb[i] = badd2(hb[i], norm2(hb[i], sbb.x, sbb.y)); }
            const bool hf = (c & 1) && cq == 0;
            const uint32_t o16 = sb + SM_XT + (hf ? 16384 + tn * 16 : tn * 64 + (cq - (c & 1)) * 16), o4 = sb + SM_XT + ((c & 1) ? tn * 64 + 48 : 16384 + tn * 16) + cq * 4;
            sts128(o16, ha[0], ha[1], ha[2], ha[3]); sts32(o4, ha[4]);
            sts128(o16 + (hf ? 128 : 512), hb[0], hb[1], hb[2], hb[3]); sts32(o4 + ((c & 1) ? 512 : 128), hb[4]);
        }
        if (warp >= 8) {
            STAMP(19);
            mbar_wait(mb + MB_KEY * 8);
            STAMP(20);
            const uint32_t mk = lds32(sb + SM_RK - 256 + (tid >> 2) * 4);
            uint32_t rank = rank4<4, 64>(sb + SM_RK + cq * 16, mk);
            rank += __shfl_xor_sync(~0u, rank, 1); rank += __shfl_xor_sync(~0u, rank, 2);
            if (rank < 8) sts64(sb + SM_SEL + rank * 8, mk, ((tid >> 2) - 64) * 1440);
        }
    }
    bar_sync(11, 640);
    STAMP(12);

    const char* gp = (const char*)g_s.cand + (go + lds32(sb + SM_SEL + 4 + (tk & 7) * 8));
    uint4 hv = ld_rlx128(gp);
    if (warp < 8) loadA();
    const uint32_t ft = (unsigned)tid / 24u, fj = 24 * q + tid - ft * 24;
    const uint32_t key = lds32(sb + SM_SEL + (ft & 7) * 8), k16 = key << 5;
    float sig = bfr(rcpf(1.f + ex2f(__uint_as_float((k16 ^ (~((int)k16 >> 31) | 0x80000000u)) & 0xFFFF0000u) * -1.4426950408889634f)));
    uint32_t ra2 = sb + SM_RED2 + tid * 12 + ft * 16, fo = (ft * 192 + fj) * 16, oo = ((~key & 2047) * D_ + 3 * fj) * 2;
    uint32_t bx = sb + SM_XS + mr * 1168 + mi * 16 + 288 * kq, gd = mapa(sb, kq * (8 / NRED)) + (SM_GU + (q * nslot + mt) * 128) + lane * 4;
    PIN(ra2); PIN(fo); PIN(oo); PIN(bx); PIN(gd);
    asm volatile("" : "+f"(sig));
    {
        if (warp < 18) {
            int n = 0;
            while (true) {
                sts128(sb + SM_XS + tk * 16 + tid * 16, hv.x ^ par, hv.y ^ par, hv.z ^ par, hv.w ^ par);
                if (!__any_sync(~0u, ((hv.x ^ par) | (hv.y ^ par) | (hv.z ^ par) | (hv.w ^ par)) & 0x40004000u) || ++n >= SPIN_LIMIT) break;
                hv = ld_rlx128(gp);
            }
        }
    }
    bar_sync(14, 768);
    STAMP(13);
    {
        float c0[4] = {0.f, 0.f, 0.f, 0.f}, c1[4] = {0.f, 0.f, 0.f, 0.f}, c2[4] = {0.f, 0.f, 0.f, 0.f};
        uint32_t b[5][4];
#pragma unroll
        for (int s = 0; s < 4; s++) ldsm4(b[s], bx + s * 64);
        asm volatile("ldmatrix.sync.aligned.m8n8.x2.shared.b16 {%0,%1}, [%2];" : "=r"(b[4][0]), "=r"(b[4][1]) : "r"(bx + 256) : "memory");
        mma_bf16(c0, A[0][0], A[0][1], A[0][2], A[0][3], b[0][0], b[0][1]);
        mma_bf16(c1, A[1][0], A[1][1], A[1][2], A[1][3], b[0][2], b[0][3]);
        mma_bf16(c2, A[2][0], A[2][1], A[2][2], A[2][3], b[1][0], b[1][1]);
        mma_bf16(c0, A[3][0], A[3][1], A[3][2], A[3][3], b[1][2], b[1][3]);
        mma_bf16(c1, A[4][0], A[4][1], A[4][2], A[4][3], b[2][0], b[2][1]);
        mma_bf16(c2, A[5][0], A[5][1], A[5][2], A[5][3], b[2][2], b[2][3]);
        mma_bf16(c0, A[6][0], A[6][1], A[6][2], A[6][3], b[3][0], b[3][1]);
        mma_bf16(c1, A[7][0], A[7][1], A[7][2], A[7][3], b[3][2], b[3][3]);
        mma_bf16(c2, A[8][0], A[8][1], A[8][2], A[8][3], b[4][0], b[4][1]);
        sts128f(sb + SM_RED + tid * 16, c0[0] + c1[0] + c2[0], c0[1] + c1[1] + c2[1], c0[2] + c1[2] + c2[2], c0[3] + c1[3] + c2[3]);
    }
    bar_sync(1 + mt, 128);
    STAMP(21);
    if (mt < nslot && kq < NRED) {
        const uint32_t ra = sb + SM_RED + mt * 512 + lane * 16;
        const float4 p0 = lds128f(ra), p1 = lds128f(ra + 2560), p2 = lds128f(ra + 5120), p3 = lds128f(ra + 7680);
        const float g0 = bfr(((p0.x + p1.x) + (p2.x + p3.x)) * 64.f), g1 = bfr(((p0.y + p1.y) + (p2.y + p3.y)) * 64.f);
        const uint32_t sg = pack_bf16(g0 * rcpf(1.f + ex2f(g0 * -1.4426950408889634f)), g1 * rcpf(1.f + ex2f(g1 * -1.4426950408889634f)));
        const uint32_t gu = bmul2(sg, pack_bf16(((p0.z + p1.z) + (p2.z + p3.z)) * 64.f, ((p0.w + p1.w) + (p2.w + p3.w)) * 64.f));
        const uint32_t pstep = mapa(sb, 1) - mapa(sb, 0), gm = mapa(mb + MB_GU * 8, kq * (8 / NRED));
#pragma unroll
        for (int i = 0; i < 8 / NRED; i++) st_async1(gd + i * pstep, gu, gm + i * pstep);
    }
    mbar_wait(mb + MB_W2 * 8);
    {
        const uint32_t aa = sb + (8 * (mi >> 1) + mr) * 144 + (mi & 1) * 16 + (SM_FAR + 2304 * kq + mt * 32);
#pragma unroll
        for (int s = 0; s < 5; s++) ldsm4t(A[s], aa + s * FAR_SZ);
    }
    {
        uint32_t ba = sb + (SM_GU + 256 * kq) + (lane & 15) * 16 + (lane >> 4) * 1024, wa = sb + (SM_RED2 + kq * 2432 + mt * 64) + g * 4 + cq * 608;
        PIN(ba); PIN(wa);
        STAMP(22);
        mbar_wait(mb + MB_GU * 8);
        STAMP(23);
        float c0[4] = {0.f, 0.f, 0.f, 0.f}, c1[4] = {0.f, 0.f, 0.f, 0.f}, c2[4] = {0.f, 0.f, 0.f, 0.f};
        uint32_t b[2][4], b8, b9;
        ldsm4t(b[0], ba); ldsm4t(b[1], ba + 2048); ldsm2t(b8, b9, ba + 4096);
        mma_bf16(c0, A[0][0], A[0][1], A[0][2], A[0][3], b[0][0], b[0][1]);
        mma_bf16(c1, A[1][0], A[1][1], A[1][2], A[1][3], b[0][2], b[0][3]);
        if (nslot == 5) {
            mma_bf16(c2, A[4][0], A[4][1], A[4][2], A[4][3], b8, b9);
            mma_bf16(c0, A[2][0], A[2][1], A[2][2], A[2][3], b[1][0], b[1][1]);
            mma_bf16(c1, A[3][0], A[3][1], A[3][2], A[3][3], b[1][2], b[1][3]);
        }
        stsf(wa, c0[0] + c1[0] + c2[0]); stsf(wa + 304, c0[1] + c1[1] + c2[1]);
        if (mt < 4) { stsf(wa + 32, c0[2] + c1[2] + c2[2]); stsf(wa + 336, c0[3] + c1[3] + c2[3]); }
    }
    if (warp < 6) {
        float v[3];
        bar_sync(6, 640);
        STAMP(14);
#pragma unroll
        for (int i = 0; i < 3; i++) v[i] = ((ldsf(ra2 + i * 4) + ldsf(ra2 + i * 4 + 2432)) + (ldsf(ra2 + i * 4 + 4864) + ldsf(ra2 + i * 4 + 7296))) * sig;
        finish(prm, fo, oo, v, 3.f);
    } else bar_arrive(6, 640);
    STAMP(15);
}

#undef pp
typedef __nv_bfloat16 bf16;
__device__ bf16 f_n[L_ * D_], f_h[L_ * D_];
__device__ float f_k[D_ * L_], f_r[L_], f_gu[8 * F_];
__device__ int f_idx[8];
__device__ __forceinline__ float b2f(bf16 v) { return __bfloat162float(v); }
__global__ void fb_ln(const bf16* in, const bf16* wr, bf16* out) {
    const int t = blockIdx.x * 8 + (threadIdx.x >> 5), lane = threadIdx.x & 31;
    const bf16* r = (in ? in : f_h) + t * D_;
    float s1 = 0.f, s2 = 0.f, s3 = 0.f;
    for (int i = lane; i < D_; i += 32) s1 += b2f(r[i]);
    for (int o = 16; o; o >>= 1) s1 += __shfl_xor_sync(~0u, s1, o);
    for (int i = lane; i < D_; i += 32) { const float d = b2f(r[i]) - s1 / D_; s2 += d * d; }
    for (int o = 16; o; o >>= 1) s2 += __shfl_xor_sync(~0u, s2, o);
    const float m = bfr(s1 / D_), sd = bfr(sqrtf(bfr(bfr(s2 / D_) + 1e-5f)));
    for (int i = lane; i < D_; i += 32) {
        const float v = bfr(bfr(b2f(r[i]) - m) / sd);
        f_n[t * D_ + i] = __float2bfloat16(v);
        if (!in) { s3 += v * b2f(wr[i]); out[t * D_ + i] = __float2bfloat16(b2f(r[i]) + v); }
    }
    for (int o = 16; o; o >>= 1) s3 += __shfl_xor_sync(~0u, s3, o);
    f_r[t] = bfr(s3);
}
__global__ void fb_taps(Params p) {
    const int d = blockIdx.x >> 3, l = (blockIdx.x & 7) * 256 + threadIdx.x;
    const float dt = bfr(expf(bf_lo(p.logdt[d]))), lf = bfr((float)l);
    float k = 0.f;
    for (int n = d * 128; n < d * 128 + 128; n++) {
        float wr, wi, sn, cs;
        cmul(wr, wi, bf_lo(p.prm6[4][n]), bf_lo(p.prm6[5][n]), dt * bf_lo(p.prm6[2][n]), dt * bf_lo(p.prm6[3][n]));
        sincosf(dt * bf_lo(p.prm6[1][n]) * lf, &sn, &cs);
        k += expf(dt * bf_lo(p.prm6[0][n]) * lf) * (wr * cs - wi * sn);
    }
    f_k[l * D_ + d] = k;
}
__global__ void fb_conv(Params p) {
    const int t = blockIdx.x, d = threadIdx.x;
    float y = 0.f;
    for (int l = 0; l <= t; l++) y += f_k[l * D_ + d] * b2f(f_n[(t - l) * D_ + d]);
    f_h[t * D_ + d] = __float2bfloat16(bf_lo(p.x[t * D_ + d]) + bfr(bfr(y) + bfr(b2f(f_n[t * D_ + d]) * bf_lo(p.dskip[d]))));
}
__global__ void fb_top() {
    const int t = blockIdx.x * 256 + threadIdx.x;
    int rank = 0;
    for (int j = 0; j < L_; j++) rank += f_r[j] > f_r[t] || (f_r[j] == f_r[t] && j < t);
    if (rank < 8) f_idx[rank] = t;
}
__global__ void fb_ffn1(const bf16* wg, const bf16* wu) {
    const int f = blockIdx.x * 256 + threadIdx.x, j = blockIdx.y;
    float g = 0.f, u = 0.f;
    for (int i = 0; i < D_; i++) { const float v = b2f(f_n[f_idx[j] * D_ + i]); g += v * b2f(wg[i * F_ + f]); u += v * b2f(wu[i * F_ + f]); }
    g = bfr(g);
    f_gu[j * F_ + f] = bfr(bfr(g / (1.f + expf(-g))) * bfr(u));
}
__global__ void fb_ffn2(const bf16* wd, bf16* out) {
    const int d = threadIdx.x, j = blockIdx.x, t = f_idx[j];
    float y = 0.f;
    for (int f = 0; f < F_; f++) y += f_gu[j * F_ + f] * b2f(wd[f * D_ + d]);
    out[t * D_ + d] = __float2bfloat16(b2f(f_h[t * D_ + d]) + bfr(b2f(f_n[t * D_ + d]) + bfr(bfr(y) * bfr(1.f / (1.f + expf(-f_r[t]))))));
}

typedef CUresult (*EncodeFn)(CUtensorMap*, CUtensorMapDataType, cuuint32_t, void*, const cuuint64_t*, const cuuint64_t*,
                             const cuuint32_t*, const cuuint32_t*, CUtensorMapInterleave, CUtensorMapSwizzle,
                             CUtensorMapL2promotion, CUtensorMapFloatOOBfill);

void make_map(EncodeFn fn, CUtensorMap* tm, const void* p, int cols, int rows, int bc, int br) {
    cuuint64_t dims[2] = {(cuuint64_t)cols, (cuuint64_t)rows};
    cuuint64_t strides[1] = {(cuuint64_t)cols * 2};
    cuuint32_t box[2] = {(cuuint32_t)bc, (cuuint32_t)br};
    cuuint32_t es[2] = {1, 1};
    fn(tm, CU_TENSOR_MAP_DATA_TYPE_BFLOAT16, 2, const_cast<void*>(p), dims, strides, box, es, CU_TENSOR_MAP_INTERLEAVE_NONE,
       CU_TENSOR_MAP_SWIZZLE_NONE, CU_TENSOR_MAP_L2_PROMOTION_L2_128B, CU_TENSOR_MAP_FLOAT_OOB_FILL_NONE);
}

void make_map3(EncodeFn fn, CUtensorMap* tm, const void* p) {
    cuuint64_t dims[5] = {(cuuint64_t)D_, 64, 2, 2, 8};
    cuuint64_t strides[4] = {(cuuint64_t)D_ * 2, (cuuint64_t)D_ * 2048, (cuuint64_t)D_ * 128, (cuuint64_t)D_ * 256};
    cuuint32_t box[5] = {XW, 9, 2, 2, 8};
    cuuint32_t es[5] = {1, 1, 1, 1, 1};
    fn(tm, CU_TENSOR_MAP_DATA_TYPE_BFLOAT16, 5, const_cast<void*>(p), dims, strides, box, es, CU_TENSOR_MAP_INTERLEAVE_NONE,
       CU_TENSOR_MAP_SWIZZLE_NONE, CU_TENSOR_MAP_L2_PROMOTION_NONE, CU_TENSOR_MAP_FLOAT_OOB_FILL_NONE);
}

void make_map5(EncodeFn fn, CUtensorMap* tm, const void* p, int bc) {
    cuuint64_t dims[5] = {(cuuint64_t)D_, 2, 4, 4, 64};
    cuuint64_t strides[4] = {(cuuint64_t)D_ * 128, (cuuint64_t)D_ * 1024, (cuuint64_t)D_ * 256, (cuuint64_t)D_ * 2};
    cuuint32_t box[5] = {(cuuint32_t)bc, 2, 4, 4, 8};
    cuuint32_t es[5] = {1, 1, 1, 1, 1};
    fn(tm, CU_TENSOR_MAP_DATA_TYPE_BFLOAT16, 5, const_cast<void*>(p), dims, strides, box, es, CU_TENSOR_MAP_INTERLEAVE_NONE,
       CU_TENSOR_MAP_SWIZZLE_NONE, CU_TENSOR_MAP_L2_PROMOTION_NONE, CU_TENSOR_MAP_FLOAT_OOB_FILL_NONE);
}

}

extern "C" void kernel_launch(void* const* d_in, const int* in_sizes, int n_in, void* d_out, int out_size) {
    (void)in_sizes; (void)n_in; (void)out_size;
    void* fp = nullptr;
    cudaDriverEntryPointQueryResult qr;
    cudaGetDriverEntryPoint("cuTensorMapEncodeTiled", &fp, cudaEnableDefault, &qr);
    EncodeFn fn = (EncodeFn)fp;
    CUtensorMap tmG, tmU, tmD, tmO, tmX, tmH;
    make_map3(fn, &tmX, d_in[0]);
    make_map(fn, &tmG, d_in[11], F_, D_, 40, 48);
    make_map(fn, &tmU, d_in[12], F_, D_, 40, 48);
    make_map(fn, &tmD, d_in[13], D_, F_, 72, 64);
    make_map5(fn, &tmO, d_out, 32);
    make_map5(fn, &tmH, d_out, 8);
    Params p;
    p.x = (const unsigned short*)d_in[0];
    for (int i = 0; i < 6; i++) p.prm6[i] = (const unsigned short*)d_in[1 + i];
    p.logdt = (const unsigned short*)d_in[7]; p.dskip = (const unsigned short*)d_in[8];
    p.wr = (const unsigned short*)d_in[10];
    p.out = (__nv_bfloat16*)d_out;
    p.zero = 0;
    cudaGetSymbolAddress((void**)&p.gs, g_s);
    cudaFuncSetAttribute(fused_kernel, cudaFuncAttributeMaxDynamicSharedMemorySize, SM_TOTAL);
    static int nclusters = -1;
    if (nclusters < 0) {
        cudaLaunchConfig_t cfg = {};
        cudaLaunchAttribute at;
        at.id = cudaLaunchAttributeClusterDimension; at.val.clusterDim.x = CS; at.val.clusterDim.y = 1; at.val.clusterDim.z = 1;
        cfg.gridDim = dim3(NCTA); cfg.blockDim = dim3(NTHR); cfg.dynamicSmemBytes = SM_TOTAL; cfg.attrs = &at; cfg.numAttrs = 1;
        if (cudaOccupancyMaxActiveClusters(&nclusters, fused_kernel, &cfg) != cudaSuccess) { (void)cudaGetLastError(); nclusters = NCL; }
    }
    if (nclusters >= NCL && !FORCE_FALLBACK) {
        fused_kernel<<<NCTA, NTHR, SM_TOTAL>>>(p, tmG, tmU, tmD, tmO, tmX, tmH);
        return;
    }
    fb_ln<<<L_ / 8, 256>>>((const bf16*)d_in[0], nullptr, nullptr);
    fb_taps<<<D_ * 8, 256>>>(p);
    fb_conv<<<L_, D_>>>(p);
    fb_ln<<<L_ / 8, 256>>>(nullptr, (const bf16*)d_in[10], p.out);
    fb_top<<<L_ / 256, 256>>>();
    fb_ffn1<<<dim3(F_ / 256, 8), 256>>>((const bf16*)d_in[11], (const bf16*)d_in[12]);
    fb_ffn2<<<8, D_>>>((const bf16*)d_in[13], p.out);
}
```

```cpp
#include <cuda_runtime.h>
#include <cuda_bf16.h>
#include <cuda_fp16.h>
#include <cuda.h>
#include <stdint.h>

namespace {

constexpr int L_ = 2048, D_ = 576, F_ = 4608;
constexpr int NCL = 15, CS = 8, NCTA = NCL * CS, NTHR = 768;
#define FORCE_FALLBACK 0
constexpr int XW = 48, NRED = 2;
constexpr int SPIN_LIMIT = 1 << 22;

constexpr int SM_WG   = 0;
constexpr int SM_WU   = 46080;
constexpr int YP = 3392, YS = 656;
constexpr int UP = 3280, US = 656;
constexpr int SM_XT   = 92160;
constexpr int SM_U    = SM_XT + 8 * YP;
constexpr int SM_FAR  = SM_U + 8 * UP;
constexpr int FAR_SZ  = 12416;
constexpr int F_E5 = 0, F_O5 = 1536, F_E3 = 3088, F_O3 = 4624, F_E7 = 6176, F_E2 = F_E7 + 1024, F_E9 = F_E7 + 2048,
              F_H = 3088, F_O7 = F_E7 + F_H, F_O2 = F_E2 + F_H, F_O9 = F_E9 + F_H;
constexpr int SM_P    = SM_FAR + 5 * FAR_SZ;
constexpr int PN_SZ = 584 * 4, SM_PN = SM_P + 65 * 4;
constexpr int P_GS = 50 * 4, P_H7 = 200 * 4, P_HS = 74 * 4;
constexpr int PF_SZ = (200 + 222) * 4, SM_PF = SM_PN + 5 * PN_SZ + 36;
constexpr int SM_MISC = SM_PF + 5 * PF_SZ;
constexpr int SM_ST   = SM_MISC;
constexpr int SM_RK   = SM_ST + 2048;
constexpr int SM_SEL  = SM_RK + 256;
constexpr int SM_KG   = SM_SEL + 64;
constexpr int SM_SC   = SM_KG + 160;
constexpr int SM_DW   = SM_SC + 32;
constexpr int SM_MB   = SM_DW + 160;
constexpr int SM_TOTAL = SM_MB + 128;
constexpr int SM_ROW  = SM_XT - 20736;
constexpr int SM_XTL  = SM_ROW - 576 * XW;
constexpr int SM_RED2 = SM_WG;
constexpr int SM_HT   = SM_P - 512;
constexpr int SM_KEY  = SM_FAR + 10240 + 128;
constexpr int SM_CAND = SM_KEY + 1024;
constexpr int SM_XS   = SM_U;
constexpr int SM_GU   = SM_XS + 9344;
constexpr int SM_RED  = SM_GU + 5632;
static_assert(F_O9 + 1024 <= FAR_SZ && FAR_SZ % 128 == 0, "far overflow");
static_assert(SM_RED + 10240 <= SM_FAR && SM_HT + 20496 <= SM_MISC, "alias overflow");
static_assert(SM_TOTAL <= 232448, "smem overflow");
static_assert(SM_FAR % 128 == 0 && SM_XT % 128 == 0 && SM_XTL % 128 == 0 && SM_P % 16 == 0 && SM_MISC % 16 == 0 && SM_MB % 8 == 0, "align");

enum { MB_X = 0, MB_W1 = 5, MB_W2 = 6, MB_KEY = 7, MB_GU = 8, MB_Y = 9, MB_OUT = 10, MB_T = 11, MB_R = 12 };

struct __align__(128) Scratch {
    unsigned epoch, zcnt, pad[30];
    uint4  st1[L_ * 2];
    float4 acc[L_];
    uint4  cand[64 * NCL * 6];
    float4 fin[8 * 192 + 24];
};
__device__ Scratch g_s;
#define STAMP(i)

__device__ __forceinline__ uint32_t mapa(uint32_t a, uint32_t r) { uint32_t d; asm("mapa.shared::cluster.u32 %0, %1, %2;" : "=r"(d) : "r"(a), "r"(r)); return d; }
__device__ __forceinline__ void mbar_wait(uint32_t mb) {
    asm volatile("{ .reg .pred p, q; .reg .u32 n; mov.u32 n, 0;\n"
                 "W_%=: mbarrier.try_wait.parity.shared::cta.b64 p, [%0], 0; add.u32 n, n, 1; setp.lt.and.u32 q, n, 65536, !p; @q bra W_%=; }" :: "r"(mb) : "memory");
}
__device__ __forceinline__ void arm(uint32_t mb, uint32_t bytes) { asm volatile("mbarrier.arrive.expect_tx.shared::cta.b64 _, [%0], %1;" :: "r"(mb), "r"(bytes) : "memory"); }
__device__ __forceinline__ void bar_sync(int id, int n) { asm volatile("bar.sync %0, %1;" :: "r"(id), "r"(n) : "memory"); }
__device__ __forceinline__ void bar_arrive(int id, int n) { asm volatile("bar.arrive %0, %1;" :: "r"(id), "r"(n) : "memory"); }
__device__ __forceinline__ uint32_t lds16(uint32_t a) { unsigned short v; asm volatile("ld.shared.u16 %0, [%1];" : "=h"(v) : "r"(a) : "memory"); return v; }
__device__ __forceinline__ uint32_t lds32(uint32_t a) { uint32_t v; asm volatile("ld.shared.u32 %0, [%1];" : "=r"(v) : "r"(a) : "memory"); return v; }
__device__ __forceinline__ uint2 lds64(uint32_t a) { uint2 v; asm volatile("ld.shared.v2.u32 {%0,%1}, [%2];" : "=r"(v.x), "=r"(v.y) : "r"(a) : "memory"); return v; }
__device__ __forceinline__ float ldsf(uint32_t a) { float v; asm volatile("ld.shared.f32 %0, [%1];" : "=f"(v) : "r"(a) : "memory"); return v; }
__device__ __forceinline__ uint4 lds128(uint32_t a) { uint4 v; asm volatile("ld.shared.v4.u32 {%0,%1,%2,%3}, [%4];" : "=r"(v.x), "=r"(v.y), "=r"(v.z), "=r"(v.w) : "r"(a) : "memory"); return v; }
__device__ __forceinline__ float4 lds128f(uint32_t a) { float4 v; asm volatile("ld.shared.v4.f32 {%0,%1,%2,%3}, [%4];" : "=f"(v.x), "=f"(v.y), "=f"(v.z), "=f"(v.w) : "r"(a) : "memory"); return v; }
__device__ __forceinline__ void sts16(uint32_t a, uint32_t v) { asm volatile("{ .reg .b16 l, h; mov.b32 {l, h}, %1; st.shared.b16 [%0], l; }" :: "r"(a), "r"(v) : "memory"); }
__device__ __forceinline__ void sts32(uint32_t a, uint32_t v) { asm volatile("st.shared.u32 [%0], %1;" :: "r"(a), "r"(v) : "memory"); }
__device__ __forceinline__ void sts64(uint32_t a, uint32_t x, uint32_t y) { asm volatile("st.shared.v2.u32 [%0], {%1,%2};" :: "r"(a), "r"(x), "r"(y) : "memory"); }
__device__ __forceinline__ void stsf(uint32_t a, float v) { asm volatile("st.shared.f32 [%0], %1;" :: "r"(a), "f"(v) : "memory"); }
__device__ __forceinline__ void sts128(uint32_t a, uint32_t x, uint32_t y, uint32_t z, uint32_t w) { asm volatile("st.shared.v4.u32 [%0], {%1,%2,%3,%4};" :: "r"(a), "r"(x), "r"(y), "r"(z), "r"(w) : "memory"); }
__device__ __forceinline__ void sts128f(uint32_t a, float x, float y, float z, float w) { asm volatile("st.shared.v4.f32 [%0], {%1,%2,%3,%4};" :: "r"(a), "f"(x), "f"(y), "f"(z), "f"(w) : "memory"); }
__device__ __forceinline__ void ldsm4(uint32_t (&r)[4], uint32_t a) { asm volatile("ldmatrix.sync.aligned.m8n8.x4.shared.b16 {%0,%1,%2,%3}, [%4];" : "=r"(r[0]), "=r"(r[1]), "=r"(r[2]), "=r"(r[3]) : "r"(a) : "memory"); }
__device__ __forceinline__ void ldsm4t(uint32_t (&r)[4], uint32_t a) { asm volatile("ldmatrix.sync.aligned.m8n8.x4.trans.shared.b16 {%0,%1,%2,%3}, [%4];" : "=r"(r[0]), "=r"(r[1]), "=r"(r[2]), "=r"(r[3]) : "r"(a) : "memory"); }
__device__ __forceinline__ void ldsm2t(uint32_t& r0, uint32_t& r1, uint32_t a) { asm volatile("ldmatrix.sync.aligned.m8n8.x2.trans.shared.b16 {%0,%1}, [%2];" : "=r"(r0), "=r"(r1) : "r"(a) : "memory"); }
__device__ __forceinline__ void stsm4t(uint32_t a, uint32_t r0, uint32_t r1, uint32_t r2, uint32_t r3) { asm volatile("stmatrix.sync.aligned.m8n8.x4.trans.shared.b16 [%0], {%1,%2,%3,%4};" :: "r"(a), "r"(r0), "r"(r1), "r"(r2), "r"(r3) : "memory"); }
__device__ __forceinline__ void stsm4(uint32_t a, uint32_t r0, uint32_t r1, uint32_t r2, uint32_t r3) { asm volatile("stmatrix.sync.aligned.m8n8.x4.shared.b16 [%0], {%1,%2,%3,%4};" :: "r"(a), "r"(r0), "r"(r1), "r"(r2), "r"(r3) : "memory"); }
__device__ __forceinline__ void stsm2(uint32_t a, uint32_t r0, uint32_t r1) { asm volatile("stmatrix.sync.aligned.m8n8.x2.shared.b16 [%0], {%1,%2};" :: "r"(a), "r"(r0), "r"(r1) : "memory"); }
__device__ __forceinline__ void stsm2t(uint32_t a, uint32_t r0, uint32_t r1) { asm volatile("stmatrix.sync.aligned.m8n8.x2.trans.shared.b16 [%0], {%1,%2};" :: "r"(a), "r"(r0), "r"(r1) : "memory"); }
__device__ __forceinline__ uint4 ldg128(const void* p) { uint4 v; asm volatile("ld.global.nc.v4.u32 {%0,%1,%2,%3}, [%4];" : "=r"(v.x), "=r"(v.y), "=r"(v.z), "=r"(v.w) : "l"(p)); return v; }
__device__ __forceinline__ uint32_t ldg16(const void* p) { unsigned short v; asm volatile("ld.global.nc.u16 %0, [%1];" : "=h"(v) : "l"(p)); return v; }
__device__ __forceinline__ uint32_t opaque(uint32_t v) { uint32_t r; asm volatile("mov.b32 %0, %1;" : "=r"(r) : "r"(v)); return r; }
__device__ __forceinline__ void mma_f16(float (&d)[4], const uint32_t (&a)[4], uint32_t b0, uint32_t b1) {
    asm volatile("mma.sync.aligned.m16n8k16.row.col.f32.f16.f16.f32 {%0,%1,%2,%3}, {%4,%5,%6,%7}, {%8,%9}, {%0,%1,%2,%3};"
        : "+f"(d[0]), "+f"(d[1]), "+f"(d[2]), "+f"(d[3]) : "r"(a[0]), "r"(a[1]), "r"(a[2]), "r"(a[3]), "r"(b0), "r"(b1));
}
__device__ __forceinline__ void mma_f16_z(float (&d)[4], const uint32_t (&a)[4], uint32_t b0, uint32_t b1) {
    asm volatile("mma.sync.aligned.m16n8k16.row.col.f32.f16.f16.f32 {%0,%1,%2,%3}, {%4,%5,%6,%7}, {%8,%9}, {%10,%10,%10,%10};"
        : "=f"(d[0]), "=f"(d[1]), "=f"(d[2]), "=f"(d[3]) : "r"(a[0]), "r"(a[1]), "r"(a[2]), "r"(a[3]), "r"(b0), "r"(b1), "f"(0.f));
}
__device__ __forceinline__ void mma_bf16(float (&d)[4], uint32_t a0, uint32_t a1, uint32_t a2, uint32_t a3, uint32_t b0, uint32_t b1) {
    asm volatile("mma.sync.aligned.m16n8k16.row.col.f32.bf16.bf16.f32 {%0,%1,%2,%3}, {%4,%5,%6,%7}, {%8,%9}, {%0,%1,%2,%3};"
        : "+f"(d[0]), "+f"(d[1]), "+f"(d[2]), "+f"(d[3]) : "r"(a0), "r"(a1), "r"(a2), "r"(a3), "r"(b0), "r"(b1));
}
__device__ __forceinline__ void mma_bf16_k8(float (&d)[4], uint32_t a0, uint32_t a1, uint32_t b0) {
    asm volatile("mma.sync.aligned.m16n8k8.row.col.f32.bf16.bf16.f32 {%0,%1,%2,%3}, {%4,%5}, {%6}, {%0,%1,%2,%3};"
        : "+f"(d[0]), "+f"(d[1]), "+f"(d[2]), "+f"(d[3]) : "r"(a0), "r"(a1), "r"(b0));
}
__device__ __forceinline__ uint32_t pack_f16(float lo, float hi) { uint32_t r; asm("cvt.rn.f16x2.f32 %0, %1, %2;" : "=r"(r) : "f"(hi), "f"(lo)); return r; }
__device__ __forceinline__ uint32_t pack_bf16(float lo, float hi) { uint32_t r; asm("cvt.rn.bf16x2.f32 %0, %1, %2;" : "=r"(r) : "f"(hi), "f"(lo)); return r; }
__device__ __forceinline__ float bf_lo(uint32_t v) { return __uint_as_float(v << 16); }
__device__ __forceinline__ float bf_hi(uint32_t v) { return __uint_as_float(v & 0xFFFF0000u); }
__device__ __forceinline__ float bfr(float x) { return __uint_as_float(pack_bf16(0.f, x)); }
__device__ __forceinline__ uint32_t badd2(uint32_t a, uint32_t b) { uint32_t r; asm("add.rn.bf16x2 %0, %1, %2;" : "=r"(r) : "r"(a), "r"(b)); return r; }
__device__ __forceinline__ uint32_t bmul2(uint32_t a, uint32_t b) { uint32_t r; asm("mul.rn.bf16x2 %0, %1, %2;" : "=r"(r) : "r"(a), "r"(b)); return r; }
__device__ __forceinline__ uint32_t hadd2(uint32_t a, uint32_t b) { uint32_t r; asm("add.rn.f16x2 %0, %1, %2;" : "=r"(r) : "r"(a), "r"(b)); return r; }
__device__ __forceinline__ uint32_t hmul2(uint32_t a, uint32_t b) { uint32_t r; asm("mul.rn.f16x2 %0, %1, %2;" : "=r"(r) : "r"(a), "r"(b)); return r; }
__device__ __forceinline__ uint32_t hneg2(uint32_t a) { uint32_t r; asm("neg.f16x2 %0, %1;" : "=r"(r) : "r"(a)); return r; }
__device__ __forceinline__ float rcpf(float x) { float r; asm("rcp.approx.ftz.f32 %0, %1;" : "=f"(r) : "f"(x)); return r; }
__device__ __forceinline__ float sqrta(float x) { float r; asm("sqrt.approx.ftz.f32 %0, %1;" : "=f"(r) : "f"(x)); return r; }
__device__ __forceinline__ float ex2f(float x) { float r; asm("ex2.approx.ftz.f32 %0, %1;" : "=f"(r) : "f"(x)); return r; }
__device__ __forceinline__ void st_async4(uint32_t a, uint32_t x, uint32_t y, uint32_t z, uint32_t w, uint32_t mb) {
    asm volatile("st.async.shared::cluster.mbarrier::complete_tx::bytes.v4.u32 [%0], {%1,%2,%3,%4}, [%5];" :: "r"(a), "r"(x), "r"(y), "r"(z), "r"(w), "r"(mb) : "memory"); }
__device__ __forceinline__ void st_async1(uint32_t a, uint32_t x, uint32_t mb) {
    asm volatile("st.async.shared::cluster.mbarrier::complete_tx::bytes.u32 [%0], %1, [%2];" :: "r"(a), "r"(x), "r"(mb) : "memory"); }
__device__ __forceinline__ unsigned ld_rlx(const void* p) { unsigned v; asm volatile("ld.relaxed.gpu.global.u32 %0, [%1];" : "=r"(v) : "l"(p) : "memory"); return v; }
__device__ __forceinline__ unsigned ld_acq(const void* p) { unsigned v; asm volatile("ld.acquire.gpu.global.u32 %0, [%1];" : "=r"(v) : "l"(p) : "memory"); return v; }
__device__ __forceinline__ uint2 ld_rlx64(const void* p) { unsigned long long v; asm volatile("ld.relaxed.gpu.global.u64 %0, [%1];" : "=l"(v) : "l"(p) : "memory"); return make_uint2((unsigned)v, (unsigned)(v >> 32)); }
__device__ __forceinline__ void st_rlx128(void* p, uint32_t x, uint32_t y, uint32_t z, uint32_t w) {
    asm volatile("st.relaxed.gpu.global.v2.u64 [%0], {%1,%2};" :: "l"(p), "l"((unsigned long long)x | ((unsigned long long)y << 32)), "l"((unsigned long long)z | ((unsigned long long)w << 32)) : "memory"); }
__device__ __forceinline__ uint4 ld_rlx128(const void* p) { unsigned long long a, b; asm volatile("ld.relaxed.gpu.global.v2.u64 {%0,%1}, [%2];" : "=l"(a), "=l"(b) : "l"(p) : "memory"); return make_uint4((unsigned)a, (unsigned)(a >> 32), (unsigned)b, (unsigned)(b >> 32)); }
__device__ __forceinline__ void tma2d(uint32_t dst, const CUtensorMap* tm, int x, int y, uint32_t mb) {
    asm volatile("cp.async.bulk.tensor.2d.shared::cluster.global.mbarrier::complete_tx::bytes [%0], [%1, {%3, %4}], [%2];"
                 :: "r"(dst), "l"(tm), "r"(mb), "r"(x), "r"(y) : "memory");
}
__device__ __forceinline__ void cmul(float& xr, float& xi, float ar, float ai, float br, float bi) {
    const float r = fmaf(ar, br, -ai * bi), i = fmaf(ar, bi, ai * br); xr = r; xi = i;
}
__device__ __forceinline__ void csq(float& xr, float& xi, float ar, float ai) {
    const float r = fmaf(ar, ar, -ai * ai), i = (ar + ar) * ai; xr = r; xi = i;
}
__device__ __forceinline__ void cexp_s(float& zr, float& zi, float e2, float turns) {
    const float mag = ex2f(e2), r = (turns - rintf(turns)) * 6.283185307179586f;
    zr = mag * __cosf(r); zi = mag * __sinf(r);
}
__device__ __forceinline__ uint32_t ln_stats(float s1, float s2) {
    const float m = s1 * (1.f / D_);
    const float var = fmaxf(fmaf(s2, 1.f / D_, -m * m), 0.f);
    return pack_bf16(m, sqrta(bfr(bfr(var) + 1e-5f)));
}
__device__ __forceinline__ uint32_t rsplit(float rs) { const float h = bfr(rs); return pack_bf16(h, rs - h); }
__device__ __forceinline__ uint32_t norm2(uint32_t v, uint32_t mx, uint32_t hl) {
    uint32_t r;
    asm("{ .reg .b16 m, h, l, x; .reg .b32 m2, h2, l2, d, t; mov.b32 {m, x}, %2; mov.b32 {h, l}, %3; mov.b32 m2, {m, m}; mov.b32 h2, {h, h}; mov.b32 l2, {l, l};\n"
        "sub.rn.bf16x2 d, %1, m2; mul.rn.bf16x2 t, d, l2; fma.rn.bf16x2 %0, d, h2, t; }" : "=r"(r) : "r"(v), "r"(mx), "r"(hl));
    return r;
}
template <int N, int S>
__device__ __forceinline__ uint32_t rank4(uint32_t a, uint32_t key) {
    uint32_t r0 = 0, r1 = 0, r2 = 0, r3 = 0;
#pragma unroll
    for (int i = 0; i < N; i++) {
        const uint4 o = lds128(a + i * S);
        r0 += (key - o.x) >> 31; r1 += (key - o.y) >> 31; r2 += (key - o.z) >> 31; r3 += (key - o.w) >> 31;
    }
    return (r0 + r1) + (r2 + r3);
}
typedef uint32_t H2C;
__device__ __forceinline__ H2C splat(float r, float i) { return pack_f16(r, i); }
__device__ __forceinline__ void hcmul(uint32_t& xr, uint32_t& xi, uint32_t R, uint32_t I, H2C m) {
    asm("{ .reg .b16 a, b; .reg .b32 a2, b2, t; mov.b32 {a, b}, %4; mov.b32 a2, {a, a}; mov.b32 b2, {b, b};\n"
        "mul.rn.f16x2 t, %3, b2; neg.f16x2 t, t; fma.rn.f16x2 %0, %2, a2, t; mul.rn.f16x2 t, %3, a2; fma.rn.f16x2 %1, %2, b2, t; }"
        : "=&r"(xr), "=r"(xi) : "r"(R), "r"(I), "r"(m));
}
__device__ __forceinline__ void expand4(uint32_t are, uint32_t aim, uint32_t R0, uint32_t R1, uint32_t I0, uint32_t I1, H2C m4) {
    uint32_t R2, I2, R3, I3;
    hcmul(R2, I2, R0, I0, m4); hcmul(R3, I3, R1, I1, m4);
    sts128(are, R0, R1, R2, R3);
    sts128(aim, I0, I1, I2, I3);
}
__device__ __forceinline__ void expand8(uint32_t are, uint32_t aim, float sr, float si, float m1r, float m1i, float m2r, float m2i, H2C m4) {
    float r1, i1, r2, i2, r3, i3;
    cmul(r1, i1, sr, si, m1r, m1i); cmul(r2, i2, sr, si, m2r, m2i); cmul(r3, i3, r1, i1, m2r, m2i);
    expand4(are, aim, pack_f16(sr, r1), pack_f16(r2, r3), pack_f16(si, i1), pack_f16(i2, i3), m4);
}
__device__ __forceinline__ uint32_t comb4(uint32_t a, uint32_t b, uint32_t c, uint32_t d, uint32_t r01, uint32_t r23) {
    uint32_t x;
    asm("{ .reg .b16 h0, h1, h2, h3; .reg .b32 m0, m1, m2, m3, u, v; mov.b32 {h0, h1}, %5; mov.b32 {h2, h3}, %6;\n"
        "mov.b32 m0, {h0, h0}; mov.b32 m1, {h1, h1}; mov.b32 m2, {h2, h2}; mov.b32 m3, {h3, h3};\n"
        "mul.rn.f16x2 u, %2, m1; fma.rn.f16x2 u, %1, m0, u; mul.rn.f16x2 v, %4, m3; fma.rn.f16x2 v, %3, m2, v; add.rn.f16x2 %0, u, v; }"
        : "=r"(x) : "r"(a), "r"(b), "r"(c), "r"(d), "r"(r01), "r"(r23));
    return x;
}
__device__ __forceinline__ void put16(uint32_t a, uint32_t v) { sts16(a, v); sts16(a + 6, v); }

struct Params {
    const unsigned short *logdt, *dskip, *prm6[6], *x, *wr;
    __nv_bfloat16* out;
    Scratch* gs;
    unsigned zero;
};
__device__ __forceinline__ uint32_t tslot(uint32_t t) { return (t & 7) * 32 + ((t >> 4) & 24) + ((t >> 8) & 6) + ((t >> 6) & 1); }
#define CP(x) ((x) | zero)
#define ZF(x) ((x) & zero)
#define PIN(x) asm volatile("or.b32 %0, %0, %1;" : "+r"(x) : "r"(zero))
__device__ __forceinline__ void wgmma32(float (&d)[4][4], const uint32_t (&a)[4], unsigned long long ds) {
    asm volatile("wgmma.mma_async.sync.aligned.m64n32k16.f32.f16.f16 {%0,%1,%2,%3,%4,%5,%6,%7,%8,%9,%10,%11,%12,%13,%14,%15}, {%16,%17,%18,%19}, %20, 1, 1, 1, 0;"
        : "+f"(d[0][0]), "+f"(d[0][1]), "+f"(d[0][2]), "+f"(d[0][3]), "+f"(d[1][0]), "+f"(d[1][1]), "+f"(d[1][2]), "+f"(d[1][3]),
          "+f"(d[2][0]), "+f"(d[2][1]), "+f"(d[2][2]), "+f"(d[2][3]), "+f"(d[3][0]), "+f"(d[3][1]), "+f"(d[3][2]), "+f"(d[3][3])
        : "r"(a[0]), "r"(a[1]), "r"(a[2]), "r"(a[3]), "l"(ds));
}

__device__ __forceinline__ void finish(const Params& prm, uint32_t fo, uint32_t oo, const float (&v)[3], float cnt) {
    float x, y, z, w;
    asm volatile("atom.relaxed.gpu.global.add.v4.f32 {%0,%1,%2,%3}, [%4], {%5,%6,%7,%8};" : "=f"(x), "=f"(y), "=f"(z), "=f"(w)
                 : "l"((char*)prm.gs->fin + fo), "f"(v[0]), "f"(v[1]), "f"(v[2]), "f"(cnt) : "memory");
    if (w + cnt == 3.f * (NCL + 1)) {
        __nv_bfloat16* op = (__nv_bfloat16*)((char*)prm.out + oo);
        op[0] = __float2bfloat16(x + v[0]); op[1] = __float2bfloat16(y + v[1]); op[2] = __float2bfloat16(z + v[2]);
    }
}

__global__ void __cluster_dims__(CS, 1, 1) __launch_bounds__(NTHR, 1)
fused_kernel(const __grid_constant__ Params prm, const __grid_constant__ CUtensorMap tmG, const __grid_constant__ CUtensorMap tmU,
             const __grid_constant__ CUtensorMap tmD, const __grid_constant__ CUtensorMap tmO, const __grid_constant__ CUtensorMap tmX, const __grid_constant__ CUtensorMap tmH)
{
    extern __shared__ __align__(1024) unsigned char smem[];
    const int tid = threadIdx.x, lane = tid & 31, warp = __shfl_sync(~0u, tid >> 5, 0);
    const int c = blockIdx.x >> 3, q = blockIdx.x & 7;
    const int nslot = (c < NCL - 1) ? 5 : 2;
    const int d0 = 40 * c;
    const uint32_t sb = opaque((uint32_t)__cvta_generic_to_shared(smem));
    const uint32_t mb = sb + SM_MB;
    Scratch& g_s = *prm.gs;
    const unsigned& zero = prm.zero;
    STAMP(0);

    if (warp >= 20) {
        unsigned epoch = 0;
        if (warp == 20) {
            if (lane == 0) {
#pragma unroll
                for (int i = 0; i < 13; i++)
                    asm volatile("mbarrier.init.shared::cta.b64 [%0], %1;" :: "r"(mb + i * 8), "r"((i == MB_R || i < 2) ? 2 : i < 5 ? (nslot + 1) / 3 : i == MB_Y ? 1 + 4 * nslot : 1) : "memory");
                asm volatile("fence.mbarrier_init.release.cluster;" ::: "memory");
                arm(mb + MB_W1 * 8, 92160); arm(mb + MB_W2 * 8, nslot * 9216); arm(mb + MB_KEY * 8, 256); arm(mb + MB_GU * 8, nslot * 1024); arm(mb + MB_T * 8, 576 * XW);
                const int bytes = max(min(18, L_ - 18 * (int)blockIdx.x), 1) * (D_ * 2);
                arm(mb + MB_R * 8, bytes);
            }
            __syncwarp();
        } else if (warp == 22) {
            epoch = ld_rlx(&g_s.epoch);
            if (lane < 18 ? 18 * c + lane < 256 : lane < 31) (lane < 18 ? &g_s.acc[256 * q + 18 * c] : &g_s.fin[13 * (int)blockIdx.x - 18])[lane] = make_float4(0.f, 0.f, 0.f, 0.f);
        } else if (warp == 23 && lane == 0) asm volatile("prefetch.tensormap [%0];" :: "l"(&tmX) : "memory");
        asm volatile("barrier.cluster.arrive.relaxed.aligned;" ::: "memory");
        bar_sync(12, NTHR);
        uint4 wv = make_uint4(0, 0, 0, 0), wv2, wv3;
        if (warp == 22) {
            if (lane == 0) { sts32(sb + SM_SC + 28, epoch); asm volatile("mbarrier.arrive.shared::cta.b64 _, [%0];" :: "r"(mb + MB_R * 8) : "memory"); }
            epoch++;
            asm volatile("fence.acq_rel.gpu;" ::: "memory");
            __syncwarp();
            if (lane == 0) asm volatile("red.relaxed.gpu.global.add.u32 [%0], 1;" :: "l"(&g_s.zcnt) : "memory");
            STAMP(1);
            wv2 = ldg128((const uint4*)prm.wr + lane); wv3 = ldg128((const uint4*)prm.wr + 32 + lane);
            if (lane < 8) wv = ldg128((const uint4*)prm.wr + 64 + lane);
            if (lane < 5) {
                uint4 v = make_uint4(0, 0, 0, 0);
                if (lane < nslot) v = ldg128((const uint4*)(prm.wr + d0) + lane);
                sts128(sb + SM_DW + lane * 16, v.x, v.y, v.z, v.w);
            }
            __syncwarp();
            if (lane < 5) asm volatile("mbarrier.arrive.shared::cta.b64 _, [%0];" :: "r"(mb + (MB_X + lane) * 8) : "memory");
        }
        if (warp == 21) {
            if (lane == 0) { asm volatile("prefetch.tensormap [%0];" :: "l"(&tmG) : "memory"); asm volatile("prefetch.tensormap [%0];" :: "l"(&tmU) : "memory"); asm volatile("prefetch.tensormap [%0];" :: "l"(&tmD) : "memory"); }
            __syncwarp();
            bar_sync(0, 672);
            {
                const uint2 m = lds64(sb + SM_KG + min(lane, 19) * 8);
                unsigned Em = max(m.x, __shfl_xor_sync(~0u, m.x, 1));
                Em = max(Em, __shfl_xor_sync(~0u, Em, 2));
                const float f = __uint_as_float(max((int)(127 + m.x - Em), 0) << 23);
                float s0 = (float)(int)m.y * f;
                s0 += __shfl_xor_sync(~0u, s0, 1); s0 += __shfl_xor_sync(~0u, s0, 2);
                if (lane < 20) {
                    sts16(sb + SM_RK + lane * 2, pack_f16(f, 0.f));
                    sts32(sb + SM_SC + (lane & 28), Em * 0x00800080u);
                    put16(sb + SM_PN + (lane >> 2) * PN_SZ, pack_f16(s0 * (1.f / 16777216.f) + ldsf(sb + SM_DW + 96 + (lane & 28)) * __uint_as_float((254u - Em) << 23), 0.f));
                }
                __syncwarp();
            }
            bar_sync(15, 672);
            asm volatile("fence.proxy.async.shared::cta;" ::: "memory");
#pragma unroll 1
            for (int i = 0; i < 24; i++) {
                if (lane == 0) tma2d(sb + SM_WG + i * 3840, i < 12 ? &tmG : &tmU, 320 * c + 8 * nslot * q, 48 * (i < 12 ? i : i - 12), mb + MB_W1 * 8);
            }
            STAMP(1);
        } else {
        if (warp == 20) {
            if (lane == 0) {
                asm volatile("cp.async.bulk.shared::cluster.global.mbarrier::complete_tx::bytes [%0], [%1], %2, [%3];"
                             :: "r"(sb + SM_ROW), "l"(prm.x + min(18 * (int)blockIdx.x, L_ - 1) * D_), "r"(max(min(18, L_ - 18 * (int)blockIdx.x), 1) * (D_ * 2)), "r"(mb + MB_R * 8) : "memory");
            }
            __syncwarp();
            mbar_wait(mb + MB_R * 8);
            if (lane == 0) {
                asm volatile("cp.async.bulk.tensor.5d.shared::cluster.global.mbarrier::complete_tx::bytes [%0], [%1, {%3, %4, %5, %5, %5}], [%2];"
                             :: "r"(sb + SM_XTL), "l"(&tmX), "r"(mb + MB_T * 8), "r"(d0 & ~15), "r"(8 * q), "r"(0) : "memory");
            }
            STAMP(6);
        }
        {
            const int idx = lane * 3 + max(warp - 21, 0), sl = nslot - 1 - (idx >> 3), pe = (idx + q + 1) & 7;
            const uint32_t rb_ = mapa(sb, pe);
            uint32_t cd = rb_ + SM_U + 128 + q * UP + sl * US, cs = sb + SM_XT + 128 + (q & 3) * 16 + pe * YP + sl * YS, cm = rb_ + SM_MB + (MB_X + sl) * 8;
            int act = sl < 0 ? 0 : pe == q ? -1 : 1;
            PIN(cd); PIN(cs); PIN(cm); PIN(act);
            asm volatile("barrier.cluster.wait.aligned;" ::: "memory");
            mbar_wait(mb + MB_R * 8);
            bar_sync(13, 608);
            asm volatile("fence.proxy.async.shared::cta;" ::: "memory");
            if (act < 0) arm(cm, 7 * 512);
            __syncwarp();
            if (act > 0)
                asm volatile("cp.async.bulk.shared::cluster.shared::cta.mbarrier::complete_tx::bytes [%0], [%1], 512, [%2];" :: "r"(cd), "r"(cs), "r"(cm) : "memory");
        }
        STAMP(1);
        if (warp == 20 && lane == 0) { asm volatile("prefetch.tensormap [%0];" :: "l"(&tmO) : "memory"); asm volatile("prefetch.tensormap [%0];" :: "l"(&tmH) : "memory"); }
        if (warp == 22) {
            __syncwarp();
            mbar_wait(mb + (MB_X + 1) * 8);
            const uint32_t old = (epoch & 1) ? 0u : 0x40004000u;
#pragma unroll
            for (int t = 0; t < 2; t++)
                if ((lane & 7) < 6) g_s.cand[((q * 8 + 4 * t + (lane >> 3)) * NCL + c) * 6 + (lane & 7)] = make_uint4(old, old, old, old);
            float a[4] = {0.f, 0.f, 0.f, 0.f};
            const uint32_t one = 0x3F803F80u;
            mma_bf16(a, one, one, one, one, wv.x, wv.y);  mma_bf16(a, one, one, one, one, wv.z, wv.w);
            mma_bf16(a, one, one, one, one, wv2.x, wv2.y); mma_bf16(a, one, one, one, one, wv2.z, wv2.w);
            mma_bf16(a, one, one, one, one, wv3.x, wv3.y); mma_bf16(a, one, one, one, one, wv3.z, wv3.w);
            float s = a[0] + a[1];
            s += __shfl_xor_sync(~0u, s, 1); s += __shfl_xor_sync(~0u, s, 2);
            stsf(sb + SM_SC + 24, s);
            __syncwarp();
            if (lane == 0) {
                int n = 0;
                while ((int)(ld_acq(&g_s.zcnt) - epoch * NCTA) < 0 && ++n < SPIN_LIMIT) __nanosleep(200);
                arm(mb + MB_Y * 8, 8 * 512 * nslot);
                if (blockIdx.x == 0) g_s.epoch = epoch;
            }
            STAMP(2);
        }
        if (warp == 23) {
#pragma unroll 1
            for (int kk = nslot - 1; kk >= 0; kk--) {
                __syncwarp();
                bar_sync(6 + kk, 160);
                if (lane == 0) { asm volatile("fence.proxy.async.shared::cta;" ::: "memory"); tma2d(sb + SM_FAR + kk * FAR_SZ, &tmD, 72 * q, 320 * c + 64 * kk, mb + MB_W2 * 8); }
            }
        }
        }
        __syncwarp();
        bar_sync(14, 768);
        if (tid == 640) {
            asm volatile("fence.proxy.async.shared::cta;" ::: "memory");
            asm volatile("cp.async.bulk.tensor.5d.global.shared::cta.bulk_group [%0, {%2, %4, %4, %4, %3}], [%1];" :: "l"(&tmH), "r"(sb + SM_XT + 16384), "r"(d0 + ((c & 1) ? 0 : 32)), "r"(8 * q), "r"(0) : "memory");
            asm volatile("cp.async.bulk.tensor.5d.global.shared::cta.bulk_group [%0, {%2, %4, %4, %4, %3}], [%1];" :: "l"(&tmO), "r"(sb + SM_XT), "r"(d0 + (c & 1) * 8), "r"(8 * q), "r"(0) : "memory");
            asm volatile("cp.async.bulk.commit_group;" ::: "memory");
        }
        __syncwarp();
        const uint32_t ft = (tid >> 4) & 7, fj = d0 / 3 + (lane & 15), tok = ~lds32(sb + SM_SEL + ft * 8) & 2047;
        float v[3], cnt = 0.f;
#pragma unroll
        for (int i = 0; i < 3; i++) {
            const uint32_t cl = 3 * fj + i - d0, cf = cl - (c & 1) * 8;
            const bool ok = cl < 8 * nslot && ((tok >> 3) & 7) == q;
            const uint32_t u = lds16(sb + SM_XT + (cf < 32 ? tslot(tok) * 64 + cf * 2 : 16384 + tslot(tok) * 16 + (cl & 7) * 2));
            v[i] = ok ? __uint_as_float(u << 16) : 0.f;
            if (ok) cnt += 1.f;
        }
        if (tid == 640) {
            asm volatile("cp.async.bulk.wait_group 0;" ::: "memory");
            asm volatile("fence.proxy.async.global;" ::: "memory");
            asm volatile("mbarrier.arrive.shared::cta.b64 _, [%0];" :: "r"(mb + MB_OUT * 8) : "memory");
        }
        __syncwarp();
        mbar_wait(mb + MB_OUT * 8);
        STAMP(5);
        if (cnt != 0.f) finish(prm, (ft * 192 + fj) * 16, (tok * D_ + 3 * fj) * 2, v, cnt);
        return;
    }

    const int g = lane >> 2, cq = lane & 3;
    const int k = warp >> 2, wq = warp & 3;
    const int trow = 18 * blockIdx.x + warp;
    const bool rowact = warp < 18 && trow < L_;
    const int dch = min(d0 + 8 * k + q, D_ - 1);
    uint32_t pv[6];
    const uint32_t pofs = opaque((dch * 128 + wq * 32 + lane) * 2);
#pragma unroll
    for (int i = 0; i < 6; i++) pv[i] = ldg16((const char*)prm.prm6[i] + pofs);
    const uint32_t pLdt = ldg16(prm.logdt + dch), pD = ldg16(prm.dskip + dch);
    const int tn = 16 * (warp & 15) + g;
    uint32_t xa[5], xb[5];
    asm volatile("barrier.cluster.arrive.relaxed.aligned;" ::: "memory");
    uint4* const st1p = &g_s.st1[(((trow >> 3) & 7) * 256 + ((trow >> 6) & 31) * 8 + (trow & 7)) * 2 + (lane >> 2)];
    const bool pub = rowact && (lane & 0x1B) == 0;
    if (pub) st_rlx128(st1p, 0, 0, 0, 0);
    {
        const uint32_t za = sb + SM_P + tid * 16;
        sts128(za, 0, 0, 0, 0);
        if (tid < (SM_MISC - SM_P) / 16 - 640) sts128(za + 10240, 0, 0, 0, 0);
        sts128(sb + SM_U + ((tid >> 3) & 7) * UP + k * US + (lane & 7) * 16, 0, 0, 0, 0);
    }
    bar_sync(12, NTHR);
    const uint32_t dep = lds32(sb + SM_P);
#define PV(x) __uint_as_float(__byte_perm(dep, x, 0x5410))
    STAMP(1);
    const uint32_t fb = sb + SM_FAR + k * FAR_SZ;
    const uint32_t pn = sb + SM_PN + k * PN_SZ, pf = sb + SM_PF + k * PF_SZ;
    unsigned epoch, t258;
    {
        const uint32_t kb = fb + wq * 3072;
        const uint32_t kl = kb + lane * 16;
        uint32_t Af[4][4];
        float sr, si, z1r, z1i, z2r, z2i, z4r, z4i, hr, hi_;
        {
            const float dt = bfr(ex2f(PV(pLdt) * 1.4426950408889634f));
            const float e2 = dt * PV(pv[0]) * 1.4426950408889634f, an = dt * PV(pv[1]);
            float ar, ai, br, bi, cr, ci, dr, di;
            { const float m = ex2f(e2 * 8.f); ar = m * __cosf(an * 8.f); ai = m * __sinf(an * 8.f); }
            csq(br, bi, ar, ai); csq(cr, ci, br, bi); csq(dr, di, cr, ci);
            const H2C m4 = splat(cr, ci);
            {
                float r3, i3;
                cmul(r3, i3, ar, ai, br, bi);
                expand4(kl, kl + 1024, pack_f16(1.f, ar), pack_f16(br, r3), pack_f16(0.f, ai), pack_f16(bi, i3), m4);
            }
            expand8(kl + 512, kl + 1536, dr, di, ar, ai, br, bi, m4);
            { const float m = ex2f(e2); z1r = m * __cosf(an); z1i = -m * __sinf(an); }
            cexp_s(hr, hi_, e2 * 128.f, an * (-128.f * 0.15915494309189535f));
            csq(z2r, z2i, z1r, z1i); csq(z4r, z4i, z2r, z2i);
            const uint32_t dep2 = lds32(sb + SM_P + 4);
#define PW(x) __uint_as_float(__byte_perm(dep2, x, 0x5410))
            cmul(sr, si, PW(pv[4]), PW(pv[5]), dt * PW(pv[2]), dt * PW(pv[3]));
            const unsigned E = min(max(__reduce_max_sync(~0u, __float_as_uint(fmaxf(fmaxf(fabsf(sr), fabsf(si)), fabsf(PW(pD)) * (1.f / 8192.f)))) >> 23, 1u), 253u);
            const float sc = __uint_as_float((254u - E) << 23);
            sr *= sc; si *= -sc;
            sts64(sb + SM_KG + warp * 8, E, __reduce_add_sync(~0u, __float2int_rn(sr * 16777216.f)));
            stsf(sb + SM_DW + 96 + k * 4, PW(pD));
        }
        __syncwarp();
#pragma unroll
        for (int ks = 0; ks < 4; ks++) ldsm4t(Af[ks], kb + (lane >> 3) * 512 + (lane & 7) * 16 + ks * 128);
        STAMP(2);
        const uint32_t la = kb + ((lane >> 3) & 1) * 512 + (lane >> 4) * 128 + (lane & 7) * 16;
        uint32_t b0[4], b1[4], b2[4], b3[4];
        auto ln1 = [&]() {
        mbar_wait(mb + MB_R * 8);
        epoch = lds32(sb + SM_SC + 28) + 1;
        {
            const uint32_t ra = sb + SM_ROW + warp * (D_ * 2);
            const uint4 r0 = lds128(ra + lane * 16), r1 = lds128(ra + 512 + lane * 16);
            const uint32_t rx[9] = {r0.x, r0.y, r0.z, r0.w, r1.x, r1.y, r1.z, r1.w, lds32(ra + 1024 + lane * 4)};
            float a0 = bf_lo(rx[0]), a1 = bf_hi(rx[0]), c0 = a0 * a0, c1 = a1 * a1;
#pragma unroll
            for (int i = 1; i < 9; i++) { const float l = bf_lo(rx[i]), h = bf_hi(rx[i]); a0 += l; a1 += h; c0 = fmaf(l, l, c0); c1 = fmaf(h, h, c1); }
            a0 += a1; c0 += c1;
            float s1 = ((lane & 1) ? c0 : a0) + __shfl_xor_sync(~0u, (lane & 1) ? a0 : c0, 1);
#pragma unroll
            for (int o = 2; o < 32; o <<= 1) s1 += __shfl_xor_sync(~0u, s1, o);
            const float s2 = __shfl_xor_sync(~0u, s1, 1);
            const uint32_t ms = ln_stats(s1, s2);
            const uint32_t p0 = __byte_perm(ms, epoch | 0x8000u, 0x5410), p1 = rsplit(rcpf(bf_hi(ms)));
            if (pub) st_rlx128(st1p, p0, p1, p0, p1);
        }
        mbar_wait(mb + MB_R * 8);
        STAMP(1);
        };
        const uint4* sp = &g_s.st1[(256 * q + tn) * 2];
        uint2 sa, sc;
        auto poll = [&]() { sa = ld_rlx64(sp); sc = ld_rlx64(sp + 16); };
        auto norm = [&]() {
        STAMP(3);
        if (warp < 16) {
            uint32_t va[5], vc[5];
            poll();
            mbar_wait(mb + MB_T * 8);
            {
                const uint32_t xt = sb + SM_XTL + (c & 1) * 16 + (36 * (warp & 7) + 9 * (warp >> 3) + g) * (2 * XW);
                uint4 a4 = lds128(xt + cq * 16), b4 = lds128(xt + cq * 16 + 36 * XW);
                va[0] = a4.x; va[1] = a4.y; va[2] = a4.z; va[3] = a4.w; va[4] = lds32(xt + 64 + cq * 4);
                vc[0] = b4.x; vc[1] = b4.y; vc[2] = b4.z; vc[3] = b4.w; vc[4] = lds32(xt + (64 + 36 * XW) + cq * 4);
            }
            const int d4 = 2 * (lane >> 3) + (lane & 1), d1_ = lane & 7;
            const uint32_t own = SM_U + 128 + q * (UP - YP), oth = SM_XT + 128 + (q & 3) * 16;
            uint32_t a4 = sb + warp * 32 + d4 * YP + (d4 == q ? own : oth) + ((lane & 7) >> 1) * YS;
            uint32_t a1 = sb + warp * 32 + d1_ * YP + (d1_ == q ? own : oth) + 4 * YS + (lane & 8) * 2;
            PIN(a4); PIN(a1);
            uint32_t tag = __byte_perm(epoch | 0x8000u, 0, 0x1010);
            PIN(tag);
            mbar_wait(mb + MB_T * 8);
            int n = 0;
            while (__byte_perm(sa.x, sc.x, 0x7632) != tag && ++n < SPIN_LIMIT) poll();
            STAMP(4);
#pragma unroll
            for (int i = 0; i < 5; i++) {
                va[i] = norm2(va[i], sa.x, sa.y); va[i] = pack_f16(bf_lo(va[i]), bf_hi(va[i]));
                vc[i] = norm2(vc[i], sc.x, sc.y); vc[i] = pack_f16(bf_lo(vc[i]), bf_hi(vc[i]));
            }
            stsm4t(a4, va[0], va[1], va[2], va[3]); stsm4t(a4 + 16, vc[0], vc[1], vc[2], vc[3]); stsm2t(a1, va[4], vc[4]);
            bar_arrive(13, 608);
            {
            const uint32_t xh = sb + SM_XTL + (c & 1) * 16 + (9 * __byte_perm(0x12100200, 0x13110301, g) + 72 * (warp & 1) + (warp >> 1)) * (2 * XW);
            const uint4 c4 = lds128(xh + cq * 16), d4_ = lds128(xh + cq * 16 + 72 * XW);
            xa[0] = c4.x; xa[1] = c4.y; xa[2] = c4.z; xa[3] = c4.w; xa[4] = lds32(xh + 64 + cq * 4);
            xb[0] = d4_.x; xb[1] = d4_.y; xb[2] = d4_.z; xb[3] = d4_.w; xb[4] = lds32(xh + (64 + 72 * XW) + cq * 4);
            }
        }
        STAMP(5);
        __syncwarp();
        bar_sync(15, 672);
        Af[0][0] |= lds32(sb + SM_P);
        };
        cmul(sr, si, sr, si, z1r, z1i);
        {
            const H2C h4 = splat(z4r, z4i);
            expand8(kl, kl + 512, sr, si, z1r, z1i, z2r, z2i, h4);
            cmul(sr, si, sr, si, hr, hi_);
            expand8(kl + 1024, kl + 1536, sr, si, z1r, z1i, z2r, z2i, h4);
        }
        __syncwarp();
        ldsm4t(b0, la); ldsm4t(b1, la + 256); ldsm4t(b2, la + 1024); ldsm4t(b3, la + 1280);
        cmul(z1r, z1i, z1r, z1i, hr, hi_);
        cmul(sr, si, sr, si, z1r, z1i);
        expand8(kl, kl + 512, sr, si, z2r, z2i, z4r, z4i, splat(hr, hi_));
        asm volatile("barrier.cluster.wait.aligned;" ::: "memory");
        bar_arrive(0, 672);
        ln1();
        csq(z1r, z1i, z1r, z1i);
        cmul(sr, si, sr, si, z1r, z1i);
        csq(z2r, z2i, hr, hi_);
        expand8(kl + 1024, kl + 1536, sr, si, z4r, z4i, hr, hi_, splat(z2r, z2i));
        csq(z1r, z1i, z1r, z1i);
        cmul(sr, si, sr, si, z1r, z1i);
        csq(z4r, z4i, z2r, z2i);
        expand8(kl + 2048, kl + 2560, sr, si, hr, hi_, z2r, z2i, splat(z4r, z4i));
        norm();
        {
            uint32_t c0[4], c1[4], c2[4], c3[4], e0[4], e1[4];
            float t[5][4];
            ldsm4t(c0, la); ldsm4t(c2, la + 1024);
            mma_f16_z(t[0], Af[0], b0[0], b0[1]);
            const uint32_t lb = la | (__float_as_uint(t[0][0]) & zero);
            mma_f16_z(t[1], Af[0], b2[0], b2[1]); mma_f16_z(t[2], Af[0], c0[0], c0[1]); mma_f16_z(t[3], Af[0], c2[0], c2[1]);
            ldsm4t(e0, lb + 2048); ldsm4t(c1, lb + 256); ldsm4t(c3, lb + 1280); ldsm4t(e1, lb + 2304);
            mma_f16(t[0], Af[1], b0[2], b0[3]); mma_f16(t[1], Af[1], b2[2], b2[3]); mma_f16(t[2], Af[1], c0[2], c0[3]); mma_f16(t[3], Af[1], c2[2], c2[3]);
            mma_f16(t[0], Af[2], b1[0], b1[1]); mma_f16(t[1], Af[2], b3[0], b3[1]);
            mma_f16_z(t[4], Af[0], e0[0], e0[1]);
            mma_f16(t[2], Af[2], c1[0], c1[1]); mma_f16(t[3], Af[2], c3[0], c3[1]);
            mma_f16(t[4], Af[1], e0[2], e0[3]);
            mma_f16(t[0], Af[3], b1[2], b1[3]); mma_f16(t[1], Af[3], b3[2], b3[3]);
            mma_f16(t[4], Af[2], e1[0], e1[1]);
            mma_f16(t[2], Af[3], c1[2], c1[3]); mma_f16(t[3], Af[3], c3[2], c3[3]);
            mma_f16(t[4], Af[3], e1[2], e1[3]);
            stsm4(kl + 1024, pack_f16(t[0][0], t[0][1]), pack_f16(t[0][2], t[0][3]), pack_f16(t[1][0], t[1][1]), pack_f16(t[1][2], t[1][3]));
            stsm2(kl + 1536, pack_f16(t[2][0], t[2][1]), pack_f16(t[2][2], t[2][3]));
            sts64(kb + lane * 8 + 1792, pack_f16(t[3][1], t[3][0]), pack_f16(t[3][3], t[3][2]));
            sts64(kb + lane * 8 + 2048, pack_f16(t[4][1], t[4][0]), pack_f16(t[4][3], t[4][2]));
        }
        bar_sync(1 + k, 128);
        const uint2 rr = lds64(opaque(sb + SM_RK + k * 8));
        const int tq = (wq + k + 2) & 3;
        const uint32_t ra = lane * 8 + opaque(fb + (tq == 1 ? 2048 : tq * 256 + 1024));
        auto comb = [&](uint32_t a, uint32_t& x, uint32_t& y) {
            const uint2 p0 = lds64(a), p1 = lds64(a + 3072), p2 = lds64(a + 6144), p3 = lds64(a + 9216);
            x = comb4(p0.x, p1.x, p2.x, p3.x, rr.x, rr.y); y = comb4(p0.y, p1.y, p2.y, p3.y, rr.x, rr.y);
        };
        uint32_t w0, w1;
        comb(ra, w0, w1);
        const bool last = lane == 31;
        if (tq == 0) {
            uint32_t v0, v1;
            comb(ra + 256, v0, v1);
            const uint32_t n0 = __shfl_sync(~0u, lane ? w0 : v0, lane + 1);
            uint32_t n1 = __shfl_sync(~0u, v0, lane + 1);
            if (last) n1 = v1 >> 16;
            sts128(pn + 12 + lane * 16, __byte_perm(w1, w0, 0x7610), __byte_perm(w1, 0, 0x1032), __byte_perm(n0, w1, 0x7610), __byte_perm(n0, 0, 0x1032));
            sts128(pn + 524 + lane * 16, __byte_perm(v1, v0, 0x7610), __byte_perm(v1, 0, 0x1032), __byte_perm(n1, v1, 0x7610), __byte_perm(n1, 0, 0x1032));
            if (lane == 0) { sts16(pn + 4, w0); sts32(pn + 8, __byte_perm(w0, 0, 0x1032)); }
        } else if (tq == 1) {
            const uint32_t ph = pf + P_H7 + (g & 1) * (2 * P_HS) + cq * 64 + (g >> 1) * 4 + (cq & 2) * 16, sw = (cq & 2) ? 0x3210 : 0x1032;
            w0 = __byte_perm(hmul2(w0, 0x18001800u), 0, sw); w1 = __byte_perm(hmul2(w1, 0x18001800u), 0, sw);
            const uint32_t pi = ph + 32 - (cq & 2) * 32;
            put16(ph, w0); put16(pi, w0 >> 16); put16(ph + 16, w1); put16(pi + 16, w1 >> 16);
        } else if (tq == 2) {
            uint32_t n = __shfl_sync(~0u, w0, lane == 30 ? 1 : lane + 2);
            if (last) { put16(pf, hmul2(w1, 0x18001800u) >> 16); w1 = hadd2(w1, hneg2(__byte_perm(w1, 0, 0x3232))); n = 0; }
            const bool od = lane & 1;
            const uint32_t pa = pn + 1036 + (lane >> 1) * 32 + (od ? 528 : 0), pb = pa + (od ? -16 : 16);
            const uint32_t u0 = od ? w1 : w0, x0 = od ? n : w1, u1 = od ? w0 : w1, x1 = od ? w1 : n;
            const uint32_t b0 = __byte_perm(u0, 0, 0x3232), b1 = __byte_perm(u1, 0, 0x3232);
            sts128(pa, __byte_perm(u0, 0, 0x1032), b0, b0, __byte_perm(x0, u0, 0x7610));
            sts128(pb, __byte_perm(u1, 0, 0x1032), b1, b1, __byte_perm(x1, u1, 0x7610));
        } else {
            const uint32_t pa = pf + ((g & 1) ? 3 * P_GS : P_GS) + cq * 32 + (g >> 1) * 4;
            const uint32_t pb = pa + ((g & 1) ? 4 - 3 * P_GS : P_GS);
            w0 = hmul2(w0, 0x18001800u); w1 = hmul2(w1, 0x18001800u);
            put16(pa, w0 >> 16); put16(pb, w0); put16(pa + 16, w1 >> 16); put16(pb + 16, w1);
            if (last) put16(pf + P_H7 + P_HS, w1);
        }
        bar_sync(1 + k, 128);
        t258 = w0;
    }
    STAMP(6);

    mbar_wait(mb + (MB_X + k) * 8);
    STAMP(7);
    if (k < nslot) {
        const int role = (wq + k) & 3;
        const uint32_t ub = sb + SM_U + k * US + 128;
        const uint32_t l16 = lane * 16, tz = opaque((lane & 28) - 8 * cq), tz4 = tz * 4;
        if (role) {
            const uint32_t al = cq * (2 * UP + 32) + tz4, au = opaque(ub + (3 - role) * 128), a1 = al + au, a0 = (cq ? al : al + (8 * UP - 16)) + au - 2 * UP;
            const uint4 q0 = lds128(a0), q1 = lds128(a0 + UP), q2 = lds128(a1), q3 = lds128(a1 + UP);
            const uint32_t U[16] = {q0.x, q0.y, q0.z, q0.w, q1.x, q1.y, q1.z, q1.w, q2.x, q2.y, q2.z, q2.w, q3.x, q3.y, q3.z, q3.w};
            uint32_t V[14], Q[14], R4[12], T[8];
#pragma unroll
            for (int i = 2; i < 14; i++) { V[i] = __byte_perm(U[i], U[i + 1], 0x5432); Q[i] = hadd2(U[i], V[i]); }
            const uint32_t rb = l16 + opaque(fb + (3 - role) * 512);
#pragma unroll
            for (int i = 0; i < 8; i++) T[i] = hadd2(V[5 + i], Q[6 + i]);
            sts128(rb + F_E3, T[0], T[1], T[2], T[3]); sts128(rb + F_O3 + 16, T[4], T[5], T[6], T[7]);
            asm volatile("{ .reg .pred p; setp.ne.u32 p, %10, 1; @p st.shared.v4.u32 [%0], {%2,%3,%4,%5}; @p st.shared.v4.u32 [%1], {%6,%7,%8,%9}; }"
                         :: "r"(rb + F_E2), "r"(rb + F_O2), "r"(Q[6]), "r"(Q[7]), "r"(Q[8]), "r"(Q[9]), "r"(Q[10]), "r"(Q[11]), "r"(Q[12]), "r"(Q[13]), "r"(role) : "memory");
#pragma unroll
            for (int i = 2; i < 12; i++) R4[i] = hadd2(Q[i], Q[i + 1]);
#pragma unroll
            for (int i = 0; i < 8; i++) T[i] = hadd2(R4[3 + i], U[5 + i]);
            sts128(rb + F_O5, T[0], T[1], T[2], T[3]); sts128(rb + F_E5, T[4], T[5], T[6], T[7]);
            if (role != 1) {
                uint32_t S[8];
#pragma unroll
                for (int i = 0; i < 8; i++) S[i] = hadd2(R4[2 + i], i < 7 ? T[i + 1] : hadd2(R4[11], U[13]));
                sts128(rb + F_O9, S[0], S[1], S[2], S[3]); sts128(rb + F_E9 + 16, S[4], S[5], S[6], S[7]);
#pragma unroll
                for (int i = 0; i < 8; i++) S[i] = hadd2(T[i], hadd2(V[2 + i], V[5 + i]));
                sts128(rb + F_E7, S[0], S[1], S[2], S[3]); sts128(rb + F_O7, S[4], S[5], S[6], S[7]);
            }
        } else if (lane == 0) {
            const uint4 m = lds128(ub + 23 * 16 + 7 * UP);
            const uint32_t U[6] = {lds32(ub + 23 * 16 + 6 * UP + 12), m.x, m.y, m.z, m.w, lds32(ub + 24 * 16)};
            uint32_t Q[5];
#pragma unroll
            for (int i = 0; i < 5; i++) Q[i] = hadd2(U[i], __byte_perm(U[i], U[i + 1], 0x5432));
            sts128(fb + F_O5 + 96 * 16, hadd2(hadd2(Q[0], Q[1]), U[2]), hadd2(hadd2(Q[1], Q[2]), U[3]), hadd2(hadd2(Q[2], Q[3]), U[4]), hadd2(hadd2(Q[3], Q[4]), U[5]));
            sts128(fb + F_O3, 0, 0, 0, 0); sts128(fb + F_E9, 0, 0, 0, 0);
            sts16(pn + 258 * 4, t258);
        }
        bar_sync(1 + k, 128);
        float acc[4][4];
        uint32_t Q[4][4];
        {
            const int h = role & 1, part = role >> 1;
            float fa[7][4];
            uint32_t B[3][4];
            const uint32_t po = tz + opaque(pf + part * (2 * P_GS)), ba = l16 + opaque(fb + (part == h ? 0 : F_O5 + h * 16));
#pragma unroll
            for (int s = 1; s >= 0; s--) {
#pragma unroll
                for (int i = 0; i < 3; i++) { Q[i][0] = lds32(po + (s * P_GS + i * 64)); if (i < 2) Q[i][1] = lds32(po + (s * P_GS + i * 64 + 32)); }
#pragma unroll
                for (int i = 0; i < 3; i++) ldsm4t(B[i], ba + (s * F_E3 + i * 512));
#pragma unroll
                for (int i = 0; i < 3; i++) { Q[i][3] = CP(Q[i][0]); if (i) Q[i][2] = CP(Q[i - 1][1]); }
                Q[0][2] = ZF(s ? tz : Q[0][0]); Q[2][1] = ZF(s ? l16 : Q[2][0]);
#pragma unroll
                for (int dl = 0; dl < 3; dl++)
#pragma unroll
                    for (int ap = 0; ap < 6 - dl; ap++) {
                        if (s == 1 && dl == 0) mma_f16_z(fa[ap + 1], Q[0], B[ap >> 1][2 * (ap & 1)], B[ap >> 1][2 * (ap & 1) + 1]);
                        else mma_f16(fa[ap + 1 + dl], Q[dl], B[ap >> 1][2 * (ap & 1)], B[ap >> 1][2 * (ap & 1) + 1]);
                    }
            }
#pragma unroll 1
            for (int s = role; s == 1; s++) {
                ldsm2t(B[0][0], B[0][1], fb + ((lane & 15) == 15 ? F_O5 : F_O3));
#pragma unroll
                for (int dl = 1; dl < 3; dl++) mma_f16(fa[dl], Q[dl], B[0][0], B[0][1]);
            }
            const uint32_t bh = l16 + opaque(fb + F_E7 + h * F_H + part * 2048), ph = tz + opaque(pf + P_H7 + part * (2 * P_HS));
#pragma unroll 1
            for (int s = part; s == 1; s++) {
                Q[2][1] = ZF(Q[2][3]); Q[2][2] = ZF(Q[2][2]); Q[2][0] = lds32(ph - P_HS);
                ldsm4t(B[0], bh - 1024); ldsm4t(B[1], bh - 512);
                Q[2][3] = CP(Q[2][0]);
#pragma unroll
                for (int ap = 0; ap < 4; ap++) mma_f16(fa[ap + 3], Q[2], B[ap >> 1][2 * (ap & 1)], B[ap >> 1][2 * (ap & 1) + 1]);
            }
            {
                Q[0][2] = ZF(tid);
#pragma unroll
                for (int i = 0; i < 4; i++) { Q[i][0] = lds32(ph + i * 64); Q[i][1] = lds32(ph + (i * 64 + 32)); }
                ldsm4t(B[0], bh); ldsm4t(B[1], bh + 512);
#pragma unroll
                for (int i = 0; i < 4; i++) { Q[i][3] = CP(Q[i][0]); if (i) Q[i][2] = CP(Q[i - 1][1]); }
#pragma unroll
                for (int dl = 0; dl < 4; dl++)
#pragma unroll
                    for (int ap = 0; ap < 4 - dl; ap++) mma_f16(fa[ap + 3 + dl], Q[dl], B[ap >> 1][2 * (ap & 1)], B[ap >> 1][2 * (ap & 1) + 1]);
            }
            const uint32_t da = (cq * 2048 + tz4) + opaque(fb + role * 128);
            bar_sync(1 + k, 128);
#pragma unroll
            for (int i = 1; i < 4; i++)
                stsm4(da + i * 512, pack_f16(fa[2 * i - 1][0], fa[2 * i - 1][1]), pack_f16(fa[2 * i - 1][2], fa[2 * i - 1][3]),
                      pack_f16(fa[2 * i][0], fa[2 * i][1]), pack_f16(fa[2 * i][2], fa[2 * i][3]));
            asm("shl.b32 %0, 0x6000, %1;" : "=r"(Q[0][0]) : "r"(tz4));
            Q[0][1] = ZF(Q[0][0]); Q[0][2] = ZF(tz4); Q[0][3] = CP(Q[0][0]);
            const uint32_t ra = l16 + opaque(fb + wq * 2016);
            acc[0][0] = acc[0][1] = acc[0][2] = acc[0][3] = 0.f;
            if (wq == 3) {
                const uint32_t uw = lds32(ub), kw = lds32(pf);
                const float2 uf = __half22float2(*(const __half2*)&uw);
                if ((lane | 4) == 31) acc[0][3] = (lane == 31 ? uf.x + uf.y : uf.x) * (__low2float(*(const __half2*)&kw) * 512.f);
            }
            bar_sync(1 + k, 128);
#pragma unroll
            for (int i = 1; i < 4; i++) {
                ldsm4(B[0], ra + i * 512);
                mma_f16_z(acc[i], Q[0], hadd2(B[0][0], B[0][2]), hadd2(B[0][1], B[0][3]));
            }
        }
        bar_arrive(6 + k, 160);
        STAMP(8);
        const uint32_t inv = lds32(opaque(sb + SM_SC + k * 4));
        const uint32_t yd = l16 + opaque(mapa(sb, 2 * wq) + (SM_XT + 128 + q * YP + k * YS + (k >> 2) * (q >> 1) * 16));
        {
            uint32_t pu = opaque(pn + 64 * (wq - 3));
#define pp (tz + pu)
            const uint32_t dlo = (((ub + 6 * UP) & 0x3FFFF) >> 4) | ((UP >> 4) << 16);
            uint32_t R[4][4];
            unsigned long long ds[4];
#pragma unroll
            for (int i = 0; i < 4; i++) asm volatile("mov.b64 %0, {%1, %2};" : "=l"(ds[i]) : "r"(dlo - i * (2 * UP >> 4)), "r"(8 | zero));
            auto loadQ = [&](uint32_t (&X)[4][4], uint32_t prev) {
#pragma unroll
                for (int i = 0; i < 4; i++) { X[i][0] = lds32(pp + i * 64); X[i][1] = lds32(pp + i * 64 + 32); }
                X[0][2] = CP(prev);
#pragma unroll
                for (int i = 0; i < 4; i++) { X[i][3] = CP(X[i][0]); if (i) X[i][2] = CP(X[i - 1][1]); }
                pu += 256;
            };
            auto issue = [&](uint32_t (&X)[4][4]) {
                asm volatile("wgmma.fence.sync.aligned;" ::: "memory");
#pragma unroll
                for (int i = 0; i < 4; i++) wgmma32(acc, X[i], ds[i]);
                asm volatile("wgmma.commit_group.sync.aligned;" ::: "memory");
#pragma unroll
                for (int i = 0; i < 4; i++) asm volatile("{ .reg .b32 l, h; mov.b64 {l, h}, %0; add.u32 l, l, %1; mov.b64 %0, {l, h}; }" : "+l"(ds[i]) : "r"(~zero));
            };
#pragma unroll
            for (int i = 0; i < 4; i++) {
                Q[i][0] = Q[i][1] = 0;
                if (wq + i >= 3) { Q[i][0] = lds32(pp + i * 64); Q[i][1] = lds32(pp + i * 64 + 32); }
            }
            Q[0][2] = CP(0);
#pragma unroll
            for (int i = 0; i < 4; i++) { Q[i][3] = CP(Q[i][0]); if (i) Q[i][2] = CP(Q[i - 1][1]); }
            pu += 256;
#pragma unroll 1
            for (int dl = 0; dl < 4; dl++) {
                issue(Q);
                asm volatile("wgmma.wait_group.sync.aligned 1;" ::: "memory");
                loadQ(R, Q[3][1]);
                issue(R);
                asm volatile("wgmma.wait_group.sync.aligned 1;" ::: "memory");
                loadQ(Q, R[3][1]);
            }
            issue(Q);
            asm volatile("wgmma.wait_group.sync.aligned 0;" ::: "memory");
        }
        const uint32_t pstep = mapa(sb, 1) - mapa(sb, 0), ym = mapa(mb + MB_Y * 8, 2 * wq);
#pragma unroll
        for (int e = 0; e < 2; e++)
            st_async4(yd + e * pstep, bmul2(pack_bf16(acc[0][2 * e], acc[0][2 * e + 1]), inv), bmul2(pack_bf16(acc[1][2 * e], acc[1][2 * e + 1]), inv),
                      bmul2(pack_bf16(acc[2][2 * e], acc[2][2 * e + 1]), inv), bmul2(pack_bf16(acc[3][2 * e], acc[3][2 * e + 1]), inv), ym + e * pstep);
        if (lane == 0) asm volatile("mbarrier.arrive.shared::cta.b64 _, [%0];" :: "r"(mb + MB_Y * 8) : "memory");
    }
    STAMP(9);
    uint32_t ha[5], hb[5];
    if (warp < 16) {
        const uint4 wk = lds128(sb + SM_DW + cq * 16);
        uint32_t sel[5] = {wk.x, wk.y, wk.z, wk.w, lds32(sb + SM_DW + 64 + cq * 4)}, sel2[5];
#pragma unroll
        for (int i = 0; i < 5; i++) {
            if (!(g & 1)) sel[i] = 0x3F803F80u;
            sel2[i] = sel[i]; PIN(sel2[i]);
        }
        const uint32_t y4 = sb + SM_XT + 128 + warp * 32 + (2 * (lane >> 3) + (lane & 1)) * YP + ((lane & 7) >> 1) * YS;
        const uint32_t y1 = sb + SM_XT + 128 + warp * 32 + (lane & 7) * YP + 4 * YS + (lane & 8) * 2 + (lane & 6) * 8;
        uint32_t ao = (256 * q + tn) * 16, hta = sb + SM_HT + tn * 80;
        PIN(ao); PIN(hta);
        mbar_wait(mb + MB_Y * 8);
        STAMP(10);
        float ca[4] = {0.f, 0.f, 0.f, 0.f}, cb[4] = {0.f, 0.f, 0.f, 0.f};
        {
            uint32_t ya[4], yb[4], yc, yd;
            ldsm4t(ya, y4); ldsm4t(yb, y4 + 16); ldsm2t(yc, yd, y1);
#pragma unroll
            for (int i = 0; i < 4; i++) { ha[i] = badd2(xa[i], ya[i]); hb[i] = badd2(xb[i], yb[i]); }
            ha[4] = badd2(xa[4], yc); hb[4] = badd2(xb[4], yd);
        }
        if (nslot != 5) {
            ha[4] = hb[4] = 0;
            if (cq >= 2) ha[0] = ha[1] = ha[2] = ha[3] = hb[0] = hb[1] = hb[2] = hb[3] = 0;
        }
#pragma unroll
        for (int i = 0; i < 5; i++) { mma_bf16_k8(ca, ha[i], sel[i], ha[i]); mma_bf16_k8(cb, hb[i], sel2[i], hb[i]); }
        if (!(g & 1)) { ca[1] = ca[0]; cb[1] = cb[0]; }
        if (cq == (g >> 1)) {
            asm volatile("red.relaxed.gpu.global.add.v4.f32 [%0], {%1,%2,%3,%4};" :: "l"((char*)g_s.acc + ao), "f"(1.0f), "f"(ca[1]), "f"(ca[2]), "f"(ca[3]) : "memory");
            asm volatile("red.relaxed.gpu.global.add.v4.f32 [%0], {%1,%2,%3,%4};" :: "l"((char*)g_s.acc + ao + 128), "f"(1.0f), "f"(cb[1]), "f"(cb[2]), "f"(cb[3]) : "memory");
        }
        sts128(hta + cq * 16, ha[0], ha[1], ha[2], ha[3]); sts32(hta + 64 + cq * 4, ha[4]);
        sts128(hta + cq * 16 + 640, hb[0], hb[1], hb[2], hb[3]); sts32(hta + 704 + cq * 4, hb[4]);
        STAMP(11);
    }
    const int kq = warp / 5, mt = warp - 5 * kq;
    const int mi = lane >> 3, mr = lane & 7;
    const unsigned tk = (unsigned)tid / 72u, ck = tid - tk * 72;
    uint32_t A[9][4];
    auto loadA = [&]() {
        mbar_wait(mb + MB_W1 * 8);
        const uint32_t aa = sb + (mi & 1) * SM_WU + (8 * (mi >> 1) + mr) * 80 + (144 * 80 * kq + mt * 16);
#pragma unroll
        for (int s = 0; s < 9; s++) ldsm4t(A[s], aa + s * 1280);
    };
    const uint32_t par = (lds32(sb + SM_SC + 28) & 1) ? 0u : 0x40004000u;
    uint32_t pk0 = mapa(sb, 2 * cq), go = (ck / 5u + ck) * 16, co = ((q * 8 * NCL + c) * 6 + cq) * 16;
    PIN(pk0); PIN(go); PIN(co);
    if (warp < 8) {
        const float wsum = ldsf(sb + SM_SC + 24);
        const uint32_t idx = 2047 - (512 * ((tid >> 1) & 3) + 128 * ((tid >> 3) & 3) + 64 * (tid & 1) + 8 * q + warp);
        uint4 s; int n = 0;
        do { s = ld_rlx128(&g_s.acc[256 * q + tid]); } while (__uint_as_float(s.x) != (float)NCL && ++n < SPIN_LIMIT);
        STAMP(16);
        const uint32_t ox = __shfl_xor_sync(~0u, (lane & 1) ? s.z : s.w, 1);
        const uint32_t ms = ln_stats(__uint_as_float((lane & 1) ? ox : s.z), __uint_as_float(s.y));
        const float rs = rcpf(bf_hi(ms));
        const uint32_t rb = pack_bf16(0.f, fmaf(-bf_lo(ms), wsum, __uint_as_float((lane & 1) ? s.w : ox)) * rs);
        const uint32_t key = (((rb ^ (((int)rb >> 31) | 0x80000000u)) >> 16) << 11) | idx;
        sts32(sb + SM_KEY + tid * 4, key);
        __syncwarp();
        const uint32_t rank = rank4<8, 16>(sb + SM_KEY + warp * 128, key);
        asm volatile("{ .reg .pred p; setp.lt.u32 p, %0, 8; @p st.shared.u32 [%1], %2; }" :: "r"(rank), "r"(sb + SM_CAND + warp * 32 + rank * 4), "r"(key) : "memory");
        sts64(sb + SM_ST + tid * 8, ms, rsplit(rs));
    } else { mbar_wait(mb + MB_Y * 8); loadA(); }
    if (warp < 16) {
        STAMP(17);
        bar_sync(12, 512);
        STAMP(18);
        if (warp < 8) {
            const uint32_t mk = lds32(sb + SM_CAND + (tid >> 2) * 4);
            uint32_t rank = rank4<4, 64>(sb + SM_CAND + cq * 16, mk);
            rank += __shfl_xor_sync(~0u, rank, 1); rank += __shfl_xor_sync(~0u, rank, 2);
            if (rank < 8) {
                const uint32_t pk1 = pk0 + (mapa(sb, 1) - mapa(sb, 0));
                st_async1(pk0 + (SM_RK + q * 32) + rank * 4, mk, pk0 + (SM_MB + MB_KEY * 8));
                st_async1(pk1 + (SM_RK + q * 32) + rank * 4, mk, pk1 + (SM_MB + MB_KEY * 8));
                const uint32_t t = tslot(~mk | ((pk1 + rank * 4) & zero));
                const uint2 sv = lds64(sb + SM_ST + t * 8);
                const uint4 hv = lds128(sb + SM_HT + t * 80 + cq * 16);
                const uint32_t h4 = lds32(sb + SM_HT + t * 80 + 64 + cq * 4);
                const uint32_t rr = bmul2(sv.y, 0x3C803C80u);
                char* const dp = (char*)g_s.cand + (co + rank * 1440);
                st_rlx128(dp, (norm2(hv.x, sv.x, rr) & 0xBFFFBFFFu) | par, (norm2(hv.y, sv.x, rr) & 0xBFFFBFFFu) | par,
                          (norm2(hv.z, sv.x, rr) & 0xBFFFBFFFu) | par, (norm2(hv.w, sv.x, rr) & 0xBFFFBFFFu) | par);
                asm volatile("st.relaxed.gpu.global.u32 [%0], %1;" :: "l"((char*)g_s.cand + (co + rank * 1440 + 64 - cq * 12)), "r"((norm2(h4, sv.x, rr) & 0xBFFFBFFFu) | par) : "memory");
            }
            __syncwarp();
        }
        {
            const uint2 sa = lds64(sb + SM_ST + tn * 8), sbb = lds64(sb + SM_ST + tn * 8 + 64);
#pragma unroll
            for (int i = 0; i < 5; i++) { ha[i] = badd2(ha[i], norm2(ha[i], sa.x, sa.y)); hb[i] = badd2(hb[i], norm2(hb[i], sbb.x, sbb.y)); }
            const bool hf = (c & 1) && cq == 0;
            const uint32_t o16 = sb + SM_XT + (hf ? 16384 + tn * 16 : tn * 64 + (cq - (c & 1)) * 16), o4 = sb + SM_XT + ((c & 1) ? tn * 64 + 48 : 16384 + tn * 16) + cq * 4;
            sts128(o16, ha[0], ha[1], ha[2], ha[3]); sts32(o4, ha[4]);
            sts128(o16 + (hf ? 128 : 512), hb[0], hb[1], hb[2], hb[3]); sts32(o4 + ((c & 1) ? 512 : 128), hb[4]);
        }
        if (warp >= 8) {
            STAMP(19);
            mbar_wait(mb + MB_KEY * 8);
            STAMP(20);
            const uint32_t mk = lds32(sb + SM_RK - 256 + (tid >> 2) * 4);
            uint32_t rank = rank4<4, 64>(sb + SM_RK + cq * 16, mk);
            rank += __shfl_xor_sync(~0u, rank, 1); rank += __shfl_xor_sync(~0u, rank, 2);
            if (rank < 8) sts64(sb + SM_SEL + rank * 8, mk, ((tid >> 2) - 64) * 1440);
        }
    }
    bar_sync(11, 640);
    STAMP(12);

    const char* gp = (const char*)g_s.cand + (go + lds32(sb + SM_SEL + 4 + (tk & 7) * 8));
    uint4 hv = ld_rlx128(gp);
    if (warp < 8) loadA();
    const uint32_t ft = (unsigned)tid / 24u, fj = 24 * q + tid - ft * 24;
    const uint32_t key = lds32(sb + SM_SEL + (ft & 7) * 8), k16 = key << 5;
    float sig = bfr(rcpf(1.f + ex2f(__uint_as_float((k16 ^ (~((int)k16 >> 31) | 0x80000000u)) & 0xFFFF0000u) * -1.4426950408889634f)));
    uint32_t ra2 = sb + SM_RED2 + tid * 12 + ft * 16, fo = (ft * 192 + fj) * 16, oo = ((~key & 2047) * D_ + 3 * fj) * 2;
    uint32_t bx = sb + SM_XS + mr * 1168 + mi * 16 + 288 * kq, gd = mapa(sb, kq * (8 / NRED)) + (SM_GU + (q * nslot + mt) * 128) + lane * 4;
    PIN(ra2); PIN(fo); PIN(oo); PIN(bx); PIN(gd);
    asm volatile("" : "+f"(sig));
    {
        if (warp < 18) {
            int n = 0;
            while (true) {
                sts128(sb + SM_XS + tk * 16 + tid * 16, hv.x ^ par, hv.y ^ par, hv.z ^ par, hv.w ^ par);
                if (!__any_sync(~0u, ((hv.x ^ par) | (hv.y ^ par) | (hv.z ^ par) | (hv.w ^ par)) & 0x40004000u) || ++n >= SPIN_LIMIT) break;
                hv = ld_rlx128(gp);
            }
        }
    }
    bar_sync(14, 768);
    STAMP(13);
    {
        float c0[4] = {0.f, 0.f, 0.f, 0.f}, c1[4] = {0.f, 0.f, 0.f, 0.f}, c2[4] = {0.f, 0.f, 0.f, 0.f};
        uint32_t b[5][4];
#pragma unroll
        for (int s = 0; s < 4; s++) ldsm4(b[s], bx + s * 64);
        asm volatile("ldmatrix.sync.aligned.m8n8.x2.shared.b16 {%0,%1}, [%2];" : "=r"(b[4][0]), "=r"(b[4][1]) : "r"(bx + 256) : "memory");
        mma_bf16(c0, A[0][0], A[0][1], A[0][2], A[0][3], b[0][0], b[0][1]);
        mma_bf16(c1, A[1][0], A[1][1], A[1][2], A[1][3], b[0][2], b[0][3]);
        mma_bf16(c2, A[2][0], A[2][1], A[2][2], A[2][3], b[1][0], b[1][1]);
        mma_bf16(c0, A[3][0], A[3][1], A[3][2], A[3][3], b[1][2], b[1][3]);
        mma_bf16(c1, A[4][0], A[4][1], A[4][2], A[4][3], b[2][0], b[2][1]);
        mma_bf16(c2, A[5][0], A[5][1], A[5][2], A[5][3], b[2][2], b[2][3]);
        mma_bf16(c0, A[6][0], A[6][1], A[6][2], A[6][3], b[3][0], b[3][1]);
        mma_bf16(c1, A[7][0], A[7][1], A[7][2], A[7][3], b[3][2], b[3][3]);
        mma_bf16(c2, A[8][0], A[8][1], A[8][2], A[8][3], b[4][0], b[4][1]);
        sts128f(sb + SM_RED + tid * 16, c0[0] + c1[0] + c2[0], c0[1] + c1[1] + c2[1], c0[2] + c1[2] + c2[2], c0[3] + c1[3] + c2[3]);
    }
    bar_sync(1 + mt, 128);
    STAMP(21);
    if (mt < nslot && kq < NRED) {
        const uint32_t ra = sb + SM_RED + mt * 512 + lane * 16;
        const float4 p0 = lds128f(ra), p1 = lds128f(ra + 2560), p2 = lds128f(ra + 5120), p3 = lds128f(ra + 7680);
        const float g0 = bfr(((p0.x + p1.x) + (p2.x + p3.x)) * 64.f), g1 = bfr(((p0.y + p1.y) + (p2.y + p3.y)) * 64.f);
        const uint32_t sg = pack_bf16(g0 * rcpf(1.f + ex2f(g0 * -1.4426950408889634f)), g1 * rcpf(1.f + ex2f(g1 * -1.4426950408889634f)));
        const uint32_t gu = bmul2(sg, pack_bf16(((p0.z + p1.z) + (p2.z + p3.z)) * 64.f, ((p0.w + p1.w) + (p2.w + p3.w)) * 64.f));
        const uint32_t pstep = mapa(sb, 1) - mapa(sb, 0), gm = mapa(mb + MB_GU * 8, kq * (8 / NRED));
#pragma unroll
        for (int i = 0; i < 8 / NRED; i++) st_async1(gd + i * pstep, gu, gm + i * pstep);
    }
    mbar_wait(mb + MB_W2 * 8);
    {
        const uint32_t aa = sb + (8 * (mi >> 1) + mr) * 144 + (mi & 1) * 16 + (SM_FAR + 2304 * kq + mt * 32);
#pragma unroll
        for (int s = 0; s < 5; s++) ldsm4t(A[s], aa + s * FAR_SZ);
    }
    {
        uint32_t ba = sb + (SM_GU + 256 * kq) + (lane & 15) * 16 + (lane >> 4) * 1024, wa = sb + (SM_RED2 + kq * 2432 + mt * 64) + g * 4 + cq * 608;
        PIN(ba); PIN(wa);
        STAMP(22);
        mbar_wait(mb + MB_GU * 8);
        STAMP(23);
        float c0[4] = {0.f, 0.f, 0.f, 0.f}, c1[4] = {0.f, 0.f, 0.f, 0.f}, c2[4] = {0.f, 0.f, 0.f, 0.f};
        uint32_t b[2][4], b8, b9;
        ldsm4t(b[0], ba); ldsm4t(b[1], ba + 2048); ldsm2t(b8, b9, ba + 4096);
        mma_bf16(c0, A[0][0], A[0][1], A[0][2], A[0][3], b[0][0], b[0][1]);
        mma_bf16(c1, A[1][0], A[1][1], A[1][2], A[1][3], b[0][2], b[0][3]);
        if (nslot == 5) {
            mma_bf16(c2, A[4][0], A[4][1], A[4][2], A[4][3], b8, b9);
            mma_bf16(c0, A[2][0], A[2][1], A[2][2], A[2][3], b[1][0], b[1][1]);
            mma_bf16(c1, A[3][0], A[3][1], A[3][2], A[3][3], b[1][2], b[1][3]);
        }
        stsf(wa, c0[0] + c1[0] + c2[0]); stsf(wa + 304, c0[1] + c1[1] + c2[1]);
        if (mt < 4) { stsf(wa + 32, c0[2] + c1[2] + c2[2]); stsf(wa + 336, c0[3] + c1[3] + c2[3]); }
    }
    if (warp < 6) {
        float v[3];
        bar_sync(6, 640);
        STAMP(14);
#pragma unroll
        for (int i = 0; i < 3; i++) v[i] = ((ldsf(ra2 + i * 4) + ldsf(ra2 + i * 4 + 2432)) + (ldsf(ra2 + i * 4 + 4864) + ldsf(ra2 + i * 4 + 7296))) * sig;
        finish(prm, fo, oo, v, 3.f);
    } else bar_arrive(6, 640);
    STAMP(15);
}

#undef pp
typedef __nv_bfloat16 bf16;
__device__ bf16 f_n[L_ * D_], f_h[L_ * D_];
__device__ float f_k[D_ * L_], f_r[L_], f_gu[8 * F_];
__device__ int f_idx[8];
__device__ __forceinline__ float b2f(bf16 v) { return __bfloat162float(v); }
__global__ void fb_ln(const bf16* in, const bf16* wr, bf16* out) {
    const int t = blockIdx.x * 8 + (threadIdx.x >> 5), lane = threadIdx.x & 31;
    const bf16* r = (in ? in : f_h) + t * D_;
    float s1 = 0.f, s2 = 0.f, s3 = 0.f;
    for (int i = lane; i < D_; i += 32) s1 += b2f(r[i]);
    for (int o = 16; o; o >>= 1) s1 += __shfl_xor_sync(~0u, s1, o);
    for (int i = lane; i < D_; i += 32) { const float d = b2f(r[i]) - s1 / D_; s2 += d * d; }
    for (int o = 16; o; o >>= 1) s2 += __shfl_xor_sync(~0u, s2, o);
    const float m = bfr(s1 / D_), sd = bfr(sqrtf(bfr(bfr(s2 / D_) + 1e-5f)));
    for (int i = lane; i < D_; i += 32) {
        const float v = bfr(bfr(b2f(r[i]) - m) / sd);
        f_n[t * D_ + i] = __float2bfloat16(v);
        if (!in) { s3 += v * b2f(wr[i]); out[t * D_ + i] = __float2bfloat16(b2f(r[i]) + v); }
    }
    for (int o = 16; o; o >>= 1) s3 += __shfl_xor_sync(~0u, s3, o);
    f_r[t] = bfr(s3);
}
__global__ void fb_taps(Params p) {
    const int d = blockIdx.x >> 3, l = (blockIdx.x & 7) * 256 + threadIdx.x;
    const float dt = bfr(expf(bf_lo(p.logdt[d]))), lf = bfr((float)l);
    float k = 0.f;
    for (int n = d * 128; n < d * 128 + 128; n++) {
        float wr, wi, sn, cs;
        cmul(wr, wi, bf_lo(p.prm6[4][n]), bf_lo(p.prm6[5][n]), dt * bf_lo(p.prm6[2][n]), dt * bf_lo(p.prm6[3][n]));
        sincosf(dt * bf_lo(p.prm6[1][n]) * lf, &sn, &cs);
        k += expf(dt * bf_lo(p.prm6[0][n]) * lf) * (wr * cs - wi * sn);
    }
    f_k[l * D_ + d] = k;
}
__global__ void fb_conv(Params p) {
    const int t = blockIdx.x, d = threadIdx.x;
    float y = 0.f;
    for (int l = 0; l <= t; l++) y += f_k[l * D_ + d] * b2f(f_n[(t - l) * D_ + d]);
    f_h[t * D_ + d] = __float2bfloat16(bf_lo(p.x[t * D_ + d]) + bfr(bfr(y) + bfr(b2f(f_n[t * D_ + d]) * bf_lo(p.dskip[d]))));
}
__global__ void fb_top() {
    const int t = blockIdx.x * 256 + threadIdx.x;
    int rank = 0;
    for (int j = 0; j < L_; j++) rank += f_r[j] > f_r[t] || (f_r[j] == f_r[t] && j < t);
    if (rank < 8) f_idx[rank] = t;
}
__global__ void fb_ffn1(const bf16* wg, const bf16* wu) {
    const int f = blockIdx.x * 256 + threadIdx.x, j = blockIdx.y;
    float g = 0.f, u = 0.f;
    for (int i = 0; i < D_; i++) { const float v = b2f(f_n[f_idx[j] * D_ + i]); g += v * b2f(wg[i * F_ + f]); u += v * b2f(wu[i * F_ + f]); }
    g = bfr(g);
    f_gu[j * F_ + f] = bfr(bfr(g / (1.f + expf(-g))) * bfr(u));
}
__global__ void fb_ffn2(const bf16* wd, bf16* out) {
    const int d = threadIdx.x, j = blockIdx.x, t = f_idx[j];
    float y = 0.f;
    for (int f = 0; f < F_; f++) y += f_gu[j * F_ + f] * b2f(wd[f * D_ + d]);
    out[t * D_ + d] = __float2bfloat16(b2f(f_h[t * D_ + d]) + bfr(b2f(f_n[t * D_ + d]) + bfr(bfr(y) * bfr(1.f / (1.f + expf(-f_r[t]))))));
}

typedef CUresult (*EncodeFn)(CUtensorMap*, CUtensorMapDataType, cuuint32_t, void*, const cuuint64_t*, const cuuint64_t*,
                             const cuuint32_t*, const cuuint32_t*, CUtensorMapInterleave, CUtensorMapSwizzle,
                             CUtensorMapL2promotion, CUtensorMapFloatOOBfill);

void make_map(EncodeFn fn, CUtensorMap* tm, const void* p, int cols, int rows, int bc, int br) {
    cuuint64_t dims[2] = {(cuuint64_t)cols, (cuuint64_t)rows};
    cuuint64_t strides[1] = {(cuuint64_t)cols * 2};
    cuuint32_t box[2] = {(cuuint32_t)bc, (cuuint32_t)br};
    cuuint32_t es[2] = {1, 1};
    fn(tm, CU_TENSOR_MAP_DATA_TYPE_BFLOAT16, 2, const_cast<void*>(p), dims, strides, box, es, CU_TENSOR_MAP_INTERLEAVE_NONE,
       CU_TENSOR_MAP_SWIZZLE_NONE, CU_TENSOR_MAP_L2_PROMOTION_L2_128B, CU_TENSOR_MAP_FLOAT_OOB_FILL_NONE);
}

void make_map3(EncodeFn fn, CUtensorMap* tm, const void* p) {
    cuuint64_t dims[5] = {(cuuint64_t)D_, 64, 2, 2, 8};
    cuuint64_t strides[4] = {(cuuint64_t)D_ * 2, (cuuint64_t)D_ * 2048, (cuuint64_t)D_ * 128, (cuuint64_t)D_ * 256};
    cuuint32_t box[5] = {XW, 9, 2, 2, 8};
    cuuint32_t es[5] = {1, 1, 1, 1, 1};
    fn(tm, CU_TENSOR_MAP_DATA_TYPE_BFLOAT16, 5, const_cast<void*>(p), dims, strides, box, es, CU_TENSOR_MAP_INTERLEAVE_NONE,
       CU_TENSOR_MAP_SWIZZLE_NONE, CU_TENSOR_MAP_L2_PROMOTION_NONE, CU_TENSOR_MAP_FLOAT_OOB_FILL_NONE);
}

void make_map5(EncodeFn fn, CUtensorMap* tm, const void* p, int bc) {
    cuuint64_t dims[5] = {(cuuint64_t)D_, 2, 4, 4, 64};
    cuuint64_t strides[4] = {(cuuint64_t)D_ * 128, (cuuint64_t)D_ * 1024, (cuuint64_t)D_ * 256, (cuuint64_t)D_ * 2};
    cuuint32_t box[5] = {(cuuint32_t)bc, 2, 4, 4, 8};
    cuuint32_t es[5] = {1, 1, 1, 1, 1};
    fn(tm, CU_TENSOR_MAP_DATA_TYPE_BFLOAT16, 5, const_cast<void*>(p), dims, strides, box, es, CU_TENSOR_MAP_INTERLEAVE_NONE,
       CU_TENSOR_MAP_SWIZZLE_NONE, CU_TENSOR_MAP_L2_PROMOTION_NONE, CU_TENSOR_MAP_FLOAT_OOB_FILL_NONE);
}

}

extern "C" void kernel_launch(void* const* d_in, const int* in_sizes, int n_in, void* d_out, int out_size) {
    (void)in_sizes; (void)n_in; (void)out_size;
    void* fp = nullptr;
    cudaDriverEntryPointQueryResult qr;
    cudaGetDriverEntryPoint("cuTensorMapEncodeTiled", &fp, cudaEnableDefault, &qr);
    EncodeFn fn = (EncodeFn)fp;
    CUtensorMap tmG, tmU, tmD, tmO, tmX, tmH;
    make_map3(fn, &tmX, d_in[0]);
    make_map(fn, &tmG, d_in[11], F_, D_, 40, 48);
    make_map(fn, &tmU, d_in[12], F_, D_, 40, 48);
    make_map(fn, &tmD, d_in[13], D_, F_, 72, 64);
    make_map5(fn, &tmO, d_out, 32);
    make_map5(fn, &tmH, d_out, 8);
    Params p;
    p.x = (const unsigned short*)d_in[0];
    for (int i = 0; i < 6; i++) p.prm6[i] = (const unsigned short*)d_in[1 + i];
    p.logdt = (const unsigned short*)d_in[7]; p.dskip = (const unsigned short*)d_in[8];
    p.wr = (const unsigned short*)d_in[10];
    p.out = (__nv_bfloat16*)d_out;
    p.zero = 0;
    cudaGetSymbolAddress((void**)&p.gs, g_s);
    cudaFuncSetAttribute(fused_kernel, cudaFuncAttributeMaxDynamicSharedMemorySize, SM_TOTAL);
    static int nclusters = -1;
    if (nclusters < 0) {
        cudaLaunchConfig_t cfg = {};
        cudaLaunchAttribute at;
        at.id = cudaLaunchAttributeClusterDimension; at.val.clusterDim.x = CS; at.val.clusterDim.y = 1; at.val.clusterDim.z = 1;
        cfg.gridDim = dim3(NCTA); cfg.blockDim = dim3(NTHR); cfg.dynamicSmemBytes = SM_TOTAL; cfg.attrs = &at; cfg.numAttrs = 1;
        if (cudaOccupancyMaxActiveClusters(&nclusters, fused_kernel, &cfg) != cudaSuccess) { (void)cudaGetLastError(); nclusters = NCL; }
    }
    if (nclusters >= NCL && !FORCE_FALLBACK) {
        fused_kernel<<<NCTA, NTHR, SM_TOTAL>>>(p, tmG, tmU, tmD, tmO, tmX, tmH);
        return;
    }
    fb_ln<<<L_ / 8, 256>>>((const bf16*)d_in[0], nullptr, nullptr);
    fb_taps<<<D_ * 8, 256>>>(p);
    fb_conv<<<L_, D_>>>(p);
    fb_ln<<<L_ / 8, 256>>>(nullptr, (const bf16*)d_in[10], p.out);
    fb_top<<<L_ / 256, 256>>>();
    fb_ffn1<<<dim3(F_ / 256, 8), 256>>>((const bf16*)d_in[11], (const bf16*)d_in[12]);
    fb_ffn2<<<8, D_>>>((const bf16*)d_in[13], p.out);
}
```

```cpp
#include <cuda_runtime.h>
#include <cuda_bf16.h>
#include <cuda_fp16.h>
#include <cuda.h>
#include <stdint.h>

namespace {

constexpr int L_ = 2048, D_ = 576, F_ = 4608;
constexpr int NCL = 15, CS = 8, NCTA = NCL * CS, NTHR = 768;
#define FORCE_FALLBACK 0
constexpr int XW = 48, NRED = 2;
constexpr int SPIN_LIMIT = 1 << 22;

constexpr int SM_WG   = 0;
constexpr int SM_WU   = 46080;
constexpr int YP = 3392, YS = 656;
constexpr int UP = 3280, US = 656;
constexpr int SM_XT   = 92160;
constexpr int SM_U    = SM_XT + 8 * YP;
constexpr int SM_FAR  = SM_U + 8 * UP;
constexpr int FAR_SZ  = 12416;
constexpr int F_E5 = 0, F_O5 = 1536, F_E3 = 3088, F_O3 = 4624, F_E7 = 6176, F_E2 = F_E7 + 1024, F_E9 = F_E7 + 2048,
              F_H = 3088, F_O7 = F_E7 + F_H, F_O2 = F_E2 + F_H, F_O9 = F_E9 + F_H;
constexpr int SM_P    = SM_FAR + 5 * FAR_SZ;
constexpr int PN_SZ = 584 * 4, SM_PN = SM_P + 65 * 4;
constexpr int P_GS = 50 * 4, P_H7 = 200 * 4, P_HS = 74 * 4;
constexpr int PF_SZ = (200 + 222) * 4, SM_PF = SM_PN + 5 * PN_SZ + 36;
constexpr int SM_MISC = SM_PF + 5 * PF_SZ;
constexpr int SM_ST   = SM_MISC;
constexpr int SM_RK   = SM_ST + 2048;
constexpr int SM_SEL  = SM_FAR + FAR_SZ + 10240;
constexpr int SM_KG   = SM_RK + 320;
constexpr int SM_SC   = SM_KG + 160;
constexpr int SM_DW   = SM_SC + 32;
constexpr int SM_MB   = SM_DW + 160;
constexpr int SM_TOTAL = SM_MB + 128;
constexpr int SM_ROW  = SM_XT - 20736;
constexpr int SM_XTL  = SM_ROW - 576 * XW;
constexpr int SM_RED2 = SM_WG;
constexpr int SM_HT   = SM_P - 512;
constexpr int SM_KEY  = SM_FAR + 10240 + 128;
constexpr int SM_CAND = SM_KEY + 1024;
constexpr int SM_XS   = SM_U;
constexpr int SM_GU   = SM_XS + 9344;
constexpr int SM_RED  = SM_GU + 5632;
static_assert(F_O9 + 1024 <= FAR_SZ && FAR_SZ % 128 == 0, "far overflow");
static_assert(SM_RED + 10240 <= SM_FAR && SM_HT + 20496 <= SM_MISC, "alias overflow");
static_assert(SM_TOTAL <= 232448, "smem overflow");
static_assert(SM_FAR % 128 == 0 && SM_XT % 128 == 0 && SM_XTL % 128 == 0 && SM_P % 16 == 0 && SM_MISC % 16 == 0 && SM_MB % 8 == 0, "align");

enum { MB_X = 0, MB_W1 = 5, MB_W2 = 6, MB_KEY = 7, MB_GU = 8, MB_Y = 9, MB_OUT = 10, MB_T = 11, MB_R = 12 };

struct __align__(128) Scratch {
    unsigned epoch, zcnt, pad[30];
    uint4  st1[L_ * 2];
    float4 acc[L_];
    uint4  cand[64 * NCL * 6];
    float4 fin[8 * 192 + 24];
};
__device__ Scratch g_s;
#define STAMP(i)

__device__ __forceinline__ uint32_t mapa(uint32_t a, uint32_t r) { uint32_t d; asm("mapa.shared::cluster.u32 %0, %1, %2;" : "=r"(d) : "r"(a), "r"(r)); return d; }
__device__ __forceinline__ void mbar_wait(uint32_t mb) {
    asm volatile("{ .reg .pred p, q; .reg .u32 n; mov.u32 n, 0;\n"
                 "W_%=: mbarrier.try_wait.parity.shared::cta.b64 p, [%0], 0; add.u32 n, n, 1; setp.lt.and.u32 q, n, 65536, !p; @q bra W_%=; }" :: "r"(mb) : "memory");
}
__device__ __forceinline__ void arm(uint32_t mb, uint32_t bytes) { asm volatile("mbarrier.arrive.expect_tx.shared::cta.b64 _, [%0], %1;" :: "r"(mb), "r"(bytes) : "memory"); }
__device__ __forceinline__ void bar_sync(int id, int n) { asm volatile("bar.sync %0, %1;" :: "r"(id), "r"(n) : "memory"); }
__device__ __forceinline__ void bar_arrive(int id, int n) { asm volatile("bar.arrive %0, %1;" :: "r"(id), "r"(n) : "memory"); }
__device__ __forceinline__ uint32_t lds16(uint32_t a) { unsigned short v; asm volatile("ld.shared.u16 %0, [%1];" : "=h"(v) : "r"(a) : "memory"); return v; }
__device__ __forceinline__ uint32_t lds32(uint32_t a) { uint32_t v; asm volatile("ld.shared.u32 %0, [%1];" : "=r"(v) : "r"(a) : "memory"); return v; }
__device__ __forceinline__ uint2 lds64(uint32_t a) { uint2 v; asm volatile("ld.shared.v2.u32 {%0,%1}, [%2];" : "=r"(v.x), "=r"(v.y) : "r"(a) : "memory"); return v; }
__device__ __forceinline__ float ldsf(uint32_t a) { float v; asm volatile("ld.shared.f32 %0, [%1];" : "=f"(v) : "r"(a) : "memory"); return v; }
__device__ __forceinline__ uint4 lds128(uint32_t a) { uint4 v; asm volatile("ld.shared.v4.u32 {%0,%1,%2,%3}, [%4];" : "=r"(v.x), "=r"(v.y), "=r"(v.z), "=r"(v.w) : "r"(a) : "memory"); return v; }
__device__ __forceinline__ float4 lds128f(uint32_t a) { float4 v; asm volatile("ld.shared.v4.f32 {%0,%1,%2,%3}, [%4];" : "=f"(v.x), "=f"(v.y), "=f"(v.z), "=f"(v.w) : "r"(a) : "memory"); return v; }
__device__ __forceinline__ void sts16(uint32_t a, uint32_t v) { asm volatile("{ .reg .b16 l, h; mov.b32 {l, h}, %1; st.shared.b16 [%0], l; }" :: "r"(a), "r"(v) : "memory"); }
__device__ __forceinline__ void sts32(uint32_t a, uint32_t v) { asm volatile("st.shared.u32 [%0], %1;" :: "r"(a), "r"(v) : "memory"); }
__device__ __forceinline__ void sts64(uint32_t a, uint32_t x, uint32_t y) { asm volatile("st.shared.v2.u32 [%0], {%1,%2};" :: "r"(a), "r"(x), "r"(y) : "memory"); }
__device__ __forceinline__ void stsf(uint32_t a, float v) { asm volatile("st.shared.f32 [%0], %1;" :: "r"(a), "f"(v) : "memory"); }
__device__ __forceinline__ void sts128(uint32_t a, uint32_t x, uint32_t y, uint32_t z, uint32_t w) { asm volatile("st.shared.v4.u32 [%0], {%1,%2,%3,%4};" :: "r"(a), "r"(x), "r"(y), "r"(z), "r"(w) : "memory"); }
__device__ __forceinline__ void sts128f(uint32_t a, float x, float y, float z, float w) { asm volatile("st.shared.v4.f32 [%0], {%1,%2,%3,%4};" :: "r"(a), "f"(x), "f"(y), "f"(z), "f"(w) : "memory"); }
__device__ __forceinline__ void ldsm4(uint32_t (&r)[4], uint32_t a) { asm volatile("ldmatrix.sync.aligned.m8n8.x4.shared.b16 {%0,%1,%2,%3}, [%4];" : "=r"(r[0]), "=r"(r[1]), "=r"(r[2]), "=r"(r[3]) : "r"(a) : "memory"); }
__device__ __forceinline__ void ldsm4t(uint32_t (&r)[4], uint32_t a) { asm volatile("ldmatrix.sync.aligned.m8n8.x4.trans.shared.b16 {%0,%1,%2,%3}, [%4];" : "=r"(r[0]), "=r"(r[1]), "=r"(r[2]), "=r"(r[3]) : "r"(a) : "memory"); }
__device__ __forceinline__ void ldsm2t(uint32_t& r0, uint32_t& r1, uint32_t a) { asm volatile("ldmatrix.sync.aligned.m8n8.x2.trans.shared.b16 {%0,%1}, [%2];" : "=r"(r0), "=r"(r1) : "r"(a) : "memory"); }
__device__ __forceinline__ void stsm4t(uint32_t a, uint32_t r0, uint32_t r1, uint32_t r2, uint32_t r3) { asm volatile("stmatrix.sync.aligned.m8n8.x4.trans.shared.b16 [%0], {%1,%2,%3,%4};" :: "r"(a), "r"(r0), "r"(r1), "r"(r2), "r"(r3) : "memory"); }
__device__ __forceinline__ void stsm4(uint32_t a, uint32_t r0, uint32_t r1, uint32_t r2, uint32_t r3) { asm volatile("stmatrix.sync.aligned.m8n8.x4.shared.b16 [%0], {%1,%2,%3,%4};" :: "r"(a), "r"(r0), "r"(r1), "r"(r2), "r"(r3) : "memory"); }
__device__ __forceinline__ void stsm2(uint32_t a, uint32_t r0, uint32_t r1) { asm volatile("stmatrix.sync.aligned.m8n8.x2.shared.b16 [%0], {%1,%2};" :: "r"(a), "r"(r0), "r"(r1) : "memory"); }
__device__ __forceinline__ void stsm2t(uint32_t a, uint32_t r0, uint32_t r1) { asm volatile("stmatrix.sync.aligned.m8n8.x2.trans.shared.b16 [%0], {%1,%2};" :: "r"(a), "r"(r0), "r"(r1) : "memory"); }
__device__ __forceinline__ uint4 ldg128(const void* p) { uint4 v; asm volatile("ld.global.nc.v4.u32 {%0,%1,%2,%3}, [%4];" : "=r"(v.x), "=r"(v.y), "=r"(v.z), "=r"(v.w) : "l"(p)); return v; }
__device__ __forceinline__ uint32_t ldg16(const void* p) { unsigned short v; asm volatile("ld.global.nc.u16 %0, [%1];" : "=h"(v) : "l"(p)); return v; }
__device__ __forceinline__ uint32_t opaque(uint32_t v) { uint32_t r; asm volatile("mov.b32 %0, %1;" : "=r"(r) : "r"(v)); return r; }
__device__ __forceinline__ void mma_f16(float (&d)[4], const uint32_t (&a)[4], uint32_t b0, uint32_t b1) {
    asm volatile("mma.sync.aligned.m16n8k16.row.col.f32.f16.f16.f32 {%0,%1,%2,%3}, {%4,%5,%6,%7}, {%8,%9}, {%0,%1,%2,%3};"
        : "+f"(d[0]), "+f"(d[1]), "+f"(d[2]), "+f"(d[3]) : "r"(a[0]), "r"(a[1]), "r"(a[2]), "r"(a[3]), "r"(b0), "r"(b1));
}
__device__ __forceinline__ void mma_f16_z(float (&d)[4], const uint32_t (&a)[4], uint32_t b0, uint32_t b1) {
    asm volatile("mma.sync.aligned.m16n8k16.row.col.f32.f16.f16.f32 {%0,%1,%2,%3}, {%4,%5,%6,%7}, {%8,%9}, {%10,%10,%10,%10};"
        : "=f"(d[0]), "=f"(d[1]), "=f"(d[2]), "=f"(d[3]) : "r"(a[0]), "r"(a[1]), "r"(a[2]), "r"(a[3]), "r"(b0), "r"(b1), "f"(0.f));
}
__device__ __forceinline__ void mma_bf16(float (&d)[4], uint32_t a0, uint32_t a1, uint32_t a2, uint32_t a3, uint32_t b0, uint32_t b1) {
    asm volatile("mma.sync.aligned.m16n8k16.row.col.f32.bf16.bf16.f32 {%0,%1,%2,%3}, {%4,%5,%6,%7}, {%8,%9}, {%0,%1,%2,%3};"
        : "+f"(d[0]), "+f"(d[1]), "+f"(d[2]), "+f"(d[3]) : "r"(a0), "r"(a1), "r"(a2), "r"(a3), "r"(b0), "r"(b1));
}
__device__ __forceinline__ void mma_bf16_k8(float (&d)[4], uint32_t a0, uint32_t a1, uint32_t b0) {
    asm volatile("mma.sync.aligned.m16n8k8.row.col.f32.bf16.bf16.f32 {%0,%1,%2,%3}, {%4,%5}, {%6}, {%0,%1,%2,%3};"
        : "+f"(d[0]), "+f"(d[1]), "+f"(d[2]), "+f"(d[3]) : "r"(a0), "r"(a1), "r"(b0));
}
__device__ __forceinline__ uint32_t pack_f16(float lo, float hi) { uint32_t r; asm("cvt.rn.f16x2.f32 %0, %1, %2;" : "=r"(r) : "f"(hi), "f"(lo)); return r; }
__device__ __forceinline__ uint32_t pack_bf16(float lo, float hi) { uint32_t r; asm("cvt.rn.bf16x2.f32 %0, %1, %2;" : "=r"(r) : "f"(hi), "f"(lo)); return r; }
__device__ __forceinline__ float bf_lo(uint32_t v) { return __uint_as_float(v << 16); }
__device__ __forceinline__ float bf_hi(uint32_t v) { return __uint_as_float(v & 0xFFFF0000u); }
__device__ __forceinline__ float bfr(float x) { return __uint_as_float(pack_bf16(0.f, x)); }
__device__ __forceinline__ uint32_t badd2(uint32_t a, uint32_t b) { uint32_t r; asm("add.rn.bf16x2 %0, %1, %2;" : "=r"(r) : "r"(a), "r"(b)); return r; }
__device__ __forceinline__ uint32_t bmul2(uint32_t a, uint32_t b) { uint32_t r; asm("mul.rn.bf16x2 %0, %1, %2;" : "=r"(r) : "r"(a), "r"(b)); return r; }
__device__ __forceinline__ uint32_t hadd2(uint32_t a, uint32_t b) { uint32_t r; asm("add.rn.f16x2 %0, %1, %2;" : "=r"(r) : "r"(a), "r"(b)); return r; }
__device__ __forceinline__ uint32_t hmul2(uint32_t a, uint32_t b) { uint32_t r; asm("mul.rn.f16x2 %0, %1, %2;" : "=r"(r) : "r"(a), "r"(b)); return r; }
__device__ __forceinline__ uint32_t hneg2(uint32_t a) { uint32_t r; asm("neg.f16x2 %0, %1;" : "=r"(r) : "r"(a)); return r; }
__device__ __forceinline__ float rcpf(float x) { float r; asm("rcp.approx.ftz.f32 %0, %1;" : "=f"(r) : "f"(x)); return r; }
__device__ __forceinline__ float sqrta(float x) { float r; asm("sqrt.approx.ftz.f32 %0, %1;" : "=f"(r) : "f"(x)); return r; }
__device__ __forceinline__ float ex2f(float x) { float r; asm("ex2.approx.ftz.f32 %0, %1;" : "=f"(r) : "f"(x)); return r; }
__device__ __forceinline__ void st_async4(uint32_t a, uint32_t x, uint32_t y, uint32_t z, uint32_t w, uint32_t mb) {
    asm volatile("st.async.shared::cluster.mbarrier::complete_tx::bytes.v4.u32 [%0], {%1,%2,%3,%4}, [%5];" :: "r"(a), "r"(x), "r"(y), "r"(z), "r"(w), "r"(mb) : "memory"); }
__device__ __forceinline__ void st_async1(uint32_t a, uint32_t x, uint32_t mb) {
    asm volatile("st.async.shared::cluster.mbarrier::complete_tx::bytes.u32 [%0], %1, [%2];" :: "r"(a), "r"(x), "r"(mb) : "memory"); }
__device__ __forceinline__ unsigned ld_rlx(const void* p) { unsigned v; asm volatile("ld.relaxed.gpu.global.u32 %0, [%1];" : "=r"(v) : "l"(p) : "memory"); return v; }
__device__ __forceinline__ unsigned ld_acq(const void* p) { unsigned v; asm volatile("ld.acquire.gpu.global.u32 %0, [%1];" : "=r"(v) : "l"(p) : "memory"); return v; }
__device__ __forceinline__ uint2 ld_rlx64(const void* p) { unsigned long long v; asm volatile("ld.relaxed.gpu.global.u64 %0, [%1];" : "=l"(v) : "l"(p) : "memory"); return make_uint2((unsigned)v, (unsigned)(v >> 32)); }
__device__ __forceinline__ void st_rlx128(void* p, uint32_t x, uint32_t y, uint32_t z, uint32_t w) {
    asm volatile("st.relaxed.gpu.global.v2.u64 [%0], {%1,%2};" :: "l"(p), "l"((unsigned long long)x | ((unsigned long long)y << 32)), "l"((unsigned long long)z | ((unsigned long long)w << 32)) : "memory"); }
__device__ __forceinline__ uint4 ld_rlx128(const void* p) { unsigned long long a, b; asm volatile("ld.relaxed.gpu.global.v2.u64 {%0,%1}, [%2];" : "=l"(a), "=l"(b) : "l"(p) : "memory"); return make_uint4((unsigned)a, (unsigned)(a >> 32), (unsigned)b, (unsigned)(b >> 32)); }
__device__ __forceinline__ void tma2d(uint32_t dst, const CUtensorMap* tm, int x, int y, uint32_t mb) {
    asm volatile("cp.async.bulk.tensor.2d.shared::cluster.global.mbarrier::complete_tx::bytes [%0], [%1, {%3, %4}], [%2];"
                 :: "r"(dst), "l"(tm), "r"(mb), "r"(x), "r"(y) : "memory");
}
__device__ __forceinline__ void cmul(float& xr, float& xi, float ar, float ai, float br, float bi) {
    const float r = fmaf(ar, br, -ai * bi), i = fmaf(ar, bi, ai * br); xr = r; xi = i;
}
__device__ __forceinline__ void csq(float& xr, float& xi, float ar, float ai) {
    const float r = fmaf(ar, ar, -ai * ai), i = (ar + ar) * ai; xr = r; xi = i;
}
__device__ __forceinline__ void cexp_s(float& zr, float& zi, float e2, float turns) {
    const float mag = ex2f(e2), r = (turns - rintf(turns)) * 6.283185307179586f;
    zr = mag * __cosf(r); zi = mag * __sinf(r);
}
__device__ __forceinline__ uint32_t ln_stats(float s1, float s2) {
    const float m = s1 * (1.f / D_);
    const float var = fmaxf(fmaf(s2, 1.f / D_, -m * m), 0.f);
    return pack_bf16(m, sqrta(bfr(bfr(var) + 1e-5f)));
}
__device__ __forceinline__ uint32_t rsplit(float rs) { const float h = bfr(rs); return pack_bf16(h, rs - h); }
__device__ __forceinline__ uint32_t norm2(uint32_t v, uint32_t mx, uint32_t hl) {
    uint32_t r;
    asm("{ .reg .b16 m, h, l, x; .reg .b32 m2, h2, l2, d, t; mov.b32 {m, x}, %2; mov.b32 {h, l}, %3; mov.b32 m2, {m, m}; mov.b32 h2, {h, h}; mov.b32 l2, {l, l};\n"
        "sub.rn.bf16x2 d, %1, m2; mul.rn.bf16x2 t, d, l2; fma.rn.bf16x2 %0, d, h2, t; }" : "=r"(r) : "r"(v), "r"(mx), "r"(hl));
    return r;
}
template <int N, int S>
__device__ __forceinline__ uint32_t rank4(uint32_t a, uint32_t key, uint32_t m1) {
    uint32_t r0 = 0, r1 = 0, r2 = 0, r3 = 0;
#pragma unroll
    for (int i = 0; i < N; i++) {
        const uint4 o = lds128(a + i * S);
        r0 += (o.x * m1 + key) >> 31; r1 += (o.y * m1 + key) >> 31; r2 += (o.z * m1 + key) >> 31; r3 += (o.w * m1 + key) >> 31;
    }
    return (r0 + r1) + (r2 + r3);
}
typedef uint32_t H2C;
__device__ __forceinline__ H2C splat(float r, float i) { return pack_f16(r, i); }
__device__ __forceinline__ void hcmul(uint32_t& xr, uint32_t& xi, uint32_t R, uint32_t I, H2C m) {
    asm("{ .reg .b16 a, b; .reg .b32 a2, b2, t; mov.b32 {a, b}, %4; mov.b32 a2, {a, a}; mov.b32 b2, {b, b};\n"
        "mul.rn.f16x2 t, %3, b2; neg.f16x2 t, t; fma.rn.f16x2 %0, %2, a2, t; mul.rn.f16x2 t, %3, a2; fma.rn.f16x2 %1, %2, b2, t; }"
        : "=&r"(xr), "=r"(xi) : "r"(R), "r"(I), "r"(m));
}
__device__ __forceinline__ void expand4(uint32_t are, uint32_t aim, uint32_t R0, uint32_t R1, uint32_t I0, uint32_t I1, H2C m4) {
    uint32_t R2, I2, R3, I3;
    hcmul(R2, I2, R0, I0, m4); hcmul(R3, I3, R1, I1, m4);
    sts128(are, R0, R1, R2, R3);
    sts128(aim, I0, I1, I2, I3);
}
__device__ __forceinline__ void expand8(uint32_t are, uint32_t aim, float sr, float si, float m1r, float m1i, float m2r, float m2i, H2C m4) {
    float r1, i1, r2, i2, r3, i3;
    cmul(r1, i1, sr, si, m1r, m1i); cmul(r2, i2, sr, si, m2r, m2i); cmul(r3, i3, r1, i1, m2r, m2i);
    expand4(are, aim, pack_f16(sr, r1), pack_f16(r2, r3), pack_f16(si, i1), pack_f16(i2, i3), m4);
}
__device__ __forceinline__ uint32_t comb4(uint32_t a, uint32_t b, uint32_t c, uint32_t d, uint32_t r01, uint32_t r23) {
    uint32_t x;
    asm("{ .reg .b16 h0, h1, h2, h3; .reg .b32 m0, m1, m2, m3, u, v; mov.b32 {h0, h1}, %5; mov.b32 {h2, h3}, %6;\n"
        "mov.b32 m0, {h0, h0}; mov.b32 m1, {h1, h1}; mov.b32 m2, {h2, h2}; mov.b32 m3, {h3, h3};\n"
        "mul.rn.f16x2 u, %2, m1; fma.rn.f16x2 u, %1, m0, u; mul.rn.f16x2 v, %4, m3; fma.rn.f16x2 v, %3, m2, v; add.rn.f16x2 %0, u, v; }"
        : "=r"(x) : "r"(a), "r"(b), "r"(c), "r"(d), "r"(r01), "r"(r23));
    return x;
}
__device__ __forceinline__ void put16(uint32_t a, uint32_t v) { sts16(a, v); sts16(a + 6, v); }

struct Params {
    const unsigned short *logdt, *dskip, *prm6[6], *x, *wr;
    __nv_bfloat16* out;
    Scratch* gs;
    unsigned zero;
};
__device__ __forceinline__ uint32_t tslot(uint32_t t) { return (t & 7) * 32 + ((t >> 4) & 24) + ((t >> 8) & 6) + ((t >> 6) & 1); }
#define CP(x) ((x) | zero)
#define ZF(x) ((x) & zero)
#define PIN(x) asm volatile("or.b32 %0, %0, %1;" : "+r"(x) : "r"(zero))
__device__ __forceinline__ void wgmma32(float (&d)[4][4], const uint32_t (&a)[4], unsigned long long ds) {
    asm volatile("wgmma.mma_async.sync.aligned.m64n32k16.f32.f16.f16 {%0,%1,%2,%3,%4,%5,%6,%7,%8,%9,%10,%11,%12,%13,%14,%15}, {%16,%17,%18,%19}, %20, 1, 1, 1, 0;"
        : "+f"(d[0][0]), "+f"(d[0][1]), "+f"(d[0][2]), "+f"(d[0][3]), "+f"(d[1][0]), "+f"(d[1][1]), "+f"(d[1][2]), "+f"(d[1][3]),
          "+f"(d[2][0]), "+f"(d[2][1]), "+f"(d[2][2]), "+f"(d[2][3]), "+f"(d[3][0]), "+f"(d[3][1]), "+f"(d[3][2]), "+f"(d[3][3])
        : "r"(a[0]), "r"(a[1]), "r"(a[2]), "r"(a[3]), "l"(ds));
}

__device__ __forceinline__ void finish(const Params& prm, uint32_t fo, uint32_t oo, const float (&v)[3], float cnt) {
    float x, y, z, w;
    asm volatile("atom.relaxed.gpu.global.add.v4.f32 {%0,%1,%2,%3}, [%4], {%5,%6,%7,%8};" : "=f"(x), "=f"(y), "=f"(z), "=f"(w)
                 : "l"((char*)prm.gs->fin + fo), "f"(v[0]), "f"(v[1]), "f"(v[2]), "f"(cnt) : "memory");
    if (w + cnt == 3.f * (NCL + 1)) {
        __nv_bfloat16* op = (__nv_bfloat16*)((char*)prm.out + oo);
        op[0] = __float2bfloat16(x + v[0]); op[1] = __float2bfloat16(y + v[1]); op[2] = __float2bfloat16(z + v[2]);
    }
}

__global__ void __cluster_dims__(CS, 1, 1) __launch_bounds__(NTHR, 1)
fused_kernel(const __grid_constant__ Params prm, const __grid_constant__ CUtensorMap tmG, const __grid_constant__ CUtensorMap tmU,
             const __grid_constant__ CUtensorMap tmD, const __grid_constant__ CUtensorMap tmO, const __grid_constant__ CUtensorMap tmX, const __grid_constant__ CUtensorMap tmH)
{
    extern __shared__ __align__(1024) unsigned char smem[];
    const int tid = threadIdx.x, lane = tid & 31, warp = __shfl_sync(~0u, tid >> 5, 0);
    const int c = blockIdx.x >> 3, q = blockIdx.x & 7;
    const int nslot = (c < NCL - 1) ? 5 : 2;
    const int d0 = 40 * c;
    const uint32_t sb = opaque((uint32_t)__cvta_generic_to_shared(smem));
    const uint32_t mb = sb + SM_MB;
    Scratch& g_s = *prm.gs;
    const unsigned& zero = prm.zero;
    const uint32_t dch2 = min(d0 + q + ((tid >> 4) & ~7), D_ - 1) * 2;
    uint32_t pv[6], pLdt;
    const uint32_t pofs = opaque(dch2 * 128 + (tid & 127) * 2);
    pLdt = ldg16((const char*)prm.logdt + dch2);
#pragma unroll
    for (int i = 0; i < 2; i++) pv[i] = ldg16((const char*)prm.prm6[i] + pofs);
    STAMP(0);

    if (warp >= 20) {
        unsigned epoch = 0;
        if (warp == 20) {
            if (lane == 0) {
#pragma unroll
                for (int i = 0; i < 13; i++)
                    asm volatile("mbarrier.init.shared::cta.b64 [%0], %1;" :: "r"(mb + i * 8), "r"((i == MB_R || i < 2) ? 2 : i < 5 ? (nslot + 1) / 3 : i == MB_Y ? 1 + 4 * nslot : 1) : "memory");
                asm volatile("fence.mbarrier_init.release.cluster;" ::: "memory");
                arm(mb + MB_W1 * 8, 92160); arm(mb + MB_W2 * 8, nslot * 9216); arm(mb + MB_KEY * 8, 256); arm(mb + MB_GU * 8, nslot * 1024); arm(mb + MB_T * 8, 576 * XW);
                const int bytes = max(min(18, L_ - 18 * (int)blockIdx.x), 1) * (D_ * 2);
                arm(mb + MB_R * 8, bytes);
            }
            __syncwarp();
        } else if (warp == 22) {
            epoch = ld_rlx(&g_s.epoch);
            if (lane < 18 ? 18 * c + lane < 256 : lane < 31) (lane < 18 ? &g_s.acc[256 * q + 18 * c] : &g_s.fin[13 * (int)blockIdx.x - 18])[lane] = make_float4(0.f, 0.f, 0.f, 0.f);
        } else if (warp == 23 && lane == 0) asm volatile("prefetch.tensormap [%0];" :: "l"(&tmX) : "memory");
        asm volatile("barrier.cluster.arrive.relaxed.aligned;" ::: "memory");
        bar_sync(12, NTHR);
        uint4 wv = make_uint4(0, 0, 0, 0), wv2, wv3;
        if (warp == 22) {
            if (lane == 0) { sts32(sb + SM_SC + 28, epoch); asm volatile("mbarrier.arrive.shared::cta.b64 _, [%0];" :: "r"(mb + MB_R * 8) : "memory"); }
            epoch++;
            asm volatile("fence.acq_rel.gpu;" ::: "memory");
            __syncwarp();
            if (lane == 0) asm volatile("red.relaxed.gpu.global.add.u32 [%0], 1;" :: "l"(&g_s.zcnt) : "memory");
            STAMP(1);
            wv2 = ldg128((const uint4*)prm.wr + lane); wv3 = ldg128((const uint4*)prm.wr + 32 + lane);
            if (lane < 8) wv = ldg128((const uint4*)prm.wr + 64 + lane);
            if (lane < 5) {
                uint4 v = make_uint4(0, 0, 0, 0);
                if (lane < nslot) v = ldg128((const uint4*)(prm.wr + d0) + lane);
                sts128(sb + SM_DW + lane * 16, v.x, v.y, v.z, v.w);
            }
            __syncwarp();
            if (lane < 5) asm volatile("mbarrier.arrive.shared::cta.b64 _, [%0];" :: "r"(mb + (MB_X + lane) * 8) : "memory");
        }
        if (warp == 21) {
            if (lane == 0) { asm volatile("prefetch.tensormap [%0];" :: "l"(&tmG) : "memory"); asm volatile("prefetch.tensormap [%0];" :: "l"(&tmU) : "memory"); asm volatile("prefetch.tensormap [%0];" :: "l"(&tmD) : "memory"); }
            __syncwarp();
            const float dsk = bf_lo(ldg16(prm.dskip + min(d0 + 2 * (lane & 28) + q, D_ - 1)));
            bar_sync(0, 672);
            {
                const uint2 m = lds64(sb + SM_KG + min(lane, 19) * 8);
                unsigned Em = max(m.x, __shfl_xor_sync(~0u, m.x, 1));
                Em = max(Em, __shfl_xor_sync(~0u, Em, 2));
                Em = max(Em, min(__float_as_uint(fabsf(dsk) * (1.f / 8192.f)) >> 23, 253u));
                const float f = __uint_as_float(max((int)(127 + m.x - Em), 0) << 23);
                float s0 = (float)(int)m.y * f;
                s0 += __shfl_xor_sync(~0u, s0, 1); s0 += __shfl_xor_sync(~0u, s0, 2);
                if (lane < 20) {
                    sts16(sb + SM_RK + lane * 2, pack_f16(f, 0.f));
                    sts32(sb + SM_SC + (lane & 28), Em * 0x00800080u);
                    put16(sb + SM_PN + (lane >> 2) * PN_SZ, pack_f16(s0 * (1.f / 16777216.f) + dsk * __uint_as_float((254u - Em) << 23), 0.f));
                }
                __syncwarp();
            }
            bar_sync(15, 672);
            asm volatile("fence.proxy.async.shared::cta;" ::: "memory");
#pragma unroll 1
            for (int i = 0; i < 24; i++) {
                if (lane == 0) tma2d(sb + SM_WG + i * 3840, i < 12 ? &tmG : &tmU, 320 * c + 8 * nslot * q, 48 * (i < 12 ? i : i - 12), mb + MB_W1 * 8);
            }
            STAMP(1);
        } else {
        if (warp == 20) {
            if (lane == 0) {
                asm volatile("cp.async.bulk.shared::cluster.global.mbarrier::complete_tx::bytes [%0], [%1], %2, [%3];"
                             :: "r"(sb + SM_ROW), "l"(prm.x + min(18 * (int)blockIdx.x, L_ - 1) * D_), "r"(max(min(18, L_ - 18 * (int)blockIdx.x), 1) * (D_ * 2)), "r"(mb + MB_R * 8) : "memory");
            }
            __syncwarp();
            mbar_wait(mb + MB_R * 8);
            if (lane == 0) {
                asm volatile("cp.async.bulk.tensor.5d.shared::cluster.global.mbarrier::complete_tx::bytes [%0], [%1, {%3, %4, %5, %5, %5}], [%2];"
                             :: "r"(sb + SM_XTL), "l"(&tmX), "r"(mb + MB_T * 8), "r"(d0 & ~15), "r"(8 * q), "r"(0) : "memory");
            }
            STAMP(6);
        }
        {
            const int idx = lane * 3 + max(warp - 21, 0), sl = nslot - 1 - (idx >> 3), pe = (idx + q + 1) & 7;
            const uint32_t rb_ = mapa(sb, pe);
            uint32_t cd = rb_ + SM_U + 128 + q * UP + sl * US, cs = sb + SM_XT + 128 + (q & 3) * 16 + pe * YP + sl * YS, cm = rb_ + SM_MB + (MB_X + sl) * 8;
            int act = sl < 0 ? 0 : pe == q ? -1 : 1;
            PIN(cd); PIN(cs); PIN(cm); PIN(act);
            asm volatile("barrier.cluster.wait.aligned;" ::: "memory");
            mbar_wait(mb + MB_R * 8);
            bar_sync(13, 608);
            asm volatile("fence.proxy.async.shared::cta;" ::: "memory");
            if (act < 0) arm(cm, 7 * 512);
            __syncwarp();
            if (act > 0)
                asm volatile("cp.async.bulk.shared::cluster.shared::cta.mbarrier::complete_tx::bytes [%0], [%1], 512, [%2];" :: "r"(cd), "r"(cs), "r"(cm) : "memory");
        }
        STAMP(1);
        if (warp == 20 && lane == 0) { asm volatile("prefetch.tensormap [%0];" :: "l"(&tmO) : "memory"); asm volatile("prefetch.tensormap [%0];" :: "l"(&tmH) : "memory"); }
        if (warp == 22) {
            __syncwarp();
            mbar_wait(mb + (MB_X + 1) * 8);
            const uint32_t old = (epoch & 1) ? 0u : 0x40004000u;
#pragma unroll
            for (int t = 0; t < 2; t++)
                if ((lane & 7) < 6) g_s.cand[((q * 8 + 4 * t + (lane >> 3)) * NCL + c) * 6 + (lane & 7)] = make_uint4(old, old, old, old);
            float a[4] = {0.f, 0.f, 0.f, 0.f};
            const uint32_t one = 0x3F803F80u;
            mma_bf16(a, one, one, one, one, wv.x, wv.y);  mma_bf16(a, one, one, one, one, wv.z, wv.w);
            mma_bf16(a, one, one, one, one, wv2.x, wv2.y); mma_bf16(a, one, one, one, one, wv2.z, wv2.w);
            mma_bf16(a, one, one, one, one, wv3.x, wv3.y); mma_bf16(a, one, one, one, one, wv3.z, wv3.w);
            float s = a[0] + a[1];
            s += __shfl_xor_sync(~0u, s, 1); s += __shfl_xor_sync(~0u, s, 2);
            stsf(sb + SM_SC + 24, s);
            __syncwarp();
            if (lane == 0) {
                int n = 0;
                while ((int)(ld_acq(&g_s.zcnt) - epoch * NCTA) < 0 && ++n < SPIN_LIMIT) __nanosleep(200);
                arm(mb + MB_Y * 8, 8 * 512 * nslot);
                if (blockIdx.x == 0) g_s.epoch = epoch;
            }
            STAMP(2);
        }
        if (warp == 23) {
#pragma unroll 1
            for (int kk = nslot - 1; kk >= 0; kk--) {
                __syncwarp();
                bar_sync(6 + kk, 160);
                if (kk < 2) mbar_wait(mb + MB_W1 * 8);
                if (lane == 0) { asm volatile("fence.proxy.async.shared::cta;" ::: "memory"); tma2d(sb + SM_FAR + kk * FAR_SZ, &tmD, 72 * q, 320 * c + 64 * kk, mb + MB_W2 * 8); }
            }
        }
        }
        __syncwarp();
        bar_sync(14, 768);
        if (tid == 640) {
            asm volatile("fence.proxy.async.shared::cta;" ::: "memory");
            asm volatile("cp.async.bulk.tensor.5d.global.shared::cta.bulk_group [%0, {%2, %4, %4, %4, %3}], [%1];" :: "l"(&tmH), "r"(sb + SM_XT + 16384), "r"(d0 + ((c & 1) ? 0 : 32)), "r"(8 * q), "r"(0) : "memory");
            asm volatile("cp.async.bulk.tensor.5d.global.shared::cta.bulk_group [%0, {%2, %4, %4, %4, %3}], [%1];" :: "l"(&tmO), "r"(sb + SM_XT), "r"(d0 + (c & 1) * 8), "r"(8 * q), "r"(0) : "memory");
            asm volatile("cp.async.bulk.commit_group;" ::: "memory");
        }
        __syncwarp();
        const uint32_t ft = (tid >> 4) & 7, fj = d0 / 3 + (lane & 15), tok = ~lds32(sb + SM_SEL + ft * 8) & 2047;
        float v[3], cnt = 0.f;
#pragma unroll
        for (int i = 0; i < 3; i++) {
            const uint32_t cl = 3 * fj + i - d0, cf = cl - (c & 1) * 8;
            const bool ok = cl < 8 * nslot && ((tok >> 3) & 7) == q;
            const uint32_t u = lds16(sb + SM_XT + (cf < 32 ? tslot(tok) * 64 + cf * 2 : 16384 + tslot(tok) * 16 + (cl & 7) * 2));
            v[i] = ok ? __uint_as_float(u << 16) : 0.f;
            if (ok) cnt += 1.f;
        }
        if (tid == 640) {
            asm volatile("cp.async.bulk.wait_group 0;" ::: "memory");
            asm volatile("fence.proxy.async.global;" ::: "memory");
            asm volatile("mbarrier.arrive.shared::cta.b64 _, [%0];" :: "r"(mb + MB_OUT * 8) : "memory");
        }
        __syncwarp();
        mbar_wait(mb + MB_OUT * 8);
        STAMP(5);
        if (cnt != 0.f) finish(prm, (ft * 192 + fj) * 16, (tok * D_ + 3 * fj) * 2, v, cnt);
        return;
    }

    const int g = lane >> 2, cq = lane & 3;
    const int k = warp >> 2, wq = warp & 3;
    const int trow = 18 * blockIdx.x + warp;
    const bool rowact = warp < 18 && trow < L_;
#pragma unroll
    for (int i = 2; i < 6; i++) pv[i] = ldg16((const char*)prm.prm6[i] + pofs);
    const int tn = 16 * (warp & 15) + g;
    uint32_t xa[5], xb[5];
    asm volatile("barrier.cluster.arrive.relaxed.aligned;" ::: "memory");
    char* const st1p = (char*)g_s.st1 + opaque(((((trow >> 3) & 7) * 256 + ((trow >> 6) & 31) * 8 + (trow & 7)) * 8 + lane) * 4);
    const bool pub = rowact && (lane & 0x1B) == 0;
    if (pub) st_rlx128(st1p, 0, 0, 0, 0);
    {
        const uint32_t za = sb + SM_P + tid * 16;
        sts128(za, 0, 0, 0, 0);
        if (tid < (SM_MISC - SM_P) / 16 - 640) sts128(za + 10240, 0, 0, 0, 0);
        sts128(sb + SM_U + ((tid >> 3) & 7) * UP + k * US + (lane & 7) * 16, 0, 0, 0, 0);
    }
    bar_sync(12, NTHR);
    const uint32_t dep = lds32(sb + SM_P);
#define PV(x) __uint_as_float(__byte_perm(dep, x, 0x5410))
    STAMP(1);
    const uint32_t fb = sb + SM_FAR + k * FAR_SZ;
    const uint32_t pn = sb + SM_PN + k * PN_SZ, pf = sb + SM_PF + k * PF_SZ;
    unsigned epoch, t258;
    {
        const uint32_t kb = fb + wq * 3072;
        const uint32_t kl = kb + lane * 16;
        uint32_t Af[4][4];
        float sr, si, z1r, z1i, z2r, z2i, z4r, z4i, hr, hi_;
        {
            const float dt = bfr(ex2f(PV(pLdt) * 1.4426950408889634f));
            const float e2 = dt * PV(pv[0]) * 1.4426950408889634f, an = dt * PV(pv[1]);
            float ar, ai, br, bi, cr, ci, dr, di;
            { const float m = ex2f(e2 * 8.f); ar = m * __cosf(an * 8.f); ai = m * __sinf(an * 8.f); }
            csq(br, bi, ar, ai); csq(cr, ci, br, bi); csq(dr, di, cr, ci);
            const H2C m4 = splat(cr, ci);
            {
                float r3, i3;
                cmul(r3, i3, ar, ai, br, bi);
                expand4(kl, kl + 1024, pack_f16(1.f, ar), pack_f16(br, r3), pack_f16(0.f, ai), pack_f16(bi, i3), m4);
            }
            expand8(kl + 512, kl + 1536, dr, di, ar, ai, br, bi, m4);
            { const float m = ex2f(e2); z1r = m * __cosf(an); z1i = -m * __sinf(an); }
            cexp_s(hr, hi_, e2 * 128.f, an * (-128.f * 0.15915494309189535f));
            csq(z2r, z2i, z1r, z1i); csq(z4r, z4i, z2r, z2i);
            const uint32_t dep2 = lds32(sb + SM_P + 4);
#define PW(x) __uint_as_float(__byte_perm(dep2, x, 0x5410))
            cmul(sr, si, PW(pv[4]), PW(pv[5]), dt * PW(pv[2]), dt * PW(pv[3]));
            const unsigned E = min(max(__reduce_max_sync(~0u, __float_as_uint(fmaxf(fabsf(sr), fabsf(si)))) >> 23, 1u), 253u);
            const float sc = __uint_as_float((254u - E) << 23);
            sr *= sc; si *= -sc;
            sts64(sb + SM_KG + warp * 8, E, __reduce_add_sync(~0u, __float2int_rn(sr * 16777216.f)));
        }
        __syncwarp();
#pragma unroll
        for (int ks = 0; ks < 4; ks++) ldsm4t(Af[ks], kb + (lane >> 3) * 512 + (lane & 7) * 16 + ks * 128);
        STAMP(2);
        const uint32_t la = kb + ((lane >> 3) & 1) * 512 + (lane >> 4) * 128 + (lane & 7) * 16;
        uint32_t b0[4], b1[4], b2[4], b3[4];
        auto ln1 = [&]() {
        mbar_wait(mb + MB_R * 8);
        epoch = lds32(sb + SM_SC + 28) + 1;
        {
            const uint32_t ra = sb + SM_ROW + warp * (D_ * 2);
            const uint4 r0 = lds128(ra + lane * 16), r1 = lds128(ra + 512 + lane * 16);
            const uint32_t rx[9] = {r0.x, r0.y, r0.z, r0.w, r1.x, r1.y, r1.z, r1.w, lds32(ra + 1024 + lane * 4)};
            float a0 = bf_lo(rx[0]), a1 = bf_hi(rx[0]), c0 = a0 * a0, c1 = a1 * a1;
#pragma unroll
            for (int i = 1; i < 9; i++) { const float l = bf_lo(rx[i]), h = bf_hi(rx[i]); a0 += l; a1 += h; c0 = fmaf(l, l, c0); c1 = fmaf(h, h, c1); }
            a0 += a1; c0 += c1;
            float s1 = ((lane & 1) ? c0 : a0) + __shfl_xor_sync(~0u, (lane & 1) ? a0 : c0, 1);
#pragma unroll
            for (int o = 2; o < 32; o <<= 1) s1 += __shfl_xor_sync(~0u, s1, o);
            const float s2 = __shfl_xor_sync(~0u, s1, 1);
            const uint32_t ms = ln_stats(s1, s2);
            const uint32_t p0 = __byte_perm(ms, epoch | 0x8000u, 0x5410), p1 = rsplit(rcpf(bf_hi(ms)));
            if (pub) st_rlx128(st1p, p0, p1, p0, p1);
        }
        mbar_wait(mb + MB_R * 8);
        STAMP(1);
        };
        const uint4* sp = &g_s.st1[(256 * q + tn) * 2];
        uint2 sa, sc;
        auto poll = [&]() { sa = ld_rlx64(sp); sc = ld_rlx64(sp + 16); };
        auto norm = [&]() {
        STAMP(3);
        if (warp < 16) {
            uint32_t va[5], vc[5];
            poll();
            mbar_wait(mb + MB_T * 8);
            {
                const uint32_t xt = sb + SM_XTL + (c & 1) * 16 + (36 * (warp & 7) + 9 * (warp >> 3) + g) * (2 * XW);
                uint4 a4 = lds128(xt + cq * 16), b4 = lds128(xt + cq * 16 + 36 * XW);
                va[0] = a4.x; va[1] = a4.y; va[2] = a4.z; va[3] = a4.w; va[4] = lds32(xt + 64 + cq * 4);
                vc[0] = b4.x; vc[1] = b4.y; vc[2] = b4.z; vc[3] = b4.w; vc[4] = lds32(xt + (64 + 36 * XW) + cq * 4);
            }
            const int d4 = 2 * (lane >> 3) + (lane & 1), d1_ = lane & 7;
            const uint32_t own = SM_U + 128 + q * (UP - YP), oth = SM_XT + 128 + (q & 3) * 16;
            uint32_t a4 = sb + warp * 32 + d4 * YP + (d4 == q ? own : oth) + ((lane & 7) >> 1) * YS;
            uint32_t a1 = sb + warp * 32 + d1_ * YP + (d1_ == q ? own : oth) + 4 * YS + (lane & 8) * 2;
            PIN(a4); PIN(a1);
            uint32_t tag = __byte_perm(epoch | 0x8000u, 0, 0x1010);
            PIN(tag);
            mbar_wait(mb + MB_T * 8);
            int n = 0;
            while (__byte_perm(sa.x, sc.x, 0x7632) != tag && ++n < SPIN_LIMIT) poll();
            STAMP(4);
#pragma unroll
            for (int i = 0; i < 5; i++) {
                va[i] = norm2(va[i], sa.x, sa.y); va[i] = pack_f16(bf_lo(va[i]), bf_hi(va[i]));
                vc[i] = norm2(vc[i], sc.x, sc.y); vc[i] = pack_f16(bf_lo(vc[i]), bf_hi(vc[i]));
            }
            stsm4t(a4, va[0], va[1], va[2], va[3]); stsm4t(a4 + 16, vc[0], vc[1], vc[2], vc[3]); stsm2t(a1, va[4], vc[4]);
            bar_arrive(13, 608);
            {
            const uint32_t xh = sb + SM_XTL + (c & 1) * 16 + (9 * __byte_perm(0x12100200, 0x13110301, g) + 72 * (warp & 1) + (warp >> 1)) * (2 * XW);
            const uint4 c4 = lds128(xh + cq * 16), d4_ = lds128(xh + cq * 16 + 72 * XW);
            xa[0] = c4.x; xa[1] = c4.y; xa[2] = c4.z; xa[3] = c4.w; xa[4] = lds32(xh + 64 + cq * 4);
            xb[0] = d4_.x; xb[1] = d4_.y; xb[2] = d4_.z; xb[3] = d4_.w; xb[4] = lds32(xh + (64 + 72 * XW) + cq * 4);
            }
        }
        STAMP(5);
        __syncwarp();
        bar_sync(15, 672);
        Af[0][0] |= lds32(sb + SM_P);
        };
        cmul(sr, si, sr, si, z1r, z1i);
        {
            const H2C h4 = splat(z4r, z4i);
            expand8(kl, kl + 512, sr, si, z1r, z1i, z2r, z2i, h4);
            cmul(sr, si, sr, si, hr, hi_);
            expand8(kl + 1024, kl + 1536, sr, si, z1r, z1i, z2r, z2i, h4);
        }
        __syncwarp();
        ldsm4t(b0, la); ldsm4t(b1, la + 256); ldsm4t(b2, la + 1024); ldsm4t(b3, la + 1280);
        cmul(z1r, z1i, z1r, z1i, hr, hi_);
        cmul(sr, si, sr, si, z1r, z1i);
        expand8(kl, kl + 512, sr, si, z2r, z2i, z4r, z4i, splat(hr, hi_));
        asm volatile("barrier.cluster.wait.aligned;" ::: "memory");
        bar_arrive(0, 672);
        ln1();
        csq(z1r, z1i, z1r, z1i);
        cmul(sr, si, sr, si, z1r, z1i);
        csq(z2r, z2i, hr, hi_);
        expand8(kl + 1024, kl + 1536, sr, si, z4r, z4i, hr, hi_, splat(z2r, z2i));
        csq(z1r, z1i, z1r, z1i);
        cmul(sr, si, sr, si, z1r, z1i);
        csq(z4r, z4i, z2r, z2i);
        expand8(kl + 2048, kl + 2560, sr, si, hr, hi_, z2r, z2i, splat(z4r, z4i));
        norm();
        {
            uint32_t c0[4], c1[4], c2[4], c3[4], e0[4], e1[4];
            float t[6][4];
            ldsm4t(c0, la); ldsm4t(c2, la + 1024);
            mma_f16_z(t[0], Af[0], b0[0], b0[1]);
            const uint32_t lb = la | (__float_as_uint(t[0][0]) & zero);
            mma_f16_z(t[1], Af[0], b2[0], b2[1]); mma_f16_z(t[2], Af[0], c0[0], c0[1]); mma_f16_z(t[3], Af[0], c2[0], c2[1]);
            ldsm4t(e0, lb + 2048); ldsm4t(c1, lb + 256); ldsm4t(c3, lb + 1280); ldsm4t(e1, lb + 2304);
            mma_f16(t[0], Af[1], b0[2], b0[3]); mma_f16(t[1], Af[1], b2[2], b2[3]); mma_f16(t[2], Af[1], c0[2], c0[3]); mma_f16(t[3], Af[1], c2[2], c2[3]);
            mma_f16(t[0], Af[2], b1[0], b1[1]); mma_f16(t[1], Af[2], b3[0], b3[1]);
            mma_f16_z(t[4], Af[0], e0[0], e0[1]); mma_f16_z(t[5], Af[1], e0[2], e0[3]);
            mma_f16(t[2], Af[2], c1[0], c1[1]); mma_f16(t[3], Af[2], c3[0], c3[1]);
            mma_f16(t[4], Af[2], e1[0], e1[1]); mma_f16(t[5], Af[3], e1[2], e1[3]);
            mma_f16(t[0], Af[3], b1[2], b1[3]); mma_f16(t[1], Af[3], b3[2], b3[3]); mma_f16(t[2], Af[3], c1[2], c1[3]); mma_f16(t[3], Af[3], c3[2], c3[3]);
#pragma unroll
            for (int i = 0; i < 4; i++) t[4][i] += t[5][i];
            stsm4(kl + 1024, pack_f16(t[0][0], t[0][1]), pack_f16(t[0][2], t[0][3]), pack_f16(t[1][0], t[1][1]), pack_f16(t[1][2], t[1][3]));
            stsm2(kl + 1536, pack_f16(t[2][0], t[2][1]), pack_f16(t[2][2], t[2][3]));
            sts64(kb + lane * 8 + 1792, pack_f16(t[3][1], t[3][0]), pack_f16(t[3][3], t[3][2]));
            sts64(kb + lane * 8 + 2048, pack_f16(t[4][1], t[4][0]), pack_f16(t[4][3], t[4][2]));
        }
        bar_sync(1 + k, 128);
        const uint2 rr = lds64(opaque(sb + SM_RK + k * 8));
        const int tq = (wq + k + 2) & 3;
        const uint32_t ra = lane * 8 + opaque(fb + (tq == 1 ? 2048 : tq * 256 + 1024));
        auto comb = [&](uint32_t a, uint32_t& x, uint32_t& y) {
            const uint2 p0 = lds64(a), p1 = lds64(a + 3072), p2 = lds64(a + 6144), p3 = lds64(a + 9216);
            x = comb4(p0.x, p1.x, p2.x, p3.x, rr.x, rr.y); y = comb4(p0.y, p1.y, p2.y, p3.y, rr.x, rr.y);
        };
        uint32_t w0, w1;
        comb(ra, w0, w1);
        const bool last = lane == 31;
        if (tq == 0) {
            uint32_t v0, v1;
            comb(ra + 256, v0, v1);
            const uint32_t n0 = __shfl_sync(~0u, lane ? w0 : v0, lane + 1);
            uint32_t n1 = __shfl_sync(~0u, v0, lane + 1);
            if (last) n1 = v1 >> 16;
            sts128(pn + 12 + lane * 16, __byte_perm(w1, w0, 0x7610), __byte_perm(w1, 0, 0x1032), __byte_perm(n0, w1, 0x7610), __byte_perm(n0, 0, 0x1032));
            sts128(pn + 524 + lane * 16, __byte_perm(v1, v0, 0x7610), __byte_perm(v1, 0, 0x1032), __byte_perm(n1, v1, 0x7610), __byte_perm(n1, 0, 0x1032));
            if (lane == 0) { sts16(pn + 4, w0); sts32(pn + 8, __byte_perm(w0, 0, 0x1032)); }
        } else if (tq == 1) {
            const uint32_t ph = pf + P_H7 + (g & 1) * (2 * P_HS) + cq * 64 + (g >> 1) * 4 + (cq & 2) * 16, sw = (cq & 2) ? 0x3210 : 0x1032;
            w0 = __byte_perm(hmul2(w0, 0x18001800u), 0, sw); w1 = __byte_perm(hmul2(w1, 0x18001800u), 0, sw);
            const uint32_t pi = ph + 32 - (cq & 2) * 32;
            put16(ph, w0); put16(pi, w0 >> 16); put16(ph + 16, w1); put16(pi + 16, w1 >> 16);
        } else if (tq == 2) {
            uint32_t n = __shfl_sync(~0u, w0, lane == 30 ? 1 : lane + 2);
            if (last) { put16(pf, hmul2(w1, 0x18001800u) >> 16); w1 = hadd2(w1, hneg2(__byte_perm(w1, 0, 0x3232))); n = 0; }
            const bool od = lane & 1;
            const uint32_t pa = pn + 1036 + (lane >> 1) * 32 + (od ? 528 : 0), pb = pa + (od ? -16 : 16);
            const uint32_t u0 = od ? w1 : w0, x0 = od ? n : w1, u1 = od ? w0 : w1, x1 = od ? w1 : n;
            const uint32_t b0 = __byte_perm(u0, 0, 0x3232), b1 = __byte_perm(u1, 0, 0x3232);
            sts128(pa, __byte_perm(u0, 0, 0x1032), b0, b0, __byte_perm(x0, u0, 0x7610));
            sts128(pb, __byte_perm(u1, 0, 0x1032), b1, b1, __byte_perm(x1, u1, 0x7610));
        } else {
            const uint32_t pa = pf + ((g & 1) ? 3 * P_GS : P_GS) + cq * 32 + (g >> 1) * 4;
            const uint32_t pb = pa + ((g & 1) ? 4 - 3 * P_GS : P_GS);
            w0 = hmul2(w0, 0x18001800u); w1 = hmul2(w1, 0x18001800u);
            put16(pa, w0 >> 16); put16(pb, w0); put16(pa + 16, w1 >> 16); put16(pb + 16, w1);
            if (last) put16(pf + P_H7 + P_HS, w1);
        }
        bar_sync(1 + k, 128);
        t258 = w0;
    }
    STAMP(6);

    mbar_wait(mb + (MB_X + k) * 8);
    STAMP(7);
    if (k < nslot) {
        const int role = (wq + k) & 3;
        const uint32_t ub = sb + SM_U + k * US + 128;
        const uint32_t l16 = lane * 16, tz = (lane & 28) - 8 * cq, tz4 = tz * 4;
        if (role) {
            const uint32_t al = cq * (2 * UP + 32) + tz4, au = opaque(ub + (3 - role) * 128), a1 = al + au, a0 = (cq ? al : al + (8 * UP - 16)) + au - 2 * UP;
            const uint4 q0 = lds128(a0), q1 = lds128(a0 + UP), q2 = lds128(a1), q3 = lds128(a1 + UP);
            const uint32_t U[16] = {q0.x, q0.y, q0.z, q0.w, q1.x, q1.y, q1.z, q1.w, q2.x, q2.y, q2.z, q2.w, q3.x, q3.y, q3.z, q3.w};
            uint32_t V[14], Q[14], R4[12], T[8];
#pragma unroll
            for (int i = 2; i < 14; i++) { V[i] = __byte_perm(U[i], U[i + 1], 0x5432); Q[i] = hadd2(U[i], V[i]); }
            const uint32_t rb = l16 + opaque(fb + (3 - role) * 512);
#pragma unroll
            for (int i = 0; i < 8; i++) T[i] = hadd2(V[5 + i], Q[6 + i]);
            sts128(rb + F_E3, T[0], T[1], T[2], T[3]); sts128(rb + F_O3 + 16, T[4], T[5], T[6], T[7]);
            asm volatile("{ .reg .pred p; setp.ne.u32 p, %10, 1; @p st.shared.v4.u32 [%0], {%2,%3,%4,%5}; @p st.shared.v4.u32 [%1], {%6,%7,%8,%9}; }"
                         :: "r"(rb + F_E2), "r"(rb + F_O2), "r"(Q[6]), "r"(Q[7]), "r"(Q[8]), "r"(Q[9]), "r"(Q[10]), "r"(Q[11]), "r"(Q[12]), "r"(Q[13]), "r"(role) : "memory");
#pragma unroll
            for (int i = 2; i < 12; i++) R4[i] = hadd2(Q[i], Q[i + 1]);
#pragma unroll
            for (int i = 0; i < 8; i++) T[i] = hadd2(R4[3 + i], U[5 + i]);
            sts128(rb + F_O5, T[0], T[1], T[2], T[3]); sts128(rb + F_E5, T[4], T[5], T[6], T[7]);
            if (role != 1) {
                uint32_t S[8];
#pragma unroll
                for (int i = 0; i < 8; i++) S[i] = hadd2(R4[2 + i], i < 7 ? T[i + 1] : hadd2(R4[11], U[13]));
                sts128(rb + F_O9, S[0], S[1], S[2], S[3]); sts128(rb + F_E9 + 16, S[4], S[5], S[6], S[7]);
#pragma unroll
                for (int i = 0; i < 8; i++) S[i] = hadd2(T[i], hadd2(V[2 + i], V[5 + i]));
                sts128(rb + F_E7, S[0], S[1], S[2], S[3]); sts128(rb + F_O7, S[4], S[5], S[6], S[7]);
            }
        } else if (lane == 0) {
            const uint4 m = lds128(ub + 23 * 16 + 7 * UP);
            const uint32_t U[6] = {lds32(ub + 23 * 16 + 6 * UP + 12), m.x, m.y, m.z, m.w, lds32(ub + 24 * 16)};
            uint32_t Q[5];
#pragma unroll
            for (int i = 0; i < 5; i++) Q[i] = hadd2(U[i], __byte_perm(U[i], U[i + 1], 0x5432));
            sts128(fb + F_O5 + 96 * 16, hadd2(hadd2(Q[0], Q[1]), U[2]), hadd2(hadd2(Q[1], Q[2]), U[3]), hadd2(hadd2(Q[2], Q[3]), U[4]), hadd2(hadd2(Q[3], Q[4]), U[5]));
            sts128(fb + F_O3, 0, 0, 0, 0); sts128(fb + F_E9, 0, 0, 0, 0);
            sts16(pn + 258 * 4, t258);
        }
        bar_sync(1 + k, 128);
        float acc[4][4];
        uint32_t Q[4][4];
        {
            const int h = role & 1, part = role >> 1;
            float fa[7][4];
            uint32_t B[3][4];
            const uint32_t po = tz + opaque(pf + part * (2 * P_GS)), ba = l16 + opaque(fb + (part == h ? 0 : F_O5 + h * 16));
#pragma unroll
            for (int s = 1; s >= 0; s--) {
#pragma unroll
                for (int i = 0; i < 3; i++) { Q[i][0] = lds32(po + (s * P_GS + i * 64)); if (i < 2) Q[i][1] = lds32(po + (s * P_GS + i * 64 + 32)); }
#pragma unroll
                for (int i = 0; i < 3; i++) ldsm4t(B[i], ba + (s * F_E3 + i * 512));
#pragma unroll
                for (int i = 0; i < 3; i++) { Q[i][3] = CP(Q[i][0]); if (i) Q[i][2] = CP(Q[i - 1][1]); }
                Q[0][2] = ZF(s ? tz : Q[0][0]); Q[2][1] = ZF(s ? l16 : Q[2][0]);
#pragma unroll
                for (int dl = 0; dl < 3; dl++)
#pragma unroll
                    for (int ap = 0; ap < 6 - dl; ap++) {
                        if (s == 1 && dl == 0) mma_f16_z(fa[ap + 1], Q[0], B[ap >> 1][2 * (ap & 1)], B[ap >> 1][2 * (ap & 1) + 1]);
                        else mma_f16(fa[ap + 1 + dl], Q[dl], B[ap >> 1][2 * (ap & 1)], B[ap >> 1][2 * (ap & 1) + 1]);
                    }
            }
#pragma unroll 1
            for (int s = role; s == 1; s++) {
                ldsm2t(B[0][0], B[0][1], fb + ((lane & 15) == 15 ? F_O5 : F_O3));
#pragma unroll
                for (int dl = 1; dl < 3; dl++) mma_f16(fa[dl], Q[dl], B[0][0], B[0][1]);
            }
            const uint32_t bh = l16 + opaque(fb + F_E7 + h * F_H + part * 2048), ph = tz + opaque(pf + P_H7 + part * (2 * P_HS));
#pragma unroll 1
            for (int s = part; s == 1; s++) {
                Q[2][1] = ZF(Q[2][3]); Q[2][2] = ZF(Q[2][2]); Q[2][0] = lds32(ph - P_HS);
                ldsm4t(B[0], bh - 1024); ldsm4t(B[1], bh - 512);
                Q[2][3] = CP(Q[2][0]);
#pragma unroll
                for (int ap = 0; ap < 4; ap++) mma_f16(fa[ap + 3], Q[2], B[ap >> 1][2 * (ap & 1)], B[ap >> 1][2 * (ap & 1) + 1]);
            }
            {
                Q[0][2] = ZF(tid);
#pragma unroll
                for (int i = 0; i < 4; i++) { Q[i][0] = lds32(ph + i * 64); Q[i][1] = lds32(ph + (i * 64 + 32)); }
                ldsm4t(B[0], bh); ldsm4t(B[1], bh + 512);
#pragma unroll
                for (int i = 0; i < 4; i++) { Q[i][3] = CP(Q[i][0]); if (i) Q[i][2] = CP(Q[i - 1][1]); }
#pragma unroll
                for (int dl = 0; dl < 4; dl++)
#pragma unroll
                    for (int ap = 0; ap < 4 - dl; ap++) mma_f16(fa[ap + 3 + dl], Q[dl], B[ap >> 1][2 * (ap & 1)], B[ap >> 1][2 * (ap & 1) + 1]);
            }
            const uint32_t da = (cq * 2048 + tz4) + opaque(fb + role * 128);
            bar_sync(1 + k, 128);
#pragma unroll
            for (int i = 1; i < 4; i++)
                stsm4(da + i * 512, pack_f16(fa[2 * i - 1][0], fa[2 * i - 1][1]), pack_f16(fa[2 * i - 1][2], fa[2 * i - 1][3]),
                      pack_f16(fa[2 * i][0], fa[2 * i][1]), pack_f16(fa[2 * i][2], fa[2 * i][3]));
            asm("shl.b32 %0, 0x6000, %1;" : "=r"(Q[0][0]) : "r"(tz4));
            Q[0][1] = ZF(Q[0][0]); Q[0][2] = ZF(tz4); Q[0][3] = CP(Q[0][0]);
            const uint32_t ra = l16 + opaque(fb + wq * 2016);
            acc[0][0] = acc[0][1] = acc[0][2] = acc[0][3] = 0.f;
            if (wq == 3) {
                const uint32_t uw = lds32(ub), kw = lds32(pf);
                const float2 uf = __half22float2(*(const __half2*)&uw);
                if ((lane | 4) == 31) acc[0][3] = (lane == 31 ? uf.x + uf.y : uf.x) * (__low2float(*(const __half2*)&kw) * 512.f);
            }
            bar_sync(1 + k, 128);
#pragma unroll
            for (int i = 1; i < 4; i++) {
                ldsm4(B[0], ra + i * 512);
                mma_f16_z(acc[i], Q[0], hadd2(B[0][0], B[0][2]), hadd2(B[0][1], B[0][3]));
            }
        }
        bar_arrive(6 + k, 160);
        STAMP(8);
        const uint32_t inv = lds32(opaque(sb + SM_SC + k * 4));
        const uint32_t yd = l16 + opaque(mapa(sb, 2 * wq) + (SM_XT + 128 + q * YP + k * YS + (k >> 2) * (q >> 1) * 16));
        {
            uint32_t pu = opaque(pn + 64 * (wq - 3));
#define pp (tz + pu)
            const uint32_t dlo = (((ub + 6 * UP) & 0x3FFFF) >> 4) | ((UP >> 4) << 16);
            uint32_t R[4][4];
            unsigned long long ds[4];
#pragma unroll
            for (int i = 0; i < 4; i++) asm volatile("mov.b64 %0, {%1, %2};" : "=l"(ds[i]) : "r"(dlo - i * (2 * UP >> 4)), "r"(8 | zero));
            auto loadQ = [&](uint32_t (&X)[4][4], uint32_t prev) {
#pragma unroll
                for (int i = 0; i < 4; i++) { X[i][0] = lds32(pp + i * 64); X[i][1] = lds32(pp + i * 64 + 32); }
                X[0][2] = CP(prev);
#pragma unroll
                for (int i = 0; i < 4; i++) { X[i][3] = CP(X[i][0]); if (i) X[i][2] = CP(X[i - 1][1]); }
                pu += 256;
            };
            auto issue = [&](uint32_t (&X)[4][4]) {
                asm volatile("wgmma.fence.sync.aligned;" ::: "memory");
#pragma unroll
                for (int i = 0; i < 4; i++) wgmma32(acc, X[i], ds[i]);
                asm volatile("wgmma.commit_group.sync.aligned;" ::: "memory");
#pragma unroll
                for (int i = 0; i < 4; i++) asm volatile("{ .reg .b32 l, h; mov.b64 {l, h}, %0; add.u32 l, l, %1; mov.b64 %0, {l, h}; }" : "+l"(ds[i]) : "r"(~zero));
            };
#pragma unroll
            for (int i = 0; i < 4; i++) {
                Q[i][0] = Q[i][1] = 0;
                if (wq + i >= 3) { Q[i][0] = lds32(pp + i * 64); Q[i][1] = lds32(pp + i * 64 + 32); }
            }
            Q[0][2] = CP(0);
#pragma unroll
            for (int i = 0; i < 4; i++) { Q[i][3] = CP(Q[i][0]); if (i) Q[i][2] = CP(Q[i - 1][1]); }
            pu += 256;
#pragma unroll 1
            for (int dl = 0; dl < 4; dl++) {
                issue(Q);
                asm volatile("wgmma.wait_group.sync.aligned 1;" ::: "memory");
                loadQ(R, Q[3][1]);
                issue(R);
                asm volatile("wgmma.wait_group.sync.aligned 1;" ::: "memory");
                loadQ(Q, R[3][1]);
            }
            issue(Q);
            asm volatile("wgmma.wait_group.sync.aligned 0;" ::: "memory");
        }
        const uint32_t pstep = mapa(sb, 1) - mapa(sb, 0), ym = mapa(mb + MB_Y * 8, 2 * wq);
#pragma unroll
        for (int e = 0; e < 2; e++)
            st_async4(yd + e * pstep, bmul2(pack_bf16(acc[0][2 * e], acc[0][2 * e + 1]), inv), bmul2(pack_bf16(acc[1][2 * e], acc[1][2 * e + 1]), inv),
                      bmul2(pack_bf16(acc[2][2 * e], acc[2][2 * e + 1]), inv), bmul2(pack_bf16(acc[3][2 * e], acc[3][2 * e + 1]), inv), ym + e * pstep);
        if (lane == 0) asm volatile("mbarrier.arrive.shared::cta.b64 _, [%0];" :: "r"(mb + MB_Y * 8) : "memory");
    }
    STAMP(9);
    uint32_t ha[5], hb[5];
    if (warp < 16) {
        const uint4 wk = lds128(sb + SM_DW + cq * 16);
        uint32_t sel[5] = {wk.x, wk.y, wk.z, wk.w, lds32(sb + SM_DW + 64 + cq * 4)}, sel2[5];
#pragma unroll
        for (int i = 0; i < 5; i++) {
            if (!(g & 1)) sel[i] = 0x3F803F80u;
            sel2[i] = sel[i]; PIN(sel2[i]);
        }
        const uint32_t y4 = sb + SM_XT + 128 + warp * 32 + (2 * (lane >> 3) + (lane & 1)) * YP + ((lane & 7) >> 1) * YS;
        const uint32_t y1 = sb + SM_XT + 128 + warp * 32 + (lane & 7) * YP + 4 * YS + (lane & 8) * 2 + (lane & 6) * 8;
        uint32_t ao = (256 * q + tn) * 16, hta = sb + SM_HT + tn * 80;
        PIN(ao); PIN(hta);
        mbar_wait(mb + MB_Y * 8);
        STAMP(10);
        float ca[4] = {0.f, 0.f, 0.f, 0.f}, cb[4] = {0.f, 0.f, 0.f, 0.f};
        {
            uint32_t ya[4], yb[4], yc, yd;
            ldsm4t(ya, y4); ldsm4t(yb, y4 + 16); ldsm2t(yc, yd, y1);
#pragma unroll
            for (int i = 0; i < 4; i++) { ha[i] = badd2(xa[i], ya[i]); hb[i] = badd2(xb[i], yb[i]); }
            ha[4] = badd2(xa[4], yc); hb[4] = badd2(xb[4], yd);
        }
        if (nslot != 5) {
            ha[4] = hb[4] = 0;
            if (cq >= 2) ha[0] = ha[1] = ha[2] = ha[3] = hb[0] = hb[1] = hb[2] = hb[3] = 0;
        }
#pragma unroll
        for (int i = 0; i < 5; i++) { mma_bf16_k8(ca, ha[i], sel[i], ha[i]); mma_bf16_k8(cb, hb[i], sel2[i], hb[i]); }
        if (!(g & 1)) { ca[1] = ca[0]; cb[1] = cb[0]; }
        if (cq == (g >> 1)) {
            asm volatile("red.relaxed.gpu.global.add.v4.f32 [%0], {%1,%2,%3,%4};" :: "l"((char*)g_s.acc + ao), "f"(1.0f), "f"(ca[1]), "f"(ca[2]), "f"(ca[3]) : "memory");
            asm volatile("red.relaxed.gpu.global.add.v4.f32 [%0], {%1,%2,%3,%4};" :: "l"((char*)g_s.acc + ao + 128), "f"(1.0f), "f"(cb[1]), "f"(cb[2]), "f"(cb[3]) : "memory");
        }
        sts128(hta + cq * 16, ha[0], ha[1], ha[2], ha[3]); sts32(hta + 64 + cq * 4, ha[4]);
        sts128(hta + cq * 16 + 640, hb[0], hb[1], hb[2], hb[3]); sts32(hta + 704 + cq * 4, hb[4]);
        STAMP(11);
    }
    const int kq = warp / 5, mt = warp - 5 * kq;
    const int mi = lane >> 3, mr = lane & 7;
    const unsigned tk = (unsigned)tid / 72u, ck = tid - tk * 72;
    uint32_t A[9][4];
    auto loadA = [&]() {
        mbar_wait(mb + MB_W1 * 8);
        const uint32_t aa = sb + (mi & 1) * SM_WU + (8 * (mi >> 1) + mr) * 80 + (144 * 80 * kq + mt * 16);
#pragma unroll
        for (int s = 0; s < 9; s++) ldsm4t(A[s], aa + s * 1280);
    };
    const uint32_t par = (epoch & 1) ? 0x40004000u : 0u;
    uint32_t go = (ck / 5u + ck) * 16, gs = sb + SM_SEL + 4 + (tk & 7) * 8;
    PIN(go); PIN(gs);
    auto outtile = [&]() {
        const uint2 sa = lds64(sb + SM_ST + tn * 8), sbb = lds64(sb + SM_ST + tn * 8 + 64);
#pragma unroll
        for (int i = 0; i < 5; i++) { ha[i] = badd2(ha[i], norm2(ha[i], sa.x, sa.y)); hb[i] = badd2(hb[i], norm2(hb[i], sbb.x, sbb.y)); }
        const bool hf = (c & 1) && cq == 0;
        const uint32_t o16 = sb + SM_XT + (hf ? 16384 + tn * 16 : tn * 64 + (cq - (c & 1)) * 16), o4 = sb + SM_XT + ((c & 1) ? tn * 64 + 48 : 16384 + tn * 16) + cq * 4;
        sts128(o16, ha[0], ha[1], ha[2], ha[3]); sts32(o4, ha[4]);
        sts128(o16 + (hf ? 128 : 512), hb[0], hb[1], hb[2], hb[3]); sts32(o4 + ((c & 1) ? 512 : 128), hb[4]);
    };
    if (warp < 8) {
        const float wsum = ldsf(sb + SM_SC + 24);
        const uint32_t idx = 2047 - (512 * ((tid >> 1) & 3) + 128 * ((tid >> 3) & 3) + 64 * (tid & 1) + 8 * q + warp);
        uint32_t km0 = mapa(mb + MB_KEY * 8, 2 * cq), km1 = mapa(mb + MB_KEY * 8, 2 * cq + 1), ka0 = mapa(sb + SM_RK + q * 32, 2 * cq), ka1 = mapa(sb + SM_RK + q * 32, 2 * cq + 1);
        unsigned long long c0 = (unsigned long long)((char*)g_s.cand + ((q * 8 * NCL + c) * 6 + cq) * 16), c1 = c0 + (64 - cq * 12);
        uint32_t hc = sb + SM_HT + cq * 16, h4a = sb + SM_HT + 64 + cq * 4;
        uint32_t ca = sb + SM_KEY + warp * 128 + (warp & 1) * 32 + (lane & 28), r2a = sb + SM_KEY + cq * 16 + (cq >> 1) * 128;
        PIN(ca); PIN(r2a); PIN(km0); PIN(km1); PIN(ka0); PIN(ka1); PIN(hc); PIN(h4a);
        asm volatile("add.u64 %0, %0, %2; add.u64 %1, %1, %2;" : "+l"(c0), "+l"(c1) : "l"((unsigned long long)zero));
        uint4 s; int n = 0;
        do { s = ld_rlx128(&g_s.acc[256 * q + tid]); } while (__uint_as_float(s.x) != (float)NCL && ++n < SPIN_LIMIT);
        STAMP(16);
        const uint32_t ox = __shfl_xor_sync(~0u, (lane & 1) ? s.z : s.w, 1);
        const uint32_t ms = ln_stats(__uint_as_float((lane & 1) ? ox : s.z), __uint_as_float(s.y));
        const float rs = rcpf(bf_hi(ms));
        const uint32_t rb = pack_bf16(0.f, fmaf(-bf_lo(ms), wsum, __uint_as_float((lane & 1) ? s.w : ox)) * rs);
        const uint32_t key = (((rb ^ (((int)rb >> 31) | 0x80000000u)) >> 16) << 11) | idx;
        sts32(sb + SM_KEY + tid * 4, key);
        sts64(sb + SM_ST + tid * 8, ms, rsplit(rs));
        __syncwarp();
        uint32_t rank = rank4<8, 16>(sb + SM_KEY + warp * 128, key, ~zero);
        {
            const uint32_t sa = (rank * 4 ^ (warp & 1) * 32) + opaque(sb + SM_KEY + warp * 128);
            sts32(sa, key); sts32(sa + 1024, tid);
        }
        __syncwarp();
        const uint32_t mk = lds32(ca), t = lds32(ca + 1024);
        STAMP(17);
        bar_sync(12, 512);
        STAMP(18);
        const uint4 hv = lds128(hc + t * 80);
        const uint2 sv = lds64(sb + SM_ST + t * 8);
        const uint32_t h4 = lds32(h4a + t * 80);
        rank = rank4<4, 256>(r2a, mk, ~zero);
        const uint32_t rr = bmul2(sv.y, 0x3C803C80u);
        const uint32_t p0 = (norm2(hv.x, sv.x, rr) & 0xBFFFBFFFu) | par, p1 = (norm2(hv.y, sv.x, rr) & 0xBFFFBFFFu) | par, p2 = (norm2(hv.z, sv.x, rr) & 0xBFFFBFFFu) | par,
                       p3 = (norm2(hv.w, sv.x, rr) & 0xBFFFBFFFu) | par, p4 = (norm2(h4, sv.x, rr) & 0xBFFFBFFFu) | par;
        rank += __shfl_xor_sync(~0u, rank, 1);
        rank += __shfl_xor_sync(~0u, rank, 2);
        if (rank < 8) {
            st_async1(ka0 + rank * 4, mk, km0); st_async1(ka1 + rank * 4, mk, km1);
            st_rlx128((void*)(c0 + (unsigned long long)rank * 1440), p0, p1, p2, p3);
            asm volatile("st.relaxed.gpu.global.u32 [%0], %1;" :: "l"(c1 + (unsigned long long)rank * 1440), "r"(p4) : "memory");
        }
        __syncwarp();
    } else {
        mbar_wait(mb + MB_Y * 8); loadA();
        if (warp < 16) {
            bar_sync(12, 512);
        }
    }
    if (warp < 16) {
        outtile();
        if (warp >= 8) {
            uint32_t src = ((tid >> 2) - 64) * 1440, ma = sb + SM_RK - 256 + (tid >> 2) * 4, ra = sb + SM_RK + cq * 16;
            PIN(src); PIN(ma); PIN(ra);
            STAMP(19);
            mbar_wait(mb + MB_KEY * 8);
            STAMP(20);
            const uint32_t mk = lds32(ma);
            uint32_t rank = rank4<4, 64>(ra, mk, ~zero);
            rank += __shfl_xor_sync(~0u, rank, 1); rank += __shfl_xor_sync(~0u, rank, 2);
            sts64(sb + SM_SEL + rank * 8, mk, src);
        }
    }
    bar_sync(11, 640);
    STAMP(12);

    const char* gp = (const char*)g_s.cand + (go + lds32(gs));
    uint4 hv = ld_rlx128(gp);
    if (warp < 8) loadA();
    uint32_t bx = sb + SM_XS + mr * 1168 + mi * 16 + 288 * kq, gd = mapa(sb, kq * (8 / NRED)) + (SM_GU + (q * nslot + mt) * 128) + lane * 4;
    PIN(bx); PIN(gd);
    {
        if (warp < 18) {
            int n = 0;
            while (true) {
                sts128(sb + SM_XS + tk * 16 + tid * 16, hv.x ^ par, hv.y ^ par, hv.z ^ par, hv.w ^ par);
                if (!__any_sync(~0u, ((hv.x ^ par) | (hv.y ^ par) | (hv.z ^ par) | (hv.w ^ par)) & 0x40004000u) || ++n >= SPIN_LIMIT) break;
                hv = ld_rlx128(gp);
            }
        }
    }
    bar_sync(14, 768);
    STAMP(13);
    {
        float c0[4] = {0.f, 0.f, 0.f, 0.f}, c1[4] = {0.f, 0.f, 0.f, 0.f}, c2[4] = {0.f, 0.f, 0.f, 0.f};
        uint32_t b[5][4];
#pragma unroll
        for (int s = 0; s < 4; s++) ldsm4(b[s], bx + s * 64);
        asm volatile("ldmatrix.sync.aligned.m8n8.x2.shared.b16 {%0,%1}, [%2];" : "=r"(b[4][0]), "=r"(b[4][1]) : "r"(bx + 256) : "memory");
        mma_bf16(c0, A[0][0], A[0][1], A[0][2], A[0][3], b[0][0], b[0][1]);
        mma_bf16(c1, A[1][0], A[1][1], A[1][2], A[1][3], b[0][2], b[0][3]);
        mma_bf16(c2, A[2][0], A[2][1], A[2][2], A[2][3], b[1][0], b[1][1]);
        mma_bf16(c0, A[3][0], A[3][1], A[3][2], A[3][3], b[1][2], b[1][3]);
        mma_bf16(c1, A[4][0], A[4][1], A[4][2], A[4][3], b[2][0], b[2][1]);
        mma_bf16(c2, A[5][0], A[5][1], A[5][2], A[5][3], b[2][2], b[2][3]);
        mma_bf16(c0, A[6][0], A[6][1], A[6][2], A[6][3], b[3][0], b[3][1]);
        mma_bf16(c1, A[7][0], A[7][1], A[7][2], A[7][3], b[3][2], b[3][3]);
        mma_bf16(c2, A[8][0], A[8][1], A[8][2], A[8][3], b[4][0], b[4][1]);
        sts128f(sb + SM_RED + tid * 16, c0[0] + c1[0] + c2[0], c0[1] + c1[1] + c2[1], c0[2] + c1[2] + c2[2], c0[3] + c1[3] + c2[3]);
    }
    bar_sync(1 + mt, 128);
    STAMP(21);
    if (mt < nslot && kq < NRED) {
        const uint32_t ra = sb + SM_RED + mt * 512 + lane * 16;
        const float4 p0 = lds128f(ra), p1 = lds128f(ra + 2560), p2 = lds128f(ra + 5120), p3 = lds128f(ra + 7680);
        const float g0 = bfr(((p0.x + p1.x) + (p2.x + p3.x)) * 64.f), g1 = bfr(((p0.y + p1.y) + (p2.y + p3.y)) * 64.f);
        const uint32_t sg = pack_bf16(g0 * rcpf(1.f + ex2f(g0 * -1.4426950408889634f)), g1 * rcpf(1.f + ex2f(g1 * -1.4426950408889634f)));
        const uint32_t gu = bmul2(sg, pack_bf16(((p0.z + p1.z) + (p2.z + p3.z)) * 64.f, ((p0.w + p1.w) + (p2.w + p3.w)) * 64.f));
        const uint32_t pstep = mapa(sb, 1) - mapa(sb, 0), gm = mapa(mb + MB_GU * 8, kq * (8 / NRED));
#pragma unroll
        for (int i = 0; i < 8 / NRED; i++) st_async1(gd + i * pstep, gu, gm + i * pstep);
    }
    mbar_wait(mb + MB_W2 * 8);
    {
        const uint32_t aa = sb + (8 * (mi >> 1) + mr) * 144 + (mi & 1) * 16 + (SM_FAR + 2304 * kq + mt * 32);
#pragma unroll
        for (int s = 0; s < 5; s++) ldsm4t(A[s], aa + s * FAR_SZ);
    }
    float sig; uint32_t ra2, fo, oo;
    if (warp < 6) {
        const uint32_t td = tid, ft = td / 24u, fj = 24 * q + td - ft * 24;
        const uint32_t key = lds32(sb + SM_SEL + ft * 8), k16 = key << 5;
        sig = bfr(rcpf(1.f + ex2f(__uint_as_float((k16 ^ (~((int)k16 >> 31) | 0x80000000u)) & 0xFFFF0000u) * -1.4426950408889634f)));
        ra2 = sb + SM_RED2 + td * 12 + ft * 16; fo = (ft * 192 + fj) * 16; oo = ((~key & 2047) * D_ + 3 * fj) * 2;
        PIN(ra2); PIN(fo); PIN(oo);
        asm volatile("" : "+f"(sig));
    }
    {
        uint32_t ba = sb + (SM_GU + 256 * kq) + (lane & 15) * 16 + (lane >> 4) * 1024, wa = sb + (SM_RED2 + kq * 2432 + mt * 64) + g * 4 + cq * 608;
        PIN(ba); PIN(wa);
        STAMP(22);
        mbar_wait(mb + MB_GU * 8);
        STAMP(23);
        float c0[4] = {0.f, 0.f, 0.f, 0.f}, c1[4] = {0.f, 0.f, 0.f, 0.f}, c2[4] = {0.f, 0.f, 0.f, 0.f};
        uint32_t b[2][4], b8, b9;
        ldsm4t(b[0], ba); ldsm4t(b[1], ba + 2048); ldsm2t(b8, b9, ba + 4096);
        mma_bf16(c0, A[0][0], A[0][1], A[0][2], A[0][3], b[0][0], b[0][1]);
        mma_bf16(c1, A[1][0], A[1][1], A[1][2], A[1][3], b[0][2], b[0][3]);
        if (nslot == 5) {
            mma_bf16(c2, A[4][0], A[4][1], A[4][2], A[4][3], b8, b9);
            mma_bf16(c0, A[2][0], A[2][1], A[2][2], A[2][3], b[1][0], b[1][1]);
            mma_bf16(c1, A[3][0], A[3][1], A[3][2], A[3][3], b[1][2], b[1][3]);
        }
        stsf(wa, c0[0] + c1[0] + c2[0]); stsf(wa + 304, c0[1] + c1[1] + c2[1]);
        if (mt < 4) { stsf(wa + 32, c0[2] + c1[2] + c2[2]); stsf(wa + 336, c0[3] + c1[3] + c2[3]); }
    }
    if (warp < 6) {
        float v[3];
        bar_sync(6, 640);
        STAMP(14);
#pragma unroll
        for (int i = 0; i < 3; i++) v[i] = ((ldsf(ra2 + i * 4) + ldsf(ra2 + i * 4 + 2432)) + (ldsf(ra2 + i * 4 + 4864) + ldsf(ra2 + i * 4 + 7296))) * sig;
        finish(prm, fo, oo, v, 3.f);
    } else bar_arrive(6, 640);
    STAMP(15);
}

#undef pp
typedef __nv_bfloat16 bf16;
__device__ bf16 f_n[L_ * D_], f_h[L_ * D_];
__device__ float f_k[D_ * L_], f_r[L_], f_gu[8 * F_];
__device__ int f_idx[8];
__device__ __forceinline__ float b2f(bf16 v) { return __bfloat162float(v); }
__global__ void fb_ln(const bf16* in, const bf16* wr, bf16* out) {
    const int t = blockIdx.x * 8 + (threadIdx.x >> 5), lane = threadIdx.x & 31;
    const bf16* r = (in ? in : f_h) + t * D_;
    float s1 = 0.f, s2 = 0.f, s3 = 0.f;
    for (int i = lane; i < D_; i += 32) s1 += b2f(r[i]);
    for (int o = 16; o; o >>= 1) s1 += __shfl_xor_sync(~0u, s1, o);
    for (int i = lane; i < D_; i += 32) { const float d = b2f(r[i]) - s1 / D_; s2 += d * d; }
    for (int o = 16; o; o >>= 1) s2 += __shfl_xor_sync(~0u, s2, o);
    const float m = bfr(s1 / D_), sd = bfr(sqrtf(bfr(bfr(s2 / D_) + 1e-5f)));
    for (int i = lane; i < D_; i += 32) {
        const float v = bfr(bfr(b2f(r[i]) - m) / sd);
        f_n[t * D_ + i] = __float2bfloat16(v);
        if (!in) { s3 += v * b2f(wr[i]); out[t * D_ + i] = __float2bfloat16(b2f(r[i]) + v); }
    }
    for (int o = 16; o; o >>= 1) s3 += __shfl_xor_sync(~0u, s3, o);
    f_r[t] = bfr(s3);
}
__global__ void fb_taps(Params p) {
    const int d = blockIdx.x >> 3, l = (blockIdx.x & 7) * 256 + threadIdx.x;
    const float dt = bfr(expf(bf_lo(p.logdt[d]))), lf = bfr((float)l);
    float k = 0.f;
    for (int n = d * 128; n < d * 128 + 128; n++) {
        float wr, wi, sn, cs;
        cmul(wr, wi, bf_lo(p.prm6[4][n]), bf_lo(p.prm6[5][n]), dt * bf_lo(p.prm6[2][n]), dt * bf_lo(p.prm6[3][n]));
        sincosf(dt * bf_lo(p.prm6[1][n]) * lf, &sn, &cs);
        k += expf(dt * bf_lo(p.prm6[0][n]) * lf) * (wr * cs - wi * sn);
    }
    f_k[l * D_ + d] = k;
}
__global__ void fb_conv(Params p) {
    const int t = blockIdx.x, d = threadIdx.x;
    float y = 0.f;
    for (int l = 0; l <= t; l++) y += f_k[l * D_ + d] * b2f(f_n[(t - l) * D_ + d]);
    f_h[t * D_ + d] = __float2bfloat16(bf_lo(p.x[t * D_ + d]) + bfr(bfr(y) + bfr(b2f(f_n[t * D_ + d]) * bf_lo(p.dskip[d]))));
}
__global__ void fb_top() {
    const int t = blockIdx.x * 256 + threadIdx.x;
    int rank = 0;
    for (int j = 0; j < L_; j++) rank += f_r[j] > f_r[t] || (f_r[j] == f_r[t] && j < t);
    if (rank < 8) f_idx[rank] = t;
}
__global__ void fb_ffn1(const bf16* wg, const bf16* wu) {
    const int f = blockIdx.x * 256 + threadIdx.x, j = blockIdx.y;
    float g = 0.f, u = 0.f;
    for (int i = 0; i < D_; i++) { const float v = b2f(f_n[f_idx[j] * D_ + i]); g += v * b2f(wg[i * F_ + f]); u += v * b2f(wu[i * F_ + f]); }
    g = bfr(g);
    f_gu[j * F_ + f] = bfr(bfr(g / (1.f + expf(-g))) * bfr(u));
}
__global__ void fb_ffn2(const bf16* wd, bf16* out) {
    const int d = threadIdx.x, j = blockIdx.x, t = f_idx[j];
    float y = 0.f;
    for (int f = 0; f < F_; f++) y += f_gu[j * F_ + f] * b2f(wd[f * D_ + d]);
    out[t * D_ + d] = __float2bfloat16(b2f(f_h[t * D_ + d]) + bfr(b2f(f_n[t * D_ + d]) + bfr(bfr(y) * bfr(1.f / (1.f + expf(-f_r[t]))))));
}

typedef CUresult (*EncodeFn)(CUtensorMap*, CUtensorMapDataType, cuuint32_t, void*, const cuuint64_t*, const cuuint64_t*,
                             const cuuint32_t*, const cuuint32_t*, CUtensorMapInterleave, CUtensorMapSwizzle,
                             CUtensorMapL2promotion, CUtensorMapFloatOOBfill);

void make_map(EncodeFn fn, CUtensorMap* tm, const void* p, int cols, int rows, int bc, int br) {
    cuuint64_t dims[2] = {(cuuint64_t)cols, (cuuint64_t)rows};
    cuuint64_t strides[1] = {(cuuint64_t)cols * 2};
    cuuint32_t box[2] = {(cuuint32_t)bc, (cuuint32_t)br};
    cuuint32_t es[2] = {1, 1};
    fn(tm, CU_TENSOR_MAP_DATA_TYPE_BFLOAT16, 2, const_cast<void*>(p), dims, strides, box, es, CU_TENSOR_MAP_INTERLEAVE_NONE,
       CU_TENSOR_MAP_SWIZZLE_NONE, CU_TENSOR_MAP_L2_PROMOTION_L2_128B, CU_TENSOR_MAP_FLOAT_OOB_FILL_NONE);
}

void make_map3(EncodeFn fn, CUtensorMap* tm, const void* p) {
    cuuint64_t dims[5] = {(cuuint64_t)D_, 64, 2, 2, 8};
    cuuint64_t strides[4] = {(cuuint64_t)D_ * 2, (cuuint64_t)D_ * 2048, (cuuint64_t)D_ * 128, (cuuint64_t)D_ * 256};
    cuuint32_t box[5] = {XW, 9, 2, 2, 8};
    cuuint32_t es[5] = {1, 1, 1, 1, 1};
    fn(tm, CU_TENSOR_MAP_DATA_TYPE_BFLOAT16, 5, const_cast<void*>(p), dims, strides, box, es, CU_TENSOR_MAP_INTERLEAVE_NONE,
       CU_TENSOR_MAP_SWIZZLE_NONE, CU_TENSOR_MAP_L2_PROMOTION_NONE, CU_TENSOR_MAP_FLOAT_OOB_FILL_NONE);
}

void make_map5(EncodeFn fn, CUtensorMap* tm, const void* p, int bc) {
    cuuint64_t dims[5] = {(cuuint64_t)D_, 2, 4, 4, 64};
    cuuint64_t strides[4] = {(cuuint64_t)D_ * 128, (cuuint64_t)D_ * 1024, (cuuint64_t)D_ * 256, (cuuint64_t)D_ * 2};
    cuuint32_t box[5] = {(cuuint32_t)bc, 2, 4, 4, 8};
    cuuint32_t es[5] = {1, 1, 1, 1, 1};
    fn(tm, CU_TENSOR_MAP_DATA_TYPE_BFLOAT16, 5, const_cast<void*>(p), dims, strides, box, es, CU_TENSOR_MAP_INTERLEAVE_NONE,
       CU_TENSOR_MAP_SWIZZLE_NONE, CU_TENSOR_MAP_L2_PROMOTION_NONE, CU_TENSOR_MAP_FLOAT_OOB_FILL_NONE);
}

}

extern "C" void kernel_launch(void* const* d_in, const int* in_sizes, int n_in, void* d_out, int out_size) {
    (void)in_sizes; (void)n_in; (void)out_size;
    void* fp = nullptr;
    cudaDriverEntryPointQueryResult qr;
    cudaGetDriverEntryPoint("cuTensorMapEncodeTiled", &fp, cudaEnableDefault, &qr);
    EncodeFn fn = (EncodeFn)fp;
    CUtensorMap tmG, tmU, tmD, tmO, tmX, tmH;
    make_map3(fn, &tmX, d_in[0]);
    make_map(fn, &tmG, d_in[11], F_, D_, 40, 48);
    make_map(fn, &tmU, d_in[12], F_, D_, 40, 48);
    make_map(fn, &tmD, d_in[13], D_, F_, 72, 64);
    make_map5(fn, &tmO, d_out, 32);
    make_map5(fn, &tmH, d_out, 8);
    Params p;
    p.x = (const unsigned short*)d_in[0];
    for (int i = 0; i < 6; i++) p.prm6[i] = (const unsigned short*)d_in[1 + i];
    p.logdt = (const unsigned short*)d_in[7]; p.dskip = (const unsigned short*)d_in[8];
    p.wr = (const unsigned short*)d_in[10];
    p.out = (__nv_bfloat16*)d_out;
    p.zero = 0;
    cudaGetSymbolAddress((void**)&p.gs, g_s);
    cudaFuncSetAttribute(fused_kernel, cudaFuncAttributeMaxDynamicSharedMemorySize, SM_TOTAL);
    static int nclusters = -1;
    if (nclusters < 0) {
        cudaLaunchConfig_t cfg = {};
        cudaLaunchAttribute at;
        at.id = cudaLaunchAttributeClusterDimension; at.val.clusterDim.x = CS; at.val.clusterDim.y = 1; at.val.clusterDim.z = 1;
        cfg.gridDim = dim3(NCTA); cfg.blockDim = dim3(NTHR); cfg.dynamicSmemBytes = SM_TOTAL; cfg.attrs = &at; cfg.numAttrs = 1;
        if (cudaOccupancyMaxActiveClusters(&nclusters, fused_kernel, &cfg) != cudaSuccess) { (void)cudaGetLastError(); nclusters = NCL; }
    }
    if (nclusters >= NCL && !FORCE_FALLBACK) {
        fused_kernel<<<NCTA, NTHR, SM_TOTAL>>>(p, tmG, tmU, tmD, tmO, tmX, tmH);
        return;
    }
    fb_ln<<<L_ / 8, 256>>>((const bf16*)d_in[0], nullptr, nullptr);
    fb_taps<<<D_ * 8, 256>>>(p);
    fb_conv<<<L_, D_>>>(p);
    fb_ln<<<L_ / 8, 256>>>(nullptr, (const bf16*)d_in[10], p.out);
    fb_top<<<L_ / 256, 256>>>();
    fb_ffn1<<<dim3(F_ / 256, 8), 256>>>((const bf16*)d_in[11], (const bf16*)d_in[12]);
    fb_ffn2<<<8, D_>>>((const bf16*)d_in[13], p.out);
}
```

```cpp
#include <cuda_runtime.h>
#include <cuda_bf16.h>
#include <cuda_fp16.h>
#include <cuda.h>
#include <stdint.h>

namespace {

constexpr int L_ = 2048, D_ = 576, F_ = 4608;
constexpr int NCL = 15, CS = 8, NCTA = NCL * CS, NTHR = 768;
#define FORCE_FALLBACK 0
constexpr int XW = 48, NRED = 2;
constexpr int SPIN_LIMIT = 1 << 22;

constexpr int SM_WG   = 0;
constexpr int SM_WU   = 46080;
constexpr int YP = 3392, YS = 656;
constexpr int UP = 3280, US = 656;
constexpr int SM_XT   = 92160;
constexpr int SM_U    = SM_XT + 8 * YP;
constexpr int SM_FAR  = SM_U + 8 * UP;
constexpr int FAR_SZ  = 12416;
constexpr int F_E5 = 0, F_O5 = 1536, F_E3 = 3088, F_O3 = 4624, F_E7 = 6176, F_E2 = F_E7 + 1024, F_E9 = F_E7 + 2048,
              F_H = 3088, F_O7 = F_E7 + F_H, F_O2 = F_E2 + F_H, F_O9 = F_E9 + F_H;
constexpr int SM_P    = SM_FAR + 5 * FAR_SZ;
constexpr int PN_SZ = 584 * 4, SM_PN = SM_P + 65 * 4;
constexpr int P_GS = 50 * 4, P_H7 = 200 * 4, P_HS = 74 * 4;
constexpr int PF_SZ = (200 + 222) * 4, SM_PF = SM_PN + 5 * PN_SZ + 36;
constexpr int SM_MISC = SM_PF + 5 * PF_SZ;
constexpr int SM_ST   = SM_MISC;
constexpr int SM_RK   = SM_ST + 2048;
constexpr int SM_SEL  = SM_FAR + FAR_SZ + 10240;
constexpr int SM_KG   = SM_RK + 320;
constexpr int SM_SC   = SM_KG + 160;
constexpr int SM_DW   = SM_SC + 32;
constexpr int SM_MB   = SM_DW + 160;
constexpr int SM_TOTAL = SM_MB + 128;
constexpr int SM_ROW  = SM_XT - 20736;
constexpr int SM_XTL  = SM_ROW - 576 * XW;
constexpr int SM_RED2 = SM_WG;
constexpr int SM_HT   = SM_P - 512;
constexpr int SM_KEY  = SM_FAR + 10240 + 128;
constexpr int SM_CAND = SM_KEY + 1024;
constexpr int SM_XS   = SM_U;
constexpr int SM_GU   = SM_XS + 9344;
constexpr int SM_RED  = SM_GU + 5632;
static_assert(F_O9 + 1024 <= FAR_SZ && FAR_SZ % 128 == 0, "far overflow");
static_assert(SM_RED + 10240 <= SM_FAR && SM_HT + 20496 <= SM_MISC, "alias overflow");
static_assert(SM_TOTAL <= 232448, "smem overflow");
static_assert(SM_FAR % 128 == 0 && SM_XT % 128 == 0 && SM_XTL % 128 == 0 && SM_P % 16 == 0 && SM_MISC % 16 == 0 && SM_MB % 8 == 0, "align");

enum { MB_X = 0, MB_W1 = 5, MB_W2 = 6, MB_KEY = 7, MB_GU = 8, MB_Y = 9, MB_OUT = 10, MB_T = 11, MB_R = 12 };

struct __align__(128) Scratch {
    unsigned epoch, zcnt, pad[30];
    uint4  st1[L_ * 2];
    float4 acc[L_];
    uint4  cand[64 * NCL * 6];
    float4 fin[8 * 192 + 24];
};
__device__ Scratch g_s;
#define STAMP(i)

__device__ __forceinline__ uint32_t mapa(uint32_t a, uint32_t r) { uint32_t d; asm("mapa.shared::cluster.u32 %0, %1, %2;" : "=r"(d) : "r"(a), "r"(r)); return d; }
__device__ __forceinline__ void mbar_wait(uint32_t mb) {
    asm volatile("{ .reg .pred p, q; .reg .u32 n; mov.u32 n, 0;\n"
                 "W_%=: mbarrier.try_wait.parity.shared::cta.b64 p, [%0], 0; add.u32 n, n, 1; setp.lt.and.u32 q, n, 65536, !p; @q bra W_%=; }" :: "r"(mb) : "memory");
}
__device__ __forceinline__ bool elect() { uint32_t e; asm volatile("{ .reg .pred p; elect.sync _|p, 0xffffffff; selp.u32 %0, 1, 0, p; }" : "=r"(e)); return e; }
__device__ __forceinline__ void arm(uint32_t mb, uint32_t bytes) { asm volatile("mbarrier.arrive.expect_tx.shared::cta.b64 _, [%0], %1;" :: "r"(mb), "r"(bytes) : "memory"); }
__device__ __forceinline__ void bar_sync(int id, int n) { asm volatile("bar.sync %0, %1;" :: "r"(id), "r"(n) : "memory"); }
__device__ __forceinline__ void bar_arrive(int id, int n) { asm volatile("bar.arrive %0, %1;" :: "r"(id), "r"(n) : "memory"); }
__device__ __forceinline__ uint32_t lds16(uint32_t a) { unsigned short v; asm volatile("ld.shared.u16 %0, [%1];" : "=h"(v) : "r"(a) : "memory"); return v; }
__device__ __forceinline__ uint32_t lds32(uint32_t a) { uint32_t v; asm volatile("ld.shared.u32 %0, [%1];" : "=r"(v) : "r"(a) : "memory"); return v; }
__device__ __forceinline__ uint2 lds64(uint32_t a) { uint2 v; asm volatile("ld.shared.v2.u32 {%0,%1}, [%2];" : "=r"(v.x), "=r"(v.y) : "r"(a) : "memory"); return v; }
__device__ __forceinline__ float ldsf(uint32_t a) { float v; asm volatile("ld.shared.f32 %0, [%1];" : "=f"(v) : "r"(a) : "memory"); return v; }
__device__ __forceinline__ uint4 lds128(uint32_t a) { uint4 v; asm volatile("ld.shared.v4.u32 {%0,%1,%2,%3}, [%4];" : "=r"(v.x), "=r"(v.y), "=r"(v.z), "=r"(v.w) : "r"(a) : "memory"); return v; }
__device__ __forceinline__ float4 lds128f(uint32_t a) { float4 v; asm volatile("ld.shared.v4.f32 {%0,%1,%2,%3}, [%4];" : "=f"(v.x), "=f"(v.y), "=f"(v.z), "=f"(v.w) : "r"(a) : "memory"); return v; }
__device__ __forceinline__ void sts16(uint32_t a, uint32_t v) { asm volatile("{ .reg .b16 l, h; mov.b32 {l, h}, %1; st.shared.b16 [%0], l; }" :: "r"(a), "r"(v) : "memory"); }
__device__ __forceinline__ void sts32(uint32_t a, uint32_t v) { asm volatile("st.shared.u32 [%0], %1;" :: "r"(a), "r"(v) : "memory"); }
__device__ __forceinline__ void sts64(uint32_t a, uint32_t x, uint32_t y) { asm volatile("st.shared.v2.u32 [%0], {%1,%2};" :: "r"(a), "r"(x), "r"(y) : "memory"); }
__device__ __forceinline__ void stsf(uint32_t a, float v) { asm volatile("st.shared.f32 [%0], %1;" :: "r"(a), "f"(v) : "memory"); }
__device__ __forceinline__ void sts128(uint32_t a, uint32_t x, uint32_t y, uint32_t z, uint32_t w) { asm volatile("st.shared.v4.u32 [%0], {%1,%2,%3,%4};" :: "r"(a), "r"(x), "r"(y), "r"(z), "r"(w) : "memory"); }
__device__ __forceinline__ void sts128f(uint32_t a, float x, float y, float z, float w) { asm volatile("st.shared.v4.f32 [%0], {%1,%2,%3,%4};" :: "r"(a), "f"(x), "f"(y), "f"(z), "f"(w) : "memory"); }
__device__ __forceinline__ void ldsm4(uint32_t (&r)[4], uint32_t a) { asm volatile("ldmatrix.sync.aligned.m8n8.x4.shared.b16 {%0,%1,%2,%3}, [%4];" : "=r"(r[0]), "=r"(r[1]), "=r"(r[2]), "=r"(r[3]) : "r"(a) : "memory"); }
__device__ __forceinline__ void ldsm4t(uint32_t (&r)[4], uint32_t a) { asm volatile("ldmatrix.sync.aligned.m8n8.x4.trans.shared.b16 {%0,%1,%2,%3}, [%4];" : "=r"(r[0]), "=r"(r[1]), "=r"(r[2]), "=r"(r[3]) : "r"(a) : "memory"); }
__device__ __forceinline__ void ldsm2t(uint32_t& r0, uint32_t& r1, uint32_t a) { asm volatile("ldmatrix.sync.aligned.m8n8.x2.trans.shared.b16 {%0,%1}, [%2];" : "=r"(r0), "=r"(r1) : "r"(a) : "memory"); }
__device__ __forceinline__ void stsm4t(uint32_t a, uint32_t r0, uint32_t r1, uint32_t r2, uint32_t r3) { asm volatile("stmatrix.sync.aligned.m8n8.x4.trans.shared.b16 [%0], {%1,%2,%3,%4};" :: "r"(a), "r"(r0), "r"(r1), "r"(r2), "r"(r3) : "memory"); }
__device__ __forceinline__ void stsm4(uint32_t a, uint32_t r0, uint32_t r1, uint32_t r2, uint32_t r3) { asm volatile("stmatrix.sync.aligned.m8n8.x4.shared.b16 [%0], {%1,%2,%3,%4};" :: "r"(a), "r"(r0), "r"(r1), "r"(r2), "r"(r3) : "memory"); }
__device__ __forceinline__ void stsm2(uint32_t a, uint32_t r0, uint32_t r1) { asm volatile("stmatrix.sync.aligned.m8n8.x2.shared.b16 [%0], {%1,%2};" :: "r"(a), "r"(r0), "r"(r1) : "memory"); }
__device__ __forceinline__ void stsm2t(uint32_t a, uint32_t r0, uint32_t r1) { asm volatile("stmatrix.sync.aligned.m8n8.x2.trans.shared.b16 [%0], {%1,%2};" :: "r"(a), "r"(r0), "r"(r1) : "memory"); }
__device__ __forceinline__ uint4 ldg128(const void* p) { uint4 v; asm volatile("ld.global.nc.v4.u32 {%0,%1,%2,%3}, [%4];" : "=r"(v.x), "=r"(v.y), "=r"(v.z), "=r"(v.w) : "l"(p)); return v; }
__device__ __forceinline__ uint32_t ldg16(const void* p) { unsigned short v; asm volatile("ld.global.nc.u16 %0, [%1];" : "=h"(v) : "l"(p)); return v; }
__device__ __forceinline__ uint32_t opaque(uint32_t v) { uint32_t r; asm volatile("mov.b32 %0, %1;" : "=r"(r) : "r"(v)); return r; }
__device__ __forceinline__ void mma_f16(float (&d)[4], const uint32_t (&a)[4], uint32_t b0, uint32_t b1) {
    asm volatile("mma.sync.aligned.m16n8k16.row.col.f32.f16.f16.f32 {%0,%1,%2,%3}, {%4,%5,%6,%7}, {%8,%9}, {%0,%1,%2,%3};"
        : "+f"(d[0]), "+f"(d[1]), "+f"(d[2]), "+f"(d[3]) : "r"(a[0]), "r"(a[1]), "r"(a[2]), "r"(a[3]), "r"(b0), "r"(b1));
}
__device__ __forceinline__ void mma_f16_z(float (&d)[4], const uint32_t (&a)[4], uint32_t b0, uint32_t b1) {
    asm volatile("mma.sync.aligned.m16n8k16.row.col.f32.f16.f16.f32 {%0,%1,%2,%3}, {%4,%5,%6,%7}, {%8,%9}, {%10,%10,%10,%10};"
        : "=f"(d[0]), "=f"(d[1]), "=f"(d[2]), "=f"(d[3]) : "r"(a[0]), "r"(a[1]), "r"(a[2]), "r"(a[3]), "r"(b0), "r"(b1), "f"(0.f));
}
__device__ __forceinline__ void mma_bf16(float (&d)[4], uint32_t a0, uint32_t a1, uint32_t a2, uint32_t a3, uint32_t b0, uint32_t b1) {
    asm volatile("mma.sync.aligned.m16n8k16.row.col.f32.bf16.bf16.f32 {%0,%1,%2,%3}, {%4,%5,%6,%7}, {%8,%9}, {%0,%1,%2,%3};"
        : "+f"(d[0]), "+f"(d[1]), "+f"(d[2]), "+f"(d[3]) : "r"(a0), "r"(a1), "r"(a2), "r"(a3), "r"(b0), "r"(b1));
}
__device__ __forceinline__ void mma_bf16_k8(float (&d)[4], uint32_t a0, uint32_t a1, uint32_t b0) {
    asm volatile("mma.sync.aligned.m16n8k8.row.col.f32.bf16.bf16.f32 {%0,%1,%2,%3}, {%4,%5}, {%6}, {%0,%1,%2,%3};"
        : "+f"(d[0]), "+f"(d[1]), "+f"(d[2]), "+f"(d[3]) : "r"(a0), "r"(a1), "r"(b0));
}
__device__ __forceinline__ uint32_t pack_f16(float lo, float hi) { uint32_t r; asm("cvt.rn.f16x2.f32 %0, %1, %2;" : "=r"(r) : "f"(hi), "f"(lo)); return r; }
__device__ __forceinline__ uint32_t pack_bf16(float lo, float hi) { uint32_t r; asm("cvt.rn.bf16x2.f32 %0, %1, %2;" : "=r"(r) : "f"(hi), "f"(lo)); return r; }
__device__ __forceinline__ float bf_lo(uint32_t v) { return __uint_as_float(v << 16); }
__device__ __forceinline__ float bf_hi(uint32_t v) { return __uint_as_float(v & 0xFFFF0000u); }
__device__ __forceinline__ float bfr(float x) { return __uint_as_float(pack_bf16(0.f, x)); }
__device__ __forceinline__ uint32_t badd2(uint32_t a, uint32_t b) { uint32_t r; asm("add.rn.bf16x2 %0, %1, %2;" : "=r"(r) : "r"(a), "r"(b)); return r; }
__device__ __forceinline__ uint32_t bmul2(uint32_t a, uint32_t b) { uint32_t r; asm("mul.rn.bf16x2 %0, %1, %2;" : "=r"(r) : "r"(a), "r"(b)); return r; }
__device__ __forceinline__ uint32_t hadd2(uint32_t a, uint32_t b) { uint32_t r; asm("add.rn.f16x2 %0, %1, %2;" : "=r"(r) : "r"(a), "r"(b)); return r; }
__device__ __forceinline__ uint32_t hmul2(uint32_t a, uint32_t b) { uint32_t r; asm("mul.rn.f16x2 %0, %1, %2;" : "=r"(r) : "r"(a), "r"(b)); return r; }
__device__ __forceinline__ uint32_t hneg2(uint32_t a) { uint32_t r; asm("neg.f16x2 %0, %1;" : "=r"(r) : "r"(a)); return r; }
__device__ __forceinline__ float rcpf(float x) { float r; asm("rcp.approx.ftz.f32 %0, %1;" : "=f"(r) : "f"(x)); return r; }
__device__ __forceinline__ float sqrta(float x) { float r; asm("sqrt.approx.ftz.f32 %0, %1;" : "=f"(r) : "f"(x)); return r; }
__device__ __forceinline__ float ex2f(float x) { float r; asm("ex2.approx.ftz.f32 %0, %1;" : "=f"(r) : "f"(x)); return r; }
__device__ __forceinline__ void st_async4(uint32_t a, uint32_t x, uint32_t y, uint32_t z, uint32_t w, uint32_t mb) {
    asm volatile("st.async.shared::cluster.mbarrier::complete_tx::bytes.v4.u32 [%0], {%1,%2,%3,%4}, [%5];" :: "r"(a), "r"(x), "r"(y), "r"(z), "r"(w), "r"(mb) : "memory"); }
__device__ __forceinline__ void st_async1(uint32_t a, uint32_t x, uint32_t mb) {
    asm volatile("st.async.shared::cluster.mbarrier::complete_tx::bytes.u32 [%0], %1, [%2];" :: "r"(a), "r"(x), "r"(mb) : "memory"); }
__device__ __forceinline__ unsigned ld_rlx(const void* p) { unsigned v; asm volatile("ld.relaxed.gpu.global.u32 %0, [%1];" : "=r"(v) : "l"(p) : "memory"); return v; }
__device__ __forceinline__ unsigned ld_acq(const void* p) { unsigned v; asm volatile("ld.acquire.gpu.global.u32 %0, [%1];" : "=r"(v) : "l"(p) : "memory"); return v; }
__device__ __forceinline__ uint2 ld_rlx64(const void* p) { unsigned long long v; asm volatile("ld.relaxed.gpu.global.u64 %0, [%1];" : "=l"(v) : "l"(p) : "memory"); return make_uint2((unsigned)v, (unsigned)(v >> 32)); }
__device__ __forceinline__ void st_rlx128(void* p, uint32_t x, uint32_t y, uint32_t z, uint32_t w) {
    asm volatile("st.relaxed.gpu.global.v2.u64 [%0], {%1,%2};" :: "l"(p), "l"((unsigned long long)x | ((unsigned long long)y << 32)), "l"((unsigned long long)z | ((unsigned long long)w << 32)) : "memory"); }
__device__ __forceinline__ uint4 ld_rlx128(const void* p) { unsigned long long a, b; asm volatile("ld.relaxed.gpu.global.v2.u64 {%0,%1}, [%2];" : "=l"(a), "=l"(b) : "l"(p) : "memory"); return make_uint4((unsigned)a, (unsigned)(a >> 32), (unsigned)b, (unsigned)(b >> 32)); }
__device__ __forceinline__ void tma2d(uint32_t dst, const CUtensorMap* tm, int x, int y, uint32_t mb) {
    asm volatile("cp.async.bulk.tensor.2d.shared::cluster.global.mbarrier::complete_tx::bytes [%0], [%1, {%3, %4}], [%2];"
                 :: "r"(dst), "l"(tm), "r"(mb), "r"(x), "r"(y) : "memory");
}
__device__ __forceinline__ void cmul(float& xr, float& xi, float ar, float ai, float br, float bi) {
    const float r = fmaf(ar, br, -ai * bi), i = fmaf(ar, bi, ai * br); xr = r; xi = i;
}
__device__ __forceinline__ void csq(float& xr, float& xi, float ar, float ai) {
    const float r = fmaf(ar, ar, -ai * ai), i = (ar + ar) * ai; xr = r; xi = i;
}
__device__ __forceinline__ void cexp_s(float& zr, float& zi, float e2, float turns) {
    const float mag = ex2f(e2), r = (turns - rintf(turns)) * 6.283185307179586f;
    zr = mag * __cosf(r); zi = mag * __sinf(r);
}
__device__ __forceinline__ uint32_t ln_stats(float s1, float s2) {
    const float m = s1 * (1.f / D_);
    const float var = fmaxf(fmaf(s2, 1.f / D_, -m * m), 0.f);
    return pack_bf16(m, sqrta(bfr(bfr(var) + 1e-5f)));
}
__device__ __forceinline__ uint32_t rsplit(float rs) { const float h = bfr(rs); return pack_bf16(h, rs - h); }
__device__ __forceinline__ uint32_t norm2(uint32_t v, uint32_t mx, uint32_t hl) {
    uint32_t r;
    asm("{ .reg .b16 m, h, l, x; .reg .b32 m2, h2, l2, d, t; mov.b32 {m, x}, %2; mov.b32 {h, l}, %3; mov.b32 m2, {m, m}; mov.b32 h2, {h, h}; mov.b32 l2, {l, l};\n"
        "sub.rn.bf16x2 d, %1, m2; mul.rn.bf16x2 t, d, l2; fma.rn.bf16x2 %0, d, h2, t; }" : "=r"(r) : "r"(v), "r"(mx), "r"(hl));
    return r;
}
template <int N, int S>
__device__ __forceinline__ uint32_t rank4(uint32_t a, uint32_t key, uint32_t m1) {
    uint32_t r0 = 0, r1 = 0, r2 = 0, r3 = 0;
#pragma unroll
    for (int i = 0; i < N; i++) {
        const uint4 o = lds128(a + i * S);
        r0 += (o.x * m1 + key) >> 31; r1 += (o.y * m1 + key) >> 31; r2 += (o.z * m1 + key) >> 31; r3 += (o.w * m1 + key) >> 31;
    }
    return (r0 + r1) + (r2 + r3);
}
typedef uint32_t H2C;
__device__ __forceinline__ H2C splat(float r, float i) { return pack_f16(r, i); }
__device__ __forceinline__ void hcmul(uint32_t& xr, uint32_t& xi, uint32_t R, uint32_t I, H2C m) {
    asm("{ .reg .b16 a, b; .reg .b32 a2, b2, t; mov.b32 {a, b}, %4; mov.b32 a2, {a, a}; mov.b32 b2, {b, b};\n"
        "mul.rn.f16x2 t, %3, b2; neg.f16x2 t, t; fma.rn.f16x2 %0, %2, a2, t; mul.rn.f16x2 t, %3, a2; fma.rn.f16x2 %1, %2, b2, t; }"
        : "=&r"(xr), "=r"(xi) : "r"(R), "r"(I), "r"(m));
}
__device__ __forceinline__ void expand4(uint32_t are, uint32_t aim, uint32_t R0, uint32_t R1, uint32_t I0, uint32_t I1, H2C m4) {
    uint32_t R2, I2, R3, I3;
    hcmul(R2, I2, R0, I0, m4); hcmul(R3, I3, R1, I1, m4);
    sts128(are, R0, R1, R2, R3);
    sts128(aim, I0, I1, I2, I3);
}
__device__ __forceinline__ void expand8(uint32_t are, uint32_t aim, float sr, float si, float m1r, float m1i, float m2r, float m2i, H2C m4) {
    float r1, i1, r2, i2, r3, i3;
    cmul(r1, i1, sr, si, m1r, m1i); cmul(r2, i2, sr, si, m2r, m2i); cmul(r3, i3, r1, i1, m2r, m2i);
    expand4(are, aim, pack_f16(sr, r1), pack_f16(r2, r3), pack_f16(si, i1), pack_f16(i2, i3), m4);
}
__device__ __forceinline__ uint32_t comb4(uint32_t a, uint32_t b, uint32_t c, uint32_t d, uint32_t r01, uint32_t r23) {
    uint32_t x;
    asm("{ .reg .b16 h0, h1, h2, h3; .reg .b32 m0, m1, m2, m3, u, v; mov.b32 {h0, h1}, %5; mov.b32 {h2, h3}, %6;\n"
        "mov.b32 m0, {h0, h0}; mov.b32 m1, {h1, h1}; mov.b32 m2, {h2, h2}; mov.b32 m3, {h3, h3};\n"
        "mul.rn.f16x2 u, %2, m1; fma.rn.f16x2 u, %1, m0, u; mul.rn.f16x2 v, %4, m3; fma.rn.f16x2 v, %3, m2, v; add.rn.f16x2 %0, u, v; }"
        : "=r"(x) : "r"(a), "r"(b), "r"(c), "r"(d), "r"(r01), "r"(r23));
    return x;
}
__device__ __forceinline__ void put16(uint32_t a, uint32_t v) { sts16(a, v); sts16(a + 6, v); }

struct Params {
    const unsigned short *logdt, *dskip, *prm6[6], *x, *wr;
    __nv_bfloat16* out;
    Scratch* gs;
    unsigned zero;
};
__device__ __forceinline__ uint32_t tslot(uint32_t t) { return (t & 7) * 32 + ((t >> 4) & 24) + ((t >> 8) & 6) + ((t >> 6) & 1); }
#define CP(x) ((x) | zero)
#define ZF(x) ((x) & zero)
#define PIN(x) asm volatile("or.b32 %0, %0, %1;" : "+r"(x) : "r"(zero))
__device__ __forceinline__ void wgmma32(float (&d)[4][4], const uint32_t (&a)[4], unsigned long long ds) {
    asm volatile("wgmma.mma_async.sync.aligned.m64n32k16.f32.f16.f16 {%0,%1,%2,%3,%4,%5,%6,%7,%8,%9,%10,%11,%12,%13,%14,%15}, {%16,%17,%18,%19}, %20, 1, 1, 1, 0;"
        : "+f"(d[0][0]), "+f"(d[0][1]), "+f"(d[0][2]), "+f"(d[0][3]), "+f"(d[1][0]), "+f"(d[1][1]), "+f"(d[1][2]), "+f"(d[1][3]),
          "+f"(d[2][0]), "+f"(d[2][1]), "+f"(d[2][2]), "+f"(d[2][3]), "+f"(d[3][0]), "+f"(d[3][1]), "+f"(d[3][2]), "+f"(d[3][3])
        : "r"(a[0]), "r"(a[1]), "r"(a[2]), "r"(a[3]), "l"(ds));
}

__device__ __forceinline__ void finish(const Params& prm, uint32_t fo, uint32_t oo, const float (&v)[3], float cnt) {
    float x, y, z, w;
    asm volatile("atom.relaxed.gpu.global.add.v4.f32 {%0,%1,%2,%3}, [%4], {%5,%6,%7,%8};" : "=f"(x), "=f"(y), "=f"(z), "=f"(w)
                 : "l"((char*)prm.gs->fin + fo), "f"(v[0]), "f"(v[1]), "f"(v[2]), "f"(cnt) : "memory");
    if (w + cnt == 3.f * (NCL + 1)) {
        __nv_bfloat16* op = (__nv_bfloat16*)((char*)prm.out + oo);
        op[0] = __float2bfloat16(x + v[0]); op[1] = __float2bfloat16(y + v[1]); op[2] = __float2bfloat16(z + v[2]);
    }
}

__global__ void __cluster_dims__(CS, 1, 1) __launch_bounds__(NTHR, 1)
fused_kernel(const __grid_constant__ Params prm, const __grid_constant__ CUtensorMap tmG, const __grid_constant__ CUtensorMap tmU,
             const __grid_constant__ CUtensorMap tmD, const __grid_constant__ CUtensorMap tmO, const __grid_constant__ CUtensorMap tmX, const __grid_constant__ CUtensorMap tmH)
{
    extern __shared__ __align__(1024) unsigned char smem[];
    const int tid = threadIdx.x, lane = tid & 31, warp = __shfl_sync(~0u, tid >> 5, 0);
    const int c = blockIdx.x >> 3, q = blockIdx.x & 7;
    const int nslot = (c < NCL - 1) ? 5 : 2;
    const int d0 = 40 * c;
    const uint32_t sb = opaque((uint32_t)__cvta_generic_to_shared(smem));
    const uint32_t mb = sb + SM_MB;
    Scratch& g_s = *prm.gs;
    const unsigned& zero = prm.zero;
    const uint32_t dch2 = min(d0 + q + ((tid >> 4) & ~7), D_ - 1) * 2;
    uint32_t pv[6], pLdt;
    const uint32_t pofs = opaque(dch2 * 128 + (tid & 127) * 2);
    pLdt = ldg16((const char*)prm.logdt + dch2);
#pragma unroll
    for (int i = 0; i < 2; i++) pv[i] = ldg16((const char*)prm.prm6[i] + pofs);
    STAMP(0);

    if (warp >= 20) {
        unsigned epoch = 0;
        if (warp == 20) {
            if (lane == 0) {
#pragma unroll
                for (int i = 0; i < 13; i++)
                    asm volatile("mbarrier.init.shared::cta.b64 [%0], %1;" :: "r"(mb + i * 8), "r"((i == MB_R || i < 2) ? 2 : i < 5 ? (nslot + 1) / 3 : i == MB_Y ? 1 + 4 * nslot : 1) : "memory");
                asm volatile("fence.mbarrier_init.release.cluster;" ::: "memory");
                arm(mb + MB_W1 * 8, 92160); arm(mb + MB_W2 * 8, nslot * 9216); arm(mb + MB_KEY * 8, 256); arm(mb + MB_GU * 8, nslot * 1024); arm(mb + MB_T * 8, 576 * XW);
                const int bytes = max(min(18, L_ - 18 * (int)blockIdx.x), 1) * (D_ * 2);
                arm(mb + MB_R * 8, bytes);
            }
            __syncwarp();
        } else if (warp == 22) {
            epoch = ld_rlx(&g_s.epoch);
            if (lane < 18 ? 18 * c + lane < 256 : lane < 31) (lane < 18 ? &g_s.acc[256 * q + 18 * c] : &g_s.fin[13 * (int)blockIdx.x - 18])[lane] = make_float4(0.f, 0.f, 0.f, 0.f);
        } else if (warp == 23 && lane == 0) asm volatile("prefetch.tensormap [%0];" :: "l"(&tmX) : "memory");
        asm volatile("barrier.cluster.arrive.relaxed.aligned;" ::: "memory");
        bar_sync(12, NTHR);
        uint4 wv = make_uint4(0, 0, 0, 0), wv2, wv3;
        if (warp == 22) {
            if (lane == 0) { sts32(sb + SM_SC + 28, epoch); asm volatile("mbarrier.arrive.shared::cta.b64 _, [%0];" :: "r"(mb + MB_R * 8) : "memory"); }
            epoch++;
            asm volatile("fence.acq_rel.gpu;" ::: "memory");
            __syncwarp();
            if (lane == 0) asm volatile("red.relaxed.gpu.global.add.u32 [%0], 1;" :: "l"(&g_s.zcnt) : "memory");
            STAMP(1);
            wv2 = ldg128((const uint4*)prm.wr + lane); wv3 = ldg128((const uint4*)prm.wr + 32 + lane);
            if (lane < 8) wv = ldg128((const uint4*)prm.wr + 64 + lane);
            if (lane < 5) {
                uint4 v = make_uint4(0, 0, 0, 0);
                if (lane < nslot) v = ldg128((const uint4*)(prm.wr + d0) + lane);
                sts128(sb + SM_DW + lane * 16, v.x, v.y, v.z, v.w);
            }
            __syncwarp();
            if (lane < 5) asm volatile("mbarrier.arrive.shared::cta.b64 _, [%0];" :: "r"(mb + (MB_X + lane) * 8) : "memory");
        }
        if (warp == 21) {
            if (lane == 0) { asm volatile("prefetch.tensormap [%0];" :: "l"(&tmG) : "memory"); asm volatile("prefetch.tensormap [%0];" :: "l"(&tmU) : "memory"); asm volatile("prefetch.tensormap [%0];" :: "l"(&tmD) : "memory"); }
            __syncwarp();
            const float dsk = bf_lo(ldg16(prm.dskip + min(d0 + 2 * (lane & 28) + q, D_ - 1)));
            bar_sync(0, 672);
            {
                const uint2 m = lds64(sb + SM_KG + min(lane, 19) * 8);
                unsigned Em = max(m.x, __shfl_xor_sync(~0u, m.x, 1));
                Em = max(Em, __shfl_xor_sync(~0u, Em, 2));
                Em = max(Em, min(__float_as_uint(fabsf(dsk) * (1.f / 8192.f)) >> 23, 253u));
                const float f = __uint_as_float(max((int)(127 + m.x - Em), 0) << 23);
                float s0 = (float)(int)m.y * f;
                s0 += __shfl_xor_sync(~0u, s0, 1); s0 += __shfl_xor_sync(~0u, s0, 2);
                if (lane < 20) {
                    sts16(sb + SM_RK + lane * 2, pack_f16(f, 0.f));
                    sts32(sb + SM_SC + (lane & 28), Em * 0x00800080u);
                    put16(sb + SM_PN + (lane >> 2) * PN_SZ, pack_f16(s0 * (1.f / 16777216.f) + dsk * __uint_as_float((254u - Em) << 23), 0.f));
                }
                __syncwarp();
            }
            bar_sync(15, 672);
            asm volatile("fence.proxy.async.shared::cta;" ::: "memory");
#pragma unroll 1
            for (int i = 0; i < 24; i++) {
                if (lane == 0) tma2d(sb + SM_WG + i * 3840, i < 12 ? &tmG : &tmU, 320 * c + 8 * nslot * q, 48 * (i < 12 ? i : i - 12), mb + MB_W1 * 8);
            }
            STAMP(1);
        } else {
        if (warp == 20) {
            if (lane == 0) {
                asm volatile("cp.async.bulk.shared::cluster.global.mbarrier::complete_tx::bytes [%0], [%1], %2, [%3];"
                             :: "r"(sb + SM_ROW), "l"(prm.x + min(18 * (int)blockIdx.x, L_ - 1) * D_), "r"(max(min(18, L_ - 18 * (int)blockIdx.x), 1) * (D_ * 2)), "r"(mb + MB_R * 8) : "memory");
            }
            __syncwarp();
            mbar_wait(mb + MB_R * 8);
            if (lane == 0) {
                asm volatile("cp.async.bulk.tensor.5d.shared::cluster.global.mbarrier::complete_tx::bytes [%0], [%1, {%3, %4, %5, %5, %5}], [%2];"
                             :: "r"(sb + SM_XTL), "l"(&tmX), "r"(mb + MB_T * 8), "r"(d0 & ~15), "r"(8 * q), "r"(0) : "memory");
            }
            STAMP(6);
        }
        {
            const int idx = lane * 3 + max(warp - 21, 0), sl = nslot - 1 - (idx >> 3), pe = (idx + q + 1) & 7;
            const uint32_t rb_ = mapa(sb, pe);
            uint32_t cd = rb_ + SM_U + 128 + q * UP + sl * US, cs = sb + SM_XT + 128 + (q & 3) * 16 + pe * YP + sl * YS, cm = rb_ + SM_MB + (MB_X + sl) * 8;
            int act = sl < 0 ? 0 : pe == q ? -1 : 1;
            PIN(cd); PIN(cs); PIN(cm); PIN(act);
            asm volatile("barrier.cluster.wait.aligned;" ::: "memory");
            mbar_wait(mb + MB_R * 8);
            bar_sync(13, 608);
            asm volatile("fence.proxy.async.shared::cta;" ::: "memory");
            if (act < 0) arm(cm, 7 * 512);
            __syncwarp();
            if (act > 0)
                asm volatile("cp.async.bulk.shared::cluster.shared::cta.mbarrier::complete_tx::bytes [%0], [%1], 512, [%2];" :: "r"(cd), "r"(cs), "r"(cm) : "memory");
        }
        STAMP(1);
        if (warp == 20 && lane == 0) { asm volatile("prefetch.tensormap [%0];" :: "l"(&tmO) : "memory"); asm volatile("prefetch.tensormap [%0];" :: "l"(&tmH) : "memory"); }
        if (warp == 22) {
            __syncwarp();
            mbar_wait(mb + (MB_X + 1) * 8);
            const uint32_t old = (epoch & 1) ? 0u : 0x40004000u;
#pragma unroll
            for (int t = 0; t < 2; t++)
                if ((lane & 7) < 6) g_s.cand[((q * 8 + 4 * t + (lane >> 3)) * NCL + c) * 6 + (lane & 7)] = make_uint4(old, old, old, old);
            float a[4] = {0.f, 0.f, 0.f, 0.f};
            const uint32_t one = 0x3F803F80u;
            mma_bf16(a, one, one, one, one, wv.x, wv.y);  mma_bf16(a, one, one, one, one, wv.z, wv.w);
            mma_bf16(a, one, one, one, one, wv2.x, wv2.y); mma_bf16(a, one, one, one, one, wv2.z, wv2.w);
            mma_bf16(a, one, one, one, one, wv3.x, wv3.y); mma_bf16(a, one, one, one, one, wv3.z, wv3.w);
            float s = a[0] + a[1];
            s += __shfl_xor_sync(~0u, s, 1); s += __shfl_xor_sync(~0u, s, 2);
            stsf(sb + SM_SC + 24, s);
            __syncwarp();
            if (lane == 0) {
                int n = 0;
                while ((int)(ld_acq(&g_s.zcnt) - epoch * NCTA) < 0 && ++n < SPIN_LIMIT) __nanosleep(200);
                arm(mb + MB_Y * 8, 8 * 512 * nslot);
                if (blockIdx.x == 0) g_s.epoch = epoch;
            }
            STAMP(2);
        }
        if (warp == 23) {
#pragma unroll 1
            for (int kk = nslot - 1; kk >= 0; kk--) {
                __syncwarp();
                bar_sync(6 + kk, 160);
                if (kk < 2) mbar_wait(mb + MB_W1 * 8);
                if (lane == 0) { asm volatile("fence.proxy.async.shared::cta;" ::: "memory"); tma2d(sb + SM_FAR + kk * FAR_SZ, &tmD, 72 * q, 320 * c + 64 * kk, mb + MB_W2 * 8); }
            }
        }
        }
        __syncwarp();
        if (warp == 20) {
            bar_sync(11, 672);
            asm volatile("fence.proxy.async.shared::cta;" ::: "memory");
            bar_sync(14, 768);
            if (elect()) {
                asm volatile("cp.async.bulk.tensor.5d.global.shared::cta.bulk_group [%0, {%2, %4, %4, %4, %3}], [%1];" :: "l"(&tmH), "r"(sb + SM_XT + 16384), "r"(d0 + ((c & 1) ? 0 : 32)), "r"(8 * q), "r"(0) : "memory");
                asm volatile("cp.async.bulk.tensor.5d.global.shared::cta.bulk_group [%0, {%2, %4, %4, %4, %3}], [%1];" :: "l"(&tmO), "r"(sb + SM_XT), "r"(d0 + (c & 1) * 8), "r"(8 * q), "r"(0) : "memory");
                asm volatile("cp.async.bulk.commit_group;" ::: "memory");
            }
        } else bar_sync(14, 768);
        __syncwarp();
        const uint32_t ft = (tid >> 4) & 7, fj = d0 / 3 + (lane & 15), tok = ~lds32(sb + SM_SEL + ft * 8) & 2047;
        float v[3], cnt = 0.f;
#pragma unroll
        for (int i = 0; i < 3; i++) {
            const uint32_t cl = 3 * fj + i - d0, cf = cl - (c & 1) * 8;
            const bool ok = cl < 8 * nslot && ((tok >> 3) & 7) == q;
            const uint32_t u = lds16(sb + SM_XT + (cf < 32 ? tslot(tok) * 64 + cf * 2 : 16384 + tslot(tok) * 16 + (cl & 7) * 2));
            v[i] = ok ? __uint_as_float(u << 16) : 0.f;
            if (ok) cnt += 1.f;
        }
        if (warp == 20 && elect()) {
            asm volatile("cp.async.bulk.wait_group 0;" ::: "memory");
            asm volatile("fence.proxy.async.global;" ::: "memory");
            asm volatile("mbarrier.arrive.shared::cta.b64 _, [%0];" :: "r"(mb + MB_OUT * 8) : "memory");
        }
        __syncwarp();
        mbar_wait(mb + MB_OUT * 8);
        STAMP(5);
        if (cnt != 0.f) finish(prm, (ft * 192 + fj) * 16, (tok * D_ + 3 * fj) * 2, v, cnt);
        return;
    }

    const int g = lane >> 2, cq = lane & 3;
    const int k = warp >> 2, wq = warp & 3;
    const int trow = 18 * blockIdx.x + warp;
    const bool rowact = warp < 18 && trow < L_;
#pragma unroll
    for (int i = 2; i < 6; i++) pv[i] = ldg16((const char*)prm.prm6[i] + pofs);
    const int tn = 16 * (warp & 15) + g;
    uint32_t xa[5], xb[5];
    asm volatile("barrier.cluster.arrive.relaxed.aligned;" ::: "memory");
    char* const st1p = (char*)g_s.st1 + opaque(((((trow >> 3) & 7) * 256 + ((trow >> 6) & 31) * 8 + (trow & 7)) * 8 + lane) * 4);
    const bool pub = rowact && (lane & 0x1B) == 0;
    if (pub) st_rlx128(st1p, 0, 0, 0, 0);
    {
        const uint32_t za = sb + SM_P + tid * 16;
        sts128(za, 0, 0, 0, 0);
        if (tid < (SM_MISC - SM_P) / 16 - 640) sts128(za + 10240, 0, 0, 0, 0);
        sts128(sb + SM_U + ((tid >> 3) & 7) * UP + k * US + (lane & 7) * 16, 0, 0, 0, 0);
    }
    bar_sync(12, NTHR);
    const uint32_t dep = lds32(sb + SM_P);
#define PV(x) __uint_as_float(__byte_perm(dep, x, 0x5410))
    STAMP(1);
    const uint32_t fb = sb + SM_FAR + k * FAR_SZ;
    const uint32_t pn = sb + SM_PN + k * PN_SZ, pf = sb + SM_PF + k * PF_SZ;
    unsigned epoch, t258;
    {
        const uint32_t kb = fb + wq * 3072;
        const uint32_t kl = kb + lane * 16;
        uint32_t Af[4][4];
        float sr, si, z1r, z1i, z2r, z2i, z4r, z4i, hr, hi_;
        {
            const float dt = bfr(ex2f(PV(pLdt) * 1.4426950408889634f));
            const float e2 = dt * PV(pv[0]) * 1.4426950408889634f, an = dt * PV(pv[1]);
            float ar, ai, br, bi, cr, ci, dr, di;
            { const float m = ex2f(e2 * 8.f); ar = m * __cosf(an * 8.f); ai = m * __sinf(an * 8.f); }
            csq(br, bi, ar, ai); csq(cr, ci, br, bi); csq(dr, di, cr, ci);
            const H2C m4 = splat(cr, ci);
            {
                float r3, i3;
                cmul(r3, i3, ar, ai, br, bi);
                expand4(kl, kl + 1024, pack_f16(1.f, ar), pack_f16(br, r3), pack_f16(0.f, ai), pack_f16(bi, i3), m4);
            }
            expand8(kl + 512, kl + 1536, dr, di, ar, ai, br, bi, m4);
            { const float m = ex2f(e2); z1r = m * __cosf(an); z1i = -m * __sinf(an); }
            cexp_s(hr, hi_, e2 * 128.f, an * (-128.f * 0.15915494309189535f));
            csq(z2r, z2i, z1r, z1i); csq(z4r, z4i, z2r, z2i);
            const uint32_t dep2 = lds32(sb + SM_P + 4);
#define PW(x) __uint_as_float(__byte_perm(dep2, x, 0x5410))
            cmul(sr, si, PW(pv[4]), PW(pv[5]), dt * PW(pv[2]), dt * PW(pv[3]));
            const unsigned E = min(max(__reduce_max_sync(~0u, __float_as_uint(fmaxf(fabsf(sr), fabsf(si)))) >> 23, 1u), 253u);
            const float sc = __uint_as_float((254u - E) << 23);
            sr *= sc; si *= -sc;
            sts64(sb + SM_KG + warp * 8, E, __reduce_add_sync(~0u, __float2int_rn(sr * 16777216.f)));
        }
        __syncwarp();
#pragma unroll
        for (int ks = 0; ks < 4; ks++) ldsm4t(Af[ks], kb + (lane >> 3) * 512 + (lane & 7) * 16 + ks * 128);
        STAMP(2);
        const uint32_t la = kb + ((lane >> 3) & 1) * 512 + (lane >> 4) * 128 + (lane & 7) * 16;
        uint32_t b0[4], b1[4], b2[4], b3[4];
        auto ln1 = [&]() {
        mbar_wait(mb + MB_R * 8);
        epoch = lds32(sb + SM_SC + 28) + 1;
        {
            const uint32_t ra = sb + SM_ROW + warp * (D_ * 2);
            const uint4 r0 = lds128(ra + lane * 16), r1 = lds128(ra + 512 + lane * 16);
            const uint32_t rx[9] = {r0.x, r0.y, r0.z, r0.w, r1.x, r1.y, r1.z, r1.w, lds32(ra + 1024 + lane * 4)};
            float a0 = bf_lo(rx[0]), a1 = bf_hi(rx[0]), c0 = a0 * a0, c1 = a1 * a1;
#pragma unroll
            for (int i = 1; i < 9; i++) { const float l = bf_lo(rx[i]), h = bf_hi(rx[i]); a0 += l; a1 += h; c0 = fmaf(l, l, c0); c1 = fmaf(h, h, c1); }
            a0 += a1; c0 += c1;
            float s1 = ((lane & 1) ? c0 : a0) + __shfl_xor_sync(~0u, (lane & 1) ? a0 : c0, 1);
#pragma unroll
            for (int o = 2; o < 32; o <<= 1) s1 += __shfl_xor_sync(~0u, s1, o);
            const float s2 = __shfl_xor_sync(~0u, s1, 1);
            const uint32_t ms = ln_stats(s1, s2);
            const uint32_t p0 = __byte_perm(ms, epoch | 0x8000u, 0x5410), p1 = rsplit(rcpf(bf_hi(ms)));
            if (pub) st_rlx128(st1p, p0, p1, p0, p1);
        }
        mbar_wait(mb + MB_R * 8);
        STAMP(1);
        };
        const uint4* sp = &g_s.st1[(256 * q + tn) * 2];
        uint2 sa, sc;
        auto poll = [&]() { sa = ld_rlx64(sp); sc = ld_rlx64(sp + 16); };
        auto norm = [&]() {
        STAMP(3);
        if (warp < 16) {
            uint32_t va[5], vc[5];
            poll();
            mbar_wait(mb + MB_T * 8);
            {
                const uint32_t xt = sb + SM_XTL + (c & 1) * 16 + (36 * (warp & 7) + 9 * (warp >> 3) + g) * (2 * XW);
                uint4 a4 = lds128(xt + cq * 16), b4 = lds128(xt + cq * 16 + 36 * XW);
                va[0] = a4.x; va[1] = a4.y; va[2] = a4.z; va[3] = a4.w; va[4] = lds32(xt + 64 + cq * 4);
                vc[0] = b4.x; vc[1] = b4.y; vc[2] = b4.z; vc[3] = b4.w; vc[4] = lds32(xt + (64 + 36 * XW) + cq * 4);
            }
            const int d4 = 2 * (lane >> 3) + (lane & 1), d1_ = lane & 7;
            const uint32_t own = SM_U + 128 + q * (UP - YP), oth = SM_XT + 128 + (q & 3) * 16;
            uint32_t a4 = sb + warp * 32 + d4 * YP + (d4 == q ? own : oth) + ((lane & 7) >> 1) * YS;
            uint32_t a1 = sb + warp * 32 + d1_ * YP + (d1_ == q ? own : oth) + 4 * YS + (lane & 8) * 2;
            PIN(a4); PIN(a1);
            uint32_t tag = __byte_perm(epoch | 0x8000u, 0, 0x1010);
            PIN(tag);
            mbar_wait(mb + MB_T * 8);
            int n = 0;
            while (__byte_perm(sa.x, sc.x, 0x7632) != tag && ++n < SPIN_LIMIT) poll();
            STAMP(4);
#pragma unroll
            for (int i = 0; i < 5; i++) {
                va[i] = norm2(va[i], sa.x, sa.y); va[i] = pack_f16(bf_lo(va[i]), bf_hi(va[i]));
                vc[i] = norm2(vc[i], sc.x, sc.y); vc[i] = pack_f16(bf_lo(vc[i]), bf_hi(vc[i]));
            }
            stsm4t(a4, va[0], va[1], va[2], va[3]); stsm4t(a4 + 16, vc[0], vc[1], vc[2], vc[3]); stsm2t(a1, va[4], vc[4]);
            bar_arrive(13, 608);
            {
            const uint32_t xh = sb + SM_XTL + (c & 1) * 16 + (9 * __byte_perm(0x12100200, 0x13110301, g) + 72 * (warp & 1) + (warp >> 1)) * (2 * XW);
            const uint4 c4 = lds128(xh + cq * 16), d4_ = lds128(xh + cq * 16 + 72 * XW);
            xa[0] = c4.x; xa[1] = c4.y; xa[2] = c4.z; xa[3] = c4.w; xa[4] = lds32(xh + 64 + cq * 4);
            xb[0] = d4_.x; xb[1] = d4_.y; xb[2] = d4_.z; xb[3] = d4_.w; xb[4] = lds32(xh + (64 + 72 * XW) + cq * 4);
            }
        }
        STAMP(5);
        __syncwarp();
        bar_sync(15, 672);
        Af[0][0] |= lds32(sb + SM_P);
        };
        cmul(sr, si, sr, si, z1r, z1i);
        {
            const H2C h4 = splat(z4r, z4i);
            expand8(kl, kl + 512, sr, si, z1r, z1i, z2r, z2i, h4);
            cmul(sr, si, sr, si, hr, hi_);
            expand8(kl + 1024, kl + 1536, sr, si, z1r, z1i, z2r, z2i, h4);
        }
        __syncwarp();
        ldsm4t(b0, la); ldsm4t(b1, la + 256); ldsm4t(b2, la + 1024); ldsm4t(b3, la + 1280);
        cmul(z1r, z1i, z1r, z1i, hr, hi_);
        cmul(sr, si, sr, si, z1r, z1i);
        expand8(kl, kl + 512, sr, si, z2r, z2i, z4r, z4i, splat(hr, hi_));
        asm volatile("barrier.cluster.wait.aligned;" ::: "memory");
        bar_arrive(0, 672);
        ln1();
        csq(z1r, z1i, z1r, z1i);
        cmul(sr, si, sr, si, z1r, z1i);
        csq(z2r, z2i, hr, hi_);
        expand8(kl + 1024, kl + 1536, sr, si, z4r, z4i, hr, hi_, splat(z2r, z2i));
        csq(z1r, z1i, z1r, z1i);
        cmul(sr, si, sr, si, z1r, z1i);
        csq(z4r, z4i, z2r, z2i);
        expand8(kl + 2048, kl + 2560, sr, si, hr, hi_, z2r, z2i, splat(z4r, z4i));
        norm();
        {
            uint32_t c0[4], c1[4], c2[4], c3[4], e0[4], e1[4];
            float t[6][4];
            ldsm4t(c0, la); ldsm4t(c2, la + 1024);
            mma_f16_z(t[0], Af[0], b0[0], b0[1]);
            const uint32_t lb = la | (__float_as_uint(t[0][0]) & zero);
            mma_f16_z(t[1], Af[0], b2[0], b2[1]); mma_f16_z(t[2], Af[0], c0[0], c0[1]); mma_f16_z(t[3], Af[0], c2[0], c2[1]);
            ldsm4t(e0, lb + 2048); ldsm4t(c1, lb + 256); ldsm4t(c3, lb + 1280); ldsm4t(e1, lb + 2304);
            mma_f16(t[0], Af[1], b0[2], b0[3]); mma_f16(t[1], Af[1], b2[2], b2[3]); mma_f16(t[2], Af[1], c0[2], c0[3]); mma_f16(t[3], Af[1], c2[2], c2[3]);
            mma_f16(t[0], Af[2], b1[0], b1[1]); mma_f16(t[1], Af[2], b3[0], b3[1]);
            mma_f16_z(t[4], Af[0], e0[0], e0[1]); mma_f16_z(t[5], Af[1], e0[2], e0[3]);
            mma_f16(t[2], Af[2], c1[0], c1[1]); mma_f16(t[3], Af[2], c3[0], c3[1]);
            mma_f16(t[4], Af[2], e1[0], e1[1]); mma_f16(t[5], Af[3], e1[2], e1[3]);
            mma_f16(t[0], Af[3], b1[2], b1[3]); mma_f16(t[1], Af[3], b3[2], b3[3]); mma_f16(t[2], Af[3], c1[2], c1[3]); mma_f16(t[3], Af[3], c3[2], c3[3]);
#pragma unroll
            for (int i = 0; i < 4; i++) t[4][i] += t[5][i];
            stsm4(kl + 1024, pack_f16(t[0][0], t[0][1]), pack_f16(t[0][2], t[0][3]), pack_f16(t[1][0], t[1][1]), pack_f16(t[1][2], t[1][3]));
            stsm2(kl + 1536, pack_f16(t[2][0], t[2][1]), pack_f16(t[2][2], t[2][3]));
            sts64(kb + lane * 8 + 1792, pack_f16(t[3][1], t[3][0]), pack_f16(t[3][3], t[3][2]));
            sts64(kb + lane * 8 + 2048, pack_f16(t[4][1], t[4][0]), pack_f16(t[4][3], t[4][2]));
        }
        bar_sync(1 + k, 128);
        const uint2 rr = lds64(opaque(sb + SM_RK + k * 8));
        const int tq = (wq + k + 2) & 3;
        const uint32_t ra = lane * 8 + opaque(fb + (tq == 1 ? 2048 : tq * 256 + 1024));
        auto comb = [&](uint32_t a, uint32_t& x, uint32_t& y) {
            const uint2 p0 = lds64(a), p1 = lds64(a + 3072), p2 = lds64(a + 6144), p3 = lds64(a + 9216);
            x = comb4(p0.x, p1.x, p2.x, p3.x, rr.x, rr.y); y = comb4(p0.y, p1.y, p2.y, p3.y, rr.x, rr.y);
        };
        uint32_t w0, w1;
        comb(ra, w0, w1);
        const bool last = lane == 31;
        if (tq == 0) {
            uint32_t v0, v1;
            comb(ra + 256, v0, v1);
            const uint32_t n0 = __shfl_sync(~0u, lane ? w0 : v0, lane + 1);
            uint32_t n1 = __shfl_sync(~0u, v0, lane + 1);
            if (last) n1 = v1 >> 16;
            sts128(pn + 12 + lane * 16, __byte_perm(w1, w0, 0x7610), __byte_perm(w1, 0, 0x1032), __byte_perm(n0, w1, 0x7610), __byte_perm(n0, 0, 0x1032));
            sts128(pn + 524 + lane * 16, __byte_perm(v1, v0, 0x7610), __byte_perm(v1, 0, 0x1032), __byte_perm(n1, v1, 0x7610), __byte_perm(n1, 0, 0x1032));
            if (lane == 0) { sts16(pn + 4, w0); sts32(pn + 8, __byte_perm(w0, 0, 0x1032)); }
        } else if (tq == 1) {
            const uint32_t ph = pf + P_H7 + (g & 1) * (2 * P_HS) + cq * 64 + (g >> 1) * 4 + (cq & 2) * 16, sw = (cq & 2) ? 0x3210 : 0x1032;
            w0 = __byte_perm(hmul2(w0, 0x18001800u), 0, sw); w1 = __byte_perm(hmul2(w1, 0x18001800u), 0, sw);
            const uint32_t pi = ph + 32 - (cq & 2) * 32;
            put16(ph, w0); put16(pi, w0 >> 16); put16(ph + 16, w1); put16(pi + 16, w1 >> 16);
        } else if (tq == 2) {
            uint32_t n = __shfl_sync(~0u, w0, lane == 30 ? 1 : lane + 2);
            if (last) { put16(pf, hmul2(w1, 0x18001800u) >> 16); w1 = hadd2(w1, hneg2(__byte_perm(w1, 0, 0x3232))); n = 0; }
            const bool od = lane & 1;
            const uint32_t pa = pn + 1036 + (lane >> 1) * 32 + (od ? 528 : 0), pb = pa + (od ? -16 : 16);
            const uint32_t u0 = od ? w1 : w0, x0 = od ? n : w1, u1 = od ? w0 : w1, x1 = od ? w1 : n;
            const uint32_t b0 = __byte_perm(u0, 0, 0x3232), b1 = __byte_perm(u1, 0, 0x3232);
            sts128(pa, __byte_perm(u0, 0, 0x1032), b0, b0, __byte_perm(x0, u0, 0x7610));
            sts128(pb, __byte_perm(u1, 0, 0x1032), b1, b1, __byte_perm(x1, u1, 0x7610));
        } else {
            const uint32_t pa = pf + ((g & 1) ? 3 * P_GS : P_GS) + cq * 32 + (g >> 1) * 4;
            const uint32_t pb = pa + ((g & 1) ? 4 - 3 * P_GS : P_GS);
            w0 = hmul2(w0, 0x18001800u); w1 = hmul2(w1, 0x18001800u);
            put16(pa, w0 >> 16); put16(pb, w0); put16(pa + 16, w1 >> 16); put16(pb + 16, w1);
            if (last) put16(pf + P_H7 + P_HS, w1);
        }
        bar_sync(1 + k, 128);
        t258 = w0;
    }
    STAMP(6);

    mbar_wait(mb + (MB_X + k) * 8);
    STAMP(7);
    if (k < nslot) {
        const int role = (wq + k) & 3;
        const uint32_t ub = sb + SM_U + k * US + 128;
        const uint32_t l16 = lane * 16, tz = (lane & 28) - 8 * cq, tz4 = tz * 4;
        if (role) {
            const uint32_t al = cq * (2 * UP + 32) + tz4, au = opaque(ub + (3 - role) * 128), a1 = al + au, a0 = (cq ? al : al + (8 * UP - 16)) + au - 2 * UP;
            const uint4 q0 = lds128(a0), q1 = lds128(a0 + UP), q2 = lds128(a1), q3 = lds128(a1 + UP);
            const uint32_t U[16] = {q0.x, q0.y, q0.z, q0.w, q1.x, q1.y, q1.z, q1.w, q2.x, q2.y, q2.z, q2.w, q3.x, q3.y, q3.z, q3.w};
            uint32_t V[14], Q[14], R4[12], T[8];
#pragma unroll
            for (int i = 2; i < 14; i++) { V[i] = __byte_perm(U[i], U[i + 1], 0x5432); Q[i] = hadd2(U[i], V[i]); }
            const uint32_t rb = l16 + opaque(fb + (3 - role) * 512);
#pragma unroll
            for (int i = 0; i < 8; i++) T[i] = hadd2(V[5 + i], Q[6 + i]);
            sts128(rb + F_E3, T[0], T[1], T[2], T[3]); sts128(rb + F_O3 + 16, T[4], T[5], T[6], T[7]);
            asm volatile("{ .reg .pred p; setp.ne.u32 p, %10, 1; @p st.shared.v4.u32 [%0], {%2,%3,%4,%5}; @p st.shared.v4.u32 [%1], {%6,%7,%8,%9}; }"
                         :: "r"(rb + F_E2), "r"(rb + F_O2), "r"(Q[6]), "r"(Q[7]), "r"(Q[8]), "r"(Q[9]), "r"(Q[10]), "r"(Q[11]), "r"(Q[12]), "r"(Q[13]), "r"(role) : "memory");
#pragma unroll
            for (int i = 2; i < 12; i++) R4[i] = hadd2(Q[i], Q[i + 1]);
#pragma unroll
            for (int i = 0; i < 8; i++) T[i] = hadd2(R4[3 + i], U[5 + i]);
            sts128(rb + F_O5, T[0], T[1], T[2], T[3]); sts128(rb + F_E5, T[4], T[5], T[6], T[7]);
            if (role != 1) {
                uint32_t S[8];
#pragma unroll
                for (int i = 0; i < 8; i++) S[i] = hadd2(R4[2 + i], i < 7 ? T[i + 1] : hadd2(R4[11], U[13]));
                sts128(rb + F_O9, S[0], S[1], S[2], S[3]); sts128(rb + F_E9 + 16, S[4], S[5], S[6], S[7]);
#pragma unroll
                for (int i = 0; i < 8; i++) S[i] = hadd2(T[i], hadd2(V[2 + i], V[5 + i]));
                sts128(rb + F_E7, S[0], S[1], S[2], S[3]); sts128(rb + F_O7, S[4], S[5], S[6], S[7]);
            }
        } else if (lane == 0) {
            const uint4 m = lds128(ub + 23 * 16 + 7 * UP);
            const uint32_t U[6] = {lds32(ub + 23 * 16 + 6 * UP + 12), m.x, m.y, m.z, m.w, lds32(ub + 24 * 16)};
            uint32_t Q[5];
#pragma unroll
            for (int i = 0; i < 5; i++) Q[i] = hadd2(U[i], __byte_perm(U[i], U[i + 1], 0x5432));
            sts128(fb + F_O5 + 96 * 16, hadd2(hadd2(Q[0], Q[1]), U[2]), hadd2(hadd2(Q[1], Q[2]), U[3]), hadd2(hadd2(Q[2], Q[3]), U[4]), hadd2(hadd2(Q[3], Q[4]), U[5]));
            sts128(fb + F_O3, 0, 0, 0, 0); sts128(fb + F_E9, 0, 0, 0, 0);
            sts16(pn + 258 * 4, t258);
        }
        bar_sync(1 + k, 128);
        float acc[4][4];
        uint32_t Q[4][4];
        {
            const int h = role & 1, part = role >> 1;
            float fa[7][4];
            uint32_t B[3][4];
            const uint32_t po = tz + opaque(pf + part * (2 * P_GS)), ba = l16 + opaque(fb + (part == h ? 0 : F_O5 + h * 16));
#pragma unroll
            for (int s = 1; s >= 0; s--) {
#pragma unroll
                for (int i = 0; i < 3; i++) { Q[i][0] = lds32(po + (s * P_GS + i * 64)); if (i < 2) Q[i][1] = lds32(po + (s * P_GS + i * 64 + 32)); }
#pragma unroll
                for (int i = 0; i < 3; i++) ldsm4t(B[i], ba + (s * F_E3 + i * 512));
#pragma unroll
                for (int i = 0; i < 3; i++) { Q[i][3] = CP(Q[i][0]); if (i) Q[i][2] = CP(Q[i - 1][1]); }
                Q[0][2] = ZF(s ? tz : Q[0][0]); Q[2][1] = ZF(s ? l16 : Q[2][0]);
#pragma unroll
                for (int dl = 0; dl < 3; dl++)
#pragma unroll
                    for (int ap = 0; ap < 6 - dl; ap++) {
                        if (s == 1 && dl == 0) mma_f16_z(fa[ap + 1], Q[0], B[ap >> 1][2 * (ap & 1)], B[ap >> 1][2 * (ap & 1) + 1]);
                        else mma_f16(fa[ap + 1 + dl], Q[dl], B[ap >> 1][2 * (ap & 1)], B[ap >> 1][2 * (ap & 1) + 1]);
                    }
            }
#pragma unroll 1
            for (int s = role; s == 1; s++) {
                ldsm2t(B[0][0], B[0][1], fb + ((lane & 15) == 15 ? F_O5 : F_O3));
#pragma unroll
                for (int dl = 1; dl < 3; dl++) mma_f16(fa[dl], Q[dl], B[0][0], B[0][1]);
            }
            const uint32_t bh = l16 + opaque(fb + F_E7 + h * F_H + part * 2048), ph = tz + opaque(pf + P_H7 + part * (2 * P_HS));
#pragma unroll 1
            for (int s = part; s == 1; s++) {
                Q[2][1] = ZF(Q[2][3]); Q[2][2] = ZF(Q[2][2]); Q[2][0] = lds32(ph - P_HS);
                ldsm4t(B[0], bh - 1024); ldsm4t(B[1], bh - 512);
                Q[2][3] = CP(Q[2][0]);
#pragma unroll
                for (int ap = 0; ap < 4; ap++) mma_f16(fa[ap + 3], Q[2], B[ap >> 1][2 * (ap & 1)], B[ap >> 1][2 * (ap & 1) + 1]);
            }
            {
                Q[0][2] = ZF(tid);
#pragma unroll
                for (int i = 0; i < 4; i++) { Q[i][0] = lds32(ph + i * 64); Q[i][1] = lds32(ph + (i * 64 + 32)); }
                ldsm4t(B[0], bh); ldsm4t(B[1], bh + 512);
#pragma unroll
                for (int i = 0; i < 4; i++) { Q[i][3] = CP(Q[i][0]); if (i) Q[i][2] = CP(Q[i - 1][1]); }
#pragma unroll
                for (int dl = 0; dl < 4; dl++)
#pragma unroll
                    for (int ap = 0; ap < 4 - dl; ap++) mma_f16(fa[ap + 3 + dl], Q[dl], B[ap >> 1][2 * (ap & 1)], B[ap >> 1][2 * (ap & 1) + 1]);
            }
            const uint32_t da = (cq * 2048 + tz4) + opaque(fb + role * 128);
            bar_sync(1 + k, 128);
#pragma unroll
            for (int i = 1; i < 4; i++)
                stsm4(da + i * 512, pack_f16(fa[2 * i - 1][0], fa[2 * i - 1][1]), pack_f16(fa[2 * i - 1][2], fa[2 * i - 1][3]),
                      pack_f16(fa[2 * i][0], fa[2 * i][1]), pack_f16(fa[2 * i][2], fa[2 * i][3]));
            asm("shl.b32 %0, 0x6000, %1;" : "=r"(Q[0][0]) : "r"(tz4));
            Q[0][1] = ZF(Q[0][0]); Q[0][2] = ZF(tz4); Q[0][3] = CP(Q[0][0]);
            const uint32_t ra = l16 + opaque(fb + wq * 2016);
            acc[0][0] = acc[0][1] = acc[0][2] = acc[0][3] = 0.f;
            if (wq == 3) {
                const uint32_t uw = lds32(ub), kw = lds32(pf);
                const float2 uf = __half22float2(*(const __half2*)&uw);
                if ((lane | 4) == 31) acc[0][3] = (lane == 31 ? uf.x + uf.y : uf.x) * (__low2float(*(const __half2*)&kw) * 512.f);
            }
            bar_sync(1 + k, 128);
#pragma unroll
            for (int i = 1; i < 4; i++) {
                ldsm4(B[0], ra + i * 512);
                mma_f16_z(acc[i], Q[0], hadd2(B[0][0], B[0][2]), hadd2(B[0][1], B[0][3]));
            }
        }
        bar_arrive(6 + k, 160);
        STAMP(8);
        const uint32_t inv = lds32(opaque(sb + SM_SC + k * 4));
        const uint32_t yd = l16 + opaque(mapa(sb, 2 * wq) + (SM_XT + 128 + q * YP + k * YS + (k >> 2) * (q >> 1) * 16));
        {
            uint32_t pu = opaque(pn + 64 * (wq - 3));
#define pp (tz + pu)
            const uint32_t dlo = (((ub + 6 * UP) & 0x3FFFF) >> 4) | ((UP >> 4) << 16);
            uint32_t R[4][4];
            unsigned long long ds[4];
#pragma unroll
            for (int i = 0; i < 4; i++) asm volatile("mov.b64 %0, {%1, %2};" : "=l"(ds[i]) : "r"(dlo - i * (2 * UP >> 4)), "r"(8 | zero));
            auto loadQ = [&](uint32_t (&X)[4][4], uint32_t prev) {
#pragma unroll
                for (int i = 0; i < 4; i++) { X[i][0] = lds32(pp + i * 64); X[i][1] = lds32(pp + i * 64 + 32); }
                X[0][2] = CP(prev);
#pragma unroll
                for (int i = 0; i < 4; i++) { X[i][3] = CP(X[i][0]); if (i) X[i][2] = CP(X[i - 1][1]); }
                pu += 256;
            };
            auto issue = [&](uint32_t (&X)[4][4]) {
                asm volatile("wgmma.fence.sync.aligned;" ::: "memory");
#pragma unroll
                for (int i = 0; i < 4; i++) wgmma32(acc, X[i], ds[i]);
                asm volatile("wgmma.commit_group.sync.aligned;" ::: "memory");
#pragma unroll
                for (int i = 0; i < 4; i++) asm volatile("{ .reg .b32 l, h; mov.b64 {l, h}, %0; add.u32 l, l, %1; mov.b64 %0, {l, h}; }" : "+l"(ds[i]) : "r"(~zero));
            };
#pragma unroll
            for (int i = 0; i < 4; i++) {
                Q[i][0] = Q[i][1] = 0;
                if (wq + i >= 3) { Q[i][0] = lds32(pp + i * 64); Q[i][1] = lds32(pp + i * 64 + 32); }
            }
            Q[0][2] = CP(0);
#pragma unroll
            for (int i = 0; i < 4; i++) { Q[i][3] = CP(Q[i][0]); if (i) Q[i][2] = CP(Q[i - 1][1]); }
            pu += 256;
#pragma unroll 1
            for (int dl = 0; dl < 4; dl++) {
                issue(Q);
                asm volatile("wgmma.wait_group.sync.aligned 1;" ::: "memory");
                loadQ(R, Q[3][1]);
                issue(R);
                asm volatile("wgmma.wait_group.sync.aligned 1;" ::: "memory");
                loadQ(Q, R[3][1]);
            }
            issue(Q);
            asm volatile("wgmma.wait_group.sync.aligned 0;" ::: "memory");
        }
        const uint32_t pstep = mapa(sb, 1) - mapa(sb, 0), ym = mapa(mb + MB_Y * 8, 2 * wq);
#pragma unroll
        for (int e = 0; e < 2; e++)
            st_async4(yd + e * pstep, bmul2(pack_bf16(acc[0][2 * e], acc[0][2 * e + 1]), inv), bmul2(pack_bf16(acc[1][2 * e], acc[1][2 * e + 1]), inv),
                      bmul2(pack_bf16(acc[2][2 * e], acc[2][2 * e + 1]), inv), bmul2(pack_bf16(acc[3][2 * e], acc[3][2 * e + 1]), inv), ym + e * pstep);
        if (lane == 0) asm volatile("mbarrier.arrive.shared::cta.b64 _, [%0];" :: "r"(mb + MB_Y * 8) : "memory");
    }
    STAMP(9);
    uint32_t ha[5], hb[5];
    if (warp < 16) {
        const uint4 wk = lds128(sb + SM_DW + cq * 16);
        uint32_t sel[5] = {wk.x, wk.y, wk.z, wk.w, lds32(sb + SM_DW + 64 + cq * 4)}, sel2[5];
#pragma unroll
        for (int i = 0; i < 5; i++) {
            if (!(g & 1)) sel[i] = 0x3F803F80u;
            sel2[i] = sel[i]; PIN(sel2[i]);
        }
        const uint32_t y4 = sb + SM_XT + 128 + warp * 32 + (2 * (lane >> 3) + (lane & 1)) * YP + ((lane & 7) >> 1) * YS;
        const uint32_t y1 = sb + SM_XT + 128 + warp * 32 + (lane & 7) * YP + 4 * YS + (lane & 8) * 2 + (lane & 6) * 8;
        uint32_t ao = (256 * q + tn) * 16, hta = sb + SM_HT + tn * 80;
        PIN(ao); PIN(hta);
        mbar_wait(mb + MB_Y * 8);
        STAMP(10);
        float ca[4] = {0.f, 0.f, 0.f, 0.f}, cb[4] = {0.f, 0.f, 0.f, 0.f};
        {
            uint32_t ya[4], yb[4], yc, yd;
            ldsm4t(ya, y4); ldsm4t(yb, y4 + 16); ldsm2t(yc, yd, y1);
#pragma unroll
            for (int i = 0; i < 4; i++) { ha[i] = badd2(xa[i], ya[i]); hb[i] = badd2(xb[i], yb[i]); }
            ha[4] = badd2(xa[4], yc); hb[4] = badd2(xb[4], yd);
        }
        if (nslot != 5) {
            ha[4] = hb[4] = 0;
            if (cq >= 2) ha[0] = ha[1] = ha[2] = ha[3] = hb[0] = hb[1] = hb[2] = hb[3] = 0;
        }
#pragma unroll
        for (int i = 0; i < 5; i++) { mma_bf16_k8(ca, ha[i], sel[i], ha[i]); mma_bf16_k8(cb, hb[i], sel2[i], hb[i]); }
        if (!(g & 1)) { ca[1] = ca[0]; cb[1] = cb[0]; }
        if (cq == (g >> 1)) {
            asm volatile("red.relaxed.gpu.global.add.v4.f32 [%0], {%1,%2,%3,%4};" :: "l"((char*)g_s.acc + ao), "f"(1.0f), "f"(ca[1]), "f"(ca[2]), "f"(ca[3]) : "memory");
            asm volatile("red.relaxed.gpu.global.add.v4.f32 [%0], {%1,%2,%3,%4};" :: "l"((char*)g_s.acc + ao + 128), "f"(1.0f), "f"(cb[1]), "f"(cb[2]), "f"(cb[3]) : "memory");
        }
        sts128(hta + cq * 16, ha[0], ha[1], ha[2], ha[3]); sts32(hta + 64 + cq * 4, ha[4]);
        sts128(hta + cq * 16 + 640, hb[0], hb[1], hb[2], hb[3]); sts32(hta + 704 + cq * 4, hb[4]);
        STAMP(11);
    }
    const int kq = warp / 5, mt = warp - 5 * kq;
    const int mi = lane >> 3, mr = lane & 7;
    const unsigned tk = (unsigned)tid / 72u, ck = tid - tk * 72;
    uint32_t A[9][4];
    auto loadA = [&]() {
        mbar_wait(mb + MB_W1 * 8);
        const uint32_t aa = sb + (mi & 1) * SM_WU + (8 * (mi >> 1) + mr) * 80 + (144 * 80 * kq + mt * 16);
#pragma unroll
        for (int s = 0; s < 9; s++) ldsm4t(A[s], aa + s * 1280);
    };
    const uint32_t par = (lds32(sb + SM_SC + 28) & 1) ? 0u : 0x40004000u;
    uint32_t go = (ck / 5u + ck) * 16, gs = sb + SM_SEL + 4 + (tk & 7) * 8;
    unsigned long long gb = (unsigned long long)((const char*)g_s.cand + go);
    uint32_t xs = sb + SM_XS + tk * 16 + tid * 16;
    asm volatile("add.u64 %0, %0, %1;" : "+l"(gb) : "l"((unsigned long long)zero));
    PIN(xs); PIN(gs);
    auto outtile = [&]() {
        const uint2 sa = lds64(sb + SM_ST + tn * 8), sbb = lds64(sb + SM_ST + tn * 8 + 64);
#pragma unroll
        for (int i = 0; i < 5; i++) { ha[i] = badd2(ha[i], norm2(ha[i], sa.x, sa.y)); hb[i] = badd2(hb[i], norm2(hb[i], sbb.x, sbb.y)); }
        const bool hf = (c & 1) && cq == 0;
        const uint32_t o16 = sb + SM_XT + (hf ? 16384 + tn * 16 : tn * 64 + (cq - (c & 1)) * 16), o4 = sb + SM_XT + ((c & 1) ? tn * 64 + 48 : 16384 + tn * 16) + cq * 4;
        sts128(o16, ha[0], ha[1], ha[2], ha[3]); sts32(o4, ha[4]);
        sts128(o16 + (hf ? 128 : 512), hb[0], hb[1], hb[2], hb[3]); sts32(o4 + ((c & 1) ? 512 : 128), hb[4]);
    };
    if (warp < 8) {
        const float wsum = ldsf(sb + SM_SC + 24);
        const uint32_t idx = 2047 - (512 * ((tid >> 1) & 3) + 128 * ((tid >> 3) & 3) + 64 * (tid & 1) + 8 * q + warp);
        uint32_t km0 = mapa(mb + MB_KEY * 8, 2 * cq), km1 = mapa(mb + MB_KEY * 8, 2 * cq + 1), ka0 = mapa(sb + SM_RK + q * 32, 2 * cq), ka1 = mapa(sb + SM_RK + q * 32, 2 * cq + 1);
        unsigned long long c0 = (unsigned long long)((char*)g_s.cand + ((q * 8 * NCL + c) * 6 + cq) * 16), c1 = c0 + (64 - cq * 12);
        uint32_t hc = sb + SM_HT + cq * 16, h4a = sb + SM_HT + 64 + cq * 4;
        uint32_t ca = sb + SM_KEY + warp * 128 + (warp & 1) * 32 + (lane & 28), r2a = sb + SM_KEY + cq * 16 + (cq >> 1) * 128;
        PIN(ca); PIN(r2a); PIN(km0); PIN(km1); PIN(ka0); PIN(ka1); PIN(hc); PIN(h4a);
        asm volatile("add.u64 %0, %0, %2; add.u64 %1, %1, %2;" : "+l"(c0), "+l"(c1) : "l"((unsigned long long)zero));
        uint4 s; int n = 0;
        do { s = ld_rlx128(&g_s.acc[256 * q + tid]); } while (__uint_as_float(s.x) != (float)NCL && ++n < SPIN_LIMIT);
        STAMP(16);
        const uint32_t ox = __shfl_xor_sync(~0u, (lane & 1) ? s.z : s.w, 1);
        const uint32_t ms = ln_stats(__uint_as_float((lane & 1) ? ox : s.z), __uint_as_float(s.y));
        const float rs = rcpf(bf_hi(ms));
        const uint32_t rb = pack_bf16(0.f, fmaf(-bf_lo(ms), wsum, __uint_as_float((lane & 1) ? s.w : ox)) * rs);
        const uint32_t key = (((rb ^ (((int)rb >> 31) | 0x80000000u)) >> 16) << 11) | idx;
        sts32(sb + SM_KEY + tid * 4, key);
        sts64(sb + SM_ST + tid * 8, ms, rsplit(rs));
        __syncwarp();
        uint32_t rank = rank4<8, 16>(sb + SM_KEY + warp * 128, key, ~zero);
        {
            const uint32_t sa = (rank * 4 ^ (warp & 1) * 32) + opaque(sb + SM_KEY + warp * 128);
            sts32(sa, key); sts32(sa + 1024, tid);
        }
        __syncwarp();
        const uint32_t mk = lds32(ca), t = lds32(ca + 1024);
        STAMP(17);
        bar_sync(12, 512);
        STAMP(18);
        const uint4 hv = lds128(hc + t * 80);
        const uint2 sv = lds64(sb + SM_ST + t * 8);
        const uint32_t h4 = lds32(h4a + t * 80);
        rank = rank4<4, 256>(r2a, mk, ~zero);
        const uint32_t rr = bmul2(sv.y, 0x3C803C80u);
        const uint32_t p0 = (norm2(hv.x, sv.x, rr) & 0xBFFFBFFFu) | par, p1 = (norm2(hv.y, sv.x, rr) & 0xBFFFBFFFu) | par, p2 = (norm2(hv.z, sv.x, rr) & 0xBFFFBFFFu) | par,
                       p3 = (norm2(hv.w, sv.x, rr) & 0xBFFFBFFFu) | par, p4 = (norm2(h4, sv.x, rr) & 0xBFFFBFFFu) | par;
        rank += __shfl_xor_sync(~0u, rank, 1);
        rank += __shfl_xor_sync(~0u, rank, 2);
        if (rank < 8) {
            st_async1(ka0 + rank * 4, mk, km0); st_async1(ka1 + rank * 4, mk, km1);
            st_rlx128((void*)(c0 + (unsigned long long)rank * 1440), p0, p1, p2, p3);
            asm volatile("st.relaxed.gpu.global.u32 [%0], %1;" :: "l"(c1 + (unsigned long long)rank * 1440), "r"(p4) : "memory");
        }
        __syncwarp();
    } else {
        mbar_wait(mb + MB_Y * 8); loadA();
        if (warp < 16) {
            bar_sync(12, 512);
        }
    }
    if (warp < 16) {
        outtile();
        if (warp >= 8) {
            uint32_t src = ((tid >> 2) - 64) * 1440, ma = sb + SM_RK - 256 + (tid >> 2) * 4, ra = sb + SM_RK + cq * 16;
            PIN(src); PIN(ma); PIN(ra);
            STAMP(19);
            mbar_wait(mb + MB_KEY * 8);
            STAMP(20);
            const uint32_t mk = lds32(ma);
            uint32_t rank = rank4<4, 64>(ra, mk, ~zero);
            rank += __shfl_xor_sync(~0u, rank, 1); rank += __shfl_xor_sync(~0u, rank, 2);
            sts64(sb + SM_SEL + rank * 8, mk, src);
        }
    }
    bar_sync(11, 672);
    STAMP(12);

    const char* gp = (const char*)gb + lds32(gs);
    uint4 hv = ld_rlx128(gp);
    if (warp < 8) loadA();
    uint32_t bx = sb + SM_XS + mr * 1168 + mi * 16 + 288 * kq, gd = mapa(sb, (kq & (NRED - 1)) * (8 / NRED)) + (SM_GU + (q * nslot + mt) * 128) + lane * 4;
    PIN(bx); PIN(gd);
    {
        if (warp < 18) {
            int n = 0;
            while (true) {
                sts128(xs, hv.x ^ par, hv.y ^ par, hv.z ^ par, hv.w ^ par);
                if (!__any_sync(~0u, ((hv.x ^ par) | (hv.y ^ par) | (hv.z ^ par) | (hv.w ^ par)) & 0x40004000u) || ++n >= SPIN_LIMIT) break;
                hv = ld_rlx128(gp);
            }
        }
    }
    bar_sync(14, 768);
    STAMP(13);
    {
        float c0[4] = {0.f, 0.f, 0.f, 0.f}, c1[4] = {0.f, 0.f, 0.f, 0.f}, c2[4] = {0.f, 0.f, 0.f, 0.f};
        uint32_t b[5][4];
#pragma unroll
        for (int s = 0; s < 4; s++) ldsm4(b[s], bx + s * 64);
        asm volatile("ldmatrix.sync.aligned.m8n8.x2.shared.b16 {%0,%1}, [%2];" : "=r"(b[4][0]), "=r"(b[4][1]) : "r"(bx + 256) : "memory");
        mma_bf16(c0, A[0][0], A[0][1], A[0][2], A[0][3], b[0][0], b[0][1]);
        mma_bf16(c1, A[1][0], A[1][1], A[1][2], A[1][3], b[0][2], b[0][3]);
        mma_bf16(c2, A[2][0], A[2][1], A[2][2], A[2][3], b[1][0], b[1][1]);
        mma_bf16(c0, A[3][0], A[3][1], A[3][2], A[3][3], b[1][2], b[1][3]);
        mma_bf16(c1, A[4][0], A[4][1], A[4][2], A[4][3], b[2][0], b[2][1]);
        mma_bf16(c2, A[5][0], A[5][1], A[5][2], A[5][3], b[2][2], b[2][3]);
        mma_bf16(c0, A[6][0], A[6][1], A[6][2], A[6][3], b[3][0], b[3][1]);
        mma_bf16(c1, A[7][0], A[7][1], A[7][2], A[7][3], b[3][2], b[3][3]);
        mma_bf16(c2, A[8][0], A[8][1], A[8][2], A[8][3], b[4][0], b[4][1]);
        sts128f(sb + SM_RED + tid * 16, c0[0] + c1[0] + c2[0], c0[1] + c1[1] + c2[1], c0[2] + c1[2] + c2[2], c0[3] + c1[3] + c2[3]);
    }
    bar_sync(1 + mt, 128);
    STAMP(21);
    if (mt < nslot && kq >= 4 - NRED) {
        const uint32_t ra = lane * 16 + opaque(sb + SM_RED + mt * 512);
        const float4 p0 = lds128f(ra), p1 = lds128f(ra + 2560), p2 = lds128f(ra + 5120), p3 = lds128f(ra + 7680);
        const float g0 = bfr(((p0.x + p1.x) + (p2.x + p3.x)) * 64.f), g1 = bfr(((p0.y + p1.y) + (p2.y + p3.y)) * 64.f);
        const uint32_t sg = pack_bf16(g0 * rcpf(1.f + ex2f(g0 * -1.4426950408889634f)), g1 * rcpf(1.f + ex2f(g1 * -1.4426950408889634f)));
        const uint32_t gu = bmul2(sg, pack_bf16(((p0.z + p1.z) + (p2.z + p3.z)) * 64.f, ((p0.w + p1.w) + (p2.w + p3.w)) * 64.f));
        const uint32_t pstep = mapa(sb, 1) - mapa(sb, 0), gm = mapa(mb + MB_GU * 8, (kq & (NRED - 1)) * (8 / NRED));
#pragma unroll
        for (int i = 0; i < 8 / NRED; i++) st_async1(gd + i * pstep, gu, gm + i * pstep);
    }
    mbar_wait(mb + MB_W2 * 8);
    {
        const uint32_t aa = sb + (8 * (mi >> 1) + mr) * 144 + (mi & 1) * 16 + (SM_FAR + 2304 * kq + mt * 32);
#pragma unroll
        for (int s = 0; s < 5; s++) ldsm4t(A[s], aa + s * FAR_SZ);
    }
    float sig; uint32_t ra2; unsigned long long fp, op;
    if (warp < 8) {
        const uint32_t key = lds32(sb + SM_SEL + warp * 8), k16 = key << 5, fj = 24 * q + lane;
        sig = bfr(rcpf(1.f + ex2f(__uint_as_float((k16 ^ (~((int)k16 >> 31) | 0x80000000u)) & 0xFFFF0000u) * -1.4426950408889634f)));
        ra2 = sb + SM_RED2 + warp * 304 + lane * 12;
        fp = (unsigned long long)(g_s.fin + warp * 192 + fj); op = (unsigned long long)(prm.out + (~key & 2047) * D_ + 3 * fj);
        PIN(ra2);
        asm volatile("add.u64 %0, %0, %3; add.u64 %1, %1, %3;" : "+l"(fp), "+l"(op), "+f"(sig) : "l"((unsigned long long)zero));
    }
    {
        uint32_t ba = sb + (SM_GU + 256 * kq) + (lane & 15) * 16 + (lane >> 4) * 1024, wa = sb + (SM_RED2 + kq * 2432 + mt * 64) + g * 4 + cq * 608;
        PIN(ba); PIN(wa);
        STAMP(22);
        mbar_wait(mb + MB_GU * 8);
        STAMP(23);
        float c0[4] = {0.f, 0.f, 0.f, 0.f}, c1[4] = {0.f, 0.f, 0.f, 0.f}, c2[4] = {0.f, 0.f, 0.f, 0.f};
        uint32_t b[2][4], b8, b9;
        ldsm4t(b[0], ba); ldsm4t(b[1], ba + 2048); ldsm2t(b8, b9, ba + 4096);
        mma_bf16(c0, A[0][0], A[0][1], A[0][2], A[0][3], b[0][0], b[0][1]);
        mma_bf16(c1, A[1][0], A[1][1], A[1][2], A[1][3], b[0][2], b[0][3]);
        if (nslot == 5) {
            mma_bf16(c2, A[4][0], A[4][1], A[4][2], A[4][3], b8, b9);
            mma_bf16(c0, A[2][0], A[2][1], A[2][2], A[2][3], b[1][0], b[1][1]);
            mma_bf16(c1, A[3][0], A[3][1], A[3][2], A[3][3], b[1][2], b[1][3]);
        }
        stsf(wa, c0[0] + c1[0] + c2[0]); stsf(wa + 304, c0[1] + c1[1] + c2[1]);
        if (mt < 4) { stsf(wa + 32, c0[2] + c1[2] + c2[2]); stsf(wa + 336, c0[3] + c1[3] + c2[3]); }
    }
    if (warp < 8) {
        float v[3];
        bar_sync(6, 640);
        STAMP(14);
        if (lane < 24) {
#pragma unroll
            for (int i = 0; i < 3; i++) v[i] = ((ldsf(ra2 + i * 4) + ldsf(ra2 + i * 4 + 2432)) + (ldsf(ra2 + i * 4 + 4864) + ldsf(ra2 + i * 4 + 7296))) * sig;
            asm volatile("{ .reg .f32 x, y, z, w; .reg .b16 a, b, c; .reg .pred p;\n"
                         "atom.relaxed.gpu.global.add.v4.f32 {x,y,z,w}, [%0], {%2,%3,%4,%5};\n"
                         "setp.eq.f32 p, w, %6; add.f32 x, x, %2; add.f32 y, y, %3; add.f32 z, z, %4;\n"
                         "cvt.rn.bf16.f32 a, x; cvt.rn.bf16.f32 b, y; cvt.rn.bf16.f32 c, z;\n"
                         "@p st.global.b16 [%1], a; @p st.global.b16 [%1 + 2], b; @p st.global.b16 [%1 + 4], c; }"
                         :: "l"(fp), "l"(op), "f"(v[0]), "f"(v[1]), "f"(v[2]), "f"(3.f), "f"(3.f * NCL) : "memory");
        }
    } else bar_arrive(6, 640);
    STAMP(15);
}

#undef pp
typedef __nv_bfloat16 bf16;
__device__ bf16 f_n[L_ * D_], f_h[L_ * D_];
__device__ float f_k[D_ * L_], f_r[L_], f_gu[8 * F_];
__device__ int f_idx[8];
__device__ __forceinline__ float b2f(bf16 v) { return __bfloat162float(v); }
__global__ void fb_ln(const bf16* in, const bf16* wr, bf16* out) {
    const int t = blockIdx.x * 8 + (threadIdx.x >> 5), lane = threadIdx.x & 31;
    const bf16* r = (in ? in : f_h) + t * D_;
    float s1 = 0.f, s2 = 0.f, s3 = 0.f;
    for (int i = lane; i < D_; i += 32) s1 += b2f(r[i]);
    for (int o = 16; o; o >>= 1) s1 += __shfl_xor_sync(~0u, s1, o);
    for (int i = lane; i < D_; i += 32) { const float d = b2f(r[i]) - s1 / D_; s2 += d * d; }
    for (int o = 16; o; o >>= 1) s2 += __shfl_xor_sync(~0u, s2, o);
    const float m = bfr(s1 / D_), sd = bfr(sqrtf(bfr(bfr(s2 / D_) + 1e-5f)));
    for (int i = lane; i < D_; i += 32) {
        const float v = bfr(bfr(b2f(r[i]) - m) / sd);
        f_n[t * D_ + i] = __float2bfloat16(v);
        if (!in) { s3 += v * b2f(wr[i]); out[t * D_ + i] = __float2bfloat16(b2f(r[i]) + v); }
    }
    for (int o = 16; o; o >>= 1) s3 += __shfl_xor_sync(~0u, s3, o);
    f_r[t] = bfr(s3);
}
__global__ void fb_taps(Params p) {
    const int d = blockIdx.x >> 3, l = (blockIdx.x & 7) * 256 + threadIdx.x;
    const float dt = bfr(expf(bf_lo(p.logdt[d]))), lf = bfr((float)l);
    float k = 0.f;
    for (int n = d * 128; n < d * 128 + 128; n++) {
        float wr, wi, sn, cs;
        cmul(wr, wi, bf_lo(p.prm6[4][n]), bf_lo(p.prm6[5][n]), dt * bf_lo(p.prm6[2][n]), dt * bf_lo(p.prm6[3][n]));
        sincosf(dt * bf_lo(p.prm6[1][n]) * lf, &sn, &cs);
        k += expf(dt * bf_lo(p.prm6[0][n]) * lf) * (wr * cs - wi * sn);
    }
    f_k[l * D_ + d] = k;
}
__global__ void fb_conv(Params p) {
    const int t = blockIdx.x, d = threadIdx.x;
    float y = 0.f;
    for (int l = 0; l <= t; l++) y += f_k[l * D_ + d] * b2f(f_n[(t - l) * D_ + d]);
    f_h[t * D_ + d] = __float2bfloat16(bf_lo(p.x[t * D_ + d]) + bfr(bfr(y) + bfr(b2f(f_n[t * D_ + d]) * bf_lo(p.dskip[d]))));
}
__global__ void fb_top() {
    const int t = blockIdx.x * 256 + threadIdx.x;
    int rank = 0;
    for (int j = 0; j < L_; j++) rank += f_r[j] > f_r[t] || (f_r[j] == f_r[t] && j < t);
    if (rank < 8) f_idx[rank] = t;
}
__global__ void fb_ffn1(const bf16* wg, const bf16* wu) {
    const int f = blockIdx.x * 256 + threadIdx.x, j = blockIdx.y;
    float g = 0.f, u = 0.f;
    for (int i = 0; i < D_; i++) { const float v = b2f(f_n[f_idx[j] * D_ + i]); g += v * b2f(wg[i * F_ + f]); u += v * b2f(wu[i * F_ + f]); }
    g = bfr(g);
    f_gu[j * F_ + f] = bfr(bfr(g / (1.f + expf(-g))) * bfr(u));
}
__global__ void fb_ffn2(const bf16* wd, bf16* out) {
    const int d = threadIdx.x, j = blockIdx.x, t = f_idx[j];
    float y = 0.f;
    for (int f = 0; f < F_; f++) y += f_gu[j * F_ + f] * b2f(wd[f * D_ + d]);
    out[t * D_ + d] = __float2bfloat16(b2f(f_h[t * D_ + d]) + bfr(b2f(f_n[t * D_ + d]) + bfr(bfr(y) * bfr(1.f / (1.f + expf(-f_r[t]))))));
}

typedef CUresult (*EncodeFn)(CUtensorMap*, CUtensorMapDataType, cuuint32_t, void*, const cuuint64_t*, const cuuint64_t*,
                             const cuuint32_t*, const cuuint32_t*, CUtensorMapInterleave, CUtensorMapSwizzle,
                             CUtensorMapL2promotion, CUtensorMapFloatOOBfill);

void make_map(EncodeFn fn, CUtensorMap* tm, const void* p, int cols, int rows, int bc, int br) {
    cuuint64_t dims[2] = {(cuuint64_t)cols, (cuuint64_t)rows};
    cuuint64_t strides[1] = {(cuuint64_t)cols * 2};
    cuuint32_t box[2] = {(cuuint32_t)bc, (cuuint32_t)br};
    cuuint32_t es[2] = {1, 1};
    fn(tm, CU_TENSOR_MAP_DATA_TYPE_BFLOAT16, 2, const_cast<void*>(p), dims, strides, box, es, CU_TENSOR_MAP_INTERLEAVE_NONE,
       CU_TENSOR_MAP_SWIZZLE_NONE, CU_TENSOR_MAP_L2_PROMOTION_L2_128B, CU_TENSOR_MAP_FLOAT_OOB_FILL_NONE);
}

void make_map3(EncodeFn fn, CUtensorMap* tm, const void* p) {
    cuuint64_t dims[5] = {(cuuint64_t)D_, 64, 2, 2, 8};
    cuuint64_t strides[4] = {(cuuint64_t)D_ * 2, (cuuint64_t)D_ * 2048, (cuuint64_t)D_ * 128, (cuuint64_t)D_ * 256};
    cuuint32_t box[5] = {XW, 9, 2, 2, 8};
    cuuint32_t es[5] = {1, 1, 1, 1, 1};
    fn(tm, CU_TENSOR_MAP_DATA_TYPE_BFLOAT16, 5, const_cast<void*>(p), dims, strides, box, es, CU_TENSOR_MAP_INTERLEAVE_NONE,
       CU_TENSOR_MAP_SWIZZLE_NONE, CU_TENSOR_MAP_L2_PROMOTION_NONE, CU_TENSOR_MAP_FLOAT_OOB_FILL_NONE);
}

void make_map5(EncodeFn fn, CUtensorMap* tm, const void* p, int bc) {
    cuuint64_t dims[5] = {(cuuint64_t)D_, 2, 4, 4, 64};
    cuuint64_t strides[4] = {(cuuint64_t)D_ * 128, (cuuint64_t)D_ * 1024, (cuuint64_t)D_ * 256, (cuuint64_t)D_ * 2};
    cuuint32_t box[5] = {(cuuint32_t)bc, 2, 4, 4, 8};
    cuuint32_t es[5] = {1, 1, 1, 1, 1};
    fn(tm, CU_TENSOR_MAP_DATA_TYPE_BFLOAT16, 5, const_cast<void*>(p), dims, strides, box, es, CU_TENSOR_MAP_INTERLEAVE_NONE,
       CU_TENSOR_MAP_SWIZZLE_NONE, CU_TENSOR_MAP_L2_PROMOTION_NONE, CU_TENSOR_MAP_FLOAT_OOB_FILL_NONE);
}

}

extern "C" void kernel_launch(void* const* d_in, const int* in_sizes, int n_in, void* d_out, int out_size) {
    (void)in_sizes; (void)n_in; (void)out_size;
    void* fp = nullptr;
    cudaDriverEntryPointQueryResult qr;
    cudaGetDriverEntryPoint("cuTensorMapEncodeTiled", &fp, cudaEnableDefault, &qr);
    EncodeFn fn = (EncodeFn)fp;
    CUtensorMap tmG, tmU, tmD, tmO, tmX, tmH;
    make_map3(fn, &tmX, d_in[0]);
    make_map(fn, &tmG, d_in[11], F_, D_, 40, 48);
    make_map(fn, &tmU, d_in[12], F_, D_, 40, 48);
    make_map(fn, &tmD, d_in[13], D_, F_, 72, 64);
    make_map5(fn, &tmO, d_out, 32);
    make_map5(fn, &tmH, d_out, 8);
    Params p;
    p.x = (const unsigned short*)d_in[0];
    for (int i = 0; i < 6; i++) p.prm6[i] = (const unsigned short*)d_in[1 + i];
    p.logdt = (const unsigned short*)d_in[7]; p.dskip = (const unsigned short*)d_in[8];
    p.wr = (const unsigned short*)d_in[10];
    p.out = (__nv_bfloat16*)d_out;
    p.zero = 0;
    cudaGetSymbolAddress((void**)&p.gs, g_s);
    cudaFuncSetAttribute(fused_kernel, cudaFuncAttributeMaxDynamicSharedMemorySize, SM_TOTAL);
    static int nclusters = -1;
    if (nclusters < 0) {
        cudaLaunchConfig_t cfg = {};
        cudaLaunchAttribute at;
        at.id = cudaLaunchAttributeClusterDimension; at.val.clusterDim.x = CS; at.val.clusterDim.y = 1; at.val.clusterDim.z = 1;
        cfg.gridDim = dim3(NCTA); cfg.blockDim = dim3(NTHR); cfg.dynamicSmemBytes = SM_TOTAL; cfg.attrs = &at; cfg.numAttrs = 1;
        if (cudaOccupancyMaxActiveClusters(&nclusters, fused_kernel, &cfg) != cudaSuccess) { (void)cudaGetLastError(); nclusters = NCL; }
    }
    if (nclusters >= NCL && !FORCE_FALLBACK) {
        fused_kernel<<<NCTA, NTHR, SM_TOTAL>>>(p, tmG, tmU, tmD, tmO, tmX, tmH);
        return;
    }
    fb_ln<<<L_ / 8, 256>>>((const bf16*)d_in[0], nullptr, nullptr);
    fb_taps<<<D_ * 8, 256>>>(p);
    fb_conv<<<L_, D_>>>(p);
    fb_ln<<<L_ / 8, 256>>>(nullptr, (const bf16*)d_in[10], p.out);
    fb_top<<<L_ / 256, 256>>>();
    fb_ffn1<<<dim3(F_ / 256, 8), 256>>>((const bf16*)d_in[11], (const bf16*)d_in[12]);
    fb_ffn2<<<8, D_>>>((const bf16*)d_in[13], p.out);
}
```

```cpp
#include <cuda_runtime.h>
#include <cuda_bf16.h>
#include <cuda_fp16.h>
#include <cuda.h>
#include <stdint.h>

namespace {

constexpr int L_ = 2048, D_ = 576, F_ = 4608;
constexpr int NCL = 15, CS = 8, NCTA = NCL * CS, NTHR = 768;
#define FORCE_FALLBACK 0
constexpr int XW = 48, NRED = 2;
constexpr int SPIN_LIMIT = 1 << 22;

constexpr int SM_WG   = 0;
constexpr int SM_WU   = 46080;
constexpr int YP = 3392, YS = 656;
constexpr int UP = 3280, US = 656;
constexpr int SM_XT   = 92160;
constexpr int SM_U    = SM_XT + 8 * YP;
constexpr int SM_FAR  = SM_U + 8 * UP;
constexpr int FAR_SZ  = 12416;
constexpr int F_E5 = 0, F_O5 = 1536, F_E3 = 3088, F_O3 = 4624, F_E7 = 6176, F_E2 = F_E7 + 1024, F_E9 = F_E7 + 2048,
              F_H = 3088, F_O7 = F_E7 + F_H, F_O2 = F_E2 + F_H, F_O9 = F_E9 + F_H;
constexpr int SM_P    = SM_FAR + 5 * FAR_SZ;
constexpr int PN_SZ = 584 * 4, SM_PN = SM_P + 65 * 4;
constexpr int P_GS = 50 * 4, P_H7 = 200 * 4, P_HS = 74 * 4;
constexpr int PF_SZ = (200 + 222) * 4, SM_PF = SM_PN + 5 * PN_SZ + 36;
constexpr int SM_MISC = SM_PF + 5 * PF_SZ;
constexpr int SM_ST   = SM_MISC;
constexpr int SM_RK   = SM_ST + 2048;
constexpr int SM_SEL  = SM_FAR + FAR_SZ + 10240;
constexpr int SM_KG   = SM_RK + 320;
constexpr int SM_SC   = SM_KG + 160;
constexpr int SM_DW   = SM_SC + 32;
constexpr int SM_MB   = SM_DW + 160;
constexpr int SM_TOTAL = SM_MB + 128;
constexpr int SM_ROW  = SM_XT - 20736;
constexpr int SM_XTL  = SM_ROW - 576 * XW;
constexpr int SM_RED2 = SM_WG;
constexpr int SM_HT   = SM_P - 512;
constexpr int SM_KEY  = SM_FAR + 10240 + 128;
constexpr int SM_CAND = SM_KEY + 1024;
constexpr int SM_XS   = SM_U;
constexpr int SM_GU   = SM_XS + 9344;
constexpr int SM_RED  = SM_GU + 5632;
static_assert(F_O9 + 1024 <= FAR_SZ && FAR_SZ % 128 == 0, "far overflow");
static_assert(SM_RED + 10240 <= SM_FAR && SM_HT + 20496 <= SM_MISC, "alias overflow");
static_assert(SM_TOTAL <= 232448, "smem overflow");
static_assert(SM_FAR % 128 == 0 && SM_XT % 128 == 0 && SM_XTL % 128 == 0 && SM_P % 16 == 0 && SM_MISC % 16 == 0 && SM_MB % 8 == 0, "align");

enum { MB_X = 0, MB_W1 = 5, MB_W2 = 6, MB_KEY = 7, MB_GU = 8, MB_Y = 9, MB_OUT = 10, MB_T = 11, MB_R = 12 };

struct __align__(128) Scratch {
    unsigned epoch, zcnt, pad[30];
    uint4  st1[L_ * 2];
    float4 acc[L_];
    uint4  cand[64 * NCL * 6];
    float4 fin[8 * 192 + 24];
};
__device__ Scratch g_s;
#define STAMP(i)

__device__ __forceinline__ uint32_t mapa(uint32_t a, uint32_t r) { uint32_t d; asm("mapa.shared::cluster.u32 %0, %1, %2;" : "=r"(d) : "r"(a), "r"(r)); return d; }
__device__ __forceinline__ void mbar_wait(uint32_t mb) {
    asm volatile("{ .reg .pred p, q; .reg .u32 n; mov.u32 n, 0;\n"
                 "W_%=: mbarrier.try_wait.parity.shared::cta.b64 p, [%0], 0; add.u32 n, n, 1; setp.lt.and.u32 q, n, 65536, !p; @q bra W_%=; }" :: "r"(mb) : "memory");
}
__device__ __forceinline__ bool elect() { uint32_t e; asm volatile("{ .reg .pred p; elect.sync _|p, 0xffffffff; selp.u32 %0, 1, 0, p; }" : "=r"(e)); return e; }
__device__ __forceinline__ void arm(uint32_t mb, uint32_t bytes) { asm volatile("mbarrier.arrive.expect_tx.shared::cta.b64 _, [%0], %1;" :: "r"(mb), "r"(bytes) : "memory"); }
__device__ __forceinline__ void bar_sync(int id, int n) { asm volatile("bar.sync %0, %1;" :: "r"(id), "r"(n) : "memory"); }
__device__ __forceinline__ void bar_arrive(int id, int n) { asm volatile("bar.arrive %0, %1;" :: "r"(id), "r"(n) : "memory"); }
__device__ __forceinline__ uint32_t lds16(uint32_t a) { unsigned short v; asm volatile("ld.shared.u16 %0, [%1];" : "=h"(v) : "r"(a) : "memory"); return v; }
__device__ __forceinline__ uint32_t lds32(uint32_t a) { uint32_t v; asm volatile("ld.shared.u32 %0, [%1];" : "=r"(v) : "r"(a) : "memory"); return v; }
__device__ __forceinline__ uint2 lds64(uint32_t a) { uint2 v; asm volatile("ld.shared.v2.u32 {%0,%1}, [%2];" : "=r"(v.x), "=r"(v.y) : "r"(a) : "memory"); return v; }
__device__ __forceinline__ float ldsf(uint32_t a) { float v; asm volatile("ld.shared.f32 %0, [%1];" : "=f"(v) : "r"(a) : "memory"); return v; }
__device__ __forceinline__ uint4 lds128(uint32_t a) { uint4 v; asm volatile("ld.shared.v4.u32 {%0,%1,%2,%3}, [%4];" : "=r"(v.x), "=r"(v.y), "=r"(v.z), "=r"(v.w) : "r"(a) : "memory"); return v; }
__device__ __forceinline__ float4 lds128f(uint32_t a) { float4 v; asm volatile("ld.shared.v4.f32 {%0,%1,%2,%3}, [%4];" : "=f"(v.x), "=f"(v.y), "=f"(v.z), "=f"(v.w) : "r"(a) : "memory"); return v; }
__device__ __forceinline__ void sts16(uint32_t a, uint32_t v) { asm volatile("{ .reg .b16 l, h; mov.b32 {l, h}, %1; st.shared.b16 [%0], l; }" :: "r"(a), "r"(v) : "memory"); }
__device__ __forceinline__ void sts32(uint32_t a, uint32_t v) { asm volatile("st.shared.u32 [%0], %1;" :: "r"(a), "r"(v) : "memory"); }
__device__ __forceinline__ void sts64(uint32_t a, uint32_t x, uint32_t y) { asm volatile("st.shared.v2.u32 [%0], {%1,%2};" :: "r"(a), "r"(x), "r"(y) : "memory"); }
__device__ __forceinline__ void stsf(uint32_t a, float v) { asm volatile("st.shared.f32 [%0], %1;" :: "r"(a), "f"(v) : "memory"); }
__device__ __forceinline__ void sts128(uint32_t a, uint32_t x, uint32_t y, uint32_t z, uint32_t w) { asm volatile("st.shared.v4.u32 [%0], {%1,%2,%3,%4};" :: "r"(a), "r"(x), "r"(y), "r"(z), "r"(w) : "memory"); }
__device__ __forceinline__ void sts128f(uint32_t a, float x, float y, float z, float w) { asm volatile("st.shared.v4.f32 [%0], {%1,%2,%3,%4};" :: "r"(a), "f"(x), "f"(y), "f"(z), "f"(w) : "memory"); }
__device__ __forceinline__ void ldsm4(uint32_t (&r)[4], uint32_t a) { asm volatile("ldmatrix.sync.aligned.m8n8.x4.shared.b16 {%0,%1,%2,%3}, [%4];" : "=r"(r[0]), "=r"(r[1]), "=r"(r[2]), "=r"(r[3]) : "r"(a) : "memory"); }
__device__ __forceinline__ void ldsm4t(uint32_t (&r)[4], uint32_t a) { asm volatile("ldmatrix.sync.aligned.m8n8.x4.trans.shared.b16 {%0,%1,%2,%3}, [%4];" : "=r"(r[0]), "=r"(r[1]), "=r"(r[2]), "=r"(r[3]) : "r"(a) : "memory"); }
__device__ __forceinline__ void ldsm2t(uint32_t& r0, uint32_t& r1, uint32_t a) { asm volatile("ldmatrix.sync.aligned.m8n8.x2.trans.shared.b16 {%0,%1}, [%2];" : "=r"(r0), "=r"(r1) : "r"(a) : "memory"); }
__device__ __forceinline__ void stsm4t(uint32_t a, uint32_t r0, uint32_t r1, uint32_t r2, uint32_t r3) { asm volatile("stmatrix.sync.aligned.m8n8.x4.trans.shared.b16 [%0], {%1,%2,%3,%4};" :: "r"(a), "r"(r0), "r"(r1), "r"(r2), "r"(r3) : "memory"); }
__device__ __forceinline__ void stsm4(uint32_t a, uint32_t r0, uint32_t r1, uint32_t r2, uint32_t r3) { asm volatile("stmatrix.sync.aligned.m8n8.x4.shared.b16 [%0], {%1,%2,%3,%4};" :: "r"(a), "r"(r0), "r"(r1), "r"(r2), "r"(r3) : "memory"); }
__device__ __forceinline__ void stsm2(uint32_t a, uint32_t r0, uint32_t r1) { asm volatile("stmatrix.sync.aligned.m8n8.x2.shared.b16 [%0], {%1,%2};" :: "r"(a), "r"(r0), "r"(r1) : "memory"); }
__device__ __forceinline__ void stsm2t(uint32_t a, uint32_t r0, uint32_t r1) { asm volatile("stmatrix.sync.aligned.m8n8.x2.trans.shared.b16 [%0], {%1,%2};" :: "r"(a), "r"(r0), "r"(r1) : "memory"); }
__device__ __forceinline__ uint4 ldg128(const void* p) { uint4 v; asm volatile("ld.global.nc.v4.u32 {%0,%1,%2,%3}, [%4];" : "=r"(v.x), "=r"(v.y), "=r"(v.z), "=r"(v.w) : "l"(p)); return v; }
__device__ __forceinline__ uint32_t ldg16(const void* p) { unsigned short v; asm volatile("ld.global.nc.u16 %0, [%1];" : "=h"(v) : "l"(p)); return v; }
__device__ __forceinline__ uint32_t opaque(uint32_t v) { uint32_t r; asm volatile("mov.b32 %0, %1;" : "=r"(r) : "r"(v)); return r; }
__device__ __forceinline__ void mma_f16(float (&d)[4], const uint32_t (&a)[4], uint32_t b0, uint32_t b1) {
    asm volatile("mma.sync.aligned.m16n8k16.row.col.f32.f16.f16.f32 {%0,%1,%2,%3}, {%4,%5,%6,%7}, {%8,%9}, {%0,%1,%2,%3};"
        : "+f"(d[0]), "+f"(d[1]), "+f"(d[2]), "+f"(d[3]) : "r"(a[0]), "r"(a[1]), "r"(a[2]), "r"(a[3]), "r"(b0), "r"(b1));
}
__device__ __forceinline__ void mma_f16_z(float (&d)[4], const uint32_t (&a)[4], uint32_t b0, uint32_t b1) {
    asm volatile("mma.sync.aligned.m16n8k16.row.col.f32.f16.f16.f32 {%0,%1,%2,%3}, {%4,%5,%6,%7}, {%8,%9}, {%10,%10,%10,%10};"
        : "=f"(d[0]), "=f"(d[1]), "=f"(d[2]), "=f"(d[3]) : "r"(a[0]), "r"(a[1]), "r"(a[2]), "r"(a[3]), "r"(b0), "r"(b1), "f"(0.f));
}
__device__ __forceinline__ void mma_bf16(float (&d)[4], uint32_t a0, uint32_t a1, uint32_t a2, uint32_t a3, uint32_t b0, uint32_t b1) {
    asm volatile("mma.sync.aligned.m16n8k16.row.col.f32.bf16.bf16.f32 {%0,%1,%2,%3}, {%4,%5,%6,%7}, {%8,%9}, {%0,%1,%2,%3};"
        : "+f"(d[0]), "+f"(d[1]), "+f"(d[2]), "+f"(d[3]) : "r"(a0), "r"(a1), "r"(a2), "r"(a3), "r"(b0), "r"(b1));
}
__device__ __forceinline__ void mma_bf16_k8(float (&d)[4], uint32_t a0, uint32_t a1, uint32_t b0) {
    asm volatile("mma.sync.aligned.m16n8k8.row.col.f32.bf16.bf16.f32 {%0,%1,%2,%3}, {%4,%5}, {%6}, {%0,%1,%2,%3};"
        : "+f"(d[0]), "+f"(d[1]), "+f"(d[2]), "+f"(d[3]) : "r"(a0), "r"(a1), "r"(b0));
}
__device__ __forceinline__ uint32_t pack_f16(float lo, float hi) { uint32_t r; asm("cvt.rn.f16x2.f32 %0, %1, %2;" : "=r"(r) : "f"(hi), "f"(lo)); return r; }
__device__ __forceinline__ uint32_t pack_bf16(float lo, float hi) { uint32_t r; asm("cvt.rn.bf16x2.f32 %0, %1, %2;" : "=r"(r) : "f"(hi), "f"(lo)); return r; }
__device__ __forceinline__ float bf_lo(uint32_t v) { return __uint_as_float(v << 16); }
__device__ __forceinline__ float bf_hi(uint32_t v) { return __uint_as_float(v & 0xFFFF0000u); }
__device__ __forceinline__ float bfr(float x) { return __uint_as_float(pack_bf16(0.f, x)); }
__device__ __forceinline__ uint32_t badd2(uint32_t a, uint32_t b) { uint32_t r; asm("add.rn.bf16x2 %0, %1, %2;" : "=r"(r) : "r"(a), "r"(b)); return r; }
__device__ __forceinline__ uint32_t bmul2(uint32_t a, uint32_t b) { uint32_t r; asm("mul.rn.bf16x2 %0, %1, %2;" : "=r"(r) : "r"(a), "r"(b)); return r; }
__device__ __forceinline__ uint32_t hadd2(uint32_t a, uint32_t b) { uint32_t r; asm("add.rn.f16x2 %0, %1, %2;" : "=r"(r) : "r"(a), "r"(b)); return r; }
__device__ __forceinline__ uint32_t hmul2(uint32_t a, uint32_t b) { uint32_t r; asm("mul.rn.f16x2 %0, %1, %2;" : "=r"(r) : "r"(a), "r"(b)); return r; }
__device__ __forceinline__ uint32_t hneg2(uint32_t a) { uint32_t r; asm("neg.f16x2 %0, %1;" : "=r"(r) : "r"(a)); return r; }
__device__ __forceinline__ float rcpf(float x) { float r; asm("rcp.approx.ftz.f32 %0, %1;" : "=f"(r) : "f"(x)); return r; }
__device__ __forceinline__ float sqrta(float x) { float r; asm("sqrt.approx.ftz.f32 %0, %1;" : "=f"(r) : "f"(x)); return r; }
__device__ __forceinline__ float ex2f(float x) { float r; asm("ex2.approx.ftz.f32 %0, %1;" : "=f"(r) : "f"(x)); return r; }
__device__ __forceinline__ void st_async4(uint32_t a, uint32_t x, uint32_t y, uint32_t z, uint32_t w, uint32_t mb) {
    asm volatile("st.async.shared::cluster.mbarrier::complete_tx::bytes.v4.u32 [%0], {%1,%2,%3,%4}, [%5];" :: "r"(a), "r"(x), "r"(y), "r"(z), "r"(w), "r"(mb) : "memory"); }
__device__ __forceinline__ void st_async1(uint32_t a, uint32_t x, uint32_t mb) {
    asm volatile("st.async.shared::cluster.mbarrier::complete_tx::bytes.u32 [%0], %1, [%2];" :: "r"(a), "r"(x), "r"(mb) : "memory"); }
__device__ __forceinline__ unsigned ld_rlx(const void* p) { unsigned v; asm volatile("ld.relaxed.gpu.global.u32 %0, [%1];" : "=r"(v) : "l"(p) : "memory"); return v; }
__device__ __forceinline__ unsigned ld_acq(const void* p) { unsigned v; asm volatile("ld.acquire.gpu.global.u32 %0, [%1];" : "=r"(v) : "l"(p) : "memory"); return v; }
__device__ __forceinline__ uint2 ld_rlx64(const void* p) { unsigned long long v; asm volatile("ld.relaxed.gpu.global.u64 %0, [%1];" : "=l"(v) : "l"(p) : "memory"); return make_uint2((unsigned)v, (unsigned)(v >> 32)); }
__device__ __forceinline__ void st_rlx128(void* p, uint32_t x, uint32_t y, uint32_t z, uint32_t w) {
    asm volatile("st.relaxed.gpu.global.v2.u64 [%0], {%1,%2};" :: "l"(p), "l"((unsigned long long)x | ((unsigned long long)y << 32)), "l"((unsigned long long)z | ((unsigned long long)w << 32)) : "memory"); }
__device__ __forceinline__ uint4 ld_rlx128(const void* p) { unsigned long long a, b; asm volatile("ld.relaxed.gpu.global.v2.u64 {%0,%1}, [%2];" : "=l"(a), "=l"(b) : "l"(p) : "memory"); return make_uint4((unsigned)a, (unsigned)(a >> 32), (unsigned)b, (unsigned)(b >> 32)); }
__device__ __forceinline__ void tma2d(uint32_t dst, const CUtensorMap* tm, int x, int y, uint32_t mb) {
    asm volatile("cp.async.bulk.tensor.2d.shared::cluster.global.mbarrier::complete_tx::bytes [%0], [%1, {%3, %4}], [%2];"
                 :: "r"(dst), "l"(tm), "r"(mb), "r"(x), "r"(y) : "memory");
}
__device__ __forceinline__ void cmul(float& xr, float& xi, float ar, float ai, float br, float bi) {
    const float r = fmaf(ar, br, -ai * bi), i = fmaf(ar, bi, ai * br); xr = r; xi = i;
}
__device__ __forceinline__ void csq(float& xr, float& xi, float ar, float ai) {
    const float r = fmaf(ar, ar, -ai * ai), i = (ar + ar) * ai; xr = r; xi = i;
}
__device__ __forceinline__ void cexp_s(float& zr, float& zi, float e2, float turns) {
    const float mag = ex2f(e2), r = (turns - rintf(turns)) * 6.283185307179586f;
    zr = mag * __cosf(r); zi = mag * __sinf(r);
}
__device__ __forceinline__ uint32_t ln_stats(float s1, float s2) {
    const float m = s1 * (1.f / D_);
    const float var = fmaxf(fmaf(s2, 1.f / D_, -m * m), 0.f);
    return pack_bf16(m, sqrta(bfr(bfr(var) + 1e-5f)));
}
__device__ __forceinline__ uint32_t rsplit(float rs) { const float h = bfr(rs); return pack_bf16(h, rs - h); }
__device__ __forceinline__ uint32_t norm2(uint32_t v, uint32_t mx, uint32_t hl) {
    uint32_t r;
    asm("{ .reg .b16 m, h, l, x; .reg .b32 m2, h2, l2, d, t; mov.b32 {m, x}, %2; mov.b32 {h, l}, %3; mov.b32 m2, {m, m}; mov.b32 h2, {h, h}; mov.b32 l2, {l, l};\n"
        "sub.rn.bf16x2 d, %1, m2; mul.rn.bf16x2 t, d, l2; fma.rn.bf16x2 %0, d, h2, t; }" : "=r"(r) : "r"(v), "r"(mx), "r"(hl));
    return r;
}
template <int N, int S>
__device__ __forceinline__ uint32_t rank4(uint32_t a, uint32_t key, uint32_t m1) {
    uint32_t r0 = 0, r1 = 0, r2 = 0, r3 = 0;
#pragma unroll
    for (int i = 0; i < N; i++) {
        const uint4 o = lds128(a + i * S);
        r0 += (o.x * m1 + key) >> 31; r1 += (o.y * m1 + key) >> 31; r2 += (o.z * m1 + key) >> 31; r3 += (o.w * m1 + key) >> 31;
    }
    return (r0 + r1) + (r2 + r3);
}
typedef uint32_t H2C;
__device__ __forceinline__ H2C splat(float r, float i) { return pack_f16(r, i); }
__device__ __forceinline__ void hcmul(uint32_t& xr, uint32_t& xi, uint32_t R, uint32_t I, H2C m) {
    asm("{ .reg .b16 a, b; .reg .b32 a2, b2, t; mov.b32 {a, b}, %4; mov.b32 a2, {a, a}; mov.b32 b2, {b, b};\n"
        "mul.rn.f16x2 t, %3, b2; neg.f16x2 t, t; fma.rn.f16x2 %0, %2, a2, t; mul.rn.f16x2 t, %3, a2; fma.rn.f16x2 %1, %2, b2, t; }"
        : "=&r"(xr), "=r"(xi) : "r"(R), "r"(I), "r"(m));
}
__device__ __forceinline__ void expand4(uint32_t are, uint32_t aim, uint32_t R0, uint32_t R1, uint32_t I0, uint32_t I1, H2C m4) {
    uint32_t R2, I2, R3, I3;
    hcmul(R2, I2, R0, I0, m4); hcmul(R3, I3, R1, I1, m4);
    sts128(are, R0, R1, R2, R3);
    sts128(aim, I0, I1, I2, I3);
}
__device__ __forceinline__ void expand8(uint32_t are, uint32_t aim, float sr, float si, float m1r, float m1i, float m2r, float m2i, H2C m4) {
    float r1, i1, r2, i2, r3, i3;
    cmul(r1, i1, sr, si, m1r, m1i); cmul(r2, i2, sr, si, m2r, m2i); cmul(r3, i3, r1, i1, m2r, m2i);
    expand4(are, aim, pack_f16(sr, r1), pack_f16(r2, r3), pack_f16(si, i1), pack_f16(i2, i3), m4);
}
__device__ __forceinline__ uint32_t comb4(uint32_t a, uint32_t b, uint32_t c, uint32_t d, uint32_t r01, uint32_t r23) {
    uint32_t x;
    asm("{ .reg .b16 h0, h1, h2, h3; .reg .b32 m0, m1, m2, m3, u, v; mov.b32 {h0, h1}, %5; mov.b32 {h2, h3}, %6;\n"
        "mov.b32 m0, {h0, h0}; mov.b32 m1, {h1, h1}; mov.b32 m2, {h2, h2}; mov.b32 m3, {h3, h3};\n"
        "mul.rn.f16x2 u, %2, m1; fma.rn.f16x2 u, %1, m0, u; mul.rn.f16x2 v, %4, m3; fma.rn.f16x2 v, %3, m2, v; add.rn.f16x2 %0, u, v; }"
        : "=r"(x) : "r"(a), "r"(b), "r"(c), "r"(d), "r"(r01), "r"(r23));
    return x;
}
__device__ __forceinline__ void put16(uint32_t a, uint32_t v) { sts16(a, v); sts16(a + 6, v); }

struct Params {
    const unsigned short *logdt, *dskip, *prm6[6], *x, *wr;
    __nv_bfloat16* out;
    Scratch* gs;
    unsigned zero;
};
__device__ __forceinline__ uint32_t tslot(uint32_t t) { return (t & 7) * 32 + ((t >> 4) & 24) + ((t >> 8) & 6) + ((t >> 6) & 1); }
#define CP(x) ((x) | zero)
#define ZF(x) ((x) & zero)
#define PIN(x) asm volatile("or.b32 %0, %0, %1;" : "+r"(x) : "r"(zero))
__device__ __forceinline__ void wgmma32(float (&d)[4][4], const uint32_t (&a)[4], unsigned long long ds) {
    asm volatile("wgmma.mma_async.sync.aligned.m64n32k16.f32.f16.f16 {%0,%1,%2,%3,%4,%5,%6,%7,%8,%9,%10,%11,%12,%13,%14,%15}, {%16,%17,%18,%19}, %20, 1, 1, 1, 0;"
        : "+f"(d[0][0]), "+f"(d[0][1]), "+f"(d[0][2]), "+f"(d[0][3]), "+f"(d[1][0]), "+f"(d[1][1]), "+f"(d[1][2]), "+f"(d[1][3]),
          "+f"(d[2][0]), "+f"(d[2][1]), "+f"(d[2][2]), "+f"(d[2][3]), "+f"(d[3][0]), "+f"(d[3][1]), "+f"(d[3][2]), "+f"(d[3][3])
        : "r"(a[0]), "r"(a[1]), "r"(a[2]), "r"(a[3]), "l"(ds));
}

__device__ __forceinline__ void finish(const Params& prm, uint32_t fo, uint32_t oo, const float (&v)[3], float cnt) {
    float x, y, z, w;
    asm volatile("atom.relaxed.gpu.global.add.v4.f32 {%0,%1,%2,%3}, [%4], {%5,%6,%7,%8};" : "=f"(x), "=f"(y), "=f"(z), "=f"(w)
                 : "l"((char*)prm.gs->fin + fo), "f"(v[0]), "f"(v[1]), "f"(v[2]), "f"(cnt) : "memory");
    if (w + cnt == 3.f * (NCL + 1)) {
        __nv_bfloat16* op = (__nv_bfloat16*)((char*)prm.out + oo);
        op[0] = __float2bfloat16(x + v[0]); op[1] = __float2bfloat16(y + v[1]); op[2] = __float2bfloat16(z + v[2]);
    }
}

__global__ void __cluster_dims__(CS, 1, 1) __launch_bounds__(NTHR, 1)
fused_kernel(const __grid_constant__ Params prm, const __grid_constant__ CUtensorMap tmG, const __grid_constant__ CUtensorMap tmU,
             const __grid_constant__ CUtensorMap tmD, const __grid_constant__ CUtensorMap tmO, const __grid_constant__ CUtensorMap tmX, const __grid_constant__ CUtensorMap tmH)
{
    extern __shared__ __align__(1024) unsigned char smem[];
    const int tid = threadIdx.x, lane = tid & 31, warp = __shfl_sync(~0u, tid >> 5, 0);
    const int c = blockIdx.x >> 3, q = blockIdx.x & 7;
    const int nslot = (c < NCL - 1) ? 5 : 2;
    const int d0 = 40 * c;
    const uint32_t sb = opaque((uint32_t)__cvta_generic_to_shared(smem));
    const uint32_t mb = sb + SM_MB;
    Scratch& g_s = *prm.gs;
    const unsigned& zero = prm.zero;
    const uint32_t dch2 = min(d0 + q + ((tid >> 4) & ~7), D_ - 1) * 2;
    uint32_t pv[6], pLdt;
    const uint32_t pofs = opaque(dch2 * 128 + (tid & 127) * 2);
    pLdt = ldg16((const char*)prm.logdt + dch2);
#pragma unroll
    for (int i = 0; i < 2; i++) pv[i] = ldg16((const char*)prm.prm6[i] + pofs);
    STAMP(0);

    if (warp >= 20) {
        unsigned epoch = 0;
        if (warp == 20) {
            if (lane == 0) {
#pragma unroll
                for (int i = 0; i < 13; i++)
                    asm volatile("mbarrier.init.shared::cta.b64 [%0], %1;" :: "r"(mb + i * 8), "r"((i == MB_R || i < 2) ? 2 : i < 5 ? (nslot + 1) / 3 : i == MB_Y ? 1 + 4 * nslot : 1) : "memory");
                asm volatile("fence.mbarrier_init.release.cluster;" ::: "memory");
                arm(mb + MB_W1 * 8, 92160); arm(mb + MB_W2 * 8, nslot * 9216); arm(mb + MB_KEY * 8, 256); arm(mb + MB_GU * 8, nslot * 1024); arm(mb + MB_T * 8, 576 * XW);
                const int bytes = max(min(18, L_ - 18 * (int)blockIdx.x), 1) * (D_ * 2);
                arm(mb + MB_R * 8, bytes);
            }
            __syncwarp();
        } else if (warp == 22) {
            epoch = ld_rlx(&g_s.epoch);
            if (lane < 18 ? 18 * c + lane < 256 : lane < 31) (lane < 18 ? &g_s.acc[256 * q + 18 * c] : &g_s.fin[13 * (int)blockIdx.x - 18])[lane] = make_float4(0.f, 0.f, 0.f, 0.f);
        } else if (warp == 23 && lane == 0) asm volatile("prefetch.tensormap [%0];" :: "l"(&tmX) : "memory");
        asm volatile("barrier.cluster.arrive.relaxed.aligned;" ::: "memory");
        bar_sync(12, NTHR);
        uint4 wv = make_uint4(0, 0, 0, 0), wv2, wv3;
        if (warp == 22) {
            if (lane == 0) { sts32(sb + SM_SC + 28, epoch); asm volatile("mbarrier.arrive.shared::cta.b64 _, [%0];" :: "r"(mb + MB_R * 8) : "memory"); }
            epoch++;
            asm volatile("fence.acq_rel.gpu;" ::: "memory");
            __syncwarp();
            if (lane == 0) asm volatile("red.relaxed.gpu.global.add.u32 [%0], 1;" :: "l"(&g_s.zcnt) : "memory");
            STAMP(1);
            wv2 = ldg128((const uint4*)prm.wr + lane); wv3 = ldg128((const uint4*)prm.wr + 32 + lane);
            if (lane < 8) wv = ldg128((const uint4*)prm.wr + 64 + lane);
            if (lane < 5) {
                uint4 v = make_uint4(0, 0, 0, 0);
                if (lane < nslot) v = ldg128((const uint4*)(prm.wr + d0) + lane);
                sts128(sb + SM_DW + lane * 16, v.x, v.y, v.z, v.w);
            }
            __syncwarp();
            if (lane < 5) asm volatile("mbarrier.arrive.shared::cta.b64 _, [%0];" :: "r"(mb + (MB_X + lane) * 8) : "memory");
        }
        if (warp == 21) {
            if (lane == 0) { asm volatile("prefetch.tensormap [%0];" :: "l"(&tmG) : "memory"); asm volatile("prefetch.tensormap [%0];" :: "l"(&tmU) : "memory"); asm volatile("prefetch.tensormap [%0];" :: "l"(&tmD) : "memory"); }
            __syncwarp();
            const float dsk = bf_lo(ldg16(prm.dskip + min(d0 + 2 * (lane & 28) + q, D_ - 1)));
            bar_sync(0, 672);
            {
                const uint2 m = lds64(sb + SM_KG + min(lane, 19) * 8);
                unsigned Em = max(m.x, __shfl_xor_sync(~0u, m.x, 1));
                Em = max(Em, __shfl_xor_sync(~0u, Em, 2));
                Em = max(Em, min(__float_as_uint(fabsf(dsk) * (1.f / 8192.f)) >> 23, 253u));
                const float f = __uint_as_float(max((int)(127 + m.x - Em), 0) << 23);
                float s0 = (float)(int)m.y * f;
                s0 += __shfl_xor_sync(~0u, s0, 1); s0 += __shfl_xor_sync(~0u, s0, 2);
                if (lane < 20) {
                    sts16(sb + SM_RK + lane * 2, pack_f16(f, 0.f));
                    sts32(sb + SM_SC + (lane & 28), Em * 0x00800080u);
                    put16(sb + SM_PN + (lane >> 2) * PN_SZ, pack_f16(s0 * (1.f / 16777216.f) + dsk * __uint_as_float((254u - Em) << 23), 0.f));
                }
                __syncwarp();
            }
            bar_sync(15, 672);
            asm volatile("fence.proxy.async.shared::cta;" ::: "memory");
#pragma unroll 1
            for (int i = 0; i < 24; i++) {
                if (lane == 0) tma2d(sb + SM_WG + i * 3840, i < 12 ? &tmG : &tmU, 320 * c + 8 * nslot * q, 48 * (i < 12 ? i : i - 12), mb + MB_W1 * 8);
            }
            STAMP(1);
        } else {
        if (warp == 20) {
            if (lane == 0) {
                asm volatile("cp.async.bulk.shared::cluster.global.mbarrier::complete_tx::bytes [%0], [%1], %2, [%3];"
                             :: "r"(sb + SM_ROW), "l"(prm.x + min(18 * (int)blockIdx.x, L_ - 1) * D_), "r"(max(min(18, L_ - 18 * (int)blockIdx.x), 1) * (D_ * 2)), "r"(mb + MB_R * 8) : "memory");
            }
            __syncwarp();
            mbar_wait(mb + MB_R * 8);
            if (lane == 0) {
                asm volatile("cp.async.bulk.tensor.5d.shared::cluster.global.mbarrier::complete_tx::bytes [%0], [%1, {%3, %4, %5, %5, %5}], [%2];"
                             :: "r"(sb + SM_XTL), "l"(&tmX), "r"(mb + MB_T * 8), "r"(d0 & ~15), "r"(8 * q), "r"(0) : "memory");
            }
            STAMP(6);
        }
        {
            const int idx = lane * 3 + max(warp - 21, 0), sl = nslot - 1 - (idx >> 3), pe = (idx + q + 1) & 7;
            const uint32_t rb_ = mapa(sb, pe);
            uint32_t cd = rb_ + SM_U + 128 + q * UP + sl * US, cs = sb + SM_XT + 128 + (q & 3) * 16 + pe * YP + sl * YS, cm = rb_ + SM_MB + (MB_X + sl) * 8;
            int act = sl < 0 ? 0 : pe == q ? -1 : 1;
            PIN(cd); PIN(cs); PIN(cm); PIN(act);
            asm volatile("barrier.cluster.wait.aligned;" ::: "memory");
            mbar_wait(mb + MB_R * 8);
            bar_sync(13, 608);
            asm volatile("fence.proxy.async.shared::cta;" ::: "memory");
            if (act < 0) arm(cm, 7 * 512);
            __syncwarp();
            if (act > 0)
                asm volatile("cp.async.bulk.shared::cluster.shared::cta.mbarrier::complete_tx::bytes [%0], [%1], 512, [%2];" :: "r"(cd), "r"(cs), "r"(cm) : "memory");
        }
        STAMP(1);
        if (warp == 20 && lane == 0) { asm volatile("prefetch.tensormap [%0];" :: "l"(&tmO) : "memory"); asm volatile("prefetch.tensormap [%0];" :: "l"(&tmH) : "memory"); }
        if (warp == 22) {
            __syncwarp();
            mbar_wait(mb + (MB_X + 1) * 8);
            const uint32_t old = (epoch & 1) ? 0u : 0x40004000u;
#pragma unroll
            for (int t = 0; t < 2; t++)
                if ((lane & 7) < 6) g_s.cand[((q * 8 + 4 * t + (lane >> 3)) * NCL + c) * 6 + (lane & 7)] = make_uint4(old, old, old, old);
            float a[4] = {0.f, 0.f, 0.f, 0.f};
            const uint32_t one = 0x3F803F80u;
            mma_bf16(a, one, one, one, one, wv.x, wv.y);  mma_bf16(a, one, one, one, one, wv.z, wv.w);
            mma_bf16(a, one, one, one, one, wv2.x, wv2.y); mma_bf16(a, one, one, one, one, wv2.z, wv2.w);
            mma_bf16(a, one, one, one, one, wv3.x, wv3.y); mma_bf16(a, one, one, one, one, wv3.z, wv3.w);
            float s = a[0] + a[1];
            s += __shfl_xor_sync(~0u, s, 1); s += __shfl_xor_sync(~0u, s, 2);
            stsf(sb + SM_SC + 24, s);
            __syncwarp();
            if (lane == 0) {
                int n = 0;
                while ((int)(ld_acq(&g_s.zcnt) - epoch * NCTA) < 0 && ++n < SPIN_LIMIT) __nanosleep(200);
                arm(mb + MB_Y * 8, 8 * 512 * nslot);
                if (blockIdx.x == 0) g_s.epoch = epoch;
            }
            STAMP(2);
        }
        if (warp == 23) {
#pragma unroll 1
            for (int kk = nslot - 1; kk >= 0; kk--) {
                __syncwarp();
                bar_sync(6 + kk, 160);
                if (kk < 2) mbar_wait(mb + MB_W1 * 8);
                if (lane == 0) { asm volatile("fence.proxy.async.shared::cta;" ::: "memory"); tma2d(sb + SM_FAR + kk * FAR_SZ, &tmD, 72 * q, 320 * c + 64 * kk, mb + MB_W2 * 8); }
            }
        }
        }
        __syncwarp();
        if (warp == 20) {
            bar_sync(11, 672);
            asm volatile("fence.proxy.async.shared::cta;" ::: "memory");
            bar_sync(14, 768);
            if (elect()) {
                asm volatile("cp.async.bulk.tensor.5d.global.shared::cta.bulk_group [%0, {%2, %4, %4, %4, %3}], [%1];" :: "l"(&tmH), "r"(sb + SM_XT + 16384), "r"(d0 + ((c & 1) ? 0 : 32)), "r"(8 * q), "r"(0) : "memory");
                asm volatile("cp.async.bulk.tensor.5d.global.shared::cta.bulk_group [%0, {%2, %4, %4, %4, %3}], [%1];" :: "l"(&tmO), "r"(sb + SM_XT), "r"(d0 + (c & 1) * 8), "r"(8 * q), "r"(0) : "memory");
                asm volatile("cp.async.bulk.commit_group;" ::: "memory");
            }
        } else bar_sync(14, 768);
        __syncwarp();
        const uint32_t ft = (tid >> 4) & 7, fj = d0 / 3 + (lane & 15), tok = ~lds32(sb + SM_SEL + ft * 8) & 2047;
        float v[3], cnt = 0.f;
#pragma unroll
        for (int i = 0; i < 3; i++) {
            const uint32_t cl = 3 * fj + i - d0, cf = cl - (c & 1) * 8;
            const bool ok = cl < 8 * nslot && ((tok >> 3) & 7) == q;
            const uint32_t u = lds16(sb + SM_XT + (cf < 32 ? tslot(tok) * 64 + cf * 2 : 16384 + tslot(tok) * 16 + (cl & 7) * 2));
            v[i] = ok ? __uint_as_float(u << 16) : 0.f;
            if (ok) cnt += 1.f;
        }
        if (warp == 20 && elect()) {
            asm volatile("cp.async.bulk.wait_group 0;" ::: "memory");
            asm volatile("fence.proxy.async.global;" ::: "memory");
            asm volatile("mbarrier.arrive.shared::cta.b64 _, [%0];" :: "r"(mb + MB_OUT * 8) : "memory");
        }
        __syncwarp();
        mbar_wait(mb + MB_OUT * 8);
        STAMP(5);
        if (cnt != 0.f) finish(prm, (ft * 192 + fj) * 16, (tok * D_ + 3 * fj) * 2, v, cnt);
        return;
    }

    const int g = lane >> 2, cq = lane & 3;
    const int k = warp >> 2, wq = warp & 3;
    const int trow = 18 * blockIdx.x + warp;
    const bool rowact = warp < 18 && trow < L_;
#pragma unroll
    for (int i = 2; i < 6; i++) pv[i] = ldg16((const char*)prm.prm6[i] + pofs);
    const int tn = 16 * (warp & 15) + g;
    uint32_t xa[5], xb[5];
    asm volatile("barrier.cluster.arrive.relaxed.aligned;" ::: "memory");
    char* const st1p = (char*)g_s.st1 + opaque(((((trow >> 3) & 7) * 256 + ((trow >> 6) & 31) * 8 + (trow & 7)) * 8 + lane) * 4);
    const bool pub = rowact && (lane & 0x1B) == 0;
    if (pub) st_rlx128(st1p, 0, 0, 0, 0);
    {
        const uint32_t za = sb + SM_P + tid * 16;
        sts128(za, 0, 0, 0, 0);
        if (tid < (SM_MISC - SM_P) / 16 - 640) sts128(za + 10240, 0, 0, 0, 0);
        sts128(sb + SM_U + ((tid >> 3) & 7) * UP + k * US + (lane & 7) * 16, 0, 0, 0, 0);
    }
    bar_sync(12, NTHR);
    const uint32_t dep = lds32(sb + SM_P);
#define PV(x) __uint_as_float(__byte_perm(dep, x, 0x5410))
    STAMP(1);
    const uint32_t fb = sb + SM_FAR + k * FAR_SZ;
    const uint32_t pn = sb + SM_PN + k * PN_SZ, pf = sb + SM_PF + k * PF_SZ;
    unsigned epoch, t258;
    {
        const uint32_t kb = fb + wq * 3072;
        const uint32_t kl = kb + lane * 16;
        uint32_t Af[4][4];
        float sr, si, z1r, z1i, z2r, z2i, z4r, z4i, hr, hi_;
        {
            const float dt = bfr(ex2f(PV(pLdt) * 1.4426950408889634f));
            const float e2 = dt * PV(pv[0]) * 1.4426950408889634f, an = dt * PV(pv[1]);
            float ar, ai, br, bi, cr, ci, dr, di;
            { const float m = ex2f(e2 * 8.f); ar = m * __cosf(an * 8.f); ai = m * __sinf(an * 8.f); }
            csq(br, bi, ar, ai); csq(cr, ci, br, bi); csq(dr, di, cr, ci);
            const H2C m4 = splat(cr, ci);
            {
                float r3, i3;
                cmul(r3, i3, ar, ai, br, bi);
                expand4(kl, kl + 1024, pack_f16(1.f, ar), pack_f16(br, r3), pack_f16(0.f, ai), pack_f16(bi, i3), m4);
            }
            expand8(kl + 512, kl + 1536, dr, di, ar, ai, br, bi, m4);
            { const float m = ex2f(e2); z1r = m * __cosf(an); z1i = -m * __sinf(an); }
            cexp_s(hr, hi_, e2 * 128.f, an * (-128.f * 0.15915494309189535f));
            csq(z2r, z2i, z1r, z1i); csq(z4r, z4i, z2r, z2i);
            const uint32_t dep2 = lds32(sb + SM_P + 4);
#define PW(x) __uint_as_float(__byte_perm(dep2, x, 0x5410))
            cmul(sr, si, PW(pv[4]), PW(pv[5]), dt * PW(pv[2]), dt * PW(pv[3]));
            const unsigned E = min(max(__reduce_max_sync(~0u, __float_as_uint(fmaxf(fabsf(sr), fabsf(si)))) >> 23, 1u), 253u);
            const float sc = __uint_as_float((254u - E) << 23);
            sr *= sc; si *= -sc;
            sts64(sb + SM_KG + warp * 8, E, __reduce_add_sync(~0u, __float2int_rn(sr * 16777216.f)));
        }
        __syncwarp();
#pragma unroll
        for (int ks = 0; ks < 4; ks++) ldsm4t(Af[ks], kb + (lane >> 3) * 512 + (lane & 7) * 16 + ks * 128);
        STAMP(2);
        const uint32_t la = kb + ((lane >> 3) & 1) * 512 + (lane >> 4) * 128 + (lane & 7) * 16;
        uint32_t b0[4], b1[4], b2[4], b3[4];
        auto ln1 = [&]() {
        mbar_wait(mb + MB_R * 8);
        epoch = lds32(sb + SM_SC + 28) + 1;
        {
            const uint32_t ra = sb + SM_ROW + warp * (D_ * 2);
            const uint4 r0 = lds128(ra + lane * 16), r1 = lds128(ra + 512 + lane * 16);
            const uint32_t rx[9] = {r0.x, r0.y, r0.z, r0.w, r1.x, r1.y, r1.z, r1.w, lds32(ra + 1024 + lane * 4)};
            float a0 = bf_lo(rx[0]), a1 = bf_hi(rx[0]), c0 = a0 * a0, c1 = a1 * a1;
#pragma unroll
            for (int i = 1; i < 9; i++) { const float l = bf_lo(rx[i]), h = bf_hi(rx[i]); a0 += l; a1 += h; c0 = fmaf(l, l, c0); c1 = fmaf(h, h, c1); }
            a0 += a1; c0 += c1;
            float s1 = ((lane & 1) ? c0 : a0) + __shfl_xor_sync(~0u, (lane & 1) ? a0 : c0, 1);
#pragma unroll
            for (int o = 2; o < 32; o <<= 1) s1 += __shfl_xor_sync(~0u, s1, o);
            const float s2 = __shfl_xor_sync(~0u, s1, 1);
            const uint32_t ms = ln_stats(s1, s2);
            const uint32_t p0 = __byte_perm(ms, epoch | 0x8000u, 0x5410), p1 = rsplit(rcpf(bf_hi(ms)));
            if (pub) st_rlx128(st1p, p0, p1, p0, p1);
        }
        mbar_wait(mb + MB_R * 8);
        STAMP(1);
        };
        const uint4* sp = &g_s.st1[(256 * q + tn) * 2];
        uint2 sa, sc;
        auto poll = [&]() { sa = ld_rlx64(sp); sc = ld_rlx64(sp + 16); };
        auto norm = [&]() {
        STAMP(3);
        if (warp < 16) {
            uint32_t va[5], vc[5];
            poll();
            mbar_wait(mb + MB_T * 8);
            {
                const uint32_t xt = sb + SM_XTL + (c & 1) * 16 + (36 * (warp & 7) + 9 * (warp >> 3) + g) * (2 * XW);
                uint4 a4 = lds128(xt + cq * 16), b4 = lds128(xt + cq * 16 + 36 * XW);
                va[0] = a4.x; va[1] = a4.y; va[2] = a4.z; va[3] = a4.w; va[4] = lds32(xt + 64 + cq * 4);
                vc[0] = b4.x; vc[1] = b4.y; vc[2] = b4.z; vc[3] = b4.w; vc[4] = lds32(xt + (64 + 36 * XW) + cq * 4);
            }
            const int d4 = 2 * (lane >> 3) + (lane & 1), d1_ = lane & 7;
            const uint32_t own = SM_U + 128 + q * (UP - YP), oth = SM_XT + 128 + (q & 3) * 16;
            uint32_t a4 = sb + warp * 32 + d4 * YP + (d4 == q ? own : oth) + ((lane & 7) >> 1) * YS;
            uint32_t a1 = sb + warp * 32 + d1_ * YP + (d1_ == q ? own : oth) + 4 * YS + (lane & 8) * 2;
            PIN(a4); PIN(a1);
            uint32_t tag = __byte_perm(epoch | 0x8000u, 0, 0x1010);
            PIN(tag);
            mbar_wait(mb + MB_T * 8);
            int n = 0;
            while (__byte_perm(sa.x, sc.x, 0x7632) != tag && ++n < SPIN_LIMIT) poll();
            STAMP(4);
#pragma unroll
            for (int i = 0; i < 5; i++) {
                va[i] = norm2(va[i], sa.x, sa.y); va[i] = pack_f16(bf_lo(va[i]), bf_hi(va[i]));
                vc[i] = norm2(vc[i], sc.x, sc.y); vc[i] = pack_f16(bf_lo(vc[i]), bf_hi(vc[i]));
            }
            stsm4t(a4, va[0], va[1], va[2], va[3]); stsm4t(a4 + 16, vc[0], vc[1], vc[2], vc[3]); stsm2t(a1, va[4], vc[4]);
            bar_arrive(13, 608);
            {
            const uint32_t xh = sb + SM_XTL + (c & 1) * 16 + (9 * __byte_perm(0x12100200, 0x13110301, g) + 72 * (warp & 1) + (warp >> 1)) * (2 * XW);
            const uint4 c4 = lds128(xh + cq * 16), d4_ = lds128(xh + cq * 16 + 72 * XW);
            xa[0] = c4.x; xa[1] = c4.y; xa[2] = c4.z; xa[3] = c4.w; xa[4] = lds32(xh + 64 + cq * 4);
            xb[0] = d4_.x; xb[1] = d4_.y; xb[2] = d4_.z; xb[3] = d4_.w; xb[4] = lds32(xh + (64 + 72 * XW) + cq * 4);
            }
        }
        STAMP(5);
        __syncwarp();
        bar_sync(15, 672);
        Af[0][0] |= lds32(sb + SM_P);
        };
        cmul(sr, si, sr, si, z1r, z1i);
        {
            const H2C h4 = splat(z4r, z4i);
            expand8(kl, kl + 512, sr, si, z1r, z1i, z2r, z2i, h4);
            cmul(sr, si, sr, si, hr, hi_);
            expand8(kl + 1024, kl + 1536, sr, si, z1r, z1i, z2r, z2i, h4);
        }
        __syncwarp();
        ldsm4t(b0, la); ldsm4t(b1, la + 256); ldsm4t(b2, la + 1024); ldsm4t(b3, la + 1280);
        cmul(z1r, z1i, z1r, z1i, hr, hi_);
        cmul(sr, si, sr, si, z1r, z1i);
        expand8(kl, kl + 512, sr, si, z2r, z2i, z4r, z4i, splat(hr, hi_));
        asm volatile("barrier.cluster.wait.aligned;" ::: "memory");
        bar_arrive(0, 672);
        ln1();
        csq(z1r, z1i, z1r, z1i);
        cmul(sr, si, sr, si, z1r, z1i);
        csq(z2r, z2i, hr, hi_);
        expand8(kl + 1024, kl + 1536, sr, si, z4r, z4i, hr, hi_, splat(z2r, z2i));
        csq(z1r, z1i, z1r, z1i);
        cmul(sr, si, sr, si, z1r, z1i);
        csq(z4r, z4i, z2r, z2i);
        expand8(kl + 2048, kl + 2560, sr, si, hr, hi_, z2r, z2i, splat(z4r, z4i));
        norm();
        {
            uint32_t c0[4], c1[4], c2[4], c3[4], e0[4], e1[4];
            float t[6][4];
            ldsm4t(c0, la); ldsm4t(c2, la + 1024);
            mma_f16_z(t[0], Af[0], b0[0], b0[1]);
            const uint32_t lb = la | (__float_as_uint(t[0][0]) & zero);
            mma_f16_z(t[1], Af[0], b2[0], b2[1]); mma_f16_z(t[2], Af[0], c0[0], c0[1]); mma_f16_z(t[3], Af[0], c2[0], c2[1]);
            ldsm4t(e0, lb + 2048); ldsm4t(c1, lb + 256); ldsm4t(c3, lb + 1280); ldsm4t(e1, lb + 2304);
            mma_f16(t[0], Af[1], b0[2], b0[3]); mma_f16(t[1], Af[1], b2[2], b2[3]); mma_f16(t[2], Af[1], c0[2], c0[3]); mma_f16(t[3], Af[1], c2[2], c2[3]);
            mma_f16(t[0], Af[2], b1[0], b1[1]); mma_f16(t[1], Af[2], b3[0], b3[1]);
            mma_f16_z(t[4], Af[0], e0[0], e0[1]); mma_f16_z(t[5], Af[1], e0[2], e0[3]);
            mma_f16(t[2], Af[2], c1[0], c1[1]); mma_f16(t[3], Af[2], c3[0], c3[1]);
            mma_f16(t[4], Af[2], e1[0], e1[1]); mma_f16(t[5], Af[3], e1[2], e1[3]);
            mma_f16(t[0], Af[3], b1[2], b1[3]); mma_f16(t[1], Af[3], b3[2], b3[3]); mma_f16(t[2], Af[3], c1[2], c1[3]); mma_f16(t[3], Af[3], c3[2], c3[3]);
#pragma unroll
            for (int i = 0; i < 4; i++) t[4][i] += t[5][i];
            stsm4(kl + 1024, pack_f16(t[0][0], t[0][1]), pack_f16(t[0][2], t[0][3]), pack_f16(t[1][0], t[1][1]), pack_f16(t[1][2], t[1][3]));
            stsm2(kl + 1536, pack_f16(t[2][0], t[2][1]), pack_f16(t[2][2], t[2][3]));
            sts64(kb + lane * 8 + 1792, pack_f16(t[3][1], t[3][0]), pack_f16(t[3][3], t[3][2]));
            sts64(kb + lane * 8 + 2048, pack_f16(t[4][1], t[4][0]), pack_f16(t[4][3], t[4][2]));
        }
        bar_sync(1 + k, 128);
        const uint2 rr = lds64(opaque(sb + SM_RK + k * 8));
        const int tq = (wq + k + 2) & 3;
        const uint32_t ra = lane * 8 + opaque(fb + (tq == 1 ? 2048 : tq * 256 + 1024));
        auto comb = [&](uint32_t a, uint32_t& x, uint32_t& y) {
            const uint2 p0 = lds64(a), p1 = lds64(a + 3072), p2 = lds64(a + 6144), p3 = lds64(a + 9216);
            x = comb4(p0.x, p1.x, p2.x, p3.x, rr.x, rr.y); y = comb4(p0.y, p1.y, p2.y, p3.y, rr.x, rr.y);
        };
        uint32_t w0, w1;
        comb(ra, w0, w1);
        const bool last = lane == 31;
        if (tq == 0) {
            uint32_t v0, v1;
            comb(ra + 256, v0, v1);
            const uint32_t n0 = __shfl_sync(~0u, lane ? w0 : v0, lane + 1);
            uint32_t n1 = __shfl_sync(~0u, v0, lane + 1);
            if (last) n1 = v1 >> 16;
            sts128(pn + 12 + lane * 16, __byte_perm(w1, w0, 0x7610), __byte_perm(w1, 0, 0x1032), __byte_perm(n0, w1, 0x7610), __byte_perm(n0, 0, 0x1032));
            sts128(pn + 524 + lane * 16, __byte_perm(v1, v0, 0x7610), __byte_perm(v1, 0, 0x1032), __byte_perm(n1, v1, 0x7610), __byte_perm(n1, 0, 0x1032));
            if (lane == 0) { sts16(pn + 4, w0); sts32(pn + 8, __byte_perm(w0, 0, 0x1032)); }
        } else if (tq == 1) {
            const uint32_t ph = pf + P_H7 + (g & 1) * (2 * P_HS) + cq * 64 + (g >> 1) * 4 + (cq & 2) * 16, sw = (cq & 2) ? 0x3210 : 0x1032;
            w0 = __byte_perm(hmul2(w0, 0x18001800u), 0, sw); w1 = __byte_perm(hmul2(w1, 0x18001800u), 0, sw);
            const uint32_t pi = ph + 32 - (cq & 2) * 32;
            put16(ph, w0); put16(pi, w0 >> 16); put16(ph + 16, w1); put16(pi + 16, w1 >> 16);
        } else if (tq == 2) {
            uint32_t n = __shfl_sync(~0u, w0, lane == 30 ? 1 : lane + 2);
            if (last) { put16(pf, hmul2(w1, 0x18001800u) >> 16); w1 = hadd2(w1, hneg2(__byte_perm(w1, 0, 0x3232))); n = 0; }
            const bool od = lane & 1;
            const uint32_t pa = pn + 1036 + (lane >> 1) * 32 + (od ? 528 : 0), pb = pa + (od ? -16 : 16);
            const uint32_t u0 = od ? w1 : w0, x0 = od ? n : w1, u1 = od ? w0 : w1, x1 = od ? w1 : n;
            const uint32_t b0 = __byte_perm(u0, 0, 0x3232), b1 = __byte_perm(u1, 0, 0x3232);
            sts128(pa, __byte_perm(u0, 0, 0x1032), b0, b0, __byte_perm(x0, u0, 0x7610));
            sts128(pb, __byte_perm(u1, 0, 0x1032), b1, b1, __byte_perm(x1, u1, 0x7610));
        } else {
            const uint32_t pa = pf + ((g & 1) ? 3 * P_GS : P_GS) + cq * 32 + (g >> 1) * 4;
            const uint32_t pb = pa + ((g & 1) ? 4 - 3 * P_GS : P_GS);
            w0 = hmul2(w0, 0x18001800u); w1 = hmul2(w1, 0x18001800u);
            put16(pa, w0 >> 16); put16(pb, w0); put16(pa + 16, w1 >> 16); put16(pb + 16, w1);
            if (last) put16(pf + P_H7 + P_HS, w1);
        }
        bar_sync(1 + k, 128);
        t258 = w0;
    }
    STAMP(6);

    mbar_wait(mb + (MB_X + k) * 8);
    STAMP(7);
    if (k < nslot) {
        const int role = (wq + k) & 3;
        const uint32_t ub = sb + SM_U + k * US + 128;
        const uint32_t l16 = lane * 16, tz = (lane & 28) - 8 * cq, tz4 = tz * 4;
        if (role) {
            const uint32_t al = cq * (2 * UP + 32) + tz4, au = opaque(ub + (3 - role) * 128), a1 = al + au, a0 = (cq ? al : al + (8 * UP - 16)) + au - 2 * UP;
            const uint4 q0 = lds128(a0), q1 = lds128(a0 + UP), q2 = lds128(a1), q3 = lds128(a1 + UP);
            const uint32_t U[16] = {q0.x, q0.y, q0.z, q0.w, q1.x, q1.y, q1.z, q1.w, q2.x, q2.y, q2.z, q2.w, q3.x, q3.y, q3.z, q3.w};
            uint32_t V[14], Q[14], R4[12], T[8];
#pragma unroll
            for (int i = 2; i < 14; i++) { V[i] = __byte_perm(U[i], U[i + 1], 0x5432); Q[i] = hadd2(U[i], V[i]); }
            const uint32_t rb = l16 + opaque(fb + (3 - role) * 512);
#pragma unroll
            for (int i = 0; i < 8; i++) T[i] = hadd2(V[5 + i], Q[6 + i]);
            sts128(rb + F_E3, T[0], T[1], T[2], T[3]); sts128(rb + F_O3 + 16, T[4], T[5], T[6], T[7]);
            asm volatile("{ .reg .pred p; setp.ne.u32 p, %10, 1; @p st.shared.v4.u32 [%0], {%2,%3,%4,%5}; @p st.shared.v4.u32 [%1], {%6,%7,%8,%9}; }"
                         :: "r"(rb + F_E2), "r"(rb + F_O2), "r"(Q[6]), "r"(Q[7]), "r"(Q[8]), "r"(Q[9]), "r"(Q[10]), "r"(Q[11]), "r"(Q[12]), "r"(Q[13]), "r"(role) : "memory");
#pragma unroll
            for (int i = 2; i < 12; i++) R4[i] = hadd2(Q[i], Q[i + 1]);
#pragma unroll
            for (int i = 0; i < 8; i++) T[i] = hadd2(R4[3 + i], U[5 + i]);
            sts128(rb + F_O5, T[0], T[1], T[2], T[3]); sts128(rb + F_E5, T[4], T[5], T[6], T[7]);
            if (role != 1) {
                uint32_t S[8];
#pragma unroll
                for (int i = 0; i < 8; i++) S[i] = hadd2(R4[2 + i], i < 7 ? T[i + 1] : hadd2(R4[11], U[13]));
                sts128(rb + F_O9, S[0], S[1], S[2], S[3]); sts128(rb + F_E9 + 16, S[4], S[5], S[6], S[7]);
#pragma unroll
                for (int i = 0; i < 8; i++) S[i] = hadd2(T[i], hadd2(V[2 + i], V[5 + i]));
                sts128(rb + F_E7, S[0], S[1], S[2], S[3]); sts128(rb + F_O7, S[4], S[5], S[6], S[7]);
            }
        } else if (lane == 0) {
            const uint4 m = lds128(ub + 23 * 16 + 7 * UP);
            const uint32_t U[6] = {lds32(ub + 23 * 16 + 6 * UP + 12), m.x, m.y, m.z, m.w, lds32(ub + 24 * 16)};
            uint32_t Q[5];
#pragma unroll
            for (int i = 0; i < 5; i++) Q[i] = hadd2(U[i], __byte_perm(U[i], U[i + 1], 0x5432));
            sts128(fb + F_O5 + 96 * 16, hadd2(hadd2(Q[0], Q[1]), U[2]), hadd2(hadd2(Q[1], Q[2]), U[3]), hadd2(hadd2(Q[2], Q[3]), U[4]), hadd2(hadd2(Q[3], Q[4]), U[5]));
            sts128(fb + F_O3, 0, 0, 0, 0); sts128(fb + F_E9, 0, 0, 0, 0);
            sts16(pn + 258 * 4, t258);
        }
        bar_sync(1 + k, 128);
        float acc[4][4];
        uint32_t Q[4][4];
        {
            const int h = role & 1, part = role >> 1;
            float fa[7][4];
            uint32_t B[3][4];
            const uint32_t po = tz + opaque(pf + part * (2 * P_GS)), ba = l16 + opaque(fb + (part == h ? 0 : F_O5 + h * 16));
#pragma unroll
            for (int s = 1; s >= 0; s--) {
#pragma unroll
                for (int i = 0; i < 3; i++) { Q[i][0] = lds32(po + (s * P_GS + i * 64)); if (i < 2) Q[i][1] = lds32(po + (s * P_GS + i * 64 + 32)); }
#pragma unroll
                for (int i = 0; i < 3; i++) ldsm4t(B[i], ba + (s * F_E3 + i * 512));
#pragma unroll
                for (int i = 0; i < 3; i++) { Q[i][3] = CP(Q[i][0]); if (i) Q[i][2] = CP(Q[i - 1][1]); }
                Q[0][2] = ZF(s ? tz : Q[0][0]); Q[2][1] = ZF(s ? l16 : Q[2][0]);
#pragma unroll
                for (int dl = 0; dl < 3; dl++)
#pragma unroll
                    for (int ap = 0; ap < 6 - dl; ap++) {
                        if (s == 1 && dl == 0) mma_f16_z(fa[ap + 1], Q[0], B[ap >> 1][2 * (ap & 1)], B[ap >> 1][2 * (ap & 1) + 1]);
                        else mma_f16(fa[ap + 1 + dl], Q[dl], B[ap >> 1][2 * (ap & 1)], B[ap >> 1][2 * (ap & 1) + 1]);
                    }
            }
#pragma unroll 1
            for (int s = role; s == 1; s++) {
                ldsm2t(B[0][0], B[0][1], fb + ((lane & 15) == 15 ? F_O5 : F_O3));
#pragma unroll
                for (int dl = 1; dl < 3; dl++) mma_f16(fa[dl], Q[dl], B[0][0], B[0][1]);
            }
            const uint32_t bh = l16 + opaque(fb + F_E7 + h * F_H + part * 2048), ph = tz + opaque(pf + P_H7 + part * (2 * P_HS));
#pragma unroll 1
            for (int s = part; s == 1; s++) {
                Q[2][1] = ZF(Q[2][3]); Q[2][2] = ZF(Q[2][2]); Q[2][0] = lds32(ph - P_HS);
                ldsm4t(B[0], bh - 1024); ldsm4t(B[1], bh - 512);
                Q[2][3] = CP(Q[2][0]);
#pragma unroll
                for (int ap = 0; ap < 4; ap++) mma_f16(fa[ap + 3], Q[2], B[ap >> 1][2 * (ap & 1)], B[ap >> 1][2 * (ap & 1) + 1]);
            }
            {
                Q[0][2] = ZF(tid);
#pragma unroll
                for (int i = 0; i < 4; i++) { Q[i][0] = lds32(ph + i * 64); Q[i][1] = lds32(ph + (i * 64 + 32)); }
                ldsm4t(B[0], bh); ldsm4t(B[1], bh + 512);
#pragma unroll
                for (int i = 0; i < 4; i++) { Q[i][3] = CP(Q[i][0]); if (i) Q[i][2] = CP(Q[i - 1][1]); }
#pragma unroll
                for (int dl = 0; dl < 4; dl++)
#pragma unroll
                    for (int ap = 0; ap < 4 - dl; ap++) mma_f16(fa[ap + 3 + dl], Q[dl], B[ap >> 1][2 * (ap & 1)], B[ap >> 1][2 * (ap & 1) + 1]);
            }
            const uint32_t da = (cq * 2048 + tz4) + opaque(fb + role * 128);
            bar_sync(1 + k, 128);
#pragma unroll
            for (int i = 1; i < 4; i++)
                stsm4(da + i * 512, pack_f16(fa[2 * i - 1][0], fa[2 * i - 1][1]), pack_f16(fa[2 * i - 1][2], fa[2 * i - 1][3]),
                      pack_f16(fa[2 * i][0], fa[2 * i][1]), pack_f16(fa[2 * i][2], fa[2 * i][3]));
            asm("shl.b32 %0, 0x6000, %1;" : "=r"(Q[0][0]) : "r"(tz4));
            Q[0][1] = ZF(Q[0][0]); Q[0][2] = ZF(tz4); Q[0][3] = CP(Q[0][0]);
            const uint32_t ra = l16 + opaque(fb + wq * 2016);
            acc[0][0] = acc[0][1] = acc[0][2] = acc[0][3] = 0.f;
            if (wq == 3) {
                const uint32_t uw = lds32(ub), kw = lds32(pf);
                const float2 uf = __half22float2(*(const __half2*)&uw);
                if ((lane | 4) == 31) acc[0][3] = (lane == 31 ? uf.x + uf.y : uf.x) * (__low2float(*(const __half2*)&kw) * 512.f);
            }
            bar_sync(1 + k, 128);
#pragma unroll
            for (int i = 1; i < 4; i++) {
                ldsm4(B[0], ra + i * 512);
                mma_f16_z(acc[i], Q[0], hadd2(B[0][0], B[0][2]), hadd2(B[0][1], B[0][3]));
            }
        }
        bar_arrive(6 + k, 160);
        STAMP(8);
        const uint32_t inv = lds32(opaque(sb + SM_SC + k * 4));
        const uint32_t yd = l16 + opaque(mapa(sb, 2 * wq) + (SM_XT + 128 + q * YP + k * YS + (k >> 2) * (q >> 1) * 16));
        {
            uint32_t pu = opaque(pn + 64 * (wq - 3));
#define pp (tz + pu)
            const uint32_t dlo = (((ub + 6 * UP) & 0x3FFFF) >> 4) | ((UP >> 4) << 16);
            uint32_t R[4][4];
            unsigned long long ds[4];
#pragma unroll
            for (int i = 0; i < 4; i++) asm volatile("mov.b64 %0, {%1, %2};" : "=l"(ds[i]) : "r"(dlo - i * (2 * UP >> 4)), "r"(8 | zero));
            auto loadQ = [&](uint32_t (&X)[4][4], uint32_t prev) {
#pragma unroll
                for (int i = 0; i < 4; i++) { X[i][0] = lds32(pp + i * 64); X[i][1] = lds32(pp + i * 64 + 32); }
                X[0][2] = CP(prev);
#pragma unroll
                for (int i = 0; i < 4; i++) { X[i][3] = CP(X[i][0]); if (i) X[i][2] = CP(X[i - 1][1]); }
                pu += 256;
            };
            auto issue = [&](uint32_t (&X)[4][4]) {
                asm volatile("wgmma.fence.sync.aligned;" ::: "memory");
#pragma unroll
                for (int i = 0; i < 4; i++) wgmma32(acc, X[i], ds[i]);
                asm volatile("wgmma.commit_group.sync.aligned;" ::: "memory");
#pragma unroll
                for (int i = 0; i < 4; i++) asm volatile("{ .reg .b32 l, h; mov.b64 {l, h}, %0; add.u32 l, l, %1; mov.b64 %0, {l, h}; }" : "+l"(ds[i]) : "r"(~zero));
            };
#pragma unroll
            for (int i = 0; i < 4; i++) {
                Q[i][0] = Q[i][1] = 0;
                if (wq + i >= 3) { Q[i][0] = lds32(pp + i * 64); Q[i][1] = lds32(pp + i * 64 + 32); }
            }
            Q[0][2] = CP(0);
#pragma unroll
            for (int i = 0; i < 4; i++) { Q[i][3] = CP(Q[i][0]); if (i) Q[i][2] = CP(Q[i - 1][1]); }
            pu += 256;
#pragma unroll 1
            for (int dl = 0; dl < 4; dl++) {
                issue(Q);
                asm volatile("wgmma.wait_group.sync.aligned 1;" ::: "memory");
                loadQ(R, Q[3][1]);
                issue(R);
                asm volatile("wgmma.wait_group.sync.aligned 1;" ::: "memory");
                loadQ(Q, R[3][1]);
            }
            issue(Q);
            asm volatile("wgmma.wait_group.sync.aligned 0;" ::: "memory");
        }
        const uint32_t pstep = mapa(sb, 1) - mapa(sb, 0), ym = mapa(mb + MB_Y * 8, 2 * wq);
#pragma unroll
        for (int e = 0; e < 2; e++)
            st_async4(yd + e * pstep, bmul2(pack_bf16(acc[0][2 * e], acc[0][2 * e + 1]), inv), bmul2(pack_bf16(acc[1][2 * e], acc[1][2 * e + 1]), inv),
                      bmul2(pack_bf16(acc[2][2 * e], acc[2][2 * e + 1]), inv), bmul2(pack_bf16(acc[3][2 * e], acc[3][2 * e + 1]), inv), ym + e * pstep);
        if (lane == 0) asm volatile("mbarrier.arrive.shared::cta.b64 _, [%0];" :: "r"(mb + MB_Y * 8) : "memory");
    }
    STAMP(9);
    uint32_t ha[5], hb[5];
    if (warp < 16) {
        const uint4 wk = lds128(sb + SM_DW + cq * 16);
        uint32_t sel[5] = {wk.x, wk.y, wk.z, wk.w, lds32(sb + SM_DW + 64 + cq * 4)}, sel2[5];
#pragma unroll
        for (int i = 0; i < 5; i++) {
            if (!(g & 1)) sel[i] = 0x3F803F80u;
            sel2[i] = sel[i]; PIN(sel2[i]);
        }
        const uint32_t y4 = sb + SM_XT + 128 + warp * 32 + (2 * (lane >> 3) + (lane & 1)) * YP + ((lane & 7) >> 1) * YS;
        const uint32_t y1 = sb + SM_XT + 128 + warp * 32 + (lane & 7) * YP + 4 * YS + (lane & 8) * 2 + (lane & 6) * 8;
        const uint32_t ao = (256 * q + tn) * 16;
        uint32_t hta = sb + SM_HT + tn * 80;
        unsigned long long ap = (unsigned long long)((char*)g_s.acc + ao);
        asm volatile("add.u64 %0, %0, %1;" : "+l"(ap) : "l"((unsigned long long)zero));
        PIN(hta);
        mbar_wait(mb + MB_Y * 8);
        STAMP(10);
        float ca[4] = {0.f, 0.f, 0.f, 0.f}, cb[4] = {0.f, 0.f, 0.f, 0.f};
        {
            uint32_t ya[4], yb[4], yc, yd;
            ldsm4t(ya, y4); ldsm4t(yb, y4 + 16); ldsm2t(yc, yd, y1);
#pragma unroll
            for (int i = 0; i < 4; i++) { ha[i] = badd2(xa[i], ya[i]); hb[i] = badd2(xb[i], yb[i]); }
            ha[4] = badd2(xa[4], yc); hb[4] = badd2(xb[4], yd);
        }
        if (nslot != 5) {
            ha[4] = hb[4] = 0;
            if (cq >= 2) ha[0] = ha[1] = ha[2] = ha[3] = hb[0] = hb[1] = hb[2] = hb[3] = 0;
        }
#pragma unroll
        for (int i = 0; i < 5; i++) { mma_bf16_k8(ca, ha[i], sel[i], ha[i]); mma_bf16_k8(cb, hb[i], sel2[i], hb[i]); }
        if (!(g & 1)) { ca[1] = ca[0]; cb[1] = cb[0]; }
        if (cq == (g >> 1)) {
            asm volatile("red.relaxed.gpu.global.add.v4.f32 [%0], {%1,%2,%3,%4};" :: "l"(ap), "f"(1.0f), "f"(ca[1]), "f"(ca[2]), "f"(ca[3]) : "memory");
            asm volatile("red.relaxed.gpu.global.add.v4.f32 [%0], {%1,%2,%3,%4};" :: "l"(ap + 128), "f"(1.0f), "f"(cb[1]), "f"(cb[2]), "f"(cb[3]) : "memory");
        }
        sts128(hta + cq * 16, ha[0], ha[1], ha[2], ha[3]); sts32(hta + 64 + cq * 4, ha[4]);
        sts128(hta + cq * 16 + 640, hb[0], hb[1], hb[2], hb[3]); sts32(hta + 704 + cq * 4, hb[4]);
        STAMP(11);
    }
    const int kq = warp / 5, mt = warp - 5 * kq;
    const int mi = lane >> 3, mr = lane & 7;
    const unsigned tk = (unsigned)tid / 72u, ck = tid - tk * 72;
    uint32_t A[9][4];
    auto loadA = [&]() {
        mbar_wait(mb + MB_W1 * 8);
        const uint32_t aa = sb + (mi & 1) * SM_WU + (8 * (mi >> 1) + mr) * 80 + (144 * 80 * kq + mt * 16);
#pragma unroll
        for (int s = 0; s < 9; s++) ldsm4t(A[s], aa + s * 1280);
    };
    const uint32_t par = (lds32(sb + SM_SC + 28) & 1) ? 0u : 0x40004000u;
    uint32_t go = (ck / 5u + ck) * 16, gs = sb + SM_SEL + 4 + (tk & 7) * 8;
    unsigned long long gb = (unsigned long long)((const char*)g_s.cand + go);
    uint32_t xs = sb + SM_XS + tk * 16 + tid * 16;
    asm volatile("add.u64 %0, %0, %1;" : "+l"(gb) : "l"((unsigned long long)zero));
    PIN(xs); PIN(gs);
    auto outtile = [&]() {
        const uint2 sa = lds64(sb + SM_ST + tn * 8), sbb = lds64(sb + SM_ST + tn * 8 + 64);
#pragma unroll
        for (int i = 0; i < 5; i++) { ha[i] = badd2(ha[i], norm2(ha[i], sa.x, sa.y)); hb[i] = badd2(hb[i], norm2(hb[i], sbb.x, sbb.y)); }
        const bool hf = (c & 1) && cq == 0;
        const uint32_t o16 = sb + SM_XT + (hf ? 16384 + tn * 16 : tn * 64 + (cq - (c & 1)) * 16), o4 = sb + SM_XT + ((c & 1) ? tn * 64 + 48 : 16384 + tn * 16) + cq * 4;
        sts128(o16, ha[0], ha[1], ha[2], ha[3]); sts32(o4, ha[4]);
        sts128(o16 + (hf ? 128 : 512), hb[0], hb[1], hb[2], hb[3]); sts32(o4 + ((c & 1) ? 512 : 128), hb[4]);
    };
    if (warp < 8) {
        const float wsum = ldsf(sb + SM_SC + 24);
        const uint32_t idx = 2047 - (512 * ((tid >> 1) & 3) + 128 * ((tid >> 3) & 3) + 64 * (tid & 1) + 8 * q + warp);
        uint32_t km0 = mapa(mb + MB_KEY * 8, 2 * cq), km1 = mapa(mb + MB_KEY * 8, 2 * cq + 1), ka0 = mapa(sb + SM_RK + q * 32, 2 * cq), ka1 = mapa(sb + SM_RK + q * 32, 2 * cq + 1);
        unsigned long long c0 = (unsigned long long)((char*)g_s.cand + ((q * 8 * NCL + c) * 6 + cq) * 16), c1 = c0 + (64 - cq * 12);
        uint32_t hc = sb + SM_HT + cq * 16, h4a = sb + SM_HT + 64 + cq * 4;
        uint32_t ca = sb + SM_KEY + warp * 128 + (warp & 1) * 32 + (lane & 28), r2a = sb + SM_KEY + cq * 16 + (cq >> 1) * 128;
        PIN(ca); PIN(r2a); PIN(km0); PIN(km1); PIN(ka0); PIN(ka1); PIN(hc); PIN(h4a);
        asm volatile("add.u64 %0, %0, %2; add.u64 %1, %1, %2;" : "+l"(c0), "+l"(c1) : "l"((unsigned long long)zero));
        uint4 s; int n = 0;
        do { s = ld_rlx128(&g_s.acc[256 * q + tid]); } while (__uint_as_float(s.x) != (float)NCL && ++n < SPIN_LIMIT);
        STAMP(16);
        const uint32_t ox = __shfl_xor_sync(~0u, (lane & 1) ? s.z : s.w, 1);
        const uint32_t ms = ln_stats(__uint_as_float((lane & 1) ? ox : s.z), __uint_as_float(s.y));
        const float rs = rcpf(bf_hi(ms));
        const uint32_t rb = pack_bf16(0.f, fmaf(-bf_lo(ms), wsum, __uint_as_float((lane & 1) ? s.w : ox)) * rs);
        const uint32_t key = (((rb ^ (((int)rb >> 31) | 0x80000000u)) >> 16) << 11) | idx;
        sts32(sb + SM_KEY + tid * 4, key);
        sts64(sb + SM_ST + tid * 8, ms, rsplit(rs));
        __syncwarp();
        uint32_t rank = rank4<8, 16>(sb + SM_KEY + warp * 128, key, ~zero);
        {
            const uint32_t sa = (rank * 4 ^ (warp & 1) * 32) + opaque(sb + SM_KEY + warp * 128);
            sts32(sa, key); sts32(sa + 1024, tid);
        }
        __syncwarp();
        const uint32_t mk = lds32(ca), t = lds32(ca + 1024);
        STAMP(17);
        bar_sync(12, 512);
        STAMP(18);
        const uint4 hv = lds128(hc + t * 80);
        const uint2 sv = lds64(sb + SM_ST + t * 8);
        const uint32_t h4 = lds32(h4a + t * 80);
        rank = rank4<4, 256>(r2a, mk, ~zero);
        const uint32_t rr = bmul2(sv.y, 0x3C803C80u);
        const uint32_t p0 = (norm2(hv.x, sv.x, rr) & 0xBFFFBFFFu) | par, p1 = (norm2(hv.y, sv.x, rr) & 0xBFFFBFFFu) | par, p2 = (norm2(hv.z, sv.x, rr) & 0xBFFFBFFFu) | par,
                       p3 = (norm2(hv.w, sv.x, rr) & 0xBFFFBFFFu) | par, p4 = (norm2(h4, sv.x, rr) & 0xBFFFBFFFu) | par;
        rank += __shfl_xor_sync(~0u, rank, 1);
        rank += __shfl_xor_sync(~0u, rank, 2);
        if (rank < 8) {
            st_async1(ka0 + rank * 4, mk, km0); st_async1(ka1 + rank * 4, mk, km1);
            st_rlx128((void*)(c0 + (unsigned long long)rank * 1440), p0, p1, p2, p3);
            asm volatile("st.relaxed.gpu.global.u32 [%0], %1;" :: "l"(c1 + (unsigned long long)rank * 1440), "r"(p4) : "memory");
        }
        __syncwarp();
    } else {
        mbar_wait(mb + MB_Y * 8); loadA();
        if (warp < 16) {
            bar_sync(12, 512);
        }
    }
    if (warp < 16) {
        outtile();
        if (warp >= 8) {
            uint32_t src = ((tid >> 2) - 64) * 1440, ma = sb + SM_RK - 256 + (tid >> 2) * 4, ra = sb + SM_RK + cq * 16;
            PIN(src); PIN(ma); PIN(ra);
            STAMP(19);
            mbar_wait(mb + MB_KEY * 8);
            STAMP(20);
            const uint32_t mk = lds32(ma);
            uint32_t rank = rank4<4, 64>(ra, mk, ~zero);
            rank += __shfl_xor_sync(~0u, rank, 1); rank += __shfl_xor_sync(~0u, rank, 2);
            sts64(sb + SM_SEL + rank * 8, mk, src);
        }
    }
    bar_sync(11, 672);
    STAMP(12);

    const char* gp = (const char*)gb + lds32(gs);
    uint4 hv = ld_rlx128(gp);
    if (warp < 8) loadA();
    uint32_t bx = sb + SM_XS + mr * 1168 + mi * 16 + 288 * kq, gd = mapa(sb, (kq & (NRED - 1)) * (8 / NRED)) + (SM_GU + (q * nslot + mt) * 128) + lane * 4;
    PIN(bx); PIN(gd);
    {
        if (warp < 18) {
            int n = 0;
            while (true) {
                sts128(xs, hv.x ^ par, hv.y ^ par, hv.z ^ par, hv.w ^ par);
                if (!__any_sync(~0u, ((hv.x ^ par) | (hv.y ^ par) | (hv.z ^ par) | (hv.w ^ par)) & 0x40004000u) || ++n >= SPIN_LIMIT) break;
                hv = ld_rlx128(gp);
            }
        }
    }
    bar_sync(14, 768);
    STAMP(13);
    float4 own;
    {
        float c0[4] = {0.f, 0.f, 0.f, 0.f}, c1[4] = {0.f, 0.f, 0.f, 0.f}, c2[4] = {0.f, 0.f, 0.f, 0.f};
        uint32_t b[5][4];
#pragma unroll
        for (int s = 0; s < 4; s++) ldsm4(b[s], bx + s * 64);
        asm volatile("ldmatrix.sync.aligned.m8n8.x2.shared.b16 {%0,%1}, [%2];" : "=r"(b[4][0]), "=r"(b[4][1]) : "r"(bx + 256) : "memory");
        mma_bf16(c0, A[0][0], A[0][1], A[0][2], A[0][3], b[0][0], b[0][1]);
        mma_bf16(c1, A[1][0], A[1][1], A[1][2], A[1][3], b[0][2], b[0][3]);
        mma_bf16(c2, A[2][0], A[2][1], A[2][2], A[2][3], b[1][0], b[1][1]);
        mma_bf16(c0, A[3][0], A[3][1], A[3][2], A[3][3], b[1][2], b[1][3]);
        mma_bf16(c1, A[4][0], A[4][1], A[4][2], A[4][3], b[2][0], b[2][1]);
        mma_bf16(c2, A[5][0], A[5][1], A[5][2], A[5][3], b[2][2], b[2][3]);
        mma_bf16(c0, A[6][0], A[6][1], A[6][2], A[6][3], b[3][0], b[3][1]);
        mma_bf16(c1, A[7][0], A[7][1], A[7][2], A[7][3], b[3][2], b[3][3]);
        mma_bf16(c2, A[8][0], A[8][1], A[8][2], A[8][3], b[4][0], b[4][1]);
        own = make_float4(c0[0] + c1[0] + c2[0], c0[1] + c1[1] + c2[1], c0[2] + c1[2] + c2[2], c0[3] + c1[3] + c2[3]);
        sts128f(sb + SM_RED + tid * 16, own.x, own.y, own.z, own.w);
    }
    bar_sync(1 + mt, 128);
    STAMP(21);
    if (mt < nslot && kq >= 4 - NRED) {
        const uint32_t ra = lane * 16 + opaque(sb + SM_RED + mt * 512);
        const float4 p0 = lds128f(ra), p1 = lds128f(ra + 2560), p2 = lds128f(lane * 16 + opaque(sb + SM_RED + mt * 512 + (5 - kq) * 2560)), p3 = own;
        const float g0 = bfr(((p0.x + p1.x) + (p2.x + p3.x)) * 64.f), g1 = bfr(((p0.y + p1.y) + (p2.y + p3.y)) * 64.f);
        const uint32_t sg = pack_bf16(g0 * rcpf(1.f + ex2f(g0 * -1.4426950408889634f)), g1 * rcpf(1.f + ex2f(g1 * -1.4426950408889634f)));
        const uint32_t gu = bmul2(sg, pack_bf16(((p0.z + p1.z) + (p2.z + p3.z)) * 64.f, ((p0.w + p1.w) + (p2.w + p3.w)) * 64.f));
        const uint32_t pstep = mapa(sb, 1) - mapa(sb, 0), gm = mapa(mb + MB_GU * 8, (kq & (NRED - 1)) * (8 / NRED));
#pragma unroll
        for (int i = 0; i < 8 / NRED; i++) st_async1(gd + i * pstep, gu, gm + i * pstep);
    }
    mbar_wait(mb + MB_W2 * 8);
    {
        const uint32_t aa = sb + (8 * (mi >> 1) + mr) * 144 + (mi & 1) * 16 + (SM_FAR + 2304 * kq + mt * 32);
#pragma unroll
        for (int s = 0; s < 5; s++) ldsm4t(A[s], aa + s * FAR_SZ);
    }
    float sig; uint32_t ra2; unsigned long long fp, op;
    if (warp < 8) {
        const uint32_t key = lds32(sb + SM_SEL + warp * 8), k16 = key << 5, fj = 24 * q + lane;
        sig = bfr(rcpf(1.f + ex2f(__uint_as_float((k16 ^ (~((int)k16 >> 31) | 0x80000000u)) & 0xFFFF0000u) * -1.4426950408889634f)));
        ra2 = sb + SM_RED2 + warp * 304 + lane * 12;
        fp = (unsigned long long)(g_s.fin + warp * 192 + fj); op = (unsigned long long)(prm.out + (~key & 2047) * D_ + 3 * fj);
        PIN(ra2);
        asm volatile("add.u64 %0, %0, %3; add.u64 %1, %1, %3;" : "+l"(fp), "+l"(op), "+f"(sig) : "l"((unsigned long long)zero));
    }
    {
        uint32_t ba = sb + (SM_GU + 256 * kq) + (lane & 15) * 16 + (lane >> 4) * 1024, wa = sb + (SM_RED2 + kq * 2432 + mt * 64) + g * 4 + cq * 608;
        PIN(ba); PIN(wa);
        STAMP(22);
        mbar_wait(mb + MB_GU * 8);
        STAMP(23);
        float c0[4] = {0.f, 0.f, 0.f, 0.f}, c1[4] = {0.f, 0.f, 0.f, 0.f}, c2[4] = {0.f, 0.f, 0.f, 0.f};
        uint32_t b[2][4], b8, b9;
        ldsm4t(b[0], ba); ldsm4t(b[1], ba + 2048); ldsm2t(b8, b9, ba + 4096);
        mma_bf16(c0, A[0][0], A[0][1], A[0][2], A[0][3], b[0][0], b[0][1]);
        mma_bf16(c1, A[1][0], A[1][1], A[1][2], A[1][3], b[0][2], b[0][3]);
        if (nslot == 5) {
            mma_bf16(c2, A[4][0], A[4][1], A[4][2], A[4][3], b8, b9);
            mma_bf16(c0, A[2][0], A[2][1], A[2][2], A[2][3], b[1][0], b[1][1]);
            mma_bf16(c1, A[3][0], A[3][1], A[3][2], A[3][3], b[1][2], b[1][3]);
        }
        stsf(wa, c0[0] + c1[0] + c2[0]); stsf(wa + 304, c0[1] + c1[1] + c2[1]);
        if (mt < 4) { stsf(wa + 32, c0[2] + c1[2] + c2[2]); stsf(wa + 336, c0[3] + c1[3] + c2[3]); }
    }
    if (warp < 8) {
        float v[3];
        bar_sync(6, 640);
        STAMP(14);
        if (lane < 24) {
#pragma unroll
            for (int i = 0; i < 3; i++) v[i] = ((ldsf(ra2 + i * 4) + ldsf(ra2 + i * 4 + 2432)) + (ldsf(ra2 + i * 4 + 4864) + ldsf(ra2 + i * 4 + 7296))) * sig;
            asm volatile("{ .reg .f32 x, y, z, w; .reg .b16 a, b, c; .reg .pred p;\n"
                         "atom.relaxed.gpu.global.add.v4.f32 {x,y,z,w}, [%0], {%2,%3,%4,%5};\n"
                         "setp.eq.f32 p, w, %6; add.f32 x, x, %2; add.f32 y, y, %3; add.f32 z, z, %4;\n"
                         "cvt.rn.bf16.f32 a, x; cvt.rn.bf16.f32 b, y; cvt.rn.bf16.f32 c, z;\n"
                         "@p st.global.b16 [%1], a; @p st.global.b16 [%1 + 2], b; @p st.global.b16 [%1 + 4], c; }"
                         :: "l"(fp), "l"(op), "f"(v[0]), "f"(v[1]), "f"(v[2]), "f"(3.f), "f"(3.f * NCL) : "memory");
        }
    } else bar_arrive(6, 640);
    STAMP(15);
}

#undef pp
typedef __nv_bfloat16 bf16;
__device__ bf16 f_n[L_ * D_], f_h[L_ * D_];
__device__ float f_k[D_ * L_], f_r[L_], f_gu[8 * F_];
__device__ int f_idx[8];
__device__ __forceinline__ float b2f(bf16 v) { return __bfloat162float(v); }
__global__ void fb_ln(const bf16* in, const bf16* wr, bf16* out) {
    const int t = blockIdx.x * 8 + (threadIdx.x >> 5), lane = threadIdx.x & 31;
    const bf16* r = (in ? in : f_h) + t * D_;
    float s1 = 0.f, s2 = 0.f, s3 = 0.f;
    for (int i = lane; i < D_; i += 32) s1 += b2f(r[i]);
    for (int o = 16; o; o >>= 1) s1 += __shfl_xor_sync(~0u, s1, o);
    for (int i = lane; i < D_; i += 32) { const float d = b2f(r[i]) - s1 / D_; s2 += d * d; }
    for (int o = 16; o; o >>= 1) s2 += __shfl_xor_sync(~0u, s2, o);
    const float m = bfr(s1 / D_), sd = bfr(sqrtf(bfr(bfr(s2 / D_) + 1e-5f)));
    for (int i = lane; i < D_; i += 32) {
        const float v = bfr(bfr(b2f(r[i]) - m) / sd);
        f_n[t * D_ + i] = __float2bfloat16(v);
        if (!in) { s3 += v * b2f(wr[i]); out[t * D_ + i] = __float2bfloat16(b2f(r[i]) + v); }
    }
    for (int o = 16; o; o >>= 1) s3 += __shfl_xor_sync(~0u, s3, o);
    f_r[t] = bfr(s3);
}
__global__ void fb_taps(Params p) {
    const int d = blockIdx.x >> 3, l = (blockIdx.x & 7) * 256 + threadIdx.x;
    const float dt = bfr(expf(bf_lo(p.logdt[d]))), lf = bfr((float)l);
    float k = 0.f;
    for (int n = d * 128; n < d * 128 + 128; n++) {
        float wr, wi, sn, cs;
        cmul(wr, wi, bf_lo(p.prm6[4][n]), bf_lo(p.prm6[5][n]), dt * bf_lo(p.prm6[2][n]), dt * bf_lo(p.prm6[3][n]));
        sincosf(dt * bf_lo(p.prm6[1][n]) * lf, &sn, &cs);
        k += expf(dt * bf_lo(p.prm6[0][n]) * lf) * (wr * cs - wi * sn);
    }
    f_k[l * D_ + d] = k;
}
__global__ void fb_conv(Params p) {
    const int t = blockIdx.x, d = threadIdx.x;
    float y = 0.f;
    for (int l = 0; l <= t; l++) y += f_k[l * D_ + d] * b2f(f_n[(t - l) * D_ + d]);
    f_h[t * D_ + d] = __float2bfloat16(bf_lo(p.x[t * D_ + d]) + bfr(bfr(y) + bfr(b2f(f_n[t * D_ + d]) * bf_lo(p.dskip[d]))));
}
__global__ void fb_top() {
    const int t = blockIdx.x * 256 + threadIdx.x;
    int rank = 0;
    for (int j = 0; j < L_; j++) rank += f_r[j] > f_r[t] || (f_r[j] == f_r[t] && j < t);
    if (rank < 8) f_idx[rank] = t;
}
__global__ void fb_ffn1(const bf16* wg, const bf16* wu) {
    const int f = blockIdx.x * 256 + threadIdx.x, j = blockIdx.y;
    float g = 0.f, u = 0.f;
    for (int i = 0; i < D_; i++) { const float v = b2f(f_n[f_idx[j] * D_ + i]); g += v * b2f(wg[i * F_ + f]); u += v * b2f(wu[i * F_ + f]); }
    g = bfr(g);
    f_gu[j * F_ + f] = bfr(bfr(g / (1.f + expf(-g))) * bfr(u));
}
__global__ void fb_ffn2(const bf16* wd, bf16* out) {
    const int d = threadIdx.x, j = blockIdx.x, t = f_idx[j];
    float y = 0.f;
    for (int f = 0; f < F_; f++) y += f_gu[j * F_ + f] * b2f(wd[f * D_ + d]);
    out[t * D_ + d] = __float2bfloat16(b2f(f_h[t * D_ + d]) + bfr(b2f(f_n[t * D_ + d]) + bfr(bfr(y) * bfr(1.f / (1.f + expf(-f_r[t]))))));
}

typedef CUresult (*EncodeFn)(CUtensorMap*, CUtensorMapDataType, cuuint32_t, void*, const cuuint64_t*, const cuuint64_t*,
                             const cuuint32_t*, const cuuint32_t*, CUtensorMapInterleave, CUtensorMapSwizzle,
                             CUtensorMapL2promotion, CUtensorMapFloatOOBfill);

void make_map(EncodeFn fn, CUtensorMap* tm, const void* p, int cols, int rows, int bc, int br) {
    cuuint64_t dims[2] = {(cuuint64_t)cols, (cuuint64_t)rows};
    cuuint64_t strides[1] = {(cuuint64_t)cols * 2};
    cuuint32_t box[2] = {(cuuint32_t)bc, (cuuint32_t)br};
    cuuint32_t es[2] = {1, 1};
    fn(tm, CU_TENSOR_MAP_DATA_TYPE_BFLOAT16, 2, const_cast<void*>(p), dims, strides, box, es, CU_TENSOR_MAP_INTERLEAVE_NONE,
       CU_TENSOR_MAP_SWIZZLE_NONE, CU_TENSOR_MAP_L2_PROMOTION_L2_128B, CU_TENSOR_MAP_FLOAT_OOB_FILL_NONE);
}

void make_map3(EncodeFn fn, CUtensorMap* tm, const void* p) {
    cuuint64_t dims[5] = {(cuuint64_t)D_, 64, 2, 2, 8};
    cuuint64_t strides[4] = {(cuuint64_t)D_ * 2, (cuuint64_t)D_ * 2048, (cuuint64_t)D_ * 128, (cuuint64_t)D_ * 256};
    cuuint32_t box[5] = {XW, 9, 2, 2, 8};
    cuuint32_t es[5] = {1, 1, 1, 1, 1};
    fn(tm, CU_TENSOR_MAP_DATA_TYPE_BFLOAT16, 5, const_cast<void*>(p), dims, strides, box, es, CU_TENSOR_MAP_INTERLEAVE_NONE,
       CU_TENSOR_MAP_SWIZZLE_NONE, CU_TENSOR_MAP_L2_PROMOTION_NONE, CU_TENSOR_MAP_FLOAT_OOB_FILL_NONE);
}

void make_map5(EncodeFn fn, CUtensorMap* tm, const void* p, int bc) {
    cuuint64_t dims[5] = {(cuuint64_t)D_, 2, 4, 4, 64};
    cuuint64_t strides[4] = {(cuuint64_t)D_ * 128, (cuuint64_t)D_ * 1024, (cuuint64_t)D_ * 256, (cuuint64_t)D_ * 2};
    cuuint32_t box[5] = {(cuuint32_t)bc, 2, 4, 4, 8};
    cuuint32_t es[5] = {1, 1, 1, 1, 1};
    fn(tm, CU_TENSOR_MAP_DATA_TYPE_BFLOAT16, 5, const_cast<void*>(p), dims, strides, box, es, CU_TENSOR_MAP_INTERLEAVE_NONE,
       CU_TENSOR_MAP_SWIZZLE_NONE, CU_TENSOR_MAP_L2_PROMOTION_NONE, CU_TENSOR_MAP_FLOAT_OOB_FILL_NONE);
}

}

extern "C" void kernel_launch(void* const* d_in, const int* in_sizes, int n_in, void* d_out, int out_size) {
    (void)in_sizes; (void)n_in; (void)out_size;
    void* fp = nullptr;
    cudaDriverEntryPointQueryResult qr;
    cudaGetDriverEntryPoint("cuTensorMapEncodeTiled", &fp, cudaEnableDefault, &qr);
    EncodeFn fn = (EncodeFn)fp;
    CUtensorMap tmG, tmU, tmD, tmO, tmX, tmH;
    make_map3(fn, &tmX, d_in[0]);
    make_map(fn, &tmG, d_in[11], F_, D_, 40, 48);
    make_map(fn, &tmU, d_in[12], F_, D_, 40, 48);
    make_map(fn, &tmD, d_in[13], D_, F_, 72, 64);
    make_map5(fn, &tmO, d_out, 32);
    make_map5(fn, &tmH, d_out, 8);
    Params p;
    p.x = (const unsigned short*)d_in[0];
    for (int i = 0; i < 6; i++) p.prm6[i] = (const unsigned short*)d_in[1 + i];
    p.logdt = (const unsigned short*)d_in[7]; p.dskip = (const unsigned short*)d_in[8];
    p.wr = (const unsigned short*)d_in[10];
    p.out = (__nv_bfloat16*)d_out;
    p.zero = 0;
    cudaGetSymbolAddress((void**)&p.gs, g_s);
    cudaFuncSetAttribute(fused_kernel, cudaFuncAttributeMaxDynamicSharedMemorySize, SM_TOTAL);
    static int nclusters = -1;
    if (nclusters < 0) {
        cudaLaunchConfig_t cfg = {};
        cudaLaunchAttribute at;
        at.id = cudaLaunchAttributeClusterDimension; at.val.clusterDim.x = CS; at.val.clusterDim.y = 1; at.val.clusterDim.z = 1;
        cfg.gridDim = dim3(NCTA); cfg.blockDim = dim3(NTHR); cfg.dynamicSmemBytes = SM_TOTAL; cfg.attrs = &at; cfg.numAttrs = 1;
        if (cudaOccupancyMaxActiveClusters(&nclusters, fused_kernel, &cfg) != cudaSuccess) { (void)cudaGetLastError(); nclusters = NCL; }
    }
    if (nclusters >= NCL && !FORCE_FALLBACK) {
        fused_kernel<<<NCTA, NTHR, SM_TOTAL>>>(p, tmG, tmU, tmD, tmO, tmX, tmH);
        return;
    }
    fb_ln<<<L_ / 8, 256>>>((const bf16*)d_in[0], nullptr, nullptr);
    fb_taps<<<D_ * 8, 256>>>(p);
    fb_conv<<<L_, D_>>>(p);
    fb_ln<<<L_ / 8, 256>>>(nullptr, (const bf16*)d_in[10], p.out);
    fb_top<<<L_ / 256, 256>>>();
    fb_ffn1<<<dim3(F_ / 256, 8), 256>>>((const bf16*)d_in[11], (const bf16*)d_in[12]);
    fb_ffn2<<<8, D_>>>((const bf16*)d_in[13], p.out);
}
```

```cpp
#include <cuda_runtime.h>
#include <cuda_bf16.h>
#include <cuda_fp16.h>
#include <cuda.h>
#include <stdint.h>

namespace {

constexpr int L_ = 2048, D_ = 576, F_ = 4608;
constexpr int NCL = 15, CS = 8, NCTA = NCL * CS, NTHR = 768;
#define FORCE_FALLBACK 0
constexpr int XW = 48, NRED = 2;
constexpr int SPIN_LIMIT = 1 << 22;

constexpr int SM_WG   = 0;
constexpr int SM_WU   = 46080;
constexpr int YP = 3392, YS = 656;
constexpr int UP = 3280, US = 656;
constexpr int SM_XT   = 92160;
constexpr int SM_U    = SM_XT + 8 * YP;
constexpr int SM_FAR  = SM_U + 8 * UP;
constexpr int FAR_SZ  = 12416;
constexpr int F_E5 = 0, F_O5 = 1536, F_E3 = 3088, F_O3 = 4624, F_E7 = 6176, F_E2 = F_E7 + 1024, F_E9 = F_E7 + 2048,
              F_H = 3088, F_O7 = F_E7 + F_H, F_O2 = F_E2 + F_H, F_O9 = F_E9 + F_H;
constexpr int SM_P    = SM_FAR + 5 * FAR_SZ;
constexpr int PN_SZ = 584 * 4, SM_PN = SM_P + 65 * 4;
constexpr int P_GS = 50 * 4, P_H7 = 200 * 4, P_HS = 74 * 4;
constexpr int PF_SZ = (200 + 222) * 4, SM_PF = SM_PN + 5 * PN_SZ + 36;
constexpr int SM_MISC = SM_PF + 5 * PF_SZ;
constexpr int SM_ST   = SM_MISC;
constexpr int SM_RK   = SM_ST + 2048;
constexpr int SM_SEL  = SM_FAR + FAR_SZ + 10240;
constexpr int SM_KG   = SM_RK + 320;
constexpr int SM_SC   = SM_KG + 160;
constexpr int SM_DW   = SM_SC + 32;
constexpr int SM_MB   = SM_DW + 160;
constexpr int SM_TOTAL = SM_MB + 128;
constexpr int SM_ROW  = SM_XT - 20736;
constexpr int SM_XTL  = SM_ROW - 576 * XW;
constexpr int SM_RED2 = SM_WG;
constexpr int SM_HT   = SM_P - 512;
constexpr int SM_KEY  = SM_FAR + 10240 + 128;
constexpr int SM_CAND = SM_KEY + 1024;
constexpr int SM_XS   = SM_U;
constexpr int SM_GU   = SM_XS + 9344;
constexpr int SM_RED  = SM_GU + 5632;
static_assert(F_O9 + 1024 <= FAR_SZ && FAR_SZ % 128 == 0, "far overflow");
static_assert(SM_RED + 10240 <= SM_FAR && SM_HT + 20496 <= SM_MISC, "alias overflow");
static_assert(SM_TOTAL <= 232448, "smem overflow");
static_assert(SM_FAR % 128 == 0 && SM_XT % 128 == 0 && SM_XTL % 128 == 0 && SM_P % 16 == 0 && SM_MISC % 16 == 0 && SM_MB % 8 == 0, "align");

enum { MB_X = 0, MB_W1 = 5, MB_W2 = 6, MB_KEY = 7, MB_GU = 8, MB_Y = 9, MB_OUT = 10, MB_T = 11, MB_R = 12 };

struct __align__(128) Scratch {
    unsigned epoch, zcnt, pad[30];
    uint4  st1[L_ * 2];
    float4 acc[L_];
    uint4  cand[64 * NCL * 6];
    float4 fin[8 * 192 + 24];
};
__device__ Scratch g_s;
#define STAMP(i)

__device__ __forceinline__ uint32_t mapa(uint32_t a, uint32_t r) { uint32_t d; asm("mapa.shared::cluster.u32 %0, %1, %2;" : "=r"(d) : "r"(a), "r"(r)); return d; }
__device__ __forceinline__ void mbar_wait(uint32_t mb) {
    asm volatile("{ .reg .pred p, q; .reg .u32 n; mov.u32 n, 0;\n"
                 "W_%=: mbarrier.try_wait.parity.shared::cta.b64 p, [%0], 0; add.u32 n, n, 1; setp.lt.and.u32 q, n, 65536, !p; @q bra W_%=; }" :: "r"(mb) : "memory");
}
__device__ __forceinline__ bool elect() { uint32_t e; asm volatile("{ .reg .pred p; elect.sync _|p, 0xffffffff; selp.u32 %0, 1, 0, p; }" : "=r"(e)); return e; }
__device__ __forceinline__ void arm(uint32_t mb, uint32_t bytes) { asm volatile("mbarrier.arrive.expect_tx.shared::cta.b64 _, [%0], %1;" :: "r"(mb), "r"(bytes) : "memory"); }
__device__ __forceinline__ void bar_sync(int id, int n) { asm volatile("bar.sync %0, %1;" :: "r"(id), "r"(n) : "memory"); }
__device__ __forceinline__ void bar_arrive(int id, int n) { asm volatile("bar.arrive %0, %1;" :: "r"(id), "r"(n) : "memory"); }
__device__ __forceinline__ uint32_t lds16(uint32_t a) { unsigned short v; asm volatile("ld.shared.u16 %0, [%1];" : "=h"(v) : "r"(a) : "memory"); return v; }
__device__ __forceinline__ uint32_t lds32(uint32_t a) { uint32_t v; asm volatile("ld.shared.u32 %0, [%1];" : "=r"(v) : "r"(a) : "memory"); return v; }
__device__ __forceinline__ uint2 lds64(uint32_t a) { uint2 v; asm volatile("ld.shared.v2.u32 {%0,%1}, [%2];" : "=r"(v.x), "=r"(v.y) : "r"(a) : "memory"); return v; }
__device__ __forceinline__ float ldsf(uint32_t a) { float v; asm volatile("ld.shared.f32 %0, [%1];" : "=f"(v) : "r"(a) : "memory"); return v; }
__device__ __forceinline__ uint4 lds128(uint32_t a) { uint4 v; asm volatile("ld.shared.v4.u32 {%0,%1,%2,%3}, [%4];" : "=r"(v.x), "=r"(v.y), "=r"(v.z), "=r"(v.w) : "r"(a) : "memory"); return v; }
__device__ __forceinline__ float4 lds128f(uint32_t a) { float4 v; asm volatile("ld.shared.v4.f32 {%0,%1,%2,%3}, [%4];" : "=f"(v.x), "=f"(v.y), "=f"(v.z), "=f"(v.w) : "r"(a) : "memory"); return v; }
__device__ __forceinline__ void sts16(uint32_t a, uint32_t v) { asm volatile("{ .reg .b16 l, h; mov.b32 {l, h}, %1; st.shared.b16 [%0], l; }" :: "r"(a), "r"(v) : "memory"); }
__device__ __forceinline__ void sts32(uint32_t a, uint32_t v) { asm volatile("st.shared.u32 [%0], %1;" :: "r"(a), "r"(v) : "memory"); }
__device__ __forceinline__ void sts64(uint32_t a, uint32_t x, uint32_t y) { asm volatile("st.shared.v2.u32 [%0], {%1,%2};" :: "r"(a), "r"(x), "r"(y) : "memory"); }
__device__ __forceinline__ void stsf(uint32_t a, float v) { asm volatile("st.shared.f32 [%0], %1;" :: "r"(a), "f"(v) : "memory"); }
__device__ __forceinline__ void sts128(uint32_t a, uint32_t x, uint32_t y, uint32_t z, uint32_t w) { asm volatile("st.shared.v4.u32 [%0], {%1,%2,%3,%4};" :: "r"(a), "r"(x), "r"(y), "r"(z), "r"(w) : "memory"); }
__device__ __forceinline__ void sts128f(uint32_t a, float x, float y, float z, float w) { asm volatile("st.shared.v4.f32 [%0], {%1,%2,%3,%4};" :: "r"(a), "f"(x), "f"(y), "f"(z), "f"(w) : "memory"); }
__device__ __forceinline__ void ldsm4(uint32_t (&r)[4], uint32_t a) { asm volatile("ldmatrix.sync.aligned.m8n8.x4.shared.b16 {%0,%1,%2,%3}, [%4];" : "=r"(r[0]), "=r"(r[1]), "=r"(r[2]), "=r"(r[3]) : "r"(a) : "memory"); }
__device__ __forceinline__ void ldsm4t(uint32_t (&r)[4], uint32_t a) { asm volatile("ldmatrix.sync.aligned.m8n8.x4.trans.shared.b16 {%0,%1,%2,%3}, [%4];" : "=r"(r[0]), "=r"(r[1]), "=r"(r[2]), "=r"(r[3]) : "r"(a) : "memory"); }
__device__ __forceinline__ void ldsm2t(uint32_t& r0, uint32_t& r1, uint32_t a) { asm volatile("ldmatrix.sync.aligned.m8n8.x2.trans.shared.b16 {%0,%1}, [%2];" : "=r"(r0), "=r"(r1) : "r"(a) : "memory"); }
__device__ __forceinline__ void stsm4t(uint32_t a, uint32_t r0, uint32_t r1, uint32_t r2, uint32_t r3) { asm volatile("stmatrix.sync.aligned.m8n8.x4.trans.shared.b16 [%0], {%1,%2,%3,%4};" :: "r"(a), "r"(r0), "r"(r1), "r"(r2), "r"(r3) : "memory"); }
__device__ __forceinline__ void stsm4(uint32_t a, uint32_t r0, uint32_t r1, uint32_t r2, uint32_t r3) { asm volatile("stmatrix.sync.aligned.m8n8.x4.shared.b16 [%0], {%1,%2,%3,%4};" :: "r"(a), "r"(r0), "r"(r1), "r"(r2), "r"(r3) : "memory"); }
__device__ __forceinline__ void stsm2(uint32_t a, uint32_t r0, uint32_t r1) { asm volatile("stmatrix.sync.aligned.m8n8.x2.shared.b16 [%0], {%1,%2};" :: "r"(a), "r"(r0), "r"(r1) : "memory"); }
__device__ __forceinline__ void stsm2t(uint32_t a, uint32_t r0, uint32_t r1) { asm volatile("stmatrix.sync.aligned.m8n8.x2.trans.shared.b16 [%0], {%1,%2};" :: "r"(a), "r"(r0), "r"(r1) : "memory"); }
__device__ __forceinline__ uint4 ldg128(const void* p) { uint4 v; asm volatile("ld.global.nc.v4.u32 {%0,%1,%2,%3}, [%4];" : "=r"(v.x), "=r"(v.y), "=r"(v.z), "=r"(v.w) : "l"(p)); return v; }
__device__ __forceinline__ uint32_t ldg16(const void* p) { unsigned short v; asm volatile("ld.global.nc.u16 %0, [%1];" : "=h"(v) : "l"(p)); return v; }
__device__ __forceinline__ uint32_t opaque(uint32_t v) { uint32_t r; asm volatile("mov.b32 %0, %1;" : "=r"(r) : "r"(v)); return r; }
__device__ __forceinline__ void mma_f16(float (&d)[4], const uint32_t (&a)[4], uint32_t b0, uint32_t b1) {
    asm volatile("mma.sync.aligned.m16n8k16.row.col.f32.f16.f16.f32 {%0,%1,%2,%3}, {%4,%5,%6,%7}, {%8,%9}, {%0,%1,%2,%3};"
        : "+f"(d[0]), "+f"(d[1]), "+f"(d[2]), "+f"(d[3]) : "r"(a[0]), "r"(a[1]), "r"(a[2]), "r"(a[3]), "r"(b0), "r"(b1));
}
__device__ __forceinline__ void mma_f16_z(float (&d)[4], const uint32_t (&a)[4], uint32_t b0, uint32_t b1) {
    asm volatile("mma.sync.aligned.m16n8k16.row.col.f32.f16.f16.f32 {%0,%1,%2,%3}, {%4,%5,%6,%7}, {%8,%9}, {%10,%10,%10,%10};"
        : "=f"(d[0]), "=f"(d[1]), "=f"(d[2]), "=f"(d[3]) : "r"(a[0]), "r"(a[1]), "r"(a[2]), "r"(a[3]), "r"(b0), "r"(b1), "f"(0.f));
}
__device__ __forceinline__ void mma_bf16(float (&d)[4], uint32_t a0, uint32_t a1, uint32_t a2, uint32_t a3, uint32_t b0, uint32_t b1) {
    asm volatile("mma.sync.aligned.m16n8k16.row.col.f32.bf16.bf16.f32 {%0,%1,%2,%3}, {%4,%5,%6,%7}, {%8,%9}, {%0,%1,%2,%3};"
        : "+f"(d[0]), "+f"(d[1]), "+f"(d[2]), "+f"(d[3]) : "r"(a0), "r"(a1), "r"(a2), "r"(a3), "r"(b0), "r"(b1));
}
__device__ __forceinline__ void mma_bf16_k8(float (&d)[4], uint32_t a0, uint32_t a1, uint32_t b0) {
    asm volatile("mma.sync.aligned.m16n8k8.row.col.f32.bf16.bf16.f32 {%0,%1,%2,%3}, {%4,%5}, {%6}, {%0,%1,%2,%3};"
        : "+f"(d[0]), "+f"(d[1]), "+f"(d[2]), "+f"(d[3]) : "r"(a0), "r"(a1), "r"(b0));
}
__device__ __forceinline__ uint32_t pack_f16(float lo, float hi) { uint32_t r; asm("cvt.rn.f16x2.f32 %0, %1, %2;" : "=r"(r) : "f"(hi), "f"(lo)); return r; }
__device__ __forceinline__ uint32_t pack_bf16(float lo, float hi) { uint32_t r; asm("cvt.rn.bf16x2.f32 %0, %1, %2;" : "=r"(r) : "f"(hi), "f"(lo)); return r; }
__device__ __forceinline__ float bf_lo(uint32_t v) { return __uint_as_float(v << 16); }
__device__ __forceinline__ float bf_hi(uint32_t v) { return __uint_as_float(v & 0xFFFF0000u); }
__device__ __forceinline__ float bfr(float x) { return __uint_as_float(pack_bf16(0.f, x)); }
__device__ __forceinline__ uint32_t badd2(uint32_t a, uint32_t b) { uint32_t r; asm("add.rn.bf16x2 %0, %1, %2;" : "=r"(r) : "r"(a), "r"(b)); return r; }
__device__ __forceinline__ uint32_t bmul2(uint32_t a, uint32_t b) { uint32_t r; asm("mul.rn.bf16x2 %0, %1, %2;" : "=r"(r) : "r"(a), "r"(b)); return r; }
__device__ __forceinline__ uint32_t hadd2(uint32_t a, uint32_t b) { uint32_t r; asm("add.rn.f16x2 %0, %1, %2;" : "=r"(r) : "r"(a), "r"(b)); return r; }
__device__ __forceinline__ uint32_t hmul2(uint32_t a, uint32_t b) { uint32_t r; asm("mul.rn.f16x2 %0, %1, %2;" : "=r"(r) : "r"(a), "r"(b)); return r; }
__device__ __forceinline__ uint32_t hneg2(uint32_t a) { uint32_t r; asm("neg.f16x2 %0, %1;" : "=r"(r) : "r"(a)); return r; }
__device__ __forceinline__ float rcpf(float x) { float r; asm("rcp.approx.ftz.f32 %0, %1;" : "=f"(r) : "f"(x)); return r; }
__device__ __forceinline__ float sqrta(float x) { float r; asm("sqrt.approx.ftz.f32 %0, %1;" : "=f"(r) : "f"(x)); return r; }
__device__ __forceinline__ float ex2f(float x) { float r; asm("ex2.approx.ftz.f32 %0, %1;" : "=f"(r) : "f"(x)); return r; }
__device__ __forceinline__ void st_async4(uint32_t a, uint32_t x, uint32_t y, uint32_t z, uint32_t w, uint32_t mb) {
    asm volatile("st.async.shared::cluster.mbarrier::complete_tx::bytes.v4.u32 [%0], {%1,%2,%3,%4}, [%5];" :: "r"(a), "r"(x), "r"(y), "r"(z), "r"(w), "r"(mb) : "memory"); }
__device__ __forceinline__ void st_async1(uint32_t a, uint32_t x, uint32_t mb) {
    asm volatile("st.async.shared::cluster.mbarrier::complete_tx::bytes.u32 [%0], %1, [%2];" :: "r"(a), "r"(x), "r"(mb) : "memory"); }
__device__ __forceinline__ unsigned ld_rlx(const void* p) { unsigned v; asm volatile("ld.relaxed.gpu.global.u32 %0, [%1];" : "=r"(v) : "l"(p) : "memory"); return v; }
__device__ __forceinline__ unsigned ld_acq(const void* p) { unsigned v; asm volatile("ld.acquire.gpu.global.u32 %0, [%1];" : "=r"(v) : "l"(p) : "memory"); return v; }
__device__ __forceinline__ uint2 ld_rlx64(const void* p) { unsigned long long v; asm volatile("ld.relaxed.gpu.global.u64 %0, [%1];" : "=l"(v) : "l"(p) : "memory"); return make_uint2((unsigned)v, (unsigned)(v >> 32)); }
__device__ __forceinline__ void st_rlx128(void* p, uint32_t x, uint32_t y, uint32_t z, uint32_t w) {
    asm volatile("st.relaxed.gpu.global.v2.u64 [%0], {%1,%2};" :: "l"(p), "l"((unsigned long long)x | ((unsigned long long)y << 32)), "l"((unsigned long long)z | ((unsigned long long)w << 32)) : "memory"); }
__device__ __forceinline__ uint4 ld_rlx128(const void* p) { unsigned long long a, b; asm volatile("ld.relaxed.gpu.global.v2.u64 {%0,%1}, [%2];" : "=l"(a), "=l"(b) : "l"(p) : "memory"); return make_uint4((unsigned)a, (unsigned)(a >> 32), (unsigned)b, (unsigned)(b >> 32)); }
__device__ __forceinline__ void tma2d(uint32_t dst, const CUtensorMap* tm, int x, int y, uint32_t mb) {
    asm volatile("cp.async.bulk.tensor.2d.shared::cluster.global.mbarrier::complete_tx::bytes [%0], [%1, {%3, %4}], [%2];"
                 :: "r"(dst), "l"(tm), "r"(mb), "r"(x), "r"(y) : "memory");
}
__device__ __forceinline__ void cmul(float& xr, float& xi, float ar, float ai, float br, float bi) {
    const float r = fmaf(ar, br, -ai * bi), i = fmaf(ar, bi, ai * br); xr = r; xi = i;
}
__device__ __forceinline__ void csq(float& xr, float& xi, float ar, float ai) {
    const float r = fmaf(ar, ar, -ai * ai), i = (ar + ar) * ai; xr = r; xi = i;
}
__device__ __forceinline__ void cexp_s(float& zr, float& zi, float e2, float turns) {
    const float mag = ex2f(e2), r = (turns - rintf(turns)) * 6.283185307179586f;
    zr = mag * __cosf(r); zi = mag * __sinf(r);
}
__device__ __forceinline__ uint32_t ln_stats(float s1, float s2) {
    const float m = s1 * (1.f / D_);
    const float var = fmaxf(fmaf(s2, 1.f / D_, -m * m), 0.f);
    return pack_bf16(m, sqrta(bfr(bfr(var) + 1e-5f)));
}
__device__ __forceinline__ uint32_t rsplit(float rs) { const float h = bfr(rs); return pack_bf16(h, rs - h); }
__device__ __forceinline__ uint32_t norm2(uint32_t v, uint32_t mx, uint32_t hl) {
    uint32_t r;
    asm("{ .reg .b16 m, h, l, x; .reg .b32 m2, h2, l2, d, t; mov.b32 {m, x}, %2; mov.b32 {h, l}, %3; mov.b32 m2, {m, m}; mov.b32 h2, {h, h}; mov.b32 l2, {l, l};\n"
        "sub.rn.bf16x2 d, %1, m2; mul.rn.bf16x2 t, d, l2; fma.rn.bf16x2 %0, d, h2, t; }" : "=r"(r) : "r"(v), "r"(mx), "r"(hl));
    return r;
}
template <int N, int S>
__device__ __forceinline__ uint32_t rank4(uint32_t a, uint32_t key, uint32_t m1) {
    uint32_t r0 = 0, r1 = 0, r2 = 0, r3 = 0;
#pragma unroll
    for (int i = 0; i < N; i++) {
        const uint4 o = lds128(a + i * S);
        r0 += (o.x * m1 + key) >> 31; r1 += (o.y * m1 + key) >> 31; r2 += (o.z * m1 + key) >> 31; r3 += (o.w * m1 + key) >> 31;
    }
    return (r0 + r1) + (r2 + r3);
}
__device__ __forceinline__ uint32_t quad_sum(uint32_t r) {
    const uint32_t a = __shfl_xor_sync(~0u, r, 1), b = __shfl_xor_sync(~0u, r, 2), c = __shfl_xor_sync(~0u, r, 3);
    return (r + a) + b + c;
}
typedef uint32_t H2C;
__device__ __forceinline__ H2C splat(float r, float i) { return pack_f16(r, i); }
__device__ __forceinline__ void hcmul(uint32_t& xr, uint32_t& xi, uint32_t R, uint32_t I, H2C m) {
    asm("{ .reg .b16 a, b; .reg .b32 a2, b2, t; mov.b32 {a, b}, %4; mov.b32 a2, {a, a}; mov.b32 b2, {b, b};\n"
        "mul.rn.f16x2 t, %3, b2; neg.f16x2 t, t; fma.rn.f16x2 %0, %2, a2, t; mul.rn.f16x2 t, %3, a2; fma.rn.f16x2 %1, %2, b2, t; }"
        : "=&r"(xr), "=r"(xi) : "r"(R), "r"(I), "r"(m));
}
__device__ __forceinline__ void expand4(uint32_t are, uint32_t aim, uint32_t R0, uint32_t R1, uint32_t I0, uint32_t I1, H2C m4) {
    uint32_t R2, I2, R3, I3;
    hcmul(R2, I2, R0, I0, m4); hcmul(R3, I3, R1, I1, m4);
    sts128(are, R0, R1, R2, R3);
    sts128(aim, I0, I1, I2, I3);
}
__device__ __forceinline__ void expand8(uint32_t are, uint32_t aim, float sr, float si, float m1r, float m1i, float m2r, float m2i, H2C m4) {
    float r1, i1, r2, i2, r3, i3;
    cmul(r1, i1, sr, si, m1r, m1i); cmul(r2, i2, sr, si, m2r, m2i); cmul(r3, i3, r1, i1, m2r, m2i);
    expand4(are, aim, pack_f16(sr, r1), pack_f16(r2, r3), pack_f16(si, i1), pack_f16(i2, i3), m4);
}
__device__ __forceinline__ uint32_t comb4(uint32_t a, uint32_t b, uint32_t c, uint32_t d, uint32_t r01, uint32_t r23) {
    uint32_t x;
    asm("{ .reg .b16 h0, h1, h2, h3; .reg .b32 m0, m1, m2, m3, u, v; mov.b32 {h0, h1}, %5; mov.b32 {h2, h3}, %6;\n"
        "mov.b32 m0, {h0, h0}; mov.b32 m1, {h1, h1}; mov.b32 m2, {h2, h2}; mov.b32 m3, {h3, h3};\n"
        "mul.rn.f16x2 u, %2, m1; fma.rn.f16x2 u, %1, m0, u; mul.rn.f16x2 v, %4, m3; fma.rn.f16x2 v, %3, m2, v; add.rn.f16x2 %0, u, v; }"
        : "=r"(x) : "r"(a), "r"(b), "r"(c), "r"(d), "r"(r01), "r"(r23));
    return x;
}
__device__ __forceinline__ void put16(uint32_t a, uint32_t v) { sts16(a, v); sts16(a + 6, v); }

struct Params {
    const unsigned short *logdt, *dskip, *prm6[6], *x, *wr;
    __nv_bfloat16* out;
    Scratch* gs;
    unsigned zero;
};
__device__ __forceinline__ uint32_t tslot(uint32_t t) { return (t & 7) * 32 + ((t >> 4) & 24) + ((t >> 8) & 6) + ((t >> 6) & 1); }
#define CP(x) ((x) | zero)
#define ZF(x) ((x) & zero)
#define PIN(x) asm volatile("or.b32 %0, %0, %1;" : "+r"(x) : "r"(zero))
__device__ __forceinline__ void wgmma32(float (&d)[4][4], const uint32_t (&a)[4], unsigned long long ds) {
    asm volatile("wgmma.mma_async.sync.aligned.m64n32k16.f32.f16.f16 {%0,%1,%2,%3,%4,%5,%6,%7,%8,%9,%10,%11,%12,%13,%14,%15}, {%16,%17,%18,%19}, %20, 1, 1, 1, 0;"
        : "+f"(d[0][0]), "+f"(d[0][1]), "+f"(d[0][2]), "+f"(d[0][3]), "+f"(d[1][0]), "+f"(d[1][1]), "+f"(d[1][2]), "+f"(d[1][3]),
          "+f"(d[2][0]), "+f"(d[2][1]), "+f"(d[2][2]), "+f"(d[2][3]), "+f"(d[3][0]), "+f"(d[3][1]), "+f"(d[3][2]), "+f"(d[3][3])
        : "r"(a[0]), "r"(a[1]), "r"(a[2]), "r"(a[3]), "l"(ds));
}

__device__ __forceinline__ void finish(const Params& prm, uint32_t fo, uint32_t oo, const float (&v)[3], float cnt) {
    float x, y, z, w;
    asm volatile("atom.relaxed.gpu.global.add.v4.f32 {%0,%1,%2,%3}, [%4], {%5,%6,%7,%8};" : "=f"(x), "=f"(y), "=f"(z), "=f"(w)
                 : "l"((char*)prm.gs->fin + fo), "f"(v[0]), "f"(v[1]), "f"(v[2]), "f"(cnt) : "memory");
    if (w + cnt == 3.f * (NCL + 1)) {
        __nv_bfloat16* op = (__nv_bfloat16*)((char*)prm.out + oo);
        op[0] = __float2bfloat16(x + v[0]); op[1] = __float2bfloat16(y + v[1]); op[2] = __float2bfloat16(z + v[2]);
    }
}

__global__ void __cluster_dims__(CS, 1, 1) __launch_bounds__(NTHR, 1)
fused_kernel(const __grid_constant__ Params prm, const __grid_constant__ CUtensorMap tmG, const __grid_constant__ CUtensorMap tmU,
             const __grid_constant__ CUtensorMap tmD, const __grid_constant__ CUtensorMap tmO, const __grid_constant__ CUtensorMap tmX, const __grid_constant__ CUtensorMap tmH)
{
    extern __shared__ __align__(1024) unsigned char smem[];
    const int tid = threadIdx.x, lane = tid & 31, warp = __shfl_sync(~0u, tid >> 5, 0);
    const int c = blockIdx.x >> 3, q = blockIdx.x & 7;
    const int nslot = (c < NCL - 1) ? 5 : 2;
    const int d0 = 40 * c;
    const uint32_t sb = opaque((uint32_t)__cvta_generic_to_shared(smem));
    const uint32_t mb = sb + SM_MB;
    Scratch& g_s = *prm.gs;
    const unsigned& zero = prm.zero;
    const uint32_t dch2 = min(d0 + q + ((tid >> 4) & ~7), D_ - 1) * 2;
    uint32_t pv[6], pLdt;
    const uint32_t pofs = opaque(dch2 * 128 + (tid & 127) * 2);
    pLdt = ldg16((const char*)prm.logdt + dch2);
#pragma unroll
    for (int i = 0; i < 2; i++) pv[i] = ldg16((const char*)prm.prm6[i] + pofs);
    STAMP(0);

    if (warp >= 20) {
        unsigned epoch = 0;
        if (warp == 20) {
            if (lane == 0) {
#pragma unroll
                for (int i = 0; i < 13; i++)
                    asm volatile("mbarrier.init.shared::cta.b64 [%0], %1;" :: "r"(mb + i * 8), "r"((i == MB_R || i < 2) ? 2 : i < 5 ? (nslot + 1) / 3 : i == MB_Y ? 1 + 4 * nslot : 1) : "memory");
                asm volatile("fence.mbarrier_init.release.cluster;" ::: "memory");
                arm(mb + MB_W1 * 8, 92160); arm(mb + MB_W2 * 8, nslot * 9216); arm(mb + MB_KEY * 8, 256); arm(mb + MB_GU * 8, nslot * 1024); arm(mb + MB_T * 8, 576 * XW);
                const int bytes = max(min(18, L_ - 18 * (int)blockIdx.x), 1) * (D_ * 2);
                arm(mb + MB_R * 8, bytes);
            }
            __syncwarp();
        } else if (warp == 22) {
            epoch = ld_rlx(&g_s.epoch);
            if (lane < 18 ? 18 * c + lane < 256 : lane < 31) (lane < 18 ? &g_s.acc[256 * q + 18 * c] : &g_s.fin[13 * (int)blockIdx.x - 18])[lane] = make_float4(0.f, 0.f, 0.f, 0.f);
        } else if (warp == 23 && lane == 0) asm volatile("prefetch.tensormap [%0];" :: "l"(&tmX) : "memory");
        asm volatile("barrier.cluster.arrive.relaxed.aligned;" ::: "memory");
        bar_sync(12, NTHR);
        uint4 wv = make_uint4(0, 0, 0, 0), wv2, wv3;
        if (warp == 22) {
            if (lane == 0) { sts32(sb + SM_SC + 28, epoch); asm volatile("mbarrier.arrive.shared::cta.b64 _, [%0];" :: "r"(mb + MB_R * 8) : "memory"); }
            epoch++;
            asm volatile("fence.acq_rel.gpu;" ::: "memory");
            __syncwarp();
            if (lane == 0) asm volatile("red.relaxed.gpu.global.add.u32 [%0], 1;" :: "l"(&g_s.zcnt) : "memory");
            STAMP(1);
            wv2 = ldg128((const uint4*)prm.wr + lane); wv3 = ldg128((const uint4*)prm.wr + 32 + lane);
            if (lane < 8) wv = ldg128((const uint4*)prm.wr + 64 + lane);
            if (lane < 5) {
                uint4 v = make_uint4(0, 0, 0, 0);
                if (lane < nslot) v = ldg128((const uint4*)(prm.wr + d0) + lane);
                sts128(sb + SM_DW + lane * 16, v.x, v.y, v.z, v.w);
            }
            __syncwarp();
            if (lane < 5) asm volatile("mbarrier.arrive.shared::cta.b64 _, [%0];" :: "r"(mb + (MB_X + lane) * 8) : "memory");
        }
        if (warp == 21) {
            if (lane == 0) { asm volatile("prefetch.tensormap [%0];" :: "l"(&tmG) : "memory"); asm volatile("prefetch.tensormap [%0];" :: "l"(&tmU) : "memory"); asm volatile("prefetch.tensormap [%0];" :: "l"(&tmD) : "memory"); }
            __syncwarp();
            const float dsk = bf_lo(ldg16(prm.dskip + min(d0 + 2 * (lane & 28) + q, D_ - 1)));
            bar_sync(0, 672);
            {
                const uint2 m = lds64(sb + SM_KG + min(lane, 19) * 8);
                unsigned Em = max(m.x, __shfl_xor_sync(~0u, m.x, 1));
                Em = max(Em, __shfl_xor_sync(~0u, Em, 2));
                Em = max(Em, min(__float_as_uint(fabsf(dsk) * (1.f / 8192.f)) >> 23, 253u));
                const float f = __uint_as_float(max((int)(127 + m.x - Em), 0) << 23);
                float s0 = (float)(int)m.y * f;
                s0 += __shfl_xor_sync(~0u, s0, 1); s0 += __shfl_xor_sync(~0u, s0, 2);
                if (lane < 20) {
                    sts16(sb + SM_RK + lane * 2, pack_f16(f, 0.f));
                    sts32(sb + SM_SC + (lane & 28), Em * 0x00800080u);
                    put16(sb + SM_PN + (lane >> 2) * PN_SZ, pack_f16(s0 * (1.f / 16777216.f) + dsk * __uint_as_float((254u - Em) << 23), 0.f));
                }
                __syncwarp();
            }
            bar_sync(15, 672);
            asm volatile("fence.proxy.async.shared::cta;" ::: "memory");
#pragma unroll 1
            for (int i = 0; i < 24; i++) {
                if (lane == 0) tma2d(sb + SM_WG + i * 3840, i < 12 ? &tmG : &tmU, 320 * c + 8 * nslot * q, 48 * (i < 12 ? i : i - 12), mb + MB_W1 * 8);
            }
            STAMP(1);
        } else {
        if (warp == 20) {
            if (lane == 0) {
                asm volatile("cp.async.bulk.shared::cluster.global.mbarrier::complete_tx::bytes [%0], [%1], %2, [%3];"
                             :: "r"(sb + SM_ROW), "l"(prm.x + min(18 * (int)blockIdx.x, L_ - 1) * D_), "r"(max(min(18, L_ - 18 * (int)blockIdx.x), 1) * (D_ * 2)), "r"(mb + MB_R * 8) : "memory");
            }
            __syncwarp();
            mbar_wait(mb + MB_R * 8);
            if (lane == 0) {
                asm volatile("cp.async.bulk.tensor.5d.shared::cluster.global.mbarrier::complete_tx::bytes [%0], [%1, {%3, %4, %5, %5, %5}], [%2];"
                             :: "r"(sb + SM_XTL), "l"(&tmX), "r"(mb + MB_T * 8), "r"(d0 & ~15), "r"(8 * q), "r"(0) : "memory");
            }
            STAMP(6);
        }
        {
            const int idx = lane * 3 + max(warp - 21, 0), sl = nslot - 1 - (idx >> 3), pe = (idx + q + 1) & 7;
            const uint32_t rb_ = mapa(sb, pe);
            uint32_t cd = rb_ + SM_U + 128 + q * UP + sl * US, cs = sb + SM_XT + 128 + (q & 3) * 16 + pe * YP + sl * YS, cm = rb_ + SM_MB + (MB_X + sl) * 8;
            int act = sl < 0 ? 0 : pe == q ? -1 : 1;
            PIN(cd); PIN(cs); PIN(cm); PIN(act);
            asm volatile("barrier.cluster.wait.aligned;" ::: "memory");
            mbar_wait(mb + MB_R * 8);
            bar_sync(13, 608);
            asm volatile("fence.proxy.async.shared::cta;" ::: "memory");
            if (act < 0) arm(cm, 7 * 512);
            __syncwarp();
            if (act > 0)
                asm volatile("cp.async.bulk.shared::cluster.shared::cta.mbarrier::complete_tx::bytes [%0], [%1], 512, [%2];" :: "r"(cd), "r"(cs), "r"(cm) : "memory");
        }
        STAMP(1);
        if (warp == 20 && lane == 0) { asm volatile("prefetch.tensormap [%0];" :: "l"(&tmO) : "memory"); asm volatile("prefetch.tensormap [%0];" :: "l"(&tmH) : "memory"); }
        if (warp == 22) {
            __syncwarp();
            mbar_wait(mb + (MB_X + 1) * 8);
            const uint32_t old = (epoch & 1) ? 0u : 0x40004000u;
#pragma unroll
            for (int t = 0; t < 2; t++)
                if ((lane & 7) < 6) g_s.cand[((q * 8 + 4 * t + (lane >> 3)) * NCL + c) * 6 + (lane & 7)] = make_uint4(old, old, old, old);
            float a[4] = {0.f, 0.f, 0.f, 0.f};
            const uint32_t one = 0x3F803F80u;
            mma_bf16(a, one, one, one, one, wv.x, wv.y);  mma_bf16(a, one, one, one, one, wv.z, wv.w);
            mma_bf16(a, one, one, one, one, wv2.x, wv2.y); mma_bf16(a, one, one, one, one, wv2.z, wv2.w);
            mma_bf16(a, one, one, one, one, wv3.x, wv3.y); mma_bf16(a, one, one, one, one, wv3.z, wv3.w);
            float s = a[0] + a[1];
            s += __shfl_xor_sync(~0u, s, 1); s += __shfl_xor_sync(~0u, s, 2);
            stsf(sb + SM_SC + 24, s);
            __syncwarp();
            if (lane == 0) {
                int n = 0;
                while ((int)(ld_acq(&g_s.zcnt) - epoch * NCTA) < 0 && ++n < SPIN_LIMIT) __nanosleep(200);
                arm(mb + MB_Y * 8, 8 * 512 * nslot);
                if (blockIdx.x == 0) g_s.epoch = epoch;
            }
            STAMP(2);
        }
        if (warp == 23) {
#pragma unroll 1
            for (int kk = nslot - 1; kk >= 0; kk--) {
                __syncwarp();
                bar_sync(6 + kk, 160);
                if (kk < 2) mbar_wait(mb + MB_W1 * 8);
                if (lane == 0) { asm volatile("fence.proxy.async.shared::cta;" ::: "memory"); tma2d(sb + SM_FAR + kk * FAR_SZ, &tmD, 72 * q, 320 * c + 64 * kk, mb + MB_W2 * 8); }
            }
        }
        }
        __syncwarp();
        if (warp == 20) {
            bar_sync(11, 672);
            asm volatile("fence.proxy.async.shared::cta;" ::: "memory");
            bar_sync(14, 768);
            if (elect()) {
                asm volatile("cp.async.bulk.tensor.5d.global.shared::cta.bulk_group [%0, {%2, %4, %4, %4, %3}], [%1];" :: "l"(&tmH), "r"(sb + SM_XT + 16384), "r"(d0 + ((c & 1) ? 0 : 32)), "r"(8 * q), "r"(0) : "memory");
                asm volatile("cp.async.bulk.tensor.5d.global.shared::cta.bulk_group [%0, {%2, %4, %4, %4, %3}], [%1];" :: "l"(&tmO), "r"(sb + SM_XT), "r"(d0 + (c & 1) * 8), "r"(8 * q), "r"(0) : "memory");
                asm volatile("cp.async.bulk.commit_group;" ::: "memory");
            }
        } else bar_sync(14, 768);
        __syncwarp();
        const uint32_t ft = (tid >> 4) & 7, fj = d0 / 3 + (lane & 15), tok = ~lds32(sb + SM_SEL + ft * 8) & 2047;
        float v[3], cnt = 0.f;
#pragma unroll
        for (int i = 0; i < 3; i++) {
            const uint32_t cl = 3 * fj + i - d0, cf = cl - (c & 1) * 8;
            const bool ok = cl < 8 * nslot && ((tok >> 3) & 7) == q;
            const uint32_t u = lds16(sb + SM_XT + (cf < 32 ? tslot(tok) * 64 + cf * 2 : 16384 + tslot(tok) * 16 + (cl & 7) * 2));
            v[i] = ok ? __uint_as_float(u << 16) : 0.f;
            if (ok) cnt += 1.f;
        }
        if (warp == 20 && elect()) {
            asm volatile("cp.async.bulk.wait_group 0;" ::: "memory");
            asm volatile("fence.proxy.async.global;" ::: "memory");
            asm volatile("mbarrier.arrive.shared::cta.b64 _, [%0];" :: "r"(mb + MB_OUT * 8) : "memory");
        }
        __syncwarp();
        mbar_wait(mb + MB_OUT * 8);
        STAMP(5);
        if (cnt != 0.f) finish(prm, (ft * 192 + fj) * 16, (tok * D_ + 3 * fj) * 2, v, cnt);
        return;
    }

    const int g = lane >> 2, cq = lane & 3;
    const int k = warp >> 2, wq = warp & 3;
    const int trow = 18 * blockIdx.x + warp;
    const bool rowact = warp < 18 && trow < L_;
#pragma unroll
    for (int i = 2; i < 6; i++) pv[i] = ldg16((const char*)prm.prm6[i] + pofs);
    const int tn = 16 * (warp & 15) + g;
    uint32_t xa[5], xb[5];
    asm volatile("barrier.cluster.arrive.relaxed.aligned;" ::: "memory");
    char* const st1p = (char*)g_s.st1 + opaque(((((trow >> 3) & 7) * 256 + ((trow >> 6) & 31) * 8 + (trow & 7)) * 8 + lane) * 4);
    const bool pub = rowact && (lane & 0x1B) == 0;
    if (pub) st_rlx128(st1p, 0, 0, 0, 0);
    {
        const uint32_t za = sb + SM_P + tid * 16;
        sts128(za, 0, 0, 0, 0);
        if (tid < (SM_MISC - SM_P) / 16 - 640) sts128(za + 10240, 0, 0, 0, 0);
        sts128(sb + SM_U + ((tid >> 3) & 7) * UP + k * US + (lane & 7) * 16, 0, 0, 0, 0);
    }
    bar_sync(12, NTHR);
    const uint32_t dep = lds32(sb + SM_P);
#define PV(x) __uint_as_float(__byte_perm(dep, x, 0x5410))
    STAMP(1);
    const uint32_t fb = sb + SM_FAR + k * FAR_SZ;
    const uint32_t pn = sb + SM_PN + k * PN_SZ, pf = sb + SM_PF + k * PF_SZ;
    unsigned epoch, t258;
    {
        const uint32_t kb = fb + wq * 3072;
        const uint32_t kl = kb + lane * 16;
        uint32_t Af[4][4];
        float sr, si, z1r, z1i, z2r, z2i, z4r, z4i, hr, hi_;
        {
            const float dt = bfr(ex2f(PV(pLdt) * 1.4426950408889634f));
            const float e2 = dt * PV(pv[0]) * 1.4426950408889634f, an = dt * PV(pv[1]);
            float ar, ai, br, bi, cr, ci, dr, di;
            { const float m = ex2f(e2 * 8.f); ar = m * __cosf(an * 8.f); ai = m * __sinf(an * 8.f); }
            csq(br, bi, ar, ai); csq(cr, ci, br, bi); csq(dr, di, cr, ci);
            const H2C m4 = splat(cr, ci);
            {
                float r3, i3;
                cmul(r3, i3, ar, ai, br, bi);
                expand4(kl, kl + 1024, pack_f16(1.f, ar), pack_f16(br, r3), pack_f16(0.f, ai), pack_f16(bi, i3), m4);
            }
            expand8(kl + 512, kl + 1536, dr, di, ar, ai, br, bi, m4);
            { const float m = ex2f(e2); z1r = m * __cosf(an); z1i = -m * __sinf(an); }
            cexp_s(hr, hi_, e2 * 128.f, an * (-128.f * 0.15915494309189535f));
            csq(z2r, z2i, z1r, z1i); csq(z4r, z4i, z2r, z2i);
            const uint32_t dep2 = lds32(sb + SM_P + 4);
#define PW(x) __uint_as_float(__byte_perm(dep2, x, 0x5410))
            cmul(sr, si, PW(pv[4]), PW(pv[5]), dt * PW(pv[2]), dt * PW(pv[3]));
            const unsigned E = min(max(__reduce_max_sync(~0u, __float_as_uint(fmaxf(fabsf(sr), fabsf(si)))) >> 23, 1u), 253u);
            const float sc = __uint_as_float((254u - E) << 23);
            sr *= sc; si *= -sc;
            sts64(sb + SM_KG + warp * 8, E, __reduce_add_sync(~0u, __float2int_rn(sr * 16777216.f)));
        }
        __syncwarp();
#pragma unroll
        for (int ks = 0; ks < 4; ks++) ldsm4t(Af[ks], kb + (lane >> 3) * 512 + (lane & 7) * 16 + ks * 128);
        STAMP(2);
        const uint32_t la = kb + ((lane >> 3) & 1) * 512 + (lane >> 4) * 128 + (lane & 7) * 16;
        uint32_t b0[4], b1[4], b2[4], b3[4];
        auto ln1 = [&]() {
        mbar_wait(mb + MB_R * 8);
        epoch = lds32(sb + SM_SC + 28) + 1;
        {
            const uint32_t ra = sb + SM_ROW + warp * (D_ * 2);
            const uint4 r0 = lds128(ra + lane * 16), r1 = lds128(ra + 512 + lane * 16);
            const uint32_t rx[9] = {r0.x, r0.y, r0.z, r0.w, r1.x, r1.y, r1.z, r1.w, lds32(ra + 1024 + lane * 4)};
            float a0 = bf_lo(rx[0]), a1 = bf_hi(rx[0]), c0 = a0 * a0, c1 = a1 * a1;
#pragma unroll
            for (int i = 1; i < 9; i++) { const float l = bf_lo(rx[i]), h = bf_hi(rx[i]); a0 += l; a1 += h; c0 = fmaf(l, l, c0); c1 = fmaf(h, h, c1); }
            a0 += a1; c0 += c1;
            float s1 = ((lane & 1) ? c0 : a0) + __shfl_xor_sync(~0u, (lane & 1) ? a0 : c0, 1);
#pragma unroll
            for (int o = 2; o < 32; o <<= 1) s1 += __shfl_xor_sync(~0u, s1, o);
            const float s2 = __shfl_xor_sync(~0u, s1, 1);
            const uint32_t ms = ln_stats(s1, s2);
            const uint32_t p0 = __byte_perm(ms, epoch | 0x8000u, 0x5410), p1 = rsplit(rcpf(bf_hi(ms)));
            if (pub) st_rlx128(st1p, p0, p1, p0, p1);
        }
        mbar_wait(mb + MB_R * 8);
        STAMP(1);
        };
        const uint4* sp = &g_s.st1[(256 * q + tn) * 2];
        uint2 sa, sc;
        auto poll = [&]() { sa = ld_rlx64(sp); sc = ld_rlx64(sp + 16); };
        auto norm = [&]() {
        STAMP(3);
        if (warp < 16) {
            uint32_t va[5], vc[5];
            poll();
            mbar_wait(mb + MB_T * 8);
            {
                const uint32_t xt = sb + SM_XTL + (c & 1) * 16 + (36 * (warp & 7) + 9 * (warp >> 3) + g) * (2 * XW);
                uint4 a4 = lds128(xt + cq * 16), b4 = lds128(xt + cq * 16 + 36 * XW);
                va[0] = a4.x; va[1] = a4.y; va[2] = a4.z; va[3] = a4.w; va[4] = lds32(xt + 64 + cq * 4);
                vc[0] = b4.x; vc[1] = b4.y; vc[2] = b4.z; vc[3] = b4.w; vc[4] = lds32(xt + (64 + 36 * XW) + cq * 4);
            }
            const int d4 = 2 * (lane >> 3) + (lane & 1), d1_ = lane & 7;
            const uint32_t own = SM_U + 128 + q * (UP - YP), oth = SM_XT + 128 + (q & 3) * 16;
            uint32_t a4 = sb + warp * 32 + d4 * YP + (d4 == q ? own : oth) + ((lane & 7) >> 1) * YS;
            uint32_t a1 = sb + warp * 32 + d1_ * YP + (d1_ == q ? own : oth) + 4 * YS + (lane & 8) * 2;
            PIN(a4); PIN(a1);
            uint32_t tag = __byte_perm(epoch | 0x8000u, 0, 0x1010);
            PIN(tag);
            mbar_wait(mb + MB_T * 8);
            int n = 0;
            while (__byte_perm(sa.x, sc.x, 0x7632) != tag && ++n < SPIN_LIMIT) poll();
            STAMP(4);
#pragma unroll
            for (int i = 0; i < 5; i++) {
                va[i] = norm2(va[i], sa.x, sa.y); va[i] = pack_f16(bf_lo(va[i]), bf_hi(va[i]));
                vc[i] = norm2(vc[i], sc.x, sc.y); vc[i] = pack_f16(bf_lo(vc[i]), bf_hi(vc[i]));
            }
            stsm4t(a4, va[0], va[1], va[2], va[3]); stsm4t(a4 + 16, vc[0], vc[1], vc[2], vc[3]); stsm2t(a1, va[4], vc[4]);
            bar_arrive(13, 608);
            {
            const uint32_t xh = sb + SM_XTL + (c & 1) * 16 + (9 * __byte_perm(0x12100200, 0x13110301, g) + 72 * (warp & 1) + (warp >> 1)) * (2 * XW);
            const uint4 c4 = lds128(xh + cq * 16), d4_ = lds128(xh + cq * 16 + 72 * XW);
            xa[0] = c4.x; xa[1] = c4.y; xa[2] = c4.z; xa[3] = c4.w; xa[4] = lds32(xh + 64 + cq * 4);
            xb[0] = d4_.x; xb[1] = d4_.y; xb[2] = d4_.z; xb[3] = d4_.w; xb[4] = lds32(xh + (64 + 72 * XW) + cq * 4);
            }
        }
        STAMP(5);
        __syncwarp();
        bar_sync(15, 672);
        Af[0][0] |= lds32(sb + SM_P);
        };
        cmul(sr, si, sr, si, z1r, z1i);
        {
            const H2C h4 = splat(z4r, z4i);
            expand8(kl, kl + 512, sr, si, z1r, z1i, z2r, z2i, h4);
            cmul(sr, si, sr, si, hr, hi_);
            expand8(kl + 1024, kl + 1536, sr, si, z1r, z1i, z2r, z2i, h4);
        }
        __syncwarp();
        ldsm4t(b0, la); ldsm4t(b1, la + 256); ldsm4t(b2, la + 1024); ldsm4t(b3, la + 1280);
        cmul(z1r, z1i, z1r, z1i, hr, hi_);
        cmul(sr, si, sr, si, z1r, z1i);
        expand8(kl, kl + 512, sr, si, z2r, z2i, z4r, z4i, splat(hr, hi_));
        asm volatile("barrier.cluster.wait.aligned;" ::: "memory");
        bar_arrive(0, 672);
        ln1();
        csq(z1r, z1i, z1r, z1i);
        cmul(sr, si, sr, si, z1r, z1i);
        csq(z2r, z2i, hr, hi_);
        expand8(kl + 1024, kl + 1536, sr, si, z4r, z4i, hr, hi_, splat(z2r, z2i));
        csq(z1r, z1i, z1r, z1i);
        cmul(sr, si, sr, si, z1r, z1i);
        csq(z4r, z4i, z2r, z2i);
        expand8(kl + 2048, kl + 2560, sr, si, hr, hi_, z2r, z2i, splat(z4r, z4i));
        norm();
        {
            uint32_t c0[4], c1[4], c2[4], c3[4], e0[4], e1[4];
            float t[6][4];
            ldsm4t(c0, la); ldsm4t(c2, la + 1024);
            mma_f16_z(t[0], Af[0], b0[0], b0[1]);
            const uint32_t lb = la | (__float_as_uint(t[0][0]) & zero);
            mma_f16_z(t[1], Af[0], b2[0], b2[1]); mma_f16_z(t[2], Af[0], c0[0], c0[1]); mma_f16_z(t[3], Af[0], c2[0], c2[1]);
            ldsm4t(e0, lb + 2048); ldsm4t(c1, lb + 256); ldsm4t(c3, lb + 1280); ldsm4t(e1, lb + 2304);
            mma_f16(t[0], Af[1], b0[2], b0[3]); mma_f16(t[1], Af[1], b2[2], b2[3]); mma_f16(t[2], Af[1], c0[2], c0[3]); mma_f16(t[3], Af[1], c2[2], c2[3]);
            mma_f16(t[0], Af[2], b1[0], b1[1]); mma_f16(t[1], Af[2], b3[0], b3[1]);
            mma_f16_z(t[4], Af[0], e0[0], e0[1]); mma_f16_z(t[5], Af[1], e0[2], e0[3]);
            mma_f16(t[2], Af[2], c1[0], c1[1]); mma_f16(t[3], Af[2], c3[0], c3[1]);
            mma_f16(t[4], Af[2], e1[0], e1[1]); mma_f16(t[5], Af[3], e1[2], e1[3]);
            mma_f16(t[0], Af[3], b1[2], b1[3]); mma_f16(t[1], Af[3], b3[2], b3[3]); mma_f16(t[2], Af[3], c1[2], c1[3]); mma_f16(t[3], Af[3], c3[2], c3[3]);
#pragma unroll
            for (int i = 0; i < 4; i++) t[4][i] += t[5][i];
            stsm4(kl + 1024, pack_f16(t[0][0], t[0][1]), pack_f16(t[0][2], t[0][3]), pack_f16(t[1][0], t[1][1]), pack_f16(t[1][2], t[1][3]));
            stsm2(kl + 1536, pack_f16(t[2][0], t[2][1]), pack_f16(t[2][2], t[2][3]));
            sts64(kb + lane * 8 + 1792, pack_f16(t[3][1], t[3][0]), pack_f16(t[3][3], t[3][2]));
            sts64(kb + lane * 8 + 2048, pack_f16(t[4][1], t[4][0]), pack_f16(t[4][3], t[4][2]));
        }
        bar_sync(1 + k, 128);
        const uint2 rr = lds64(opaque(sb + SM_RK + k * 8));
        const int tq = (wq + k + 2) & 3;
        const uint32_t ra = lane * 8 + opaque(fb + (tq == 1 ? 2048 : tq * 256 + 1024));
        auto comb = [&](uint32_t a, uint32_t& x, uint32_t& y) {
            const uint2 p0 = lds64(a), p1 = lds64(a + 3072), p2 = lds64(a + 6144), p3 = lds64(a + 9216);
            x = comb4(p0.x, p1.x, p2.x, p3.x, rr.x, rr.y); y = comb4(p0.y, p1.y, p2.y, p3.y, rr.x, rr.y);
        };
        uint32_t w0, w1;
        comb(ra, w0, w1);
        const bool last = lane == 31;
        if (tq == 0) {
            uint32_t v0, v1;
            comb(ra + 256, v0, v1);
            const uint32_t n0 = __shfl_sync(~0u, lane ? w0 : v0, lane + 1);
            uint32_t n1 = __shfl_sync(~0u, v0, lane + 1);
            if (last) n1 = v1 >> 16;
            sts128(pn + 12 + lane * 16, __byte_perm(w1, w0, 0x7610), __byte_perm(w1, 0, 0x1032), __byte_perm(n0, w1, 0x7610), __byte_perm(n0, 0, 0x1032));
            sts128(pn + 524 + lane * 16, __byte_perm(v1, v0, 0x7610), __byte_perm(v1, 0, 0x1032), __byte_perm(n1, v1, 0x7610), __byte_perm(n1, 0, 0x1032));
            if (lane == 0) { sts16(pn + 4, w0); sts32(pn + 8, __byte_perm(w0, 0, 0x1032)); }
        } else if (tq == 1) {
            const uint32_t ph = pf + P_H7 + (g & 1) * (2 * P_HS) + cq * 64 + (g >> 1) * 4 + (cq & 2) * 16, sw = (cq & 2) ? 0x3210 : 0x1032;
            w0 = __byte_perm(hmul2(w0, 0x18001800u), 0, sw); w1 = __byte_perm(hmul2(w1, 0x18001800u), 0, sw);
            const uint32_t pi = ph + 32 - (cq & 2) * 32;
            put16(ph, w0); put16(pi, w0 >> 16); put16(ph + 16, w1); put16(pi + 16, w1 >> 16);
        } else if (tq == 2) {
            uint32_t n = __shfl_sync(~0u, w0, lane == 30 ? 1 : lane + 2);
            if (last) { put16(pf, hmul2(w1, 0x18001800u) >> 16); w1 = hadd2(w1, hneg2(__byte_perm(w1, 0, 0x3232))); n = 0; }
            const bool od = lane & 1;
            const uint32_t pa = pn + 1036 + (lane >> 1) * 32 + (od ? 528 : 0), pb = pa + (od ? -16 : 16);
            const uint32_t u0 = od ? w1 : w0, x0 = od ? n : w1, u1 = od ? w0 : w1, x1 = od ? w1 : n;
            const uint32_t b0 = __byte_perm(u0, 0, 0x3232), b1 = __byte_perm(u1, 0, 0x3232);
            sts128(pa, __byte_perm(u0, 0, 0x1032), b0, b0, __byte_perm(x0, u0, 0x7610));
            sts128(pb, __byte_perm(u1, 0, 0x1032), b1, b1, __byte_perm(x1, u1, 0x7610));
        } else {
            const uint32_t pa = pf + ((g & 1) ? 3 * P_GS : P_GS) + cq * 32 + (g >> 1) * 4;
            const uint32_t pb = pa + ((g & 1) ? 4 - 3 * P_GS : P_GS);
            w0 = hmul2(w0, 0x18001800u); w1 = hmul2(w1, 0x18001800u);
            put16(pa, w0 >> 16); put16(pb, w0); put16(pa + 16, w1 >> 16); put16(pb + 16, w1);
            if (last) put16(pf + P_H7 + P_HS, w1);
        }
        bar_sync(1 + k, 128);
        t258 = w0;
    }
    STAMP(6);

    mbar_wait(mb + (MB_X + k) * 8);
    STAMP(7);
    if (k < nslot) {
        const int role = (wq + k) & 3;
        const uint32_t ub = sb + SM_U + k * US + 128;
        const uint32_t l16 = lane * 16, tz = (lane & 28) - 8 * cq, tz4 = tz * 4;
        if (role) {
            const uint32_t al = cq * (2 * UP + 32) + tz4, au = opaque(ub + (3 - role) * 128), a1 = al + au, a0 = (cq ? al : al + (8 * UP - 16)) + au - 2 * UP;
            const uint4 q0 = lds128(a0), q1 = lds128(a0 + UP), q2 = lds128(a1), q3 = lds128(a1 + UP);
            const uint32_t U[16] = {q0.x, q0.y, q0.z, q0.w, q1.x, q1.y, q1.z, q1.w, q2.x, q2.y, q2.z, q2.w, q3.x, q3.y, q3.z, q3.w};
            uint32_t V[14], Q[14], R4[12], T[8];
#pragma unroll
            for (int i = 2; i < 14; i++) { V[i] = __byte_perm(U[i], U[i + 1], 0x5432); Q[i] = hadd2(U[i], V[i]); }
            const uint32_t rb = l16 + opaque(fb + (3 - role) * 512);
#pragma unroll
            for (int i = 0; i < 8; i++) T[i] = hadd2(V[5 + i], Q[6 + i]);
            sts128(rb + F_E3, T[0], T[1], T[2], T[3]); sts128(rb + F_O3 + 16, T[4], T[5], T[6], T[7]);
            asm volatile("{ .reg .pred p; setp.ne.u32 p, %10, 1; @p st.shared.v4.u32 [%0], {%2,%3,%4,%5}; @p st.shared.v4.u32 [%1], {%6,%7,%8,%9}; }"
                         :: "r"(rb + F_E2), "r"(rb + F_O2), "r"(Q[6]), "r"(Q[7]), "r"(Q[8]), "r"(Q[9]), "r"(Q[10]), "r"(Q[11]), "r"(Q[12]), "r"(Q[13]), "r"(role) : "memory");
#pragma unroll
            for (int i = 2; i < 12; i++) R4[i] = hadd2(Q[i], Q[i + 1]);
#pragma unroll
            for (int i = 0; i < 8; i++) T[i] = hadd2(R4[3 + i], U[5 + i]);
            sts128(rb + F_O5, T[0], T[1], T[2], T[3]); sts128(rb + F_E5, T[4], T[5], T[6], T[7]);
            if (role != 1) {
                uint32_t S[8];
#pragma unroll
                for (int i = 0; i < 8; i++) S[i] = hadd2(R4[2 + i], i < 7 ? T[i + 1] : hadd2(R4[11], U[13]));
                sts128(rb + F_O9, S[0], S[1], S[2], S[3]); sts128(rb + F_E9 + 16, S[4], S[5], S[6], S[7]);
#pragma unroll
                for (int i = 0; i < 8; i++) S[i] = hadd2(T[i], hadd2(V[2 + i], V[5 + i]));
                sts128(rb + F_E7, S[0], S[1], S[2], S[3]); sts128(rb + F_O7, S[4], S[5], S[6], S[7]);
            }
        } else if (lane == 0) {
            const uint4 m = lds128(ub + 23 * 16 + 7 * UP);
            const uint32_t U[6] = {lds32(ub + 23 * 16 + 6 * UP + 12), m.x, m.y, m.z, m.w, lds32(ub + 24 * 16)};
            uint32_t Q[5];
#pragma unroll
            for (int i = 0; i < 5; i++) Q[i] = hadd2(U[i], __byte_perm(U[i], U[i + 1], 0x5432));
            sts128(fb + F_O5 + 96 * 16, hadd2(hadd2(Q[0], Q[1]), U[2]), hadd2(hadd2(Q[1], Q[2]), U[3]), hadd2(hadd2(Q[2], Q[3]), U[4]), hadd2(hadd2(Q[3], Q[4]), U[5]));
            sts128(fb + F_O3, 0, 0, 0, 0); sts128(fb + F_E9, 0, 0, 0, 0);
            sts16(pn + 258 * 4, t258);
        }
        bar_sync(1 + k, 128);
        float acc[4][4];
        uint32_t Q[4][4];
        {
            const int h = role & 1, part = role >> 1;
            float fa[7][4];
            uint32_t B[3][4];
            const uint32_t po = tz + opaque(pf + part * (2 * P_GS)), ba = l16 + opaque(fb + (part == h ? 0 : F_O5 + h * 16));
#pragma unroll
            for (int s = 1; s >= 0; s--) {
#pragma unroll
                for (int i = 0; i < 3; i++) { Q[i][0] = lds32(po + (s * P_GS + i * 64)); if (i < 2) Q[i][1] = lds32(po + (s * P_GS + i * 64 + 32)); }
#pragma unroll
                for (int i = 0; i < 3; i++) ldsm4t(B[i], ba + (s * F_E3 + i * 512));
#pragma unroll
                for (int i = 0; i < 3; i++) { Q[i][3] = CP(Q[i][0]); if (i) Q[i][2] = CP(Q[i - 1][1]); }
                Q[0][2] = ZF(s ? tz : Q[0][0]); Q[2][1] = ZF(s ? l16 : Q[2][0]);
#pragma unroll
                for (int dl = 0; dl < 3; dl++)
#pragma unroll
                    for (int ap = 0; ap < 6 - dl; ap++) {
                        if (s == 1 && dl == 0) mma_f16_z(fa[ap + 1], Q[0], B[ap >> 1][2 * (ap & 1)], B[ap >> 1][2 * (ap & 1) + 1]);
                        else mma_f16(fa[ap + 1 + dl], Q[dl], B[ap >> 1][2 * (ap & 1)], B[ap >> 1][2 * (ap & 1) + 1]);
                    }
            }
#pragma unroll 1
            for (int s = role; s == 1; s++) {
                ldsm2t(B[0][0], B[0][1], fb + ((lane & 15) == 15 ? F_O5 : F_O3));
#pragma unroll
                for (int dl = 1; dl < 3; dl++) mma_f16(fa[dl], Q[dl], B[0][0], B[0][1]);
            }
            const uint32_t bh = l16 + opaque(fb + F_E7 + h * F_H + part * 2048), ph = tz + opaque(pf + P_H7 + part * (2 * P_HS));
#pragma unroll 1
            for (int s = part; s == 1; s++) {
                Q[2][1] = ZF(Q[2][3]); Q[2][2] = ZF(Q[2][2]); Q[2][0] = lds32(ph - P_HS);
                ldsm4t(B[0], bh - 1024); ldsm4t(B[1], bh - 512);
                Q[2][3] = CP(Q[2][0]);
#pragma unroll
                for (int ap = 0; ap < 4; ap++) mma_f16(fa[ap + 3], Q[2], B[ap >> 1][2 * (ap & 1)], B[ap >> 1][2 * (ap & 1) + 1]);
            }
            {
                Q[0][2] = ZF(tid);
#pragma unroll
                for (int i = 0; i < 4; i++) { Q[i][0] = lds32(ph + i * 64); Q[i][1] = lds32(ph + (i * 64 + 32)); }
                ldsm4t(B[0], bh); ldsm4t(B[1], bh + 512);
#pragma unroll
                for (int i = 0; i < 4; i++) { Q[i][3] = CP(Q[i][0]); if (i) Q[i][2] = CP(Q[i - 1][1]); }
#pragma unroll
                for (int dl = 0; dl < 4; dl++)
#pragma unroll
                    for (int ap = 0; ap < 4 - dl; ap++) mma_f16(fa[ap + 3 + dl], Q[dl], B[ap >> 1][2 * (ap & 1)], B[ap >> 1][2 * (ap & 1) + 1]);
            }
            const uint32_t da = (cq * 2048 + tz4) + opaque(fb + role * 128);
            bar_sync(1 + k, 128);
#pragma unroll
            for (int i = 1; i < 4; i++)
                stsm4(da + i * 512, pack_f16(fa[2 * i - 1][0], fa[2 * i - 1][1]), pack_f16(fa[2 * i - 1][2], fa[2 * i - 1][3]),
                      pack_f16(fa[2 * i][0], fa[2 * i][1]), pack_f16(fa[2 * i][2], fa[2 * i][3]));
            asm("shl.b32 %0, 0x6000, %1;" : "=r"(Q[0][0]) : "r"(tz4));
            Q[0][1] = ZF(Q[0][0]); Q[0][2] = ZF(tz4); Q[0][3] = CP(Q[0][0]);
            const uint32_t ra = l16 + opaque(fb + wq * 2016);
            acc[0][0] = acc[0][1] = acc[0][2] = acc[0][3] = 0.f;
            if (wq == 3) {
                const uint32_t uw = lds32(ub), kw = lds32(pf);
                const float2 uf = __half22float2(*(const __half2*)&uw);
                if ((lane | 4) == 31) acc[0][3] = (lane == 31 ? uf.x + uf.y : uf.x) * (__low2float(*(const __half2*)&kw) * 512.f);
            }
            bar_sync(1 + k, 128);
#pragma unroll
            for (int i = 1; i < 4; i++) {
                ldsm4(B[0], ra + i * 512);
                mma_f16_z(acc[i], Q[0], hadd2(B[0][0], B[0][2]), hadd2(B[0][1], B[0][3]));
            }
        }
        bar_arrive(6 + k, 160);
        STAMP(8);
        const uint32_t inv = lds32(opaque(sb + SM_SC + k * 4));
        const uint32_t yd = l16 + opaque(mapa(sb, 2 * wq) + (SM_XT + 128 + q * YP + k * YS + (k >> 2) * (q >> 1) * 16));
        {
            uint32_t pu = opaque(pn + 64 * (wq - 3));
#define pp (tz + pu)
            const uint32_t dlo = (((ub + 6 * UP) & 0x3FFFF) >> 4) | ((UP >> 4) << 16);
            uint32_t R[4][4];
            unsigned long long ds[4];
#pragma unroll
            for (int i = 0; i < 4; i++) asm volatile("mov.b64 %0, {%1, %2};" : "=l"(ds[i]) : "r"(dlo - i * (2 * UP >> 4)), "r"(8 | zero));
            auto loadQ = [&](uint32_t (&X)[4][4], uint32_t prev) {
#pragma unroll
                for (int i = 0; i < 4; i++) { X[i][0] = lds32(pp + i * 64); X[i][1] = lds32(pp + i * 64 + 32); }
                X[0][2] = CP(prev);
#pragma unroll
                for (int i = 0; i < 4; i++) { X[i][3] = CP(X[i][0]); if (i) X[i][2] = CP(X[i - 1][1]); }
                pu += 256;
            };
            auto issue = [&](uint32_t (&X)[4][4]) {
                asm volatile("wgmma.fence.sync.aligned;" ::: "memory");
#pragma unroll
                for (int i = 0; i < 4; i++) wgmma32(acc, X[i], ds[i]);
                asm volatile("wgmma.commit_group.sync.aligned;" ::: "memory");
#pragma unroll
                for (int i = 0; i < 4; i++) asm volatile("{ .reg .b32 l, h; mov.b64 {l, h}, %0; add.u32 l, l, %1; mov.b64 %0, {l, h}; }" : "+l"(ds[i]) : "r"(~zero));
            };
#pragma unroll
            for (int i = 0; i < 4; i++) {
                Q[i][0] = Q[i][1] = 0;
                if (wq + i >= 3) { Q[i][0] = lds32(pp + i * 64); Q[i][1] = lds32(pp + i * 64 + 32); }
            }
            Q[0][2] = CP(0);
#pragma unroll
            for (int i = 0; i < 4; i++) { Q[i][3] = CP(Q[i][0]); if (i) Q[i][2] = CP(Q[i - 1][1]); }
            pu += 256;
#pragma unroll 1
            for (int dl = 0; dl < 4; dl++) {
                issue(Q);
                asm volatile("wgmma.wait_group.sync.aligned 1;" ::: "memory");
                loadQ(R, Q[3][1]);
                issue(R);
                asm volatile("wgmma.wait_group.sync.aligned 1;" ::: "memory");
                loadQ(Q, R[3][1]);
            }
            issue(Q);
            asm volatile("wgmma.wait_group.sync.aligned 0;" ::: "memory");
        }
        const uint32_t pstep = mapa(sb, 1) - mapa(sb, 0), ym = mapa(mb + MB_Y * 8, 2 * wq);
#pragma unroll
        for (int e = 0; e < 2; e++)
            st_async4(yd + e * pstep, bmul2(pack_bf16(acc[0][2 * e], acc[0][2 * e + 1]), inv), bmul2(pack_bf16(acc[1][2 * e], acc[1][2 * e + 1]), inv),
                      bmul2(pack_bf16(acc[2][2 * e], acc[2][2 * e + 1]), inv), bmul2(pack_bf16(acc[3][2 * e], acc[3][2 * e + 1]), inv), ym + e * pstep);
        if (lane == 0) asm volatile("mbarrier.arrive.shared::cta.b64 _, [%0];" :: "r"(mb + MB_Y * 8) : "memory");
    }
    STAMP(9);
    uint32_t ha[5], hb[5];
    if (warp < 16) {
        const uint4 wk = lds128(sb + SM_DW + cq * 16);
        uint32_t sel[5] = {wk.x, wk.y, wk.z, wk.w, lds32(sb + SM_DW + 64 + cq * 4)}, sel2[5];
#pragma unroll
        for (int i = 0; i < 5; i++) {
            if (!(g & 1)) sel[i] = 0x3F803F80u;
            sel2[i] = sel[i]; PIN(sel2[i]);
        }
        const uint32_t y4 = sb + SM_XT + 128 + warp * 32 + (2 * (lane >> 3) + (lane & 1)) * YP + ((lane & 7) >> 1) * YS;
        const uint32_t y1 = sb + SM_XT + 128 + warp * 32 + (lane & 7) * YP + 4 * YS + (lane & 8) * 2 + (lane & 6) * 8;
        const uint32_t ao = (256 * q + tn) * 16;
        uint32_t hta = sb + SM_HT + tn * 80;
        unsigned long long ap = (unsigned long long)((char*)g_s.acc + ao);
        asm volatile("add.u64 %0, %0, %1;" : "+l"(ap) : "l"((unsigned long long)zero));
        PIN(hta);
        mbar_wait(mb + MB_Y * 8);
        STAMP(10);
        float ca[4] = {0.f, 0.f, 0.f, 0.f}, cb[4] = {0.f, 0.f, 0.f, 0.f};
        {
            uint32_t ya[4], yb[4], yc, yd;
            ldsm4t(ya, y4); ldsm4t(yb, y4 + 16); ldsm2t(yc, yd, y1);
#pragma unroll
            for (int i = 0; i < 4; i++) { ha[i] = badd2(xa[i], ya[i]); hb[i] = badd2(xb[i], yb[i]); }
            ha[4] = badd2(xa[4], yc); hb[4] = badd2(xb[4], yd);
        }
        if (nslot != 5) {
            ha[4] = hb[4] = 0;
            if (cq >= 2) ha[0] = ha[1] = ha[2] = ha[3] = hb[0] = hb[1] = hb[2] = hb[3] = 0;
        }
#pragma unroll
        for (int i = 0; i < 5; i++) { mma_bf16_k8(ca, ha[i], sel[i], ha[i]); mma_bf16_k8(cb, hb[i], sel2[i], hb[i]); }
        if (!(g & 1)) { ca[1] = ca[0]; cb[1] = cb[0]; }
        if (cq == (g >> 1)) {
            asm volatile("red.relaxed.gpu.global.add.v4.f32 [%0], {%1,%2,%3,%4};" :: "l"(ap), "f"(1.0f), "f"(ca[1]), "f"(ca[2]), "f"(ca[3]) : "memory");
            asm volatile("red.relaxed.gpu.global.add.v4.f32 [%0], {%1,%2,%3,%4};" :: "l"(ap + 128), "f"(1.0f), "f"(cb[1]), "f"(cb[2]), "f"(cb[3]) : "memory");
        }
        sts128(hta + cq * 16, ha[0], ha[1], ha[2], ha[3]); sts32(hta + 64 + cq * 4, ha[4]);
        sts128(hta + cq * 16 + 640, hb[0], hb[1], hb[2], hb[3]); sts32(hta + 704 + cq * 4, hb[4]);
        STAMP(11);
    }
    const int kq = warp / 5, mt = warp - 5 * kq;
    const int mi = lane >> 3, mr = lane & 7;
    const unsigned tk = (unsigned)tid / 72u, ck = tid - tk * 72;
    uint32_t A[9][4];
    auto loadA = [&]() {
        mbar_wait(mb + MB_W1 * 8);
        const uint32_t aa = sb + (mi & 1) * SM_WU + (8 * (mi >> 1) + mr) * 80 + (144 * 80 * kq + mt * 16);
#pragma unroll
        for (int s = 0; s < 9; s++) ldsm4t(A[s], aa + s * 1280);
    };
    const uint32_t par = (lds32(sb + SM_SC + 28) & 1) ? 0u : 0x40004000u;
    uint32_t go = (ck / 5u + ck) * 16, gs = sb + SM_SEL + 4 + (tk & 7) * 8;
    unsigned long long gb = (unsigned long long)((const char*)g_s.cand + go);
    uint32_t xs = sb + SM_XS + tk * 16 + tid * 16;
    asm volatile("add.u64 %0, %0, %1;" : "+l"(gb) : "l"((unsigned long long)zero));
    PIN(xs); PIN(gs);
    auto outtile = [&]() {
        const uint2 sa = lds64(sb + SM_ST + tn * 8), sbb = lds64(sb + SM_ST + tn * 8 + 64);
#pragma unroll
        for (int i = 0; i < 5; i++) { ha[i] = badd2(ha[i], norm2(ha[i], sa.x, sa.y)); hb[i] = badd2(hb[i], norm2(hb[i], sbb.x, sbb.y)); }
        const bool hf = (c & 1) && cq == 0;
        const uint32_t o16 = sb + SM_XT + (hf ? 16384 + tn * 16 : tn * 64 + (cq - (c & 1)) * 16), o4 = sb + SM_XT + ((c & 1) ? tn * 64 + 48 : 16384 + tn * 16) + cq * 4;
        sts128(o16, ha[0], ha[1], ha[2], ha[3]); sts32(o4, ha[4]);
        sts128(o16 + (hf ? 128 : 512), hb[0], hb[1], hb[2], hb[3]); sts32(o4 + ((c & 1) ? 512 : 128), hb[4]);
    };
    if (warp < 8) {
        const float wsum = ldsf(sb + SM_SC + 24);
        const uint32_t idx = 2047 - (512 * ((tid >> 1) & 3) + 128 * ((tid >> 3) & 3) + 64 * (tid & 1) + 8 * q + warp);
        uint32_t km0 = mapa(mb + MB_KEY * 8, 2 * cq), km1 = mapa(mb + MB_KEY * 8, 2 * cq + 1), ka0 = mapa(sb + SM_RK + q * 32, 2 * cq), ka1 = mapa(sb + SM_RK + q * 32, 2 * cq + 1);
        unsigned long long c0 = (unsigned long long)((char*)g_s.cand + ((q * 8 * NCL + c) * 6 + cq) * 16), c1 = c0 + (64 - cq * 12);
        uint32_t hc = sb + SM_HT + cq * 16, h4a = sb + SM_HT + 64 + cq * 4;
        uint32_t ca = sb + SM_KEY + warp * 128 + (warp & 1) * 32 + (lane & 28), r2a = sb + SM_KEY + cq * 16 + (cq >> 1) * 128;
        PIN(ca); PIN(r2a); PIN(km0); PIN(km1); PIN(ka0); PIN(ka1); PIN(hc); PIN(h4a);
        asm volatile("add.u64 %0, %0, %2; add.u64 %1, %1, %2;" : "+l"(c0), "+l"(c1) : "l"((unsigned long long)zero));
        uint4 s; int n = 0;
        uint32_t ox;
        do {
            s = ld_rlx128(&g_s.acc[256 * q + tid]);
            ox = __shfl_xor_sync(~0u, (lane & 1) ? s.z : s.w, 1);
        } while (__any_sync(~0u, __uint_as_float(s.x) != (float)NCL && ++n < SPIN_LIMIT));
        STAMP(16);
        const uint32_t ms = ln_stats(__uint_as_float((lane & 1) ? ox : s.z), __uint_as_float(s.y));
        const float rs = rcpf(bf_hi(ms));
        const uint32_t rb = pack_bf16(0.f, fmaf(-bf_lo(ms), wsum, __uint_as_float((lane & 1) ? s.w : ox)) * rs);
        const uint32_t key = (((rb ^ (((int)rb >> 31) | 0x80000000u)) >> 16) << 11) | idx;
        sts32(sb + SM_KEY + tid * 4, key);
        sts64(sb + SM_ST + tid * 8, ms, rsplit(rs));
        __syncwarp();
        uint32_t rank = rank4<8, 16>(sb + SM_KEY + warp * 128, key, ~zero);
        {
            const uint32_t sa = (rank * 4 ^ (warp & 1) * 32) + opaque(sb + SM_KEY + warp * 128);
            sts32(sa, key); sts32(sa + 1024, tid);
        }
        __syncwarp();
        const uint32_t mk = lds32(ca), t = lds32(ca + 1024);
        STAMP(17);
        bar_sync(12, 512);
        STAMP(18);
        const uint4 hv = lds128(hc + t * 80);
        const uint2 sv = lds64(sb + SM_ST + t * 8);
        const uint32_t h4 = lds32(h4a + t * 80);
        rank = rank4<4, 256>(r2a, mk, ~zero);
        const uint32_t rr = bmul2(sv.y, 0x3C803C80u);
        const uint32_t p0 = (norm2(hv.x, sv.x, rr) & 0xBFFFBFFFu) | par, p1 = (norm2(hv.y, sv.x, rr) & 0xBFFFBFFFu) | par, p2 = (norm2(hv.z, sv.x, rr) & 0xBFFFBFFFu) | par,
                       p3 = (norm2(hv.w, sv.x, rr) & 0xBFFFBFFFu) | par, p4 = (norm2(h4, sv.x, rr) & 0xBFFFBFFFu) | par;
        rank = quad_sum(rank);
        if (rank < 8) {
            st_async1(ka0 + rank * 4, mk, km0); st_async1(ka1 + rank * 4, mk, km1);
            st_rlx128((void*)(c0 + (unsigned long long)rank * 1440), p0, p1, p2, p3);
            asm volatile("st.relaxed.gpu.global.u32 [%0], %1;" :: "l"(c1 + (unsigned long long)rank * 1440), "r"(p4) : "memory");
        }
        __syncwarp();
    } else {
        mbar_wait(mb + MB_Y * 8); loadA();
        if (warp < 16) {
            bar_sync(12, 512);
        }
    }
    if (warp < 16) {
        outtile();
        if (warp >= 8) {
            uint32_t src = ((tid >> 2) - 64) * 1440, ma = sb + SM_RK - 256 + (tid >> 2) * 4, ra = sb + SM_RK + cq * 16;
            PIN(src); PIN(ma); PIN(ra);
            STAMP(19);
            mbar_wait(mb + MB_KEY * 8);
            STAMP(20);
            const uint32_t mk = lds32(ma);
            uint32_t rank = rank4<4, 64>(ra, mk, ~zero);
            rank = quad_sum(rank);
            sts64(sb + SM_SEL + rank * 8, mk, src);
        }
    }
    bar_sync(11, 672);
    STAMP(12);

    const char* gp = (const char*)gb + lds32(gs);
    uint4 hv = ld_rlx128(gp);
    if (warp < 8) loadA();
    uint32_t bx = sb + SM_XS + mr * 1168 + mi * 16 + 288 * kq, gd = mapa(sb, (kq & (NRED - 1)) * (8 / NRED)) + (SM_GU + (q * nslot + mt) * 128) + lane * 4;
    PIN(bx); PIN(gd);
    {
        if (warp < 18) {
            int n = 0;
            while (true) {
                sts128(xs, hv.x ^ par, hv.y ^ par, hv.z ^ par, hv.w ^ par);
                if (!__any_sync(~0u, ((hv.x ^ par) | (hv.y ^ par) | (hv.z ^ par) | (hv.w ^ par)) & 0x40004000u) || ++n >= SPIN_LIMIT) break;
                hv = ld_rlx128(gp);
            }
        }
    }
    bar_sync(14, 768);
    STAMP(13);
    float4 own;
    {
        float c0[4] = {0.f, 0.f, 0.f, 0.f}, c1[4] = {0.f, 0.f, 0.f, 0.f}, c2[4] = {0.f, 0.f, 0.f, 0.f};
        uint32_t b[5][4];
#pragma unroll
        for (int s = 0; s < 4; s++) ldsm4(b[s], bx + s * 64);
        asm volatile("ldmatrix.sync.aligned.m8n8.x2.shared.b16 {%0,%1}, [%2];" : "=r"(b[4][0]), "=r"(b[4][1]) : "r"(bx + 256) : "memory");
        mma_bf16(c0, A[0][0], A[0][1], A[0][2], A[0][3], b[0][0], b[0][1]);
        mma_bf16(c1, A[1][0], A[1][1], A[1][2], A[1][3], b[0][2], b[0][3]);
        mma_bf16(c2, A[2][0], A[2][1], A[2][2], A[2][3], b[1][0], b[1][1]);
        mma_bf16(c0, A[3][0], A[3][1], A[3][2], A[3][3], b[1][2], b[1][3]);
        mma_bf16(c1, A[4][0], A[4][1], A[4][2], A[4][3], b[2][0], b[2][1]);
        mma_bf16(c2, A[5][0], A[5][1], A[5][2], A[5][3], b[2][2], b[2][3]);
        mma_bf16(c0, A[6][0], A[6][1], A[6][2], A[6][3], b[3][0], b[3][1]);
        mma_bf16(c1, A[7][0], A[7][1], A[7][2], A[7][3], b[3][2], b[3][3]);
        mma_bf16(c2, A[8][0], A[8][1], A[8][2], A[8][3], b[4][0], b[4][1]);
        own = make_float4(c0[0] + c1[0] + c2[0], c0[1] + c1[1] + c2[1], c0[2] + c1[2] + c2[2], c0[3] + c1[3] + c2[3]);
        sts128f(sb + SM_RED + tid * 16, own.x, own.y, own.z, own.w);
    }
    if (kq < 4 - NRED) bar_arrive(1 + mt, 128); else
    bar_sync(1 + mt, 128);
    STAMP(21);
    if (mt < nslot && kq >= 4 - NRED) {
        const uint32_t ra = lane * 16 + opaque(sb + SM_RED + mt * 512);
        const float4 p0 = lds128f(ra), p1 = lds128f(ra + 2560), p2 = lds128f(lane * 16 + opaque(sb + SM_RED + mt * 512 + (5 - kq) * 2560)), p3 = own;
        const float g0 = bfr((p0.x + p1.x) + (p2.x + p3.x)), g1 = bfr((p0.y + p1.y) + (p2.y + p3.y));
        const uint32_t sg = pack_bf16(g0 * rcpf(1.f + ex2f(g0 * (-64.f * 1.4426950408889634f))), g1 * rcpf(1.f + ex2f(g1 * (-64.f * 1.4426950408889634f))));
        const uint32_t gu = bmul2(sg, pack_bf16(((p0.z + p1.z) + (p2.z + p3.z)) * 4096.f, ((p0.w + p1.w) + (p2.w + p3.w)) * 4096.f));
        const uint32_t pstep = mapa(sb, 1) - mapa(sb, 0), gm = mapa(mb + MB_GU * 8, (kq & (NRED - 1)) * (8 / NRED));
#pragma unroll
        for (int i = 0; i < 8 / NRED; i++) st_async1(gd + i * pstep, gu, gm + i * pstep);
    }
    mbar_wait(mb + MB_W2 * 8);
    {
        const uint32_t aa = sb + (8 * (mi >> 1) + mr) * 144 + (mi & 1) * 16 + (SM_FAR + 2304 * kq + mt * 32);
#pragma unroll
        for (int s = 0; s < 5; s++) ldsm4t(A[s], aa + s * FAR_SZ);
    }
    float sig; uint32_t ra2; unsigned long long fp, op;
    if (warp < 8) {
        const uint32_t key = lds32(sb + SM_SEL + warp * 8), k16 = key << 5, fj = 24 * q + lane;
        sig = bfr(rcpf(1.f + ex2f(__uint_as_float((k16 ^ (~((int)k16 >> 31) | 0x80000000u)) & 0xFFFF0000u) * -1.4426950408889634f)));
        ra2 = sb + SM_RED2 + warp * 304 + lane * 12;
        fp = (unsigned long long)(g_s.fin + warp * 192 + fj); op = (unsigned long long)(prm.out + (~key & 2047) * D_ + 3 * fj);
        PIN(ra2);
        asm volatile("add.u64 %0, %0, %3; add.u64 %1, %1, %3;" : "+l"(fp), "+l"(op), "+f"(sig) : "l"((unsigned long long)zero));
    }
    {
        uint32_t ba = sb + (SM_GU + 256 * kq) + (lane & 15) * 16 + (lane >> 4) * 1024, wa = sb + (SM_RED2 + kq * 2432 + mt * 64) + g * 4 + cq * 608;
        PIN(ba); PIN(wa);
        STAMP(22);
        mbar_wait(mb + MB_GU * 8);
        STAMP(23);
        float c0[4] = {0.f, 0.f, 0.f, 0.f}, c1[4] = {0.f, 0.f, 0.f, 0.f}, c2[4] = {0.f, 0.f, 0.f, 0.f};
        uint32_t b[2][4], b8, b9;
        ldsm4t(b[0], ba); ldsm4t(b[1], ba + 2048); ldsm2t(b8, b9, ba + 4096);
        mma_bf16(c0, A[0][0], A[0][1], A[0][2], A[0][3], b[0][0], b[0][1]);
        mma_bf16(c1, A[1][0], A[1][1], A[1][2], A[1][3], b[0][2], b[0][3]);
        if (nslot == 5) {
            mma_bf16(c2, A[4][0], A[4][1], A[4][2], A[4][3], b8, b9);
            mma_bf16(c0, A[2][0], A[2][1], A[2][2], A[2][3], b[1][0], b[1][1]);
            mma_bf16(c1, A[3][0], A[3][1], A[3][2], A[3][3], b[1][2], b[1][3]);
        }
        stsf(wa, c0[0] + c1[0] + c2[0]); stsf(wa + 304, c0[1] + c1[1] + c2[1]);
        if (mt < 4) { stsf(wa + 32, c0[2] + c1[2] + c2[2]); stsf(wa + 336, c0[3] + c1[3] + c2[3]); }
    }
    if (warp < 8) {
        float v[3];
        bar_sync(6, 640);
        STAMP(14);
        if (lane < 24) {
#pragma unroll
            for (int i = 0; i < 3; i++) v[i] = ((ldsf(ra2 + i * 4) + ldsf(ra2 + i * 4 + 2432)) + (ldsf(ra2 + i * 4 + 4864) + ldsf(ra2 + i * 4 + 7296))) * sig;
            asm volatile("{ .reg .f32 x, y, z, w; .reg .b16 a, b, c; .reg .pred p;\n"
                         "atom.relaxed.gpu.global.add.v4.f32 {x,y,z,w}, [%0], {%2,%3,%4,%5};\n"
                         "setp.eq.f32 p, w, %6; add.f32 x, x, %2; add.f32 y, y, %3; add.f32 z, z, %4;\n"
                         "cvt.rn.bf16.f32 a, x; cvt.rn.bf16.f32 b, y; cvt.rn.bf16.f32 c, z;\n"
                         "@p st.global.b16 [%1], a; @p st.global.b16 [%1 + 2], b; @p st.global.b16 [%1 + 4], c; }"
                         :: "l"(fp), "l"(op), "f"(v[0]), "f"(v[1]), "f"(v[2]), "f"(3.f), "f"(3.f * NCL) : "memory");
        }
    } else bar_arrive(6, 640);
    STAMP(15);
}

#undef pp
typedef __nv_bfloat16 bf16;
__device__ bf16 f_n[L_ * D_], f_h[L_ * D_];
__device__ float f_k[D_ * L_], f_r[L_], f_gu[8 * F_];
__device__ int f_idx[8];
__device__ __forceinline__ float b2f(bf16 v) { return __bfloat162float(v); }
__global__ void fb_ln(const bf16* in, const bf16* wr, bf16* out) {
    const int t = blockIdx.x * 8 + (threadIdx.x >> 5), lane = threadIdx.x & 31;
    const bf16* r = (in ? in : f_h) + t * D_;
    float s1 = 0.f, s2 = 0.f, s3 = 0.f;
    for (int i = lane; i < D_; i += 32) s1 += b2f(r[i]);
    for (int o = 16; o; o >>= 1) s1 += __shfl_xor_sync(~0u, s1, o);
    for (int i = lane; i < D_; i += 32) { const float d = b2f(r[i]) - s1 / D_; s2 += d * d; }
    for (int o = 16; o; o >>= 1) s2 += __shfl_xor_sync(~0u, s2, o);
    const float m = bfr(s1 / D_), sd = bfr(sqrtf(bfr(bfr(s2 / D_) + 1e-5f)));
    for (int i = lane; i < D_; i += 32) {
        const float v = bfr(bfr(b2f(r[i]) - m) / sd);
        f_n[t * D_ + i] = __float2bfloat16(v);
        if (!in) { s3 += v * b2f(wr[i]); out[t * D_ + i] = __float2bfloat16(b2f(r[i]) + v); }
    }
    for (int o = 16; o; o >>= 1) s3 += __shfl_xor_sync(~0u, s3, o);
    f_r[t] = bfr(s3);
}
__global__ void fb_taps(Params p) {
    const int d = blockIdx.x >> 3, l = (blockIdx.x & 7) * 256 + threadIdx.x;
    const float dt = bfr(expf(bf_lo(p.logdt[d]))), lf = bfr((float)l);
    float k = 0.f;
    for (int n = d * 128; n < d * 128 + 128; n++) {
        float wr, wi, sn, cs;
        cmul(wr, wi, bf_lo(p.prm6[4][n]), bf_lo(p.prm6[5][n]), dt * bf_lo(p.prm6[2][n]), dt * bf_lo(p.prm6[3][n]));
        sincosf(dt * bf_lo(p.prm6[1][n]) * lf, &sn, &cs);
        k += expf(dt * bf_lo(p.prm6[0][n]) * lf) * (wr * cs - wi * sn);
    }
    f_k[l * D_ + d] = k;
}
__global__ void fb_conv(Params p) {
    const int t = blockIdx.x, d = threadIdx.x;
    float y = 0.f;
    for (int l = 0; l <= t; l++) y += f_k[l * D_ + d] * b2f(f_n[(t - l) * D_ + d]);
    f_h[t * D_ + d] = __float2bfloat16(bf_lo(p.x[t * D_ + d]) + bfr(bfr(y) + bfr(b2f(f_n[t * D_ + d]) * bf_lo(p.dskip[d]))));
}
__global__ void fb_top() {
    const int t = blockIdx.x * 256 + threadIdx.x;
    int rank = 0;
    for (int j = 0; j < L_; j++) rank += f_r[j] > f_r[t] || (f_r[j] == f_r[t] && j < t);
    if (rank < 8) f_idx[rank] = t;
}
__global__ void fb_ffn1(const bf16* wg, const bf16* wu) {
    const int f = blockIdx.x * 256 + threadIdx.x, j = blockIdx.y;
    float g = 0.f, u = 0.f;
    for (int i = 0; i < D_; i++) { const float v = b2f(f_n[f_idx[j] * D_ + i]); g += v * b2f(wg[i * F_ + f]); u += v * b2f(wu[i * F_ + f]); }
    g = bfr(g);
    f_gu[j * F_ + f] = bfr(bfr(g / (1.f + expf(-g))) * bfr(u));
}
__global__ void fb_ffn2(const bf16* wd, bf16* out) {
    const int d = threadIdx.x, j = blockIdx.x, t = f_idx[j];
    float y = 0.f;
    for (int f = 0; f < F_; f++) y += f_gu[j * F_ + f] * b2f(wd[f * D_ + d]);
    out[t * D_ + d] = __float2bfloat16(b2f(f_h[t * D_ + d]) + bfr(b2f(f_n[t * D_ + d]) + bfr(bfr(y) * bfr(1.f / (1.f + expf(-f_r[t]))))));
}

typedef CUresult (*EncodeFn)(CUtensorMap*, CUtensorMapDataType, cuuint32_t, void*, const cuuint64_t*, const cuuint64_t*,
                             const cuuint32_t*, const cuuint32_t*, CUtensorMapInterleave, CUtensorMapSwizzle,
                             CUtensorMapL2promotion, CUtensorMapFloatOOBfill);

void make_map(EncodeFn fn, CUtensorMap* tm, const void* p, int cols, int rows, int bc, int br) {
    cuuint64_t dims[2] = {(cuuint64_t)cols, (cuuint64_t)rows};
    cuuint64_t strides[1] = {(cuuint64_t)cols * 2};
    cuuint32_t box[2] = {(cuuint32_t)bc, (cuuint32_t)br};
    cuuint32_t es[2] = {1, 1};
    fn(tm, CU_TENSOR_MAP_DATA_TYPE_BFLOAT16, 2, const_cast<void*>(p), dims, strides, box, es, CU_TENSOR_MAP_INTERLEAVE_NONE,
       CU_TENSOR_MAP_SWIZZLE_NONE, CU_TENSOR_MAP_L2_PROMOTION_L2_128B, CU_TENSOR_MAP_FLOAT_OOB_FILL_NONE);
}

void make_map3(EncodeFn fn, CUtensorMap* tm, const void* p) {
    cuuint64_t dims[5] = {(cuuint64_t)D_, 64, 2, 2, 8};
    cuuint64_t strides[4] = {(cuuint64_t)D_ * 2, (cuuint64_t)D_ * 2048, (cuuint64_t)D_ * 128, (cuuint64_t)D_ * 256};
    cuuint32_t box[5] = {XW, 9, 2, 2, 8};
    cuuint32_t es[5] = {1, 1, 1, 1, 1};
    fn(tm, CU_TENSOR_MAP_DATA_TYPE_BFLOAT16, 5, const_cast<void*>(p), dims, strides, box, es, CU_TENSOR_MAP_INTERLEAVE_NONE,
       CU_TENSOR_MAP_SWIZZLE_NONE, CU_TENSOR_MAP_L2_PROMOTION_NONE, CU_TENSOR_MAP_FLOAT_OOB_FILL_NONE);
}

void make_map5(EncodeFn fn, CUtensorMap* tm, const void* p, int bc) {
    cuuint64_t dims[5] = {(cuuint64_t)D_, 2, 4, 4, 64};
    cuuint64_t strides[4] = {(cuuint64_t)D_ * 128, (cuuint64_t)D_ * 1024, (cuuint64_t)D_ * 256, (cuuint64_t)D_ * 2};
    cuuint32_t box[5] = {(cuuint32_t)bc, 2, 4, 4, 8};
    cuuint32_t es[5] = {1, 1, 1, 1, 1};
    fn(tm, CU_TENSOR_MAP_DATA_TYPE_BFLOAT16, 5, const_cast<void*>(p), dims, strides, box, es, CU_TENSOR_MAP_INTERLEAVE_NONE,
       CU_TENSOR_MAP_SWIZZLE_NONE, CU_TENSOR_MAP_L2_PROMOTION_NONE, CU_TENSOR_MAP_FLOAT_OOB_FILL_NONE);
}

}

extern "C" void kernel_launch(void* const* d_in, const int* in_sizes, int n_in, void* d_out, int out_size) {
    (void)in_sizes; (void)n_in; (void)out_size;
    void* fp = nullptr;
    cudaDriverEntryPointQueryResult qr;
    cudaGetDriverEntryPoint("cuTensorMapEncodeTiled", &fp, cudaEnableDefault, &qr);
    EncodeFn fn = (EncodeFn)fp;
    CUtensorMap tmG, tmU, tmD, tmO, tmX, tmH;
    make_map3(fn, &tmX, d_in[0]);
    make_map(fn, &tmG, d_in[11], F_, D_, 40, 48);
    make_map(fn, &tmU, d_in[12], F_, D_, 40, 48);
    make_map(fn, &tmD, d_in[13], D_, F_, 72, 64);
    make_map5(fn, &tmO, d_out, 32);
    make_map5(fn, &tmH, d_out, 8);
    Params p;
    p.x = (const unsigned short*)d_in[0];
    for (int i = 0; i < 6; i++) p.prm6[i] = (const unsigned short*)d_in[1 + i];
    p.logdt = (const unsigned short*)d_in[7]; p.dskip = (const unsigned short*)d_in[8];
    p.wr = (const unsigned short*)d_in[10];
    p.out = (__nv_bfloat16*)d_out;
    p.zero = 0;
    cudaGetSymbolAddress((void**)&p.gs, g_s);
    cudaFuncSetAttribute(fused_kernel, cudaFuncAttributeMaxDynamicSharedMemorySize, SM_TOTAL);
    static int nclusters = -1;
    if (nclusters < 0) {
        cudaLaunchConfig_t cfg = {};
        cudaLaunchAttribute at;
        at.id = cudaLaunchAttributeClusterDimension; at.val.clusterDim.x = CS; at.val.clusterDim.y = 1; at.val.clusterDim.z = 1;
        cfg.gridDim = dim3(NCTA); cfg.blockDim = dim3(NTHR); cfg.dynamicSmemBytes = SM_TOTAL; cfg.attrs = &at; cfg.numAttrs = 1;
        if (cudaOccupancyMaxActiveClusters(&nclusters, fused_kernel, &cfg) != cudaSuccess) { (void)cudaGetLastError(); nclusters = NCL; }
    }
    if (nclusters >= NCL && !FORCE_FALLBACK) {
        fused_kernel<<<NCTA, NTHR, SM_TOTAL>>>(p, tmG, tmU, tmD, tmO, tmX, tmH);
        return;
    }
    fb_ln<<<L_ / 8, 256>>>((const bf16*)d_in[0], nullptr, nullptr);
    fb_taps<<<D_ * 8, 256>>>(p);
    fb_conv<<<L_, D_>>>(p);
    fb_ln<<<L_ / 8, 256>>>(nullptr, (const bf16*)d_in[10], p.out);
    fb_top<<<L_ / 256, 256>>>();
    fb_ffn1<<<dim3(F_ / 256, 8), 256>>>((const bf16*)d_in[11], (const bf16*)d_in[12]);
    fb_ffn2<<<8, D_>>>((const bf16*)d_in[13], p.out);
}
```

```cpp
#include <cuda_runtime.h>
#include <cuda_bf16.h>
#include <cuda_fp16.h>
#include <cuda.h>
#include <stdint.h>

namespace {

constexpr int L_ = 2048, D_ = 576, F_ = 4608;
constexpr int NCL = 15, CS = 8, NCTA = NCL * CS, NTHR = 768;
#define FORCE_FALLBACK 0
constexpr int XW = 48, NRED = 2;
constexpr int SPIN_LIMIT = 1 << 22;

constexpr int SM_WG   = 0;
constexpr int SM_WU   = 46080;
constexpr int YP = 3392, YS = 656;
constexpr int UP = 3280, US = 656;
constexpr int SM_XT   = 92160;
constexpr int SM_U    = SM_XT + 8 * YP;
constexpr int SM_FAR  = SM_U + 8 * UP;
constexpr int FAR_SZ  = 12416;
constexpr int F_E5 = 0, F_O5 = 1536, F_E3 = 3088, F_O3 = 4624, F_E7 = 6176, F_E2 = F_E7 + 1024, F_E9 = F_E7 + 2048,
              F_H = 3088, F_O7 = F_E7 + F_H, F_O2 = F_E2 + F_H, F_O9 = F_E9 + F_H;
constexpr int SM_P    = SM_FAR + 5 * FAR_SZ;
constexpr int PN_SZ = 584 * 4, SM_PN = SM_P + 65 * 4;
constexpr int P_GS = 50 * 4, P_H7 = 200 * 4, P_HS = 74 * 4;
constexpr int PF_SZ = (200 + 222) * 4, SM_PF = SM_PN + 5 * PN_SZ + 36;
constexpr int SM_MISC = SM_PF + 5 * PF_SZ;
constexpr int SM_ST   = SM_MISC;
constexpr int SM_RK   = SM_ST + 2048;
constexpr int SM_SEL  = SM_FAR + FAR_SZ + 10240;
constexpr int SM_KG   = SM_RK + 320;
constexpr int SM_SC   = SM_KG + 160;
constexpr int SM_DW   = SM_SC + 32;
constexpr int SM_MB   = SM_DW + 160;
constexpr int SM_TOTAL = SM_MB + 128;
constexpr int SM_ROW  = SM_XT - 20736;
constexpr int SM_XTL  = SM_ROW - 576 * XW;
constexpr int SM_RED2 = SM_WG;
constexpr int SM_HT   = SM_P - 512;
constexpr int SM_KEY  = SM_FAR + 10240 + 128;
constexpr int SM_CAND = SM_KEY + 1024;
constexpr int SM_XS   = SM_U;
constexpr int SM_GU   = SM_XS + 9344;
constexpr int SM_RED  = SM_GU + 5632;
static_assert(F_O9 + 1024 <= FAR_SZ && FAR_SZ % 128 == 0, "far overflow");
static_assert(SM_RED + 10240 <= SM_FAR && SM_HT + 20496 <= SM_MISC, "alias overflow");
static_assert(SM_TOTAL <= 232448, "smem overflow");
static_assert(SM_FAR % 128 == 0 && SM_XT % 128 == 0 && SM_XTL % 128 == 0 && SM_P % 16 == 0 && SM_MISC % 16 == 0 && SM_MB % 8 == 0, "align");

enum { MB_X = 0, MB_W1 = 5, MB_W2 = 6, MB_KEY = 7, MB_GU = 8, MB_Y = 9, MB_OUT = 10, MB_T = 11, MB_R = 12 };

struct __align__(128) Scratch {
    unsigned epoch, zcnt, pad[30];
    uint4  st1[L_ * 2];
    float4 acc[L_];
    uint4  cand[64 * NCL * 6];
    float4 fin[8 * 192 + 24];
};
__device__ Scratch g_s;
#define STAMP(i)

__device__ __forceinline__ uint32_t mapa(uint32_t a, uint32_t r) { uint32_t d; asm("mapa.shared::cluster.u32 %0, %1, %2;" : "=r"(d) : "r"(a), "r"(r)); return d; }
__device__ __forceinline__ void mbar_wait(uint32_t mb) {
    asm volatile("{ .reg .pred p, q; .reg .u32 n; mov.u32 n, 0;\n"
                 "W_%=: mbarrier.try_wait.parity.shared::cta.b64 p, [%0], 0; add.u32 n, n, 1; setp.lt.and.u32 q, n, 65536, !p; @q bra W_%=; }" :: "r"(mb) : "memory");
}
__device__ __forceinline__ bool elect() { uint32_t e; asm volatile("{ .reg .pred p; elect.sync _|p, 0xffffffff; selp.u32 %0, 1, 0, p; }" : "=r"(e)); return e; }
__device__ __forceinline__ void arm(uint32_t mb, uint32_t bytes) { asm volatile("mbarrier.arrive.expect_tx.shared::cta.b64 _, [%0], %1;" :: "r"(mb), "r"(bytes) : "memory"); }
__device__ __forceinline__ void bar_sync(int id, int n) { asm volatile("bar.sync %0, %1;" :: "r"(id), "r"(n) : "memory"); }
__device__ __forceinline__ void bar_arrive(int id, int n) { asm volatile("bar.arrive %0, %1;" :: "r"(id), "r"(n) : "memory"); }
__device__ __forceinline__ uint32_t lds16(uint32_t a) { unsigned short v; asm volatile("ld.shared.u16 %0, [%1];" : "=h"(v) : "r"(a) : "memory"); return v; }
__device__ __forceinline__ uint32_t lds32(uint32_t a) { uint32_t v; asm volatile("ld.shared.u32 %0, [%1];" : "=r"(v) : "r"(a) : "memory"); return v; }
__device__ __forceinline__ uint2 lds64(uint32_t a) { uint2 v; asm volatile("ld.shared.v2.u32 {%0,%1}, [%2];" : "=r"(v.x), "=r"(v.y) : "r"(a) : "memory"); return v; }
__device__ __forceinline__ float ldsf(uint32_t a) { float v; asm volatile("ld.shared.f32 %0, [%1];" : "=f"(v) : "r"(a) : "memory"); return v; }
__device__ __forceinline__ uint4 lds128(uint32_t a) { uint4 v; asm volatile("ld.shared.v4.u32 {%0,%1,%2,%3}, [%4];" : "=r"(v.x), "=r"(v.y), "=r"(v.z), "=r"(v.w) : "r"(a) : "memory"); return v; }
__device__ __forceinline__ float4 lds128f(uint32_t a) { float4 v; asm volatile("ld.shared.v4.f32 {%0,%1,%2,%3}, [%4];" : "=f"(v.x), "=f"(v.y), "=f"(v.z), "=f"(v.w) : "r"(a) : "memory"); return v; }
__device__ __forceinline__ void sts16(uint32_t a, uint32_t v) { asm volatile("{ .reg .b16 l, h; mov.b32 {l, h}, %1; st.shared.b16 [%0], l; }" :: "r"(a), "r"(v) : "memory"); }
__device__ __forceinline__ void sts32(uint32_t a, uint32_t v) { asm volatile("st.shared.u32 [%0], %1;" :: "r"(a), "r"(v) : "memory"); }
__device__ __forceinline__ void sts64(uint32_t a, uint32_t x, uint32_t y) { asm volatile("st.shared.v2.u32 [%0], {%1,%2};" :: "r"(a), "r"(x), "r"(y) : "memory"); }
__device__ __forceinline__ void stsf(uint32_t a, float v) { asm volatile("st.shared.f32 [%0], %1;" :: "r"(a), "f"(v) : "memory"); }
__device__ __forceinline__ void sts128(uint32_t a, uint32_t x, uint32_t y, uint32_t z, uint32_t w) { asm volatile("st.shared.v4.u32 [%0], {%1,%2,%3,%4};" :: "r"(a), "r"(x), "r"(y), "r"(z), "r"(w) : "memory"); }
__device__ __forceinline__ void sts128f(uint32_t a, float x, float y, float z, float w) { asm volatile("st.shared.v4.f32 [%0], {%1,%2,%3,%4};" :: "r"(a), "f"(x), "f"(y), "f"(z), "f"(w) : "memory"); }
__device__ __forceinline__ void ldsm4(uint32_t (&r)[4], uint32_t a) { asm volatile("ldmatrix.sync.aligned.m8n8.x4.shared.b16 {%0,%1,%2,%3}, [%4];" : "=r"(r[0]), "=r"(r[1]), "=r"(r[2]), "=r"(r[3]) : "r"(a) : "memory"); }
__device__ __forceinline__ void ldsm4t(uint32_t (&r)[4], uint32_t a) { asm volatile("ldmatrix.sync.aligned.m8n8.x4.trans.shared.b16 {%0,%1,%2,%3}, [%4];" : "=r"(r[0]), "=r"(r[1]), "=r"(r[2]), "=r"(r[3]) : "r"(a) : "memory"); }
__device__ __forceinline__ void ldsm2t(uint32_t& r0, uint32_t& r1, uint32_t a) { asm volatile("ldmatrix.sync.aligned.m8n8.x2.trans.shared.b16 {%0,%1}, [%2];" : "=r"(r0), "=r"(r1) : "r"(a) : "memory"); }
__device__ __forceinline__ void stsm4t(uint32_t a, uint32_t r0, uint32_t r1, uint32_t r2, uint32_t r3) { asm volatile("stmatrix.sync.aligned.m8n8.x4.trans.shared.b16 [%0], {%1,%2,%3,%4};" :: "r"(a), "r"(r0), "r"(r1), "r"(r2), "r"(r3) : "memory"); }
__device__ __forceinline__ void stsm4(uint32_t a, uint32_t r0, uint32_t r1, uint32_t r2, uint32_t r3) { asm volatile("stmatrix.sync.aligned.m8n8.x4.shared.b16 [%0], {%1,%2,%3,%4};" :: "r"(a), "r"(r0), "r"(r1), "r"(r2), "r"(r3) : "memory"); }
__device__ __forceinline__ void stsm2(uint32_t a, uint32_t r0, uint32_t r1) { asm volatile("stmatrix.sync.aligned.m8n8.x2.shared.b16 [%0], {%1,%2};" :: "r"(a), "r"(r0), "r"(r1) : "memory"); }
__device__ __forceinline__ void stsm2t(uint32_t a, uint32_t r0, uint32_t r1) { asm volatile("stmatrix.sync.aligned.m8n8.x2.trans.shared.b16 [%0], {%1,%2};" :: "r"(a), "r"(r0), "r"(r1) : "memory"); }
__device__ __forceinline__ uint4 ldg128(const void* p) { uint4 v; asm volatile("ld.global.nc.v4.u32 {%0,%1,%2,%3}, [%4];" : "=r"(v.x), "=r"(v.y), "=r"(v.z), "=r"(v.w) : "l"(p)); return v; }
__device__ __forceinline__ uint32_t ldg16(const void* p) { unsigned short v; asm volatile("ld.global.nc.u16 %0, [%1];" : "=h"(v) : "l"(p)); return v; }
__device__ __forceinline__ uint32_t opaque(uint32_t v) { uint32_t r; asm volatile("mov.b32 %0, %1;" : "=r"(r) : "r"(v)); return r; }
__device__ __forceinline__ void mma_f16(float (&d)[4], const uint32_t (&a)[4], uint32_t b0, uint32_t b1) {
    asm volatile("mma.sync.aligned.m16n8k16.row.col.f32.f16.f16.f32 {%0,%1,%2,%3}, {%4,%5,%6,%7}, {%8,%9}, {%0,%1,%2,%3};"
        : "+f"(d[0]), "+f"(d[1]), "+f"(d[2]), "+f"(d[3]) : "r"(a[0]), "r"(a[1]), "r"(a[2]), "r"(a[3]), "r"(b0), "r"(b1));
}
__device__ __forceinline__ void mma_f16_z(float (&d)[4], const uint32_t (&a)[4], uint32_t b0, uint32_t b1) {
    asm volatile("mma.sync.aligned.m16n8k16.row.col.f32.f16.f16.f32 {%0,%1,%2,%3}, {%4,%5,%6,%7}, {%8,%9}, {%10,%10,%10,%10};"
        : "=f"(d[0]), "=f"(d[1]), "=f"(d[2]), "=f"(d[3]) : "r"(a[0]), "r"(a[1]), "r"(a[2]), "r"(a[3]), "r"(b0), "r"(b1), "f"(0.f));
}
__device__ __forceinline__ void mma_bf16(float (&d)[4], uint32_t a0, uint32_t a1, uint32_t a2, uint32_t a3, uint32_t b0, uint32_t b1) {
    asm volatile("mma.sync.aligned.m16n8k16.row.col.f32.bf16.bf16.f32 {%0,%1,%2,%3}, {%4,%5,%6,%7}, {%8,%9}, {%0,%1,%2,%3};"
        : "+f"(d[0]), "+f"(d[1]), "+f"(d[2]), "+f"(d[3]) : "r"(a0), "r"(a1), "r"(a2), "r"(a3), "r"(b0), "r"(b1));
}
__device__ __forceinline__ void mma_bf16_k8(float (&d)[4], uint32_t a0, uint32_t a1, uint32_t b0) {
    asm volatile("mma.sync.aligned.m16n8k8.row.col.f32.bf16.bf16.f32 {%0,%1,%2,%3}, {%4,%5}, {%6}, {%0,%1,%2,%3};"
        : "+f"(d[0]), "+f"(d[1]), "+f"(d[2]), "+f"(d[3]) : "r"(a0), "r"(a1), "r"(b0));
}
__device__ __forceinline__ uint32_t pack_f16(float lo, float hi) { uint32_t r; asm("cvt.rn.f16x2.f32 %0, %1, %2;" : "=r"(r) : "f"(hi), "f"(lo)); return r; }
__device__ __forceinline__ uint32_t pack_bf16(float lo, float hi) { uint32_t r; asm("cvt.rn.bf16x2.f32 %0, %1, %2;" : "=r"(r) : "f"(hi), "f"(lo)); return r; }
__device__ __forceinline__ float bf_lo(uint32_t v) { return __uint_as_float(v << 16); }
__device__ __forceinline__ float bf_hi(uint32_t v) { return __uint_as_float(v & 0xFFFF0000u); }
__device__ __forceinline__ float bfr(float x) { return __uint_as_float(pack_bf16(0.f, x)); }
__device__ __forceinline__ uint32_t badd2(uint32_t a, uint32_t b) { uint32_t r; asm("add.rn.bf16x2 %0, %1, %2;" : "=r"(r) : "r"(a), "r"(b)); return r; }
__device__ __forceinline__ uint32_t bmul2(uint32_t a, uint32_t b) { uint32_t r; asm("mul.rn.bf16x2 %0, %1, %2;" : "=r"(r) : "r"(a), "r"(b)); return r; }
__device__ __forceinline__ uint32_t hadd2(uint32_t a, uint32_t b) { uint32_t r; asm("add.rn.f16x2 %0, %1, %2;" : "=r"(r) : "r"(a), "r"(b)); return r; }
__device__ __forceinline__ uint32_t hmul2(uint32_t a, uint32_t b) { uint32_t r; asm("mul.rn.f16x2 %0, %1, %2;" : "=r"(r) : "r"(a), "r"(b)); return r; }
__device__ __forceinline__ uint32_t hneg2(uint32_t a) { uint32_t r; asm("neg.f16x2 %0, %1;" : "=r"(r) : "r"(a)); return r; }
__device__ __forceinline__ float rcpf(float x) { float r; asm("rcp.approx.ftz.f32 %0, %1;" : "=f"(r) : "f"(x)); return r; }
__device__ __forceinline__ float sqrta(float x) { float r; asm("sqrt.approx.ftz.f32 %0, %1;" : "=f"(r) : "f"(x)); return r; }
__device__ __forceinline__ float ex2f(float x) { float r; asm("ex2.approx.ftz.f32 %0, %1;" : "=f"(r) : "f"(x)); return r; }
__device__ __forceinline__ void st_async4(uint32_t a, uint32_t x, uint32_t y, uint32_t z, uint32_t w, uint32_t mb) {
    asm volatile("st.async.shared::cluster.mbarrier::complete_tx::bytes.v4.u32 [%0], {%1,%2,%3,%4}, [%5];" :: "r"(a), "r"(x), "r"(y), "r"(z), "r"(w), "r"(mb) : "memory"); }
__device__ __forceinline__ void st_async1(uint32_t a, uint32_t x, uint32_t mb) {
    asm volatile("st.async.shared::cluster.mbarrier::complete_tx::bytes.u32 [%0], %1, [%2];" :: "r"(a), "r"(x), "r"(mb) : "memory"); }
__device__ __forceinline__ unsigned ld_rlx(const void* p) { unsigned v; asm volatile("ld.relaxed.gpu.global.u32 %0, [%1];" : "=r"(v) : "l"(p) : "memory"); return v; }
__device__ __forceinline__ unsigned ld_acq(const void* p) { unsigned v; asm volatile("ld.acquire.gpu.global.u32 %0, [%1];" : "=r"(v) : "l"(p) : "memory"); return v; }
__device__ __forceinline__ uint2 ld_rlx64(const void* p) { unsigned long long v; asm volatile("ld.relaxed.gpu.global.u64 %0, [%1];" : "=l"(v) : "l"(p) : "memory"); return make_uint2((unsigned)v, (unsigned)(v >> 32)); }
__device__ __forceinline__ void st_rlx128(void* p, uint32_t x, uint32_t y, uint32_t z, uint32_t w) {
    asm volatile("st.relaxed.gpu.global.v2.u64 [%0], {%1,%2};" :: "l"(p), "l"((unsigned long long)x | ((unsigned long long)y << 32)), "l"((unsigned long long)z | ((unsigned long long)w << 32)) : "memory"); }
__device__ __forceinline__ uint4 ld_rlx128(const void* p) { unsigned long long a, b; asm volatile("ld.relaxed.gpu.global.v2.u64 {%0,%1}, [%2];" : "=l"(a), "=l"(b) : "l"(p) : "memory"); return make_uint4((unsigned)a, (unsigned)(a >> 32), (unsigned)b, (unsigned)(b >> 32)); }
__device__ __forceinline__ void tma2d(uint32_t dst, const CUtensorMap* tm, int x, int y, uint32_t mb) {
    asm volatile("cp.async.bulk.tensor.2d.shared::cluster.global.mbarrier::complete_tx::bytes [%0], [%1, {%3, %4}], [%2];"
                 :: "r"(dst), "l"(tm), "r"(mb), "r"(x), "r"(y) : "memory");
}
__device__ __forceinline__ void cmul(float& xr, float& xi, float ar, float ai, float br, float bi) {
    const float r = fmaf(ar, br, -ai * bi), i = fmaf(ar, bi, ai * br); xr = r; xi = i;
}
__device__ __forceinline__ void csq(float& xr, float& xi, float ar, float ai) {
    const float r = fmaf(ar, ar, -ai * ai), i = (ar + ar) * ai; xr = r; xi = i;
}
__device__ __forceinline__ void cexp_s(float& zr, float& zi, float e2, float turns) {
    const float mag = ex2f(e2), r = (turns - rintf(turns)) * 6.283185307179586f;
    zr = mag * __cosf(r); zi = mag * __sinf(r);
}
__device__ __forceinline__ uint32_t ln_stats(float s1, float s2) {
    const float m = s1 * (1.f / D_);
    const float var = fmaxf(fmaf(s2, 1.f / D_, -m * m), 0.f);
    return pack_bf16(m, sqrta(bfr(bfr(var) + 1e-5f)));
}
__device__ __forceinline__ uint32_t rsplit(float rs) { const float h = bfr(rs); return pack_bf16(h, rs - h); }
__device__ __forceinline__ uint32_t norm2(uint32_t v, uint32_t mx, uint32_t hl) {
    uint32_t r;
    asm("{ .reg .b16 m, h, l, x; .reg .b32 m2, h2, l2, d, t; mov.b32 {m, x}, %2; mov.b32 {h, l}, %3; mov.b32 m2, {m, m}; mov.b32 h2, {h, h}; mov.b32 l2, {l, l};\n"
        "sub.rn.bf16x2 d, %1, m2; mul.rn.bf16x2 t, d, l2; fma.rn.bf16x2 %0, d, h2, t; }" : "=r"(r) : "r"(v), "r"(mx), "r"(hl));
    return r;
}
template <int N, int S>
__device__ __forceinline__ uint32_t rank4(uint32_t a, uint32_t key, uint32_t m1) {
    uint32_t r0 = 0, r1 = 0, r2 = 0, r3 = 0;
#pragma unroll
    for (int i = 0; i < N; i++) {
        const uint4 o = lds128(a + i * S);
        r0 += (o.x * m1 + key) >> 31; r1 += (o.y * m1 + key) >> 31; r2 += (o.z * m1 + key) >> 31; r3 += (o.w * m1 + key) >> 31;
    }
    return (r0 + r1) + (r2 + r3);
}
__device__ __forceinline__ uint32_t quad_sum(uint32_t r) {
    const uint32_t a = __shfl_xor_sync(~0u, r, 1), b = __shfl_xor_sync(~0u, r, 2), c = __shfl_xor_sync(~0u, r, 3);
    return (r + a) + b + c;
}
typedef uint32_t H2C;
__device__ __forceinline__ H2C splat(float r, float i) { return pack_f16(r, i); }
__device__ __forceinline__ void hcmul(uint32_t& xr, uint32_t& xi, uint32_t R, uint32_t I, H2C m) {
    asm("{ .reg .b16 a, b; .reg .b32 a2, b2, t; mov.b32 {a, b}, %4; mov.b32 a2, {a, a}; mov.b32 b2, {b, b};\n"
        "mul.rn.f16x2 t, %3, b2; neg.f16x2 t, t; fma.rn.f16x2 %0, %2, a2, t; mul.rn.f16x2 t, %3, a2; fma.rn.f16x2 %1, %2, b2, t; }"
        : "=&r"(xr), "=r"(xi) : "r"(R), "r"(I), "r"(m));
}
__device__ __forceinline__ void expand4(uint32_t are, uint32_t aim, uint32_t R0, uint32_t R1, uint32_t I0, uint32_t I1, H2C m4) {
    uint32_t R2, I2, R3, I3;
    hcmul(R2, I2, R0, I0, m4); hcmul(R3, I3, R1, I1, m4);
    sts128(are, R0, R1, R2, R3);
    sts128(aim, I0, I1, I2, I3);
}
__device__ __forceinline__ void expand8(uint32_t are, uint32_t aim, float sr, float si, float m1r, float m1i, float m2r, float m2i, H2C m4) {
    float r1, i1, r2, i2, r3, i3;
    cmul(r1, i1, sr, si, m1r, m1i); cmul(r2, i2, sr, si, m2r, m2i); cmul(r3, i3, r1, i1, m2r, m2i);
    expand4(are, aim, pack_f16(sr, r1), pack_f16(r2, r3), pack_f16(si, i1), pack_f16(i2, i3), m4);
}
__device__ __forceinline__ uint32_t comb4(uint32_t a, uint32_t b, uint32_t c, uint32_t d, uint32_t r01, uint32_t r23) {
    uint32_t x;
    asm("{ .reg .b16 h0, h1, h2, h3; .reg .b32 m0, m1, m2, m3, u, v; mov.b32 {h0, h1}, %5; mov.b32 {h2, h3}, %6;\n"
        "mov.b32 m0, {h0, h0}; mov.b32 m1, {h1, h1}; mov.b32 m2, {h2, h2}; mov.b32 m3, {h3, h3};\n"
        "mul.rn.f16x2 u, %2, m1; fma.rn.f16x2 u, %1, m0, u; mul.rn.f16x2 v, %4, m3; fma.rn.f16x2 v, %3, m2, v; add.rn.f16x2 %0, u, v; }"
        : "=r"(x) : "r"(a), "r"(b), "r"(c), "r"(d), "r"(r01), "r"(r23));
    return x;
}
__device__ __forceinline__ void put16(uint32_t a, uint32_t v) { sts16(a, v); sts16(a + 6, v); }

struct Params {
    const unsigned short *logdt, *dskip, *prm6[6], *x, *wr;
    __nv_bfloat16* out;
    Scratch* gs;
    unsigned zero;
};
__device__ __forceinline__ uint32_t tslot(uint32_t t) { return (t & 7) * 32 + ((t >> 4) & 24) + ((t >> 8) & 6) + ((t >> 6) & 1); }
#define CP(x) ((x) | zero)
#define ZF(x) ((x) & zero)
#define PIN(x) asm volatile("or.b32 %0, %0, %1;" : "+r"(x) : "r"(zero))
__device__ __forceinline__ void wgmma32(float (&d)[4][4], const uint32_t (&a)[4], unsigned long long ds) {
    asm volatile("wgmma.mma_async.sync.aligned.m64n32k16.f32.f16.f16 {%0,%1,%2,%3,%4,%5,%6,%7,%8,%9,%10,%11,%12,%13,%14,%15}, {%16,%17,%18,%19}, %20, 1, 1, 1, 0;"
        : "+f"(d[0][0]), "+f"(d[0][1]), "+f"(d[0][2]), "+f"(d[0][3]), "+f"(d[1][0]), "+f"(d[1][1]), "+f"(d[1][2]), "+f"(d[1][3]),
          "+f"(d[2][0]), "+f"(d[2][1]), "+f"(d[2][2]), "+f"(d[2][3]), "+f"(d[3][0]), "+f"(d[3][1]), "+f"(d[3][2]), "+f"(d[3][3])
        : "r"(a[0]), "r"(a[1]), "r"(a[2]), "r"(a[3]), "l"(ds));
}

__device__ __forceinline__ void finish(const Params& prm, uint32_t fo, uint32_t oo, const float (&v)[3], float cnt) {
    float x, y, z, w;
    asm volatile("atom.relaxed.gpu.global.add.v4.f32 {%0,%1,%2,%3}, [%4], {%5,%6,%7,%8};" : "=f"(x), "=f"(y), "=f"(z), "=f"(w)
                 : "l"((char*)prm.gs->fin + fo), "f"(v[0]), "f"(v[1]), "f"(v[2]), "f"(cnt) : "memory");
    if (w + cnt == 3.f * (NCL + 1)) {
        __nv_bfloat16* op = (__nv_bfloat16*)((char*)prm.out + oo);
        op[0] = __float2bfloat16(x + v[0]); op[1] = __float2bfloat16(y + v[1]); op[2] = __float2bfloat16(z + v[2]);
    }
}

__global__ void __cluster_dims__(CS, 1, 1) __launch_bounds__(NTHR, 1)
fused_kernel(const __grid_constant__ Params prm, const __grid_constant__ CUtensorMap tmG, const __grid_constant__ CUtensorMap tmU,
             const __grid_constant__ CUtensorMap tmD, const __grid_constant__ CUtensorMap tmO, const __grid_constant__ CUtensorMap tmX, const __grid_constant__ CUtensorMap tmH)
{
    extern __shared__ __align__(1024) unsigned char smem[];
    const int tid = threadIdx.x, lane = tid & 31, warp = __shfl_sync(~0u, tid >> 5, 0);
    const int c = blockIdx.x >> 3, q = blockIdx.x & 7;
    const int nslot = (c < NCL - 1) ? 5 : 2;
    const int d0 = 40 * c;
    const uint32_t sb = opaque((uint32_t)__cvta_generic_to_shared(smem));
    const uint32_t mb = sb + SM_MB;
    Scratch& g_s = *prm.gs;
    const unsigned& zero = prm.zero;
    const uint32_t dch2 = min(d0 + q + ((tid >> 4) & ~7), D_ - 1) * 2;
    uint32_t pv[6], pLdt;
    const uint32_t pofs = opaque(dch2 * 128 + (tid & 127) * 2);
    pLdt = ldg16((const char*)prm.logdt + dch2);
#pragma unroll
    for (int i = 0; i < 2; i++) pv[i] = ldg16((const char*)prm.prm6[i] + pofs);
    STAMP(0);

    if (warp >= 20) {
        unsigned epoch = 0;
        if (warp == 20) {
            if (lane == 0) {
#pragma unroll
                for (int i = 0; i < 13; i++)
                    asm volatile("mbarrier.init.shared::cta.b64 [%0], %1;" :: "r"(mb + i * 8), "r"((i == MB_R || i < 2) ? 2 : i < 5 ? (nslot + 1) / 3 : i == MB_Y ? 1 + 4 * nslot : 1) : "memory");
                asm volatile("fence.mbarrier_init.release.cluster;" ::: "memory");
                arm(mb + MB_W1 * 8, 92160); arm(mb + MB_W2 * 8, nslot * 9216); arm(mb + MB_KEY * 8, 256); arm(mb + MB_GU * 8, nslot * 1024); arm(mb + MB_T * 8, 576 * XW);
                const int bytes = max(min(18, L_ - 18 * (int)blockIdx.x), 1) * (D_ * 2);
                arm(mb + MB_R * 8, bytes);
            }
            __syncwarp();
        } else if (warp == 22) {
            epoch = ld_rlx(&g_s.epoch);
            if (lane < 18 ? 18 * c + lane < 256 : lane < 31) (lane < 18 ? &g_s.acc[256 * q + 18 * c] : &g_s.fin[13 * (int)blockIdx.x - 18])[lane] = make_float4(0.f, 0.f, 0.f, 0.f);
        } else if (warp == 23 && lane == 0) asm volatile("prefetch.tensormap [%0];" :: "l"(&tmX) : "memory");
        asm volatile("barrier.cluster.arrive.relaxed.aligned;" ::: "memory");
        bar_sync(12, NTHR);
        uint4 wv = make_uint4(0, 0, 0, 0), wv2, wv3;
        if (warp == 22) {
            if (lane == 0) { sts32(sb + SM_SC + 28, epoch); asm volatile("mbarrier.arrive.shared::cta.b64 _, [%0];" :: "r"(mb + MB_R * 8) : "memory"); }
            epoch++;
            asm volatile("fence.acq_rel.gpu;" ::: "memory");
            __syncwarp();
            if (lane == 0) asm volatile("red.relaxed.gpu.global.add.u32 [%0], 1;" :: "l"(&g_s.zcnt) : "memory");
            STAMP(1);
            wv2 = ldg128((const uint4*)prm.wr + lane); wv3 = ldg128((const uint4*)prm.wr + 32 + lane);
            if (lane < 8) wv = ldg128((const uint4*)prm.wr + 64 + lane);
            if (lane < 5) {
                uint4 v = make_uint4(0, 0, 0, 0);
                if (lane < nslot) v = ldg128((const uint4*)(prm.wr + d0) + lane);
                sts128(sb + SM_DW + lane * 16, v.x, v.y, v.z, v.w);
            }
            __syncwarp();
            if (lane < 5) asm volatile("mbarrier.arrive.shared::cta.b64 _, [%0];" :: "r"(mb + (MB_X + lane) * 8) : "memory");
        }
        if (warp == 21) {
            if (lane == 0) { asm volatile("prefetch.tensormap [%0];" :: "l"(&tmG) : "memory"); asm volatile("prefetch.tensormap [%0];" :: "l"(&tmU) : "memory"); asm volatile("prefetch.tensormap [%0];" :: "l"(&tmD) : "memory"); }
            __syncwarp();
            const float dsk = bf_lo(ldg16(prm.dskip + min(d0 + 2 * (lane & 28) + q, D_ - 1)));
            bar_sync(0, 672);
            {
                const uint2 m = lds64(sb + SM_KG + min(lane, 19) * 8);
                unsigned Em = max(m.x, __shfl_xor_sync(~0u, m.x, 1));
                Em = max(Em, __shfl_xor_sync(~0u, Em, 2));
                Em = max(Em, min(__float_as_uint(fabsf(dsk) * (1.f / 8192.f)) >> 23, 253u));
                const float f = __uint_as_float(max((int)(127 + m.x - Em), 0) << 23);
                float s0 = (float)(int)m.y * f;
                s0 += __shfl_xor_sync(~0u, s0, 1); s0 += __shfl_xor_sync(~0u, s0, 2);
                if (lane < 20) {
                    sts16(sb + SM_RK + lane * 2, pack_f16(f, 0.f));
                    sts32(sb + SM_SC + (lane & 28), Em * 0x00800080u);
                    put16(sb + SM_PN + (lane >> 2) * PN_SZ, pack_f16(s0 * (1.f / 16777216.f) + dsk * __uint_as_float((254u - Em) << 23), 0.f));
                }
                __syncwarp();
            }
            bar_sync(15, 672);
            asm volatile("fence.proxy.async.shared::cta;" ::: "memory");
#pragma unroll 1
            for (int i = 0; i < 24; i++) {
                if (lane == 0) tma2d(sb + SM_WG + i * 3840, i < 12 ? &tmG : &tmU, 320 * c + 8 * nslot * q, 48 * (i < 12 ? i : i - 12), mb + MB_W1 * 8);
            }
            STAMP(1);
        } else {
        if (warp == 20) {
            if (lane == 0) {
                asm volatile("cp.async.bulk.shared::cluster.global.mbarrier::complete_tx::bytes [%0], [%1], %2, [%3];"
                             :: "r"(sb + SM_ROW), "l"(prm.x + min(18 * (int)blockIdx.x, L_ - 1) * D_), "r"(max(min(18, L_ - 18 * (int)blockIdx.x), 1) * (D_ * 2)), "r"(mb + MB_R * 8) : "memory");
            }
            __syncwarp();
            mbar_wait(mb + MB_R * 8);
            if (lane == 0) {
                asm volatile("cp.async.bulk.tensor.5d.shared::cluster.global.mbarrier::complete_tx::bytes [%0], [%1, {%3, %4, %5, %5, %5}], [%2];"
                             :: "r"(sb + SM_XTL), "l"(&tmX), "r"(mb + MB_T * 8), "r"(d0 & ~15), "r"(8 * q), "r"(0) : "memory");
            }
            STAMP(6);
        }
        {
            const int idx = lane * 3 + max(warp - 21, 0), sl = nslot - 1 - (idx >> 3), pe = (idx + q + 1) & 7;
            const uint32_t rb_ = mapa(sb, pe);
            uint32_t cd = rb_ + SM_U + 128 + q * UP + sl * US, cs = sb + SM_XT + 128 + (q & 3) * 16 + pe * YP + sl * YS, cm = rb_ + SM_MB + (MB_X + sl) * 8;
            int act = sl < 0 ? 0 : pe == q ? -1 : 1;
            PIN(cd); PIN(cs); PIN(cm); PIN(act);
            asm volatile("barrier.cluster.wait.aligned;" ::: "memory");
            mbar_wait(mb + MB_R * 8);
            bar_sync(13, 608);
            asm volatile("fence.proxy.async.shared::cta;" ::: "memory");
            if (act < 0) arm(cm, 7 * 512);
            __syncwarp();
            if (act > 0)
                asm volatile("cp.async.bulk.shared::cluster.shared::cta.mbarrier::complete_tx::bytes [%0], [%1], 512, [%2];" :: "r"(cd), "r"(cs), "r"(cm) : "memory");
        }
        STAMP(1);
        if (warp == 20 && lane == 0) { asm volatile("prefetch.tensormap [%0];" :: "l"(&tmO) : "memory"); asm volatile("prefetch.tensormap [%0];" :: "l"(&tmH) : "memory"); }
        if (warp == 22) {
            __syncwarp();
            mbar_wait(mb + (MB_X + 1) * 8);
            const uint32_t old = (epoch & 1) ? 0u : 0x40004000u;
#pragma unroll
            for (int t = 0; t < 2; t++)
                if ((lane & 7) < 6) g_s.cand[((q * 8 + 4 * t + (lane >> 3)) * NCL + c) * 6 + (lane & 7)] = make_uint4(old, old, old, old);
            float a[4] = {0.f, 0.f, 0.f, 0.f};
            const uint32_t one = 0x3F803F80u;
            mma_bf16(a, one, one, one, one, wv.x, wv.y);  mma_bf16(a, one, one, one, one, wv.z, wv.w);
            mma_bf16(a, one, one, one, one, wv2.x, wv2.y); mma_bf16(a, one, one, one, one, wv2.z, wv2.w);
            mma_bf16(a, one, one, one, one, wv3.x, wv3.y); mma_bf16(a, one, one, one, one, wv3.z, wv3.w);
            float s = a[0] + a[1];
            s += __shfl_xor_sync(~0u, s, 1); s += __shfl_xor_sync(~0u, s, 2);
            stsf(sb + SM_SC + 24, s);
            __syncwarp();
            if (lane == 0) {
                int n = 0;
                while ((int)(ld_acq(&g_s.zcnt) - epoch * NCTA) < 0 && ++n < SPIN_LIMIT) __nanosleep(200);
                arm(mb + MB_Y * 8, 8 * 512 * nslot);
                if (blockIdx.x == 0) g_s.epoch = epoch;
            }
            STAMP(2);
        }
        if (warp == 23) {
#pragma unroll 1
            for (int kk = nslot - 1; kk >= 0; kk--) {
                __syncwarp();
                bar_sync(6 + kk, 160);
                if (kk < 2) mbar_wait(mb + MB_W1 * 8);
                if (lane == 0) { asm volatile("fence.proxy.async.shared::cta;" ::: "memory"); tma2d(sb + SM_FAR + kk * FAR_SZ, &tmD, 72 * q, 320 * c + 64 * kk, mb + MB_W2 * 8); }
            }
        }
        }
        __syncwarp();
        if (warp == 20) {
            bar_sync(11, 672);
            asm volatile("fence.proxy.async.shared::cta;" ::: "memory");
            bar_sync(14, 768);
            if (elect()) {
                asm volatile("cp.async.bulk.tensor.5d.global.shared::cta.bulk_group [%0, {%2, %4, %4, %4, %3}], [%1];" :: "l"(&tmH), "r"(sb + SM_XT + 16384), "r"(d0 + ((c & 1) ? 0 : 32)), "r"(8 * q), "r"(0) : "memory");
                asm volatile("cp.async.bulk.tensor.5d.global.shared::cta.bulk_group [%0, {%2, %4, %4, %4, %3}], [%1];" :: "l"(&tmO), "r"(sb + SM_XT), "r"(d0 + (c & 1) * 8), "r"(8 * q), "r"(0) : "memory");
                asm volatile("cp.async.bulk.commit_group;" ::: "memory");
            }
        } else bar_sync(14, 768);
        __syncwarp();
        const uint32_t ft = (tid >> 4) & 7, fj = d0 / 3 + (lane & 15), tok = ~lds32(sb + SM_SEL + ft * 8) & 2047;
        float v[3], cnt = 0.f;
#pragma unroll
        for (int i = 0; i < 3; i++) {
            const uint32_t cl = 3 * fj + i - d0, cf = cl - (c & 1) * 8;
            const bool ok = cl < 8 * nslot && ((tok >> 3) & 7) == q;
            const uint32_t u = lds16(sb + SM_XT + (cf < 32 ? tslot(tok) * 64 + cf * 2 : 16384 + tslot(tok) * 16 + (cl & 7) * 2));
            v[i] = ok ? __uint_as_float(u << 16) : 0.f;
            if (ok) cnt += 1.f;
        }
        if (warp == 20 && elect()) {
            asm volatile("cp.async.bulk.wait_group 0;" ::: "memory");
            asm volatile("fence.proxy.async.global;" ::: "memory");
            asm volatile("mbarrier.arrive.shared::cta.b64 _, [%0];" :: "r"(mb + MB_OUT * 8) : "memory");
        }
        __syncwarp();
        mbar_wait(mb + MB_OUT * 8);
        STAMP(5);
        if (cnt != 0.f) finish(prm, (ft * 192 + fj) * 16, (tok * D_ + 3 * fj) * 2, v, cnt);
        return;
    }

    const int g = lane >> 2, cq = lane & 3;
    const int k = warp >> 2, wq = warp & 3;
    const int trow = 18 * blockIdx.x + warp;
    const bool rowact = warp < 18 && trow < L_;
#pragma unroll
    for (int i = 2; i < 6; i++) pv[i] = ldg16((const char*)prm.prm6[i] + pofs);
    const int tn = 16 * (warp & 15) + g;
    uint32_t xa[5], xb[5];
    asm volatile("barrier.cluster.arrive.relaxed.aligned;" ::: "memory");
    char* const st1p = (char*)g_s.st1 + opaque(((((trow >> 3) & 7) * 256 + ((trow >> 6) & 31) * 8 + (trow & 7)) * 8 + lane) * 4);
    const bool pub = rowact && (lane & 0x1B) == 0;
    if (pub) st_rlx128(st1p, 0, 0, 0, 0);
    {
        const uint32_t za = sb + SM_P + tid * 16;
        sts128(za, 0, 0, 0, 0);
        if (tid < (SM_MISC - SM_P) / 16 - 640) sts128(za + 10240, 0, 0, 0, 0);
        sts128(sb + SM_U + ((tid >> 3) & 7) * UP + k * US + (lane & 7) * 16, 0, 0, 0, 0);
    }
    bar_sync(12, NTHR);
    const uint32_t dep = lds32(sb + SM_P);
#define PV(x) __uint_as_float(__byte_perm(dep, x, 0x5410))
    STAMP(1);
    const uint32_t fb = sb + SM_FAR + k * FAR_SZ;
    const uint32_t pn = sb + SM_PN + k * PN_SZ, pf = sb + SM_PF + k * PF_SZ;
    unsigned epoch, t258;
    {
        const uint32_t kb = fb + wq * 3072;
        const uint32_t kl = kb + lane * 16;
        uint32_t Af[4][4];
        float sr, si, z1r, z1i, z2r, z2i, z4r, z4i, hr, hi_;
        {
            const float dt = bfr(ex2f(PV(pLdt) * 1.4426950408889634f));
            const float e2 = dt * PV(pv[0]) * 1.4426950408889634f, an = dt * PV(pv[1]);
            float ar, ai, br, bi, cr, ci, dr, di;
            { const float m = ex2f(e2 * 8.f); ar = m * __cosf(an * 8.f); ai = m * __sinf(an * 8.f); }
            csq(br, bi, ar, ai); csq(cr, ci, br, bi); csq(dr, di, cr, ci);
            const H2C m4 = splat(cr, ci);
            {
                float r3, i3;
                cmul(r3, i3, ar, ai, br, bi);
                expand4(kl, kl + 1024, pack_f16(1.f, ar), pack_f16(br, r3), pack_f16(0.f, ai), pack_f16(bi, i3), m4);
            }
            expand8(kl + 512, kl + 1536, dr, di, ar, ai, br, bi, m4);
            { const float m = ex2f(e2); z1r = m * __cosf(an); z1i = -m * __sinf(an); }
            cexp_s(hr, hi_, e2 * 128.f, an * (-128.f * 0.15915494309189535f));
            csq(z2r, z2i, z1r, z1i); csq(z4r, z4i, z2r, z2i);
            const uint32_t dep2 = lds32(sb + SM_P + 4);
#define PW(x) __uint_as_float(__byte_perm(dep2, x, 0x5410))
            cmul(sr, si, PW(pv[4]), PW(pv[5]), dt * PW(pv[2]), dt * PW(pv[3]));
            const unsigned E = min(max(__reduce_max_sync(~0u, __float_as_uint(fmaxf(fabsf(sr), fabsf(si)))) >> 23, 1u), 253u);
            const float sc = __uint_as_float((254u - E) << 23);
            sr *= sc; si *= -sc;
            sts64(sb + SM_KG + warp * 8, E, __reduce_add_sync(~0u, __float2int_rn(sr * 16777216.f)));
        }
        __syncwarp();
#pragma unroll
        for (int ks = 0; ks < 4; ks++) ldsm4t(Af[ks], kb + (lane >> 3) * 512 + (lane & 7) * 16 + ks * 128);
        STAMP(2);
        const uint32_t la = kb + ((lane >> 3) & 1) * 512 + (lane >> 4) * 128 + (lane & 7) * 16;
        uint32_t b0[4], b1[4], b2[4], b3[4];
        auto ln1 = [&]() {
        mbar_wait(mb + MB_R * 8);
        epoch = lds32(sb + SM_SC + 28) + 1;
        {
            const uint32_t ra = sb + SM_ROW + warp * (D_ * 2);
            const uint4 r0 = lds128(ra + lane * 16), r1 = lds128(ra + 512 + lane * 16);
            const uint32_t rx[9] = {r0.x, r0.y, r0.z, r0.w, r1.x, r1.y, r1.z, r1.w, lds32(ra + 1024 + lane * 4)};
            float a0 = bf_lo(rx[0]), a1 = bf_hi(rx[0]), c0 = a0 * a0, c1 = a1 * a1;
#pragma unroll
            for (int i = 1; i < 9; i++) { const float l = bf_lo(rx[i]), h = bf_hi(rx[i]); a0 += l; a1 += h; c0 = fmaf(l, l, c0); c1 = fmaf(h, h, c1); }
            a0 += a1; c0 += c1;
            float s1 = ((lane & 1) ? c0 : a0) + __shfl_xor_sync(~0u, (lane & 1) ? a0 : c0, 1);
#pragma unroll
            for (int o = 2; o < 32; o <<= 1) s1 += __shfl_xor_sync(~0u, s1, o);
            const float s2 = __shfl_xor_sync(~0u, s1, 1);
            const uint32_t ms = ln_stats(s1, s2);
            const uint32_t p0 = __byte_perm(ms, epoch | 0x8000u, 0x5410), p1 = rsplit(rcpf(bf_hi(ms)));
            if (pub) st_rlx128(st1p, p0, p1, p0, p1);
        }
        mbar_wait(mb + MB_R * 8);
        STAMP(1);
        };
        const uint4* sp = &g_s.st1[(256 * q + tn) * 2];
        uint2 sa, sc;
        auto poll = [&]() { sa = ld_rlx64(sp); sc = ld_rlx64(sp + 16); };
        auto norm = [&]() {
        STAMP(3);
        if (warp < 16) {
            uint32_t va[5], vc[5];
            poll();
            mbar_wait(mb + MB_T * 8);
            {
                const uint32_t xt = sb + SM_XTL + (c & 1) * 16 + (36 * (warp & 7) + 9 * (warp >> 3) + g) * (2 * XW);
                uint4 a4 = lds128(xt + cq * 16), b4 = lds128(xt + cq * 16 + 36 * XW);
                va[0] = a4.x; va[1] = a4.y; va[2] = a4.z; va[3] = a4.w; va[4] = lds32(xt + 64 + cq * 4);
                vc[0] = b4.x; vc[1] = b4.y; vc[2] = b4.z; vc[3] = b4.w; vc[4] = lds32(xt + (64 + 36 * XW) + cq * 4);
            }
            const int d4 = 2 * (lane >> 3) + (lane & 1), d1_ = lane & 7;
            const uint32_t own = SM_U + 128 + q * (UP - YP), oth = SM_XT + 128 + (q & 3) * 16;
            uint32_t a4 = sb + warp * 32 + d4 * YP + (d4 == q ? own : oth) + ((lane & 7) >> 1) * YS;
            uint32_t a1 = sb + warp * 32 + d1_ * YP + (d1_ == q ? own : oth) + 4 * YS + (lane & 8) * 2;
            PIN(a4); PIN(a1);
            uint32_t tag = __byte_perm(epoch | 0x8000u, 0, 0x1010);
            PIN(tag);
            mbar_wait(mb + MB_T * 8);
            int n = 0;
            while (__byte_perm(sa.x, sc.x, 0x7632) != tag && ++n < SPIN_LIMIT) poll();
            STAMP(4);
#pragma unroll
            for (int i = 0; i < 5; i++) {
                va[i] = norm2(va[i], sa.x, sa.y); va[i] = pack_f16(bf_lo(va[i]), bf_hi(va[i]));
                vc[i] = norm2(vc[i], sc.x, sc.y); vc[i] = pack_f16(bf_lo(vc[i]), bf_hi(vc[i]));
            }
            stsm4t(a4, va[0], va[1], va[2], va[3]); stsm4t(a4 + 16, vc[0], vc[1], vc[2], vc[3]); stsm2t(a1, va[4], vc[4]);
            bar_arrive(13, 608);
            {
            const uint32_t xh = sb + SM_XTL + (c & 1) * 16 + (9 * __byte_perm(0x12100200, 0x13110301, g) + 72 * (warp & 1) + (warp >> 1)) * (2 * XW);
            const uint4 c4 = lds128(xh + cq * 16), d4_ = lds128(xh + cq * 16 + 72 * XW);
            xa[0] = c4.x; xa[1] = c4.y; xa[2] = c4.z; xa[3] = c4.w; xa[4] = lds32(xh + 64 + cq * 4);
            xb[0] = d4_.x; xb[1] = d4_.y; xb[2] = d4_.z; xb[3] = d4_.w; xb[4] = lds32(xh + (64 + 72 * XW) + cq * 4);
            }
        }
        STAMP(5);
        __syncwarp();
        bar_sync(15, 672);
        Af[0][0] |= lds32(sb + SM_P);
        };
        cmul(sr, si, sr, si, z1r, z1i);
        {
            const H2C h4 = splat(z4r, z4i);
            expand8(kl, kl + 512, sr, si, z1r, z1i, z2r, z2i, h4);
            cmul(sr, si, sr, si, hr, hi_);
            expand8(kl + 1024, kl + 1536, sr, si, z1r, z1i, z2r, z2i, h4);
        }
        __syncwarp();
        ldsm4t(b0, la); ldsm4t(b1, la + 256); ldsm4t(b2, la + 1024); ldsm4t(b3, la + 1280);
        cmul(z1r, z1i, z1r, z1i, hr, hi_);
        cmul(sr, si, sr, si, z1r, z1i);
        expand8(kl, kl + 512, sr, si, z2r, z2i, z4r, z4i, splat(hr, hi_));
        asm volatile("barrier.cluster.wait.aligned;" ::: "memory");
        bar_arrive(0, 672);
        ln1();
        csq(z1r, z1i, z1r, z1i);
        cmul(sr, si, sr, si, z1r, z1i);
        csq(z2r, z2i, hr, hi_);
        expand8(kl + 1024, kl + 1536, sr, si, z4r, z4i, hr, hi_, splat(z2r, z2i));
        csq(z1r, z1i, z1r, z1i);
        cmul(sr, si, sr, si, z1r, z1i);
        csq(z4r, z4i, z2r, z2i);
        expand8(kl + 2048, kl + 2560, sr, si, hr, hi_, z2r, z2i, splat(z4r, z4i));
        norm();
        {
            uint32_t c0[4], c1[4], c2[4], c3[4], e0[4], e1[4];
            float t[6][4];
            ldsm4t(c0, la); ldsm4t(c2, la + 1024);
            mma_f16_z(t[0], Af[0], b0[0], b0[1]);
            const uint32_t lb = la | (__float_as_uint(t[0][0]) & zero);
            mma_f16_z(t[1], Af[0], b2[0], b2[1]); mma_f16_z(t[2], Af[0], c0[0], c0[1]); mma_f16_z(t[3], Af[0], c2[0], c2[1]);
            ldsm4t(e0, lb + 2048); ldsm4t(c1, lb + 256); ldsm4t(c3, lb + 1280); ldsm4t(e1, lb + 2304);
            mma_f16(t[0], Af[1], b0[2], b0[3]); mma_f16(t[1], Af[1], b2[2], b2[3]); mma_f16(t[2], Af[1], c0[2], c0[3]); mma_f16(t[3], Af[1], c2[2], c2[3]);
            mma_f16(t[0], Af[2], b1[0], b1[1]); mma_f16(t[1], Af[2], b3[0], b3[1]);
            mma_f16_z(t[4], Af[0], e0[0], e0[1]); mma_f16_z(t[5], Af[1], e0[2], e0[3]);
            mma_f16(t[2], Af[2], c1[0], c1[1]); mma_f16(t[3], Af[2], c3[0], c3[1]);
            mma_f16(t[4], Af[2], e1[0], e1[1]); mma_f16(t[5], Af[3], e1[2], e1[3]);
            mma_f16(t[0], Af[3], b1[2], b1[3]); mma_f16(t[1], Af[3], b3[2], b3[3]); mma_f16(t[2], Af[3], c1[2], c1[3]); mma_f16(t[3], Af[3], c3[2], c3[3]);
#pragma unroll
            for (int i = 0; i < 4; i++) t[4][i] += t[5][i];
            stsm4(kl + 1024, pack_f16(t[0][0], t[0][1]), pack_f16(t[0][2], t[0][3]), pack_f16(t[1][0], t[1][1]), pack_f16(t[1][2], t[1][3]));
            stsm2(kl + 1536, pack_f16(t[2][0], t[2][1]), pack_f16(t[2][2], t[2][3]));
            sts64(kb + lane * 8 + 1792, pack_f16(t[3][1], t[3][0]), pack_f16(t[3][3], t[3][2]));
            sts64(kb + lane * 8 + 2048, pack_f16(t[4][1], t[4][0]), pack_f16(t[4][3], t[4][2]));
        }
        bar_sync(1 + k, 128);
        const uint2 rr = lds64(opaque(sb + SM_RK + k * 8));
        const int tq = (wq + k + 2) & 3;
        const uint32_t ra = lane * 8 + opaque(fb + (tq == 1 ? 2048 : tq * 256 + 1024));
        auto comb = [&](uint32_t a, uint32_t& x, uint32_t& y) {
            const uint2 p0 = lds64(a), p1 = lds64(a + 3072), p2 = lds64(a + 6144), p3 = lds64(a + 9216);
            x = comb4(p0.x, p1.x, p2.x, p3.x, rr.x, rr.y); y = comb4(p0.y, p1.y, p2.y, p3.y, rr.x, rr.y);
        };
        uint32_t w0, w1;
        comb(ra, w0, w1);
        const bool last = lane == 31;
        if (tq == 0) {
            uint32_t v0, v1;
            comb(ra + 256, v0, v1);
            const uint32_t n0 = __shfl_sync(~0u, lane ? w0 : v0, lane + 1);
            uint32_t n1 = __shfl_sync(~0u, v0, lane + 1);
            if (last) n1 = v1 >> 16;
            sts128(pn + 12 + lane * 16, __byte_perm(w1, w0, 0x7610), __byte_perm(w1, 0, 0x1032), __byte_perm(n0, w1, 0x7610), __byte_perm(n0, 0, 0x1032));
            sts128(pn + 524 + lane * 16, __byte_perm(v1, v0, 0x7610), __byte_perm(v1, 0, 0x1032), __byte_perm(n1, v1, 0x7610), __byte_perm(n1, 0, 0x1032));
            if (lane == 0) { sts16(pn + 4, w0); sts32(pn + 8, __byte_perm(w0, 0, 0x1032)); }
        } else if (tq == 1) {
            const uint32_t ph = pf + P_H7 + (g & 1) * (2 * P_HS) + cq * 64 + (g >> 1) * 4 + (cq & 2) * 16, sw = (cq & 2) ? 0x3210 : 0x1032;
            w0 = __byte_perm(hmul2(w0, 0x18001800u), 0, sw); w1 = __byte_perm(hmul2(w1, 0x18001800u), 0, sw);
            const uint32_t pi = ph + 32 - (cq & 2) * 32;
            put16(ph, w0); put16(pi, w0 >> 16); put16(ph + 16, w1); put16(pi + 16, w1 >> 16);
        } else if (tq == 2) {
            uint32_t n = __shfl_sync(~0u, w0, lane == 30 ? 1 : lane + 2);
            if (last) { put16(pf, hmul2(w1, 0x18001800u) >> 16); w1 = hadd2(w1, hneg2(__byte_perm(w1, 0, 0x3232))); n = 0; }
            const bool od = lane & 1;
            const uint32_t pa = pn + 1036 + (lane >> 1) * 32 + (od ? 528 : 0), pb = pa + (od ? -16 : 16);
            const uint32_t u0 = od ? w1 : w0, x0 = od ? n : w1, u1 = od ? w0 : w1, x1 = od ? w1 : n;
            const uint32_t b0 = __byte_perm(u0, 0, 0x3232), b1 = __byte_perm(u1, 0, 0x3232);
            sts128(pa, __byte_perm(u0, 0, 0x1032), b0, b0, __byte_perm(x0, u0, 0x7610));
            sts128(pb, __byte_perm(u1, 0, 0x1032), b1, b1, __byte_perm(x1, u1, 0x7610));
        } else {
            const uint32_t pa = pf + ((g & 1) ? 3 * P_GS : P_GS) + cq * 32 + (g >> 1) * 4;
            const uint32_t pb = pa + ((g & 1) ? 4 - 3 * P_GS : P_GS);
            w0 = hmul2(w0, 0x18001800u); w1 = hmul2(w1, 0x18001800u);
            put16(pa, w0 >> 16); put16(pb, w0); put16(pa + 16, w1 >> 16); put16(pb + 16, w1);
            if (last) put16(pf + P_H7 + P_HS, w1);
        }
        bar_sync(1 + k, 128);
        t258 = w0;
    }
    STAMP(6);

    mbar_wait(mb + (MB_X + k) * 8);
    STAMP(7);
    if (k < nslot) {
        const int role = (wq + k) & 3;
        const uint32_t ub = sb + SM_U + k * US + 128;
        const uint32_t l16 = lane * 16, tz = (lane & 28) - 8 * cq, tz4 = tz * 4;
        if (role) {
            const uint32_t al = cq * (2 * UP + 32) + tz4, au = opaque(ub + (3 - role) * 128), a1 = al + au, a0 = (cq ? al : al + (8 * UP - 16)) + au - 2 * UP;
            const uint4 q0 = lds128(a0), q1 = lds128(a0 + UP), q2 = lds128(a1), q3 = lds128(a1 + UP);
            const uint32_t U[16] = {q0.x, q0.y, q0.z, q0.w, q1.x, q1.y, q1.z, q1.w, q2.x, q2.y, q2.z, q2.w, q3.x, q3.y, q3.z, q3.w};
            uint32_t V[14], Q[14], R4[12], T[8];
#pragma unroll
            for (int i = 2; i < 14; i++) { V[i] = __byte_perm(U[i], U[i + 1], 0x5432); Q[i] = hadd2(U[i], V[i]); }
            const uint32_t rb = l16 + opaque(fb + (3 - role) * 512);
#pragma unroll
            for (int i = 0; i < 8; i++) T[i] = hadd2(V[5 + i], Q[6 + i]);
            sts128(rb + F_E3, T[0], T[1], T[2], T[3]); sts128(rb + F_O3 + 16, T[4], T[5], T[6], T[7]);
            asm volatile("{ .reg .pred p; setp.ne.u32 p, %10, 1; @p st.shared.v4.u32 [%0], {%2,%3,%4,%5}; @p st.shared.v4.u32 [%1], {%6,%7,%8,%9}; }"
                         :: "r"(rb + F_E2), "r"(rb + F_O2), "r"(Q[6]), "r"(Q[7]), "r"(Q[8]), "r"(Q[9]), "r"(Q[10]), "r"(Q[11]), "r"(Q[12]), "r"(Q[13]), "r"(role) : "memory");
#pragma unroll
            for (int i = 2; i < 12; i++) R4[i] = hadd2(Q[i], Q[i + 1]);
#pragma unroll
            for (int i = 0; i < 8; i++) T[i] = hadd2(R4[3 + i], U[5 + i]);
            sts128(rb + F_O5, T[0], T[1], T[2], T[3]); sts128(rb + F_E5, T[4], T[5], T[6], T[7]);
            if (role != 1) {
                uint32_t S[8];
#pragma unroll
                for (int i = 0; i < 8; i++) S[i] = hadd2(R4[2 + i], i < 7 ? T[i + 1] : hadd2(R4[11], U[13]));
                sts128(rb + F_O9, S[0], S[1], S[2], S[3]); sts128(rb + F_E9 + 16, S[4], S[5], S[6], S[7]);
#pragma unroll
                for (int i = 0; i < 8; i++) S[i] = hadd2(T[i], hadd2(V[2 + i], V[5 + i]));
                sts128(rb + F_E7, S[0], S[1], S[2], S[3]); sts128(rb + F_O7, S[4], S[5], S[6], S[7]);
            }
        } else if (lane == 0) {
            const uint4 m = lds128(ub + 23 * 16 + 7 * UP);
            const uint32_t U[6] = {lds32(ub + 23 * 16 + 6 * UP + 12), m.x, m.y, m.z, m.w, lds32(ub + 24 * 16)};
            uint32_t Q[5];
#pragma unroll
            for (int i = 0; i < 5; i++) Q[i] = hadd2(U[i], __byte_perm(U[i], U[i + 1], 0x5432));
            sts128(fb + F_O5 + 96 * 16, hadd2(hadd2(Q[0], Q[1]), U[2]), hadd2(hadd2(Q[1], Q[2]), U[3]), hadd2(hadd2(Q[2], Q[3]), U[4]), hadd2(hadd2(Q[3], Q[4]), U[5]));
            sts128(fb + F_O3, 0, 0, 0, 0); sts128(fb + F_E9, 0, 0, 0, 0);
            sts16(pn + 258 * 4, t258);
        }
        bar_sync(1 + k, 128);
        float acc[4][4];
        uint32_t Q[4][4];
        {
            const int h = role & 1, part = role >> 1;
            float fa[7][4];
            uint32_t B[3][4];
            const uint32_t po = tz + opaque(pf + part * (2 * P_GS)), ba = l16 + opaque(fb + (part == h ? 0 : F_O5 + h * 16));
#pragma unroll
            for (int s = 1; s >= 0; s--) {
#pragma unroll
                for (int i = 0; i < 3; i++) { Q[i][0] = lds32(po + (s * P_GS + i * 64)); if (i < 2) Q[i][1] = lds32(po + (s * P_GS + i * 64 + 32)); }
#pragma unroll
                for (int i = 0; i < 3; i++) ldsm4t(B[i], ba + (s * F_E3 + i * 512));
#pragma unroll
                for (int i = 0; i < 3; i++) { Q[i][3] = CP(Q[i][0]); if (i) Q[i][2] = CP(Q[i - 1][1]); }
                Q[0][2] = ZF(s ? tz : Q[0][0]); Q[2][1] = ZF(s ? l16 : Q[2][0]);
#pragma unroll
                for (int dl = 0; dl < 3; dl++)
#pragma unroll
                    for (int ap = 0; ap < 6 - dl; ap++) {
                        if (s == 1 && dl == 0) mma_f16_z(fa[ap + 1], Q[0], B[ap >> 1][2 * (ap & 1)], B[ap >> 1][2 * (ap & 1) + 1]);
                        else mma_f16(fa[ap + 1 + dl], Q[dl], B[ap >> 1][2 * (ap & 1)], B[ap >> 1][2 * (ap & 1) + 1]);
                    }
            }
#pragma unroll 1
            for (int s = role; s == 1; s++) {
                ldsm2t(B[0][0], B[0][1], fb + ((lane & 15) == 15 ? F_O5 : F_O3));
#pragma unroll
                for (int dl = 1; dl < 3; dl++) mma_f16(fa[dl], Q[dl], B[0][0], B[0][1]);
            }
            const uint32_t bh = l16 + opaque(fb + F_E7 + h * F_H + part * 2048), ph = tz + opaque(pf + P_H7 + part * (2 * P_HS));
#pragma unroll 1
            for (int s = part; s == 1; s++) {
                Q[2][1] = ZF(Q[2][3]); Q[2][2] = ZF(Q[2][2]); Q[2][0] = lds32(ph - P_HS);
                ldsm4t(B[0], bh - 1024); ldsm4t(B[1], bh - 512);
                Q[2][3] = CP(Q[2][0]);
#pragma unroll
                for (int ap = 0; ap < 4; ap++) mma_f16(fa[ap + 3], Q[2], B[ap >> 1][2 * (ap & 1)], B[ap >> 1][2 * (ap & 1) + 1]);
            }
            {
                Q[0][2] = ZF(tid);
#pragma unroll
                for (int i = 0; i < 4; i++) { Q[i][0] = lds32(ph + i * 64); Q[i][1] = lds32(ph + (i * 64 + 32)); }
                ldsm4t(B[0], bh); ldsm4t(B[1], bh + 512);
#pragma unroll
                for (int i = 0; i < 4; i++) { Q[i][3] = CP(Q[i][0]); if (i) Q[i][2] = CP(Q[i - 1][1]); }
#pragma unroll
                for (int dl = 0; dl < 4; dl++)
#pragma unroll
                    for (int ap = 0; ap < 4 - dl; ap++) mma_f16(fa[ap + 3 + dl], Q[dl], B[ap >> 1][2 * (ap & 1)], B[ap >> 1][2 * (ap & 1) + 1]);
            }
            const uint32_t da = (cq * 2048 + tz4) + opaque(fb + role * 128);
            bar_sync(1 + k, 128);
#pragma unroll
            for (int i = 1; i < 4; i++)
                stsm4(da + i * 512, pack_f16(fa[2 * i - 1][0], fa[2 * i - 1][1]), pack_f16(fa[2 * i - 1][2], fa[2 * i - 1][3]),
                      pack_f16(fa[2 * i][0], fa[2 * i][1]), pack_f16(fa[2 * i][2], fa[2 * i][3]));
            asm("shl.b32 %0, 0x6000, %1;" : "=r"(Q[0][0]) : "r"(tz4));
            Q[0][1] = ZF(Q[0][0]); Q[0][2] = ZF(tz4); Q[0][3] = CP(Q[0][0]);
            const uint32_t ra = l16 + opaque(fb + wq * 2016);
            acc[0][0] = acc[0][1] = acc[0][2] = acc[0][3] = 0.f;
            if (wq == 3) {
                const uint32_t uw = lds32(ub), kw = lds32(pf);
                const float2 uf = __half22float2(*(const __half2*)&uw);
                if ((lane | 4) == 31) acc[0][3] = (lane == 31 ? uf.x + uf.y : uf.x) * (__low2float(*(const __half2*)&kw) * 512.f);
            }
            bar_sync(1 + k, 128);
#pragma unroll
            for (int i = 1; i < 4; i++) {
                ldsm4(B[0], ra + i * 512);
                mma_f16_z(acc[i], Q[0], hadd2(B[0][0], B[0][2]), hadd2(B[0][1], B[0][3]));
            }
        }
        bar_arrive(6 + k, 160);
        STAMP(8);
        const uint32_t inv = lds32(opaque(sb + SM_SC + k * 4));
        const uint32_t yd = l16 + opaque(mapa(sb, 2 * wq) + (SM_XT + 128 + q * YP + k * YS + (k >> 2) * (q >> 1) * 16));
        {
            uint32_t pu = opaque(pn + 64 * (wq - 3));
#define pp (tz + pu)
            const uint32_t dlo = (((ub + 6 * UP) & 0x3FFFF) >> 4) | ((UP >> 4) << 16);
            uint32_t R[4][4];
            unsigned long long ds[4];
#pragma unroll
            for (int i = 0; i < 4; i++) asm volatile("mov.b64 %0, {%1, %2};" : "=l"(ds[i]) : "r"(dlo - i * (2 * UP >> 4)), "r"(8 | zero));
            auto loadQ = [&](uint32_t (&X)[4][4], uint32_t prev) {
#pragma unroll
                for (int i = 0; i < 4; i++) { X[i][0] = lds32(pp + i * 64); X[i][1] = lds32(pp + i * 64 + 32); }
                X[0][2] = CP(prev);
#pragma unroll
                for (int i = 0; i < 4; i++) { X[i][3] = CP(X[i][0]); if (i) X[i][2] = CP(X[i - 1][1]); }
                pu += 256;
            };
            auto issue = [&](uint32_t (&X)[4][4]) {
                asm volatile("wgmma.fence.sync.aligned;" ::: "memory");
#pragma unroll
                for (int i = 0; i < 4; i++) wgmma32(acc, X[i], ds[i]);
                asm volatile("wgmma.commit_group.sync.aligned;" ::: "memory");
#pragma unroll
                for (int i = 0; i < 4; i++) asm volatile("{ .reg .b32 l, h; mov.b64 {l, h}, %0; add.u32 l, l, %1; mov.b64 %0, {l, h}; }" : "+l"(ds[i]) : "r"(~zero));
            };
#pragma unroll
            for (int i = 0; i < 4; i++) {
                Q[i][0] = Q[i][1] = 0;
                if (wq + i >= 3) { Q[i][0] = lds32(pp + i * 64); Q[i][1] = lds32(pp + i * 64 + 32); }
            }
            Q[0][2] = CP(0);
#pragma unroll
            for (int i = 0; i < 4; i++) { Q[i][3] = CP(Q[i][0]); if (i) Q[i][2] = CP(Q[i - 1][1]); }
            pu += 256;
#pragma unroll 1
            for (int dl = 0; dl < 4; dl++) {
                issue(Q);
                asm volatile("wgmma.wait_group.sync.aligned 1;" ::: "memory");
                loadQ(R, Q[3][1]);
                issue(R);
                asm volatile("wgmma.wait_group.sync.aligned 1;" ::: "memory");
                loadQ(Q, R[3][1]);
            }
            issue(Q);
            asm volatile("wgmma.wait_group.sync.aligned 0;" ::: "memory");
        }
        const uint32_t pstep = mapa(sb, 1) - mapa(sb, 0), ym = mapa(mb + MB_Y * 8, 2 * wq);
#pragma unroll
        for (int e = 0; e < 2; e++)
            st_async4(yd + e * pstep, bmul2(pack_bf16(acc[0][2 * e], acc[0][2 * e + 1]), inv), bmul2(pack_bf16(acc[1][2 * e], acc[1][2 * e + 1]), inv),
                      bmul2(pack_bf16(acc[2][2 * e], acc[2][2 * e + 1]), inv), bmul2(pack_bf16(acc[3][2 * e], acc[3][2 * e + 1]), inv), ym + e * pstep);
        if (lane == 0) asm volatile("mbarrier.arrive.shared::cta.b64 _, [%0];" :: "r"(mb + MB_Y * 8) : "memory");
    }
    STAMP(9);
    uint32_t ha[5], hb[5];
    if (warp < 16) {
        const uint4 wk = lds128(sb + SM_DW + cq * 16);
        uint32_t sel[5] = {wk.x, wk.y, wk.z, wk.w, lds32(sb + SM_DW + 64 + cq * 4)}, sel2[5];
#pragma unroll
        for (int i = 0; i < 5; i++) {
            if (!(g & 1)) sel[i] = 0x3F803F80u;
            sel2[i] = sel[i]; PIN(sel2[i]);
        }
        uint32_t y4 = sb + SM_XT + 128 + warp * 32 + (2 * (lane >> 3) + (lane & 1)) * YP + ((lane & 7) >> 1) * YS;
        uint32_t y1 = sb + SM_XT + 128 + warp * 32 + (lane & 7) * YP + 4 * YS + (lane & 8) * 2 + (lane & 6) * 8;
        if (nslot != 5) {
            y1 = sb + SM_U;
            if (lane & 4) y4 = y1;
        }
        PIN(y4); PIN(y1);
        const uint32_t ao = (256 * q + tn) * 16;
        const uint32_t hta = opaque(sb + SM_HT + warp * 1024), htb = opaque(sb + SM_HT + 16384 + warp * 256);
        unsigned long long ap = (unsigned long long)((char*)g_s.acc + ao);
        asm volatile("add.u64 %0, %0, %1;" : "+l"(ap) : "l"((unsigned long long)zero));
        mbar_wait(mb + MB_Y * 8);
        STAMP(10);
        float ca[4] = {0.f, 0.f, 0.f, 0.f}, cb[4] = {0.f, 0.f, 0.f, 0.f};
        {
            uint32_t ya[4], yb[4], yc, yd;
            ldsm4t(ya, y4); ldsm4t(yb, y4 + 16); ldsm2t(yc, yd, y1);
#pragma unroll
            for (int i = 0; i < 4; i++) { ha[i] = badd2(xa[i], ya[i]); hb[i] = badd2(xb[i], yb[i]); }
            ha[4] = badd2(xa[4], yc); hb[4] = badd2(xb[4], yd);
        }
#pragma unroll
        for (int i = 0; i < 5; i++) { mma_bf16_k8(ca, ha[i], sel[i], ha[i]); mma_bf16_k8(cb, hb[i], sel2[i], hb[i]); }
        if (!(g & 1)) { ca[1] = ca[0]; cb[1] = cb[0]; }
        if (cq == (g >> 1)) {
            asm volatile("red.relaxed.gpu.global.add.v4.f32 [%0], {%1,%2,%3,%4};" :: "l"(ap), "f"(1.0f), "f"(ca[1]), "f"(ca[2]), "f"(ca[3]) : "memory");
            asm volatile("red.relaxed.gpu.global.add.v4.f32 [%0], {%1,%2,%3,%4};" :: "l"(ap + 128), "f"(1.0f), "f"(cb[1]), "f"(cb[2]), "f"(cb[3]) : "memory");
        }
        __syncwarp();
        mbar_wait(mb + MB_Y * 8);
#pragma unroll
        for (int i = 0; i < 4; i++) {
            asm volatile("or.b32 %0, %1, %2;" : "=r"(ha[i]) : "r"(ha[i]), "r"(zero));
            asm volatile("or.b32 %0, %1, %2;" : "=r"(hb[i]) : "r"(hb[i]), "r"(zero));
        }
        sts128(hta + lane * 16, ha[0], ha[1], ha[2], ha[3]); sts32(htb + lane * 4, ha[4]);
        sts128(hta + lane * 16 + 512, hb[0], hb[1], hb[2], hb[3]); sts32(htb + lane * 4 + 128, hb[4]);
        STAMP(11);
    }
    const int kq = warp / 5, mt = warp - 5 * kq;
    const int mi = lane >> 3, mr = lane & 7;
    const unsigned tk = (unsigned)tid / 72u, ck = tid - tk * 72;
    uint32_t A[9][4];
    auto loadA = [&]() {
        mbar_wait(mb + MB_W1 * 8);
        const uint32_t aa = sb + (mi & 1) * SM_WU + (8 * (mi >> 1) + mr) * 80 + (144 * 80 * kq + mt * 16);
#pragma unroll
        for (int s = 0; s < 9; s++) ldsm4t(A[s], aa + s * 1280);
    };
    const uint32_t par = (lds32(sb + SM_SC + 28) & 1) ? 0u : 0x40004000u;
    uint32_t go = (ck / 5u + ck) * 16, gs = sb + SM_SEL + 4 + (tk & 7) * 8;
    unsigned long long gb = (unsigned long long)((const char*)g_s.cand + go);
    uint32_t xs = sb + SM_XS + tk * 16 + tid * 16;
    asm volatile("add.u64 %0, %0, %1;" : "+l"(gb) : "l"((unsigned long long)zero));
    PIN(xs); PIN(gs);
    auto outtile = [&]() {
        const uint2 sa = lds64(sb + SM_ST + tn * 8), sbb = lds64(sb + SM_ST + tn * 8 + 64);
#pragma unroll
        for (int i = 0; i < 5; i++) { ha[i] = badd2(ha[i], norm2(ha[i], sa.x, sa.y)); hb[i] = badd2(hb[i], norm2(hb[i], sbb.x, sbb.y)); }
        const bool hf = (c & 1) && cq == 0;
        const uint32_t o16 = sb + SM_XT + (hf ? 16384 + tn * 16 : tn * 64 + (cq - (c & 1)) * 16), o4 = sb + SM_XT + ((c & 1) ? tn * 64 + 48 : 16384 + tn * 16) + cq * 4;
        sts128(o16, ha[0], ha[1], ha[2], ha[3]); sts32(o4, ha[4]);
        sts128(o16 + (hf ? 128 : 512), hb[0], hb[1], hb[2], hb[3]); sts32(o4 + ((c & 1) ? 512 : 128), hb[4]);
    };
    if (warp < 8) {
        const float wsum = ldsf(sb + SM_SC + 24);
        const uint32_t idx = 2047 - (512 * ((tid >> 1) & 3) + 128 * ((tid >> 3) & 3) + 64 * (tid & 1) + 8 * q + warp);
        uint32_t km0 = mapa(mb + MB_KEY * 8, 2 * cq), km1 = mapa(mb + MB_KEY * 8, 2 * cq + 1), ka0 = mapa(sb + SM_RK + q * 32, 2 * cq), ka1 = mapa(sb + SM_RK + q * 32, 2 * cq + 1);
        unsigned long long c0 = (unsigned long long)((char*)g_s.cand + ((q * 8 * NCL + c) * 6 + cq) * 16), c1 = c0 + (64 - cq * 12);
        uint32_t hc = sb + SM_HT + cq * 16, h4a = sb + SM_HT + 16384 + cq * 4;
        uint32_t ca = sb + SM_KEY + warp * 128 + (warp & 1) * 32 + (lane & 28), r2a = sb + SM_KEY + cq * 16 + (cq >> 1) * 128;
        PIN(ca); PIN(r2a); PIN(km0); PIN(km1); PIN(ka0); PIN(ka1); PIN(hc); PIN(h4a);
        asm volatile("add.u64 %0, %0, %2; add.u64 %1, %1, %2;" : "+l"(c0), "+l"(c1) : "l"((unsigned long long)zero));
        uint4 s; int n = 0;
        uint32_t ox;
        do {
            s = ld_rlx128(&g_s.acc[256 * q + tid]);
            ox = __shfl_xor_sync(~0u, (lane & 1) ? s.z : s.w, 1);
        } while (__any_sync(~0u, __uint_as_float(s.x) != (float)NCL && ++n < SPIN_LIMIT));
        STAMP(16);
        const uint32_t ms = ln_stats(__uint_as_float((lane & 1) ? ox : s.z), __uint_as_float(s.y));
        const float rs = rcpf(bf_hi(ms));
        const uint32_t rb = pack_bf16(0.f, fmaf(-bf_lo(ms), wsum, __uint_as_float((lane & 1) ? s.w : ox)) * rs);
        const uint32_t key = (((rb ^ (((int)rb >> 31) | 0x80000000u)) >> 16) << 11) | idx;
        sts32(sb + SM_KEY + tid * 4, key);
        sts64(sb + SM_ST + tid * 8, ms, rsplit(rs));
        __syncwarp();
        uint32_t rank = rank4<8, 16>(sb + SM_KEY + warp * 128, key, ~zero);
        {
            const uint32_t sa = (rank * 4 ^ (warp & 1) * 32) + opaque(sb + SM_KEY + warp * 128);
            sts32(sa, key); sts32(sa + 1024, tid);
        }
        __syncwarp();
        const uint32_t mk = lds32(ca), t = lds32(ca + 1024);
        STAMP(17);
        bar_sync(12, 512);
        STAMP(18);
        const uint4 hv = lds128(hc + t * 64);
        const uint2 sv = lds64(sb + SM_ST + t * 8);
        const uint32_t h4 = lds32(h4a + t * 16);
        rank = rank4<4, 256>(r2a, mk, ~zero);
        const uint32_t rr = bmul2(sv.y, 0x3C803C80u);
        const uint32_t p0 = (norm2(hv.x, sv.x, rr) & 0xBFFFBFFFu) | par, p1 = (norm2(hv.y, sv.x, rr) & 0xBFFFBFFFu) | par, p2 = (norm2(hv.z, sv.x, rr) & 0xBFFFBFFFu) | par,
                       p3 = (norm2(hv.w, sv.x, rr) & 0xBFFFBFFFu) | par, p4 = (norm2(h4, sv.x, rr) & 0xBFFFBFFFu) | par;
        rank = quad_sum(rank);
        if (rank < 8) {
            st_async1(ka0 + rank * 4, mk, km0); st_async1(ka1 + rank * 4, mk, km1);
            st_rlx128((void*)(c0 + (unsigned long long)rank * 1440), p0, p1, p2, p3);
            asm volatile("st.relaxed.gpu.global.u32 [%0], %1;" :: "l"(c1 + (unsigned long long)rank * 1440), "r"(p4) : "memory");
        }
        __syncwarp();
    } else {
        mbar_wait(mb + MB_Y * 8); loadA();
        if (warp < 16) {
            bar_sync(12, 512);
        }
    }
    if (warp < 16) {
        outtile();
        if (warp >= 8) {
            uint32_t src = ((tid >> 2) - 64) * 1440, ma = sb + SM_RK - 256 + (tid >> 2) * 4, ra = sb + SM_RK + cq * 16;
            PIN(src); PIN(ma); PIN(ra);
            STAMP(19);
            mbar_wait(mb + MB_KEY * 8);
            STAMP(20);
            const uint32_t mk = lds32(ma);
            uint32_t rank = rank4<4, 64>(ra, mk, ~zero);
            rank = quad_sum(rank);
            sts64(sb + SM_SEL + rank * 8, mk, src);
        }
    }
    bar_sync(11, 672);
    STAMP(12);

    const char* gp = (const char*)gb + lds32(gs);
    uint4 hv = ld_rlx128(gp);
    if (warp < 8) loadA();
    uint32_t bx = sb + SM_XS + mr * 1168 + mi * 16 + 288 * kq, gd = mapa(sb, (kq & (NRED - 1)) * (8 / NRED)) + (SM_GU + (q * nslot + mt) * 128) + lane * 4;
    PIN(bx); PIN(gd);
    {
        if (warp < 18) {
            int n = 0;
            while (true) {
                sts128(xs, hv.x ^ par, hv.y ^ par, hv.z ^ par, hv.w ^ par);
                if (!__any_sync(~0u, ((hv.x ^ par) | (hv.y ^ par) | (hv.z ^ par) | (hv.w ^ par)) & 0x40004000u) || ++n >= SPIN_LIMIT) break;
                hv = ld_rlx128(gp);
            }
        }
    }
    bar_sync(14, 768);
    STAMP(13);
    float4 own;
    {
        float c0[4] = {0.f, 0.f, 0.f, 0.f}, c1[4] = {0.f, 0.f, 0.f, 0.f}, c2[4] = {0.f, 0.f, 0.f, 0.f};
        uint32_t b[5][4];
#pragma unroll
        for (int s = 0; s < 4; s++) ldsm4(b[s], bx + s * 64);
        asm volatile("ldmatrix.sync.aligned.m8n8.x2.shared.b16 {%0,%1}, [%2];" : "=r"(b[4][0]), "=r"(b[4][1]) : "r"(bx + 256) : "memory");
        mma_bf16(c0, A[0][0], A[0][1], A[0][2], A[0][3], b[0][0], b[0][1]);
        mma_bf16(c1, A[1][0], A[1][1], A[1][2], A[1][3], b[0][2], b[0][3]);
        mma_bf16(c2, A[2][0], A[2][1], A[2][2], A[2][3], b[1][0], b[1][1]);
        mma_bf16(c0, A[3][0], A[3][1], A[3][2], A[3][3], b[1][2], b[1][3]);
        mma_bf16(c1, A[4][0], A[4][1], A[4][2], A[4][3], b[2][0], b[2][1]);
        mma_bf16(c2, A[5][0], A[5][1], A[5][2], A[5][3], b[2][2], b[2][3]);
        mma_bf16(c0, A[6][0], A[6][1], A[6][2], A[6][3], b[3][0], b[3][1]);
        mma_bf16(c1, A[7][0], A[7][1], A[7][2], A[7][3], b[3][2], b[3][3]);
        mma_bf16(c2, A[8][0], A[8][1], A[8][2], A[8][3], b[4][0], b[4][1]);
        own = make_float4(c0[0] + c1[0] + c2[0], c0[1] + c1[1] + c2[1], c0[2] + c1[2] + c2[2], c0[3] + c1[3] + c2[3]);
        sts128f(sb + SM_RED + tid * 16, own.x, own.y, own.z, own.w);
    }
    if (kq < 4 - NRED) bar_arrive(1 + mt, 128); else
    bar_sync(1 + mt, 128);
    STAMP(21);
    if (mt < nslot && kq >= 4 - NRED) {
        const uint32_t ra = lane * 16 + opaque(sb + SM_RED + mt * 512);
        const float4 p0 = lds128f(ra), p1 = lds128f(ra + 2560), p2 = lds128f(lane * 16 + opaque(sb + SM_RED + mt * 512 + (5 - kq) * 2560)), p3 = own;
        const float g0 = bfr((p0.x + p1.x) + (p2.x + p3.x)), g1 = bfr((p0.y + p1.y) + (p2.y + p3.y));
        const uint32_t sg = pack_bf16(g0 * rcpf(1.f + ex2f(g0 * (-64.f * 1.4426950408889634f))), g1 * rcpf(1.f + ex2f(g1 * (-64.f * 1.4426950408889634f))));
        const uint32_t gu = bmul2(sg, pack_bf16(((p0.z + p1.z) + (p2.z + p3.z)) * 4096.f, ((p0.w + p1.w) + (p2.w + p3.w)) * 4096.f));
        const uint32_t pstep = mapa(sb, 1) - mapa(sb, 0), gm = mapa(mb + MB_GU * 8, (kq & (NRED - 1)) * (8 / NRED));
#pragma unroll
        for (int i = 0; i < 8 / NRED; i++) st_async1(gd + i * pstep, gu, gm + i * pstep);
    }
    mbar_wait(mb + MB_W2 * 8);
    {
        const uint32_t aa = sb + (8 * (mi >> 1) + mr) * 144 + (mi & 1) * 16 + (SM_FAR + 2304 * kq + mt * 32);
#pragma unroll
        for (int s = 0; s < 5; s++) ldsm4t(A[s], aa + s * FAR_SZ);
    }
    float sig; uint32_t ra2; unsigned long long fp, op;
    if (warp < 8) {
        const uint32_t key = lds32(sb + SM_SEL + warp * 8), k16 = key << 5, fj = 24 * q + lane;
        sig = bfr(rcpf(1.f + ex2f(__uint_as_float((k16 ^ (~((int)k16 >> 31) | 0x80000000u)) & 0xFFFF0000u) * -1.4426950408889634f)));
        ra2 = sb + SM_RED2 + warp * 304 + lane * 12;
        fp = (unsigned long long)(g_s.fin + warp * 192 + fj); op = (unsigned long long)(prm.out + (~key & 2047) * D_ + 3 * fj);
        PIN(ra2);
        asm volatile("add.u64 %0, %0, %3; add.u64 %1, %1, %3;" : "+l"(fp), "+l"(op), "+f"(sig) : "l"((unsigned long long)zero));
    }
    {
        uint32_t ba = sb + (SM_GU + 256 * kq) + (lane & 15) * 16 + (lane >> 4) * 1024, wa = sb + (SM_RED2 + kq * 2432 + mt * 64) + g * 4 + cq * 608;
        PIN(ba); PIN(wa);
        STAMP(22);
        mbar_wait(mb + MB_GU * 8);
        STAMP(23);
        float c0[4] = {0.f, 0.f, 0.f, 0.f}, c1[4] = {0.f, 0.f, 0.f, 0.f}, c2[4] = {0.f, 0.f, 0.f, 0.f};
        uint32_t b[2][4], b8, b9;
        ldsm4t(b[0], ba); ldsm4t(b[1], ba + 2048); ldsm2t(b8, b9, ba + 4096);
        mma_bf16(c0, A[0][0], A[0][1], A[0][2], A[0][3], b[0][0], b[0][1]);
        mma_bf16(c1, A[1][0], A[1][1], A[1][2], A[1][3], b[0][2], b[0][3]);
        if (nslot == 5) {
            mma_bf16(c2, A[4][0], A[4][1], A[4][2], A[4][3], b8, b9);
            mma_bf16(c0, A[2][0], A[2][1], A[2][2], A[2][3], b[1][0], b[1][1]);
            mma_bf16(c1, A[3][0], A[3][1], A[3][2], A[3][3], b[1][2], b[1][3]);
        }
        stsf(wa, c0[0] + c1[0] + c2[0]); stsf(wa + 304, c0[1] + c1[1] + c2[1]);
        if (mt < 4) { stsf(wa + 32, c0[2] + c1[2] + c2[2]); stsf(wa + 336, c0[3] + c1[3] + c2[3]); }
    }
    if (warp < 8) {
        float v[3];
        bar_sync(6, 640);
        STAMP(14);
        if (lane < 24) {
#pragma unroll
            for (int i = 0; i < 3; i++) v[i] = ((ldsf(ra2 + i * 4) + ldsf(ra2 + i * 4 + 2432)) + (ldsf(ra2 + i * 4 + 4864) + ldsf(ra2 + i * 4 + 7296))) * sig;
            asm volatile("{ .reg .f32 x, y, z, w; .reg .b16 a, b, c; .reg .pred p;\n"
                         "atom.relaxed.gpu.global.add.v4.f32 {x,y,z,w}, [%0], {%2,%3,%4,%5};\n"
                         "setp.eq.f32 p, w, %6; add.f32 x, x, %2; add.f32 y, y, %3; add.f32 z, z, %4;\n"
                         "cvt.rn.bf16.f32 a, x; cvt.rn.bf16.f32 b, y; cvt.rn.bf16.f32 c, z;\n"
                         "@p st.global.b16 [%1], a; @p st.global.b16 [%1 + 2], b; @p st.global.b16 [%1 + 4], c; }"
                         :: "l"(fp), "l"(op), "f"(v[0]), "f"(v[1]), "f"(v[2]), "f"(3.f), "f"(3.f * NCL) : "memory");
        }
    } else bar_arrive(6, 640);
    STAMP(15);
}

#undef pp
typedef __nv_bfloat16 bf16;
__device__ bf16 f_n[L_ * D_], f_h[L_ * D_];
__device__ float f_k[D_ * L_], f_r[L_], f_gu[8 * F_];
__device__ int f_idx[8];
__device__ __forceinline__ float b2f(bf16 v) { return __bfloat162float(v); }
__global__ void fb_ln(const bf16* in, const bf16* wr, bf16* out) {
    const int t = blockIdx.x * 8 + (threadIdx.x >> 5), lane = threadIdx.x & 31;
    const bf16* r = (in ? in : f_h) + t * D_;
    float s1 = 0.f, s2 = 0.f, s3 = 0.f;
    for (int i = lane; i < D_; i += 32) s1 += b2f(r[i]);
    for (int o = 16; o; o >>= 1) s1 += __shfl_xor_sync(~0u, s1, o);
    for (int i = lane; i < D_; i += 32) { const float d = b2f(r[i]) - s1 / D_; s2 += d * d; }
    for (int o = 16; o; o >>= 1) s2 += __shfl_xor_sync(~0u, s2, o);
    const float m = bfr(s1 / D_), sd = bfr(sqrtf(bfr(bfr(s2 / D_) + 1e-5f)));
    for (int i = lane; i < D_; i += 32) {
        const float v = bfr(bfr(b2f(r[i]) - m) / sd);
        f_n[t * D_ + i] = __float2bfloat16(v);
        if (!in) { s3 += v * b2f(wr[i]); out[t * D_ + i] = __float2bfloat16(b2f(r[i]) + v); }
    }
    for (int o = 16; o; o >>= 1) s3 += __shfl_xor_sync(~0u, s3, o);
    f_r[t] = bfr(s3);
}
__global__ void fb_taps(Params p) {
    const int d = blockIdx.x >> 3, l = (blockIdx.x & 7) * 256 + threadIdx.x;
    const float dt = bfr(expf(bf_lo(p.logdt[d]))), lf = bfr((float)l);
    float k = 0.f;
    for (int n = d * 128; n < d * 128 + 128; n++) {
        float wr, wi, sn, cs;
        cmul(wr, wi, bf_lo(p.prm6[4][n]), bf_lo(p.prm6[5][n]), dt * bf_lo(p.prm6[2][n]), dt * bf_lo(p.prm6[3][n]));
        sincosf(dt * bf_lo(p.prm6[1][n]) * lf, &sn, &cs);
        k += expf(dt * bf_lo(p.prm6[0][n]) * lf) * (wr * cs - wi * sn);
    }
    f_k[l * D_ + d] = k;
}
__global__ void fb_conv(Params p) {
    const int t = blockIdx.x, d = threadIdx.x;
    float y = 0.f;
    for (int l = 0; l <= t; l++) y += f_k[l * D_ + d] * b2f(f_n[(t - l) * D_ + d]);
    f_h[t * D_ + d] = __float2bfloat16(bf_lo(p.x[t * D_ + d]) + bfr(bfr(y) + bfr(b2f(f_n[t * D_ + d]) * bf_lo(p.dskip[d]))));
}
__global__ void fb_top() {
    const int t = blockIdx.x * 256 + threadIdx.x;
    int rank = 0;
    for (int j = 0; j < L_; j++) rank += f_r[j] > f_r[t] || (f_r[j] == f_r[t] && j < t);
    if (rank < 8) f_idx[rank] = t;
}
__global__ void fb_ffn1(const bf16* wg, const bf16* wu) {
    const int f = blockIdx.x * 256 + threadIdx.x, j = blockIdx.y;
    float g = 0.f, u = 0.f;
    for (int i = 0; i < D_; i++) { const float v = b2f(f_n[f_idx[j] * D_ + i]); g += v * b2f(wg[i * F_ + f]); u += v * b2f(wu[i * F_ + f]); }
    g = bfr(g);
    f_gu[j * F_ + f] = bfr(bfr(g / (1.f + expf(-g))) * bfr(u));
}
__global__ void fb_ffn2(const bf16* wd, bf16* out) {
    const int d = threadIdx.x, j = blockIdx.x, t = f_idx[j];
    float y = 0.f;
    for (int f = 0; f < F_; f++) y += f_gu[j * F_ + f] * b2f(wd[f * D_ + d]);
    out[t * D_ + d] = __float2bfloat16(b2f(f_h[t * D_ + d]) + bfr(b2f(f_n[t * D_ + d]) + bfr(bfr(y) * bfr(1.f / (1.f + expf(-f_r[t]))))));
}

typedef CUresult (*EncodeFn)(CUtensorMap*, CUtensorMapDataType, cuuint32_t, void*, const cuuint64_t*, const cuuint64_t*,
                             const cuuint32_t*, const cuuint32_t*, CUtensorMapInterleave, CUtensorMapSwizzle,
                             CUtensorMapL2promotion, CUtensorMapFloatOOBfill);

void make_map(EncodeFn fn, CUtensorMap* tm, const void* p, int cols, int rows, int bc, int br) {
    cuuint64_t dims[2] = {(cuuint64_t)cols, (cuuint64_t)rows};
    cuuint64_t strides[1] = {(cuuint64_t)cols * 2};
    cuuint32_t box[2] = {(cuuint32_t)bc, (cuuint32_t)br};
    cuuint32_t es[2] = {1, 1};
    fn(tm, CU_TENSOR_MAP_DATA_TYPE_BFLOAT16, 2, const_cast<void*>(p), dims, strides, box, es, CU_TENSOR_MAP_INTERLEAVE_NONE,
       CU_TENSOR_MAP_SWIZZLE_NONE, CU_TENSOR_MAP_L2_PROMOTION_L2_128B, CU_TENSOR_MAP_FLOAT_OOB_FILL_NONE);
}

void make_map3(EncodeFn fn, CUtensorMap* tm, const void* p) {
    cuuint64_t dims[5] = {(cuuint64_t)D_, 64, 2, 2, 8};
    cuuint64_t strides[4] = {(cuuint64_t)D_ * 2, (cuuint64_t)D_ * 2048, (cuuint64_t)D_ * 128, (cuuint64_t)D_ * 256};
    cuuint32_t box[5] = {XW, 9, 2, 2, 8};
    cuuint32_t es[5] = {1, 1, 1, 1, 1};
    fn(tm, CU_TENSOR_MAP_DATA_TYPE_BFLOAT16, 5, const_cast<void*>(p), dims, strides, box, es, CU_TENSOR_MAP_INTERLEAVE_NONE,
       CU_TENSOR_MAP_SWIZZLE_NONE, CU_TENSOR_MAP_L2_PROMOTION_NONE, CU_TENSOR_MAP_FLOAT_OOB_FILL_NONE);
}

void make_map5(EncodeFn fn, CUtensorMap* tm, const void* p, int bc) {
    cuuint64_t dims[5] = {(cuuint64_t)D_, 2, 4, 4, 64};
    cuuint64_t strides[4] = {(cuuint64_t)D_ * 128, (cuuint64_t)D_ * 1024, (cuuint64_t)D_ * 256, (cuuint64_t)D_ * 2};
    cuuint32_t box[5] = {(cuuint32_t)bc, 2, 4, 4, 8};
    cuuint32_t es[5] = {1, 1, 1, 1, 1};
    fn(tm, CU_TENSOR_MAP_DATA_TYPE_BFLOAT16, 5, const_cast<void*>(p), dims, strides, box, es, CU_TENSOR_MAP_INTERLEAVE_NONE,
       CU_TENSOR_MAP_SWIZZLE_NONE, CU_TENSOR_MAP_L2_PROMOTION_NONE, CU_TENSOR_MAP_FLOAT_OOB_FILL_NONE);
}

}

extern "C" void kernel_launch(void* const* d_in, const int* in_sizes, int n_in, void* d_out, int out_size) {
    (void)in_sizes; (void)n_in; (void)out_size;
    void* fp = nullptr;
    cudaDriverEntryPointQueryResult qr;
    cudaGetDriverEntryPoint("cuTensorMapEncodeTiled", &fp, cudaEnableDefault, &qr);
    EncodeFn fn = (EncodeFn)fp;
    CUtensorMap tmG, tmU, tmD, tmO, tmX, tmH;
    make_map3(fn, &tmX, d_in[0]);
    make_map(fn, &tmG, d_in[11], F_, D_, 40, 48);
    make_map(fn, &tmU, d_in[12], F_, D_, 40, 48);
    make_map(fn, &tmD, d_in[13], D_, F_, 72, 64);
    make_map5(fn, &tmO, d_out, 32);
    make_map5(fn, &tmH, d_out, 8);
    Params p;
    p.x = (const unsigned short*)d_in[0];
    for (int i = 0; i < 6; i++) p.prm6[i] = (const unsigned short*)d_in[1 + i];
    p.logdt = (const unsigned short*)d_in[7]; p.dskip = (const unsigned short*)d_in[8];
    p.wr = (const unsigned short*)d_in[10];
    p.out = (__nv_bfloat16*)d_out;
    p.zero = 0;
    cudaGetSymbolAddress((void**)&p.gs, g_s);
    cudaFuncSetAttribute(fused_kernel, cudaFuncAttributeMaxDynamicSharedMemorySize, SM_TOTAL);
    static int nclusters = -1;
    if (nclusters < 0) {
        cudaLaunchConfig_t cfg = {};
        cudaLaunchAttribute at;
        at.id = cudaLaunchAttributeClusterDimension; at.val.clusterDim.x = CS; at.val.clusterDim.y = 1; at.val.clusterDim.z = 1;
        cfg.gridDim = dim3(NCTA); cfg.blockDim = dim3(NTHR); cfg.dynamicSmemBytes = SM_TOTAL; cfg.attrs = &at; cfg.numAttrs = 1;
        if (cudaOccupancyMaxActiveClusters(&nclusters, fused_kernel, &cfg) != cudaSuccess) { (void)cudaGetLastError(); nclusters = NCL; }
    }
    if (nclusters >= NCL && !FORCE_FALLBACK) {
        fused_kernel<<<NCTA, NTHR, SM_TOTAL>>>(p, tmG, tmU, tmD, tmO, tmX, tmH);
        return;
    }
    fb_ln<<<L_ / 8, 256>>>((const bf16*)d_in[0], nullptr, nullptr);
    fb_taps<<<D_ * 8, 256>>>(p);
    fb_conv<<<L_, D_>>>(p);
    fb_ln<<<L_ / 8, 256>>>(nullptr, (const bf16*)d_in[10], p.out);
    fb_top<<<L_ / 256, 256>>>();
    fb_ffn1<<<dim3(F_ / 256, 8), 256>>>((const bf16*)d_in[11], (const bf16*)d_in[12]);
    fb_ffn2<<<8, D_>>>((const bf16*)d_in[13], p.out);
}
```

```cpp
#include <cuda_runtime.h>
#include <cuda_bf16.h>
#include <cuda_fp16.h>
#include <cuda.h>
#include <stdint.h>

namespace {

constexpr int L_ = 2048, D_ = 576, F_ = 4608;
constexpr int NCL = 15, CS = 8, NCTA = NCL * CS, NTHR = 768;
#define FORCE_FALLBACK 0
constexpr int XW = 48, NRED = 2;
constexpr int SPIN_LIMIT = 1 << 22;

constexpr int SM_WG   = 0;
constexpr int SM_WU   = 46080;
constexpr int YP = 3392, YS = 656;
constexpr int UP = 3280, US = 656;
constexpr int SM_XT   = 92160;
constexpr int SM_U    = SM_XT + 8 * YP;
constexpr int SM_FAR  = SM_U + 8 * UP;
constexpr int FAR_SZ  = 12416;
constexpr int F_E5 = 0, F_O5 = 1536, F_E3 = 3088, F_O3 = 4624, F_E7 = 6176, F_E2 = F_E7 + 1024, F_E9 = F_E7 + 2048,
              F_H = 3088, F_O7 = F_E7 + F_H, F_O2 = F_E2 + F_H, F_O9 = F_E9 + F_H;
constexpr int SM_P    = SM_FAR + 5 * FAR_SZ;
constexpr int PN_SZ = 584 * 4, SM_PN = SM_P + 65 * 4;
constexpr int P_GS = 50 * 4, P_H7 = 200 * 4, P_HS = 74 * 4;
constexpr int PF_SZ = (200 + 222) * 4, SM_PF = SM_PN + 5 * PN_SZ + 36;
constexpr int SM_MISC = SM_PF + 5 * PF_SZ;
constexpr int SM_ST   = SM_MISC;
constexpr int SM_RK   = SM_ST + 2048;
constexpr int SM_SEL  = SM_FAR + FAR_SZ + 10240;
constexpr int SM_KG   = SM_RK + 320;
constexpr int SM_SC   = SM_KG + 160;
constexpr int SM_DW   = SM_SC + 32;
constexpr int SM_MB   = SM_DW + 160;
constexpr int SM_TOTAL = SM_MB + 128;
constexpr int SM_ROW  = SM_XT - 20736;
constexpr int SM_XTL  = SM_ROW - 576 * XW;
constexpr int SM_RED2 = SM_WG;
constexpr int SM_HT   = SM_P - 512;
constexpr int SM_KEY  = SM_FAR + 10240 + 128;
constexpr int SM_CAND = SM_KEY + 1024;
constexpr int SM_XS   = SM_U;
constexpr int SM_GU   = SM_XS + 9344;
constexpr int SM_RED  = SM_GU + 5632;
static_assert(F_O9 + 1024 <= FAR_SZ && FAR_SZ % 128 == 0, "far overflow");
static_assert(SM_RED + 10240 <= SM_FAR && SM_HT + 20496 <= SM_MISC, "alias overflow");
static_assert(SM_TOTAL <= 232448, "smem overflow");
static_assert(SM_FAR % 128 == 0 && SM_XT % 128 == 0 && SM_XTL % 128 == 0 && SM_P % 16 == 0 && SM_MISC % 16 == 0 && SM_MB % 8 == 0, "align");

enum { MB_X = 0, MB_W1 = 5, MB_W2 = 6, MB_KEY = 7, MB_GU = 8, MB_Y = 9, MB_OUT = 10, MB_T = 11, MB_R = 12 };

struct __align__(128) Scratch {
    unsigned epoch, zcnt, pad[30];
    uint4  st1[L_ * 2];
    float4 acc[L_];
    uint4  cand[2 * 64 * NCL * 6];
    float4 fin[8 * 192 + 24];
};
__device__ Scratch g_s;
#define STAMP(i)

__device__ __forceinline__ uint32_t mapa(uint32_t a, uint32_t r) { uint32_t d; asm("mapa.shared::cluster.u32 %0, %1, %2;" : "=r"(d) : "r"(a), "r"(r)); return d; }
__device__ __forceinline__ void mbar_wait(uint32_t mb) {
    asm volatile("{ .reg .pred p, q; .reg .u32 n; mov.u32 n, 0;\n"
                 "W_%=: mbarrier.try_wait.parity.shared::cta.b64 p, [%0], 0; add.u32 n, n, 1; setp.lt.and.u32 q, n, 65536, !p; @q bra W_%=; }" :: "r"(mb) : "memory");
}
__device__ __forceinline__ bool elect() { uint32_t e; asm volatile("{ .reg .pred p; elect.sync _|p, 0xffffffff; selp.u32 %0, 1, 0, p; }" : "=r"(e)); return e; }
__device__ __forceinline__ void arm(uint32_t mb, uint32_t bytes) { asm volatile("mbarrier.arrive.expect_tx.shared::cta.b64 _, [%0], %1;" :: "r"(mb), "r"(bytes) : "memory"); }
__device__ __forceinline__ void bar_sync(int id, int n) { asm volatile("bar.sync %0, %1;" :: "r"(id), "r"(n) : "memory"); }
__device__ __forceinline__ void bar_arrive(int id, int n) { asm volatile("bar.arrive %0, %1;" :: "r"(id), "r"(n) : "memory"); }
__device__ __forceinline__ uint32_t lds16(uint32_t a) { unsigned short v; asm volatile("ld.shared.u16 %0, [%1];" : "=h"(v) : "r"(a) : "memory"); return v; }
__device__ __forceinline__ uint32_t lds32(uint32_t a) { uint32_t v; asm volatile("ld.shared.u32 %0, [%1];" : "=r"(v) : "r"(a) : "memory"); return v; }
__device__ __forceinline__ uint2 lds64(uint32_t a) { uint2 v; asm volatile("ld.shared.v2.u32 {%0,%1}, [%2];" : "=r"(v.x), "=r"(v.y) : "r"(a) : "memory"); return v; }
__device__ __forceinline__ float ldsf(uint32_t a) { float v; asm volatile("ld.shared.f32 %0, [%1];" : "=f"(v) : "r"(a) : "memory"); return v; }
__device__ __forceinline__ uint4 lds128(uint32_t a) { uint4 v; asm volatile("ld.shared.v4.u32 {%0,%1,%2,%3}, [%4];" : "=r"(v.x), "=r"(v.y), "=r"(v.z), "=r"(v.w) : "r"(a) : "memory"); return v; }
__device__ __forceinline__ float4 lds128f(uint32_t a) { float4 v; asm volatile("ld.shared.v4.f32 {%0,%1,%2,%3}, [%4];" : "=f"(v.x), "=f"(v.y), "=f"(v.z), "=f"(v.w) : "r"(a) : "memory"); return v; }
__device__ __forceinline__ void sts16(uint32_t a, uint32_t v) { asm volatile("{ .reg .b16 l, h; mov.b32 {l, h}, %1; st.shared.b16 [%0], l; }" :: "r"(a), "r"(v) : "memory"); }
__device__ __forceinline__ void sts32(uint32_t a, uint32_t v) { asm volatile("st.shared.u32 [%0], %1;" :: "r"(a), "r"(v) : "memory"); }
__device__ __forceinline__ void sts64(uint32_t a, uint32_t x, uint32_t y) { asm volatile("st.shared.v2.u32 [%0], {%1,%2};" :: "r"(a), "r"(x), "r"(y) : "memory"); }
__device__ __forceinline__ void stsf(uint32_t a, float v) { asm volatile("st.shared.f32 [%0], %1;" :: "r"(a), "f"(v) : "memory"); }
__device__ __forceinline__ void sts128(uint32_t a, uint32_t x, uint32_t y, uint32_t z, uint32_t w) { asm volatile("st.shared.v4.u32 [%0], {%1,%2,%3,%4};" :: "r"(a), "r"(x), "r"(y), "r"(z), "r"(w) : "memory"); }
__device__ __forceinline__ void sts128f(uint32_t a, float x, float y, float z, float w) { asm volatile("st.shared.v4.f32 [%0], {%1,%2,%3,%4};" :: "r"(a), "f"(x), "f"(y), "f"(z), "f"(w) : "memory"); }
__device__ __forceinline__ void ldsm4(uint32_t (&r)[4], uint32_t a) { asm volatile("ldmatrix.sync.aligned.m8n8.x4.shared.b16 {%0,%1,%2,%3}, [%4];" : "=r"(r[0]), "=r"(r[1]), "=r"(r[2]), "=r"(r[3]) : "r"(a) : "memory"); }
__device__ __forceinline__ void ldsm4t(uint32_t (&r)[4], uint32_t a) { asm volatile("ldmatrix.sync.aligned.m8n8.x4.trans.shared.b16 {%0,%1,%2,%3}, [%4];" : "=r"(r[0]), "=r"(r[1]), "=r"(r[2]), "=r"(r[3]) : "r"(a) : "memory"); }
__device__ __forceinline__ void ldsm2t(uint32_t& r0, uint32_t& r1, uint32_t a) { asm volatile("ldmatrix.sync.aligned.m8n8.x2.trans.shared.b16 {%0,%1}, [%2];" : "=r"(r0), "=r"(r1) : "r"(a) : "memory"); }
__device__ __forceinline__ void stsm4t(uint32_t a, uint32_t r0, uint32_t r1, uint32_t r2, uint32_t r3) { asm volatile("stmatrix.sync.aligned.m8n8.x4.trans.shared.b16 [%0], {%1,%2,%3,%4};" :: "r"(a), "r"(r0), "r"(r1), "r"(r2), "r"(r3) : "memory"); }
__device__ __forceinline__ void stsm4(uint32_t a, uint32_t r0, uint32_t r1, uint32_t r2, uint32_t r3) { asm volatile("stmatrix.sync.aligned.m8n8.x4.shared.b16 [%0], {%1,%2,%3,%4};" :: "r"(a), "r"(r0), "r"(r1), "r"(r2), "r"(r3) : "memory"); }
__device__ __forceinline__ void stsm2(uint32_t a, uint32_t r0, uint32_t r1) { asm volatile("stmatrix.sync.aligned.m8n8.x2.shared.b16 [%0], {%1,%2};" :: "r"(a), "r"(r0), "r"(r1) : "memory"); }
__device__ __forceinline__ void stsm2t(uint32_t a, uint32_t r0, uint32_t r1) { asm volatile("stmatrix.sync.aligned.m8n8.x2.trans.shared.b16 [%0], {%1,%2};" :: "r"(a), "r"(r0), "r"(r1) : "memory"); }
__device__ __forceinline__ uint4 ldg128(const void* p) { uint4 v; asm volatile("ld.global.nc.v4.u32 {%0,%1,%2,%3}, [%4];" : "=r"(v.x), "=r"(v.y), "=r"(v.z), "=r"(v.w) : "l"(p)); return v; }
__device__ __forceinline__ uint32_t ldg16(const void* p) { unsigned short v; asm volatile("ld.global.nc.u16 %0, [%1];" : "=h"(v) : "l"(p)); return v; }
__device__ __forceinline__ uint32_t opaque(uint32_t v) { uint32_t r; asm volatile("mov.b32 %0, %1;" : "=r"(r) : "r"(v)); return r; }
__device__ __forceinline__ void mma_f16(float (&d)[4], const uint32_t (&a)[4], uint32_t b0, uint32_t b1) {
    asm volatile("mma.sync.aligned.m16n8k16.row.col.f32.f16.f16.f32 {%0,%1,%2,%3}, {%4,%5,%6,%7}, {%8,%9}, {%0,%1,%2,%3};"
        : "+f"(d[0]), "+f"(d[1]), "+f"(d[2]), "+f"(d[3]) : "r"(a[0]), "r"(a[1]), "r"(a[2]), "r"(a[3]), "r"(b0), "r"(b1));
}
__device__ __forceinline__ void mma_f16_z(float (&d)[4], const uint32_t (&a)[4], uint32_t b0, uint32_t b1) {
    asm volatile("mma.sync.aligned.m16n8k16.row.col.f32.f16.f16.f32 {%0,%1,%2,%3}, {%4,%5,%6,%7}, {%8,%9}, {%10,%10,%10,%10};"
        : "=f"(d[0]), "=f"(d[1]), "=f"(d[2]), "=f"(d[3]) : "r"(a[0]), "r"(a[1]), "r"(a[2]), "r"(a[3]), "r"(b0), "r"(b1), "f"(0.f));
}
__device__ __forceinline__ void mma_bf16(float (&d)[4], uint32_t a0, uint32_t a1, uint32_t a2, uint32_t a3, uint32_t b0, uint32_t b1) {
    asm volatile("mma.sync.aligned.m16n8k16.row.col.f32.bf16.bf16.f32 {%0,%1,%2,%3}, {%4,%5,%6,%7}, {%8,%9}, {%0,%1,%2,%3};"
        : "+f"(d[0]), "+f"(d[1]), "+f"(d[2]), "+f"(d[3]) : "r"(a0), "r"(a1), "r"(a2), "r"(a3), "r"(b0), "r"(b1));
}
__device__ __forceinline__ void mma_bf16_k8(float (&d)[4], uint32_t a0, uint32_t a1, uint32_t b0) {
    asm volatile("mma.sync.aligned.m16n8k8.row.col.f32.bf16.bf16.f32 {%0,%1,%2,%3}, {%4,%5}, {%6}, {%0,%1,%2,%3};"
        : "+f"(d[0]), "+f"(d[1]), "+f"(d[2]), "+f"(d[3]) : "r"(a0), "r"(a1), "r"(b0));
}
__device__ __forceinline__ uint32_t pack_f16(float lo, float hi) { uint32_t r; asm("cvt.rn.f16x2.f32 %0, %1, %2;" : "=r"(r) : "f"(hi), "f"(lo)); return r; }
__device__ __forceinline__ uint32_t pack_bf16(float lo, float hi) { uint32_t r; asm("cvt.rn.bf16x2.f32 %0, %1, %2;" : "=r"(r) : "f"(hi), "f"(lo)); return r; }
__device__ __forceinline__ float bf_lo(uint32_t v) { return __uint_as_float(v << 16); }
__device__ __forceinline__ float bf_hi(uint32_t v) { return __uint_as_float(v & 0xFFFF0000u); }
__device__ __forceinline__ float bfr(float x) { return __uint_as_float(pack_bf16(0.f, x)); }
__device__ __forceinline__ uint32_t badd2(uint32_t a, uint32_t b) { uint32_t r; asm("add.rn.bf16x2 %0, %1, %2;" : "=r"(r) : "r"(a), "r"(b)); return r; }
__device__ __forceinline__ uint32_t bmul2(uint32_t a, uint32_t b) { uint32_t r; asm("mul.rn.bf16x2 %0, %1, %2;" : "=r"(r) : "r"(a), "r"(b)); return r; }
__device__ __forceinline__ uint32_t hadd2(uint32_t a, uint32_t b) { uint32_t r; asm("add.rn.f16x2 %0, %1, %2;" : "=r"(r) : "r"(a), "r"(b)); return r; }
__device__ __forceinline__ uint32_t hmul2(uint32_t a, uint32_t b) { uint32_t r; asm("mul.rn.f16x2 %0, %1, %2;" : "=r"(r) : "r"(a), "r"(b)); return r; }
__device__ __forceinline__ uint32_t hneg2(uint32_t a) { uint32_t r; asm("neg.f16x2 %0, %1;" : "=r"(r) : "r"(a)); return r; }
__device__ __forceinline__ float rcpf(float x) { float r; asm("rcp.approx.ftz.f32 %0, %1;" : "=f"(r) : "f"(x)); return r; }
__device__ __forceinline__ float sqrta(float x) { float r; asm("sqrt.approx.ftz.f32 %0, %1;" : "=f"(r) : "f"(x)); return r; }
__device__ __forceinline__ float ex2f(float x) { float r; asm("ex2.approx.ftz.f32 %0, %1;" : "=f"(r) : "f"(x)); return r; }
__device__ __forceinline__ void st_async4(uint32_t a, uint32_t x, uint32_t y, uint32_t z, uint32_t w, uint32_t mb) {
    asm volatile("st.async.shared::cluster.mbarrier::complete_tx::bytes.v4.u32 [%0], {%1,%2,%3,%4}, [%5];" :: "r"(a), "r"(x), "r"(y), "r"(z), "r"(w), "r"(mb) : "memory"); }
__device__ __forceinline__ void st_async1(uint32_t a, uint32_t x, uint32_t mb) {
    asm volatile("st.async.shared::cluster.mbarrier::complete_tx::bytes.u32 [%0], %1, [%2];" :: "r"(a), "r"(x), "r"(mb) : "memory"); }
__device__ __forceinline__ unsigned ld_rlx(const void* p) { unsigned v; asm volatile("ld.relaxed.gpu.global.u32 %0, [%1];" : "=r"(v) : "l"(p) : "memory"); return v; }
__device__ __forceinline__ unsigned ld_acq(const void* p) { unsigned v; asm volatile("ld.acquire.gpu.global.u32 %0, [%1];" : "=r"(v) : "l"(p) : "memory"); return v; }
__device__ __forceinline__ uint2 ld_rlx64(const void* p) { unsigned long long v; asm volatile("ld.relaxed.gpu.global.u64 %0, [%1];" : "=l"(v) : "l"(p) : "memory"); return make_uint2((unsigned)v, (unsigned)(v >> 32)); }
__device__ __forceinline__ void st_rlx128(void* p, uint32_t x, uint32_t y, uint32_t z, uint32_t w) {
    asm volatile("st.relaxed.gpu.global.v2.u64 [%0], {%1,%2};" :: "l"(p), "l"((unsigned long long)x | ((unsigned long long)y << 32)), "l"((unsigned long long)z | ((unsigned long long)w << 32)) : "memory"); }
__device__ __forceinline__ uint4 ld_rlx128(const void* p) { unsigned long long a, b; asm volatile("ld.relaxed.gpu.global.v2.u64 {%0,%1}, [%2];" : "=l"(a), "=l"(b) : "l"(p) : "memory"); return make_uint4((unsigned)a, (unsigned)(a >> 32), (unsigned)b, (unsigned)(b >> 32)); }
__device__ __forceinline__ void tma2d(uint32_t dst, const CUtensorMap* tm, int x, int y, uint32_t mb) {
    asm volatile("cp.async.bulk.tensor.2d.shared::cluster.global.mbarrier::complete_tx::bytes [%0], [%1, {%3, %4}], [%2];"
                 :: "r"(dst), "l"(tm), "r"(mb), "r"(x), "r"(y) : "memory");
}
__device__ __forceinline__ void cmul(float& xr, float& xi, float ar, float ai, float br, float bi) {
    const float r = fmaf(ar, br, -ai * bi), i = fmaf(ar, bi, ai * br); xr = r; xi = i;
}
__device__ __forceinline__ void csq(float& xr, float& xi, float ar, float ai) {
    const float r = fmaf(ar, ar, -ai * ai), i = (ar + ar) * ai; xr = r; xi = i;
}
__device__ __forceinline__ void cexp_s(float& zr, float& zi, float e2, float turns) {
    const float mag = ex2f(e2), r = (turns - rintf(turns)) * 6.283185307179586f;
    zr = mag * __cosf(r); zi = mag * __sinf(r);
}
__device__ __forceinline__ uint32_t ln_stats(float s1, float s2) {
    const float m = s1 * (1.f / D_);
    const float var = fmaxf(fmaf(s2, 1.f / D_, -m * m), 0.f);
    return pack_bf16(m, sqrta(bfr(bfr(var) + 1e-5f)));
}
__device__ __forceinline__ uint32_t rsplit(float rs) { const float h = bfr(rs); return pack_bf16(h, rs - h); }
__device__ __forceinline__ uint32_t norm2(uint32_t v, uint32_t mx, uint32_t hl) {
    uint32_t r;
    asm("{ .reg .b16 m, h, l, x; .reg .b32 m2, h2, l2, d, t; mov.b32 {m, x}, %2; mov.b32 {h, l}, %3; mov.b32 m2, {m, m}; mov.b32 h2, {h, h}; mov.b32 l2, {l, l};\n"
        "sub.rn.bf16x2 d, %1, m2; mul.rn.bf16x2 t, d, l2; fma.rn.bf16x2 %0, d, h2, t; }" : "=r"(r) : "r"(v), "r"(mx), "r"(hl));
    return r;
}
template <int N, int S>
__device__ __forceinline__ uint32_t rank4(uint32_t a, uint32_t key, uint32_t m1) {
    uint32_t r0 = 0, r1 = 0, r2 = 0, r3 = 0;
#pragma unroll
    for (int i = 0; i < N; i++) {
        const uint4 o = lds128(a + i * S);
        r0 += (o.x * m1 + key) >> 31; r1 += (o.y * m1 + key) >> 31; r2 += (o.z * m1 + key) >> 31; r3 += (o.w * m1 + key) >> 31;
    }
    return (r0 + r1) + (r2 + r3);
}
__device__ __forceinline__ uint32_t quad_sum(uint32_t r) {
    const uint32_t a = __shfl_xor_sync(~0u, r, 1), b = __shfl_xor_sync(~0u, r, 2), c = __shfl_xor_sync(~0u, r, 3);
    return (r + a) + b + c;
}
typedef uint32_t H2C;
__device__ __forceinline__ H2C splat(float r, float i) { return pack_f16(r, i); }
__device__ __forceinline__ void hcmul(uint32_t& xr, uint32_t& xi, uint32_t R, uint32_t I, H2C m) {
    asm("{ .reg .b16 a, b; .reg .b32 a2, b2, t; mov.b32 {a, b}, %4; mov.b32 a2, {a, a}; mov.b32 b2, {b, b};\n"
        "mul.rn.f16x2 t, %3, b2; neg.f16x2 t, t; fma.rn.f16x2 %0, %2, a2, t; mul.rn.f16x2 t, %3, a2; fma.rn.f16x2 %1, %2, b2, t; }"
        : "=&r"(xr), "=r"(xi) : "r"(R), "r"(I), "r"(m));
}
__device__ __forceinline__ void expand4(uint32_t are, uint32_t aim, uint32_t R0, uint32_t R1, uint32_t I0, uint32_t I1, H2C m4) {
    uint32_t R2, I2, R3, I3;
    hcmul(R2, I2, R0, I0, m4); hcmul(R3, I3, R1, I1, m4);
    sts128(are, R0, R1, R2, R3);
    sts128(aim, I0, I1, I2, I3);
}
__device__ __forceinline__ void expand8(uint32_t are, uint32_t aim, float sr, float si, float m1r, float m1i, float m2r, float m2i, H2C m4) {
    float r1, i1, r2, i2, r3, i3;
    cmul(r1, i1, sr, si, m1r, m1i); cmul(r2, i2, sr, si, m2r, m2i); cmul(r3, i3, r1, i1, m2r, m2i);
    expand4(are, aim, pack_f16(sr, r1), pack_f16(r2, r3), pack_f16(si, i1), pack_f16(i2, i3), m4);
}
__device__ __forceinline__ uint32_t comb4(uint32_t a, uint32_t b, uint32_t c, uint32_t d, uint32_t r01, uint32_t r23) {
    uint32_t x;
    asm("{ .reg .b16 h0, h1, h2, h3; .reg .b32 m0, m1, m2, m3, u, v; mov.b32 {h0, h1}, %5; mov.b32 {h2, h3}, %6;\n"
        "mov.b32 m0, {h0, h0}; mov.b32 m1, {h1, h1}; mov.b32 m2, {h2, h2}; mov.b32 m3, {h3, h3};\n"
        "mul.rn.f16x2 u, %2, m1; fma.rn.f16x2 u, %1, m0, u; mul.rn.f16x2 v, %4, m3; fma.rn.f16x2 v, %3, m2, v; add.rn.f16x2 %0, u, v; }"
        : "=r"(x) : "r"(a), "r"(b), "r"(c), "r"(d), "r"(r01), "r"(r23));
    return x;
}
__device__ __forceinline__ void put16(uint32_t a, uint32_t v) { sts16(a, v); sts16(a + 6, v); }

struct Params {
    const unsigned short *logdt, *dskip, *prm6[6], *x, *wr;
    __nv_bfloat16* out;
    Scratch* gs;
    unsigned zero;
};
__device__ __forceinline__ uint32_t tslot(uint32_t t) { return (t & 7) * 32 + ((t >> 4) & 24) + ((t >> 8) & 6) + ((t >> 6) & 1); }
#define CP(x) ((x) | zero)
#define ZF(x) ((x) & zero)
#define PIN(x) asm volatile("or.b32 %0, %0, %1;" : "+r"(x) : "r"(zero))
__device__ __forceinline__ void wgmma32(float (&d)[4][4], const uint32_t (&a)[4], unsigned long long ds) {
    asm volatile("wgmma.mma_async.sync.aligned.m64n32k16.f32.f16.f16 {%0,%1,%2,%3,%4,%5,%6,%7,%8,%9,%10,%11,%12,%13,%14,%15}, {%16,%17,%18,%19}, %20, 1, 1, 1, 0;"
        : "+f"(d[0][0]), "+f"(d[0][1]), "+f"(d[0][2]), "+f"(d[0][3]), "+f"(d[1][0]), "+f"(d[1][1]), "+f"(d[1][2]), "+f"(d[1][3]),
          "+f"(d[2][0]), "+f"(d[2][1]), "+f"(d[2][2]), "+f"(d[2][3]), "+f"(d[3][0]), "+f"(d[3][1]), "+f"(d[3][2]), "+f"(d[3][3])
        : "r"(a[0]), "r"(a[1]), "r"(a[2]), "r"(a[3]), "l"(ds));
}

__device__ __forceinline__ void finish(const Params& prm, uint32_t fo, uint32_t oo, const float (&v)[3], float cnt) {
    float x, y, z, w;
    asm volatile("atom.relaxed.gpu.global.add.v4.f32 {%0,%1,%2,%3}, [%4], {%5,%6,%7,%8};" : "=f"(x), "=f"(y), "=f"(z), "=f"(w)
                 : "l"((char*)prm.gs->fin + fo), "f"(v[0]), "f"(v[1]), "f"(v[2]), "f"(cnt) : "memory");
    if (w + cnt == 3.f * (NCL + 1)) {
        __nv_bfloat16* op = (__nv_bfloat16*)((char*)prm.out + oo);
        op[0] = __float2bfloat16(x + v[0]); op[1] = __float2bfloat16(y + v[1]); op[2] = __float2bfloat16(z + v[2]);
    }
}

__global__ void __cluster_dims__(CS, 1, 1) __launch_bounds__(NTHR, 1)
fused_kernel(const __grid_constant__ Params prm, const __grid_constant__ CUtensorMap tmG, const __grid_constant__ CUtensorMap tmU,
             const __grid_constant__ CUtensorMap tmD, const __grid_constant__ CUtensorMap tmO, const __grid_constant__ CUtensorMap tmX, const __grid_constant__ CUtensorMap tmH)
{
    extern __shared__ __align__(1024) unsigned char smem[];
    const int tid = threadIdx.x, lane = tid & 31, warp = __shfl_sync(~0u, tid >> 5, 0);
    const int c = blockIdx.x >> 3, q = blockIdx.x & 7;
    const int nslot = (c < NCL - 1) ? 5 : 2;
    const int d0 = 40 * c;
    const uint32_t sb = opaque((uint32_t)__cvta_generic_to_shared(smem));
    const uint32_t mb = sb + SM_MB;
    Scratch& g_s = *prm.gs;
    const unsigned& zero = prm.zero;
    const uint32_t dch2 = min(d0 + q + ((tid >> 4) & ~7), D_ - 1) * 2;
    uint32_t pv[6], pLdt;
    const uint32_t pofs = opaque(dch2 * 128 + (tid & 127) * 2);
    pLdt = ldg16((const char*)prm.logdt + dch2);
#pragma unroll
    for (int i = 0; i < 2; i++) pv[i] = ldg16((const char*)prm.prm6[i] + pofs);
    STAMP(0);

    if (warp >= 20) {
        unsigned epoch = 0;
        if (warp == 20) {
            if (lane == 0) {
#pragma unroll
                for (int i = 0; i < 13; i++)
                    asm volatile("mbarrier.init.shared::cta.b64 [%0], %1;" :: "r"(mb + i * 8), "r"((i == MB_R || i < 2) ? 2 : i < 5 ? (nslot + 1) / 3 : i == MB_Y ? 1 + 4 * nslot : 1) : "memory");
                asm volatile("fence.mbarrier_init.release.cluster;" ::: "memory");
                arm(mb + MB_W1 * 8, 92160); arm(mb + MB_W2 * 8, nslot * 9216); arm(mb + MB_KEY * 8, 256); arm(mb + MB_GU * 8, nslot * 1024); arm(mb + MB_T * 8, 576 * XW);
                const int bytes = max(min(18, L_ - 18 * (int)blockIdx.x), 1) * (D_ * 2);
                arm(mb + MB_R * 8, bytes);
            }
            __syncwarp();
        } else if (warp == 22) {
            epoch = ld_rlx(&g_s.epoch);
            if (lane < 18 ? 18 * c + lane < 256 : lane < 31) (lane < 18 ? &g_s.acc[256 * q + 18 * c] : &g_s.fin[13 * (int)blockIdx.x - 18])[lane] = make_float4(0.f, 0.f, 0.f, 0.f);
        } else if (warp == 23 && lane == 0) asm volatile("prefetch.tensormap [%0];" :: "l"(&tmX) : "memory");
        asm volatile("barrier.cluster.arrive.relaxed.aligned;" ::: "memory");
        bar_sync(12, NTHR);
        uint4 wv = make_uint4(0, 0, 0, 0), wv2, wv3;
        if (warp == 22) {
            if (lane == 0) { sts32(sb + SM_SC + 28, epoch); asm volatile("mbarrier.arrive.shared::cta.b64 _, [%0];" :: "r"(mb + MB_R * 8) : "memory"); }
            epoch++;
            asm volatile("fence.acq_rel.gpu;" ::: "memory");
            __syncwarp();
            if (lane == 0) asm volatile("red.relaxed.gpu.global.add.u32 [%0], 1;" :: "l"(&g_s.zcnt) : "memory");
            STAMP(1);
            wv2 = ldg128((const uint4*)prm.wr + lane); wv3 = ldg128((const uint4*)prm.wr + 32 + lane);
            if (lane < 8) wv = ldg128((const uint4*)prm.wr + 64 + lane);
            if (lane < 5) {
                uint4 v = make_uint4(0, 0, 0, 0);
                if (lane < nslot) v = ldg128((const uint4*)(prm.wr + d0) + lane);
                sts128(sb + SM_DW + lane * 16, v.x, v.y, v.z, v.w);
            }
            __syncwarp();
            if (lane < 5) asm volatile("mbarrier.arrive.shared::cta.b64 _, [%0];" :: "r"(mb + (MB_X + lane) * 8) : "memory");
        }
        if (warp == 21) {
            if (lane == 0) { asm volatile("prefetch.tensormap [%0];" :: "l"(&tmG) : "memory"); asm volatile("prefetch.tensormap [%0];" :: "l"(&tmU) : "memory"); asm volatile("prefetch.tensormap [%0];" :: "l"(&tmD) : "memory"); }
            __syncwarp();
            const float dsk = bf_lo(ldg16(prm.dskip + min(d0 + 2 * (lane & 28) + q, D_ - 1)));
            bar_sync(0, 672);
            {
                const uint2 m = lds64(sb + SM_KG + min(lane, 19) * 8);
                unsigned Em = max(m.x, __shfl_xor_sync(~0u, m.x, 1));
                Em = max(Em, __shfl_xor_sync(~0u, Em, 2));
                Em = max(Em, min(__float_as_uint(fabsf(dsk) * (1.f / 8192.f)) >> 23, 253u));
                const float f = __uint_as_float(max((int)(127 + m.x - Em), 0) << 23);
                float s0 = (float)(int)m.y * f;
                s0 += __shfl_xor_sync(~0u, s0, 1); s0 += __shfl_xor_sync(~0u, s0, 2);
                if (lane < 20) {
                    sts16(sb + SM_RK + lane * 2, pack_f16(f, 0.f));
                    sts32(sb + SM_SC + (lane & 28), Em * 0x00800080u);
                    put16(sb + SM_PN + (lane >> 2) * PN_SZ, pack_f16(s0 * (1.f / 16777216.f) + dsk * __uint_as_float((254u - Em) << 23), 0.f));
                }
                __syncwarp();
            }
            bar_sync(15, 672);
            asm volatile("fence.proxy.async.shared::cta;" ::: "memory");
#pragma unroll 1
            for (int i = 0; i < 24; i++) {
                if (lane == 0) tma2d(sb + SM_WG + i * 3840, i < 12 ? &tmG : &tmU, 320 * c + 8 * nslot * q, 48 * (i < 12 ? i : i - 12), mb + MB_W1 * 8);
            }
            STAMP(1);
        } else {
        if (warp == 20) {
            if (lane == 0) {
                asm volatile("cp.async.bulk.shared::cluster.global.mbarrier::complete_tx::bytes [%0], [%1], %2, [%3];"
                             :: "r"(sb + SM_ROW), "l"(prm.x + min(18 * (int)blockIdx.x, L_ - 1) * D_), "r"(max(min(18, L_ - 18 * (int)blockIdx.x), 1) * (D_ * 2)), "r"(mb + MB_R * 8) : "memory");
            }
            __syncwarp();
            mbar_wait(mb + MB_R * 8);
            if (lane == 0) {
                asm volatile("cp.async.bulk.tensor.5d.shared::cluster.global.mbarrier::complete_tx::bytes [%0], [%1, {%3, %4, %5, %5, %5}], [%2];"
                             :: "r"(sb + SM_XTL), "l"(&tmX), "r"(mb + MB_T * 8), "r"(d0 & ~15), "r"(8 * q), "r"(0) : "memory");
            }
            STAMP(6);
        }
        {
            const int idx = lane * 3 + max(warp - 21, 0), sl = nslot - 1 - (idx >> 3), pe = (idx + q + 1) & 7;
            const uint32_t rb_ = mapa(sb, pe);
            uint32_t cd = rb_ + SM_U + 128 + q * UP + sl * US, cs = sb + SM_XT + 128 + (q & 3) * 16 + pe * YP + sl * YS, cm = rb_ + SM_MB + (MB_X + sl) * 8;
            int act = sl < 0 ? 0 : pe == q ? -1 : 1;
            PIN(cd); PIN(cs); PIN(cm); PIN(act);
            asm volatile("barrier.cluster.wait.aligned;" ::: "memory");
            mbar_wait(mb + MB_R * 8);
            bar_sync(13, 608);
            asm volatile("fence.proxy.async.shared::cta;" ::: "memory");
            if (act < 0) arm(cm, 7 * 512);
            __syncwarp();
            if (act > 0)
                asm volatile("cp.async.bulk.shared::cluster.shared::cta.mbarrier::complete_tx::bytes [%0], [%1], 512, [%2];" :: "r"(cd), "r"(cs), "r"(cm) : "memory");
        }
        STAMP(1);
        if (warp == 20 && lane == 0) { asm volatile("prefetch.tensormap [%0];" :: "l"(&tmO) : "memory"); asm volatile("prefetch.tensormap [%0];" :: "l"(&tmH) : "memory"); }
        if (warp == 22) {
            __syncwarp();
            mbar_wait(mb + (MB_X + 1) * 8);
            const uint32_t old = (epoch & 1) ? 0u : 0x40004000u;
#pragma unroll
            for (int t = 0; t < 2; t++)
#pragma unroll
                for (int r = 0; r < 2; r++)
                    if ((lane & 7) < 6) g_s.cand[r * (64 * NCL * 6) + ((q * 8 + 4 * t + (lane >> 3)) * NCL + c) * 6 + (lane & 7)] = make_uint4(old, old, old, old);
            float a[4] = {0.f, 0.f, 0.f, 0.f};
            const uint32_t one = 0x3F803F80u;
            mma_bf16(a, one, one, one, one, wv.x, wv.y);  mma_bf16(a, one, one, one, one, wv.z, wv.w);
            mma_bf16(a, one, one, one, one, wv2.x, wv2.y); mma_bf16(a, one, one, one, one, wv2.z, wv2.w);
            mma_bf16(a, one, one, one, one, wv3.x, wv3.y); mma_bf16(a, one, one, one, one, wv3.z, wv3.w);
            float s = a[0] + a[1];
            s += __shfl_xor_sync(~0u, s, 1); s += __shfl_xor_sync(~0u, s, 2);
            stsf(sb + SM_SC + 24, s);
            __syncwarp();
            if (lane == 0) {
                int n = 0;
                while ((int)(ld_acq(&g_s.zcnt) - epoch * NCTA) < 0 && ++n < SPIN_LIMIT) __nanosleep(200);
                arm(mb + MB_Y * 8, 8 * 512 * nslot);
                if (blockIdx.x == 0) g_s.epoch = epoch;
            }
            STAMP(2);
        }
        if (warp == 23) {
#pragma unroll 1
            for (int kk = nslot - 1; kk >= 0; kk--) {
                __syncwarp();
                bar_sync(6 + kk, 160);
                if (kk < 2) mbar_wait(mb + MB_W1 * 8);
                if (lane == 0) { asm volatile("fence.proxy.async.shared::cta;" ::: "memory"); tma2d(sb + SM_FAR + kk * FAR_SZ, &tmD, 72 * q, 320 * c + 64 * kk, mb + MB_W2 * 8); }
            }
        }
        }
        __syncwarp();
        if (warp == 20) {
            bar_sync(11, 672);
            asm volatile("fence.proxy.async.shared::cta;" ::: "memory");
            bar_sync(14, 768);
            if (elect()) {
                asm volatile("cp.async.bulk.tensor.5d.global.shared::cta.bulk_group [%0, {%2, %4, %4, %4, %3}], [%1];" :: "l"(&tmH), "r"(sb + SM_XT + 16384), "r"(d0 + ((c & 1) ? 0 : 32)), "r"(8 * q), "r"(0) : "memory");
                asm volatile("cp.async.bulk.tensor.5d.global.shared::cta.bulk_group [%0, {%2, %4, %4, %4, %3}], [%1];" :: "l"(&tmO), "r"(sb + SM_XT), "r"(d0 + (c & 1) * 8), "r"(8 * q), "r"(0) : "memory");
                asm volatile("cp.async.bulk.commit_group;" ::: "memory");
            }
        } else bar_sync(14, 768);
        __syncwarp();
        const uint32_t ft = (tid >> 4) & 7, fj = d0 / 3 + (lane & 15), tok = ~lds32(sb + SM_SEL + ft * 8) & 2047;
        float v[3], cnt = 0.f;
#pragma unroll
        for (int i = 0; i < 3; i++) {
            const uint32_t cl = 3 * fj + i - d0, cf = cl - (c & 1) * 8;
            const bool ok = cl < 8 * nslot && ((tok >> 3) & 7) == q;
            const uint32_t u = lds16(sb + SM_XT + (cf < 32 ? tslot(tok) * 64 + cf * 2 : 16384 + tslot(tok) * 16 + (cl & 7) * 2));
            v[i] = ok ? __uint_as_float(u << 16) : 0.f;
            if (ok) cnt += 1.f;
        }
        if (warp == 20 && elect()) {
            asm volatile("cp.async.bulk.wait_group 0;" ::: "memory");
            asm volatile("fence.proxy.async.global;" ::: "memory");
            asm volatile("mbarrier.arrive.shared::cta.b64 _, [%0];" :: "r"(mb + MB_OUT * 8) : "memory");
        }
        __syncwarp();
        mbar_wait(mb + MB_OUT * 8);
        STAMP(5);
        if (cnt != 0.f) finish(prm, (ft * 192 + fj) * 16, (tok * D_ + 3 * fj) * 2, v, cnt);
        return;
    }

    const int g = lane >> 2, cq = lane & 3;
    const int k = warp >> 2, wq = warp & 3;
    const int trow = 18 * blockIdx.x + warp;
    const bool rowact = warp < 18 && trow < L_;
#pragma unroll
    for (int i = 2; i < 6; i++) pv[i] = ldg16((const char*)prm.prm6[i] + pofs);
    const int tn = 16 * (warp & 15) + g;
    uint32_t xa[5], xb[5];
    asm volatile("barrier.cluster.arrive.relaxed.aligned;" ::: "memory");
    char* const st1p = (char*)g_s.st1 + opaque(((((trow >> 3) & 7) * 256 + ((trow >> 6) & 31) * 8 + (trow & 7)) * 8 + lane) * 4);
    const bool pub = rowact && (lane & 0x1B) == 0;
    if (pub) st_rlx128(st1p, 0, 0, 0, 0);
    {
        const uint32_t za = sb + SM_P + tid * 16;
        sts128(za, 0, 0, 0, 0);
        if (tid < (SM_MISC - SM_P) / 16 - 640) sts128(za + 10240, 0, 0, 0, 0);
        sts128(sb + SM_U + ((tid >> 3) & 7) * UP + k * US + (lane & 7) * 16, 0, 0, 0, 0);
    }
    bar_sync(12, NTHR);
    const uint32_t dep = lds32(sb + SM_P);
#define PV(x) __uint_as_float(__byte_perm(dep, x, 0x5410))
    STAMP(1);
    const uint32_t fb = sb + SM_FAR + k * FAR_SZ;
    const uint32_t pn = sb + SM_PN + k * PN_SZ, pf = sb + SM_PF + k * PF_SZ;
    unsigned epoch, t258;
    {
        const uint32_t kb = fb + wq * 3072;
        const uint32_t kl = kb + lane * 16;
        uint32_t Af[4][4];
        float sr, si, z1r, z1i, z2r, z2i, z4r, z4i, hr, hi_;
        {
            const float dt = bfr(ex2f(PV(pLdt) * 1.4426950408889634f));
            const float e2 = dt * PV(pv[0]) * 1.4426950408889634f, an = dt * PV(pv[1]);
            float ar, ai, br, bi, cr, ci, dr, di;
            { const float m = ex2f(e2 * 8.f); ar = m * __cosf(an * 8.f); ai = m * __sinf(an * 8.f); }
            csq(br, bi, ar, ai); csq(cr, ci, br, bi); csq(dr, di, cr, ci);
            const H2C m4 = splat(cr, ci);
            {
                float r3, i3;
                cmul(r3, i3, ar, ai, br, bi);
                expand4(kl, kl + 1024, pack_f16(1.f, ar), pack_f16(br, r3), pack_f16(0.f, ai), pack_f16(bi, i3), m4);
            }
            expand8(kl + 512, kl + 1536, dr, di, ar, ai, br, bi, m4);
            { const float m = ex2f(e2); z1r = m * __cosf(an); z1i = -m * __sinf(an); }
            cexp_s(hr, hi_, e2 * 128.f, an * (-128.f * 0.15915494309189535f));
            csq(z2r, z2i, z1r, z1i); csq(z4r, z4i, z2r, z2i);
            const uint32_t dep2 = lds32(sb + SM_P + 4);
#define PW(x) __uint_as_float(__byte_perm(dep2, x, 0x5410))
            cmul(sr, si, PW(pv[4]), PW(pv[5]), dt * PW(pv[2]), dt * PW(pv[3]));
            const unsigned E = min(max(__reduce_max_sync(~0u, __float_as_uint(fmaxf(fabsf(sr), fabsf(si)))) >> 23, 1u), 253u);
            const float sc = __uint_as_float((254u - E) << 23);
            sr *= sc; si *= -sc;
            sts64(sb + SM_KG + warp * 8, E, __reduce_add_sync(~0u, __float2int_rn(sr * 16777216.f)));
        }
        __syncwarp();
#pragma unroll
        for (int ks = 0; ks < 4; ks++) ldsm4t(Af[ks], kb + (lane >> 3) * 512 + (lane & 7) * 16 + ks * 128);
        STAMP(2);
        const uint32_t la = kb + ((lane >> 3) & 1) * 512 + (lane >> 4) * 128 + (lane & 7) * 16;
        uint32_t b0[4], b1[4], b2[4], b3[4];
        auto ln1 = [&]() {
        mbar_wait(mb + MB_R * 8);
        epoch = lds32(sb + SM_SC + 28) + 1;
        {
            const uint32_t ra = sb + SM_ROW + warp * (D_ * 2);
            const uint4 r0 = lds128(ra + lane * 16), r1 = lds128(ra + 512 + lane * 16);
            const uint32_t rx[9] = {r0.x, r0.y, r0.z, r0.w, r1.x, r1.y, r1.z, r1.w, lds32(ra + 1024 + lane * 4)};
            float a0 = bf_lo(rx[0]), a1 = bf_hi(rx[0]), c0 = a0 * a0, c1 = a1 * a1;
#pragma unroll
            for (int i = 1; i < 9; i++) { const float l = bf_lo(rx[i]), h = bf_hi(rx[i]); a0 += l; a1 += h; c0 = fmaf(l, l, c0); c1 = fmaf(h, h, c1); }
            a0 += a1; c0 += c1;
            float s1 = ((lane & 1) ? c0 : a0) + __shfl_xor_sync(~0u, (lane & 1) ? a0 : c0, 1);
#pragma unroll
            for (int o = 2; o < 32; o <<= 1) s1 += __shfl_xor_sync(~0u, s1, o);
            const float s2 = __shfl_xor_sync(~0u, s1, 1);
            const uint32_t ms = ln_stats(s1, s2);
            const uint32_t p0 = __byte_perm(ms, epoch | 0x8000u, 0x5410), p1 = rsplit(rcpf(bf_hi(ms)));
            if (pub) st_rlx128(st1p, p0, p1, epoch, lane);
        }
        mbar_wait(mb + MB_R * 8);
        STAMP(1);
        };
        const uint4* sp = &g_s.st1[(256 * q + tn) * 2];
        uint2 sa, sc;
        auto poll = [&]() { sa = ld_rlx64(sp); sc = ld_rlx64(sp + 16); };
        auto norm = [&]() {
        STAMP(3);
        if (warp < 16) {
            uint32_t va[5], vc[5];
            poll();
            mbar_wait(mb + MB_T * 8);
            {
                const uint32_t xt = sb + SM_XTL + (c & 1) * 16 + (36 * (warp & 7) + 9 * (warp >> 3) + g) * (2 * XW);
                uint4 a4 = lds128(xt + cq * 16), b4 = lds128(xt + cq * 16 + 36 * XW);
                va[0] = a4.x; va[1] = a4.y; va[2] = a4.z; va[3] = a4.w; va[4] = lds32(xt + 64 + cq * 4);
                vc[0] = b4.x; vc[1] = b4.y; vc[2] = b4.z; vc[3] = b4.w; vc[4] = lds32(xt + (64 + 36 * XW) + cq * 4);
            }
            const int d4 = 2 * (lane >> 3) + (lane & 1), d1_ = lane & 7;
            const uint32_t own = SM_U + 128 + q * (UP - YP), oth = SM_XT + 128 + (q & 3) * 16;
            uint32_t a4 = sb + warp * 32 + d4 * YP + (d4 == q ? own : oth) + ((lane & 7) >> 1) * YS;
            uint32_t a1 = sb + warp * 32 + d1_ * YP + (d1_ == q ? own : oth) + 4 * YS + (lane & 8) * 2;
            PIN(a4); PIN(a1);
            uint32_t tag = __byte_perm(epoch | 0x8000u, 0, 0x1010);
            PIN(tag);
            mbar_wait(mb + MB_T * 8);
            int n = 0;
            while (__byte_perm(sa.x, sc.x, 0x7632) != tag && ++n < SPIN_LIMIT) poll();
            STAMP(4);
#pragma unroll
            for (int i = 0; i < 5; i++) {
                va[i] = norm2(va[i], sa.x, sa.y); va[i] = pack_f16(bf_lo(va[i]), bf_hi(va[i]));
                vc[i] = norm2(vc[i], sc.x, sc.y); vc[i] = pack_f16(bf_lo(vc[i]), bf_hi(vc[i]));
            }
            stsm4t(a4, va[0], va[1], va[2], va[3]); stsm4t(a4 + 16, vc[0], vc[1], vc[2], vc[3]); stsm2t(a1, va[4], vc[4]);
            bar_arrive(13, 608);
            {
            const uint32_t xh = sb + SM_XTL + (c & 1) * 16 + (9 * __byte_perm(0x12100200, 0x13110301, g) + 72 * (warp & 1) + (warp >> 1)) * (2 * XW);
            const uint4 c4 = lds128(xh + cq * 16), d4_ = lds128(xh + cq * 16 + 72 * XW);
            xa[0] = c4.x; xa[1] = c4.y; xa[2] = c4.z; xa[3] = c4.w; xa[4] = lds32(xh + 64 + cq * 4);
            xb[0] = d4_.x; xb[1] = d4_.y; xb[2] = d4_.z; xb[3] = d4_.w; xb[4] = lds32(xh + (64 + 72 * XW) + cq * 4);
            }
        }
        STAMP(5);
        __syncwarp();
        bar_sync(15, 672);
        Af[0][0] |= lds32(sb + SM_P);
        };
        cmul(sr, si, sr, si, z1r, z1i);
        {
            const H2C h4 = splat(z4r, z4i);
            expand8(kl, kl + 512, sr, si, z1r, z1i, z2r, z2i, h4);
            cmul(sr, si, sr, si, hr, hi_);
            expand8(kl + 1024, kl + 1536, sr, si, z1r, z1i, z2r, z2i, h4);
        }
        __syncwarp();
        ldsm4t(b0, la); ldsm4t(b1, la + 256); ldsm4t(b2, la + 1024); ldsm4t(b3, la + 1280);
        cmul(z1r, z1i, z1r, z1i, hr, hi_);
        cmul(sr, si, sr, si, z1r, z1i);
        expand8(kl, kl + 512, sr, si, z2r, z2i, z4r, z4i, splat(hr, hi_));
        asm volatile("barrier.cluster.wait.aligned;" ::: "memory");
        bar_arrive(0, 672);
        ln1();
        csq(z1r, z1i, z1r, z1i);
        cmul(sr, si, sr, si, z1r, z1i);
        csq(z2r, z2i, hr, hi_);
        expand8(kl + 1024, kl + 1536, sr, si, z4r, z4i, hr, hi_, splat(z2r, z2i));
        csq(z1r, z1i, z1r, z1i);
        cmul(sr, si, sr, si, z1r, z1i);
        csq(z4r, z4i, z2r, z2i);
        expand8(kl + 2048, kl + 2560, sr, si, hr, hi_, z2r, z2i, splat(z4r, z4i));
        norm();
        {
            uint32_t c0[4], c1[4], c2[4], c3[4], e0[4], e1[4];
            float t[6][4];
            ldsm4t(c0, la); ldsm4t(c2, la + 1024);
            mma_f16_z(t[0], Af[0], b0[0], b0[1]);
            const uint32_t lb = la | (__float_as_uint(t[0][0]) & zero);
            mma_f16_z(t[1], Af[0], b2[0], b2[1]); mma_f16_z(t[2], Af[0], c0[0], c0[1]); mma_f16_z(t[3], Af[0], c2[0], c2[1]);
            ldsm4t(e0, lb + 2048); ldsm4t(c1, lb + 256); ldsm4t(c3, lb + 1280); ldsm4t(e1, lb + 2304);
            mma_f16(t[0], Af[1], b0[2], b0[3]); mma_f16(t[1], Af[1], b2[2], b2[3]); mma_f16(t[2], Af[1], c0[2], c0[3]); mma_f16(t[3], Af[1], c2[2], c2[3]);
            mma_f16(t[0], Af[2], b1[0], b1[1]); mma_f16(t[1], Af[2], b3[0], b3[1]);
            mma_f16_z(t[4], Af[0], e0[0], e0[1]); mma_f16_z(t[5], Af[1], e0[2], e0[3]);
            mma_f16(t[2], Af[2], c1[0], c1[1]); mma_f16(t[3], Af[2], c3[0], c3[1]);
            mma_f16(t[4], Af[2], e1[0], e1[1]); mma_f16(t[5], Af[3], e1[2], e1[3]);
            mma_f16(t[0], Af[3], b1[2], b1[3]); mma_f16(t[1], Af[3], b3[2], b3[3]); mma_f16(t[2], Af[3], c1[2], c1[3]); mma_f16(t[3], Af[3], c3[2], c3[3]);
#pragma unroll
            for (int i = 0; i < 4; i++) t[4][i] += t[5][i];
            stsm4(kl + 1024, pack_f16(t[0][0], t[0][1]), pack_f16(t[0][2], t[0][3]), pack_f16(t[1][0], t[1][1]), pack_f16(t[1][2], t[1][3]));
            stsm2(kl + 1536, pack_f16(t[2][0], t[2][1]), pack_f16(t[2][2], t[2][3]));
            sts64(kb + lane * 8 + 1792, pack_f16(t[3][1], t[3][0]), pack_f16(t[3][3], t[3][2]));
            sts64(kb + lane * 8 + 2048, pack_f16(t[4][1], t[4][0]), pack_f16(t[4][3], t[4][2]));
        }
        bar_sync(1 + k, 128);
        const uint2 rr = lds64(opaque(sb + SM_RK + k * 8));
        const int tq = (wq + k + 2) & 3;
        const uint32_t ra = lane * 8 + opaque(fb + (tq == 1 ? 2048 : tq * 256 + 1024));
        auto comb = [&](uint32_t a, uint32_t& x, uint32_t& y) {
            const uint2 p0 = lds64(a), p1 = lds64(a + 3072), p2 = lds64(a + 6144), p3 = lds64(a + 9216);
            x = comb4(p0.x, p1.x, p2.x, p3.x, rr.x, rr.y); y = comb4(p0.y, p1.y, p2.y, p3.y, rr.x, rr.y);
        };
        uint32_t w0, w1;
        comb(ra, w0, w1);
        const bool last = lane == 31;
        if (tq == 0) {
            uint32_t v0, v1;
            comb(ra + 256, v0, v1);
            const uint32_t n0 = __shfl_sync(~0u, lane ? w0 : v0, lane + 1);
            uint32_t n1 = __shfl_sync(~0u, v0, lane + 1);
            if (last) n1 = v1 >> 16;
            sts128(pn + 12 + lane * 16, __byte_perm(w1, w0, 0x7610), __byte_perm(w1, 0, 0x1032), __byte_perm(n0, w1, 0x7610), __byte_perm(n0, 0, 0x1032));
            sts128(pn + 524 + lane * 16, __byte_perm(v1, v0, 0x7610), __byte_perm(v1, 0, 0x1032), __byte_perm(n1, v1, 0x7610), __byte_perm(n1, 0, 0x1032));
            if (lane == 0) { sts16(pn + 4, w0); sts32(pn + 8, __byte_perm(w0, 0, 0x1032)); }
        } else if (tq == 1) {
            const uint32_t ph = pf + P_H7 + (g & 1) * (2 * P_HS) + cq * 64 + (g >> 1) * 4 + (cq & 2) * 16, sw = (cq & 2) ? 0x3210 : 0x1032;
            w0 = __byte_perm(hmul2(w0, 0x18001800u), 0, sw); w1 = __byte_perm(hmul2(w1, 0x18001800u), 0, sw);
            const uint32_t pi = ph + 32 - (cq & 2) * 32;
            put16(ph, w0); put16(pi, w0 >> 16); put16(ph + 16, w1); put16(pi + 16, w1 >> 16);
        } else if (tq == 2) {
            uint32_t n = __shfl_sync(~0u, w0, lane == 30 ? 1 : lane + 2);
            if (last) { put16(pf, hmul2(w1, 0x18001800u) >> 16); w1 = hadd2(w1, hneg2(__byte_perm(w1, 0, 0x3232))); n = 0; }
            const bool od = lane & 1;
            const uint32_t pa = pn + 1036 + (lane >> 1) * 32 + (od ? 528 : 0), pb = pa + (od ? -16 : 16);
            const uint32_t u0 = od ? w1 : w0, x0 = od ? n : w1, u1 = od ? w0 : w1, x1 = od ? w1 : n;
            const uint32_t b0 = __byte_perm(u0, 0, 0x3232), b1 = __byte_perm(u1, 0, 0x3232);
            sts128(pa, __byte_perm(u0, 0, 0x1032), b0, b0, __byte_perm(x0, u0, 0x7610));
            sts128(pb, __byte_perm(u1, 0, 0x1032), b1, b1, __byte_perm(x1, u1, 0x7610));
        } else {
            const uint32_t pa = pf + ((g & 1) ? 3 * P_GS : P_GS) + cq * 32 + (g >> 1) * 4;
            const uint32_t pb = pa + ((g & 1) ? 4 - 3 * P_GS : P_GS);
            w0 = hmul2(w0, 0x18001800u); w1 = hmul2(w1, 0x18001800u);
            put16(pa, w0 >> 16); put16(pb, w0); put16(pa + 16, w1 >> 16); put16(pb + 16, w1);
            if (last) put16(pf + P_H7 + P_HS, w1);
        }
        bar_sync(1 + k, 128);
        t258 = w0;
    }
    STAMP(6);

    mbar_wait(mb + (MB_X + k) * 8);
    STAMP(7);
    if (k < nslot) {
        const int role = (wq + k) & 3;
        const uint32_t ub = sb + SM_U + k * US + 128;
        const uint32_t l16 = lane * 16, tz = (lane & 28) - 8 * cq, tz4 = tz * 4;
        if (role) {
            const uint32_t al = cq * (2 * UP + 32) + tz4, au = opaque(ub + (3 - role) * 128), a1 = al + au, a0 = (cq ? al : al + (8 * UP - 16)) + au - 2 * UP;
            const uint4 q0 = lds128(a0), q1 = lds128(a0 + UP), q2 = lds128(a1), q3 = lds128(a1 + UP);
            const uint32_t U[16] = {q0.x, q0.y, q0.z, q0.w, q1.x, q1.y, q1.z, q1.w, q2.x, q2.y, q2.z, q2.w, q3.x, q3.y, q3.z, q3.w};
            uint32_t V[14], Q[14], R4[12], T[8];
#pragma unroll
            for (int i = 2; i < 14; i++) { V[i] = __byte_perm(U[i], U[i + 1], 0x5432); Q[i] = hadd2(U[i], V[i]); }
            const uint32_t rb = l16 + opaque(fb + (3 - role) * 512);
#pragma unroll
            for (int i = 0; i < 8; i++) T[i] = hadd2(V[5 + i], Q[6 + i]);
            sts128(rb + F_E3, T[0], T[1], T[2], T[3]); sts128(rb + F_O3 + 16, T[4], T[5], T[6], T[7]);
            asm volatile("{ .reg .pred p; setp.ne.u32 p, %10, 1; @p st.shared.v4.u32 [%0], {%2,%3,%4,%5}; @p st.shared.v4.u32 [%1], {%6,%7,%8,%9}; }"
                         :: "r"(rb + F_E2), "r"(rb + F_O2), "r"(Q[6]), "r"(Q[7]), "r"(Q[8]), "r"(Q[9]), "r"(Q[10]), "r"(Q[11]), "r"(Q[12]), "r"(Q[13]), "r"(role) : "memory");
#pragma unroll
            for (int i = 2; i < 12; i++) R4[i] = hadd2(Q[i], Q[i + 1]);
#pragma unroll
            for (int i = 0; i < 8; i++) T[i] = hadd2(R4[3 + i], U[5 + i]);
            sts128(rb + F_O5, T[0], T[1], T[2], T[3]); sts128(rb + F_E5, T[4], T[5], T[6], T[7]);
            if (role != 1) {
                uint32_t S[8];
#pragma unroll
                for (int i = 0; i < 8; i++) S[i] = hadd2(R4[2 + i], i < 7 ? T[i + 1] : hadd2(R4[11], U[13]));
                sts128(rb + F_O9, S[0], S[1], S[2], S[3]); sts128(rb + F_E9 + 16, S[4], S[5], S[6], S[7]);
#pragma unroll
                for (int i = 0; i < 8; i++) S[i] = hadd2(T[i], hadd2(V[2 + i], V[5 + i]));
                sts128(rb + F_E7, S[0], S[1], S[2], S[3]); sts128(rb + F_O7, S[4], S[5], S[6], S[7]);
            }
        } else if (lane == 0) {
            const uint4 m = lds128(ub + 23 * 16 + 7 * UP);
            const uint32_t U[6] = {lds32(ub + 23 * 16 + 6 * UP + 12), m.x, m.y, m.z, m.w, lds32(ub + 24 * 16)};
            uint32_t Q[5];
#pragma unroll
            for (int i = 0; i < 5; i++) Q[i] = hadd2(U[i], __byte_perm(U[i], U[i + 1], 0x5432));
            sts128(fb + F_O5 + 96 * 16, hadd2(hadd2(Q[0], Q[1]), U[2]), hadd2(hadd2(Q[1], Q[2]), U[3]), hadd2(hadd2(Q[2], Q[3]), U[4]), hadd2(hadd2(Q[3], Q[4]), U[5]));
            sts128(fb + F_O3, 0, 0, 0, 0); sts128(fb + F_E9, 0, 0, 0, 0);
            sts16(pn + 258 * 4, t258);
        }
        bar_sync(1 + k, 128);
        float acc[4][4];
        uint32_t Q[4][4];
        {
            const int h = role & 1, part = role >> 1;
            float fa[7][4];
            uint32_t B[3][4];
            const uint32_t po = tz + opaque(pf + part * (2 * P_GS)), ba = l16 + opaque(fb + (part == h ? 0 : F_O5 + h * 16));
#pragma unroll
            for (int s = 1; s >= 0; s--) {
#pragma unroll
                for (int i = 0; i < 3; i++) { Q[i][0] = lds32(po + (s * P_GS + i * 64)); if (i < 2) Q[i][1] = lds32(po + (s * P_GS + i * 64 + 32)); }
#pragma unroll
                for (int i = 0; i < 3; i++) ldsm4t(B[i], ba + (s * F_E3 + i * 512));
#pragma unroll
                for (int i = 0; i < 3; i++) { Q[i][3] = CP(Q[i][0]); if (i) Q[i][2] = CP(Q[i - 1][1]); }
                Q[0][2] = ZF(s ? tz : Q[0][0]); Q[2][1] = ZF(s ? l16 : Q[2][0]);
#pragma unroll
                for (int dl = 0; dl < 3; dl++)
#pragma unroll
                    for (int ap = 0; ap < 6 - dl; ap++) {
                        if (s == 1 && dl == 0) mma_f16_z(fa[ap + 1], Q[0], B[ap >> 1][2 * (ap & 1)], B[ap >> 1][2 * (ap & 1) + 1]);
                        else mma_f16(fa[ap + 1 + dl], Q[dl], B[ap >> 1][2 * (ap & 1)], B[ap >> 1][2 * (ap & 1) + 1]);
                    }
            }
#pragma unroll 1
            for (int s = role; s == 1; s++) {
                ldsm2t(B[0][0], B[0][1], fb + ((lane & 15) == 15 ? F_O5 : F_O3));
#pragma unroll
                for (int dl = 1; dl < 3; dl++) mma_f16(fa[dl], Q[dl], B[0][0], B[0][1]);
            }
            const uint32_t bh = l16 + opaque(fb + F_E7 + h * F_H + part * 2048), ph = tz + opaque(pf + P_H7 + part * (2 * P_HS));
#pragma unroll 1
            for (int s = part; s == 1; s++) {
                Q[2][1] = ZF(Q[2][3]); Q[2][2] = ZF(Q[2][2]); Q[2][0] = lds32(ph - P_HS);
                ldsm4t(B[0], bh - 1024); ldsm4t(B[1], bh - 512);
                Q[2][3] = CP(Q[2][0]);
#pragma unroll
                for (int ap = 0; ap < 4; ap++) mma_f16(fa[ap + 3], Q[2], B[ap >> 1][2 * (ap & 1)], B[ap >> 1][2 * (ap & 1) + 1]);
            }
            {
                Q[0][2] = ZF(tid);
#pragma unroll
                for (int i = 0; i < 4; i++) { Q[i][0] = lds32(ph + i * 64); Q[i][1] = lds32(ph + (i * 64 + 32)); }
                ldsm4t(B[0], bh); ldsm4t(B[1], bh + 512);
#pragma unroll
                for (int i = 0; i < 4; i++) { Q[i][3] = CP(Q[i][0]); if (i) Q[i][2] = CP(Q[i - 1][1]); }
#pragma unroll
                for (int dl = 0; dl < 4; dl++)
#pragma unroll
                    for (int ap = 0; ap < 4 - dl; ap++) mma_f16(fa[ap + 3 + dl], Q[dl], B[ap >> 1][2 * (ap & 1)], B[ap >> 1][2 * (ap & 1) + 1]);
            }
            const uint32_t da = (cq * 2048 + tz4) + opaque(fb + role * 128);
            bar_sync(1 + k, 128);
#pragma unroll
            for (int i = 1; i < 4; i++)
                stsm4(da + i * 512, pack_f16(fa[2 * i - 1][0], fa[2 * i - 1][1]), pack_f16(fa[2 * i - 1][2], fa[2 * i - 1][3]),
                      pack_f16(fa[2 * i][0], fa[2 * i][1]), pack_f16(fa[2 * i][2], fa[2 * i][3]));
            asm("shl.b32 %0, 0x6000, %1;" : "=r"(Q[0][0]) : "r"(tz4));
            Q[0][1] = ZF(Q[0][0]); Q[0][2] = ZF(tz4); Q[0][3] = CP(Q[0][0]);
            const uint32_t ra = l16 + opaque(fb + wq * 2016);
            acc[0][0] = acc[0][1] = acc[0][2] = acc[0][3] = 0.f;
            if (wq == 3) {
                const uint32_t uw = lds32(ub), kw = lds32(pf);
                const float2 uf = __half22float2(*(const __half2*)&uw);
                if ((lane | 4) == 31) acc[0][3] = (lane == 31 ? uf.x + uf.y : uf.x) * (__low2float(*(const __half2*)&kw) * 512.f);
            }
            bar_sync(1 + k, 128);
#pragma unroll
            for (int i = 1; i < 4; i++) {
                ldsm4(B[0], ra + i * 512);
                mma_f16_z(acc[i], Q[0], hadd2(B[0][0], B[0][2]), hadd2(B[0][1], B[0][3]));
            }
        }
        bar_arrive(6 + k, 160);
        STAMP(8);
        const uint32_t inv = lds32(opaque(sb + SM_SC + k * 4));
        const uint32_t yd = l16 + opaque(mapa(sb, 2 * wq) + (SM_XT + 128 + q * YP + k * YS + (k >> 2) * (q >> 1) * 16));
        {
            uint32_t pu = opaque(pn + 64 * (wq - 3));
#define pp (tz + pu)
            const uint32_t dlo = (((ub + 6 * UP) & 0x3FFFF) >> 4) | ((UP >> 4) << 16);
            uint32_t R[4][4];
            unsigned long long ds[4];
#pragma unroll
            for (int i = 0; i < 4; i++) asm volatile("mov.b64 %0, {%1, %2};" : "=l"(ds[i]) : "r"(dlo - i * (2 * UP >> 4)), "r"(8 | zero));
            auto loadQ = [&](uint32_t (&X)[4][4], uint32_t prev) {
#pragma unroll
                for (int i = 0; i < 4; i++) { X[i][0] = lds32(pp + i * 64); X[i][1] = lds32(pp + i * 64 + 32); }
                X[0][2] = CP(prev);
#pragma unroll
                for (int i = 0; i < 4; i++) { X[i][3] = CP(X[i][0]); if (i) X[i][2] = CP(X[i - 1][1]); }
                pu += 256;
            };
            auto issue = [&](uint32_t (&X)[4][4]) {
                asm volatile("wgmma.fence.sync.aligned;" ::: "memory");
#pragma unroll
                for (int i = 0; i < 4; i++) wgmma32(acc, X[i], ds[i]);
                asm volatile("wgmma.commit_group.sync.aligned;" ::: "memory");
#pragma unroll
                for (int i = 0; i < 4; i++) asm volatile("{ .reg .b32 l, h; mov.b64 {l, h}, %0; add.u32 l, l, %1; mov.b64 %0, {l, h}; }" : "+l"(ds[i]) : "r"(~zero));
            };
#pragma unroll
            for (int i = 0; i < 4; i++) {
                Q[i][0] = Q[i][1] = 0;
                if (wq + i >= 3) { Q[i][0] = lds32(pp + i * 64); Q[i][1] = lds32(pp + i * 64 + 32); }
            }
            Q[0][2] = CP(0);
#pragma unroll
            for (int i = 0; i < 4; i++) { Q[i][3] = CP(Q[i][0]); if (i) Q[i][2] = CP(Q[i - 1][1]); }
            pu += 256;
#pragma unroll 1
            for (int dl = 0; dl < 4; dl++) {
                issue(Q);
                asm volatile("wgmma.wait_group.sync.aligned 1;" ::: "memory");
                loadQ(R, Q[3][1]);
                issue(R);
                asm volatile("wgmma.wait_group.sync.aligned 1;" ::: "memory");
                loadQ(Q, R[3][1]);
            }
            issue(Q);
            asm volatile("wgmma.wait_group.sync.aligned 0;" ::: "memory");
        }
        const uint32_t pstep = mapa(sb, 1) - mapa(sb, 0), ym = mapa(mb + MB_Y * 8, 2 * wq);
#pragma unroll
        for (int e = 0; e < 2; e++)
            st_async4(yd + e * pstep, bmul2(pack_bf16(acc[0][2 * e], acc[0][2 * e + 1]), inv), bmul2(pack_bf16(acc[1][2 * e], acc[1][2 * e + 1]), inv),
                      bmul2(pack_bf16(acc[2][2 * e], acc[2][2 * e + 1]), inv), bmul2(pack_bf16(acc[3][2 * e], acc[3][2 * e + 1]), inv), ym + e * pstep);
        if (lane == 0) asm volatile("mbarrier.arrive.shared::cta.b64 _, [%0];" :: "r"(mb + MB_Y * 8) : "memory");
    }
    STAMP(9);
    uint32_t ha[5], hb[5];
    if (warp < 16) {
        const uint4 wk = lds128(sb + SM_DW + cq * 16);
        uint32_t sel[5] = {wk.x, wk.y, wk.z, wk.w, lds32(sb + SM_DW + 64 + cq * 4)}, sel2[5];
#pragma unroll
        for (int i = 0; i < 5; i++) {
            if (!(g & 1)) sel[i] = 0x3F803F80u;
            sel2[i] = sel[i]; PIN(sel2[i]);
        }
        uint32_t y4 = sb + SM_XT + 128 + warp * 32 + (2 * (lane >> 3) + (lane & 1)) * YP + ((lane & 7) >> 1) * YS;
        uint32_t y1 = sb + SM_XT + 128 + warp * 32 + (lane & 7) * YP + 4 * YS + (lane & 8) * 2 + (lane & 6) * 8;
        if (nslot != 5) {
            y1 = sb + SM_U;
            if (lane & 4) y4 = y1;
        }
        PIN(y4); PIN(y1);
        const uint32_t ao = (256 * q + tn) * 16;
        const uint32_t hta = opaque(sb + SM_HT + warp * 1024), htb = opaque(sb + SM_HT + 16384 + warp * 256);
        unsigned long long ap = (unsigned long long)((char*)g_s.acc + ao);
        asm volatile("add.u64 %0, %0, %1;" : "+l"(ap) : "l"((unsigned long long)zero));
        mbar_wait(mb + MB_Y * 8);
        STAMP(10);
        float ca[4] = {0.f, 0.f, 0.f, 0.f}, cb[4] = {0.f, 0.f, 0.f, 0.f};
        {
            uint32_t ya[4], yb[4], yc, yd;
            ldsm4t(ya, y4); ldsm4t(yb, y4 + 16); ldsm2t(yc, yd, y1);
#pragma unroll
            for (int i = 0; i < 4; i++) { ha[i] = badd2(xa[i], ya[i]); hb[i] = badd2(xb[i], yb[i]); }
            ha[4] = badd2(xa[4], yc); hb[4] = badd2(xb[4], yd);
        }
#pragma unroll
        for (int i = 0; i < 5; i++) { mma_bf16_k8(ca, ha[i], sel[i], ha[i]); mma_bf16_k8(cb, hb[i], sel2[i], hb[i]); }
        if (!(g & 1)) { ca[1] = ca[0]; cb[1] = cb[0]; }
        if (cq == (g >> 1)) {
            asm volatile("red.relaxed.gpu.global.add.v4.f32 [%0], {%1,%2,%3,%4};" :: "l"(ap), "f"(1.0f), "f"(ca[1]), "f"(ca[2]), "f"(ca[3]) : "memory");
            asm volatile("red.relaxed.gpu.global.add.v4.f32 [%0], {%1,%2,%3,%4};" :: "l"(ap + 128), "f"(1.0f), "f"(cb[1]), "f"(cb[2]), "f"(cb[3]) : "memory");
        }
        __syncwarp();
        mbar_wait(mb + MB_Y * 8);
#pragma unroll
        for (int i = 0; i < 4; i++) {
            asm volatile("or.b32 %0, %1, %2;" : "=r"(ha[i]) : "r"(ha[i]), "r"(zero));
            asm volatile("or.b32 %0, %1, %2;" : "=r"(hb[i]) : "r"(hb[i]), "r"(zero));
        }
        sts128(hta + lane * 16, ha[0], ha[1], ha[2], ha[3]); sts32(htb + lane * 4, ha[4]);
        sts128(hta + lane * 16 + 512, hb[0], hb[1], hb[2], hb[3]); sts32(htb + lane * 4 + 128, hb[4]);
        STAMP(11);
    }
    const int kq = warp / 5, mt = warp - 5 * kq;
    const int mi = lane >> 3, mr = lane & 7;
    const unsigned tk = (unsigned)tid / 72u, ck = tid - tk * 72;
    uint32_t A[9][4];
    auto loadA = [&]() {
        mbar_wait(mb + MB_W1 * 8);
        const uint32_t aa = sb + (mi & 1) * SM_WU + (8 * (mi >> 1) + mr) * 80 + (144 * 80 * kq + mt * 16);
#pragma unroll
        for (int s = 0; s < 9; s++) ldsm4t(A[s], aa + s * 1280);
    };
    const uint32_t par = (lds32(sb + SM_SC + 28) & 1) ? 0u : 0x40004000u;
    uint32_t go = (ck / 5u + ck) * 16, gs = sb + SM_SEL + 4 + (tk & 7) * 8;
    unsigned long long gb = (unsigned long long)((const char*)g_s.cand + go + (q & 1) * 92160);
    uint32_t xs = sb + SM_XS + tk * 16 + tid * 16;
    asm volatile("add.u64 %0, %0, %1;" : "+l"(gb) : "l"((unsigned long long)zero));
    PIN(xs); PIN(gs);
    auto outtile = [&]() {
        const uint2 sa = lds64(sb + SM_ST + tn * 8), sbb = lds64(sb + SM_ST + tn * 8 + 64);
#pragma unroll
        for (int i = 0; i < 5; i++) { ha[i] = badd2(ha[i], norm2(ha[i], sa.x, sa.y)); hb[i] = badd2(hb[i], norm2(hb[i], sbb.x, sbb.y)); }
        const bool hf = (c & 1) && cq == 0;
        const uint32_t o16 = sb + SM_XT + (hf ? 16384 + tn * 16 : tn * 64 + (cq - (c & 1)) * 16), o4 = sb + SM_XT + ((c & 1) ? tn * 64 + 48 : 16384 + tn * 16) + cq * 4;
        sts128(o16, ha[0], ha[1], ha[2], ha[3]); sts32(o4, ha[4]);
        sts128(o16 + (hf ? 128 : 512), hb[0], hb[1], hb[2], hb[3]); sts32(o4 + ((c & 1) ? 512 : 128), hb[4]);
    };
    if (warp < 8) {
        const float wsum = ldsf(sb + SM_SC + 24);
        const uint32_t idx = 2047 - (512 * ((tid >> 1) & 3) + 128 * ((tid >> 3) & 3) + 64 * (tid & 1) + 8 * q + warp);
        uint32_t km0 = mapa(mb + MB_KEY * 8, 2 * cq), km1 = mapa(mb + MB_KEY * 8, 2 * cq + 1), ka0 = mapa(sb + SM_RK + q * 32, 2 * cq), ka1 = mapa(sb + SM_RK + q * 32, 2 * cq + 1);
        unsigned long long c0 = (unsigned long long)((char*)g_s.cand + ((q * 8 * NCL + c) * 6 + cq) * 16), c1 = c0 + (64 - cq * 12);
        uint32_t hc = sb + SM_HT + cq * 16, h4a = sb + SM_HT + 16384 + cq * 4;
        uint32_t ca = sb + SM_KEY + warp * 128 + (warp & 1) * 32 + (lane & 28), r2a = sb + SM_KEY + cq * 16 + (cq >> 1) * 128;
        PIN(ca); PIN(r2a); PIN(km0); PIN(km1); PIN(ka0); PIN(ka1); PIN(hc); PIN(h4a);
        asm volatile("add.u64 %0, %0, %2; add.u64 %1, %1, %2;" : "+l"(c0), "+l"(c1) : "l"((unsigned long long)zero));
        uint4 s; int n = 0;
        uint32_t ox;
        do {
            s = ld_rlx128(&g_s.acc[256 * q + tid]);
            ox = __shfl_xor_sync(~0u, (lane & 1) ? s.z : s.w, 1);
        } while (__any_sync(~0u, __uint_as_float(s.x) != (float)NCL && ++n < SPIN_LIMIT));
        STAMP(16);
        const uint32_t ms = ln_stats(__uint_as_float((lane & 1) ? ox : s.z), __uint_as_float(s.y));
        const float rs = rcpf(bf_hi(ms));
        const uint32_t rb = pack_bf16(0.f, fmaf(-bf_lo(ms), wsum, __uint_as_float((lane & 1) ? s.w : ox)) * rs);
        const uint32_t key = (((rb ^ (((int)rb >> 31) | 0x80000000u)) >> 16) << 11) | idx;
        sts32(sb + SM_KEY + tid * 4, key);
        sts64(sb + SM_ST + tid * 8, ms, rsplit(rs));
        __syncwarp();
        uint32_t rank = rank4<8, 16>(sb + SM_KEY + warp * 128, key, ~zero);
        {
            const uint32_t sa = (rank * 4 ^ (warp & 1) * 32) + opaque(sb + SM_KEY + warp * 128);
            sts32(sa, key); sts32(sa + 1024, tid);
        }
        __syncwarp();
        const uint32_t mk = lds32(ca), t = lds32(ca + 1024);
        STAMP(17);
        bar_sync(12, 512);
        STAMP(18);
        const uint4 hv = lds128(hc + t * 64);
        const uint2 sv = lds64(sb + SM_ST + t * 8);
        const uint32_t h4 = lds32(h4a + t * 16);
        rank = rank4<4, 256>(r2a, mk, ~zero);
        const uint32_t rr = bmul2(sv.y, 0x3C803C80u);
        const uint32_t p0 = (norm2(hv.x, sv.x, rr) & 0xBFFFBFFFu) | par, p1 = (norm2(hv.y, sv.x, rr) & 0xBFFFBFFFu) | par, p2 = (norm2(hv.z, sv.x, rr) & 0xBFFFBFFFu) | par,
                       p3 = (norm2(hv.w, sv.x, rr) & 0xBFFFBFFFu) | par, p4 = (norm2(h4, sv.x, rr) & 0xBFFFBFFFu) | par;
        rank = quad_sum(rank);
        if (rank < 8) {
            st_async1(ka0 + rank * 4, mk, km0); st_async1(ka1 + rank * 4, mk, km1);
#pragma unroll
            for (int r = 0; r < 2; r++) {
                st_rlx128((void*)(c0 + (unsigned long long)rank * 1440 + r * 92160), p0, p1, p2, p3);
                asm volatile("st.relaxed.gpu.global.u32 [%0], %1;" :: "l"(c1 + (unsigned long long)rank * 1440 + r * 92160), "r"(p4) : "memory");
            }
        }
        __syncwarp();
    } else {
        mbar_wait(mb + MB_Y * 8); loadA();
        if (warp < 16) {
            bar_sync(12, 512);
        }
    }
    if (warp < 16) {
        outtile();
        if (warp >= 8) {
            uint32_t src = ((tid >> 2) - 64) * 1440, ma = sb + SM_RK - 256 + (tid >> 2) * 4, ra = sb + SM_RK + cq * 16;
            PIN(src); PIN(ma); PIN(ra);
            STAMP(19);
            mbar_wait(mb + MB_KEY * 8);
            STAMP(20);
            const uint32_t mk = lds32(ma);
            uint32_t rank = rank4<4, 64>(ra, mk, ~zero);
            rank = quad_sum(rank);
            sts64(sb + SM_SEL + rank * 8, mk, src);
        }
    }
    bar_sync(11, 672);
    STAMP(12);

    const char* gp = (const char*)gb + lds32(gs);
    uint4 hv = ld_rlx128(gp);
    if (warp < 8) loadA();
    uint32_t bx = sb + SM_XS + mr * 1168 + mi * 16 + 288 * kq, gd = mapa(sb, (kq & (NRED - 1)) * (8 / NRED)) + (SM_GU + (q * nslot + mt) * 128) + lane * 4;
    PIN(bx); PIN(gd);
    {
        if (warp < 18) {
            int n = 0;
            while (true) {
                sts128(xs, hv.x ^ par, hv.y ^ par, hv.z ^ par, hv.w ^ par);
                if (!__any_sync(~0u, ((hv.x ^ par) | (hv.y ^ par) | (hv.z ^ par) | (hv.w ^ par)) & 0x40004000u) || ++n >= SPIN_LIMIT) break;
                hv = ld_rlx128(gp);
            }
        }
    }
    bar_sync(14, 768);
    STAMP(13);
    float4 own;
    {
        float c0[4] = {0.f, 0.f, 0.f, 0.f}, c1[4] = {0.f, 0.f, 0.f, 0.f}, c2[4] = {0.f, 0.f, 0.f, 0.f};
        uint32_t b[5][4];
#pragma unroll
        for (int s = 0; s < 4; s++) ldsm4(b[s], bx + s * 64);
        asm volatile("ldmatrix.sync.aligned.m8n8.x2.shared.b16 {%0,%1}, [%2];" : "=r"(b[4][0]), "=r"(b[4][1]) : "r"(bx + 256) : "memory");
        mma_bf16(c0, A[0][0], A[0][1], A[0][2], A[0][3], b[0][0], b[0][1]);
        mma_bf16(c1, A[1][0], A[1][1], A[1][2], A[1][3], b[0][2], b[0][3]);
        mma_bf16(c2, A[2][0], A[2][1], A[2][2], A[2][3], b[1][0], b[1][1]);
        mma_bf16(c0, A[3][0], A[3][1], A[3][2], A[3][3], b[1][2], b[1][3]);
        mma_bf16(c1, A[4][0], A[4][1], A[4][2], A[4][3], b[2][0], b[2][1]);
        mma_bf16(c2, A[5][0], A[5][1], A[5][2], A[5][3], b[2][2], b[2][3]);
        mma_bf16(c0, A[6][0], A[6][1], A[6][2], A[6][3], b[3][0], b[3][1]);
        mma_bf16(c1, A[7][0], A[7][1], A[7][2], A[7][3], b[3][2], b[3][3]);
        mma_bf16(c2, A[8][0], A[8][1], A[8][2], A[8][3], b[4][0], b[4][1]);
        own = make_float4(c0[0] + c1[0] + c2[0], c0[1] + c1[1] + c2[1], c0[2] + c1[2] + c2[2], c0[3] + c1[3] + c2[3]);
        sts128f(sb + SM_RED + tid * 16, own.x, own.y, own.z, own.w);
    }
    if (kq < 4 - NRED) bar_arrive(1 + mt, 128); else
    bar_sync(1 + mt, 128);
    STAMP(21);
    if (mt < nslot && kq >= 4 - NRED) {
        const uint32_t ra = lane * 16 + opaque(sb + SM_RED + mt * 512);
        const float4 p0 = lds128f(ra), p1 = lds128f(ra + 2560), p2 = lds128f(lane * 16 + opaque(sb + SM_RED + mt * 512 + (5 - kq) * 2560)), p3 = own;
        const float g0 = bfr((p0.x + p1.x) + (p2.x + p3.x)), g1 = bfr((p0.y + p1.y) + (p2.y + p3.y));
        const uint32_t sg = pack_bf16(g0 * rcpf(1.f + ex2f(g0 * (-64.f * 1.4426950408889634f))), g1 * rcpf(1.f + ex2f(g1 * (-64.f * 1.4426950408889634f))));
        const uint32_t gu = bmul2(sg, pack_bf16(((p0.z + p1.z) + (p2.z + p3.z)) * 4096.f, ((p0.w + p1.w) + (p2.w + p3.w)) * 4096.f));
        const uint32_t pstep = mapa(sb, 1) - mapa(sb, 0), gm = mapa(mb + MB_GU * 8, (kq & (NRED - 1)) * (8 / NRED));
#pragma unroll
        for (int i = 0; i < 8 / NRED; i++) st_async1(gd + i * pstep, gu, gm + i * pstep);
    }
    mbar_wait(mb + MB_W2 * 8);
    {
        const uint32_t aa = sb + (8 * (mi >> 1) + mr) * 144 + (mi & 1) * 16 + (SM_FAR + 2304 * kq + mt * 32);
#pragma unroll
        for (int s = 0; s < 5; s++) ldsm4t(A[s], aa + s * FAR_SZ);
    }
    float sig; uint32_t ra2; unsigned long long fp, op;
    if (warp < 8) {
        const uint32_t key = lds32(sb + SM_SEL + warp * 8), k16 = key << 5, fj = 24 * q + lane;
        sig = bfr(rcpf(1.f + ex2f(__uint_as_float((k16 ^ (~((int)k16 >> 31) | 0x80000000u)) & 0xFFFF0000u) * -1.4426950408889634f)));
        ra2 = sb + SM_RED2 + warp * 304 + lane * 12;
        fp = (unsigned long long)(g_s.fin + warp * 192 + fj); op = (unsigned long long)(prm.out + (~key & 2047) * D_ + 3 * fj);
        PIN(ra2);
        asm volatile("add.u64 %0, %0, %3; add.u64 %1, %1, %3;" : "+l"(fp), "+l"(op), "+f"(sig) : "l"((unsigned long long)zero));
    }
    {
        uint32_t ba = sb + (SM_GU + 256 * kq) + (lane & 15) * 16 + (lane >> 4) * 1024, wa = sb + (SM_RED2 + kq * 2432 + mt * 64) + g * 4 + cq * 608;
        PIN(ba); PIN(wa);
        STAMP(22);
        mbar_wait(mb + MB_GU * 8);
        STAMP(23);
        float c0[4] = {0.f, 0.f, 0.f, 0.f}, c1[4] = {0.f, 0.f, 0.f, 0.f}, c2[4] = {0.f, 0.f, 0.f, 0.f};
        uint32_t b[2][4], b8, b9;
        ldsm4t(b[0], ba); ldsm4t(b[1], ba + 2048); ldsm2t(b8, b9, ba + 4096);
        mma_bf16(c0, A[0][0], A[0][1], A[0][2], A[0][3], b[0][0], b[0][1]);
        mma_bf16(c1, A[1][0], A[1][1], A[1][2], A[1][3], b[0][2], b[0][3]);
        if (nslot == 5) {
            mma_bf16(c2, A[4][0], A[4][1], A[4][2], A[4][3], b8, b9);
            mma_bf16(c0, A[2][0], A[2][1], A[2][2], A[2][3], b[1][0], b[1][1]);
            mma_bf16(c1, A[3][0], A[3][1], A[3][2], A[3][3], b[1][2], b[1][3]);
        }
        stsf(wa, c0[0] + c1[0] + c2[0]); stsf(wa + 304, c0[1] + c1[1] + c2[1]);
        if (mt < 4) { stsf(wa + 32, c0[2] + c1[2] + c2[2]); stsf(wa + 336, c0[3] + c1[3] + c2[3]); }
    }
    if (warp < 8) {
        float v[3];
        bar_sync(6, 640);
        STAMP(14);
        if (lane < 24) {
#pragma unroll
            for (int i = 0; i < 3; i++) v[i] = ((ldsf(ra2 + i * 4) + ldsf(ra2 + i * 4 + 2432)) + (ldsf(ra2 + i * 4 + 4864) + ldsf(ra2 + i * 4 + 7296))) * sig;
            asm volatile("{ .reg .f32 x, y, z, w; .reg .b16 a, b, c; .reg .pred p;\n"
                         "atom.relaxed.gpu.global.add.v4.f32 {x,y,z,w}, [%0], {%2,%3,%4,%5};\n"
                         "setp.eq.f32 p, w, %6; add.f32 x, x, %2; add.f32 y, y, %3; add.f32 z, z, %4;\n"
                         "cvt.rn.bf16.f32 a, x; cvt.rn.bf16.f32 b, y; cvt.rn.bf16.f32 c, z;\n"
                         "@p st.global.b16 [%1], a; @p st.global.b16 [%1 + 2], b; @p st.global.b16 [%1 + 4], c; }"
                         :: "l"(fp), "l"(op), "f"(v[0]), "f"(v[1]), "f"(v[2]), "f"(3.f), "f"(3.f * NCL) : "memory");
        }
    } else bar_arrive(6, 640);
    STAMP(15);
}

#undef pp
typedef __nv_bfloat16 bf16;
__device__ bf16 f_n[L_ * D_], f_h[L_ * D_];
__device__ float f_k[D_ * L_], f_r[L_], f_gu[8 * F_];
__device__ int f_idx[8];
__device__ __forceinline__ float b2f(bf16 v) { return __bfloat162float(v); }
__global__ void fb_ln(const bf16* in, const bf16* wr, bf16* out) {
    const int t = blockIdx.x * 8 + (threadIdx.x >> 5), lane = threadIdx.x & 31;
    const bf16* r = (in ? in : f_h) + t * D_;
    float s1 = 0.f, s2 = 0.f, s3 = 0.f;
    for (int i = lane; i < D_; i += 32) s1 += b2f(r[i]);
    for (int o = 16; o; o >>= 1) s1 += __shfl_xor_sync(~0u, s1, o);
    for (int i = lane; i < D_; i += 32) { const float d = b2f(r[i]) - s1 / D_; s2 += d * d; }
    for (int o = 16; o; o >>= 1) s2 += __shfl_xor_sync(~0u, s2, o);
    const float m = bfr(s1 / D_), sd = bfr(sqrtf(bfr(bfr(s2 / D_) + 1e-5f)));
    for (int i = lane; i < D_; i += 32) {
        const float v = bfr(bfr(b2f(r[i]) - m) / sd);
        f_n[t * D_ + i] = __float2bfloat16(v);
        if (!in) { s3 += v * b2f(wr[i]); out[t * D_ + i] = __float2bfloat16(b2f(r[i]) + v); }
    }
    for (int o = 16; o; o >>= 1) s3 += __shfl_xor_sync(~0u, s3, o);
    f_r[t] = bfr(s3);
}
__global__ void fb_taps(Params p) {
    const int d = blockIdx.x >> 3, l = (blockIdx.x & 7) * 256 + threadIdx.x;
    const float dt = bfr(expf(bf_lo(p.logdt[d]))), lf = bfr((float)l);
    float k = 0.f;
    for (int n = d * 128; n < d * 128 + 128; n++) {
        float wr, wi, sn, cs;
        cmul(wr, wi, bf_lo(p.prm6[4][n]), bf_lo(p.prm6[5][n]), dt * bf_lo(p.prm6[2][n]), dt * bf_lo(p.prm6[3][n]));
        sincosf(dt * bf_lo(p.prm6[1][n]) * lf, &sn, &cs);
        k += expf(dt * bf_lo(p.prm6[0][n]) * lf) * (wr * cs - wi * sn);
    }
    f_k[l * D_ + d] = k;
}
__global__ void fb_conv(Params p) {
    const int t = blockIdx.x, d = threadIdx.x;
    float y = 0.f;
    for (int l = 0; l <= t; l++) y += f_k[l * D_ + d] * b2f(f_n[(t - l) * D_ + d]);
    f_h[t * D_ + d] = __float2bfloat16(bf_lo(p.x[t * D_ + d]) + bfr(bfr(y) + bfr(b2f(f_n[t * D_ + d]) * bf_lo(p.dskip[d]))));
}
__global__ void fb_top() {
    const int t = blockIdx.x * 256 + threadIdx.x;
    int rank = 0;
    for (int j = 0; j < L_; j++) rank += f_r[j] > f_r[t] || (f_r[j] == f_r[t] && j < t);
    if (rank < 8) f_idx[rank] = t;
}
__global__ void fb_ffn1(const bf16* wg, const bf16* wu) {
    const int f = blockIdx.x * 256 + threadIdx.x, j = blockIdx.y;
    float g = 0.f, u = 0.f;
    for (int i = 0; i < D_; i++) { const float v = b2f(f_n[f_idx[j] * D_ + i]); g += v * b2f(wg[i * F_ + f]); u += v * b2f(wu[i * F_ + f]); }
    g = bfr(g);
    f_gu[j * F_ + f] = bfr(bfr(g / (1.f + expf(-g))) * bfr(u));
}
__global__ void fb_ffn2(const bf16* wd, bf16* out) {
    const int d = threadIdx.x, j = blockIdx.x, t = f_idx[j];
    float y = 0.f;
    for (int f = 0; f < F_; f++) y += f_gu[j * F_ + f] * b2f(wd[f * D_ + d]);
    out[t * D_ + d] = __float2bfloat16(b2f(f_h[t * D_ + d]) + bfr(b2f(f_n[t * D_ + d]) + bfr(bfr(y) * bfr(1.f / (1.f + expf(-f_r[t]))))));
}

typedef CUresult (*EncodeFn)(CUtensorMap*, CUtensorMapDataType, cuuint32_t, void*, const cuuint64_t*, const cuuint64_t*,
                             const cuuint32_t*, const cuuint32_t*, CUtensorMapInterleave, CUtensorMapSwizzle,
                             CUtensorMapL2promotion, CUtensorMapFloatOOBfill);

void make_map(EncodeFn fn, CUtensorMap* tm, const void* p, int cols, int rows, int bc, int br) {
    cuuint64_t dims[2] = {(cuuint64_t)cols, (cuuint64_t)rows};
    cuuint64_t strides[1] = {(cuuint64_t)cols * 2};
    cuuint32_t box[2] = {(cuuint32_t)bc, (cuuint32_t)br};
    cuuint32_t es[2] = {1, 1};
    fn(tm, CU_TENSOR_MAP_DATA_TYPE_BFLOAT16, 2, const_cast<void*>(p), dims, strides, box, es, CU_TENSOR_MAP_INTERLEAVE_NONE,
       CU_TENSOR_MAP_SWIZZLE_NONE, CU_TENSOR_MAP_L2_PROMOTION_L2_128B, CU_TENSOR_MAP_FLOAT_OOB_FILL_NONE);
}

void make_map3(EncodeFn fn, CUtensorMap* tm, const void* p) {
    cuuint64_t dims[5] = {(cuuint64_t)D_, 64, 2, 2, 8};
    cuuint64_t strides[4] = {(cuuint64_t)D_ * 2, (cuuint64_t)D_ * 2048, (cuuint64_t)D_ * 128, (cuuint64_t)D_ * 256};
    cuuint32_t box[5] = {XW, 9, 2, 2, 8};
    cuuint32_t es[5] = {1, 1, 1, 1, 1};
    fn(tm, CU_TENSOR_MAP_DATA_TYPE_BFLOAT16, 5, const_cast<void*>(p), dims, strides, box, es, CU_TENSOR_MAP_INTERLEAVE_NONE,
       CU_TENSOR_MAP_SWIZZLE_NONE, CU_TENSOR_MAP_L2_PROMOTION_NONE, CU_TENSOR_MAP_FLOAT_OOB_FILL_NONE);
}

void make_map5(EncodeFn fn, CUtensorMap* tm, const void* p, int bc) {
    cuuint64_t dims[5] = {(cuuint64_t)D_, 2, 4, 4, 64};
    cuuint64_t strides[4] = {(cuuint64_t)D_ * 128, (cuuint64_t)D_ * 1024, (cuuint64_t)D_ * 256, (cuuint64_t)D_ * 2};
    cuuint32_t box[5] = {(cuuint32_t)bc, 2, 4, 4, 8};
    cuuint32_t es[5] = {1, 1, 1, 1, 1};
    fn(tm, CU_TENSOR_MAP_DATA_TYPE_BFLOAT16, 5, const_cast<void*>(p), dims, strides, box, es, CU_TENSOR_MAP_INTERLEAVE_NONE,
       CU_TENSOR_MAP_SWIZZLE_NONE, CU_TENSOR_MAP_L2_PROMOTION_NONE, CU_TENSOR_MAP_FLOAT_OOB_FILL_NONE);
}

}

extern "C" void kernel_launch(void* const* d_in, const int* in_sizes, int n_in, void* d_out, int out_size) {
    (void)in_sizes; (void)n_in; (void)out_size;
    void* fp = nullptr;
    cudaDriverEntryPointQueryResult qr;
    cudaGetDriverEntryPoint("cuTensorMapEncodeTiled", &fp, cudaEnableDefault, &qr);
    EncodeFn fn = (EncodeFn)fp;
    CUtensorMap tmG, tmU, tmD, tmO, tmX, tmH;
    make_map3(fn, &tmX, d_in[0]);
    make_map(fn, &tmG, d_in[11], F_, D_, 40, 48);
    make_map(fn, &tmU, d_in[12], F_, D_, 40, 48);
    make_map(fn, &tmD, d_in[13], D_, F_, 72, 64);
    make_map5(fn, &tmO, d_out, 32);
    make_map5(fn, &tmH, d_out, 8);
    Params p;
    p.x = (const unsigned short*)d_in[0];
    for (int i = 0; i < 6; i++) p.prm6[i] = (const unsigned short*)d_in[1 + i];
    p.logdt = (const unsigned short*)d_in[7]; p.dskip = (const unsigned short*)d_in[8];
    p.wr = (const unsigned short*)d_in[10];
    p.out = (__nv_bfloat16*)d_out;
    p.zero = 0;
    cudaGetSymbolAddress((void**)&p.gs, g_s);
    cudaFuncSetAttribute(fused_kernel, cudaFuncAttributeMaxDynamicSharedMemorySize, SM_TOTAL);
    static int nclusters = -1;
    if (nclusters < 0) {
        cudaLaunchConfig_t cfg = {};
        cudaLaunchAttribute at;
        at.id = cudaLaunchAttributeClusterDimension; at.val.clusterDim.x = CS; at.val.clusterDim.y = 1; at.val.clusterDim.z = 1;
        cfg.gridDim = dim3(NCTA); cfg.blockDim = dim3(NTHR); cfg.dynamicSmemBytes = SM_TOTAL; cfg.attrs = &at; cfg.numAttrs = 1;
        if (cudaOccupancyMaxActiveClusters(&nclusters, fused_kernel, &cfg) != cudaSuccess) { (void)cudaGetLastError(); nclusters = NCL; }
    }
    if (nclusters >= NCL && !FORCE_FALLBACK) {
        fused_kernel<<<NCTA, NTHR, SM_TOTAL>>>(p, tmG, tmU, tmD, tmO, tmX, tmH);
        return;
    }
    fb_ln<<<L_ / 8, 256>>>((const bf16*)d_in[0], nullptr, nullptr);
    fb_taps<<<D_ * 8, 256>>>(p);
    fb_conv<<<L_, D_>>>(p);
    fb_ln<<<L_ / 8, 256>>>(nullptr, (const bf16*)d_in[10], p.out);
    fb_top<<<L_ / 256, 256>>>();
    fb_ffn1<<<dim3(F_ / 256, 8), 256>>>((const bf16*)d_in[11], (const bf16*)d_in[12]);
    fb_ffn2<<<8, D_>>>((const bf16*)d_in[13], p.out);
}
```

```cpp
#include <cuda_runtime.h>
#include <cuda_bf16.h>
#include <cuda_fp16.h>
#include <cuda.h>
#include <stdint.h>

namespace {

constexpr int L_ = 2048, D_ = 576, F_ = 4608;
constexpr int NCL = 15, CS = 8, NCTA = NCL * CS, NTHR = 768;
#define FORCE_FALLBACK 0
constexpr int XW = 48, NRED = 2;
constexpr int SPIN_LIMIT = 1 << 22;

constexpr int SM_WG   = 0;
constexpr int SM_WU   = 46080;
constexpr int YP = 3392, YS = 656;
constexpr int UP = 3280, US = 656;
constexpr int SM_XT   = 92160;
constexpr int SM_U    = SM_XT + 8 * YP;
constexpr int SM_FAR  = SM_U + 8 * UP;
constexpr int FAR_SZ  = 12416;
constexpr int F_E5 = 0, F_O5 = 1536, F_E3 = 3088, F_O3 = 4624, F_E7 = 6176, F_E2 = F_E7 + 1024, F_E9 = F_E7 + 2048,
              F_H = 3088, F_O7 = F_E7 + F_H, F_O2 = F_E2 + F_H, F_O9 = F_E9 + F_H;
constexpr int SM_P    = SM_FAR + 5 * FAR_SZ;
constexpr int PN_SZ = 584 * 4, SM_PN = SM_P + 65 * 4;
constexpr int P_GS = 50 * 4, P_H7 = 200 * 4, P_HS = 74 * 4;
constexpr int PF_SZ = (200 + 222) * 4, SM_PF = SM_PN + 5 * PN_SZ + 36;
constexpr int SM_MISC = SM_PF + 5 * PF_SZ;
constexpr int SM_ST   = SM_MISC;
constexpr int SM_RK   = SM_ST + 2048;
constexpr int SM_SEL  = SM_FAR + FAR_SZ + 10240;
constexpr int SM_KG   = SM_RK + 320;
constexpr int SM_SC   = SM_KG + 160;
constexpr int SM_DW   = SM_SC + 32;
constexpr int SM_MB   = SM_DW + 160;
constexpr int SM_TOTAL = SM_MB + 128;
constexpr int SM_ROW  = SM_XT - 20736;
constexpr int SM_XTL  = SM_ROW - 576 * XW;
constexpr int SM_RED2 = SM_WG;
constexpr int SM_HT   = SM_P - 512;
constexpr int SM_KEY  = SM_FAR + 10240 + 128;
constexpr int SM_CAND = SM_KEY + 1024;
constexpr int SM_XS   = SM_U;
constexpr int SM_GU   = SM_XS + 9344;
constexpr int SM_RED  = SM_GU + 5632;
static_assert(F_O9 + 1024 <= FAR_SZ && FAR_SZ % 128 == 0, "far overflow");
static_assert(SM_RED + 10240 <= SM_FAR && SM_HT + 20496 <= SM_MISC, "alias overflow");
static_assert(SM_TOTAL <= 232448, "smem overflow");
static_assert(SM_FAR % 128 == 0 && SM_XT % 128 == 0 && SM_XTL % 128 == 0 && SM_P % 16 == 0 && SM_MISC % 16 == 0 && SM_MB % 8 == 0, "align");

enum { MB_X = 0, MB_W1 = 5, MB_W2 = 6, MB_KEY = 7, MB_GU = 8, MB_Y = 9, MB_OUT = 10, MB_T = 11, MB_R = 12 };

struct __align__(128) Scratch {
    unsigned epoch, zcnt, pad[30];
    uint4  st1[L_ * 2];
    float4 acc[L_];
    uint4  cand[2 * 64 * NCL * 6];
    float4 fin[8 * 192 + 24];
};
__device__ Scratch g_s;
#define STAMP(i)

__device__ __forceinline__ uint32_t mapa(uint32_t a, uint32_t r) { uint32_t d; asm("mapa.shared::cluster.u32 %0, %1, %2;" : "=r"(d) : "r"(a), "r"(r)); return d; }
__device__ __forceinline__ void mbar_wait(uint32_t mb) {
    asm volatile("{ .reg .pred p, q; .reg .u32 n; mov.u32 n, 0;\n"
                 "W_%=: mbarrier.try_wait.parity.shared::cta.b64 p, [%0], 0; add.u32 n, n, 1; setp.lt.and.u32 q, n, 65536, !p; @q bra W_%=; }" :: "r"(mb) : "memory");
}
__device__ __forceinline__ bool elect() { uint32_t e; asm volatile("{ .reg .pred p; elect.sync _|p, 0xffffffff; selp.u32 %0, 1, 0, p; }" : "=r"(e)); return e; }
__device__ __forceinline__ void arm(uint32_t mb, uint32_t bytes) { asm volatile("mbarrier.arrive.expect_tx.shared::cta.b64 _, [%0], %1;" :: "r"(mb), "r"(bytes) : "memory"); }
__device__ __forceinline__ void bar_sync(int id, int n) { asm volatile("bar.sync %0, %1;" :: "r"(id), "r"(n) : "memory"); }
__device__ __forceinline__ void bar_arrive(int id, int n) { asm volatile("bar.arrive %0, %1;" :: "r"(id), "r"(n) : "memory"); }
__device__ __forceinline__ uint32_t lds16(uint32_t a) { unsigned short v; asm volatile("ld.shared.u16 %0, [%1];" : "=h"(v) : "r"(a) : "memory"); return v; }
__device__ __forceinline__ uint32_t lds32(uint32_t a) { uint32_t v; asm volatile("ld.shared.u32 %0, [%1];" : "=r"(v) : "r"(a) : "memory"); return v; }
__device__ __forceinline__ uint2 lds64(uint32_t a) { uint2 v; asm volatile("ld.shared.v2.u32 {%0,%1}, [%2];" : "=r"(v.x), "=r"(v.y) : "r"(a) : "memory"); return v; }
__device__ __forceinline__ float ldsf(uint32_t a) { float v; asm volatile("ld.shared.f32 %0, [%1];" : "=f"(v) : "r"(a) : "memory"); return v; }
__device__ __forceinline__ uint4 lds128(uint32_t a) { uint4 v; asm volatile("ld.shared.v4.u32 {%0,%1,%2,%3}, [%4];" : "=r"(v.x), "=r"(v.y), "=r"(v.z), "=r"(v.w) : "r"(a) : "memory"); return v; }
__device__ __forceinline__ float4 lds128f(uint32_t a) { float4 v; asm volatile("ld.shared.v4.f32 {%0,%1,%2,%3}, [%4];" : "=f"(v.x), "=f"(v.y), "=f"(v.z), "=f"(v.w) : "r"(a) : "memory"); return v; }
__device__ __forceinline__ void sts16(uint32_t a, uint32_t v) { asm volatile("{ .reg .b16 l, h; mov.b32 {l, h}, %1; st.shared.b16 [%0], l; }" :: "r"(a), "r"(v) : "memory"); }
__device__ __forceinline__ void sts32(uint32_t a, uint32_t v) { asm volatile("st.shared.u32 [%0], %1;" :: "r"(a), "r"(v) : "memory"); }
__device__ __forceinline__ void sts64(uint32_t a, uint32_t x, uint32_t y) { asm volatile("st.shared.v2.u32 [%0], {%1,%2};" :: "r"(a), "r"(x), "r"(y) : "memory"); }
__device__ __forceinline__ void stsf(uint32_t a, float v) { asm volatile("st.shared.f32 [%0], %1;" :: "r"(a), "f"(v) : "memory"); }
__device__ __forceinline__ void sts128(uint32_t a, uint32_t x, uint32_t y, uint32_t z, uint32_t w) { asm volatile("st.shared.v4.u32 [%0], {%1,%2,%3,%4};" :: "r"(a), "r"(x), "r"(y), "r"(z), "r"(w) : "memory"); }
__device__ __forceinline__ void sts128f(uint32_t a, float x, float y, float z, float w) { asm volatile("st.shared.v4.f32 [%0], {%1,%2,%3,%4};" :: "r"(a), "f"(x), "f"(y), "f"(z), "f"(w) : "memory"); }
__device__ __forceinline__ void ldsm4(uint32_t (&r)[4], uint32_t a) { asm volatile("ldmatrix.sync.aligned.m8n8.x4.shared.b16 {%0,%1,%2,%3}, [%4];" : "=r"(r[0]), "=r"(r[1]), "=r"(r[2]), "=r"(r[3]) : "r"(a) : "memory"); }
__device__ __forceinline__ void ldsm4t(uint32_t (&r)[4], uint32_t a) { asm volatile("ldmatrix.sync.aligned.m8n8.x4.trans.shared.b16 {%0,%1,%2,%3}, [%4];" : "=r"(r[0]), "=r"(r[1]), "=r"(r[2]), "=r"(r[3]) : "r"(a) : "memory"); }
__device__ __forceinline__ void ldsm2t(uint32_t& r0, uint32_t& r1, uint32_t a) { asm volatile("ldmatrix.sync.aligned.m8n8.x2.trans.shared.b16 {%0,%1}, [%2];" : "=r"(r0), "=r"(r1) : "r"(a) : "memory"); }
__device__ __forceinline__ void stsm4t(uint32_t a, uint32_t r0, uint32_t r1, uint32_t r2, uint32_t r3) { asm volatile("stmatrix.sync.aligned.m8n8.x4.trans.shared.b16 [%0], {%1,%2,%3,%4};" :: "r"(a), "r"(r0), "r"(r1), "r"(r2), "r"(r3) : "memory"); }
__device__ __forceinline__ void stsm4(uint32_t a, uint32_t r0, uint32_t r1, uint32_t r2, uint32_t r3) { asm volatile("stmatrix.sync.aligned.m8n8.x4.shared.b16 [%0], {%1,%2,%3,%4};" :: "r"(a), "r"(r0), "r"(r1), "r"(r2), "r"(r3) : "memory"); }
__device__ __forceinline__ void stsm2(uint32_t a, uint32_t r0, uint32_t r1) { asm volatile("stmatrix.sync.aligned.m8n8.x2.shared.b16 [%0], {%1,%2};" :: "r"(a), "r"(r0), "r"(r1) : "memory"); }
__device__ __forceinline__ void stsm2t(uint32_t a, uint32_t r0, uint32_t r1) { asm volatile("stmatrix.sync.aligned.m8n8.x2.trans.shared.b16 [%0], {%1,%2};" :: "r"(a), "r"(r0), "r"(r1) : "memory"); }
__device__ __forceinline__ uint4 ldg128(const void* p) { uint4 v; asm volatile("ld.global.nc.v4.u32 {%0,%1,%2,%3}, [%4];" : "=r"(v.x), "=r"(v.y), "=r"(v.z), "=r"(v.w) : "l"(p)); return v; }
__device__ __forceinline__ uint32_t ldg16(const void* p) { unsigned short v; asm volatile("ld.global.nc.u16 %0, [%1];" : "=h"(v) : "l"(p)); return v; }
__device__ __forceinline__ uint32_t opaque(uint32_t v) { uint32_t r; asm volatile("mov.b32 %0, %1;" : "=r"(r) : "r"(v)); return r; }
__device__ __forceinline__ void mma_f16(float (&d)[4], const uint32_t (&a)[4], uint32_t b0, uint32_t b1) {
    asm volatile("mma.sync.aligned.m16n8k16.row.col.f32.f16.f16.f32 {%0,%1,%2,%3}, {%4,%5,%6,%7}, {%8,%9}, {%0,%1,%2,%3};"
        : "+f"(d[0]), "+f"(d[1]), "+f"(d[2]), "+f"(d[3]) : "r"(a[0]), "r"(a[1]), "r"(a[2]), "r"(a[3]), "r"(b0), "r"(b1));
}
__device__ __forceinline__ void mma_f16_z(float (&d)[4], const uint32_t (&a)[4], uint32_t b0, uint32_t b1) {
    asm volatile("mma.sync.aligned.m16n8k16.row.col.f32.f16.f16.f32 {%0,%1,%2,%3}, {%4,%5,%6,%7}, {%8,%9}, {%10,%10,%10,%10};"
        : "=f"(d[0]), "=f"(d[1]), "=f"(d[2]), "=f"(d[3]) : "r"(a[0]), "r"(a[1]), "r"(a[2]), "r"(a[3]), "r"(b0), "r"(b1), "f"(0.f));
}
__device__ __forceinline__ void mma_bf16(float (&d)[4], uint32_t a0, uint32_t a1, uint32_t a2, uint32_t a3, uint32_t b0, uint32_t b1) {
    asm volatile("mma.sync.aligned.m16n8k16.row.col.f32.bf16.bf16.f32 {%0,%1,%2,%3}, {%4,%5,%6,%7}, {%8,%9}, {%0,%1,%2,%3};"
        : "+f"(d[0]), "+f"(d[1]), "+f"(d[2]), "+f"(d[3]) : "r"(a0), "r"(a1), "r"(a2), "r"(a3), "r"(b0), "r"(b1));
}
__device__ __forceinline__ void mma_bf16_k8(float (&d)[4], uint32_t a0, uint32_t a1, uint32_t b0) {
    asm volatile("mma.sync.aligned.m16n8k8.row.col.f32.bf16.bf16.f32 {%0,%1,%2,%3}, {%4,%5}, {%6}, {%0,%1,%2,%3};"
        : "+f"(d[0]), "+f"(d[1]), "+f"(d[2]), "+f"(d[3]) : "r"(a0), "r"(a1), "r"(b0));
}
__device__ __forceinline__ uint32_t pack_f16(float lo, float hi) { uint32_t r; asm("cvt.rn.f16x2.f32 %0, %1, %2;" : "=r"(r) : "f"(hi), "f"(lo)); return r; }
__device__ __forceinline__ uint32_t pack_bf16(float lo, float hi) { uint32_t r; asm("cvt.rn.bf16x2.f32 %0, %1, %2;" : "=r"(r) : "f"(hi), "f"(lo)); return r; }
__device__ __forceinline__ float bf_lo(uint32_t v) { return __uint_as_float(v << 16); }
__device__ __forceinline__ float bf_hi(uint32_t v) { return __uint_as_float(v & 0xFFFF0000u); }
__device__ __forceinline__ float bfr(float x) { return __uint_as_float(pack_bf16(0.f, x)); }
__device__ __forceinline__ uint32_t badd2(uint32_t a, uint32_t b) { uint32_t r; asm("add.rn.bf16x2 %0, %1, %2;" : "=r"(r) : "r"(a), "r"(b)); return r; }
__device__ __forceinline__ uint32_t bmul2(uint32_t a, uint32_t b) { uint32_t r; asm("mul.rn.bf16x2 %0, %1, %2;" : "=r"(r) : "r"(a), "r"(b)); return r; }
__device__ __forceinline__ uint32_t hadd2(uint32_t a, uint32_t b) { uint32_t r; asm("add.rn.f16x2 %0, %1, %2;" : "=r"(r) : "r"(a), "r"(b)); return r; }
__device__ __forceinline__ uint32_t hmul2(uint32_t a, uint32_t b) { uint32_t r; asm("mul.rn.f16x2 %0, %1, %2;" : "=r"(r) : "r"(a), "r"(b)); return r; }
__device__ __forceinline__ uint32_t hneg2(uint32_t a) { uint32_t r; asm("neg.f16x2 %0, %1;" : "=r"(r) : "r"(a)); return r; }
__device__ __forceinline__ float rcpf(float x) { float r; asm("rcp.approx.ftz.f32 %0, %1;" : "=f"(r) : "f"(x)); return r; }
__device__ __forceinline__ float sqrta(float x) { float r; asm("sqrt.approx.ftz.f32 %0, %1;" : "=f"(r) : "f"(x)); return r; }
__device__ __forceinline__ float ex2f(float x) { float r; asm("ex2.approx.ftz.f32 %0, %1;" : "=f"(r) : "f"(x)); return r; }
__device__ __forceinline__ void st_async4(uint32_t a, uint32_t x, uint32_t y, uint32_t z, uint32_t w, uint32_t mb) {
    asm volatile("st.async.shared::cluster.mbarrier::complete_tx::bytes.v4.u32 [%0], {%1,%2,%3,%4}, [%5];" :: "r"(a), "r"(x), "r"(y), "r"(z), "r"(w), "r"(mb) : "memory"); }
__device__ __forceinline__ void st_async1(uint32_t a, uint32_t x, uint32_t mb) {
    asm volatile("st.async.shared::cluster.mbarrier::complete_tx::bytes.u32 [%0], %1, [%2];" :: "r"(a), "r"(x), "r"(mb) : "memory"); }
__device__ __forceinline__ unsigned ld_rlx(const void* p) { unsigned v; asm volatile("ld.relaxed.gpu.global.u32 %0, [%1];" : "=r"(v) : "l"(p) : "memory"); return v; }
__device__ __forceinline__ unsigned ld_acq(const void* p) { unsigned v; asm volatile("ld.acquire.gpu.global.u32 %0, [%1];" : "=r"(v) : "l"(p) : "memory"); return v; }
__device__ __forceinline__ uint2 ld_rlx64(const void* p) { unsigned long long v; asm volatile("ld.relaxed.gpu.global.u64 %0, [%1];" : "=l"(v) : "l"(p) : "memory"); return make_uint2((unsigned)v, (unsigned)(v >> 32)); }
__device__ __forceinline__ void st_rlx128(void* p, uint32_t x, uint32_t y, uint32_t z, uint32_t w) {
    asm volatile("st.relaxed.gpu.global.v2.u64 [%0], {%1,%2};" :: "l"(p), "l"((unsigned long long)x | ((unsigned long long)y << 32)), "l"((unsigned long long)z | ((unsigned long long)w << 32)) : "memory"); }
__device__ __forceinline__ uint4 ld_rlx128(const void* p) { unsigned long long a, b; asm volatile("ld.relaxed.gpu.global.v2.u64 {%0,%1}, [%2];" : "=l"(a), "=l"(b) : "l"(p) : "memory"); return make_uint4((unsigned)a, (unsigned)(a >> 32), (unsigned)b, (unsigned)(b >> 32)); }
__device__ __forceinline__ void tma2d(uint32_t dst, const CUtensorMap* tm, int x, int y, uint32_t mb) {
    asm volatile("cp.async.bulk.tensor.2d.shared::cluster.global.mbarrier::complete_tx::bytes [%0], [%1, {%3, %4}], [%2];"
                 :: "r"(dst), "l"(tm), "r"(mb), "r"(x), "r"(y) : "memory");
}
__device__ __forceinline__ void cmul(float& xr, float& xi, float ar, float ai, float br, float bi) {
    const float r = fmaf(ar, br, -ai * bi), i = fmaf(ar, bi, ai * br); xr = r; xi = i;
}
__device__ __forceinline__ void csq(float& xr, float& xi, float ar, float ai) {
    const float r = fmaf(ar, ar, -ai * ai), i = (ar + ar) * ai; xr = r; xi = i;
}
__device__ __forceinline__ void cexp_s(float& zr, float& zi, float e2, float turns) {
    const float mag = ex2f(e2), r = (turns - rintf(turns)) * 6.283185307179586f;
    zr = mag * __cosf(r); zi = mag * __sinf(r);
}
__device__ __forceinline__ uint32_t ln_stats(float s1, float s2) {
    const float m = s1 * (1.f / D_);
    const float var = fmaxf(fmaf(s2, 1.f / D_, -m * m), 0.f);
    return pack_bf16(m, sqrta(bfr(bfr(var) + 1e-5f)));
}
__device__ __forceinline__ uint32_t rsplit(float rs) { const float h = bfr(rs); return pack_bf16(h, rs - h); }
__device__ __forceinline__ uint32_t norm2(uint32_t v, uint32_t mx, uint32_t hl) {
    uint32_t r;
    asm("{ .reg .b16 m, h, l, x; .reg .b32 m2, h2, l2, d, t; mov.b32 {m, x}, %2; mov.b32 {h, l}, %3; mov.b32 m2, {m, m}; mov.b32 h2, {h, h}; mov.b32 l2, {l, l};\n"
        "sub.rn.bf16x2 d, %1, m2; mul.rn.bf16x2 t, d, l2; fma.rn.bf16x2 %0, d, h2, t; }" : "=r"(r) : "r"(v), "r"(mx), "r"(hl));
    return r;
}
template <int N, int S>
__device__ __forceinline__ uint32_t rank4(uint32_t a, uint32_t key, uint32_t m1) {
    uint32_t r0 = 0, r1 = 0, r2 = 0, r3 = 0;
#pragma unroll
    for (int i = 0; i < N; i++) {
        const uint4 o = lds128(a + i * S);
        r0 += (o.x * m1 + key) >> 31; r1 += (o.y * m1 + key) >> 31; r2 += (o.z * m1 + key) >> 31; r3 += (o.w * m1 + key) >> 31;
    }
    return (r0 + r1) + (r2 + r3);
}
__device__ __forceinline__ uint32_t quad_sum(uint32_t r) {
    const uint32_t a = __shfl_xor_sync(~0u, r, 1), b = __shfl_xor_sync(~0u, r, 2), c = __shfl_xor_sync(~0u, r, 3);
    return (r + a) + b + c;
}
typedef uint32_t H2C;
__device__ __forceinline__ H2C splat(float r, float i) { return pack_f16(r, i); }
__device__ __forceinline__ void hcmul(uint32_t& xr, uint32_t& xi, uint32_t R, uint32_t I, H2C m) {
    asm("{ .reg .b16 a, b; .reg .b32 a2, b2, t; mov.b32 {a, b}, %4; mov.b32 a2, {a, a}; mov.b32 b2, {b, b};\n"
        "mul.rn.f16x2 t, %3, b2; neg.f16x2 t, t; fma.rn.f16x2 %0, %2, a2, t; mul.rn.f16x2 t, %3, a2; fma.rn.f16x2 %1, %2, b2, t; }"
        : "=&r"(xr), "=r"(xi) : "r"(R), "r"(I), "r"(m));
}
__device__ __forceinline__ void expand4(uint32_t are, uint32_t aim, uint32_t R0, uint32_t R1, uint32_t I0, uint32_t I1, H2C m4) {
    uint32_t R2, I2, R3, I3;
    hcmul(R2, I2, R0, I0, m4); hcmul(R3, I3, R1, I1, m4);
    sts128(are, R0, R1, R2, R3);
    sts128(aim, I0, I1, I2, I3);
}
__device__ __forceinline__ void expand8(uint32_t are, uint32_t aim, float sr, float si, float m1r, float m1i, float m2r, float m2i, H2C m4) {
    float r1, i1, r2, i2, r3, i3;
    cmul(r1, i1, sr, si, m1r, m1i); cmul(r2, i2, sr, si, m2r, m2i); cmul(r3, i3, r1, i1, m2r, m2i);
    expand4(are, aim, pack_f16(sr, r1), pack_f16(r2, r3), pack_f16(si, i1), pack_f16(i2, i3), m4);
}
__device__ __forceinline__ uint32_t comb4(uint32_t a, uint32_t b, uint32_t c, uint32_t d, uint32_t r01, uint32_t r23) {
    uint32_t x;
    asm("{ .reg .b16 h0, h1, h2, h3; .reg .b32 m0, m1, m2, m3, u, v; mov.b32 {h0, h1}, %5; mov.b32 {h2, h3}, %6;\n"
        "mov.b32 m0, {h0, h0}; mov.b32 m1, {h1, h1}; mov.b32 m2, {h2, h2}; mov.b32 m3, {h3, h3};\n"
        "mul.rn.f16x2 u, %2, m1; fma.rn.f16x2 u, %1, m0, u; mul.rn.f16x2 v, %4, m3; fma.rn.f16x2 v, %3, m2, v; add.rn.f16x2 %0, u, v; }"
        : "=r"(x) : "r"(a), "r"(b), "r"(c), "r"(d), "r"(r01), "r"(r23));
    return x;
}
__device__ __forceinline__ void put16(uint32_t a, uint32_t v) { sts16(a, v); sts16(a + 6, v); }

struct Params {
    const unsigned short *logdt, *dskip, *prm6[6], *x, *wr;
    __nv_bfloat16* out;
    Scratch* gs;
    unsigned zero;
};
__device__ __forceinline__ uint32_t tslot(uint32_t t) { return (t & 7) * 32 + ((t >> 4) & 24) + ((t >> 8) & 6) + ((t >> 6) & 1); }
#define CP(x) ((x) | zero)
#define ZF(x) ((x) & zero)
#define PIN(x) asm volatile("or.b32 %0, %0, %1;" : "+r"(x) : "r"(zero))
__device__ __forceinline__ void wgmma32(float (&d)[4][4], const uint32_t (&a)[4], unsigned long long ds) {
    asm volatile("wgmma.mma_async.sync.aligned.m64n32k16.f32.f16.f16 {%0,%1,%2,%3,%4,%5,%6,%7,%8,%9,%10,%11,%12,%13,%14,%15}, {%16,%17,%18,%19}, %20, 1, 1, 1, 0;"
        : "+f"(d[0][0]), "+f"(d[0][1]), "+f"(d[0][2]), "+f"(d[0][3]), "+f"(d[1][0]), "+f"(d[1][1]), "+f"(d[1][2]), "+f"(d[1][3]),
          "+f"(d[2][0]), "+f"(d[2][1]), "+f"(d[2][2]), "+f"(d[2][3]), "+f"(d[3][0]), "+f"(d[3][1]), "+f"(d[3][2]), "+f"(d[3][3])
        : "r"(a[0]), "r"(a[1]), "r"(a[2]), "r"(a[3]), "l"(ds));
}

__device__ __forceinline__ void finish(const Params& prm, uint32_t fo, uint32_t oo, const float (&v)[3], float cnt) {
    float x, y, z, w;
    asm volatile("atom.relaxed.gpu.global.add.v4.f32 {%0,%1,%2,%3}, [%4], {%5,%6,%7,%8};" : "=f"(x), "=f"(y), "=f"(z), "=f"(w)
                 : "l"((char*)prm.gs->fin + fo), "f"(v[0]), "f"(v[1]), "f"(v[2]), "f"(cnt) : "memory");
    if (w + cnt == 3.f * (NCL + 1)) {
        __nv_bfloat16* op = (__nv_bfloat16*)((char*)prm.out + oo);
        op[0] = __float2bfloat16(x + v[0]); op[1] = __float2bfloat16(y + v[1]); op[2] = __float2bfloat16(z + v[2]);
    }
}

__global__ void __cluster_dims__(CS, 1, 1) __launch_bounds__(NTHR, 1)
fused_kernel(const __grid_constant__ Params prm, const __grid_constant__ CUtensorMap tmG, const __grid_constant__ CUtensorMap tmU,
             const __grid_constant__ CUtensorMap tmD, const __grid_constant__ CUtensorMap tmO, const __grid_constant__ CUtensorMap tmX, const __grid_constant__ CUtensorMap tmH)
{
    extern __shared__ __align__(1024) unsigned char smem[];
    const int tid = threadIdx.x, lane = tid & 31, warp = __shfl_sync(~0u, tid >> 5, 0);
    const int c = blockIdx.x >> 3, q = blockIdx.x & 7;
    const int nslot = (c < NCL - 1) ? 5 : 2;
    const int d0 = 40 * c;
    const uint32_t sb = opaque((uint32_t)__cvta_generic_to_shared(smem));
    const uint32_t mb = sb + SM_MB;
    Scratch& g_s = *prm.gs;
    const unsigned& zero = prm.zero;
    const uint32_t dch2 = min(d0 + q + ((tid >> 4) & ~7), D_ - 1) * 2;
    uint32_t pv[6], pLdt;
    const uint32_t pofs = opaque(dch2 * 128 + (tid & 127) * 2);
    pLdt = ldg16((const char*)prm.logdt + dch2);
#pragma unroll
    for (int i = 0; i < 2; i++) pv[i] = ldg16((const char*)prm.prm6[i] + pofs);
    STAMP(0);

    if (warp >= 20) {
        unsigned epoch = 0;
        if (warp == 20) {
            if (lane == 0) {
#pragma unroll
                for (int i = 0; i < 13; i++)
                    asm volatile("mbarrier.init.shared::cta.b64 [%0], %1;" :: "r"(mb + i * 8), "r"((i == MB_R || i < 2) ? 2 : i < 5 ? (nslot + 1) / 3 : i == MB_Y ? 1 + 4 * nslot : 1) : "memory");
                asm volatile("fence.mbarrier_init.release.cluster;" ::: "memory");
                arm(mb + MB_W1 * 8, 92160); arm(mb + MB_W2 * 8, nslot * 9216); arm(mb + MB_KEY * 8, 256); arm(mb + MB_GU * 8, nslot * 1024); arm(mb + MB_T * 8, 576 * XW);
                const int bytes = max(min(18, L_ - 18 * (int)blockIdx.x), 1) * (D_ * 2);
                arm(mb + MB_R * 8, bytes);
            }
            __syncwarp();
        } else if (warp == 22) {
            epoch = ld_rlx(&g_s.epoch);
            if (lane < 18 ? 18 * c + lane < 256 : lane < 31) (lane < 18 ? &g_s.acc[256 * q + 18 * c] : &g_s.fin[13 * (int)blockIdx.x - 18])[lane] = make_float4(0.f, 0.f, 0.f, 0.f);
        } else if (warp == 23 && lane == 0) asm volatile("prefetch.tensormap [%0];" :: "l"(&tmX) : "memory");
        asm volatile("barrier.cluster.arrive.relaxed.aligned;" ::: "memory");
        bar_sync(12, NTHR);
        uint4 wv = make_uint4(0, 0, 0, 0), wv2, wv3;
        if (warp == 22) {
            if (lane == 0) { sts32(sb + SM_SC + 28, epoch); asm volatile("mbarrier.arrive.shared::cta.b64 _, [%0];" :: "r"(mb + MB_R * 8) : "memory"); }
            epoch++;
            asm volatile("fence.acq_rel.gpu;" ::: "memory");
            __syncwarp();
            if (lane == 0) asm volatile("red.relaxed.gpu.global.add.u32 [%0], 1;" :: "l"(&g_s.zcnt) : "memory");
            STAMP(1);
            wv2 = ldg128((const uint4*)prm.wr + lane); wv3 = ldg128((const uint4*)prm.wr + 32 + lane);
            if (lane < 8) wv = ldg128((const uint4*)prm.wr + 64 + lane);
            if (lane < 5) {
                uint4 v = make_uint4(0, 0, 0, 0);
                if (lane < nslot) v = ldg128((const uint4*)(prm.wr + d0) + lane);
                sts128(sb + SM_DW + lane * 16, v.x, v.y, v.z, v.w);
            }
            __syncwarp();
            if (lane < 5) asm volatile("mbarrier.arrive.shared::cta.b64 _, [%0];" :: "r"(mb + (MB_X + lane) * 8) : "memory");
        }
        if (warp == 21) {
            if (lane == 0) { asm volatile("prefetch.tensormap [%0];" :: "l"(&tmG) : "memory"); asm volatile("prefetch.tensormap [%0];" :: "l"(&tmU) : "memory"); asm volatile("prefetch.tensormap [%0];" :: "l"(&tmD) : "memory"); }
            __syncwarp();
            const float dsk = bf_lo(ldg16(prm.dskip + min(d0 + 2 * (lane & 28) + q, D_ - 1)));
            bar_sync(0, 672);
            {
                const uint2 m = lds64(sb + SM_KG + min(lane, 19) * 8);
                unsigned Em = max(m.x, __shfl_xor_sync(~0u, m.x, 1));
                Em = max(Em, __shfl_xor_sync(~0u, Em, 2));
                Em = max(Em, min(__float_as_uint(fabsf(dsk) * (1.f / 8192.f)) >> 23, 253u));
                const float f = __uint_as_float(max((int)(127 + m.x - Em), 0) << 23);
                float s0 = (float)(int)m.y * f;
                s0 += __shfl_xor_sync(~0u, s0, 1); s0 += __shfl_xor_sync(~0u, s0, 2);
                if (lane < 20) {
                    sts16(sb + SM_RK + lane * 2, pack_f16(f, 0.f));
                    sts32(sb + SM_SC + (lane & 28), Em * 0x00800080u);
                    put16(sb + SM_PN + (lane >> 2) * PN_SZ, pack_f16(s0 * (1.f / 16777216.f) + dsk * __uint_as_float((254u - Em) << 23), 0.f));
                }
                __syncwarp();
            }
            bar_sync(15, 672);
            asm volatile("fence.proxy.async.shared::cta;" ::: "memory");
#pragma unroll 1
            for (int i = 0; i < 24; i++) {
                if (lane == 0) tma2d(sb + SM_WG + i * 3840, i < 12 ? &tmG : &tmU, 320 * c + 8 * nslot * q, 48 * (i < 12 ? i : i - 12), mb + MB_W1 * 8);
            }
            STAMP(1);
        } else {
        if (warp == 20) {
            if (lane == 0) {
                asm volatile("cp.async.bulk.shared::cluster.global.mbarrier::complete_tx::bytes [%0], [%1], %2, [%3];"
                             :: "r"(sb + SM_ROW), "l"(prm.x + min(18 * (int)blockIdx.x, L_ - 1) * D_), "r"(max(min(18, L_ - 18 * (int)blockIdx.x), 1) * (D_ * 2)), "r"(mb + MB_R * 8) : "memory");
            }
            __syncwarp();
            mbar_wait(mb + MB_R * 8);
            if (lane == 0) {
                asm volatile("cp.async.bulk.tensor.5d.shared::cluster.global.mbarrier::complete_tx::bytes [%0], [%1, {%3, %4, %5, %5, %5}], [%2];"
                             :: "r"(sb + SM_XTL), "l"(&tmX), "r"(mb + MB_T * 8), "r"(d0 & ~15), "r"(8 * q), "r"(0) : "memory");
            }
            STAMP(6);
        }
        {
            const int idx = lane * 3 + max(warp - 21, 0), sl = nslot - 1 - (idx >> 3), pe = (idx + q + 1) & 7;
            const uint32_t rb_ = mapa(sb, pe);
            uint32_t cd = rb_ + SM_U + 128 + q * UP + sl * US, cs = sb + SM_XT + 128 + (q & 3) * 16 + pe * YP + sl * YS, cm = rb_ + SM_MB + (MB_X + sl) * 8;
            int act = sl < 0 ? 0 : pe == q ? -1 : 1;
            PIN(cd); PIN(cs); PIN(cm); PIN(act);
            asm volatile("barrier.cluster.wait.aligned;" ::: "memory");
            mbar_wait(mb + MB_R * 8);
            bar_sync(13, 608);
            asm volatile("fence.proxy.async.shared::cta;" ::: "memory");
            if (act < 0) arm(cm, 7 * 512);
            __syncwarp();
            if (act > 0)
                asm volatile("cp.async.bulk.shared::cluster.shared::cta.mbarrier::complete_tx::bytes [%0], [%1], 512, [%2];" :: "r"(cd), "r"(cs), "r"(cm) : "memory");
        }
        STAMP(1);
        if (warp == 20 && lane == 0) { asm volatile("prefetch.tensormap [%0];" :: "l"(&tmO) : "memory"); asm volatile("prefetch.tensormap [%0];" :: "l"(&tmH) : "memory"); }
        if (warp == 22) {
            __syncwarp();
            mbar_wait(mb + (MB_X + 1) * 8);
            const uint32_t old = (epoch & 1) ? 0u : 0x40004000u;
#pragma unroll
            for (int t = 0; t < 2; t++)
#pragma unroll
                for (int r = 0; r < 2; r++)
                    if ((lane & 7) < 6) g_s.cand[r * (64 * NCL * 6) + ((q * 8 + 4 * t + (lane >> 3)) * NCL + c) * 6 + (lane & 7)] = make_uint4(old, old, old, old);
            float a[4] = {0.f, 0.f, 0.f, 0.f};
            const uint32_t one = 0x3F803F80u;
            mma_bf16(a, one, one, one, one, wv.x, wv.y);  mma_bf16(a, one, one, one, one, wv.z, wv.w);
            mma_bf16(a, one, one, one, one, wv2.x, wv2.y); mma_bf16(a, one, one, one, one, wv2.z, wv2.w);
            mma_bf16(a, one, one, one, one, wv3.x, wv3.y); mma_bf16(a, one, one, one, one, wv3.z, wv3.w);
            float s = a[0] + a[1];
            s += __shfl_xor_sync(~0u, s, 1); s += __shfl_xor_sync(~0u, s, 2);
            stsf(sb + SM_SC + 24, s);
            __syncwarp();
            if (lane == 0) {
                int n = 0;
                while ((int)(ld_acq(&g_s.zcnt) - epoch * NCTA) < 0 && ++n < SPIN_LIMIT) __nanosleep(200);
                arm(mb + MB_Y * 8, 8 * 512 * nslot);
                if (blockIdx.x == 0) g_s.epoch = epoch;
            }
            STAMP(2);
        }
        if (warp == 23) {
#pragma unroll 1
            for (int kk = nslot - 1; kk >= 0; kk--) {
                __syncwarp();
                bar_sync(6 + kk, 160);
                if (kk < 2) mbar_wait(mb + MB_W1 * 8);
                if (lane == 0) { asm volatile("fence.proxy.async.shared::cta;" ::: "memory"); tma2d(sb + SM_FAR + kk * FAR_SZ, &tmD, 72 * q, 320 * c + 64 * kk, mb + MB_W2 * 8); }
            }
        }
        }
        __syncwarp();
        if (warp == 20) {
            bar_sync(11, 672);
            asm volatile("fence.proxy.async.shared::cta;" ::: "memory");
            bar_sync(14, 768);
            if (elect()) {
                asm volatile("cp.async.bulk.tensor.5d.global.shared::cta.bulk_group [%0, {%2, %4, %4, %4, %3}], [%1];" :: "l"(&tmH), "r"(sb + SM_XT + 16384), "r"(d0 + ((c & 1) ? 0 : 32)), "r"(8 * q), "r"(0) : "memory");
                asm volatile("cp.async.bulk.tensor.5d.global.shared::cta.bulk_group [%0, {%2, %4, %4, %4, %3}], [%1];" :: "l"(&tmO), "r"(sb + SM_XT), "r"(d0 + (c & 1) * 8), "r"(8 * q), "r"(0) : "memory");
                asm volatile("cp.async.bulk.commit_group;" ::: "memory");
            }
        } else bar_sync(14, 768);
        __syncwarp();
        const uint32_t ft = (tid >> 4) & 7, fj = d0 / 3 + (lane & 15), tok = ~lds32(sb + SM_SEL + ft * 8) & 2047;
        float v[3], cnt = 0.f;
#pragma unroll
        for (int i = 0; i < 3; i++) {
            const uint32_t cl = 3 * fj + i - d0, cf = cl - (c & 1) * 8;
            const bool ok = cl < 8 * nslot && ((tok >> 3) & 7) == q;
            const uint32_t u = lds16(sb + SM_XT + (cf < 32 ? tslot(tok) * 64 + cf * 2 : 16384 + tslot(tok) * 16 + (cl & 7) * 2));
            v[i] = ok ? __uint_as_float(u << 16) : 0.f;
            if (ok) cnt += 1.f;
        }
        if (warp == 20 && elect()) {
            asm volatile("cp.async.bulk.wait_group 0;" ::: "memory");
            asm volatile("fence.proxy.async.global;" ::: "memory");
            asm volatile("mbarrier.arrive.shared::cta.b64 _, [%0];" :: "r"(mb + MB_OUT * 8) : "memory");
        }
        __syncwarp();
        mbar_wait(mb + MB_OUT * 8);
        STAMP(5);
        if (cnt != 0.f) finish(prm, (ft * 192 + fj) * 16, (tok * D_ + 3 * fj) * 2, v, cnt);
        return;
    }

    const int g = lane >> 2, cq = lane & 3;
    const int k = warp >> 2, wq = warp & 3;
    const int trow = 18 * blockIdx.x + warp;
    const bool rowact = warp < 18 && trow < L_;
#pragma unroll
    for (int i = 2; i < 6; i++) pv[i] = ldg16((const char*)prm.prm6[i] + pofs);
    const int tn = 16 * (warp & 15) + g;
    uint32_t xa[5], xb[5];
    asm volatile("barrier.cluster.arrive.relaxed.aligned;" ::: "memory");
    char* const st1p = (char*)g_s.st1 + opaque(((((trow >> 3) & 7) * 256 + ((trow >> 6) & 31) * 8 + (trow & 7)) * 8 + lane) * 4);
    const bool pub = rowact && (lane & 0x1B) == 0;
    if (pub) st_rlx128(st1p, 0, 0, 0, 0);
    {
        const uint32_t za = sb + SM_P + tid * 16;
        sts128(za, 0, 0, 0, 0);
        if (tid < (SM_MISC - SM_P) / 16 - 640) sts128(za + 10240, 0, 0, 0, 0);
        sts128(sb + SM_U + ((tid >> 3) & 7) * UP + k * US + (lane & 7) * 16, 0, 0, 0, 0);
    }
    bar_sync(12, NTHR);
    const uint32_t dep = lds32(sb + SM_P);
#define PV(x) __uint_as_float(__byte_perm(dep, x, 0x5410))
    STAMP(1);
    const uint32_t fb = sb + SM_FAR + k * FAR_SZ;
    const uint32_t pn = sb + SM_PN + k * PN_SZ, pf = sb + SM_PF + k * PF_SZ;
    unsigned epoch, t258;
    {
        const uint32_t kb = fb + wq * 3072;
        const uint32_t kl = kb + lane * 16;
        uint32_t Af[4][4];
        float sr, si, z1r, z1i, z2r, z2i, z4r, z4i, hr, hi_;
        {
            const float dt = bfr(ex2f(PV(pLdt) * 1.4426950408889634f));
            const float e2 = dt * PV(pv[0]) * 1.4426950408889634f, an = dt * PV(pv[1]);
            float ar, ai, br, bi, cr, ci, dr, di;
            { const float m = ex2f(e2 * 8.f); ar = m * __cosf(an * 8.f); ai = m * __sinf(an * 8.f); }
            csq(br, bi, ar, ai); csq(cr, ci, br, bi); csq(dr, di, cr, ci);
            const H2C m4 = splat(cr, ci);
            {
                float r3, i3;
                cmul(r3, i3, ar, ai, br, bi);
                expand4(kl, kl + 1024, pack_f16(1.f, ar), pack_f16(br, r3), pack_f16(0.f, ai), pack_f16(bi, i3), m4);
            }
            expand8(kl + 512, kl + 1536, dr, di, ar, ai, br, bi, m4);
            { const float m = ex2f(e2); z1r = m * __cosf(an); z1i = -m * __sinf(an); }
            cexp_s(hr, hi_, e2 * 128.f, an * (-128.f * 0.15915494309189535f));
            csq(z2r, z2i, z1r, z1i); csq(z4r, z4i, z2r, z2i);
            const uint32_t dep2 = lds32(sb + SM_P + 4);
#define PW(x) __uint_as_float(__byte_perm(dep2, x, 0x5410))
            cmul(sr, si, PW(pv[4]), PW(pv[5]), dt * PW(pv[2]), dt * PW(pv[3]));
            const unsigned E = min(max(__reduce_max_sync(~0u, __float_as_uint(fmaxf(fabsf(sr), fabsf(si)))) >> 23, 1u), 253u);
            const float sc = __uint_as_float((254u - E) << 23);
            sr *= sc; si *= -sc;
            sts64(sb + SM_KG + warp * 8, E, __reduce_add_sync(~0u, __float2int_rn(sr * 16777216.f)));
        }
        __syncwarp();
#pragma unroll
        for (int ks = 0; ks < 4; ks++) ldsm4t(Af[ks], kb + (lane >> 3) * 512 + (lane & 7) * 16 + ks * 128);
        STAMP(2);
        const uint32_t la = kb + ((lane >> 3) & 1) * 512 + (lane >> 4) * 128 + (lane & 7) * 16;
        uint32_t b0[4], b1[4], b2[4], b3[4];
        auto ln1 = [&]() {
        mbar_wait(mb + MB_R * 8);
        epoch = lds32(sb + SM_SC + 28) + 1;
        {
            const uint32_t ra = sb + SM_ROW + warp * (D_ * 2);
            const uint4 r0 = lds128(ra + lane * 16), r1 = lds128(ra + 512 + lane * 16);
            const uint32_t rx[9] = {r0.x, r0.y, r0.z, r0.w, r1.x, r1.y, r1.z, r1.w, lds32(ra + 1024 + lane * 4)};
            float a0 = bf_lo(rx[0]), a1 = bf_hi(rx[0]), c0 = a0 * a0, c1 = a1 * a1;
#pragma unroll
            for (int i = 1; i < 9; i++) { const float l = bf_lo(rx[i]), h = bf_hi(rx[i]); a0 += l; a1 += h; c0 = fmaf(l, l, c0); c1 = fmaf(h, h, c1); }
            a0 += a1; c0 += c1;
            float s1 = ((lane & 1) ? c0 : a0) + __shfl_xor_sync(~0u, (lane & 1) ? a0 : c0, 1);
#pragma unroll
            for (int o = 2; o < 32; o <<= 1) s1 += __shfl_xor_sync(~0u, s1, o);
            const float s2 = __shfl_xor_sync(~0u, s1, 1);
            const uint32_t ms = ln_stats(s1, s2);
            const uint32_t p0 = __byte_perm(ms, epoch | 0x8000u, 0x5410), p1 = rsplit(rcpf(bf_hi(ms)));
            if (pub) st_rlx128(st1p, p0, p1, epoch, lane);
        }
        mbar_wait(mb + MB_R * 8);
        STAMP(1);
        };
        const uint4* sp = &g_s.st1[(256 * q + tn) * 2];
        uint2 sa, sc;
        auto poll = [&]() { sa = ld_rlx64(sp); sc = ld_rlx64(sp + 16); };
        auto norm = [&]() {
        STAMP(3);
        if (warp < 16) {
            uint32_t va[5], vc[5];
            poll();
            uint32_t x16 = g * (2 * XW) + cq * 16, x4 = g * (2 * XW) + cq * 4;
            const uint32_t xt = opaque(sb + SM_XTL + (c & 1) * 16 + (36 * (warp & 7) + 9 * (warp >> 3)) * (2 * XW));
            const int d4 = 2 * (lane >> 3) + (lane & 1), d1_ = lane & 7;
            const uint32_t own = SM_U + 128 + q * (UP - YP), oth = SM_XT + 128 + (q & 3) * 16;
            uint32_t a4 = sb + warp * 32 + d4 * YP + (d4 == q ? own : oth) + ((lane & 7) >> 1) * YS;
            uint32_t a1 = sb + warp * 32 + d1_ * YP + (d1_ == q ? own : oth) + 4 * YS + (lane & 8) * 2;
            PIN(a4); PIN(a1);
            uint32_t tag = __byte_perm(epoch | 0x8000u, 0, 0x1010);
            PIN(tag);
            PIN(x16); PIN(x4);
            uint32_t xh = sb + SM_XTL + (c & 1) * 16 + (9 * __byte_perm(0x12100200, 0x13110301, g) + 72 * (warp & 1) + (warp >> 1)) * (2 * XW) + cq * 4;
            PIN(xh);
            mbar_wait(mb + MB_T * 8);
            {
                const uint4 a4 = lds128(xt + x16), b4 = lds128(xt + x16 + 36 * XW);
                va[0] = a4.x; va[1] = a4.y; va[2] = a4.z; va[3] = a4.w; va[4] = lds32(xt + x4 + 64);
                vc[0] = b4.x; vc[1] = b4.y; vc[2] = b4.z; vc[3] = b4.w; vc[4] = lds32(xt + x4 + (64 + 36 * XW));
            }
            mbar_wait(mb + MB_T * 8);
            int n = 0;
            while (__byte_perm(sa.x, sc.x, 0x7632) != tag && ++n < SPIN_LIMIT) poll();
            STAMP(4);
#pragma unroll
            for (int i = 0; i < 5; i++) {
                va[i] = norm2(va[i], sa.x, sa.y); va[i] = pack_f16(bf_lo(va[i]), bf_hi(va[i]));
                vc[i] = norm2(vc[i], sc.x, sc.y); vc[i] = pack_f16(bf_lo(vc[i]), bf_hi(vc[i]));
            }
            stsm4t(a4, va[0], va[1], va[2], va[3]); stsm4t(a4 + 16, vc[0], vc[1], vc[2], vc[3]); stsm2t(a1, va[4], vc[4]);
            bar_arrive(13, 608);
            {
            const uint4 c4 = lds128(xh + cq * 12), d4_ = lds128(xh + cq * 12 + 72 * XW);
            xa[0] = c4.x; xa[1] = c4.y; xa[2] = c4.z; xa[3] = c4.w; xa[4] = lds32(xh + 64);
            xb[0] = d4_.x; xb[1] = d4_.y; xb[2] = d4_.z; xb[3] = d4_.w; xb[4] = lds32(xh + (64 + 72 * XW));
            }
        }
        STAMP(5);
        __syncwarp();
        bar_sync(15, 672);
        Af[0][0] |= lds32(sb + SM_P);
        };
        cmul(sr, si, sr, si, z1r, z1i);
        {
            const H2C h4 = splat(z4r, z4i);
            expand8(kl, kl + 512, sr, si, z1r, z1i, z2r, z2i, h4);
            cmul(sr, si, sr, si, hr, hi_);
            expand8(kl + 1024, kl + 1536, sr, si, z1r, z1i, z2r, z2i, h4);
        }
        __syncwarp();
        ldsm4t(b0, la); ldsm4t(b1, la + 256); ldsm4t(b2, la + 1024); ldsm4t(b3, la + 1280);
        cmul(z1r, z1i, z1r, z1i, hr, hi_);
        cmul(sr, si, sr, si, z1r, z1i);
        expand8(kl, kl + 512, sr, si, z2r, z2i, z4r, z4i, splat(hr, hi_));
        asm volatile("barrier.cluster.wait.aligned;" ::: "memory");
        bar_arrive(0, 672);
        ln1();
        csq(z1r, z1i, z1r, z1i);
        cmul(sr, si, sr, si, z1r, z1i);
        csq(z2r, z2i, hr, hi_);
        expand8(kl + 1024, kl + 1536, sr, si, z4r, z4i, hr, hi_, splat(z2r, z2i));
        csq(z1r, z1i, z1r, z1i);
        cmul(sr, si, sr, si, z1r, z1i);
        csq(z4r, z4i, z2r, z2i);
        expand8(kl + 2048, kl + 2560, sr, si, hr, hi_, z2r, z2i, splat(z4r, z4i));
        norm();
        {
            uint32_t c0[4], c1[4], c2[4], c3[4], e0[4], e1[4];
            float t[6][4];
            ldsm4t(c0, la); ldsm4t(c2, la + 1024);
            mma_f16_z(t[0], Af[0], b0[0], b0[1]);
            const uint32_t lb = la | (__float_as_uint(t[0][0]) & zero);
            mma_f16_z(t[1], Af[0], b2[0], b2[1]); mma_f16_z(t[2], Af[0], c0[0], c0[1]); mma_f16_z(t[3], Af[0], c2[0], c2[1]);
            ldsm4t(e0, lb + 2048); ldsm4t(c1, lb + 256); ldsm4t(c3, lb + 1280); ldsm4t(e1, lb + 2304);
            mma_f16(t[0], Af[1], b0[2], b0[3]); mma_f16(t[1], Af[1], b2[2], b2[3]); mma_f16(t[2], Af[1], c0[2], c0[3]); mma_f16(t[3], Af[1], c2[2], c2[3]);
            mma_f16(t[0], Af[2], b1[0], b1[1]); mma_f16(t[1], Af[2], b3[0], b3[1]);
            mma_f16_z(t[4], Af[0], e0[0], e0[1]); mma_f16_z(t[5], Af[1], e0[2], e0[3]);
            mma_f16(t[2], Af[2], c1[0], c1[1]); mma_f16(t[3], Af[2], c3[0], c3[1]);
            mma_f16(t[4], Af[2], e1[0], e1[1]); mma_f16(t[5], Af[3], e1[2], e1[3]);
            mma_f16(t[0], Af[3], b1[2], b1[3]); mma_f16(t[1], Af[3], b3[2], b3[3]); mma_f16(t[2], Af[3], c1[2], c1[3]); mma_f16(t[3], Af[3], c3[2], c3[3]);
#pragma unroll
            for (int i = 0; i < 4; i++) t[4][i] += t[5][i];
            stsm4(kl + 1024, pack_f16(t[0][0], t[0][1]), pack_f16(t[0][2], t[0][3]), pack_f16(t[1][0], t[1][1]), pack_f16(t[1][2], t[1][3]));
            stsm2(kl + 1536, pack_f16(t[2][0], t[2][1]), pack_f16(t[2][2], t[2][3]));
            sts64(kb + lane * 8 + 1792, pack_f16(t[3][1], t[3][0]), pack_f16(t[3][3], t[3][2]));
            sts64(kb + lane * 8 + 2048, pack_f16(t[4][1], t[4][0]), pack_f16(t[4][3], t[4][2]));
        }
        bar_sync(1 + k, 128);
        const uint2 rr = lds64(opaque(sb + SM_RK + k * 8));
        const int tq = (wq + k + 2) & 3;
        const uint32_t ra = lane * 8 + opaque(fb + (tq == 1 ? 2048 : tq * 256 + 1024));
        auto comb = [&](uint32_t a, uint32_t& x, uint32_t& y) {
            const uint2 p0 = lds64(a), p1 = lds64(a + 3072), p2 = lds64(a + 6144), p3 = lds64(a + 9216);
            x = comb4(p0.x, p1.x, p2.x, p3.x, rr.x, rr.y); y = comb4(p0.y, p1.y, p2.y, p3.y, rr.x, rr.y);
        };
        uint32_t w0, w1;
        comb(ra, w0, w1);
        const bool last = lane == 31;
        if (tq == 0) {
            uint32_t v0, v1;
            comb(ra + 256, v0, v1);
            const uint32_t n0 = __shfl_sync(~0u, lane ? w0 : v0, lane + 1);
            uint32_t n1 = __shfl_sync(~0u, v0, lane + 1);
            if (last) n1 = v1 >> 16;
            sts128(pn + 12 + lane * 16, __byte_perm(w1, w0, 0x7610), __byte_perm(w1, 0, 0x1032), __byte_perm(n0, w1, 0x7610), __byte_perm(n0, 0, 0x1032));
            sts128(pn + 524 + lane * 16, __byte_perm(v1, v0, 0x7610), __byte_perm(v1, 0, 0x1032), __byte_perm(n1, v1, 0x7610), __byte_perm(n1, 0, 0x1032));
            if (lane == 0) { sts16(pn + 4, w0); sts32(pn + 8, __byte_perm(w0, 0, 0x1032)); }
        } else if (tq == 1) {
            const uint32_t ph = pf + P_H7 + (g & 1) * (2 * P_HS) + cq * 64 + (g >> 1) * 4 + (cq & 2) * 16, sw = (cq & 2) ? 0x3210 : 0x1032;
            w0 = __byte_perm(hmul2(w0, 0x18001800u), 0, sw); w1 = __byte_perm(hmul2(w1, 0x18001800u), 0, sw);
            const uint32_t pi = ph + 32 - (cq & 2) * 32;
            put16(ph, w0); put16(pi, w0 >> 16); put16(ph + 16, w1); put16(pi + 16, w1 >> 16);
        } else if (tq == 2) {
            uint32_t n = __shfl_sync(~0u, w0, lane == 30 ? 1 : lane + 2);
            if (last) { put16(pf, hmul2(w1, 0x18001800u) >> 16); w1 = hadd2(w1, hneg2(__byte_perm(w1, 0, 0x3232))); n = 0; }
            const bool od = lane & 1;
            const uint32_t pa = pn + 1036 + (lane >> 1) * 32 + (od ? 528 : 0), pb = pa + (od ? -16 : 16);
            const uint32_t u0 = od ? w1 : w0, x0 = od ? n : w1, u1 = od ? w0 : w1, x1 = od ? w1 : n;
            const uint32_t b0 = __byte_perm(u0, 0, 0x3232), b1 = __byte_perm(u1, 0, 0x3232);
            sts128(pa, __byte_perm(u0, 0, 0x1032), b0, b0, __byte_perm(x0, u0, 0x7610));
            sts128(pb, __byte_perm(u1, 0, 0x1032), b1, b1, __byte_perm(x1, u1, 0x7610));
        } else {
            const uint32_t pa = pf + ((g & 1) ? 3 * P_GS : P_GS) + cq * 32 + (g >> 1) * 4;
            const uint32_t pb = pa + ((g & 1) ? 4 - 3 * P_GS : P_GS);
            w0 = hmul2(w0, 0x18001800u); w1 = hmul2(w1, 0x18001800u);
            put16(pa, w0 >> 16); put16(pb, w0); put16(pa + 16, w1 >> 16); put16(pb + 16, w1);
            if (last) put16(pf + P_H7 + P_HS, w1);
        }
        bar_sync(1 + k, 128);
        t258 = w0;
    }
    STAMP(6);

    mbar_wait(mb + (MB_X + k) * 8);
    STAMP(7);
    if (k < nslot) {
        const int role = (wq + k) & 3;
        const uint32_t ub = sb + SM_U + k * US + 128;
        const uint32_t l16 = lane * 16, tz = (lane & 28) - 8 * cq, tz4 = tz * 4;
        if (role) {
            const uint32_t al = cq * (2 * UP + 32) + tz4, au = opaque(ub + (3 - role) * 128), a1 = al + au, a0 = (cq ? al : al + (8 * UP - 16)) + au - 2 * UP;
            const uint4 q0 = lds128(a0), q1 = lds128(a0 + UP), q2 = lds128(a1), q3 = lds128(a1 + UP);
            const uint32_t U[16] = {q0.x, q0.y, q0.z, q0.w, q1.x, q1.y, q1.z, q1.w, q2.x, q2.y, q2.z, q2.w, q3.x, q3.y, q3.z, q3.w};
            uint32_t V[14], Q[14], R4[12], T[8];
#pragma unroll
            for (int i = 2; i < 14; i++) { V[i] = __byte_perm(U[i], U[i + 1], 0x5432); Q[i] = hadd2(U[i], V[i]); }
            const uint32_t rb = l16 + opaque(fb + (3 - role) * 512);
#pragma unroll
            for (int i = 0; i < 8; i++) T[i] = hadd2(V[5 + i], Q[6 + i]);
            sts128(rb + F_E3, T[0], T[1], T[2], T[3]); sts128(rb + F_O3 + 16, T[4], T[5], T[6], T[7]);
            asm volatile("{ .reg .pred p; setp.ne.u32 p, %10, 1; @p st.shared.v4.u32 [%0], {%2,%3,%4,%5}; @p st.shared.v4.u32 [%1], {%6,%7,%8,%9}; }"
                         :: "r"(rb + F_E2), "r"(rb + F_O2), "r"(Q[6]), "r"(Q[7]), "r"(Q[8]), "r"(Q[9]), "r"(Q[10]), "r"(Q[11]), "r"(Q[12]), "r"(Q[13]), "r"(role) : "memory");
#pragma unroll
            for (int i = 2; i < 12; i++) R4[i] = hadd2(Q[i], Q[i + 1]);
#pragma unroll
            for (int i = 0; i < 8; i++) T[i] = hadd2(R4[3 + i], U[5 + i]);
            sts128(rb + F_O5, T[0], T[1], T[2], T[3]); sts128(rb + F_E5, T[4], T[5], T[6], T[7]);
            if (role != 1) {
                uint32_t S[8];
#pragma unroll
                for (int i = 0; i < 8; i++) S[i] = hadd2(R4[2 + i], i < 7 ? T[i + 1] : hadd2(R4[11], U[13]));
                sts128(rb + F_O9, S[0], S[1], S[2], S[3]); sts128(rb + F_E9 + 16, S[4], S[5], S[6], S[7]);
#pragma unroll
                for (int i = 0; i < 8; i++) S[i] = hadd2(T[i], hadd2(V[2 + i], V[5 + i]));
                sts128(rb + F_E7, S[0], S[1], S[2], S[3]); sts128(rb + F_O7, S[4], S[5], S[6], S[7]);
            }
        } else if (lane == 0) {
            const uint4 m = lds128(ub + 23 * 16 + 7 * UP);
            const uint32_t U[6] = {lds32(ub + 23 * 16 + 6 * UP + 12), m.x, m.y, m.z, m.w, lds32(ub + 24 * 16)};
            uint32_t Q[5];
#pragma unroll
            for (int i = 0; i < 5; i++) Q[i] = hadd2(U[i], __byte_perm(U[i], U[i + 1], 0x5432));
            sts128(fb + F_O5 + 96 * 16, hadd2(hadd2(Q[0], Q[1]), U[2]), hadd2(hadd2(Q[1], Q[2]), U[3]), hadd2(hadd2(Q[2], Q[3]), U[4]), hadd2(hadd2(Q[3], Q[4]), U[5]));
            sts128(fb + F_O3, 0, 0, 0, 0); sts128(fb + F_E9, 0, 0, 0, 0);
            sts16(pn + 258 * 4, t258);
        }
        bar_sync(1 + k, 128);
        float acc[4][4];
        uint32_t Q[4][4];
        {
            const int h = role & 1, part = role >> 1;
            float fa[7][4];
            uint32_t B[3][4];
            const uint32_t po = tz + opaque(pf + part * (2 * P_GS)), ba = l16 + opaque(fb + (part == h ? 0 : F_O5 + h * 16));
#pragma unroll
            for (int s = 1; s >= 0; s--) {
#pragma unroll
                for (int i = 0; i < 3; i++) { Q[i][0] = lds32(po + (s * P_GS + i * 64)); if (i < 2) Q[i][1] = lds32(po + (s * P_GS + i * 64 + 32)); }
#pragma unroll
                for (int i = 0; i < 3; i++) ldsm4t(B[i], ba + (s * F_E3 + i * 512));
#pragma unroll
                for (int i = 0; i < 3; i++) { Q[i][3] = CP(Q[i][0]); if (i) Q[i][2] = CP(Q[i - 1][1]); }
                Q[0][2] = ZF(s ? tz : Q[0][0]); Q[2][1] = ZF(s ? l16 : Q[2][0]);
#pragma unroll
                for (int dl = 0; dl < 3; dl++)
#pragma unroll
                    for (int ap = 0; ap < 6 - dl; ap++) {
                        if (s == 1 && dl == 0) mma_f16_z(fa[ap + 1], Q[0], B[ap >> 1][2 * (ap & 1)], B[ap >> 1][2 * (ap & 1) + 1]);
                        else mma_f16(fa[ap + 1 + dl], Q[dl], B[ap >> 1][2 * (ap & 1)], B[ap >> 1][2 * (ap & 1) + 1]);
                    }
            }
#pragma unroll 1
            for (int s = role; s == 1; s++) {
                ldsm2t(B[0][0], B[0][1], fb + ((lane & 15) == 15 ? F_O5 : F_O3));
#pragma unroll
                for (int dl = 1; dl < 3; dl++) mma_f16(fa[dl], Q[dl], B[0][0], B[0][1]);
            }
            const uint32_t bh = l16 + opaque(fb + F_E7 + h * F_H + part * 2048), ph = tz + opaque(pf + P_H7 + part * (2 * P_HS));
#pragma unroll 1
            for (int s = part; s == 1; s++) {
                Q[2][1] = ZF(Q[2][3]); Q[2][2] = ZF(Q[2][2]); Q[2][0] = lds32(ph - P_HS);
                ldsm4t(B[0], bh - 1024); ldsm4t(B[1], bh - 512);
                Q[2][3] = CP(Q[2][0]);
#pragma unroll
                for (int ap = 0; ap < 4; ap++) mma_f16(fa[ap + 3], Q[2], B[ap >> 1][2 * (ap & 1)], B[ap >> 1][2 * (ap & 1) + 1]);
            }
            {
                Q[0][2] = ZF(tid);
#pragma unroll
                for (int i = 0; i < 4; i++) { Q[i][0] = lds32(ph + i * 64); Q[i][1] = lds32(ph + (i * 64 + 32)); }
                ldsm4t(B[0], bh); ldsm4t(B[1], bh + 512);
#pragma unroll
                for (int i = 0; i < 4; i++) { Q[i][3] = CP(Q[i][0]); if (i) Q[i][2] = CP(Q[i - 1][1]); }
#pragma unroll
                for (int dl = 0; dl < 4; dl++)
#pragma unroll
                    for (int ap = 0; ap < 4 - dl; ap++) mma_f16(fa[ap + 3 + dl], Q[dl], B[ap >> 1][2 * (ap & 1)], B[ap >> 1][2 * (ap & 1) + 1]);
            }
            const uint32_t da = (cq * 2048 + tz4) + opaque(fb + role * 128);
            bar_sync(1 + k, 128);
#pragma unroll
            for (int i = 1; i < 4; i++)
                stsm4(da + i * 512, pack_f16(fa[2 * i - 1][0], fa[2 * i - 1][1]), pack_f16(fa[2 * i - 1][2], fa[2 * i - 1][3]),
                      pack_f16(fa[2 * i][0], fa[2 * i][1]), pack_f16(fa[2 * i][2], fa[2 * i][3]));
            asm("shl.b32 %0, 0x6000, %1;" : "=r"(Q[0][0]) : "r"(tz4));
            Q[0][1] = ZF(Q[0][0]); Q[0][2] = ZF(tz4); Q[0][3] = CP(Q[0][0]);
            const uint32_t ra = l16 + opaque(fb + wq * 2016);
            acc[0][0] = acc[0][1] = acc[0][2] = acc[0][3] = 0.f;
            if (wq == 3) {
                const uint32_t uw = lds32(ub), kw = lds32(pf);
                const float2 uf = __half22float2(*(const __half2*)&uw);
                if ((lane | 4) == 31) acc[0][3] = (lane == 31 ? uf.x + uf.y : uf.x) * (__low2float(*(const __half2*)&kw) * 512.f);
            }
            bar_sync(1 + k, 128);
#pragma unroll
            for (int i = 1; i < 4; i++) {
                ldsm4(B[0], ra + i * 512);
                mma_f16_z(acc[i], Q[0], hadd2(B[0][0], B[0][2]), hadd2(B[0][1], B[0][3]));
            }
        }
        bar_arrive(6 + k, 160);
        STAMP(8);
        const uint32_t inv = lds32(opaque(sb + SM_SC + k * 4));
        const uint32_t yd = l16 + opaque(mapa(sb, 2 * wq) + (SM_XT + 128 + q * YP + k * YS + (k >> 2) * (q >> 1) * 16));
        {
            uint32_t pu = opaque(pn + 64 * (wq - 3));
#define pp (tz + pu)
            const uint32_t dlo = (((ub + 6 * UP) & 0x3FFFF) >> 4) | ((UP >> 4) << 16);
            uint32_t R[4][4];
            unsigned long long ds[4];
#pragma unroll
            for (int i = 0; i < 4; i++) asm volatile("mov.b64 %0, {%1, %2};" : "=l"(ds[i]) : "r"(dlo - i * (2 * UP >> 4)), "r"(8 | zero));
            auto loadQ = [&](uint32_t (&X)[4][4], uint32_t prev) {
#pragma unroll
                for (int i = 0; i < 4; i++) { X[i][0] = lds32(pp + i * 64); X[i][1] = lds32(pp + i * 64 + 32); }
                X[0][2] = CP(prev);
#pragma unroll
                for (int i = 0; i < 4; i++) { X[i][3] = CP(X[i][0]); if (i) X[i][2] = CP(X[i - 1][1]); }
                pu += 256;
            };
            auto issue = [&](uint32_t (&X)[4][4]) {
                asm volatile("wgmma.fence.sync.aligned;" ::: "memory");
#pragma unroll
                for (int i = 0; i < 4; i++) wgmma32(acc, X[i], ds[i]);
                asm volatile("wgmma.commit_group.sync.aligned;" ::: "memory");
#pragma unroll
                for (int i = 0; i < 4; i++) asm volatile("{ .reg .b32 l, h; mov.b64 {l, h}, %0; add.u32 l, l, %1; mov.b64 %0, {l, h}; }" : "+l"(ds[i]) : "r"(~zero));
            };
#pragma unroll
            for (int i = 0; i < 4; i++) {
                Q[i][0] = Q[i][1] = 0;
                if (wq + i >= 3) { Q[i][0] = lds32(pp + i * 64); Q[i][1] = lds32(pp + i * 64 + 32); }
            }
            Q[0][2] = CP(0);
#pragma unroll
            for (int i = 0; i < 4; i++) { Q[i][3] = CP(Q[i][0]); if (i) Q[i][2] = CP(Q[i - 1][1]); }
            pu += 256;
#pragma unroll 1
            for (int dl = 0; dl < 4; dl++) {
                issue(Q);
                asm volatile("wgmma.wait_group.sync.aligned 1;" ::: "memory");
                loadQ(R, Q[3][1]);
                issue(R);
                asm volatile("wgmma.wait_group.sync.aligned 1;" ::: "memory");
                loadQ(Q, R[3][1]);
            }
            issue(Q);
            asm volatile("wgmma.wait_group.sync.aligned 0;" ::: "memory");
        }
        const uint32_t pstep = mapa(sb, 1) - mapa(sb, 0), ym = mapa(mb + MB_Y * 8, 2 * wq);
#pragma unroll
        for (int e = 0; e < 2; e++)
            st_async4(yd + e * pstep, bmul2(pack_bf16(acc[0][2 * e], acc[0][2 * e + 1]), inv), bmul2(pack_bf16(acc[1][2 * e], acc[1][2 * e + 1]), inv),
                      bmul2(pack_bf16(acc[2][2 * e], acc[2][2 * e + 1]), inv), bmul2(pack_bf16(acc[3][2 * e], acc[3][2 * e + 1]), inv), ym + e * pstep);
        if (lane == 0) asm volatile("mbarrier.arrive.shared::cta.b64 _, [%0];" :: "r"(mb + MB_Y * 8) : "memory");
    }
    STAMP(9);
    uint32_t ha[5], hb[5];
    if (warp < 16) {
        const uint4 wk = lds128(sb + SM_DW + cq * 16);
        uint32_t sel[5] = {wk.x, wk.y, wk.z, wk.w, lds32(sb + SM_DW + 64 + cq * 4)}, sel2[5];
#pragma unroll
        for (int i = 0; i < 5; i++) {
            if (!(g & 1)) sel[i] = 0x3F803F80u;
            sel2[i] = sel[i]; PIN(sel2[i]);
        }
        uint32_t y4 = sb + SM_XT + 128 + warp * 32 + (2 * (lane >> 3) + (lane & 1)) * YP + ((lane & 7) >> 1) * YS;
        uint32_t y1 = sb + SM_XT + 128 + warp * 32 + (lane & 7) * YP + 4 * YS + (lane & 8) * 2 + (lane & 6) * 8;
        if (nslot != 5) {
            y1 = sb + SM_U;
            if (lane & 4) y4 = y1;
        }
        PIN(y4); PIN(y1);
        const uint32_t ao = (256 * q + tn) * 16;
        const uint32_t hta = opaque(sb + SM_HT + warp * 1024), htb = opaque(sb + SM_HT + 16384 + warp * 256);
        unsigned long long ap = (unsigned long long)((char*)g_s.acc + ao);
        asm volatile("add.u64 %0, %0, %1;" : "+l"(ap) : "l"((unsigned long long)zero));
        mbar_wait(mb + MB_Y * 8);
        STAMP(10);
        float ca[4] = {0.f, 0.f, 0.f, 0.f}, cb[4] = {0.f, 0.f, 0.f, 0.f};
        {
            uint32_t ya[4], yb[4], yc, yd;
            ldsm4t(ya, y4); ldsm4t(yb, y4 + 16); ldsm2t(yc, yd, y1);
#pragma unroll
            for (int i = 0; i < 4; i++) { ha[i] = badd2(xa[i], ya[i]); hb[i] = badd2(xb[i], yb[i]); }
            ha[4] = badd2(xa[4], yc); hb[4] = badd2(xb[4], yd);
        }
#pragma unroll
        for (int i = 0; i < 5; i++) { mma_bf16_k8(ca, ha[i], sel[i], ha[i]); mma_bf16_k8(cb, hb[i], sel2[i], hb[i]); }
        if (!(g & 1)) { ca[1] = ca[0]; cb[1] = cb[0]; }
        if (cq == (g >> 1)) {
            asm volatile("red.relaxed.gpu.global.add.v4.f32 [%0], {%1,%2,%3,%4};" :: "l"(ap), "f"(1.0f), "f"(ca[1]), "f"(ca[2]), "f"(ca[3]) : "memory");
            asm volatile("red.relaxed.gpu.global.add.v4.f32 [%0], {%1,%2,%3,%4};" :: "l"(ap + 128), "f"(1.0f), "f"(cb[1]), "f"(cb[2]), "f"(cb[3]) : "memory");
        }
        __syncwarp();
        mbar_wait(mb + MB_Y * 8);
#pragma unroll
        for (int i = 0; i < 4; i++) {
            asm volatile("or.b32 %0, %1, %2;" : "=r"(ha[i]) : "r"(ha[i]), "r"(zero));
            asm volatile("or.b32 %0, %1, %2;" : "=r"(hb[i]) : "r"(hb[i]), "r"(zero));
        }
        sts128(hta + lane * 16, ha[0], ha[1], ha[2], ha[3]); sts32(htb + lane * 4, ha[4]);
        sts128(hta + lane * 16 + 512, hb[0], hb[1], hb[2], hb[3]); sts32(htb + lane * 4 + 128, hb[4]);
        STAMP(11);
    }
    const int kq = warp / 5, mt = warp - 5 * kq;
    const int mi = lane >> 3, mr = lane & 7;
    const unsigned tk = (unsigned)tid / 72u, ck = tid - tk * 72;
    uint32_t A[9][4];
    auto loadA = [&]() {
        mbar_wait(mb + MB_W1 * 8);
        const uint32_t aa = sb + (mi & 1) * SM_WU + (8 * (mi >> 1) + mr) * 80 + (144 * 80 * kq + mt * 16);
#pragma unroll
        for (int s = 0; s < 9; s++) ldsm4t(A[s], aa + s * 1280);
    };
    const uint32_t par = (lds32(sb + SM_SC + 28) & 1) ? 0u : 0x40004000u;
    uint32_t go = (ck / 5u + ck) * 16, gs = sb + SM_SEL + 4 + (tk & 7) * 8;
    unsigned long long gb = (unsigned long long)((const char*)g_s.cand + go + (q & 1) * 92160);
    uint32_t xs = sb + SM_XS + tk * 16 + tid * 16;
    asm volatile("add.u64 %0, %0, %1;" : "+l"(gb) : "l"((unsigned long long)zero));
    PIN(xs); PIN(gs);
    auto outtile = [&]() {
        const uint2 sa = lds64(sb + SM_ST + tn * 8), sbb = lds64(sb + SM_ST + tn * 8 + 64);
#pragma unroll
        for (int i = 0; i < 5; i++) { ha[i] = badd2(ha[i], norm2(ha[i], sa.x, sa.y)); hb[i] = badd2(hb[i], norm2(hb[i], sbb.x, sbb.y)); }
        const bool hf = (c & 1) && cq == 0;
        const uint32_t o16 = sb + SM_XT + (hf ? 16384 + tn * 16 : tn * 64 + (cq - (c & 1)) * 16), o4 = sb + SM_XT + ((c & 1) ? tn * 64 + 48 : 16384 + tn * 16) + cq * 4;
        sts128(o16, ha[0], ha[1], ha[2], ha[3]); sts32(o4, ha[4]);
        sts128(o16 + (hf ? 128 : 512), hb[0], hb[1], hb[2], hb[3]); sts32(o4 + ((c & 1) ? 512 : 128), hb[4]);
    };
    if (warp < 8) {
        const float wsum = ldsf(sb + SM_SC + 24);
        const uint32_t idx = 2047 - (512 * ((tid >> 1) & 3) + 128 * ((tid >> 3) & 3) + 64 * (tid & 1) + 8 * q + warp);
        uint32_t km0 = mapa(mb + MB_KEY * 8, 2 * cq), km1 = mapa(mb + MB_KEY * 8, 2 * cq + 1), ka0 = mapa(sb + SM_RK + q * 32, 2 * cq), ka1 = mapa(sb + SM_RK + q * 32, 2 * cq + 1);
        unsigned long long c0 = (unsigned long long)((char*)g_s.cand + ((q * 8 * NCL + c) * 6 + cq) * 16), c1 = c0 + (64 - cq * 12);
        uint32_t hc = sb + SM_HT + cq * 16, h4a = sb + SM_HT + 16384 + cq * 4;
        uint32_t ca = sb + SM_KEY + warp * 128 + (warp & 1) * 32 + (lane & 28), r2a = sb + SM_KEY + cq * 16 + (cq >> 1) * 128;
        PIN(ca); PIN(r2a); PIN(km0); PIN(km1); PIN(ka0); PIN(ka1); PIN(hc); PIN(h4a);
        asm volatile("add.u64 %0, %0, %2; add.u64 %1, %1, %2;" : "+l"(c0), "+l"(c1) : "l"((unsigned long long)zero));
        uint4 s; int n = 0;
        uint32_t ox;
        do {
            s = ld_rlx128(&g_s.acc[256 * q + tid]);
            ox = __shfl_xor_sync(~0u, (lane & 1) ? s.z : s.w, 1);
        } while (__any_sync(~0u, __uint_as_float(s.x) != (float)NCL && ++n < SPIN_LIMIT));
        STAMP(16);
        const uint32_t ms = ln_stats(__uint_as_float((lane & 1) ? ox : s.z), __uint_as_float(s.y));
        const float rs = rcpf(bf_hi(ms));
        const uint32_t rb = pack_bf16(0.f, fmaf(-bf_lo(ms), wsum, __uint_as_float((lane & 1) ? s.w : ox)) * rs);
        const uint32_t key = (((rb ^ (((int)rb >> 31) | 0x80000000u)) >> 16) << 11) | idx;
        sts32(sb + SM_KEY + tid * 4, key);
        sts64(sb + SM_ST + tid * 8, ms, rsplit(rs));
        __syncwarp();
        uint32_t rank = rank4<8, 16>(sb + SM_KEY + warp * 128, key, ~zero);
        {
            const uint32_t sa = (rank * 4 ^ (warp & 1) * 32) + opaque(sb + SM_KEY + warp * 128);
            sts32(sa, key); sts32(sa + 1024, tid);
        }
        __syncwarp();
        const uint32_t mk = lds32(ca), t = lds32(ca + 1024);
        STAMP(17);
        bar_sync(12, 512);
        STAMP(18);
        const uint4 hv = lds128(hc + t * 64);
        const uint2 sv = lds64(sb + SM_ST + t * 8);
        const uint32_t h4 = lds32(h4a + t * 16);
        rank = rank4<4, 256>(r2a, mk, ~zero);
        const uint32_t rr = bmul2(sv.y, 0x3C803C80u);
        const uint32_t p0 = (norm2(hv.x, sv.x, rr) & 0xBFFFBFFFu) | par, p1 = (norm2(hv.y, sv.x, rr) & 0xBFFFBFFFu) | par, p2 = (norm2(hv.z, sv.x, rr) & 0xBFFFBFFFu) | par,
                       p3 = (norm2(hv.w, sv.x, rr) & 0xBFFFBFFFu) | par, p4 = (norm2(h4, sv.x, rr) & 0xBFFFBFFFu) | par;
        rank = quad_sum(rank);
        if (rank < 8) {
            st_async1(ka0 + rank * 4, mk, km0); st_async1(ka1 + rank * 4, mk, km1);
#pragma unroll
            for (int r = 0; r < 2; r++) {
                st_rlx128((void*)(c0 + (unsigned long long)rank * 1440 + r * 92160), p0, p1, p2, p3);
                asm volatile("st.relaxed.gpu.global.u32 [%0], %1;" :: "l"(c1 + (unsigned long long)rank * 1440 + r * 92160), "r"(p4) : "memory");
            }
        }
        __syncwarp();
    } else {
        mbar_wait(mb + MB_Y * 8); loadA();
        if (warp < 16) {
            bar_sync(12, 512);
        }
    }
    if (warp < 16) {
        outtile();
        if (warp >= 8) {
            uint32_t src = ((tid >> 2) - 64) * 1440, ma = sb + SM_RK - 256 + (tid >> 2) * 4, ra = sb + SM_RK + cq * 16;
            PIN(src); PIN(ma); PIN(ra);
            STAMP(19);
            mbar_wait(mb + MB_KEY * 8);
            STAMP(20);
            const uint32_t mk = lds32(ma);
            uint32_t rank = rank4<4, 64>(ra, mk, ~zero);
            rank = quad_sum(rank);
            sts64(sb + SM_SEL + rank * 8, mk, src);
        }
    }
    bar_sync(11, 672);
    STAMP(12);

    const char* gp = (const char*)gb + lds32(gs);
    uint4 hv = ld_rlx128(gp);
    if (warp < 8) loadA();
    uint32_t bx = sb + SM_XS + mr * 1168 + mi * 16 + 288 * kq, gd = mapa(sb, (kq & (NRED - 1)) * (8 / NRED)) + (SM_GU + (q * nslot + mt) * 128) + lane * 4;
    PIN(bx); PIN(gd);
    {
        if (warp < 18) {
            int n = 0;
            while (true) {
                sts128(xs, hv.x ^ par, hv.y ^ par, hv.z ^ par, hv.w ^ par);
                if (!__any_sync(~0u, ((hv.x ^ par) | (hv.y ^ par) | (hv.z ^ par) | (hv.w ^ par)) & 0x40004000u) || ++n >= SPIN_LIMIT) break;
                hv = ld_rlx128(gp);
            }
        }
    }
    bar_sync(14, 768);
    STAMP(13);
    float4 own;
    {
        float c0[4] = {0.f, 0.f, 0.f, 0.f}, c1[4] = {0.f, 0.f, 0.f, 0.f}, c2[4] = {0.f, 0.f, 0.f, 0.f};
        uint32_t b[5][4];
#pragma unroll
        for (int s = 0; s < 4; s++) ldsm4(b[s], bx + s * 64);
        asm volatile("ldmatrix.sync.aligned.m8n8.x2.shared.b16 {%0,%1}, [%2];" : "=r"(b[4][0]), "=r"(b[4][1]) : "r"(bx + 256) : "memory");
        mma_bf16(c0, A[0][0], A[0][1], A[0][2], A[0][3], b[0][0], b[0][1]);
        mma_bf16(c1, A[1][0], A[1][1], A[1][2], A[1][3], b[0][2], b[0][3]);
        mma_bf16(c2, A[2][0], A[2][1], A[2][2], A[2][3], b[1][0], b[1][1]);
        mma_bf16(c0, A[3][0], A[3][1], A[3][2], A[3][3], b[1][2], b[1][3]);
        mma_bf16(c1, A[4][0], A[4][1], A[4][2], A[4][3], b[2][0], b[2][1]);
        mma_bf16(c2, A[5][0], A[5][1], A[5][2], A[5][3], b[2][2], b[2][3]);
        mma_bf16(c0, A[6][0], A[6][1], A[6][2], A[6][3], b[3][0], b[3][1]);
        mma_bf16(c1, A[7][0], A[7][1], A[7][2], A[7][3], b[3][2], b[3][3]);
        mma_bf16(c2, A[8][0], A[8][1], A[8][2], A[8][3], b[4][0], b[4][1]);
        own = make_float4(c0[0] + c1[0] + c2[0], c0[1] + c1[1] + c2[1], c0[2] + c1[2] + c2[2], c0[3] + c1[3] + c2[3]);
        sts128f(sb + SM_RED + tid * 16, own.x, own.y, own.z, own.w);
    }
    if (kq < 4 - NRED) bar_arrive(1 + mt, 128); else
    bar_sync(1 + mt, 128);
    STAMP(21);
    if (mt < nslot && kq >= 4 - NRED) {
        const uint32_t ra = lane * 16 + opaque(sb + SM_RED + mt * 512);
        const float4 p0 = lds128f(ra), p1 = lds128f(ra + 2560), p2 = lds128f(lane * 16 + opaque(sb + SM_RED + mt * 512 + (5 - kq) * 2560)), p3 = own;
        const float g0 = bfr((p0.x + p1.x) + (p2.x + p3.x)), g1 = bfr((p0.y + p1.y) + (p2.y + p3.y));
        const uint32_t sg = pack_bf16(g0 * rcpf(1.f + ex2f(g0 * (-64.f * 1.4426950408889634f))), g1 * rcpf(1.f + ex2f(g1 * (-64.f * 1.4426950408889634f))));
        const uint32_t gu = bmul2(sg, pack_bf16(((p0.z + p1.z) + (p2.z + p3.z)) * 4096.f, ((p0.w + p1.w) + (p2.w + p3.w)) * 4096.f));
        const uint32_t pstep = mapa(sb, 1) - mapa(sb, 0), gm = mapa(mb + MB_GU * 8, (kq & (NRED - 1)) * (8 / NRED));
#pragma unroll
        for (int i = 0; i < 8 / NRED; i++) st_async1(gd + i * pstep, gu, gm + i * pstep);
    }
    mbar_wait(mb + MB_W2 * 8);
    {
        const uint32_t aa = sb + (8 * (mi >> 1) + mr) * 144 + (mi & 1) * 16 + (SM_FAR + 2304 * kq + mt * 32);
#pragma unroll
        for (int s = 0; s < 5; s++) ldsm4t(A[s], aa + s * FAR_SZ);
    }
    float sig; uint32_t ra2; unsigned long long fp, op;
    if (warp < 8) {
        const uint32_t key = lds32(sb + SM_SEL + warp * 8), k16 = key << 5, fj = 24 * q + lane;
        sig = bfr(rcpf(1.f + ex2f(__uint_as_float((k16 ^ (~((int)k16 >> 31) | 0x80000000u)) & 0xFFFF0000u) * -1.4426950408889634f)));
        ra2 = sb + SM_RED2 + warp * 304 + lane * 12;
        fp = (unsigned long long)(g_s.fin + warp * 192 + fj); op = (unsigned long long)(prm.out + (~key & 2047) * D_ + 3 * fj);
        PIN(ra2);
        asm volatile("add.u64 %0, %0, %3; add.u64 %1, %1, %3;" : "+l"(fp), "+l"(op), "+f"(sig) : "l"((unsigned long long)zero));
    }
    {
        uint32_t ba = sb + (SM_GU + 256 * kq) + (lane & 15) * 16 + (lane >> 4) * 1024, wa = sb + (SM_RED2 + kq * 2432 + mt * 64) + g * 4 + cq * 608;
        PIN(ba); PIN(wa);
        STAMP(22);
        mbar_wait(mb + MB_GU * 8);
        STAMP(23);
        float c0[4] = {0.f, 0.f, 0.f, 0.f}, c1[4] = {0.f, 0.f, 0.f, 0.f}, c2[4] = {0.f, 0.f, 0.f, 0.f};
        uint32_t b[2][4], b8, b9;
        ldsm4t(b[0], ba); ldsm4t(b[1], ba + 2048); ldsm2t(b8, b9, ba + 4096);
        mma_bf16(c0, A[0][0], A[0][1], A[0][2], A[0][3], b[0][0], b[0][1]);
        mma_bf16(c1, A[1][0], A[1][1], A[1][2], A[1][3], b[0][2], b[0][3]);
        if (nslot == 5) {
            mma_bf16(c2, A[4][0], A[4][1], A[4][2], A[4][3], b8, b9);
            mma_bf16(c0, A[2][0], A[2][1], A[2][2], A[2][3], b[1][0], b[1][1]);
            mma_bf16(c1, A[3][0], A[3][1], A[3][2], A[3][3], b[1][2], b[1][3]);
        }
        stsf(wa, c0[0] + c1[0] + c2[0]); stsf(wa + 304, c0[1] + c1[1] + c2[1]);
        if (mt < 4) { stsf(wa + 32, c0[2] + c1[2] + c2[2]); stsf(wa + 336, c0[3] + c1[3] + c2[3]); }
    }
    if (warp < 8) {
        float v[3];
        bar_sync(6, 640);
        STAMP(14);
        if (lane < 24) {
#pragma unroll
            for (int i = 0; i < 3; i++) v[i] = ((ldsf(ra2 + i * 4) + ldsf(ra2 + i * 4 + 2432)) + (ldsf(ra2 + i * 4 + 4864) + ldsf(ra2 + i * 4 + 7296))) * sig;
            asm volatile("{ .reg .f32 x, y, z, w; .reg .b16 a, b, c; .reg .pred p;\n"
                         "atom.relaxed.gpu.global.add.v4.f32 {x,y,z,w}, [%0], {%2,%3,%4,%5};\n"
                         "setp.eq.f32 p, w, %6; add.f32 x, x, %2; add.f32 y, y, %3; add.f32 z, z, %4;\n"
                         "cvt.rn.bf16.f32 a, x; cvt.rn.bf16.f32 b, y; cvt.rn.bf16.f32 c, z;\n"
                         "@p st.global.b16 [%1], a; @p st.global.b16 [%1 + 2], b; @p st.global.b16 [%1 + 4], c; }"
                         :: "l"(fp), "l"(op), "f"(v[0]), "f"(v[1]), "f"(v[2]), "f"(3.f), "f"(3.f * NCL) : "memory");
        }
    } else bar_arrive(6, 640);
    STAMP(15);
}

#undef pp
typedef __nv_bfloat16 bf16;
__device__ bf16 f_n[L_ * D_], f_h[L_ * D_];
__device__ float f_k[D_ * L_], f_r[L_], f_gu[8 * F_];
__device__ int f_idx[8];
__device__ __forceinline__ float b2f(bf16 v) { return __bfloat162float(v); }
__global__ void fb_ln(const bf16* in, const bf16* wr, bf16* out) {
    const int t = blockIdx.x * 8 + (threadIdx.x >> 5), lane = threadIdx.x & 31;
    const bf16* r = (in ? in : f_h) + t * D_;
    float s1 = 0.f, s2 = 0.f, s3 = 0.f;
    for (int i = lane; i < D_; i += 32) s1 += b2f(r[i]);
    for (int o = 16; o; o >>= 1) s1 += __shfl_xor_sync(~0u, s1, o);
    for (int i = lane; i < D_; i += 32) { const float d = b2f(r[i]) - s1 / D_; s2 += d * d; }
    for (int o = 16; o; o >>= 1) s2 += __shfl_xor_sync(~0u, s2, o);
    const float m = bfr(s1 / D_), sd = bfr(sqrtf(bfr(bfr(s2 / D_) + 1e-5f)));
    for (int i = lane; i < D_; i += 32) {
        const float v = bfr(bfr(b2f(r[i]) - m) / sd);
        f_n[t * D_ + i] = __float2bfloat16(v);
        if (!in) { s3 += v * b2f(wr[i]); out[t * D_ + i] = __float2bfloat16(b2f(r[i]) + v); }
    }
    for (int o = 16; o; o >>= 1) s3 += __shfl_xor_sync(~0u, s3, o);
    f_r[t] = bfr(s3);
}
__global__ void fb_taps(Params p) {
    const int d = blockIdx.x >> 3, l = (blockIdx.x & 7) * 256 + threadIdx.x;
    const float dt = bfr(expf(bf_lo(p.logdt[d]))), lf = bfr((float)l);
    float k = 0.f;
    for (int n = d * 128; n < d * 128 + 128; n++) {
        float wr, wi, sn, cs;
        cmul(wr, wi, bf_lo(p.prm6[4][n]), bf_lo(p.prm6[5][n]), dt * bf_lo(p.prm6[2][n]), dt * bf_lo(p.prm6[3][n]));
        sincosf(dt * bf_lo(p.prm6[1][n]) * lf, &sn, &cs);
        k += expf(dt * bf_lo(p.prm6[0][n]) * lf) * (wr * cs - wi * sn);
    }
    f_k[l * D_ + d] = k;
}
__global__ void fb_conv(Params p) {
    const int t = blockIdx.x, d = threadIdx.x;
    float y = 0.f;
    for (int l = 0; l <= t; l++) y += f_k[l * D_ + d] * b2f(f_n[(t - l) * D_ + d]);
    f_h[t * D_ + d] = __float2bfloat16(bf_lo(p.x[t * D_ + d]) + bfr(bfr(y) + bfr(b2f(f_n[t * D_ + d]) * bf_lo(p.dskip[d]))));
}
__global__ void fb_top() {
    const int t = blockIdx.x * 256 + threadIdx.x;
    int rank = 0;
    for (int j = 0; j < L_; j++) rank += f_r[j] > f_r[t] || (f_r[j] == f_r[t] && j < t);
    if (rank < 8) f_idx[rank] = t;
}
__global__ void fb_ffn1(const bf16* wg, const bf16* wu) {
    const int f = blockIdx.x * 256 + threadIdx.x, j = blockIdx.y;
    float g = 0.f, u = 0.f;
    for (int i = 0; i < D_; i++) { const float v = b2f(f_n[f_idx[j] * D_ + i]); g += v * b2f(wg[i * F_ + f]); u += v * b2f(wu[i * F_ + f]); }
    g = bfr(g);
    f_gu[j * F_ + f] = bfr(bfr(g / (1.f + expf(-g))) * bfr(u));
}
__global__ void fb_ffn2(const bf16* wd, bf16* out) {
    const int d = threadIdx.x, j = blockIdx.x, t = f_idx[j];
    float y = 0.f;
    for (int f = 0; f < F_; f++) y += f_gu[j * F_ + f] * b2f(wd[f * D_ + d]);
    out[t * D_ + d] = __float2bfloat16(b2f(f_h[t * D_ + d]) + bfr(b2f(f_n[t * D_ + d]) + bfr(bfr(y) * bfr(1.f / (1.f + expf(-f_r[t]))))));
}

typedef CUresult (*EncodeFn)(CUtensorMap*, CUtensorMapDataType, cuuint32_t, void*, const cuuint64_t*, const cuuint64_t*,
                             const cuuint32_t*, const cuuint32_t*, CUtensorMapInterleave, CUtensorMapSwizzle,
                             CUtensorMapL2promotion, CUtensorMapFloatOOBfill);

void make_map(EncodeFn fn, CUtensorMap* tm, const void* p, int cols, int rows, int bc, int br) {
    cuuint64_t dims[2] = {(cuuint64_t)cols, (cuuint64_t)rows};
    cuuint64_t strides[1] = {(cuuint64_t)cols * 2};
    cuuint32_t box[2] = {(cuuint32_t)bc, (cuuint32_t)br};
    cuuint32_t es[2] = {1, 1};
    fn(tm, CU_TENSOR_MAP_DATA_TYPE_BFLOAT16, 2, const_cast<void*>(p), dims, strides, box, es, CU_TENSOR_MAP_INTERLEAVE_NONE,
       CU_TENSOR_MAP_SWIZZLE_NONE, CU_TENSOR_MAP_L2_PROMOTION_L2_128B, CU_TENSOR_MAP_FLOAT_OOB_FILL_NONE);
}

void make_map3(EncodeFn fn, CUtensorMap* tm, const void* p) {
    cuuint64_t dims[5] = {(cuuint64_t)D_, 64, 2, 2, 8};
    cuuint64_t strides[4] = {(cuuint64_t)D_ * 2, (cuuint64_t)D_ * 2048, (cuuint64_t)D_ * 128, (cuuint64_t)D_ * 256};
    cuuint32_t box[5] = {XW, 9, 2, 2, 8};
    cuuint32_t es[5] = {1, 1, 1, 1, 1};
    fn(tm, CU_TENSOR_MAP_DATA_TYPE_BFLOAT16, 5, const_cast<void*>(p), dims, strides, box, es, CU_TENSOR_MAP_INTERLEAVE_NONE,
       CU_TENSOR_MAP_SWIZZLE_NONE, CU_TENSOR_MAP_L2_PROMOTION_NONE, CU_TENSOR_MAP_FLOAT_OOB_FILL_NONE);
}

void make_map5(EncodeFn fn, CUtensorMap* tm, const void* p, int bc) {
    cuuint64_t dims[5] = {(cuuint64_t)D_, 2, 4, 4, 64};
    cuuint64_t strides[4] = {(cuuint64_t)D_ * 128, (cuuint64_t)D_ * 1024, (cuuint64_t)D_ * 256, (cuuint64_t)D_ * 2};
    cuuint32_t box[5] = {(cuuint32_t)bc, 2, 4, 4, 8};
    cuuint32_t es[5] = {1, 1, 1, 1, 1};
    fn(tm, CU_TENSOR_MAP_DATA_TYPE_BFLOAT16, 5, const_cast<void*>(p), dims, strides, box, es, CU_TENSOR_MAP_INTERLEAVE_NONE,
       CU_TENSOR_MAP_SWIZZLE_NONE, CU_TENSOR_MAP_L2_PROMOTION_NONE, CU_TENSOR_MAP_FLOAT_OOB_FILL_NONE);
}

}

extern "C" void kernel_launch(void* const* d_in, const int* in_sizes, int n_in, void* d_out, int out_size) {
    (void)in_sizes; (void)n_in; (void)out_size;
    void* fp = nullptr;
    cudaDriverEntryPointQueryResult qr;
    cudaGetDriverEntryPoint("cuTensorMapEncodeTiled", &fp, cudaEnableDefault, &qr);
    EncodeFn fn = (EncodeFn)fp;
    CUtensorMap tmG, tmU, tmD, tmO, tmX, tmH;
    make_map3(fn, &tmX, d_in[0]);
    make_map(fn, &tmG, d_in[11], F_, D_, 40, 48);
    make_map(fn, &tmU, d_in[12], F_, D_, 40, 48);
    make_map(fn, &tmD, d_in[13], D_, F_, 72, 64);
    make_map5(fn, &tmO, d_out, 32);
    make_map5(fn, &tmH, d_out, 8);
    Params p;
    p.x = (const unsigned short*)d_in[0];
    for (int i = 0; i < 6; i++) p.prm6[i] = (const unsigned short*)d_in[1 + i];
    p.logdt = (const unsigned short*)d_in[7]; p.dskip = (const unsigned short*)d_in[8];
    p.wr = (const unsigned short*)d_in[10];
    p.out = (__nv_bfloat16*)d_out;
    p.zero = 0;
    cudaGetSymbolAddress((void**)&p.gs, g_s);
    cudaFuncSetAttribute(fused_kernel, cudaFuncAttributeMaxDynamicSharedMemorySize, SM_TOTAL);
    static int nclusters = -1;
    if (nclusters < 0) {
        cudaLaunchConfig_t cfg = {};
        cudaLaunchAttribute at;
        at.id = cudaLaunchAttributeClusterDimension; at.val.clusterDim.x = CS; at.val.clusterDim.y = 1; at.val.clusterDim.z = 1;
        cfg.gridDim = dim3(NCTA); cfg.blockDim = dim3(NTHR); cfg.dynamicSmemBytes = SM_TOTAL; cfg.attrs = &at; cfg.numAttrs = 1;
        if (cudaOccupancyMaxActiveClusters(&nclusters, fused_kernel, &cfg) != cudaSuccess) { (void)cudaGetLastError(); nclusters = NCL; }
    }
    if (nclusters >= NCL && !FORCE_FALLBACK) {
        fused_kernel<<<NCTA, NTHR, SM_TOTAL>>>(p, tmG, tmU, tmD, tmO, tmX, tmH);
        return;
    }
    fb_ln<<<L_ / 8, 256>>>((const bf16*)d_in[0], nullptr, nullptr);
    fb_taps<<<D_ * 8, 256>>>(p);
    fb_conv<<<L_, D_>>>(p);
    fb_ln<<<L_ / 8, 256>>>(nullptr, (const bf16*)d_in[10], p.out);
    fb_top<<<L_ / 256, 256>>>();
    fb_ffn1<<<dim3(F_ / 256, 8), 256>>>((const bf16*)d_in[11], (const bf16*)d_in[12]);
    fb_ffn2<<<8, D_>>>((const bf16*)d_in[13], p.out);
}
```

```cpp
#include <cuda_runtime.h>
#include <cuda_bf16.h>
#include <cuda_fp16.h>
#include <cuda.h>
#include <stdint.h>

namespace {

constexpr int L_ = 2048, D_ = 576, F_ = 4608;
constexpr int NCL = 15, CS = 8, NCTA = NCL * CS, NTHR = 768;
#define FORCE_FALLBACK 0
constexpr int XW = 48, NRED = 2;
constexpr int SPIN_LIMIT = 1 << 22;

constexpr int SM_WG   = 0;
constexpr int SM_WU   = 46080;
constexpr int YP = 3392, YS = 656;
constexpr int UP = 3280, US = 656;
constexpr int SM_XT   = 92160;
constexpr int SM_U    = SM_XT + 8 * YP;
constexpr int SM_FAR  = SM_U + 8 * UP;
constexpr int FAR_SZ  = 12416;
constexpr int F_E5 = 0, F_O5 = 1536, F_E3 = 3088, F_O3 = 4624, F_E7 = 6176, F_E2 = F_E7 + 1024, F_E9 = F_E7 + 2048,
              F_H = 3088, F_O7 = F_E7 + F_H, F_O2 = F_E2 + F_H, F_O9 = F_E9 + F_H;
constexpr int SM_P    = SM_FAR + 5 * FAR_SZ;
constexpr int PN_SZ = 584 * 4, SM_PN = SM_P + 65 * 4;
constexpr int P_GS = 50 * 4, P_H7 = 200 * 4, P_HS = 74 * 4;
constexpr int PF_SZ = (200 + 222) * 4, SM_PF = SM_PN + 5 * PN_SZ + 36;
constexpr int SM_MISC = SM_PF + 5 * PF_SZ;
constexpr int SM_ST   = SM_MISC;
constexpr int SM_RK   = SM_ST + 2048;
constexpr int SM_SEL  = SM_FAR + FAR_SZ + 10240;
constexpr int SM_KG   = SM_RK + 320;
constexpr int SM_SC   = SM_KG + 160;
constexpr int SM_DW   = SM_SC + 32;
constexpr int SM_MB   = SM_DW + 160;
constexpr int SM_TOTAL = SM_MB + 128;
constexpr int SM_ROW  = SM_XT - 20736;
constexpr int SM_XTL  = SM_ROW - 576 * XW;
constexpr int SM_RED2 = SM_WG;
constexpr int SM_HT   = SM_P - 512;
constexpr int SM_KEY  = SM_FAR + 10240 + 128;
constexpr int SM_CAND = SM_KEY + 1024;
constexpr int SM_XS   = SM_U;
constexpr int SM_GU   = SM_XS + 9344;
constexpr int SM_RED  = SM_GU + 5632;
static_assert(F_O9 + 1024 <= FAR_SZ && FAR_SZ % 128 == 0, "far overflow");
static_assert(SM_RED + 10240 <= SM_FAR && SM_HT + 20496 <= SM_MISC, "alias overflow");
static_assert(SM_TOTAL <= 232448, "smem overflow");
static_assert(SM_FAR % 128 == 0 && SM_XT % 128 == 0 && SM_XTL % 128 == 0 && SM_P % 16 == 0 && SM_MISC % 16 == 0 && SM_MB % 8 == 0, "align");

enum { MB_X = 0, MB_W1 = 5, MB_W2 = 6, MB_KEY = 7, MB_GU = 8, MB_Y = 9, MB_OUT = 10, MB_T = 11, MB_R = 12 };

struct __align__(128) Scratch {
    unsigned epoch, zcnt, pad[30];
    uint4  st1[L_ * 2];
    float4 acc[L_];
    uint4  cand[2 * 64 * NCL * 6];
    float4 fin[8 * 192 + 24];
};
__device__ Scratch g_s;
#define STAMP(i)

__device__ __forceinline__ uint32_t mapa(uint32_t a, uint32_t r) { uint32_t d; asm("mapa.shared::cluster.u32 %0, %1, %2;" : "=r"(d) : "r"(a), "r"(r)); return d; }
__device__ __forceinline__ void mbar_wait(uint32_t mb) {
    asm volatile("{ .reg .pred p, q; .reg .u32 n; mov.u32 n, 0;\n"
                 "W_%=: mbarrier.try_wait.parity.shared::cta.b64 p, [%0], 0; add.u32 n, n, 1; setp.lt.and.u32 q, n, 65536, !p; @q bra W_%=; }" :: "r"(mb) : "memory");
}
__device__ __forceinline__ bool elect() { uint32_t e; asm volatile("{ .reg .pred p; elect.sync _|p, 0xffffffff; selp.u32 %0, 1, 0, p; }" : "=r"(e)); return e; }
__device__ __forceinline__ void arm(uint32_t mb, uint32_t bytes) { asm volatile("mbarrier.arrive.expect_tx.shared::cta.b64 _, [%0], %1;" :: "r"(mb), "r"(bytes) : "memory"); }
__device__ __forceinline__ void bar_sync(int id, int n) { asm volatile("bar.sync %0, %1;" :: "r"(id), "r"(n) : "memory"); }
__device__ __forceinline__ void bar_arrive(int id, int n) { asm volatile("bar.arrive %0, %1;" :: "r"(id), "r"(n) : "memory"); }
__device__ __forceinline__ uint32_t lds16(uint32_t a) { unsigned short v; asm volatile("ld.shared.u16 %0, [%1];" : "=h"(v) : "r"(a) : "memory"); return v; }
__device__ __forceinline__ uint32_t lds32(uint32_t a) { uint32_t v; asm volatile("ld.shared.u32 %0, [%1];" : "=r"(v) : "r"(a) : "memory"); return v; }
__device__ __forceinline__ uint2 lds64(uint32_t a) { uint2 v; asm volatile("ld.shared.v2.u32 {%0,%1}, [%2];" : "=r"(v.x), "=r"(v.y) : "r"(a) : "memory"); return v; }
__device__ __forceinline__ float ldsf(uint32_t a) { float v; asm volatile("ld.shared.f32 %0, [%1];" : "=f"(v) : "r"(a) : "memory"); return v; }
__device__ __forceinline__ uint4 lds128(uint32_t a) { uint4 v; asm volatile("ld.shared.v4.u32 {%0,%1,%2,%3}, [%4];" : "=r"(v.x), "=r"(v.y), "=r"(v.z), "=r"(v.w) : "r"(a) : "memory"); return v; }
__device__ __forceinline__ float4 lds128f(uint32_t a) { float4 v; asm volatile("ld.shared.v4.f32 {%0,%1,%2,%3}, [%4];" : "=f"(v.x), "=f"(v.y), "=f"(v.z), "=f"(v.w) : "r"(a) : "memory"); return v; }
__device__ __forceinline__ void sts16(uint32_t a, uint32_t v) { asm volatile("{ .reg .b16 l, h; mov.b32 {l, h}, %1; st.shared.b16 [%0], l; }" :: "r"(a), "r"(v) : "memory"); }
__device__ __forceinline__ void sts32(uint32_t a, uint32_t v) { asm volatile("st.shared.u32 [%0], %1;" :: "r"(a), "r"(v) : "memory"); }
__device__ __forceinline__ void sts64(uint32_t a, uint32_t x, uint32_t y) { asm volatile("st.shared.v2.u32 [%0], {%1,%2};" :: "r"(a), "r"(x), "r"(y) : "memory"); }
__device__ __forceinline__ void stsf(uint32_t a, float v) { asm volatile("st.shared.f32 [%0], %1;" :: "r"(a), "f"(v) : "memory"); }
__device__ __forceinline__ void sts128(uint32_t a, uint32_t x, uint32_t y, uint32_t z, uint32_t w) { asm volatile("st.shared.v4.u32 [%0], {%1,%2,%3,%4};" :: "r"(a), "r"(x), "r"(y), "r"(z), "r"(w) : "memory"); }
__device__ __forceinline__ void sts128f(uint32_t a, float x, float y, float z, float w) { asm volatile("st.shared.v4.f32 [%0], {%1,%2,%3,%4};" :: "r"(a), "f"(x), "f"(y), "f"(z), "f"(w) : "memory"); }
__device__ __forceinline__ void ldsm4(uint32_t (&r)[4], uint32_t a) { asm volatile("ldmatrix.sync.aligned.m8n8.x4.shared.b16 {%0,%1,%2,%3}, [%4];" : "=r"(r[0]), "=r"(r[1]), "=r"(r[2]), "=r"(r[3]) : "r"(a) : "memory"); }
__device__ __forceinline__ void ldsm4t(uint32_t (&r)[4], uint32_t a) { asm volatile("ldmatrix.sync.aligned.m8n8.x4.trans.shared.b16 {%0,%1,%2,%3}, [%4];" : "=r"(r[0]), "=r"(r[1]), "=r"(r[2]), "=r"(r[3]) : "r"(a) : "memory"); }
__device__ __forceinline__ void ldsm2t(uint32_t& r0, uint32_t& r1, uint32_t a) { asm volatile("ldmatrix.sync.aligned.m8n8.x2.trans.shared.b16 {%0,%1}, [%2];" : "=r"(r0), "=r"(r1) : "r"(a) : "memory"); }
__device__ __forceinline__ void stsm4t(uint32_t a, uint32_t r0, uint32_t r1, uint32_t r2, uint32_t r3) { asm volatile("stmatrix.sync.aligned.m8n8.x4.trans.shared.b16 [%0], {%1,%2,%3,%4};" :: "r"(a), "r"(r0), "r"(r1), "r"(r2), "r"(r3) : "memory"); }
__device__ __forceinline__ void stsm4(uint32_t a, uint32_t r0, uint32_t r1, uint32_t r2, uint32_t r3) { asm volatile("stmatrix.sync.aligned.m8n8.x4.shared.b16 [%0], {%1,%2,%3,%4};" :: "r"(a), "r"(r0), "r"(r1), "r"(r2), "r"(r3) : "memory"); }
__device__ __forceinline__ void stsm2(uint32_t a, uint32_t r0, uint32_t r1) { asm volatile("stmatrix.sync.aligned.m8n8.x2.shared.b16 [%0], {%1,%2};" :: "r"(a), "r"(r0), "r"(r1) : "memory"); }
__device__ __forceinline__ void stsm2t(uint32_t a, uint32_t r0, uint32_t r1) { asm volatile("stmatrix.sync.aligned.m8n8.x2.trans.shared.b16 [%0], {%1,%2};" :: "r"(a), "r"(r0), "r"(r1) : "memory"); }
__device__ __forceinline__ uint4 ldg128(const void* p) { uint4 v; asm volatile("ld.global.nc.v4.u32 {%0,%1,%2,%3}, [%4];" : "=r"(v.x), "=r"(v.y), "=r"(v.z), "=r"(v.w) : "l"(p)); return v; }
__device__ __forceinline__ uint32_t ldg16(const void* p) { unsigned short v; asm volatile("ld.global.nc.u16 %0, [%1];" : "=h"(v) : "l"(p)); return v; }
__device__ __forceinline__ uint32_t opaque(uint32_t v) { uint32_t r; asm volatile("mov.b32 %0, %1;" : "=r"(r) : "r"(v)); return r; }
__device__ __forceinline__ void mma_f16(float (&d)[4], const uint32_t (&a)[4], uint32_t b0, uint32_t b1) {
    asm volatile("mma.sync.aligned.m16n8k16.row.col.f32.f16.f16.f32 {%0,%1,%2,%3}, {%4,%5,%6,%7}, {%8,%9}, {%0,%1,%2,%3};"
        : "+f"(d[0]), "+f"(d[1]), "+f"(d[2]), "+f"(d[3]) : "r"(a[0]), "r"(a[1]), "r"(a[2]), "r"(a[3]), "r"(b0), "r"(b1));
}
__device__ __forceinline__ void mma_f16_z(float (&d)[4], const uint32_t (&a)[4], uint32_t b0, uint32_t b1) {
    asm volatile("mma.sync.aligned.m16n8k16.row.col.f32.f16.f16.f32 {%0,%1,%2,%3}, {%4,%5,%6,%7}, {%8,%9}, {%10,%10,%10,%10};"
        : "=f"(d[0]), "=f"(d[1]), "=f"(d[2]), "=f"(d[3]) : "r"(a[0]), "r"(a[1]), "r"(a[2]), "r"(a[3]), "r"(b0), "r"(b1), "f"(0.f));
}
__device__ __forceinline__ void mma_bf16(float (&d)[4], uint32_t a0, uint32_t a1, uint32_t a2, uint32_t a3, uint32_t b0, uint32_t b1) {
    asm volatile("mma.sync.aligned.m16n8k16.row.col.f32.bf16.bf16.f32 {%0,%1,%2,%3}, {%4,%5,%6,%7}, {%8,%9}, {%0,%1,%2,%3};"
        : "+f"(d[0]), "+f"(d[1]), "+f"(d[2]), "+f"(d[3]) : "r"(a0), "r"(a1), "r"(a2), "r"(a3), "r"(b0), "r"(b1));
}
__device__ __forceinline__ void mma_bf16_k8(float (&d)[4], uint32_t a0, uint32_t a1, uint32_t b0) {
    asm volatile("mma.sync.aligned.m16n8k8.row.col.f32.bf16.bf16.f32 {%0,%1,%2,%3}, {%4,%5}, {%6}, {%0,%1,%2,%3};"
        : "+f"(d[0]), "+f"(d[1]), "+f"(d[2]), "+f"(d[3]) : "r"(a0), "r"(a1), "r"(b0));
}
__device__ __forceinline__ uint32_t pack_f16(float lo, float hi) { uint32_t r; asm("cvt.rn.f16x2.f32 %0, %1, %2;" : "=r"(r) : "f"(hi), "f"(lo)); return r; }
__device__ __forceinline__ uint32_t pack_bf16(float lo, float hi) { uint32_t r; asm("cvt.rn.bf16x2.f32 %0, %1, %2;" : "=r"(r) : "f"(hi), "f"(lo)); return r; }
__device__ __forceinline__ float bf_lo(uint32_t v) { return __uint_as_float(v << 16); }
__device__ __forceinline__ float bf_hi(uint32_t v) { return __uint_as_float(v & 0xFFFF0000u); }
__device__ __forceinline__ float bfr(float x) { return __uint_as_float(pack_bf16(0.f, x)); }
__device__ __forceinline__ uint32_t badd2(uint32_t a, uint32_t b) { uint32_t r; asm("add.rn.bf16x2 %0, %1, %2;" : "=r"(r) : "r"(a), "r"(b)); return r; }
__device__ __forceinline__ uint32_t bmul2(uint32_t a, uint32_t b) { uint32_t r; asm("mul.rn.bf16x2 %0, %1, %2;" : "=r"(r) : "r"(a), "r"(b)); return r; }
__device__ __forceinline__ uint32_t hadd2(uint32_t a, uint32_t b) { uint32_t r; asm("add.rn.f16x2 %0, %1, %2;" : "=r"(r) : "r"(a), "r"(b)); return r; }
__device__ __forceinline__ uint32_t hmul2(uint32_t a, uint32_t b) { uint32_t r; asm("mul.rn.f16x2 %0, %1, %2;" : "=r"(r) : "r"(a), "r"(b)); return r; }
__device__ __forceinline__ uint32_t hneg2(uint32_t a) { uint32_t r; asm("neg.f16x2 %0, %1;" : "=r"(r) : "r"(a)); return r; }
__device__ __forceinline__ float rcpf(float x) { float r; asm("rcp.approx.ftz.f32 %0, %1;" : "=f"(r) : "f"(x)); return r; }
__device__ __forceinline__ float sqrta(float x) { float r; asm("sqrt.approx.ftz.f32 %0, %1;" : "=f"(r) : "f"(x)); return r; }
__device__ __forceinline__ float ex2f(float x) { float r; asm("ex2.approx.ftz.f32 %0, %1;" : "=f"(r) : "f"(x)); return r; }
__device__ __forceinline__ void st_async4(uint32_t a, uint32_t x, uint32_t y, uint32_t z, uint32_t w, uint32_t mb) {
    asm volatile("st.async.shared::cluster.mbarrier::complete_tx::bytes.v4.u32 [%0], {%1,%2,%3,%4}, [%5];" :: "r"(a), "r"(x), "r"(y), "r"(z), "r"(w), "r"(mb) : "memory"); }
__device__ __forceinline__ void st_async1(uint32_t a, uint32_t x, uint32_t mb) {
    asm volatile("st.async.shared::cluster.mbarrier::complete_tx::bytes.u32 [%0], %1, [%2];" :: "r"(a), "r"(x), "r"(mb) : "memory"); }
__device__ __forceinline__ unsigned ld_rlx(const void* p) { unsigned v; asm volatile("ld.relaxed.gpu.global.u32 %0, [%1];" : "=r"(v) : "l"(p) : "memory"); return v; }
__device__ __forceinline__ unsigned ld_acq(const void* p) { unsigned v; asm volatile("ld.acquire.gpu.global.u32 %0, [%1];" : "=r"(v) : "l"(p) : "memory"); return v; }
__device__ __forceinline__ uint2 ld_rlx64(const void* p) { unsigned long long v; asm volatile("ld.relaxed.gpu.global.u64 %0, [%1];" : "=l"(v) : "l"(p) : "memory"); return make_uint2((unsigned)v, (unsigned)(v >> 32)); }
__device__ __forceinline__ void st_rlx128(void* p, uint32_t x, uint32_t y, uint32_t z, uint32_t w) {
    asm volatile("st.relaxed.gpu.global.v2.u64 [%0], {%1,%2};" :: "l"(p), "l"((unsigned long long)x | ((unsigned long long)y << 32)), "l"((unsigned long long)z | ((unsigned long long)w << 32)) : "memory"); }
__device__ __forceinline__ uint4 ld_rlx128(const void* p) { unsigned long long a, b; asm volatile("ld.relaxed.gpu.global.v2.u64 {%0,%1}, [%2];" : "=l"(a), "=l"(b) : "l"(p) : "memory"); return make_uint4((unsigned)a, (unsigned)(a >> 32), (unsigned)b, (unsigned)(b >> 32)); }
__device__ __forceinline__ void tma2d(uint32_t dst, const CUtensorMap* tm, int x, int y, uint32_t mb) {
    asm volatile("cp.async.bulk.tensor.2d.shared::cluster.global.mbarrier::complete_tx::bytes [%0], [%1, {%3, %4}], [%2];"
                 :: "r"(dst), "l"(tm), "r"(mb), "r"(x), "r"(y) : "memory");
}
__device__ __forceinline__ void cmul(float& xr, float& xi, float ar, float ai, float br, float bi) {
    const float r = fmaf(ar, br, -ai * bi), i = fmaf(ar, bi, ai * br); xr = r; xi = i;
}
__device__ __forceinline__ void csq(float& xr, float& xi, float ar, float ai) {
    const float r = fmaf(ar, ar, -ai * ai), i = (ar + ar) * ai; xr = r; xi = i;
}
__device__ __forceinline__ void cexp_s(float& zr, float& zi, float e2, float turns) {
    const float mag = ex2f(e2), r = (turns - rintf(turns)) * 6.283185307179586f;
    zr = mag * __cosf(r); zi = mag * __sinf(r);
}
__device__ __forceinline__ uint32_t ln_stats(float s1, float s2) {
    const float m = s1 * (1.f / D_);
    const float var = fmaxf(fmaf(s2, 1.f / D_, -m * m), 0.f);
    return pack_bf16(m, sqrta(bfr(bfr(var) + 1e-5f)));
}
__device__ __forceinline__ uint32_t rsplit(float rs) { const float h = bfr(rs); return pack_bf16(h, rs - h); }
__device__ __forceinline__ uint32_t norm2(uint32_t v, uint32_t mx, uint32_t hl) {
    uint32_t r;
    asm("{ .reg .b16 m, h, l, x; .reg .b32 m2, h2, l2, d, t; mov.b32 {m, x}, %2; mov.b32 {h, l}, %3; mov.b32 m2, {m, m}; mov.b32 h2, {h, h}; mov.b32 l2, {l, l};\n"
        "sub.rn.bf16x2 d, %1, m2; mul.rn.bf16x2 t, d, l2; fma.rn.bf16x2 %0, d, h2, t; }" : "=r"(r) : "r"(v), "r"(mx), "r"(hl));
    return r;
}
template <int N, int S>
__device__ __forceinline__ uint32_t rank4(uint32_t a, uint32_t key, uint32_t m1) {
    uint32_t r0 = 0, r1 = 0, r2 = 0, r3 = 0;
#pragma unroll
    for (int i = 0; i < N; i++) {
        const uint4 o = lds128(a + i * S);
        r0 += (o.x * m1 + key) >> 31; r1 += (o.y * m1 + key) >> 31; r2 += (o.z * m1 + key) >> 31; r3 += (o.w * m1 + key) >> 31;
    }
    return (r0 + r1) + (r2 + r3);
}
__device__ __forceinline__ uint32_t quad_sum(uint32_t r) {
    const uint32_t a = __shfl_xor_sync(~0u, r, 1), b = __shfl_xor_sync(~0u, r, 2), c = __shfl_xor_sync(~0u, r, 3);
    return (r + a) + b + c;
}
typedef uint32_t H2C;
__device__ __forceinline__ H2C splat(float r, float i) { return pack_f16(r, i); }
__device__ __forceinline__ void hcmul(uint32_t& xr, uint32_t& xi, uint32_t R, uint32_t I, H2C m) {
    asm("{ .reg .b16 a, b; .reg .b32 a2, b2, t; mov.b32 {a, b}, %4; mov.b32 a2, {a, a}; mov.b32 b2, {b, b};\n"
        "mul.rn.f16x2 t, %3, b2; neg.f16x2 t, t; fma.rn.f16x2 %0, %2, a2, t; mul.rn.f16x2 t, %3, a2; fma.rn.f16x2 %1, %2, b2, t; }"
        : "=&r"(xr), "=r"(xi) : "r"(R), "r"(I), "r"(m));
}
__device__ __forceinline__ void expand4(uint32_t are, uint32_t aim, uint32_t R0, uint32_t R1, uint32_t I0, uint32_t I1, H2C m4) {
    uint32_t R2, I2, R3, I3;
    hcmul(R2, I2, R0, I0, m4); hcmul(R3, I3, R1, I1, m4);
    sts128(are, R0, R1, R2, R3);
    sts128(aim, I0, I1, I2, I3);
}
__device__ __forceinline__ void expand8(uint32_t are, uint32_t aim, float sr, float si, float m1r, float m1i, float m2r, float m2i, H2C m4) {
    float r1, i1, r2, i2, r3, i3;
    cmul(r1, i1, sr, si, m1r, m1i); cmul(r2, i2, sr, si, m2r, m2i); cmul(r3, i3, r1, i1, m2r, m2i);
    expand4(are, aim, pack_f16(sr, r1), pack_f16(r2, r3), pack_f16(si, i1), pack_f16(i2, i3), m4);
}
__device__ __forceinline__ uint32_t comb4(uint32_t a, uint32_t b, uint32_t c, uint32_t d, uint32_t r01, uint32_t r23) {
    uint32_t x;
    asm("{ .reg .b16 h0, h1, h2, h3; .reg .b32 m0, m1, m2, m3, u, v; mov.b32 {h0, h1}, %5; mov.b32 {h2, h3}, %6;\n"
        "mov.b32 m0, {h0, h0}; mov.b32 m1, {h1, h1}; mov.b32 m2, {h2, h2}; mov.b32 m3, {h3, h3};\n"
        "mul.rn.f16x2 u, %2, m1; fma.rn.f16x2 u, %1, m0, u; mul.rn.f16x2 v, %4, m3; fma.rn.f16x2 v, %3, m2, v; add.rn.f16x2 %0, u, v; }"
        : "=r"(x) : "r"(a), "r"(b), "r"(c), "r"(d), "r"(r01), "r"(r23));
    return x;
}
__device__ __forceinline__ void put16(uint32_t a, uint32_t v) { sts16(a, v); sts16(a + 6, v); }

struct Params {
    const unsigned short *logdt, *dskip, *prm6[6], *x, *wr;
    __nv_bfloat16* out;
    Scratch* gs;
    unsigned zero;
};
__device__ __forceinline__ uint32_t tslot(uint32_t t) { return (t & 7) * 32 + ((t >> 4) & 24) + ((t >> 8) & 6) + ((t >> 6) & 1); }
#define CP(x) ((x) | zero)
#define ZF(x) ((x) & zero)
#define PIN(x) asm volatile("or.b32 %0, %0, %1;" : "+r"(x) : "r"(zero))
__device__ __forceinline__ void wgmma32(float (&d)[4][4], const uint32_t (&a)[4], unsigned long long ds) {
    asm volatile("wgmma.mma_async.sync.aligned.m64n32k16.f32.f16.f16 {%0,%1,%2,%3,%4,%5,%6,%7,%8,%9,%10,%11,%12,%13,%14,%15}, {%16,%17,%18,%19}, %20, 1, 1, 1, 0;"
        : "+f"(d[0][0]), "+f"(d[0][1]), "+f"(d[0][2]), "+f"(d[0][3]), "+f"(d[1][0]), "+f"(d[1][1]), "+f"(d[1][2]), "+f"(d[1][3]),
          "+f"(d[2][0]), "+f"(d[2][1]), "+f"(d[2][2]), "+f"(d[2][3]), "+f"(d[3][0]), "+f"(d[3][1]), "+f"(d[3][2]), "+f"(d[3][3])
        : "r"(a[0]), "r"(a[1]), "r"(a[2]), "r"(a[3]), "l"(ds));
}

__device__ __forceinline__ void finish(const Params& prm, uint32_t fo, uint32_t oo, const float (&v)[3], float cnt) {
    float x, y, z, w;
    asm volatile("atom.relaxed.gpu.global.add.v4.f32 {%0,%1,%2,%3}, [%4], {%5,%6,%7,%8};" : "=f"(x), "=f"(y), "=f"(z), "=f"(w)
                 : "l"((char*)prm.gs->fin + fo), "f"(v[0]), "f"(v[1]), "f"(v[2]), "f"(cnt) : "memory");
    if (w + cnt == 3.f * (NCL + 1)) {
        __nv_bfloat16* op = (__nv_bfloat16*)((char*)prm.out + oo);
        op[0] = __float2bfloat16(x + v[0]); op[1] = __float2bfloat16(y + v[1]); op[2] = __float2bfloat16(z + v[2]);
    }
}

__global__ void __cluster_dims__(CS, 1, 1) __launch_bounds__(NTHR, 1)
fused_kernel(const __grid_constant__ Params prm, const __grid_constant__ CUtensorMap tmG, const __grid_constant__ CUtensorMap tmU,
             const __grid_constant__ CUtensorMap tmD, const __grid_constant__ CUtensorMap tmO, const __grid_constant__ CUtensorMap tmX, const __grid_constant__ CUtensorMap tmH)
{
    extern __shared__ __align__(1024) unsigned char smem[];
    const int tid = threadIdx.x, lane = tid & 31, warp = __shfl_sync(~0u, tid >> 5, 0);
    const int c = blockIdx.x >> 3, q = blockIdx.x & 7;
    const int nslot = (c < NCL - 1) ? 5 : 2;
    const int d0 = 40 * c;
    const uint32_t sb = opaque((uint32_t)__cvta_generic_to_shared(smem));
    const uint32_t mb = sb + SM_MB;
    Scratch& g_s = *prm.gs;
    const unsigned& zero = prm.zero;
    const uint32_t dch2 = min(d0 + q + ((tid >> 4) & ~7), D_ - 1) * 2;
    uint32_t pv[6], pLdt;
    const uint32_t pofs = opaque(dch2 * 128 + (tid & 127) * 2);
    pLdt = ldg16((const char*)prm.logdt + dch2);
#pragma unroll
    for (int i = 0; i < 2; i++) pv[i] = ldg16((const char*)prm.prm6[i] + pofs);
    STAMP(0);

    if (warp >= 20) {
        unsigned epoch = 0;
        if (warp == 20) {
            if (lane == 0) {
#pragma unroll
                for (int i = 0; i < 13; i++)
                    asm volatile("mbarrier.init.shared::cta.b64 [%0], %1;" :: "r"(mb + i * 8), "r"((i == MB_R || i < 2) ? 2 : i < 5 ? (nslot + 1) / 3 : i == MB_Y ? 1 + 4 * nslot : 1) : "memory");
                asm volatile("fence.mbarrier_init.release.cluster;" ::: "memory");
                arm(mb + MB_W1 * 8, 92160); arm(mb + MB_W2 * 8, nslot * 9216); arm(mb + MB_KEY * 8, 256); arm(mb + MB_GU * 8, nslot * 1024); arm(mb + MB_T * 8, 576 * XW);
                const int bytes = max(min(18, L_ - 18 * (int)blockIdx.x), 1) * (D_ * 2);
                arm(mb + MB_R * 8, bytes);
            }
            __syncwarp();
        } else if (warp == 22) {
            epoch = ld_rlx(&g_s.epoch);
            if (lane < 18 ? 18 * c + lane < 256 : lane < 31) (lane < 18 ? &g_s.acc[256 * q + 18 * c] : &g_s.fin[13 * (int)blockIdx.x - 18])[lane] = make_float4(0.f, 0.f, 0.f, 0.f);
        } else if (warp == 23 && lane == 0) asm volatile("prefetch.tensormap [%0];" :: "l"(&tmX) : "memory");
        asm volatile("barrier.cluster.arrive.relaxed.aligned;" ::: "memory");
        bar_sync(12, NTHR);
        uint4 wv = make_uint4(0, 0, 0, 0), wv2, wv3;
        if (warp == 22) {
            if (lane == 0) { sts32(sb + SM_SC + 28, epoch); asm volatile("mbarrier.arrive.shared::cta.b64 _, [%0];" :: "r"(mb + MB_R * 8) : "memory"); }
            epoch++;
            asm volatile("fence.acq_rel.gpu;" ::: "memory");
            __syncwarp();
            if (lane == 0) asm volatile("red.relaxed.gpu.global.add.u32 [%0], 1;" :: "l"(&g_s.zcnt) : "memory");
            STAMP(1);
            wv2 = ldg128((const uint4*)prm.wr + lane); wv3 = ldg128((const uint4*)prm.wr + 32 + lane);
            if (lane < 8) wv = ldg128((const uint4*)prm.wr + 64 + lane);
            if (lane < 5) {
                uint4 v = make_uint4(0, 0, 0, 0);
                if (lane < nslot) v = ldg128((const uint4*)(prm.wr + d0) + lane);
                sts128(sb + SM_DW + lane * 16, v.x, v.y, v.z, v.w);
            }
            __syncwarp();
            if (lane < 5) asm volatile("mbarrier.arrive.shared::cta.b64 _, [%0];" :: "r"(mb + (MB_X + lane) * 8) : "memory");
        }
        if (warp == 21) {
            if (lane == 0) { asm volatile("prefetch.tensormap [%0];" :: "l"(&tmG) : "memory"); asm volatile("prefetch.tensormap [%0];" :: "l"(&tmU) : "memory"); asm volatile("prefetch.tensormap [%0];" :: "l"(&tmD) : "memory"); }
            __syncwarp();
            const float dsk = bf_lo(ldg16(prm.dskip + min(d0 + 2 * (lane & 28) + q, D_ - 1)));
            bar_sync(0, 672);
            {
                const uint2 m = lds64(sb + SM_KG + min(lane, 19) * 8);
                unsigned Em = max(m.x, __shfl_xor_sync(~0u, m.x, 1));
                Em = max(Em, __shfl_xor_sync(~0u, Em, 2));
                Em = max(Em, min(__float_as_uint(fabsf(dsk) * (1.f / 8192.f)) >> 23, 253u));
                const float f = __uint_as_float(max((int)(127 + m.x - Em), 0) << 23);
                float s0 = (float)(int)m.y * f;
                s0 += __shfl_xor_sync(~0u, s0, 1); s0 += __shfl_xor_sync(~0u, s0, 2);
                if (lane < 20) {
                    sts16(sb + SM_RK + lane * 2, pack_f16(f, 0.f));
                    sts32(sb + SM_SC + (lane & 28), Em * 0x00800080u);
                    put16(sb + SM_PN + (lane >> 2) * PN_SZ, pack_f16(s0 * (1.f / 16777216.f) + dsk * __uint_as_float((254u - Em) << 23), 0.f));
                }
                __syncwarp();
            }
            bar_sync(15, 672);
            asm volatile("fence.proxy.async.shared::cta;" ::: "memory");
#pragma unroll 1
            for (int i = 0; i < 24; i++) {
                if (lane == 0) tma2d(sb + SM_WG + i * 3840, i < 12 ? &tmG : &tmU, 320 * c + 8 * nslot * q, 48 * (i < 12 ? i : i - 12), mb + MB_W1 * 8);
            }
            STAMP(1);
        } else {
        if (warp == 20) {
            if (lane == 0) {
                asm volatile("cp.async.bulk.shared::cluster.global.mbarrier::complete_tx::bytes [%0], [%1], %2, [%3];"
                             :: "r"(sb + SM_ROW), "l"(prm.x + min(18 * (int)blockIdx.x, L_ - 1) * D_), "r"(max(min(18, L_ - 18 * (int)blockIdx.x), 1) * (D_ * 2)), "r"(mb + MB_R * 8) : "memory");
            }
            __syncwarp();
            {
                const long long t0 = clock64();
                uint32_t ok;
                do {
                    asm volatile("{ .reg .pred p; mbarrier.test_wait.parity.shared::cta.b64 p, [%1], 0; selp.u32 %0, 1, 0, p; }" : "=r"(ok) : "r"(mb + MB_R * 8) : "memory");
                    __nanosleep(20);
                } while (!ok && clock64() - t0 < 1800);
                __syncwarp();
            }
            if (elect()) {
                asm volatile("cp.async.bulk.tensor.5d.shared::cluster.global.mbarrier::complete_tx::bytes [%0], [%1, {%3, %4, %5, %5, %5}], [%2];"
                             :: "r"(sb + SM_XTL), "l"(&tmX), "r"(mb + MB_T * 8), "r"(d0 & ~15), "r"(8 * q), "r"(0) : "memory");
            }
            STAMP(6);
        }
        {
            const int idx = lane * 3 + max(warp - 21, 0), sl = nslot - 1 - (idx >> 3), pe = (idx + q + 1) & 7;
            const uint32_t rb_ = mapa(sb, pe);
            uint32_t cd = rb_ + SM_U + 128 + q * UP + sl * US, cs = sb + SM_XT + 128 + (q & 3) * 16 + pe * YP + sl * YS, cm = rb_ + SM_MB + (MB_X + sl) * 8;
            int act = sl < 0 ? 0 : pe == q ? -1 : 1;
            PIN(cd); PIN(cs); PIN(cm); PIN(act);
            asm volatile("barrier.cluster.wait.aligned;" ::: "memory");
            mbar_wait(mb + MB_R * 8);
            bar_sync(13, 608);
            asm volatile("fence.proxy.async.shared::cta;" ::: "memory");
            if (act < 0) arm(cm, 7 * 512);
            __syncwarp();
            if (act > 0)
                asm volatile("cp.async.bulk.shared::cluster.shared::cta.mbarrier::complete_tx::bytes [%0], [%1], 512, [%2];" :: "r"(cd), "r"(cs), "r"(cm) : "memory");
        }
        STAMP(1);
        if (warp == 20 && lane == 0) { asm volatile("prefetch.tensormap [%0];" :: "l"(&tmO) : "memory"); asm volatile("prefetch.tensormap [%0];" :: "l"(&tmH) : "memory"); }
        if (warp == 22) {
            __syncwarp();
            mbar_wait(mb + (MB_X + 1) * 8);
            const uint32_t old = (epoch & 1) ? 0u : 0x40004000u;
#pragma unroll
            for (int t = 0; t < 2; t++)
#pragma unroll
                for (int r = 0; r < 2; r++)
                    if ((lane & 7) < 6) g_s.cand[r * (64 * NCL * 6) + ((q * 8 + 4 * t + (lane >> 3)) * NCL + c) * 6 + (lane & 7)] = make_uint4(old, old, old, old);
            float a[4] = {0.f, 0.f, 0.f, 0.f};
            const uint32_t one = 0x3F803F80u;
            mma_bf16(a, one, one, one, one, wv.x, wv.y);  mma_bf16(a, one, one, one, one, wv.z, wv.w);
            mma_bf16(a, one, one, one, one, wv2.x, wv2.y); mma_bf16(a, one, one, one, one, wv2.z, wv2.w);
            mma_bf16(a, one, one, one, one, wv3.x, wv3.y); mma_bf16(a, one, one, one, one, wv3.z, wv3.w);
            float s = a[0] + a[1];
            s += __shfl_xor_sync(~0u, s, 1); s += __shfl_xor_sync(~0u, s, 2);
            stsf(sb + SM_SC + 24, s);
            __syncwarp();
            if (lane == 0) {
                int n = 0;
                while ((int)(ld_acq(&g_s.zcnt) - epoch * NCTA) < 0 && ++n < SPIN_LIMIT) __nanosleep(200);
                arm(mb + MB_Y * 8, 8 * 512 * nslot);
                if (blockIdx.x == 0) g_s.epoch = epoch;
            }
            STAMP(2);
        }
        if (warp == 23) {
#pragma unroll 1
            for (int kk = nslot - 1; kk >= 0; kk--) {
                __syncwarp();
                bar_sync(6 + kk, 160);
                if (kk < 2) mbar_wait(mb + MB_W1 * 8);
                if (lane == 0) { asm volatile("fence.proxy.async.shared::cta;" ::: "memory"); tma2d(sb + SM_FAR + kk * FAR_SZ, &tmD, 72 * q, 320 * c + 64 * kk, mb + MB_W2 * 8); }
            }
        }
        }
        __syncwarp();
        if (warp == 20) {
            bar_sync(11, 672);
            asm volatile("fence.proxy.async.shared::cta;" ::: "memory");
            bar_sync(14, 768);
            if (elect()) {
                asm volatile("cp.async.bulk.tensor.5d.global.shared::cta.bulk_group [%0, {%2, %4, %4, %4, %3}], [%1];" :: "l"(&tmH), "r"(sb + SM_XT + 16384), "r"(d0 + ((c & 1) ? 0 : 32)), "r"(8 * q), "r"(0) : "memory");
                asm volatile("cp.async.bulk.tensor.5d.global.shared::cta.bulk_group [%0, {%2, %4, %4, %4, %3}], [%1];" :: "l"(&tmO), "r"(sb + SM_XT), "r"(d0 + (c & 1) * 8), "r"(8 * q), "r"(0) : "memory");
                asm volatile("cp.async.bulk.commit_group;" ::: "memory");
            }
        } else bar_sync(14, 768);
        __syncwarp();
        const uint32_t ft = (tid >> 4) & 7, fj = d0 / 3 + (lane & 15), tok = ~lds32(sb + SM_SEL + ft * 8) & 2047;
        float v[3], cnt = 0.f;
#pragma unroll
        for (int i = 0; i < 3; i++) {
            const uint32_t cl = 3 * fj + i - d0, cf = cl - (c & 1) * 8;
            const bool ok = cl < 8 * nslot && ((tok >> 3) & 7) == q;
            const uint32_t u = lds16(sb + SM_XT + (cf < 32 ? tslot(tok) * 64 + cf * 2 : 16384 + tslot(tok) * 16 + (cl & 7) * 2));
            v[i] = ok ? __uint_as_float(u << 16) : 0.f;
            if (ok) cnt += 1.f;
        }
        if (warp == 20 && elect()) {
            asm volatile("cp.async.bulk.wait_group 0;" ::: "memory");
            asm volatile("fence.proxy.async.global;" ::: "memory");
            asm volatile("mbarrier.arrive.shared::cta.b64 _, [%0];" :: "r"(mb + MB_OUT * 8) : "memory");
        }
        __syncwarp();
        mbar_wait(mb + MB_OUT * 8);
        STAMP(5);
        if (cnt != 0.f) finish(prm, (ft * 192 + fj) * 16, (tok * D_ + 3 * fj) * 2, v, cnt);
        return;
    }

    const int g = lane >> 2, cq = lane & 3;
    const int k = warp >> 2, wq = warp & 3;
    const int trow = 18 * blockIdx.x + warp;
    const bool rowact = warp < 18 && trow < L_;
#pragma unroll
    for (int i = 2; i < 6; i++) pv[i] = ldg16((const char*)prm.prm6[i] + pofs);
    const int tn = 16 * (warp & 15) + g;
    uint32_t xa[5], xb[5];
    asm volatile("barrier.cluster.arrive.relaxed.aligned;" ::: "memory");
    char* const st1p = (char*)g_s.st1 + opaque(((((trow >> 3) & 7) * 256 + ((trow >> 6) & 31) * 8 + (trow & 7)) * 8 + lane) * 4);
    const bool pub = rowact && (lane & 0x1B) == 0;
    if (pub) st_rlx128(st1p, 0, 0, 0, 0);
    {
        const uint32_t za = sb + SM_P + tid * 16;
        sts128(za, 0, 0, 0, 0);
        if (tid < (SM_MISC - SM_P) / 16 - 640) sts128(za + 10240, 0, 0, 0, 0);
        sts128(sb + SM_U + ((tid >> 3) & 7) * UP + k * US + (lane & 7) * 16, 0, 0, 0, 0);
    }
    bar_sync(12, NTHR);
    const uint32_t dep = lds32(sb + SM_P);
#define PV(x) __uint_as_float(__byte_perm(dep, x, 0x5410))
    STAMP(1);
    const uint32_t fb = sb + SM_FAR + k * FAR_SZ;
    const uint32_t pn = sb + SM_PN + k * PN_SZ, pf = sb + SM_PF + k * PF_SZ;
    unsigned epoch, t258;
    {
        const uint32_t kb = fb + wq * 3072;
        const uint32_t kl = kb + lane * 16;
        uint32_t Af[4][4];
        float sr, si, z1r, z1i, z2r, z2i, z4r, z4i, hr, hi_;
        {
            const float dt = bfr(ex2f(PV(pLdt) * 1.4426950408889634f));
            const float e2 = dt * PV(pv[0]) * 1.4426950408889634f, an = dt * PV(pv[1]);
            float ar, ai, br, bi, cr, ci, dr, di;
            { const float m = ex2f(e2 * 8.f); ar = m * __cosf(an * 8.f); ai = m * __sinf(an * 8.f); }
            csq(br, bi, ar, ai); csq(cr, ci, br, bi); csq(dr, di, cr, ci);
            const H2C m4 = splat(cr, ci);
            {
                float r3, i3;
                cmul(r3, i3, ar, ai, br, bi);
                expand4(kl, kl + 1024, pack_f16(1.f, ar), pack_f16(br, r3), pack_f16(0.f, ai), pack_f16(bi, i3), m4);
            }
            expand8(kl + 512, kl + 1536, dr, di, ar, ai, br, bi, m4);
            { const float m = ex2f(e2); z1r = m * __cosf(an); z1i = -m * __sinf(an); }
            cexp_s(hr, hi_, e2 * 128.f, an * (-128.f * 0.15915494309189535f));
            csq(z2r, z2i, z1r, z1i); csq(z4r, z4i, z2r, z2i);
            const uint32_t dep2 = lds32(sb + SM_P + 4);
#define PW(x) __uint_as_float(__byte_perm(dep2, x, 0x5410))
            cmul(sr, si, PW(pv[4]), PW(pv[5]), dt * PW(pv[2]), dt * PW(pv[3]));
            const unsigned E = min(max(__reduce_max_sync(~0u, __float_as_uint(fmaxf(fabsf(sr), fabsf(si)))) >> 23, 1u), 253u);
            const float sc = __uint_as_float((254u - E) << 23);
            sr *= sc; si *= -sc;
            sts64(sb + SM_KG + warp * 8, E, __reduce_add_sync(~0u, __float2int_rn(sr * 16777216.f)));
        }
        __syncwarp();
#pragma unroll
        for (int ks = 0; ks < 4; ks++) ldsm4t(Af[ks], kb + (lane >> 3) * 512 + (lane & 7) * 16 + ks * 128);
        STAMP(2);
        const uint32_t la = kb + ((lane >> 3) & 1) * 512 + (lane >> 4) * 128 + (lane & 7) * 16;
        uint32_t b0[4], b1[4], b2[4], b3[4];
        auto ln1 = [&]() {
        mbar_wait(mb + MB_R * 8);
        epoch = lds32(sb + SM_SC + 28) + 1;
        {
            const uint32_t ra = sb + SM_ROW + warp * (D_ * 2);
            const uint4 r0 = lds128(ra + lane * 16), r1 = lds128(ra + 512 + lane * 16);
            const uint32_t rx[9] = {r0.x, r0.y, r0.z, r0.w, r1.x, r1.y, r1.z, r1.w, lds32(ra + 1024 + lane * 4)};
            float a0 = bf_lo(rx[0]), a1 = bf_hi(rx[0]), c0 = a0 * a0, c1 = a1 * a1;
#pragma unroll
            for (int i = 1; i < 9; i++) { const float l = bf_lo(rx[i]), h = bf_hi(rx[i]); a0 += l; a1 += h; c0 = fmaf(l, l, c0); c1 = fmaf(h, h, c1); }
            a0 += a1; c0 += c1;
            float s1 = ((lane & 1) ? c0 : a0) + __shfl_xor_sync(~0u, (lane & 1) ? a0 : c0, 1);
#pragma unroll
            for (int o = 2; o < 32; o <<= 1) s1 += __shfl_xor_sync(~0u, s1, o);
            const float s2 = __shfl_xor_sync(~0u, s1, 1);
            const uint32_t ms = ln_stats(s1, s2);
            const uint32_t p0 = __byte_perm(ms, epoch | 0x8000u, 0x5410), p1 = rsplit(rcpf(bf_hi(ms)));
            if (pub) st_rlx128(st1p, p0, p1, epoch, lane);
        }
        mbar_wait(mb + MB_R * 8);
        STAMP(1);
        };
        const uint4* sp = &g_s.st1[(256 * q + tn) * 2];
        uint2 sa, sc;
        auto poll = [&]() { sa = ld_rlx64(sp); sc = ld_rlx64(sp + 16); };
        auto norm = [&]() {
        STAMP(3);
        if (warp < 16) {
            uint32_t va[5], vc[5];
            poll();
            uint32_t x16 = g * (2 * XW) + cq * 16, x4 = g * (2 * XW) + cq * 4;
            const uint32_t xt = opaque(sb + SM_XTL + (c & 1) * 16 + (36 * (warp & 7) + 9 * (warp >> 3)) * (2 * XW));
            const int d4 = 2 * (lane >> 3) + (lane & 1), d1_ = lane & 7;
            const uint32_t own = SM_U + 128 + q * (UP - YP), oth = SM_XT + 128 + (q & 3) * 16;
            uint32_t a4 = sb + warp * 32 + d4 * YP + (d4 == q ? own : oth) + ((lane & 7) >> 1) * YS;
            uint32_t a1 = sb + warp * 32 + d1_ * YP + (d1_ == q ? own : oth) + 4 * YS + (lane & 8) * 2;
            PIN(a4); PIN(a1);
            uint32_t tag = __byte_perm(epoch | 0x8000u, 0, 0x1010);
            PIN(tag);
            PIN(x16); PIN(x4);
            uint32_t xh = sb + SM_XTL + (c & 1) * 16 + (9 * __byte_perm(0x12100200, 0x13110301, g) + 72 * (warp & 1) + (warp >> 1)) * (2 * XW) + cq * 4;
            PIN(xh);
            mbar_wait(mb + MB_T * 8);
            {
                const uint4 a4 = lds128(xt + x16), b4 = lds128(xt + x16 + 36 * XW);
                va[0] = a4.x; va[1] = a4.y; va[2] = a4.z; va[3] = a4.w; va[4] = lds32(xt + x4 + 64);
                vc[0] = b4.x; vc[1] = b4.y; vc[2] = b4.z; vc[3] = b4.w; vc[4] = lds32(xt + x4 + (64 + 36 * XW));
            }
            mbar_wait(mb + MB_T * 8);
            int n = 0;
            while (__byte_perm(sa.x, sc.x, 0x7632) != tag && ++n < SPIN_LIMIT) poll();
            STAMP(4);
#pragma unroll
            for (int i = 0; i < 5; i++) {
                va[i] = norm2(va[i], sa.x, sa.y); va[i] = pack_f16(bf_lo(va[i]), bf_hi(va[i]));
                vc[i] = norm2(vc[i], sc.x, sc.y); vc[i] = pack_f16(bf_lo(vc[i]), bf_hi(vc[i]));
            }
            stsm4t(a4, va[0], va[1], va[2], va[3]); stsm4t(a4 + 16, vc[0], vc[1], vc[2], vc[3]); stsm2t(a1, va[4], vc[4]);
            bar_arrive(13, 608);
            {
            const uint4 c4 = lds128(xh + cq * 12), d4_ = lds128(xh + cq * 12 + 72 * XW);
            xa[0] = c4.x; xa[1] = c4.y; xa[2] = c4.z; xa[3] = c4.w; xa[4] = lds32(xh + 64);
            xb[0] = d4_.x; xb[1] = d4_.y; xb[2] = d4_.z; xb[3] = d4_.w; xb[4] = lds32(xh + (64 + 72 * XW));
            }
        }
        STAMP(5);
        __syncwarp();
        bar_sync(15, 672);
        Af[0][0] |= lds32(sb + SM_P);
        };
        cmul(sr, si, sr, si, z1r, z1i);
        {
            const H2C h4 = splat(z4r, z4i);
            expand8(kl, kl + 512, sr, si, z1r, z1i, z2r, z2i, h4);
            cmul(sr, si, sr, si, hr, hi_);
            expand8(kl + 1024, kl + 1536, sr, si, z1r, z1i, z2r, z2i, h4);
        }
        __syncwarp();
        ldsm4t(b0, la); ldsm4t(b1, la + 256); ldsm4t(b2, la + 1024); ldsm4t(b3, la + 1280);
        cmul(z1r, z1i, z1r, z1i, hr, hi_);
        cmul(sr, si, sr, si, z1r, z1i);
        expand8(kl, kl + 512, sr, si, z2r, z2i, z4r, z4i, splat(hr, hi_));
        asm volatile("barrier.cluster.wait.aligned;" ::: "memory");
        bar_arrive(0, 672);
        ln1();
        csq(z1r, z1i, z1r, z1i);
        cmul(sr, si, sr, si, z1r, z1i);
        csq(z2r, z2i, hr, hi_);
        expand8(kl + 1024, kl + 1536, sr, si, z4r, z4i, hr, hi_, splat(z2r, z2i));
        csq(z1r, z1i, z1r, z1i);
        cmul(sr, si, sr, si, z1r, z1i);
        csq(z4r, z4i, z2r, z2i);
        expand8(kl + 2048, kl + 2560, sr, si, hr, hi_, z2r, z2i, splat(z4r, z4i));
        norm();
        {
            uint32_t c0[4], c1[4], c2[4], c3[4], e0[4], e1[4];
            float t[6][4];
            ldsm4t(c0, la); ldsm4t(c2, la + 1024);
            mma_f16_z(t[0], Af[0], b0[0], b0[1]);
            const uint32_t lb = la | (__float_as_uint(t[0][0]) & zero);
            mma_f16_z(t[1], Af[0], b2[0], b2[1]); mma_f16_z(t[2], Af[0], c0[0], c0[1]); mma_f16_z(t[3], Af[0], c2[0], c2[1]);
            ldsm4t(e0, lb + 2048); ldsm4t(c1, lb + 256); ldsm4t(c3, lb + 1280); ldsm4t(e1, lb + 2304);
            mma_f16(t[0], Af[1], b0[2], b0[3]); mma_f16(t[1], Af[1], b2[2], b2[3]); mma_f16(t[2], Af[1], c0[2], c0[3]); mma_f16(t[3], Af[1], c2[2], c2[3]);
            mma_f16(t[0], Af[2], b1[0], b1[1]); mma_f16(t[1], Af[2], b3[0], b3[1]);
            mma_f16_z(t[4], Af[0], e0[0], e0[1]); mma_f16_z(t[5], Af[1], e0[2], e0[3]);
            mma_f16(t[2], Af[2], c1[0], c1[1]); mma_f16(t[3], Af[2], c3[0], c3[1]);
            mma_f16(t[4], Af[2], e1[0], e1[1]); mma_f16(t[5], Af[3], e1[2], e1[3]);
            mma_f16(t[0], Af[3], b1[2], b1[3]); mma_f16(t[1], Af[3], b3[2], b3[3]); mma_f16(t[2], Af[3], c1[2], c1[3]); mma_f16(t[3], Af[3], c3[2], c3[3]);
#pragma unroll
            for (int i = 0; i < 4; i++) t[4][i] += t[5][i];
            stsm4(kl + 1024, pack_f16(t[0][0], t[0][1]), pack_f16(t[0][2], t[0][3]), pack_f16(t[1][0], t[1][1]), pack_f16(t[1][2], t[1][3]));
            stsm2(kl + 1536, pack_f16(t[2][0], t[2][1]), pack_f16(t[2][2], t[2][3]));
            sts64(kb + lane * 8 + 1792, pack_f16(t[3][1], t[3][0]), pack_f16(t[3][3], t[3][2]));
            sts64(kb + lane * 8 + 2048, pack_f16(t[4][1], t[4][0]), pack_f16(t[4][3], t[4][2]));
        }
        bar_sync(1 + k, 128);
        const uint2 rr = lds64(opaque(sb + SM_RK + k * 8));
        const int tq = (wq + k + 2) & 3;
        const uint32_t ra = lane * 8 + opaque(fb + (tq == 1 ? 2048 : tq * 256 + 1024));
        auto comb = [&](uint32_t a, uint32_t& x, uint32_t& y) {
            const uint2 p0 = lds64(a), p1 = lds64(a + 3072), p2 = lds64(a + 6144), p3 = lds64(a + 9216);
            x = comb4(p0.x, p1.x, p2.x, p3.x, rr.x, rr.y); y = comb4(p0.y, p1.y, p2.y, p3.y, rr.x, rr.y);
        };
        uint32_t w0, w1;
        comb(ra, w0, w1);
        const bool last = lane == 31;
        if (tq == 0) {
            uint32_t v0, v1;
            comb(ra + 256, v0, v1);
            const uint32_t n0 = __shfl_sync(~0u, lane ? w0 : v0, lane + 1);
            uint32_t n1 = __shfl_sync(~0u, v0, lane + 1);
            if (last) n1 = v1 >> 16;
            sts128(pn + 12 + lane * 16, __byte_perm(w1, w0, 0x7610), __byte_perm(w1, 0, 0x1032), __byte_perm(n0, w1, 0x7610), __byte_perm(n0, 0, 0x1032));
            sts128(pn + 524 + lane * 16, __byte_perm(v1, v0, 0x7610), __byte_perm(v1, 0, 0x1032), __byte_perm(n1, v1, 0x7610), __byte_perm(n1, 0, 0x1032));
            if (lane == 0) { sts16(pn + 4, w0); sts32(pn + 8, __byte_perm(w0, 0, 0x1032)); }
        } else if (tq == 1) {
            const uint32_t ph = pf + P_H7 + (g & 1) * (2 * P_HS) + cq * 64 + (g >> 1) * 4 + (cq & 2) * 16, sw = (cq & 2) ? 0x3210 : 0x1032;
            w0 = __byte_perm(hmul2(w0, 0x18001800u), 0, sw); w1 = __byte_perm(hmul2(w1, 0x18001800u), 0, sw);
            const uint32_t pi = ph + 32 - (cq & 2) * 32;
            put16(ph, w0); put16(pi, w0 >> 16); put16(ph + 16, w1); put16(pi + 16, w1 >> 16);
        } else if (tq == 2) {
            uint32_t n = __shfl_sync(~0u, w0, lane == 30 ? 1 : lane + 2);
            if (last) { put16(pf, hmul2(w1, 0x18001800u) >> 16); w1 = hadd2(w1, hneg2(__byte_perm(w1, 0, 0x3232))); n = 0; }
            const bool od = lane & 1;
            const uint32_t pa = pn + 1036 + (lane >> 1) * 32 + (od ? 528 : 0), pb = pa + (od ? -16 : 16);
            const uint32_t u0 = od ? w1 : w0, x0 = od ? n : w1, u1 = od ? w0 : w1, x1 = od ? w1 : n;
            const uint32_t b0 = __byte_perm(u0, 0, 0x3232), b1 = __byte_perm(u1, 0, 0x3232);
            sts128(pa, __byte_perm(u0, 0, 0x1032), b0, b0, __byte_perm(x0, u0, 0x7610));
            sts128(pb, __byte_perm(u1, 0, 0x1032), b1, b1, __byte_perm(x1, u1, 0x7610));
        } else {
            const uint32_t pa = pf + ((g & 1) ? 3 * P_GS : P_GS) + cq * 32 + (g >> 1) * 4;
            const uint32_t pb = pa + ((g & 1) ? 4 - 3 * P_GS : P_GS);
            w0 = hmul2(w0, 0x18001800u); w1 = hmul2(w1, 0x18001800u);
            put16(pa, w0 >> 16); put16(pb, w0); put16(pa + 16, w1 >> 16); put16(pb + 16, w1);
            if (last) put16(pf + P_H7 + P_HS, w1);
        }
        bar_sync(1 + k, 128);
        t258 = w0;
    }
    STAMP(6);

    mbar_wait(mb + (MB_X + k) * 8);
    STAMP(7);
    if (k < nslot) {
        const int role = (wq + k) & 3;
        const uint32_t ub = sb + SM_U + k * US + 128;
        const uint32_t l16 = lane * 16, tz = (lane & 28) - 8 * cq, tz4 = tz * 4;
        if (role) {
            const uint32_t al = cq * (2 * UP + 32) + tz4, au = opaque(ub + (3 - role) * 128), a1 = al + au, a0 = (cq ? al : al + (8 * UP - 16)) + au - 2 * UP;
            const uint4 q0 = lds128(a0), q1 = lds128(a0 + UP), q2 = lds128(a1), q3 = lds128(a1 + UP);
            const uint32_t U[16] = {q0.x, q0.y, q0.z, q0.w, q1.x, q1.y, q1.z, q1.w, q2.x, q2.y, q2.z, q2.w, q3.x, q3.y, q3.z, q3.w};
            uint32_t V[14], Q[14], R4[12], T[8];
#pragma unroll
            for (int i = 2; i < 14; i++) { V[i] = __byte_perm(U[i], U[i + 1], 0x5432); Q[i] = hadd2(U[i], V[i]); }
            const uint32_t rb = l16 + opaque(fb + (3 - role) * 512);
#pragma unroll
            for (int i = 0; i < 8; i++) T[i] = hadd2(V[5 + i], Q[6 + i]);
            sts128(rb + F_E3, T[0], T[1], T[2], T[3]); sts128(rb + F_O3 + 16, T[4], T[5], T[6], T[7]);
            asm volatile("{ .reg .pred p; setp.ne.u32 p, %10, 1; @p st.shared.v4.u32 [%0], {%2,%3,%4,%5}; @p st.shared.v4.u32 [%1], {%6,%7,%8,%9}; }"
                         :: "r"(rb + F_E2), "r"(rb + F_O2), "r"(Q[6]), "r"(Q[7]), "r"(Q[8]), "r"(Q[9]), "r"(Q[10]), "r"(Q[11]), "r"(Q[12]), "r"(Q[13]), "r"(role) : "memory");
#pragma unroll
            for (int i = 2; i < 12; i++) R4[i] = hadd2(Q[i], Q[i + 1]);
#pragma unroll
            for (int i = 0; i < 8; i++) T[i] = hadd2(R4[3 + i], U[5 + i]);
            sts128(rb + F_O5, T[0], T[1], T[2], T[3]); sts128(rb + F_E5, T[4], T[5], T[6], T[7]);
            if (role != 1) {
                uint32_t S[8];
#pragma unroll
                for (int i = 0; i < 8; i++) S[i] = hadd2(R4[2 + i], i < 7 ? T[i + 1] : hadd2(R4[11], U[13]));
                sts128(rb + F_O9, S[0], S[1], S[2], S[3]); sts128(rb + F_E9 + 16, S[4], S[5], S[6], S[7]);
#pragma unroll
                for (int i = 0; i < 8; i++) S[i] = hadd2(T[i], hadd2(V[2 + i], V[5 + i]));
                sts128(rb + F_E7, S[0], S[1], S[2], S[3]); sts128(rb + F_O7, S[4], S[5], S[6], S[7]);
            }
        } else if (lane == 0) {
            const uint4 m = lds128(ub + 23 * 16 + 7 * UP);
            const uint32_t U[6] = {lds32(ub + 23 * 16 + 6 * UP + 12), m.x, m.y, m.z, m.w, lds32(ub + 24 * 16)};
            uint32_t Q[5];
#pragma unroll
            for (int i = 0; i < 5; i++) Q[i] = hadd2(U[i], __byte_perm(U[i], U[i + 1], 0x5432));
            sts128(fb + F_O5 + 96 * 16, hadd2(hadd2(Q[0], Q[1]), U[2]), hadd2(hadd2(Q[1], Q[2]), U[3]), hadd2(hadd2(Q[2], Q[3]), U[4]), hadd2(hadd2(Q[3], Q[4]), U[5]));
            sts128(fb + F_O3, 0, 0, 0, 0); sts128(fb + F_E9, 0, 0, 0, 0);
            sts16(pn + 258 * 4, t258);
        }
        bar_sync(1 + k, 128);
        float acc[4][4];
        uint32_t Q[4][4];
        {
            const int h = role & 1, part = role >> 1;
            float fa[7][4];
            uint32_t B[3][4];
            const uint32_t po = tz + opaque(pf + part * (2 * P_GS)), ba = l16 + opaque(fb + (part == h ? 0 : F_O5 + h * 16));
#pragma unroll
            for (int s = 1; s >= 0; s--) {
#pragma unroll
                for (int i = 0; i < 3; i++) { Q[i][0] = lds32(po + (s * P_GS + i * 64)); if (i < 2) Q[i][1] = lds32(po + (s * P_GS + i * 64 + 32)); }
#pragma unroll
                for (int i = 0; i < 3; i++) ldsm4t(B[i], ba + (s * F_E3 + i * 512));
#pragma unroll
                for (int i = 0; i < 3; i++) { Q[i][3] = CP(Q[i][0]); if (i) Q[i][2] = CP(Q[i - 1][1]); }
                Q[0][2] = ZF(s ? tz : Q[0][0]); Q[2][1] = ZF(s ? l16 : Q[2][0]);
#pragma unroll
                for (int dl = 0; dl < 3; dl++)
#pragma unroll
                    for (int ap = 0; ap < 6 - dl; ap++) {
                        if (s == 1 && dl == 0) mma_f16_z(fa[ap + 1], Q[0], B[ap >> 1][2 * (ap & 1)], B[ap >> 1][2 * (ap & 1) + 1]);
                        else mma_f16(fa[ap + 1 + dl], Q[dl], B[ap >> 1][2 * (ap & 1)], B[ap >> 1][2 * (ap & 1) + 1]);
                    }
            }
#pragma unroll 1
            for (int s = role; s == 1; s++) {
                ldsm2t(B[0][0], B[0][1], fb + ((lane & 15) == 15 ? F_O5 : F_O3));
#pragma unroll
                for (int dl = 1; dl < 3; dl++) mma_f16(fa[dl], Q[dl], B[0][0], B[0][1]);
            }
            const uint32_t bh = l16 + opaque(fb + F_E7 + h * F_H + part * 2048), ph = tz + opaque(pf + P_H7 + part * (2 * P_HS));
#pragma unroll 1
            for (int s = part; s == 1; s++) {
                Q[2][1] = ZF(Q[2][3]); Q[2][2] = ZF(Q[2][2]); Q[2][0] = lds32(ph - P_HS);
                ldsm4t(B[0], bh - 1024); ldsm4t(B[1], bh - 512);
                Q[2][3] = CP(Q[2][0]);
#pragma unroll
                for (int ap = 0; ap < 4; ap++) mma_f16(fa[ap + 3], Q[2], B[ap >> 1][2 * (ap & 1)], B[ap >> 1][2 * (ap & 1) + 1]);
            }
            {
                Q[0][2] = ZF(tid);
#pragma unroll
                for (int i = 0; i < 4; i++) { Q[i][0] = lds32(ph + i * 64); Q[i][1] = lds32(ph + (i * 64 + 32)); }
                ldsm4t(B[0], bh); ldsm4t(B[1], bh + 512);
#pragma unroll
                for (int i = 0; i < 4; i++) { Q[i][3] = CP(Q[i][0]); if (i) Q[i][2] = CP(Q[i - 1][1]); }
#pragma unroll
                for (int dl = 0; dl < 4; dl++)
#pragma unroll
                    for (int ap = 0; ap < 4 - dl; ap++) mma_f16(fa[ap + 3 + dl], Q[dl], B[ap >> 1][2 * (ap & 1)], B[ap >> 1][2 * (ap & 1) + 1]);
            }
            const uint32_t da = (cq * 2048 + tz4) + opaque(fb + role * 128);
            bar_sync(1 + k, 128);
#pragma unroll
            for (int i = 1; i < 4; i++)
                stsm4(da + i * 512, pack_f16(fa[2 * i - 1][0], fa[2 * i - 1][1]), pack_f16(fa[2 * i - 1][2], fa[2 * i - 1][3]),
                      pack_f16(fa[2 * i][0], fa[2 * i][1]), pack_f16(fa[2 * i][2], fa[2 * i][3]));
            asm("shl.b32 %0, 0x6000, %1;" : "=r"(Q[0][0]) : "r"(tz4));
            Q[0][1] = ZF(Q[0][0]); Q[0][2] = ZF(tz4); Q[0][3] = CP(Q[0][0]);
            const uint32_t ra = l16 + opaque(fb + wq * 2016);
            acc[0][0] = acc[0][1] = acc[0][2] = acc[0][3] = 0.f;
            if (wq == 3) {
                const uint32_t uw = lds32(ub), kw = lds32(pf);
                const float2 uf = __half22float2(*(const __half2*)&uw);
                if ((lane | 4) == 31) acc[0][3] = (lane == 31 ? uf.x + uf.y : uf.x) * (__low2float(*(const __half2*)&kw) * 512.f);
            }
            bar_sync(1 + k, 128);
#pragma unroll
            for (int i = 1; i < 4; i++) {
                ldsm4(B[0], ra + i * 512);
                mma_f16_z(acc[i], Q[0], hadd2(B[0][0], B[0][2]), hadd2(B[0][1], B[0][3]));
            }
        }
        bar_arrive(6 + k, 160);
        STAMP(8);
        const uint32_t inv = lds32(opaque(sb + SM_SC + k * 4));
        const uint32_t yd = l16 + opaque(mapa(sb, 2 * wq) + (SM_XT + 128 + q * YP + k * YS + (k >> 2) * (q >> 1) * 16));
        {
            uint32_t pu = opaque(pn + 64 * (wq - 3));
#define pp (tz + pu)
            const uint32_t dlo = (((ub + 6 * UP) & 0x3FFFF) >> 4) | ((UP >> 4) << 16);
            uint32_t R[4][4];
            unsigned long long ds[4];
#pragma unroll
            for (int i = 0; i < 4; i++) asm volatile("mov.b64 %0, {%1, %2};" : "=l"(ds[i]) : "r"(dlo - i * (2 * UP >> 4)), "r"(8 | zero));
            auto loadQ = [&](uint32_t (&X)[4][4], uint32_t prev) {
#pragma unroll
                for (int i = 0; i < 4; i++) { X[i][0] = lds32(pp + i * 64); X[i][1] = lds32(pp + i * 64 + 32); }
                X[0][2] = CP(prev);
#pragma unroll
                for (int i = 0; i < 4; i++) { X[i][3] = CP(X[i][0]); if (i) X[i][2] = CP(X[i - 1][1]); }
                pu += 256;
            };
            auto issue = [&](uint32_t (&X)[4][4]) {
                asm volatile("wgmma.fence.sync.aligned;" ::: "memory");
#pragma unroll
                for (int i = 0; i < 4; i++) wgmma32(acc, X[i], ds[i]);
                asm volatile("wgmma.commit_group.sync.aligned;" ::: "memory");
#pragma unroll
                for (int i = 0; i < 4; i++) asm volatile("{ .reg .b32 l, h; mov.b64 {l, h}, %0; add.u32 l, l, %1; mov.b64 %0, {l, h}; }" : "+l"(ds[i]) : "r"(~zero));
            };
#pragma unroll
            for (int i = 0; i < 4; i++) {
                Q[i][0] = Q[i][1] = 0;
                if (wq + i >= 3) { Q[i][0] = lds32(pp + i * 64); Q[i][1] = lds32(pp + i * 64 + 32); }
            }
            Q[0][2] = CP(0);
#pragma unroll
            for (int i = 0; i < 4; i++) { Q[i][3] = CP(Q[i][0]); if (i) Q[i][2] = CP(Q[i - 1][1]); }
            pu += 256;
#pragma unroll 1
            for (int dl = 0; dl < 4; dl++) {
                issue(Q);
                asm volatile("wgmma.wait_group.sync.aligned 1;" ::: "memory");
                loadQ(R, Q[3][1]);
                issue(R);
                asm volatile("wgmma.wait_group.sync.aligned 1;" ::: "memory");
                loadQ(Q, R[3][1]);
            }
            issue(Q);
            asm volatile("wgmma.wait_group.sync.aligned 0;" ::: "memory");
        }
        const uint32_t pstep = mapa(sb, 1) - mapa(sb, 0), ym = mapa(mb + MB_Y * 8, 2 * wq);
#pragma unroll
        for (int e = 0; e < 2; e++)
            st_async4(yd + e * pstep, bmul2(pack_bf16(acc[0][2 * e], acc[0][2 * e + 1]), inv), bmul2(pack_bf16(acc[1][2 * e], acc[1][2 * e + 1]), inv),
                      bmul2(pack_bf16(acc[2][2 * e], acc[2][2 * e + 1]), inv), bmul2(pack_bf16(acc[3][2 * e], acc[3][2 * e + 1]), inv), ym + e * pstep);
        if (lane == 0) asm volatile("mbarrier.arrive.shared::cta.b64 _, [%0];" :: "r"(mb + MB_Y * 8) : "memory");
    }
    STAMP(9);
    uint32_t ha[5], hb[5];
    if (warp < 16) {
        const uint4 wk = lds128(sb + SM_DW + cq * 16);
        uint32_t sel[5] = {wk.x, wk.y, wk.z, wk.w, lds32(sb + SM_DW + 64 + cq * 4)}, sel2[5];
#pragma unroll
        for (int i = 0; i < 5; i++) {
            if (!(g & 1)) sel[i] = 0x3F803F80u;
            sel2[i] = sel[i]; PIN(sel2[i]);
        }
        uint32_t y4 = sb + SM_XT + 128 + warp * 32 + (2 * (lane >> 3) + (lane & 1)) * YP + ((lane & 7) >> 1) * YS;
        uint32_t y1 = sb + SM_XT + 128 + warp * 32 + (lane & 7) * YP + 4 * YS + (lane & 8) * 2 + (lane & 6) * 8;
        if (nslot != 5) {
            y1 = sb + SM_U;
            if (lane & 4) y4 = y1;
        }
        PIN(y4); PIN(y1);
        const uint32_t ao = (256 * q + tn) * 16;
        const uint32_t hta = opaque(sb + SM_HT + warp * 1024), htb = opaque(sb + SM_HT + 16384 + warp * 256);
        unsigned long long ap = (unsigned long long)((char*)g_s.acc + ao);
        asm volatile("add.u64 %0, %0, %1;" : "+l"(ap) : "l"((unsigned long long)zero));
        mbar_wait(mb + MB_Y * 8);
        STAMP(10);
        float ca[4] = {0.f, 0.f, 0.f, 0.f}, cb[4] = {0.f, 0.f, 0.f, 0.f};
        {
            uint32_t ya[4], yb[4], yc, yd;
            ldsm4t(ya, y4); ldsm4t(yb, y4 + 16); ldsm2t(yc, yd, y1);
#pragma unroll
            for (int i = 0; i < 4; i++) { ha[i] = badd2(xa[i], ya[i]); hb[i] = badd2(xb[i], yb[i]); }
            ha[4] = badd2(xa[4], yc); hb[4] = badd2(xb[4], yd);
        }
#pragma unroll
        for (int i = 0; i < 5; i++) { mma_bf16_k8(ca, ha[i], sel[i], ha[i]); mma_bf16_k8(cb, hb[i], sel2[i], hb[i]); }
        if (!(g & 1)) { ca[1] = ca[0]; cb[1] = cb[0]; }
        if (cq == (g >> 1)) {
            asm volatile("red.relaxed.gpu.global.add.v4.f32 [%0], {%1,%2,%3,%4};" :: "l"(ap), "f"(1.0f), "f"(ca[1]), "f"(ca[2]), "f"(ca[3]) : "memory");
            asm volatile("red.relaxed.gpu.global.add.v4.f32 [%0], {%1,%2,%3,%4};" :: "l"(ap + 128), "f"(1.0f), "f"(cb[1]), "f"(cb[2]), "f"(cb[3]) : "memory");
        }
        __syncwarp();
        mbar_wait(mb + MB_Y * 8);
#pragma unroll
        for (int i = 0; i < 4; i++) {
            asm volatile("or.b32 %0, %1, %2;" : "=r"(ha[i]) : "r"(ha[i]), "r"(zero));
            asm volatile("or.b32 %0, %1, %2;" : "=r"(hb[i]) : "r"(hb[i]), "r"(zero));
        }
        sts128(hta + lane * 16, ha[0], ha[1], ha[2], ha[3]); sts32(htb + lane * 4, ha[4]);
        sts128(hta + lane * 16 + 512, hb[0], hb[1], hb[2], hb[3]); sts32(htb + lane * 4 + 128, hb[4]);
        STAMP(11);
    }
    const int kq = warp / 5, mt = warp - 5 * kq;
    const int mi = lane >> 3, mr = lane & 7;
    const unsigned tk = (unsigned)tid / 72u, ck = tid - tk * 72;
    uint32_t A[9][4];
    auto loadA = [&]() {
        mbar_wait(mb + MB_W1 * 8);
        const uint32_t aa = sb + (mi & 1) * SM_WU + (8 * (mi >> 1) + mr) * 80 + (144 * 80 * kq + mt * 16);
#pragma unroll
        for (int s = 0; s < 9; s++) ldsm4t(A[s], aa + s * 1280);
    };
    const uint32_t par = (lds32(sb + SM_SC + 28) & 1) ? 0u : 0x40004000u;
    uint32_t go = (ck / 5u + ck) * 16, gs = sb + SM_SEL + 4 + (tk & 7) * 8;
    unsigned long long gb = (unsigned long long)((const char*)g_s.cand + go + (q & 1) * 92160);
    uint32_t xs = sb + SM_XS + tk * 16 + tid * 16;
    asm volatile("add.u64 %0, %0, %1;" : "+l"(gb) : "l"((unsigned long long)zero));
    PIN(xs); PIN(gs);
    auto outtile = [&]() {
        const uint2 sa = lds64(sb + SM_ST + tn * 8), sbb = lds64(sb + SM_ST + tn * 8 + 64);
#pragma unroll
        for (int i = 0; i < 5; i++) { ha[i] = badd2(ha[i], norm2(ha[i], sa.x, sa.y)); hb[i] = badd2(hb[i], norm2(hb[i], sbb.x, sbb.y)); }
        const bool hf = (c & 1) && cq == 0;
        const uint32_t o16 = sb + SM_XT + (hf ? 16384 + tn * 16 : tn * 64 + (cq - (c & 1)) * 16), o4 = sb + SM_XT + ((c & 1) ? tn * 64 + 48 : 16384 + tn * 16) + cq * 4;
        sts128(o16, ha[0], ha[1], ha[2], ha[3]); sts32(o4, ha[4]);
        sts128(o16 + (hf ? 128 : 512), hb[0], hb[1], hb[2], hb[3]); sts32(o4 + ((c & 1) ? 512 : 128), hb[4]);
    };
    if (warp < 8) {
        const float wsum = ldsf(sb + SM_SC + 24);
        const uint32_t idx = 2047 - (512 * ((tid >> 1) & 3) + 128 * ((tid >> 3) & 3) + 64 * (tid & 1) + 8 * q + warp);
        uint32_t km0 = mapa(mb + MB_KEY * 8, 2 * cq), km1 = mapa(mb + MB_KEY * 8, 2 * cq + 1), ka0 = mapa(sb + SM_RK + q * 32, 2 * cq), ka1 = mapa(sb + SM_RK + q * 32, 2 * cq + 1);
        unsigned long long c0 = (unsigned long long)((char*)g_s.cand + ((q * 8 * NCL + c) * 6 + cq) * 16), c1 = c0 + (64 - cq * 12);
        uint32_t hc = sb + SM_HT + cq * 16, h4a = sb + SM_HT + 16384 + cq * 4;
        uint32_t ca = sb + SM_KEY + warp * 128 + (warp & 1) * 32 + (lane & 28), r2a = sb + SM_KEY + cq * 16 + (cq >> 1) * 128;
        PIN(ca); PIN(r2a); PIN(km0); PIN(km1); PIN(ka0); PIN(ka1); PIN(hc); PIN(h4a);
        asm volatile("add.u64 %0, %0, %2; add.u64 %1, %1, %2;" : "+l"(c0), "+l"(c1) : "l"((unsigned long long)zero));
        uint4 s; int n = 0;
        uint32_t ox;
        do {
            s = ld_rlx128(&g_s.acc[256 * q + tid]);
            ox = __shfl_xor_sync(~0u, (lane & 1) ? s.z : s.w, 1);
        } while (__any_sync(~0u, __uint_as_float(s.x) != (float)NCL && ++n < SPIN_LIMIT));
        STAMP(16);
        const uint32_t ms = ln_stats(__uint_as_float((lane & 1) ? ox : s.z), __uint_as_float(s.y));
        const float rs = rcpf(bf_hi(ms));
        const uint32_t rb = pack_bf16(0.f, fmaf(-bf_lo(ms), wsum, __uint_as_float((lane & 1) ? s.w : ox)) * rs);
        const uint32_t key = (((rb ^ (((int)rb >> 31) | 0x80000000u)) >> 16) << 11) | idx;
        sts32(sb + SM_KEY + tid * 4, key);
        sts64(sb + SM_ST + tid * 8, ms, rsplit(rs));
        __syncwarp();
        uint32_t rank = rank4<8, 16>(sb + SM_KEY + warp * 128, key, ~zero);
        {
            const uint32_t sa = (rank * 4 ^ (warp & 1) * 32) + opaque(sb + SM_KEY + warp * 128);
            sts32(sa, key); sts32(sa + 1024, tid);
        }
        __syncwarp();
        const uint32_t mk = lds32(ca), t = lds32(ca + 1024);
        STAMP(17);
        bar_sync(12, 512);
        STAMP(18);
        const uint4 hv = lds128(hc + t * 64);
        const uint2 sv = lds64(sb + SM_ST + t * 8);
        const uint32_t h4 = lds32(h4a + t * 16);
        rank = rank4<4, 256>(r2a, mk, ~zero);
        const uint32_t rr = bmul2(sv.y, 0x3C803C80u);
        const uint32_t p0 = (norm2(hv.x, sv.x, rr) & 0xBFFFBFFFu) | par, p1 = (norm2(hv.y, sv.x, rr) & 0xBFFFBFFFu) | par, p2 = (norm2(hv.z, sv.x, rr) & 0xBFFFBFFFu) | par,
                       p3 = (norm2(hv.w, sv.x, rr) & 0xBFFFBFFFu) | par, p4 = (norm2(h4, sv.x, rr) & 0xBFFFBFFFu) | par;
        rank = quad_sum(rank);
        if (rank < 8) {
            st_async1(ka0 + rank * 4, mk, km0); st_async1(ka1 + rank * 4, mk, km1);
#pragma unroll
            for (int r = 0; r < 2; r++) {
                st_rlx128((void*)(c0 + (unsigned long long)rank * 1440 + r * 92160), p0, p1, p2, p3);
                asm volatile("st.relaxed.gpu.global.u32 [%0], %1;" :: "l"(c1 + (unsigned long long)rank * 1440 + r * 92160), "r"(p4) : "memory");
            }
        }
        __syncwarp();
    } else {
        mbar_wait(mb + MB_Y * 8); loadA();
        if (warp < 16) {
            bar_sync(12, 512);
        }
    }
    if (warp < 16) {
        outtile();
        if (warp >= 8) {
            uint32_t src = ((tid >> 2) - 64) * 1440, ma = sb + SM_RK - 256 + (tid >> 2) * 4, ra = sb + SM_RK + cq * 16;
            PIN(src); PIN(ma); PIN(ra);
            STAMP(19);
            mbar_wait(mb + MB_KEY * 8);
            STAMP(20);
            const uint32_t mk = lds32(ma);
            uint32_t rank = rank4<4, 64>(ra, mk, ~zero);
            rank = quad_sum(rank);
            sts64(sb + SM_SEL + rank * 8, mk, src);
        }
    }
    bar_sync(11, 672);
    STAMP(12);

    const char* gp = (const char*)gb + lds32(gs);
    uint4 hv = ld_rlx128(gp);
    if (warp < 8) loadA();
    uint32_t bx = sb + SM_XS + mr * 1168 + mi * 16 + 288 * kq, gd = mapa(sb, (kq & (NRED - 1)) * (8 / NRED)) + (SM_GU + (q * nslot + mt) * 128) + lane * 4;
    PIN(bx); PIN(gd);
    {
        if (warp < 18) {
            int n = 0;
            while (true) {
                sts128(xs, hv.x ^ par, hv.y ^ par, hv.z ^ par, hv.w ^ par);
                if (!__any_sync(~0u, ((hv.x ^ par) | (hv.y ^ par) | (hv.z ^ par) | (hv.w ^ par)) & 0x40004000u) || ++n >= SPIN_LIMIT) break;
                hv = ld_rlx128(gp);
            }
        }
    }
    bar_sync(14, 768);
    STAMP(13);
    float4 own;
    {
        float c0[4] = {0.f, 0.f, 0.f, 0.f}, c1[4] = {0.f, 0.f, 0.f, 0.f}, c2[4] = {0.f, 0.f, 0.f, 0.f};
        uint32_t b[5][4];
#pragma unroll
        for (int s = 0; s < 4; s++) ldsm4(b[s], bx + s * 64);
        asm volatile("ldmatrix.sync.aligned.m8n8.x2.shared.b16 {%0,%1}, [%2];" : "=r"(b[4][0]), "=r"(b[4][1]) : "r"(bx + 256) : "memory");
        mma_bf16(c0, A[0][0], A[0][1], A[0][2], A[0][3], b[0][0], b[0][1]);
        mma_bf16(c1, A[1][0], A[1][1], A[1][2], A[1][3], b[0][2], b[0][3]);
        mma_bf16(c2, A[2][0], A[2][1], A[2][2], A[2][3], b[1][0], b[1][1]);
        mma_bf16(c0, A[3][0], A[3][1], A[3][2], A[3][3], b[1][2], b[1][3]);
        mma_bf16(c1, A[4][0], A[4][1], A[4][2], A[4][3], b[2][0], b[2][1]);
        mma_bf16(c2, A[5][0], A[5][1], A[5][2], A[5][3], b[2][2], b[2][3]);
        mma_bf16(c0, A[6][0], A[6][1], A[6][2], A[6][3], b[3][0], b[3][1]);
        mma_bf16(c1, A[7][0], A[7][1], A[7][2], A[7][3], b[3][2], b[3][3]);
        mma_bf16(c2, A[8][0], A[8][1], A[8][2], A[8][3], b[4][0], b[4][1]);
        own = make_float4(c0[0] + c1[0] + c2[0], c0[1] + c1[1] + c2[1], c0[2] + c1[2] + c2[2], c0[3] + c1[3] + c2[3]);
        sts128f(sb + SM_RED + tid * 16, own.x, own.y, own.z, own.w);
    }
    if (kq < 4 - NRED) bar_arrive(1 + mt, 128); else
    bar_sync(1 + mt, 128);
    STAMP(21);
    if (mt < nslot && kq >= 4 - NRED) {
        const uint32_t ra = lane * 16 + opaque(sb + SM_RED + mt * 512);
        const float4 p0 = lds128f(ra), p1 = lds128f(ra + 2560), p2 = lds128f(lane * 16 + opaque(sb + SM_RED + mt * 512 + (5 - kq) * 2560)), p3 = own;
        const float g0 = bfr((p0.x + p1.x) + (p2.x + p3.x)), g1 = bfr((p0.y + p1.y) + (p2.y + p3.y));
        const uint32_t sg = pack_bf16(g0 * rcpf(1.f + ex2f(g0 * (-64.f * 1.4426950408889634f))), g1 * rcpf(1.f + ex2f(g1 * (-64.f * 1.4426950408889634f))));
        const uint32_t gu = bmul2(sg, pack_bf16(((p0.z + p1.z) + (p2.z + p3.z)) * 4096.f, ((p0.w + p1.w) + (p2.w + p3.w)) * 4096.f));
        const uint32_t pstep = mapa(sb, 1) - mapa(sb, 0), gm = mapa(mb + MB_GU * 8, (kq & (NRED - 1)) * (8 / NRED));
#pragma unroll
        for (int i = 0; i < 8 / NRED; i++) st_async1(gd + i * pstep, gu, gm + i * pstep);
    }
    mbar_wait(mb + MB_W2 * 8);
    {
        const uint32_t aa = sb + (8 * (mi >> 1) + mr) * 144 + (mi & 1) * 16 + (SM_FAR + 2304 * kq + mt * 32);
#pragma unroll
        for (int s = 0; s < 5; s++) ldsm4t(A[s], aa + s * FAR_SZ);
    }
    float sig; uint32_t ra2; unsigned long long fp, op;
    if (warp < 8) {
        const uint32_t key = lds32(sb + SM_SEL + warp * 8), k16 = key << 5, fj = 24 * q + lane;
        sig = bfr(rcpf(1.f + ex2f(__uint_as_float((k16 ^ (~((int)k16 >> 31) | 0x80000000u)) & 0xFFFF0000u) * -1.4426950408889634f)));
        ra2 = sb + SM_RED2 + warp * 304 + lane * 12;
        fp = (unsigned long long)(g_s.fin + warp * 192 + fj); op = (unsigned long long)(prm.out + (~key & 2047) * D_ + 3 * fj);
        PIN(ra2);
        asm volatile("add.u64 %0, %0, %3; add.u64 %1, %1, %3;" : "+l"(fp), "+l"(op), "+f"(sig) : "l"((unsigned long long)zero));
    }
    {
        uint32_t ba = sb + (SM_GU + 256 * kq) + (lane & 15) * 16 + (lane >> 4) * 1024, wa = sb + (SM_RED2 + kq * 2432 + mt * 64) + g * 4 + cq * 608;
        PIN(ba); PIN(wa);
        STAMP(22);
        mbar_wait(mb + MB_GU * 8);
        STAMP(23);
        float c0[4] = {0.f, 0.f, 0.f, 0.f}, c1[4] = {0.f, 0.f, 0.f, 0.f}, c2[4] = {0.f, 0.f, 0.f, 0.f};
        uint32_t b[2][4], b8, b9;
        ldsm4t(b[0], ba); ldsm4t(b[1], ba + 2048); ldsm2t(b8, b9, ba + 4096);
        mma_bf16(c0, A[0][0], A[0][1], A[0][2], A[0][3], b[0][0], b[0][1]);
        mma_bf16(c1, A[1][0], A[1][1], A[1][2], A[1][3], b[0][2], b[0][3]);
        if (nslot == 5) {
            mma_bf16(c2, A[4][0], A[4][1], A[4][2], A[4][3], b8, b9);
            mma_bf16(c0, A[2][0], A[2][1], A[2][2], A[2][3], b[1][0], b[1][1]);
            mma_bf16(c1, A[3][0], A[3][1], A[3][2], A[3][3], b[1][2], b[1][3]);
        }
        stsf(wa, c0[0] + c1[0] + c2[0]); stsf(wa + 304, c0[1] + c1[1] + c2[1]);
        if (mt < 4) { stsf(wa + 32, c0[2] + c1[2] + c2[2]); stsf(wa + 336, c0[3] + c1[3] + c2[3]); }
    }
    if (warp < 8) {
        float v[3];
        bar_sync(6, 640);
        STAMP(14);
        if (lane < 24) {
#pragma unroll
            for (int i = 0; i < 3; i++) v[i] = ((ldsf(ra2 + i * 4) + ldsf(ra2 + i * 4 + 2432)) + (ldsf(ra2 + i * 4 + 4864) + ldsf(ra2 + i * 4 + 7296))) * sig;
            asm volatile("{ .reg .f32 x, y, z, w; .reg .b16 a, b, c; .reg .pred p;\n"
                         "atom.relaxed.gpu.global.add.v4.f32 {x,y,z,w}, [%0], {%2,%3,%4,%5};\n"
                         "setp.eq.f32 p, w, %6; add.f32 x, x, %2; add.f32 y, y, %3; add.f32 z, z, %4;\n"
                         "cvt.rn.bf16.f32 a, x; cvt.rn.bf16.f32 b, y; cvt.rn.bf16.f32 c, z;\n"
                         "@p st.global.b16 [%1], a; @p st.global.b16 [%1 + 2], b; @p st.global.b16 [%1 + 4], c; }"
                         :: "l"(fp), "l"(op), "f"(v[0]), "f"(v[1]), "f"(v[2]), "f"(3.f), "f"(3.f * NCL) : "memory");
        }
    } else bar_arrive(6, 640);
    STAMP(15);
}

#undef pp
typedef __nv_bfloat16 bf16;
__device__ bf16 f_n[L_ * D_], f_h[L_ * D_];
__device__ float f_k[D_ * L_], f_r[L_], f_gu[8 * F_];
__device__ int f_idx[8];
__device__ __forceinline__ float b2f(bf16 v) { return __bfloat162float(v); }
__global__ void fb_ln(const bf16* in, const bf16* wr, bf16* out) {
    const int t = blockIdx.x * 8 + (threadIdx.x >> 5), lane = threadIdx.x & 31;
    const bf16* r = (in ? in : f_h) + t * D_;
    float s1 = 0.f, s2 = 0.f, s3 = 0.f;
    for (int i = lane; i < D_; i += 32) s1 += b2f(r[i]);
    for (int o = 16; o; o >>= 1) s1 += __shfl_xor_sync(~0u, s1, o);
    for (int i = lane; i < D_; i += 32) { const float d = b2f(r[i]) - s1 / D_; s2 += d * d; }
    for (int o = 16; o; o >>= 1) s2 += __shfl_xor_sync(~0u, s2, o);
    const float m = bfr(s1 / D_), sd = bfr(sqrtf(bfr(bfr(s2 / D_) + 1e-5f)));
    for (int i = lane; i < D_; i += 32) {
        const float v = bfr(bfr(b2f(r[i]) - m) / sd);
        f_n[t * D_ + i] = __float2bfloat16(v);
        if (!in) { s3 += v * b2f(wr[i]); out[t * D_ + i] = __float2bfloat16(b2f(r[i]) + v); }
    }
    for (int o = 16; o; o >>= 1) s3 += __shfl_xor_sync(~0u, s3, o);
    f_r[t] = bfr(s3);
}
__global__ void fb_taps(Params p) {
    const int d = blockIdx.x >> 3, l = (blockIdx.x & 7) * 256 + threadIdx.x;
    const float dt = bfr(expf(bf_lo(p.logdt[d]))), lf = bfr((float)l);
    float k = 0.f;
    for (int n = d * 128; n < d * 128 + 128; n++) {
        float wr, wi, sn, cs;
        cmul(wr, wi, bf_lo(p.prm6[4][n]), bf_lo(p.prm6[5][n]), dt * bf_lo(p.prm6[2][n]), dt * bf_lo(p.prm6[3][n]));
        sincosf(dt * bf_lo(p.prm6[1][n]) * lf, &sn, &cs);
        k += expf(dt * bf_lo(p.prm6[0][n]) * lf) * (wr * cs - wi * sn);
    }
    f_k[l * D_ + d] = k;
}
__global__ void fb_conv(Params p) {
    const int t = blockIdx.x, d = threadIdx.x;
    float y = 0.f;
    for (int l = 0; l <= t; l++) y += f_k[l * D_ + d] * b2f(f_n[(t - l) * D_ + d]);
    f_h[t * D_ + d] = __float2bfloat16(bf_lo(p.x[t * D_ + d]) + bfr(bfr(y) + bfr(b2f(f_n[t * D_ + d]) * bf_lo(p.dskip[d]))));
}
__global__ void fb_top() {
    const int t = blockIdx.x * 256 + threadIdx.x;
    int rank = 0;
    for (int j = 0; j < L_; j++) rank += f_r[j] > f_r[t] || (f_r[j] == f_r[t] && j < t);
    if (rank < 8) f_idx[rank] = t;
}
__global__ void fb_ffn1(const bf16* wg, const bf16* wu) {
    const int f = blockIdx.x * 256 + threadIdx.x, j = blockIdx.y;
    float g = 0.f, u = 0.f;
    for (int i = 0; i < D_; i++) { const float v = b2f(f_n[f_idx[j] * D_ + i]); g += v * b2f(wg[i * F_ + f]); u += v * b2f(wu[i * F_ + f]); }
    g = bfr(g);
    f_gu[j * F_ + f] = bfr(bfr(g / (1.f + expf(-g))) * bfr(u));
}
__global__ void fb_ffn2(const bf16* wd, bf16* out) {
    const int d = threadIdx.x, j = blockIdx.x, t = f_idx[j];
    float y = 0.f;
    for (int f = 0; f < F_; f++) y += f_gu[j * F_ + f] * b2f(wd[f * D_ + d]);
    out[t * D_ + d] = __float2bfloat16(b2f(f_h[t * D_ + d]) + bfr(b2f(f_n[t * D_ + d]) + bfr(bfr(y) * bfr(1.f / (1.f + expf(-f_r[t]))))));
}

typedef CUresult (*EncodeFn)(CUtensorMap*, CUtensorMapDataType, cuuint32_t, void*, const cuuint64_t*, const cuuint64_t*,
                             const cuuint32_t*, const cuuint32_t*, CUtensorMapInterleave, CUtensorMapSwizzle,
                             CUtensorMapL2promotion, CUtensorMapFloatOOBfill);

void make_map(EncodeFn fn, CUtensorMap* tm, const void* p, int cols, int rows, int bc, int br) {
    cuuint64_t dims[2] = {(cuuint64_t)cols, (cuuint64_t)rows};
    cuuint64_t strides[1] = {(cuuint64_t)cols * 2};
    cuuint32_t box[2] = {(cuuint32_t)bc, (cuuint32_t)br};
    cuuint32_t es[2] = {1, 1};
    fn(tm, CU_TENSOR_MAP_DATA_TYPE_BFLOAT16, 2, const_cast<void*>(p), dims, strides, box, es, CU_TENSOR_MAP_INTERLEAVE_NONE,
       CU_TENSOR_MAP_SWIZZLE_NONE, CU_TENSOR_MAP_L2_PROMOTION_L2_128B, CU_TENSOR_MAP_FLOAT_OOB_FILL_NONE);
}

void make_map3(EncodeFn fn, CUtensorMap* tm, const void* p) {
    cuuint64_t dims[5] = {(cuuint64_t)D_, 64, 2, 2, 8};
    cuuint64_t strides[4] = {(cuuint64_t)D_ * 2, (cuuint64_t)D_ * 2048, (cuuint64_t)D_ * 128, (cuuint64_t)D_ * 256};
    cuuint32_t box[5] = {XW, 9, 2, 2, 8};
    cuuint32_t es[5] = {1, 1, 1, 1, 1};
    fn(tm, CU_TENSOR_MAP_DATA_TYPE_BFLOAT16, 5, const_cast<void*>(p), dims, strides, box, es, CU_TENSOR_MAP_INTERLEAVE_NONE,
       CU_TENSOR_MAP_SWIZZLE_NONE, CU_TENSOR_MAP_L2_PROMOTION_NONE, CU_TENSOR_MAP_FLOAT_OOB_FILL_NONE);
}

void make_map5(EncodeFn fn, CUtensorMap* tm, const void* p, int bc) {
    cuuint64_t dims[5] = {(cuuint64_t)D_, 2, 4, 4, 64};
    cuuint64_t strides[4] = {(cuuint64_t)D_ * 128, (cuuint64_t)D_ * 1024, (cuuint64_t)D_ * 256, (cuuint64_t)D_ * 2};
    cuuint32_t box[5] = {(cuuint32_t)bc, 2, 4, 4, 8};
    cuuint32_t es[5] = {1, 1, 1, 1, 1};
    fn(tm, CU_TENSOR_MAP_DATA_TYPE_BFLOAT16, 5, const_cast<void*>(p), dims, strides, box, es, CU_TENSOR_MAP_INTERLEAVE_NONE,
       CU_TENSOR_MAP_SWIZZLE_NONE, CU_TENSOR_MAP_L2_PROMOTION_NONE, CU_TENSOR_MAP_FLOAT_OOB_FILL_NONE);
}

}

extern "C" void kernel_launch(void* const* d_in, const int* in_sizes, int n_in, void* d_out, int out_size) {
    (void)in_sizes; (void)n_in; (void)out_size;
    void* fp = nullptr;
    cudaDriverEntryPointQueryResult qr;
    cudaGetDriverEntryPoint("cuTensorMapEncodeTiled", &fp, cudaEnableDefault, &qr);
    EncodeFn fn = (EncodeFn)fp;
    CUtensorMap tmG, tmU, tmD, tmO, tmX, tmH;
    make_map3(fn, &tmX, d_in[0]);
    make_map(fn, &tmG, d_in[11], F_, D_, 40, 48);
    make_map(fn, &tmU, d_in[12], F_, D_, 40, 48);
    make_map(fn, &tmD, d_in[13], D_, F_, 72, 64);
    make_map5(fn, &tmO, d_out, 32);
    make_map5(fn, &tmH, d_out, 8);
    Params p;
    p.x = (const unsigned short*)d_in[0];
    for (int i = 0; i < 6; i++) p.prm6[i] = (const unsigned short*)d_in[1 + i];
    p.logdt = (const unsigned short*)d_in[7]; p.dskip = (const unsigned short*)d_in[8];
    p.wr = (const unsigned short*)d_in[10];
    p.out = (__nv_bfloat16*)d_out;
    p.zero = 0;
    cudaGetSymbolAddress((void**)&p.gs, g_s);
    cudaFuncSetAttribute(fused_kernel, cudaFuncAttributeMaxDynamicSharedMemorySize, SM_TOTAL);
    static int nclusters = -1;
    if (nclusters < 0) {
        cudaLaunchConfig_t cfg = {};
        cudaLaunchAttribute at;
        at.id = cudaLaunchAttributeClusterDimension; at.val.clusterDim.x = CS; at.val.clusterDim.y = 1; at.val.clusterDim.z = 1;
        cfg.gridDim = dim3(NCTA); cfg.blockDim = dim3(NTHR); cfg.dynamicSmemBytes = SM_TOTAL; cfg.attrs = &at; cfg.numAttrs = 1;
        if (cudaOccupancyMaxActiveClusters(&nclusters, fused_kernel, &cfg) != cudaSuccess) { (void)cudaGetLastError(); nclusters = NCL; }
    }
    if (nclusters >= NCL && !FORCE_FALLBACK) {
        fused_kernel<<<NCTA, NTHR, SM_TOTAL>>>(p, tmG, tmU, tmD, tmO, tmX, tmH);
        return;
    }
    fb_ln<<<L_ / 8, 256>>>((const bf16*)d_in[0], nullptr, nullptr);
    fb_taps<<<D_ * 8, 256>>>(p);
    fb_conv<<<L_, D_>>>(p);
    fb_ln<<<L_ / 8, 256>>>(nullptr, (const bf16*)d_in[10], p.out);
    fb_top<<<L_ / 256, 256>>>();
    fb_ffn1<<<dim3(F_ / 256, 8), 256>>>((const bf16*)d_in[11], (const bf16*)d_in[12]);
    fb_ffn2<<<8, D_>>>((const bf16*)d_in[13], p.out);
}
```

```cpp
#include <cuda_runtime.h>
#include <cuda_bf16.h>
#include <cuda_fp16.h>
#include <cuda.h>
#include <stdint.h>

namespace {

constexpr int L_ = 2048, D_ = 576, F_ = 4608;
constexpr int NCL = 15, CS = 8, NCTA = NCL * CS, NTHR = 768;
#define FORCE_FALLBACK 0
constexpr int XW = 48, NRED = 2;
constexpr int SPIN_LIMIT = 1 << 22;

constexpr int SM_WG   = 0;
constexpr int SM_WU   = 46080;
constexpr int YP = 3392, YS = 656;
constexpr int UP = 3280, US = 656;
constexpr int SM_XT   = 92160;
constexpr int SM_U    = SM_XT + 8 * YP;
constexpr int SM_FAR  = SM_U + 8 * UP;
constexpr int FAR_SZ  = 12416;
constexpr int F_E5 = 0, F_O5 = 1536, F_E3 = 3088, F_O3 = 4624, F_E7 = 6176, F_E2 = F_E7 + 1024, F_E9 = F_E7 + 2048,
              F_H = 3088, F_O7 = F_E7 + F_H, F_O2 = F_E2 + F_H, F_O9 = F_E9 + F_H;
constexpr int SM_P    = SM_FAR + 5 * FAR_SZ;
constexpr int PN_SZ = 584 * 4, SM_PN = SM_P + 65 * 4;
constexpr int P_GS = 50 * 4, P_H7 = 200 * 4, P_HS = 74 * 4;
constexpr int PF_SZ = (200 + 222) * 4, SM_PF = SM_PN + 5 * PN_SZ + 36;
constexpr int SM_MISC = SM_PF + 5 * PF_SZ;
constexpr int SM_ST   = SM_MISC;
constexpr int SM_RK   = SM_ST + 2048;
constexpr int SM_SEL  = SM_FAR + FAR_SZ + 10240;
constexpr int SM_KG   = SM_RK + 320;
constexpr int SM_SC   = SM_KG + 160;
constexpr int SM_DW   = SM_SC + 32;
constexpr int SM_MB   = SM_DW + 160;
constexpr int SM_TOTAL = SM_MB + 128;
constexpr int SM_ROW  = SM_XT - 20736;
constexpr int SM_XTL  = SM_ROW - 576 * XW;
constexpr int SM_RED2 = SM_WG;
constexpr int SM_HT   = SM_P - 512;
constexpr int SM_KEY  = SM_FAR + 10240 + 128;
constexpr int SM_CAND = SM_KEY + 1024;
constexpr int SM_XS   = SM_U;
constexpr int SM_GU   = SM_XS + 9344;
constexpr int SM_RED  = SM_GU + 5632;
static_assert(F_O9 + 1024 <= FAR_SZ && FAR_SZ % 128 == 0, "far overflow");
static_assert(SM_RED + 10240 <= SM_FAR && SM_HT + 20496 <= SM_MISC, "alias overflow");
static_assert(SM_TOTAL <= 232448, "smem overflow");
static_assert(SM_FAR % 128 == 0 && SM_XT % 128 == 0 && SM_XTL % 128 == 0 && SM_P % 16 == 0 && SM_MISC % 16 == 0 && SM_MB % 8 == 0, "align");

enum { MB_X = 0, MB_W1 = 5, MB_W2 = 6, MB_KEY = 7, MB_GU = 8, MB_Y = 9, MB_OUT = 10, MB_T = 11, MB_R = 12 };

struct __align__(128) Scratch {
    unsigned epoch, zcnt, pad[30];
    uint4  st1[L_ * 2];
    float4 acc[L_];
    uint4  cand[2 * 64 * NCL * 6];
    float4 fin[8 * 192 + 24];
};
__device__ Scratch g_s;
#define STAMP(i)

__device__ __forceinline__ uint32_t mapa(uint32_t a, uint32_t r) { uint32_t d; asm("mapa.shared::cluster.u32 %0, %1, %2;" : "=r"(d) : "r"(a), "r"(r)); return d; }
__device__ __forceinline__ void mbar_wait(uint32_t mb) {
    asm volatile("{ .reg .pred p, q; .reg .u32 n; mov.u32 n, 0;\n"
                 "W_%=: mbarrier.try_wait.parity.shared::cta.b64 p, [%0], 0; add.u32 n, n, 1; setp.lt.and.u32 q, n, 65536, !p; @q bra W_%=; }" :: "r"(mb) : "memory");
}
__device__ __forceinline__ bool elect() { uint32_t e; asm volatile("{ .reg .pred p; elect.sync _|p, 0xffffffff; selp.u32 %0, 1, 0, p; }" : "=r"(e)); return e; }
__device__ __forceinline__ void arm(uint32_t mb, uint32_t bytes) { asm volatile("mbarrier.arrive.expect_tx.shared::cta.b64 _, [%0], %1;" :: "r"(mb), "r"(bytes) : "memory"); }
__device__ __forceinline__ void bar_sync(int id, int n) { asm volatile("bar.sync %0, %1;" :: "r"(id), "r"(n) : "memory"); }
__device__ __forceinline__ void bar_arrive(int id, int n) { asm volatile("bar.arrive %0, %1;" :: "r"(id), "r"(n) : "memory"); }
__device__ __forceinline__ uint32_t lds16(uint32_t a) { unsigned short v; asm volatile("ld.shared.u16 %0, [%1];" : "=h"(v) : "r"(a) : "memory"); return v; }
__device__ __forceinline__ uint32_t lds32(uint32_t a) { uint32_t v; asm volatile("ld.shared.u32 %0, [%1];" : "=r"(v) : "r"(a) : "memory"); return v; }
__device__ __forceinline__ uint2 lds64(uint32_t a) { uint2 v; asm volatile("ld.shared.v2.u32 {%0,%1}, [%2];" : "=r"(v.x), "=r"(v.y) : "r"(a) : "memory"); return v; }
__device__ __forceinline__ float ldsf(uint32_t a) { float v; asm volatile("ld.shared.f32 %0, [%1];" : "=f"(v) : "r"(a) : "memory"); return v; }
__device__ __forceinline__ uint4 lds128(uint32_t a) { uint4 v; asm volatile("ld.shared.v4.u32 {%0,%1,%2,%3}, [%4];" : "=r"(v.x), "=r"(v.y), "=r"(v.z), "=r"(v.w) : "r"(a) : "memory"); return v; }
__device__ __forceinline__ float4 lds128f(uint32_t a) { float4 v; asm volatile("ld.shared.v4.f32 {%0,%1,%2,%3}, [%4];" : "=f"(v.x), "=f"(v.y), "=f"(v.z), "=f"(v.w) : "r"(a) : "memory"); return v; }
__device__ __forceinline__ void sts16(uint32_t a, uint32_t v) { asm volatile("{ .reg .b16 l, h; mov.b32 {l, h}, %1; st.shared.b16 [%0], l; }" :: "r"(a), "r"(v) : "memory"); }
__device__ __forceinline__ void sts32(uint32_t a, uint32_t v) { asm volatile("st.shared.u32 [%0], %1;" :: "r"(a), "r"(v) : "memory"); }
__device__ __forceinline__ void sts64(uint32_t a, uint32_t x, uint32_t y) { asm volatile("st.shared.v2.u32 [%0], {%1,%2};" :: "r"(a), "r"(x), "r"(y) : "memory"); }
__device__ __forceinline__ void stsf(uint32_t a, float v) { asm volatile("st.shared.f32 [%0], %1;" :: "r"(a), "f"(v) : "memory"); }
__device__ __forceinline__ void sts128(uint32_t a, uint32_t x, uint32_t y, uint32_t z, uint32_t w) { asm volatile("st.shared.v4.u32 [%0], {%1,%2,%3,%4};" :: "r"(a), "r"(x), "r"(y), "r"(z), "r"(w) : "memory"); }
__device__ __forceinline__ void sts128f(uint32_t a, float x, float y, float z, float w) { asm volatile("st.shared.v4.f32 [%0], {%1,%2,%3,%4};" :: "r"(a), "f"(x), "f"(y), "f"(z), "f"(w) : "memory"); }
__device__ __forceinline__ void ldsm4(uint32_t (&r)[4], uint32_t a) { asm volatile("ldmatrix.sync.aligned.m8n8.x4.shared.b16 {%0,%1,%2,%3}, [%4];" : "=r"(r[0]), "=r"(r[1]), "=r"(r[2]), "=r"(r[3]) : "r"(a) : "memory"); }
__device__ __forceinline__ void ldsm4t(uint32_t (&r)[4], uint32_t a) { asm volatile("ldmatrix.sync.aligned.m8n8.x4.trans.shared.b16 {%0,%1,%2,%3}, [%4];" : "=r"(r[0]), "=r"(r[1]), "=r"(r[2]), "=r"(r[3]) : "r"(a) : "memory"); }
__device__ __forceinline__ void ldsm2t(uint32_t& r0, uint32_t& r1, uint32_t a) { asm volatile("ldmatrix.sync.aligned.m8n8.x2.trans.shared.b16 {%0,%1}, [%2];" : "=r"(r0), "=r"(r1) : "r"(a) : "memory"); }
__device__ __forceinline__ void stsm4t(uint32_t a, uint32_t r0, uint32_t r1, uint32_t r2, uint32_t r3) { asm volatile("stmatrix.sync.aligned.m8n8.x4.trans.shared.b16 [%0], {%1,%2,%3,%4};" :: "r"(a), "r"(r0), "r"(r1), "r"(r2), "r"(r3) : "memory"); }
__device__ __forceinline__ void stsm4(uint32_t a, uint32_t r0, uint32_t r1, uint32_t r2, uint32_t r3) { asm volatile("stmatrix.sync.aligned.m8n8.x4.shared.b16 [%0], {%1,%2,%3,%4};" :: "r"(a), "r"(r0), "r"(r1), "r"(r2), "r"(r3) : "memory"); }
__device__ __forceinline__ void stsm2(uint32_t a, uint32_t r0, uint32_t r1) { asm volatile("stmatrix.sync.aligned.m8n8.x2.shared.b16 [%0], {%1,%2};" :: "r"(a), "r"(r0), "r"(r1) : "memory"); }
__device__ __forceinline__ void stsm2t(uint32_t a, uint32_t r0, uint32_t r1) { asm volatile("stmatrix.sync.aligned.m8n8.x2.trans.shared.b16 [%0], {%1,%2};" :: "r"(a), "r"(r0), "r"(r1) : "memory"); }
__device__ __forceinline__ uint4 ldg128(const void* p) { uint4 v; asm volatile("ld.global.nc.v4.u32 {%0,%1,%2,%3}, [%4];" : "=r"(v.x), "=r"(v.y), "=r"(v.z), "=r"(v.w) : "l"(p)); return v; }
__device__ __forceinline__ uint32_t ldg16(const void* p) { unsigned short v; asm volatile("ld.global.nc.u16 %0, [%1];" : "=h"(v) : "l"(p)); return v; }
__device__ __forceinline__ uint32_t opaque(uint32_t v) { uint32_t r; asm volatile("mov.b32 %0, %1;" : "=r"(r) : "r"(v)); return r; }
__device__ __forceinline__ void mma_f16(float (&d)[4], const uint32_t (&a)[4], uint32_t b0, uint32_t b1) {
    asm volatile("mma.sync.aligned.m16n8k16.row.col.f32.f16.f16.f32 {%0,%1,%2,%3}, {%4,%5,%6,%7}, {%8,%9}, {%0,%1,%2,%3};"
        : "+f"(d[0]), "+f"(d[1]), "+f"(d[2]), "+f"(d[3]) : "r"(a[0]), "r"(a[1]), "r"(a[2]), "r"(a[3]), "r"(b0), "r"(b1));
}
__device__ __forceinline__ void mma_f16_z(float (&d)[4], const uint32_t (&a)[4], uint32_t b0, uint32_t b1) {
    asm volatile("mma.sync.aligned.m16n8k16.row.col.f32.f16.f16.f32 {%0,%1,%2,%3}, {%4,%5,%6,%7}, {%8,%9}, {%10,%10,%10,%10};"
        : "=f"(d[0]), "=f"(d[1]), "=f"(d[2]), "=f"(d[3]) : "r"(a[0]), "r"(a[1]), "r"(a[2]), "r"(a[3]), "r"(b0), "r"(b1), "f"(0.f));
}
__device__ __forceinline__ void mma_bf16(float (&d)[4], uint32_t a0, uint32_t a1, uint32_t a2, uint32_t a3, uint32_t b0, uint32_t b1) {
    asm volatile("mma.sync.aligned.m16n8k16.row.col.f32.bf16.bf16.f32 {%0,%1,%2,%3}, {%4,%5,%6,%7}, {%8,%9}, {%0,%1,%2,%3};"
        : "+f"(d[0]), "+f"(d[1]), "+f"(d[2]), "+f"(d[3]) : "r"(a0), "r"(a1), "r"(a2), "r"(a3), "r"(b0), "r"(b1));
}
__device__ __forceinline__ void mma_bf16_k8(float (&d)[4], uint32_t a0, uint32_t a1, uint32_t b0) {
    asm volatile("mma.sync.aligned.m16n8k8.row.col.f32.bf16.bf16.f32 {%0,%1,%2,%3}, {%4,%5}, {%6}, {%0,%1,%2,%3};"
        : "+f"(d[0]), "+f"(d[1]), "+f"(d[2]), "+f"(d[3]) : "r"(a0), "r"(a1), "r"(b0));
}
__device__ __forceinline__ uint32_t pack_f16(float lo, float hi) { uint32_t r; asm("cvt.rn.f16x2.f32 %0, %1, %2;" : "=r"(r) : "f"(hi), "f"(lo)); return r; }
__device__ __forceinline__ uint32_t pack_bf16(float lo, float hi) { uint32_t r; asm("cvt.rn.bf16x2.f32 %0, %1, %2;" : "=r"(r) : "f"(hi), "f"(lo)); return r; }
__device__ __forceinline__ float bf_lo(uint32_t v) { return __uint_as_float(v << 16); }
__device__ __forceinline__ float bf_hi(uint32_t v) { return __uint_as_float(v & 0xFFFF0000u); }
__device__ __forceinline__ float bfr(float x) { return __uint_as_float(pack_bf16(0.f, x)); }
__device__ __forceinline__ uint32_t badd2(uint32_t a, uint32_t b) { uint32_t r; asm("add.rn.bf16x2 %0, %1, %2;" : "=r"(r) : "r"(a), "r"(b)); return r; }
__device__ __forceinline__ uint32_t bmul2(uint32_t a, uint32_t b) { uint32_t r; asm("mul.rn.bf16x2 %0, %1, %2;" : "=r"(r) : "r"(a), "r"(b)); return r; }
__device__ __forceinline__ uint32_t hadd2(uint32_t a, uint32_t b) { uint32_t r; asm("add.rn.f16x2 %0, %1, %2;" : "=r"(r) : "r"(a), "r"(b)); return r; }
__device__ __forceinline__ uint32_t hmul2(uint32_t a, uint32_t b) { uint32_t r; asm("mul.rn.f16x2 %0, %1, %2;" : "=r"(r) : "r"(a), "r"(b)); return r; }
__device__ __forceinline__ uint32_t hneg2(uint32_t a) { uint32_t r; asm("neg.f16x2 %0, %1;" : "=r"(r) : "r"(a)); return r; }
__device__ __forceinline__ float rcpf(float x) { float r; asm("rcp.approx.ftz.f32 %0, %1;" : "=f"(r) : "f"(x)); return r; }
__device__ __forceinline__ float sqrta(float x) { float r; asm("sqrt.approx.ftz.f32 %0, %1;" : "=f"(r) : "f"(x)); return r; }
__device__ __forceinline__ float ex2f(float x) { float r; asm("ex2.approx.ftz.f32 %0, %1;" : "=f"(r) : "f"(x)); return r; }
__device__ __forceinline__ void st_async4(uint32_t a, uint32_t x, uint32_t y, uint32_t z, uint32_t w, uint32_t mb) {
    asm volatile("st.async.shared::cluster.mbarrier::complete_tx::bytes.v4.u32 [%0], {%1,%2,%3,%4}, [%5];" :: "r"(a), "r"(x), "r"(y), "r"(z), "r"(w), "r"(mb) : "memory"); }
__device__ __forceinline__ void st_async1(uint32_t a, uint32_t x, uint32_t mb) {
    asm volatile("st.async.shared::cluster.mbarrier::complete_tx::bytes.u32 [%0], %1, [%2];" :: "r"(a), "r"(x), "r"(mb) : "memory"); }
__device__ __forceinline__ unsigned ld_rlx(const void* p) { unsigned v; asm volatile("ld.relaxed.gpu.global.u32 %0, [%1];" : "=r"(v) : "l"(p) : "memory"); return v; }
__device__ __forceinline__ unsigned ld_acq(const void* p) { unsigned v; asm volatile("ld.acquire.gpu.global.u32 %0, [%1];" : "=r"(v) : "l"(p) : "memory"); return v; }
__device__ __forceinline__ uint2 ld_rlx64(const void* p) { unsigned long long v; asm volatile("ld.relaxed.gpu.global.u64 %0, [%1];" : "=l"(v) : "l"(p) : "memory"); return make_uint2((unsigned)v, (unsigned)(v >> 32)); }
__device__ __forceinline__ void st_rlx128(void* p, uint32_t x, uint32_t y, uint32_t z, uint32_t w) {
    asm volatile("st.relaxed.gpu.global.v2.u64 [%0], {%1,%2};" :: "l"(p), "l"((unsigned long long)x | ((unsigned long long)y << 32)), "l"((unsigned long long)z | ((unsigned long long)w << 32)) : "memory"); }
__device__ __forceinline__ uint4 ld_rlx128(const void* p) { unsigned long long a, b; asm volatile("ld.relaxed.gpu.global.v2.u64 {%0,%1}, [%2];" : "=l"(a), "=l"(b) : "l"(p) : "memory"); return make_uint4((unsigned)a, (unsigned)(a >> 32), (unsigned)b, (unsigned)(b >> 32)); }
__device__ __forceinline__ void tma2d(uint32_t dst, const CUtensorMap* tm, int x, int y, uint32_t mb) {
    asm volatile("cp.async.bulk.tensor.2d.shared::cluster.global.mbarrier::complete_tx::bytes [%0], [%1, {%3, %4}], [%2];"
                 :: "r"(dst), "l"(tm), "r"(mb), "r"(x), "r"(y) : "memory");
}
__device__ __forceinline__ void cmul(float& xr, float& xi, float ar, float ai, float br, float bi) {
    const float r = fmaf(ar, br, -ai * bi), i = fmaf(ar, bi, ai * br); xr = r; xi = i;
}
__device__ __forceinline__ void csq(float& xr, float& xi, float ar, float ai) {
    const float r = fmaf(ar, ar, -ai * ai), i = (ar + ar) * ai; xr = r; xi = i;
}
__device__ __forceinline__ void cexp_s(float& zr, float& zi, float e2, float turns) {
    const float mag = ex2f(e2), r = (turns - rintf(turns)) * 6.283185307179586f;
    zr = mag * __cosf(r); zi = mag * __sinf(r);
}
__device__ __forceinline__ uint32_t ln_stats(float s1, float s2) {
    const float m = s1 * (1.f / D_);
    const float var = fmaxf(fmaf(s2, 1.f / D_, -m * m), 0.f);
    return pack_bf16(m, sqrta(bfr(bfr(var) + 1e-5f)));
}
__device__ __forceinline__ uint32_t rsplit(float rs) { const float h = bfr(rs); return pack_bf16(h, rs - h); }
__device__ __forceinline__ uint32_t norm2(uint32_t v, uint32_t mx, uint32_t hl) {
    uint32_t r;
    asm("{ .reg .b16 m, h, l, x; .reg .b32 m2, h2, l2, d, t; mov.b32 {m, x}, %2; mov.b32 {h, l}, %3; mov.b32 m2, {m, m}; mov.b32 h2, {h, h}; mov.b32 l2, {l, l};\n"
        "sub.rn.bf16x2 d, %1, m2; mul.rn.bf16x2 t, d, l2; fma.rn.bf16x2 %0, d, h2, t; }" : "=r"(r) : "r"(v), "r"(mx), "r"(hl));
    return r;
}
template <int N, int S>
__device__ __forceinline__ uint32_t rank4(uint32_t a, uint32_t key, uint32_t m1) {
    uint32_t r0 = 0, r1 = 0, r2 = 0, r3 = 0;
#pragma unroll
    for (int i = 0; i < N; i++) {
        const uint4 o = lds128(a + i * S);
        r0 += (o.x * m1 + key) >> 31; r1 += (o.y * m1 + key) >> 31; r2 += (o.z * m1 + key) >> 31; r3 += (o.w * m1 + key) >> 31;
    }
    return (r0 + r1) + (r2 + r3);
}
__device__ __forceinline__ uint32_t quad_sum(uint32_t r) {
    const uint32_t a = __shfl_xor_sync(~0u, r, 1), b = __shfl_xor_sync(~0u, r, 2), c = __shfl_xor_sync(~0u, r, 3);
    return (r + a) + b + c;
}
typedef uint32_t H2C;
__device__ __forceinline__ H2C splat(float r, float i) { return pack_f16(r, i); }
__device__ __forceinline__ void hcmul(uint32_t& xr, uint32_t& xi, uint32_t R, uint32_t I, H2C m) {
    asm("{ .reg .b16 a, b; .reg .b32 a2, b2, t; mov.b32 {a, b}, %4; mov.b32 a2, {a, a}; mov.b32 b2, {b, b};\n"
        "mul.rn.f16x2 t, %3, b2; neg.f16x2 t, t; fma.rn.f16x2 %0, %2, a2, t; mul.rn.f16x2 t, %3, a2; fma.rn.f16x2 %1, %2, b2, t; }"
        : "=&r"(xr), "=r"(xi) : "r"(R), "r"(I), "r"(m));
}
__device__ __forceinline__ void expand4(uint32_t are, uint32_t aim, uint32_t R0, uint32_t R1, uint32_t I0, uint32_t I1, H2C m4) {
    uint32_t R2, I2, R3, I3;
    hcmul(R2, I2, R0, I0, m4); hcmul(R3, I3, R1, I1, m4);
    sts128(are, R0, R1, R2, R3);
    sts128(aim, I0, I1, I2, I3);
}
__device__ __forceinline__ void expand8(uint32_t are, uint32_t aim, float sr, float si, float m1r, float m1i, float m2r, float m2i, H2C m4) {
    float r1, i1, r2, i2, r3, i3;
    cmul(r1, i1, sr, si, m1r, m1i); cmul(r2, i2, sr, si, m2r, m2i); cmul(r3, i3, r1, i1, m2r, m2i);
    expand4(are, aim, pack_f16(sr, r1), pack_f16(r2, r3), pack_f16(si, i1), pack_f16(i2, i3), m4);
}
__device__ __forceinline__ uint32_t comb4(uint32_t a, uint32_t b, uint32_t c, uint32_t d, uint32_t r01, uint32_t r23) {
    uint32_t x;
    asm("{ .reg .b16 h0, h1, h2, h3; .reg .b32 m0, m1, m2, m3, u, v; mov.b32 {h0, h1}, %5; mov.b32 {h2, h3}, %6;\n"
        "mov.b32 m0, {h0, h0}; mov.b32 m1, {h1, h1}; mov.b32 m2, {h2, h2}; mov.b32 m3, {h3, h3};\n"
        "mul.rn.f16x2 u, %2, m1; fma.rn.f16x2 u, %1, m0, u; mul.rn.f16x2 v, %4, m3; fma.rn.f16x2 v, %3, m2, v; add.rn.f16x2 %0, u, v; }"
        : "=r"(x) : "r"(a), "r"(b), "r"(c), "r"(d), "r"(r01), "r"(r23));
    return x;
}
__device__ __forceinline__ void put16(uint32_t a, uint32_t v) { sts16(a, v); sts16(a + 6, v); }

struct Params {
    const unsigned short *logdt, *dskip, *prm6[6], *x, *wr;
    __nv_bfloat16* out;
    Scratch* gs;
    unsigned zero;
};
__device__ __forceinline__ uint32_t tslot(uint32_t t) { return (t & 7) * 32 + ((t >> 4) & 24) + ((t >> 8) & 6) + ((t >> 6) & 1); }
#define CP(x) ((x) | zero)
#define ZF(x) ((x) & zero)
#define PIN(x) asm volatile("or.b32 %0, %0, %1;" : "+r"(x) : "r"(zero))
__device__ __forceinline__ void wgmma32(float (&d)[4][4], const uint32_t (&a)[4], unsigned long long ds) {
    asm volatile("wgmma.mma_async.sync.aligned.m64n32k16.f32.f16.f16 {%0,%1,%2,%3,%4,%5,%6,%7,%8,%9,%10,%11,%12,%13,%14,%15}, {%16,%17,%18,%19}, %20, 1, 1, 1, 0;"
        : "+f"(d[0][0]), "+f"(d[0][1]), "+f"(d[0][2]), "+f"(d[0][3]), "+f"(d[1][0]), "+f"(d[1][1]), "+f"(d[1][2]), "+f"(d[1][3]),
          "+f"(d[2][0]), "+f"(d[2][1]), "+f"(d[2][2]), "+f"(d[2][3]), "+f"(d[3][0]), "+f"(d[3][1]), "+f"(d[3][2]), "+f"(d[3][3])
        : "r"(a[0]), "r"(a[1]), "r"(a[2]), "r"(a[3]), "l"(ds));
}

__device__ __forceinline__ void finish(const Params& prm, uint32_t fo, uint32_t oo, const float (&v)[3], float cnt) {
    float x, y, z, w;
    asm volatile("atom.relaxed.gpu.global.add.v4.f32 {%0,%1,%2,%3}, [%4], {%5,%6,%7,%8};" : "=f"(x), "=f"(y), "=f"(z), "=f"(w)
                 : "l"((char*)prm.gs->fin + fo), "f"(v[0]), "f"(v[1]), "f"(v[2]), "f"(cnt) : "memory");
    if (w + cnt == 3.f * (NCL + 1)) {
        __nv_bfloat16* op = (__nv_bfloat16*)((char*)prm.out + oo);
        op[0] = __float2bfloat16(x + v[0]); op[1] = __float2bfloat16(y + v[1]); op[2] = __float2bfloat16(z + v[2]);
    }
}

__global__ void __cluster_dims__(CS, 1, 1) __launch_bounds__(NTHR, 1)
fused_kernel(const __grid_constant__ Params prm, const __grid_constant__ CUtensorMap tmG, const __grid_constant__ CUtensorMap tmU,
             const __grid_constant__ CUtensorMap tmD, const __grid_constant__ CUtensorMap tmO, const __grid_constant__ CUtensorMap tmX, const __grid_constant__ CUtensorMap tmH)
{
    extern __shared__ __align__(1024) unsigned char smem[];
    const int tid = threadIdx.x, lane = tid & 31, warp = __shfl_sync(~0u, tid >> 5, 0);
    const int c = blockIdx.x >> 3, q = blockIdx.x & 7;
    const int nslot = (c < NCL - 1) ? 5 : 2;
    const int d0 = 40 * c;
    const uint32_t sb = opaque((uint32_t)__cvta_generic_to_shared(smem));
    const uint32_t mb = sb + SM_MB;
    Scratch& g_s = *prm.gs;
    const unsigned& zero = prm.zero;
    const uint32_t dch2 = min(d0 + q + ((tid >> 4) & ~7), D_ - 1) * 2;
    uint32_t pv[6], pLdt;
    const uint32_t pofs = opaque(dch2 * 128 + (tid & 127) * 2);
    pLdt = ldg16((const char*)prm.logdt + dch2);
#pragma unroll
    for (int i = 0; i < 2; i++) pv[i] = ldg16((const char*)prm.prm6[i] + pofs);
    STAMP(0);

    if (warp >= 20) {
        unsigned epoch = 0;
        if (warp == 20) {
            if (lane == 0) {
#pragma unroll
                for (int i = 0; i < 13; i++)
                    asm volatile("mbarrier.init.shared::cta.b64 [%0], %1;" :: "r"(mb + i * 8), "r"((i == MB_R || i < 2) ? 2 : i < 5 ? (nslot + 1) / 3 : i == MB_Y ? 1 + 4 * nslot : 1) : "memory");
                asm volatile("fence.mbarrier_init.release.cluster;" ::: "memory");
                arm(mb + MB_W1 * 8, 92160); arm(mb + MB_W2 * 8, nslot * 9216); arm(mb + MB_KEY * 8, 256); arm(mb + MB_GU * 8, nslot * 1024); arm(mb + MB_T * 8, 576 * XW);
                const int bytes = max(min(18, L_ - 18 * (int)blockIdx.x), 1) * (D_ * 2);
                arm(mb + MB_R * 8, bytes);
            }
            __syncwarp();
        } else if (warp == 22) {
            epoch = ld_rlx(&g_s.epoch);
            if (lane < 18 ? 18 * c + lane < 256 : lane < 31) (lane < 18 ? &g_s.acc[256 * q + 18 * c] : &g_s.fin[13 * (int)blockIdx.x - 18])[lane] = make_float4(0.f, 0.f, 0.f, 0.f);
        } else if (warp == 23 && lane == 0) asm volatile("prefetch.tensormap [%0];" :: "l"(&tmX) : "memory");
        asm volatile("barrier.cluster.arrive.relaxed.aligned;" ::: "memory");
        bar_sync(12, NTHR);
        uint4 wv = make_uint4(0, 0, 0, 0), wv2, wv3;
        if (warp == 22) {
            if (lane == 0) { sts32(sb + SM_SC + 28, epoch); asm volatile("mbarrier.arrive.shared::cta.b64 _, [%0];" :: "r"(mb + MB_R * 8) : "memory"); }
            epoch++;
            asm volatile("fence.acq_rel.gpu;" ::: "memory");
            __syncwarp();
            if (lane == 0) asm volatile("red.relaxed.gpu.global.add.u32 [%0], 1;" :: "l"(&g_s.zcnt) : "memory");
            STAMP(1);
            wv2 = ldg128((const uint4*)prm.wr + lane); wv3 = ldg128((const uint4*)prm.wr + 32 + lane);
            if (lane < 8) wv = ldg128((const uint4*)prm.wr + 64 + lane);
            if (lane < 5) {
                uint4 v = make_uint4(0, 0, 0, 0);
                if (lane < nslot) v = ldg128((const uint4*)(prm.wr + d0) + lane);
                sts128(sb + SM_DW + lane * 16, v.x, v.y, v.z, v.w);
            }
            __syncwarp();
            if (lane < 5) asm volatile("mbarrier.arrive.shared::cta.b64 _, [%0];" :: "r"(mb + (MB_X + lane) * 8) : "memory");
        }
        if (warp == 21) {
            if (lane == 0) { asm volatile("prefetch.tensormap [%0];" :: "l"(&tmG) : "memory"); asm volatile("prefetch.tensormap [%0];" :: "l"(&tmU) : "memory"); asm volatile("prefetch.tensormap [%0];" :: "l"(&tmD) : "memory"); }
            __syncwarp();
            const float dsk = bf_lo(ldg16(prm.dskip + min(d0 + 2 * (lane & 28) + q, D_ - 1)));
            bar_sync(0, 672);
            {
                const uint2 m = lds64(sb + SM_KG + min(lane, 19) * 8);
                unsigned Em = max(m.x, __shfl_xor_sync(~0u, m.x, 1));
                Em = max(Em, __shfl_xor_sync(~0u, Em, 2));
                Em = max(Em, min(__float_as_uint(fabsf(dsk) * (1.f / 8192.f)) >> 23, 253u));
                const float f = __uint_as_float(max((int)(127 + m.x - Em), 0) << 23);
                float s0 = (float)(int)m.y * f;
                s0 += __shfl_xor_sync(~0u, s0, 1); s0 += __shfl_xor_sync(~0u, s0, 2);
                if (lane < 20) {
                    sts16(sb + SM_RK + lane * 2, pack_f16(f, 0.f));
                    sts32(sb + SM_SC + (lane & 28), Em * 0x00800080u);
                    put16(sb + SM_PN + (lane >> 2) * PN_SZ, pack_f16(s0 * (1.f / 16777216.f) + dsk * __uint_as_float((254u - Em) << 23), 0.f));
                }
                __syncwarp();
            }
            bar_sync(15, 672);
            asm volatile("fence.proxy.async.shared::cta;" ::: "memory");
#pragma unroll 1
            for (int i = 0; i < 24; i++) {
                if (lane == 0) tma2d(sb + SM_WG + i * 3840, i < 12 ? &tmG : &tmU, 320 * c + 8 * nslot * q, 48 * (i < 12 ? i : i - 12), mb + MB_W1 * 8);
            }
            STAMP(1);
        } else {
        if (warp == 20) {
            if (elect()) {
                asm volatile("cp.async.bulk.shared::cluster.global.mbarrier::complete_tx::bytes [%0], [%1], %2, [%3];"
                             :: "r"(sb + SM_ROW), "l"(prm.x + min(18 * (int)blockIdx.x, L_ - 1) * D_), "r"(max(min(18, L_ - 18 * (int)blockIdx.x), 1) * (D_ * 2)), "r"(mb + MB_R * 8) : "memory");
            }
            __syncwarp();
            {
                const long long t0 = clock64();
                uint32_t ok;
                do {
                    asm volatile("{ .reg .pred p; mbarrier.test_wait.parity.shared::cta.b64 p, [%1], 0; selp.u32 %0, 1, 0, p; }" : "=r"(ok) : "r"(mb + MB_R * 8) : "memory");
                    __nanosleep(20);
                } while (!ok && clock64() - t0 < 1700);
                __syncwarp();
            }
            if (elect()) {
                asm volatile("cp.async.bulk.tensor.5d.shared::cluster.global.mbarrier::complete_tx::bytes [%0], [%1, {%3, %4, %5, %5, %5}], [%2];"
                             :: "r"(sb + SM_XTL), "l"(&tmX), "r"(mb + MB_T * 8), "r"(d0 & ~15), "r"(8 * q), "r"(0) : "memory");
            }
            STAMP(6);
        }
        {
            const int idx = lane * 3 + max(warp - 21, 0), sl = nslot - 1 - (idx >> 3), pe = (idx + q + 1) & 7;
            const uint32_t rb_ = mapa(sb, pe);
            uint32_t cd = rb_ + SM_U + 128 + q * UP + sl * US, cs = sb + SM_XT + 128 + (q & 3) * 16 + pe * YP + sl * YS, cm = rb_ + SM_MB + (MB_X + sl) * 8;
            int act = sl < 0 ? 0 : pe == q ? -1 : 1;
            PIN(cd); PIN(cs); PIN(cm); PIN(act);
            asm volatile("barrier.cluster.wait.aligned;" ::: "memory");
            mbar_wait(mb + MB_R * 8);
            bar_sync(13, 608);
            asm volatile("fence.proxy.async.shared::cta;" ::: "memory");
            if (act < 0) arm(cm, 7 * 512);
            __syncwarp();
            if (act > 0)
                asm volatile("cp.async.bulk.shared::cluster.shared::cta.mbarrier::complete_tx::bytes [%0], [%1], 512, [%2];" :: "r"(cd), "r"(cs), "r"(cm) : "memory");
        }
        STAMP(1);
        if (warp == 20 && lane == 0) { asm volatile("prefetch.tensormap [%0];" :: "l"(&tmO) : "memory"); asm volatile("prefetch.tensormap [%0];" :: "l"(&tmH) : "memory"); }
        if (warp == 22) {
            __syncwarp();
            mbar_wait(mb + (MB_X + 1) * 8);
            const uint32_t old = (epoch & 1) ? 0u : 0x40004000u;
#pragma unroll
            for (int t = 0; t < 2; t++)
#pragma unroll
                for (int r = 0; r < 2; r++)
                    if ((lane & 7) < 6) g_s.cand[r * (64 * NCL * 6) + ((q * 8 + 4 * t + (lane >> 3)) * NCL + c) * 6 + (lane & 7)] = make_uint4(old, old, old, old);
            float a[4] = {0.f, 0.f, 0.f, 0.f};
            const uint32_t one = 0x3F803F80u;
            mma_bf16(a, one, one, one, one, wv.x, wv.y);  mma_bf16(a, one, one, one, one, wv.z, wv.w);
            mma_bf16(a, one, one, one, one, wv2.x, wv2.y); mma_bf16(a, one, one, one, one, wv2.z, wv2.w);
            mma_bf16(a, one, one, one, one, wv3.x, wv3.y); mma_bf16(a, one, one, one, one, wv3.z, wv3.w);
            float s = a[0] + a[1];
            s += __shfl_xor_sync(~0u, s, 1); s += __shfl_xor_sync(~0u, s, 2);
            stsf(sb + SM_SC + 24, s);
            __syncwarp();
            if (lane == 0) {
                int n = 0;
                while ((int)(ld_acq(&g_s.zcnt) - epoch * NCTA) < 0 && ++n < SPIN_LIMIT) __nanosleep(200);
                arm(mb + MB_Y * 8, 8 * 512 * nslot);
                if (blockIdx.x == 0) g_s.epoch = epoch;
            }
            STAMP(2);
        }
        if (warp == 23) {
#pragma unroll 1
            for (int kk = nslot - 1; kk >= 0; kk--) {
                __syncwarp();
                bar_sync(6 + kk, 160);
                if (kk < 2) mbar_wait(mb + MB_W1 * 8);
                if (lane == 0) { asm volatile("fence.proxy.async.shared::cta;" ::: "memory"); tma2d(sb + SM_FAR + kk * FAR_SZ, &tmD, 72 * q, 320 * c + 64 * kk, mb + MB_W2 * 8); }
            }
        }
        }
        __syncwarp();
        if (warp == 20) {
            bar_sync(11, 672);
            asm volatile("fence.proxy.async.shared::cta;" ::: "memory");
            bar_sync(14, 768);
            if (elect()) {
                asm volatile("cp.async.bulk.tensor.5d.global.shared::cta.bulk_group [%0, {%2, %4, %4, %4, %3}], [%1];" :: "l"(&tmH), "r"(sb + SM_XT + 16384), "r"(d0 + ((c & 1) ? 0 : 32)), "r"(8 * q), "r"(0) : "memory");
                asm volatile("cp.async.bulk.tensor.5d.global.shared::cta.bulk_group [%0, {%2, %4, %4, %4, %3}], [%1];" :: "l"(&tmO), "r"(sb + SM_XT), "r"(d0 + (c & 1) * 8), "r"(8 * q), "r"(0) : "memory");
                asm volatile("cp.async.bulk.commit_group;" ::: "memory");
            }
        } else bar_sync(14, 768);
        __syncwarp();
        const uint32_t ft = (tid >> 4) & 7, fj = d0 / 3 + (lane & 15), tok = ~lds32(sb + SM_SEL + ft * 8) & 2047;
        float v[3], cnt = 0.f;
#pragma unroll
        for (int i = 0; i < 3; i++) {
            const uint32_t cl = 3 * fj + i - d0, cf = cl - (c & 1) * 8;
            const bool ok = cl < 8 * nslot && ((tok >> 3) & 7) == q;
            const uint32_t u = lds16(sb + SM_XT + (cf < 32 ? tslot(tok) * 64 + cf * 2 : 16384 + tslot(tok) * 16 + (cl & 7) * 2));
            v[i] = ok ? __uint_as_float(u << 16) : 0.f;
            if (ok) cnt += 1.f;
        }
        if (warp == 20 && elect()) {
            asm volatile("cp.async.bulk.wait_group 0;" ::: "memory");
            asm volatile("fence.proxy.async.global;" ::: "memory");
            asm volatile("mbarrier.arrive.shared::cta.b64 _, [%0];" :: "r"(mb + MB_OUT * 8) : "memory");
        }
        __syncwarp();
        mbar_wait(mb + MB_OUT * 8);
        STAMP(5);
        if (cnt != 0.f) finish(prm, (ft * 192 + fj) * 16, (tok * D_ + 3 * fj) * 2, v, cnt);
        return;
    }

    const int g = lane >> 2, cq = lane & 3;
    const int k = warp >> 2, wq = warp & 3;
    const int trow = 18 * blockIdx.x + warp;
    const bool rowact = warp < 18 && trow < L_;
#pragma unroll
    for (int i = 2; i < 6; i++) pv[i] = ldg16((const char*)prm.prm6[i] + pofs);
    const int tn = 16 * (warp & 15) + g;
    uint32_t xa[5], xb[5];
    asm volatile("barrier.cluster.arrive.relaxed.aligned;" ::: "memory");
    char* const st1p = (char*)g_s.st1 + opaque(((((trow >> 3) & 7) * 256 + ((trow >> 6) & 31) * 8 + (trow & 7)) * 8 + lane) * 4);
    const bool pub = rowact && (lane & 0x1B) == 0;
    if (pub) st_rlx128(st1p, 0, 0, 0, 0);
    {
        const uint32_t za = sb + SM_P + tid * 16;
        sts128(za, 0, 0, 0, 0);
        if (tid < (SM_MISC - SM_P) / 16 - 640) sts128(za + 10240, 0, 0, 0, 0);
        sts128(sb + SM_U + ((tid >> 3) & 7) * UP + k * US + (lane & 7) * 16, 0, 0, 0, 0);
    }
    bar_sync(12, NTHR);
    const uint32_t dep = lds32(sb + SM_P);
#define PV(x) __uint_as_float(__byte_perm(dep, x, 0x5410))
    STAMP(1);
    const uint32_t fb = sb + SM_FAR + k * FAR_SZ;
    const uint32_t pn = sb + SM_PN + k * PN_SZ, pf = sb + SM_PF + k * PF_SZ;
    unsigned epoch, t258;
    {
        const uint32_t kb = fb + wq * 3072;
        const uint32_t kl = kb + lane * 16;
        uint32_t Af[4][4];
        float sr, si, z1r, z1i, z2r, z2i, z4r, z4i, hr, hi_;
        {
            const float dt = bfr(ex2f(PV(pLdt) * 1.4426950408889634f));
            const float e2 = dt * PV(pv[0]) * 1.4426950408889634f, an = dt * PV(pv[1]);
            float ar, ai, br, bi, cr, ci, dr, di;
            { const float m = ex2f(e2 * 8.f); ar = m * __cosf(an * 8.f); ai = m * __sinf(an * 8.f); }
            csq(br, bi, ar, ai); csq(cr, ci, br, bi); csq(dr, di, cr, ci);
            const H2C m4 = splat(cr, ci);
            {
                float r3, i3;
                cmul(r3, i3, ar, ai, br, bi);
                expand4(kl, kl + 1024, pack_f16(1.f, ar), pack_f16(br, r3), pack_f16(0.f, ai), pack_f16(bi, i3), m4);
            }
            expand8(kl + 512, kl + 1536, dr, di, ar, ai, br, bi, m4);
            { const float m = ex2f(e2); z1r = m * __cosf(an); z1i = -m * __sinf(an); }
            cexp_s(hr, hi_, e2 * 128.f, an * (-128.f * 0.15915494309189535f));
            csq(z2r, z2i, z1r, z1i); csq(z4r, z4i, z2r, z2i);
            const uint32_t dep2 = lds32(sb + SM_P + 4);
#define PW(x) __uint_as_float(__byte_perm(dep2, x, 0x5410))
            cmul(sr, si, PW(pv[4]), PW(pv[5]), dt * PW(pv[2]), dt * PW(pv[3]));
            const unsigned E = min(max(__reduce_max_sync(~0u, __float_as_uint(fmaxf(fabsf(sr), fabsf(si)))) >> 23, 1u), 253u);
            const float sc = __uint_as_float((254u - E) << 23);
            sr *= sc; si *= -sc;
            sts64(sb + SM_KG + warp * 8, E, __reduce_add_sync(~0u, __float2int_rn(sr * 16777216.f)));
        }
        __syncwarp();
#pragma unroll
        for (int ks = 0; ks < 4; ks++) ldsm4t(Af[ks], kb + (lane >> 3) * 512 + (lane & 7) * 16 + ks * 128);
        STAMP(2);
        const uint32_t la = kb + ((lane >> 3) & 1) * 512 + (lane >> 4) * 128 + (lane & 7) * 16;
        uint32_t b0[4], b1[4], b2[4], b3[4];
        auto ln1 = [&]() {
        mbar_wait(mb + MB_R * 8);
        epoch = lds32(sb + SM_SC + 28) + 1;
        {
            const uint32_t ra = sb + SM_ROW + warp * (D_ * 2);
            const uint4 r0 = lds128(ra + lane * 16), r1 = lds128(ra + 512 + lane * 16);
            const uint32_t rx[9] = {r0.x, r0.y, r0.z, r0.w, r1.x, r1.y, r1.z, r1.w, lds32(ra + 1024 + lane * 4)};
            float a0 = bf_lo(rx[0]), a1 = bf_hi(rx[0]), c0 = a0 * a0, c1 = a1 * a1;
#pragma unroll
            for (int i = 1; i < 9; i++) { const float l = bf_lo(rx[i]), h = bf_hi(rx[i]); a0 += l; a1 += h; c0 = fmaf(l, l, c0); c1 = fmaf(h, h, c1); }
            a0 += a1; c0 += c1;
            float s1 = ((lane & 1) ? c0 : a0) + __shfl_xor_sync(~0u, (lane & 1) ? a0 : c0, 1);
#pragma unroll
            for (int o = 2; o < 32; o <<= 1) s1 += __shfl_xor_sync(~0u, s1, o);
            const float s2 = __shfl_xor_sync(~0u, s1, 1);
            const uint32_t ms = ln_stats(s1, s2);
            const uint32_t p0 = __byte_perm(ms, epoch | 0x8000u, 0x5410), p1 = rsplit(rcpf(bf_hi(ms)));
            if (pub) st_rlx128(st1p, p0, p1, epoch, lane);
        }
        mbar_wait(mb + MB_R * 8);
        STAMP(1);
        };
        const uint4* sp = &g_s.st1[(256 * q + tn) * 2];
        uint2 sa, sc;
        auto poll = [&]() { sa = ld_rlx64(sp); sc = ld_rlx64(sp + 16); };
        auto norm = [&]() {
        STAMP(3);
        if (warp < 16) {
            uint32_t va[5], vc[5];
            poll();
            uint32_t x16 = g * (2 * XW) + cq * 16, x4 = g * (2 * XW) + cq * 4;
            const uint32_t xt = opaque(sb + SM_XTL + (c & 1) * 16 + (36 * (warp & 7) + 9 * (warp >> 3)) * (2 * XW));
            const int d4 = 2 * (lane >> 3) + (lane & 1), d1_ = lane & 7;
            const uint32_t own = SM_U + 128 + q * (UP - YP), oth = SM_XT + 128 + (q & 3) * 16;
            uint32_t a4 = sb + warp * 32 + d4 * YP + (d4 == q ? own : oth) + ((lane & 7) >> 1) * YS;
            uint32_t a1 = sb + warp * 32 + d1_ * YP + (d1_ == q ? own : oth) + 4 * YS + (lane & 8) * 2;
            PIN(a4); PIN(a1);
            uint32_t tag = __byte_perm(epoch | 0x8000u, 0, 0x1010);
            PIN(tag);
            PIN(x16); PIN(x4);
            uint32_t xh = sb + SM_XTL + (c & 1) * 16 + (9 * __byte_perm(0x12100200, 0x13110301, g) + 72 * (warp & 1) + (warp >> 1)) * (2 * XW) + cq * 4;
            PIN(xh);
            mbar_wait(mb + MB_T * 8);
            {
                const uint4 a4 = lds128(xt + x16), b4 = lds128(xt + x16 + 36 * XW);
                va[0] = a4.x; va[1] = a4.y; va[2] = a4.z; va[3] = a4.w; va[4] = lds32(xt + x4 + 64);
                vc[0] = b4.x; vc[1] = b4.y; vc[2] = b4.z; vc[3] = b4.w; vc[4] = lds32(xt + x4 + (64 + 36 * XW));
            }
            mbar_wait(mb + MB_T * 8);
            int n = 0;
            while (__byte_perm(sa.x, sc.x, 0x7632) != tag && ++n < SPIN_LIMIT) poll();
            STAMP(4);
#pragma unroll
            for (int i = 0; i < 5; i++) {
                va[i] = norm2(va[i], sa.x, sa.y); va[i] = pack_f16(bf_lo(va[i]), bf_hi(va[i]));
                vc[i] = norm2(vc[i], sc.x, sc.y); vc[i] = pack_f16(bf_lo(vc[i]), bf_hi(vc[i]));
            }
            stsm4t(a4, va[0], va[1], va[2], va[3]); stsm4t(a4 + 16, vc[0], vc[1], vc[2], vc[3]); stsm2t(a1, va[4], vc[4]);
            bar_arrive(13, 608);
            {
            const uint4 c4 = lds128(xh + cq * 12), d4_ = lds128(xh + cq * 12 + 72 * XW);
            xa[0] = c4.x; xa[1] = c4.y; xa[2] = c4.z; xa[3] = c4.w; xa[4] = lds32(xh + 64);
            xb[0] = d4_.x; xb[1] = d4_.y; xb[2] = d4_.z; xb[3] = d4_.w; xb[4] = lds32(xh + (64 + 72 * XW));
            }
        }
        STAMP(5);
        __syncwarp();
        bar_sync(15, 672);
        Af[0][0] |= lds32(sb + SM_P);
        };
        cmul(sr, si, sr, si, z1r, z1i);
        {
            const H2C h4 = splat(z4r, z4i);
            expand8(kl, kl + 512, sr, si, z1r, z1i, z2r, z2i, h4);
            cmul(sr, si, sr, si, hr, hi_);
            expand8(kl + 1024, kl + 1536, sr, si, z1r, z1i, z2r, z2i, h4);
        }
        __syncwarp();
        ldsm4t(b0, la); ldsm4t(b1, la + 256); ldsm4t(b2, la + 1024); ldsm4t(b3, la + 1280);
        cmul(z1r, z1i, z1r, z1i, hr, hi_);
        cmul(sr, si, sr, si, z1r, z1i);
        expand8(kl, kl + 512, sr, si, z2r, z2i, z4r, z4i, splat(hr, hi_));
        asm volatile("barrier.cluster.wait.aligned;" ::: "memory");
        bar_arrive(0, 672);
        ln1();
        csq(z1r, z1i, z1r, z1i);
        cmul(sr, si, sr, si, z1r, z1i);
        csq(z2r, z2i, hr, hi_);
        expand8(kl + 1024, kl + 1536, sr, si, z4r, z4i, hr, hi_, splat(z2r, z2i));
        csq(z1r, z1i, z1r, z1i);
        cmul(sr, si, sr, si, z1r, z1i);
        csq(z4r, z4i, z2r, z2i);
        expand8(kl + 2048, kl + 2560, sr, si, hr, hi_, z2r, z2i, splat(z4r, z4i));
        norm();
        {
            uint32_t c0[4], c1[4], c2[4], c3[4], e0[4], e1[4];
            float t[5][4];
            mma_f16_z(t[0], Af[0], b0[0], b0[1]); mma_f16_z(t[1], Af[0], b2[0], b2[1]);
            mma_f16(t[0], Af[1], b0[2], b0[3]); mma_f16(t[1], Af[1], b2[2], b2[3]);
            const uint32_t lb = la | (__float_as_uint(t[0][0]) & zero);
            ldsm4t(c0, lb); ldsm4t(c2, lb + 1024); ldsm4t(e0, lb + 2048);
            mma_f16(t[0], Af[2], b1[0], b1[1]); mma_f16(t[1], Af[2], b3[0], b3[1]);
            mma_f16(t[0], Af[3], b1[2], b1[3]); mma_f16(t[1], Af[3], b3[2], b3[3]);
            ldsm4t(c1, lb + 256); ldsm4t(c3, lb + 1280); ldsm4t(e1, lb + 2304);
            mma_f16_z(t[2], Af[0], c0[0], c0[1]); mma_f16_z(t[3], Af[0], c2[0], c2[1]); mma_f16_z(t[4], Af[0], e0[0], e0[1]);
            mma_f16(t[2], Af[1], c0[2], c0[3]); mma_f16(t[3], Af[1], c2[2], c2[3]); mma_f16(t[4], Af[1], e0[2], e0[3]);
            mma_f16(t[2], Af[2], c1[0], c1[1]); mma_f16(t[3], Af[2], c3[0], c3[1]); mma_f16(t[4], Af[2], e1[0], e1[1]);
            mma_f16(t[2], Af[3], c1[2], c1[3]); mma_f16(t[3], Af[3], c3[2], c3[3]); mma_f16(t[4], Af[3], e1[2], e1[3]);
            stsm4(kl + 1024, pack_f16(t[0][0], t[0][1]), pack_f16(t[0][2], t[0][3]), pack_f16(t[1][0], t[1][1]), pack_f16(t[1][2], t[1][3]));
            stsm2(kl + 1536, pack_f16(t[2][0], t[2][1]), pack_f16(t[2][2], t[2][3]));
            sts64(kb + lane * 8 + 1792, pack_f16(t[3][1], t[3][0]), pack_f16(t[3][3], t[3][2]));
            sts64(kb + lane * 8 + 2048, pack_f16(t[4][1], t[4][0]), pack_f16(t[4][3], t[4][2]));
        }
        bar_sync(1 + k, 128);
        const uint2 rr = lds64(opaque(sb + SM_RK + k * 8));
        const int tq = (wq + k + 2) & 3;
        const uint32_t ra = lane * 8 + opaque(fb + (tq == 1 ? 2048 : tq * 256 + 1024));
        auto comb = [&](uint32_t a, uint32_t& x, uint32_t& y) {
            const uint2 p0 = lds64(a), p1 = lds64(a + 3072), p2 = lds64(a + 6144), p3 = lds64(a + 9216);
            x = comb4(p0.x, p1.x, p2.x, p3.x, rr.x, rr.y); y = comb4(p0.y, p1.y, p2.y, p3.y, rr.x, rr.y);
        };
        uint32_t w0, w1;
        comb(ra, w0, w1);
        const bool last = lane == 31;
        if (tq == 0) {
            uint32_t v0, v1;
            comb(ra + 256, v0, v1);
            const uint32_t n0 = __shfl_sync(~0u, lane ? w0 : v0, lane + 1);
            uint32_t n1 = __shfl_sync(~0u, v0, lane + 1);
            if (last) n1 = v1 >> 16;
            sts128(pn + 12 + lane * 16, __byte_perm(w1, w0, 0x7610), __byte_perm(w1, 0, 0x1032), __byte_perm(n0, w1, 0x7610), __byte_perm(n0, 0, 0x1032));
            sts128(pn + 524 + lane * 16, __byte_perm(v1, v0, 0x7610), __byte_perm(v1, 0, 0x1032), __byte_perm(n1, v1, 0x7610), __byte_perm(n1, 0, 0x1032));
            if (lane == 0) { sts16(pn + 4, w0); sts32(pn + 8, __byte_perm(w0, 0, 0x1032)); }
        } else if (tq == 1) {
            const uint32_t ph = pf + P_H7 + (g & 1) * (2 * P_HS) + cq * 64 + (g >> 1) * 4 + (cq & 2) * 16, sw = (cq & 2) ? 0x3210 : 0x1032;
            w0 = __byte_perm(hmul2(w0, 0x18001800u), 0, sw); w1 = __byte_perm(hmul2(w1, 0x18001800u), 0, sw);
            const uint32_t pi = ph + 32 - (cq & 2) * 32;
            put16(ph, w0); put16(pi, w0 >> 16); put16(ph + 16, w1); put16(pi + 16, w1 >> 16);
        } else if (tq == 2) {
            uint32_t n = __shfl_sync(~0u, w0, lane == 30 ? 1 : lane + 2);
            if (last) { put16(pf, hmul2(w1, 0x18001800u) >> 16); w1 = hadd2(w1, hneg2(__byte_perm(w1, 0, 0x3232))); n = 0; }
            const bool od = lane & 1;
            const uint32_t pa = pn + 1036 + (lane >> 1) * 32 + (od ? 528 : 0), pb = pa + (od ? -16 : 16);
            const uint32_t u0 = od ? w1 : w0, x0 = od ? n : w1, u1 = od ? w0 : w1, x1 = od ? w1 : n;
            const uint32_t b0 = __byte_perm(u0, 0, 0x3232), b1 = __byte_perm(u1, 0, 0x3232);
            sts128(pa, __byte_perm(u0, 0, 0x1032), b0, b0, __byte_perm(x0, u0, 0x7610));
            sts128(pb, __byte_perm(u1, 0, 0x1032), b1, b1, __byte_perm(x1, u1, 0x7610));
        } else {
            const uint32_t pa = pf + ((g & 1) ? 3 * P_GS : P_GS) + cq * 32 + (g >> 1) * 4;
            const uint32_t pb = pa + ((g & 1) ? 4 - 3 * P_GS : P_GS);
            w0 = hmul2(w0, 0x18001800u); w1 = hmul2(w1, 0x18001800u);
            put16(pa, w0 >> 16); put16(pb, w0); put16(pa + 16, w1 >> 16); put16(pb + 16, w1);
            if (last) put16(pf + P_H7 + P_HS, w1);
        }
        bar_sync(1 + k, 128);
        t258 = w0;
    }
    STAMP(6);

    mbar_wait(mb + (MB_X + k) * 8);
    STAMP(7);
    if (k < nslot) {
        const int role = (wq + k) & 3;
        const uint32_t ub = sb + SM_U + k * US + 128;
        const uint32_t l16 = lane * 16, tz = (lane & 28) - 8 * cq, tz4 = tz * 4;
        if (role) {
            const uint32_t al = cq * (2 * UP + 32) + tz4, au = opaque(ub + (3 - role) * 128), a1 = al + au, a0 = (cq ? al : al + (8 * UP - 16)) + au - 2 * UP;
            const uint4 q0 = lds128(a0), q1 = lds128(a0 + UP), q2 = lds128(a1), q3 = lds128(a1 + UP);
            const uint32_t U[16] = {q0.x, q0.y, q0.z, q0.w, q1.x, q1.y, q1.z, q1.w, q2.x, q2.y, q2.z, q2.w, q3.x, q3.y, q3.z, q3.w};
            uint32_t V[14], Q[14], R4[12], T[8];
#pragma unroll
            for (int i = 2; i < 14; i++) { V[i] = __byte_perm(U[i], U[i + 1], 0x5432); Q[i] = hadd2(U[i], V[i]); }
            const uint32_t rb = l16 + opaque(fb + (3 - role) * 512);
#pragma unroll
            for (int i = 0; i < 8; i++) T[i] = hadd2(V[5 + i], Q[6 + i]);
            sts128(rb + F_E3, T[0], T[1], T[2], T[3]); sts128(rb + F_O3 + 16, T[4], T[5], T[6], T[7]);
            asm volatile("{ .reg .pred p; setp.ne.u32 p, %10, 1; @p st.shared.v4.u32 [%0], {%2,%3,%4,%5}; @p st.shared.v4.u32 [%1], {%6,%7,%8,%9}; }"
                         :: "r"(rb + F_E2), "r"(rb + F_O2), "r"(Q[6]), "r"(Q[7]), "r"(Q[8]), "r"(Q[9]), "r"(Q[10]), "r"(Q[11]), "r"(Q[12]), "r"(Q[13]), "r"(role) : "memory");
#pragma unroll
            for (int i = 2; i < 12; i++) R4[i] = hadd2(Q[i], Q[i + 1]);
#pragma unroll
            for (int i = 0; i < 8; i++) T[i] = hadd2(R4[3 + i], U[5 + i]);
            sts128(rb + F_O5, T[0], T[1], T[2], T[3]); sts128(rb + F_E5, T[4], T[5], T[6], T[7]);
            if (role != 1) {
                uint32_t S[8];
#pragma unroll
                for (int i = 0; i < 8; i++) S[i] = hadd2(R4[2 + i], i < 7 ? T[i + 1] : hadd2(R4[11], U[13]));
                sts128(rb + F_O9, S[0], S[1], S[2], S[3]); sts128(rb + F_E9 + 16, S[4], S[5], S[6], S[7]);
#pragma unroll
                for (int i = 0; i < 8; i++) S[i] = hadd2(T[i], hadd2(V[2 + i], V[5 + i]));
                sts128(rb + F_E7, S[0], S[1], S[2], S[3]); sts128(rb + F_O7, S[4], S[5], S[6], S[7]);
            }
        } else if (lane == 0) {
            const uint4 m = lds128(ub + 23 * 16 + 7 * UP);
            const uint32_t U[6] = {lds32(ub + 23 * 16 + 6 * UP + 12), m.x, m.y, m.z, m.w, lds32(ub + 24 * 16)};
            uint32_t Q[5];
#pragma unroll
            for (int i = 0; i < 5; i++) Q[i] = hadd2(U[i], __byte_perm(U[i], U[i + 1], 0x5432));
            sts128(fb + F_O5 + 96 * 16, hadd2(hadd2(Q[0], Q[1]), U[2]), hadd2(hadd2(Q[1], Q[2]), U[3]), hadd2(hadd2(Q[2], Q[3]), U[4]), hadd2(hadd2(Q[3], Q[4]), U[5]));
            sts128(fb + F_O3, 0, 0, 0, 0); sts128(fb + F_E9, 0, 0, 0, 0);
            sts16(pn + 258 * 4, t258);
        }
        bar_sync(1 + k, 128);
        float acc[4][4];
        uint32_t Q[4][4];
        {
            const int h = role & 1, part = role >> 1;
            float fa[7][4];
            uint32_t B[3][4];
            const uint32_t po = tz + opaque(pf + part * (2 * P_GS)), ba = l16 + opaque(fb + (part == h ? 0 : F_O5 + h * 16));
#pragma unroll
            for (int s = 1; s >= 0; s--) {
#pragma unroll
                for (int i = 0; i < 3; i++) { Q[i][0] = lds32(po + (s * P_GS + i * 64)); if (i < 2) Q[i][1] = lds32(po + (s * P_GS + i * 64 + 32)); }
#pragma unroll
                for (int i = 0; i < 3; i++) ldsm4t(B[i], ba + (s * F_E3 + i * 512));
#pragma unroll
                for (int i = 0; i < 3; i++) { Q[i][3] = CP(Q[i][0]); if (i) Q[i][2] = CP(Q[i - 1][1]); }
                Q[0][2] = ZF(s ? tz : Q[0][0]); Q[2][1] = ZF(s ? l16 : Q[2][0]);
#pragma unroll
                for (int dl = 0; dl < 3; dl++)
#pragma unroll
                    for (int ap = 0; ap < 6 - dl; ap++) {
                        if (s == 1 && dl == 0) mma_f16_z(fa[ap + 1], Q[0], B[ap >> 1][2 * (ap & 1)], B[ap >> 1][2 * (ap & 1) + 1]);
                        else mma_f16(fa[ap + 1 + dl], Q[dl], B[ap >> 1][2 * (ap & 1)], B[ap >> 1][2 * (ap & 1) + 1]);
                    }
            }
#pragma unroll 1
            for (int s = role; s == 1; s++) {
                ldsm2t(B[0][0], B[0][1], fb + ((lane & 15) == 15 ? F_O5 : F_O3));
#pragma unroll
                for (int dl = 1; dl < 3; dl++) mma_f16(fa[dl], Q[dl], B[0][0], B[0][1]);
            }
            const uint32_t bh = l16 + opaque(fb + F_E7 + h * F_H + part * 2048), ph = tz + opaque(pf + P_H7 + part * (2 * P_HS));
#pragma unroll 1
            for (int s = part; s == 1; s++) {
                Q[2][1] = ZF(Q[2][3]); Q[2][2] = ZF(Q[2][2]); Q[2][0] = lds32(ph - P_HS);
                ldsm4t(B[0], bh - 1024); ldsm4t(B[1], bh - 512);
                Q[2][3] = CP(Q[2][0]);
#pragma unroll
                for (int ap = 0; ap < 4; ap++) mma_f16(fa[ap + 3], Q[2], B[ap >> 1][2 * (ap & 1)], B[ap >> 1][2 * (ap & 1) + 1]);
            }
            {
                Q[0][2] = ZF(tid);
#pragma unroll
                for (int i = 0; i < 4; i++) { Q[i][0] = lds32(ph + i * 64); Q[i][1] = lds32(ph + (i * 64 + 32)); }
                ldsm4t(B[0], bh); ldsm4t(B[1], bh + 512);
#pragma unroll
                for (int i = 0; i < 4; i++) { Q[i][3] = CP(Q[i][0]); if (i) Q[i][2] = CP(Q[i - 1][1]); }
#pragma unroll
                for (int dl = 0; dl < 4; dl++)
#pragma unroll
                    for (int ap = 0; ap < 4 - dl; ap++) mma_f16(fa[ap + 3 + dl], Q[dl], B[ap >> 1][2 * (ap & 1)], B[ap >> 1][2 * (ap & 1) + 1]);
            }
            const uint32_t da = (cq * 2048 + tz4) + opaque(fb + role * 128);
            bar_sync(1 + k, 128);
#pragma unroll
            for (int i = 1; i < 4; i++)
                stsm4(da + i * 512, pack_f16(fa[2 * i - 1][0], fa[2 * i - 1][1]), pack_f16(fa[2 * i - 1][2], fa[2 * i - 1][3]),
                      pack_f16(fa[2 * i][0], fa[2 * i][1]), pack_f16(fa[2 * i][2], fa[2 * i][3]));
            asm("shl.b32 %0, 0x6000, %1;" : "=r"(Q[0][0]) : "r"(tz4));
            Q[0][1] = ZF(Q[0][0]); Q[0][2] = ZF(tz4); Q[0][3] = CP(Q[0][0]);
            const uint32_t ra = l16 + opaque(fb + wq * 2016);
            acc[0][0] = acc[0][1] = acc[0][2] = acc[0][3] = 0.f;
            if (wq == 3) {
                const uint32_t uw = lds32(ub), kw = lds32(pf);
                const float2 uf = __half22float2(*(const __half2*)&uw);
                if ((lane | 4) == 31) acc[0][3] = (lane == 31 ? uf.x + uf.y : uf.x) * (__low2float(*(const __half2*)&kw) * 512.f);
            }
            bar_sync(1 + k, 128);
#pragma unroll
            for (int i = 1; i < 4; i++) {
                ldsm4(B[0], ra + i * 512);
                mma_f16_z(acc[i], Q[0], hadd2(B[0][0], B[0][2]), hadd2(B[0][1], B[0][3]));
            }
        }
        bar_arrive(6 + k, 160);
        STAMP(8);
        const uint32_t inv = lds32(opaque(sb + SM_SC + k * 4));
        const uint32_t yd = l16 + opaque(mapa(sb, 2 * wq) + (SM_XT + 128 + q * YP + k * YS + (k >> 2) * (q >> 1) * 16));
        {
            uint32_t pu = opaque(pn + 64 * (wq - 3));
#define pp (tz + pu)
            const uint32_t dlo = (((ub + 6 * UP) & 0x3FFFF) >> 4) | ((UP >> 4) << 16);
            uint32_t R[4][4];
            unsigned long long ds[4];
#pragma unroll
            for (int i = 0; i < 4; i++) asm volatile("mov.b64 %0, {%1, %2};" : "=l"(ds[i]) : "r"(dlo - i * (2 * UP >> 4)), "r"(8 | zero));
            auto loadQ = [&](uint32_t (&X)[4][4], uint32_t prev) {
#pragma unroll
                for (int i = 0; i < 4; i++) { X[i][0] = lds32(pp + i * 64); X[i][1] = lds32(pp + i * 64 + 32); }
                X[0][2] = CP(prev);
#pragma unroll
                for (int i = 0; i < 4; i++) { X[i][3] = CP(X[i][0]); if (i) X[i][2] = CP(X[i - 1][1]); }
                pu += 256;
            };
            auto issue = [&](uint32_t (&X)[4][4]) {
                asm volatile("wgmma.fence.sync.aligned;" ::: "memory");
#pragma unroll
                for (int i = 0; i < 4; i++) wgmma32(acc, X[i], ds[i]);
                asm volatile("wgmma.commit_group.sync.aligned;" ::: "memory");
#pragma unroll
                for (int i = 0; i < 4; i++) asm volatile("{ .reg .b32 l, h; mov.b64 {l, h}, %0; add.u32 l, l, %1; mov.b64 %0, {l, h}; }" : "+l"(ds[i]) : "r"(~zero));
            };
#pragma unroll
            for (int i = 0; i < 4; i++) {
                Q[i][0] = Q[i][1] = 0;
                if (wq + i >= 3) { Q[i][0] = lds32(pp + i * 64); Q[i][1] = lds32(pp + i * 64 + 32); }
            }
            Q[0][2] = CP(0);
#pragma unroll
            for (int i = 0; i < 4; i++) { Q[i][3] = CP(Q[i][0]); if (i) Q[i][2] = CP(Q[i - 1][1]); }
            pu += 256;
#pragma unroll 1
            for (int dl = 0; dl < 4; dl++) {
                issue(Q);
                asm volatile("wgmma.wait_group.sync.aligned 1;" ::: "memory");
                loadQ(R, Q[3][1]);
                issue(R);
                asm volatile("wgmma.wait_group.sync.aligned 1;" ::: "memory");
                loadQ(Q, R[3][1]);
            }
            issue(Q);
            asm volatile("wgmma.wait_group.sync.aligned 0;" ::: "memory");
        }
        const uint32_t pstep = mapa(sb, 1) - mapa(sb, 0), ym = mapa(mb + MB_Y * 8, 2 * wq);
#pragma unroll
        for (int e = 0; e < 2; e++)
            st_async4(yd + e * pstep, bmul2(pack_bf16(acc[0][2 * e], acc[0][2 * e + 1]), inv), bmul2(pack_bf16(acc[1][2 * e], acc[1][2 * e + 1]), inv),
                      bmul2(pack_bf16(acc[2][2 * e], acc[2][2 * e + 1]), inv), bmul2(pack_bf16(acc[3][2 * e], acc[3][2 * e + 1]), inv), ym + e * pstep);
        if (lane == 0) asm volatile("mbarrier.arrive.shared::cta.b64 _, [%0];" :: "r"(mb + MB_Y * 8) : "memory");
    }
    STAMP(9);
    uint32_t ha[5], hb[5];
    if (warp < 16) {
        const uint4 wk = lds128(sb + SM_DW + cq * 16);
        uint32_t sel[5] = {wk.x, wk.y, wk.z, wk.w, lds32(sb + SM_DW + 64 + cq * 4)}, sel2[5];
#pragma unroll
        for (int i = 0; i < 5; i++) {
            if (!(g & 1)) sel[i] = 0x3F803F80u;
            sel2[i] = sel[i]; PIN(sel2[i]);
        }
        uint32_t y4 = sb + SM_XT + 128 + warp * 32 + (2 * (lane >> 3) + (lane & 1)) * YP + ((lane & 7) >> 1) * YS;
        uint32_t y1 = sb + SM_XT + 128 + warp * 32 + (lane & 7) * YP + 4 * YS + (lane & 8) * 2 + (lane & 6) * 8;
        if (nslot != 5) {
            y1 = sb + SM_U;
            if (lane & 4) y4 = y1;
        }
        PIN(y4); PIN(y1);
        const uint32_t ao = (256 * q + tn) * 16;
        const uint32_t hta = opaque(sb + SM_HT + warp * 1024), htb = opaque(sb + SM_HT + 16384 + warp * 256);
        unsigned long long ap = (unsigned long long)((char*)g_s.acc + ao);
        asm volatile("add.u64 %0, %0, %1;" : "+l"(ap) : "l"((unsigned long long)zero));
        mbar_wait(mb + MB_Y * 8);
        STAMP(10);
        float ca[4] = {0.f, 0.f, 0.f, 0.f}, cb[4] = {0.f, 0.f, 0.f, 0.f};
        {
            uint32_t ya[4], yb[4], yc, yd;
            ldsm4t(ya, y4); ldsm4t(yb, y4 + 16); ldsm2t(yc, yd, y1);
#pragma unroll
            for (int i = 0; i < 4; i++) { ha[i] = badd2(xa[i], ya[i]); hb[i] = badd2(xb[i], yb[i]); }
            ha[4] = badd2(xa[4], yc); hb[4] = badd2(xb[4], yd);
        }
#pragma unroll
        for (int i = 0; i < 5; i++) { mma_bf16_k8(ca, ha[i], sel[i], ha[i]); mma_bf16_k8(cb, hb[i], sel2[i], hb[i]); }
        if (!(g & 1)) { ca[1] = ca[0]; cb[1] = cb[0]; }
        if (cq == (g >> 1)) {
            asm volatile("red.relaxed.gpu.global.add.v4.f32 [%0], {%1,%2,%3,%4};" :: "l"(ap), "f"(1.0f), "f"(ca[1]), "f"(ca[2]), "f"(ca[3]) : "memory");
            asm volatile("red.relaxed.gpu.global.add.v4.f32 [%0], {%1,%2,%3,%4};" :: "l"(ap + 128), "f"(1.0f), "f"(cb[1]), "f"(cb[2]), "f"(cb[3]) : "memory");
        }
        __syncwarp();
        mbar_wait(mb + MB_Y * 8);
#pragma unroll
        for (int i = 0; i < 4; i++) {
            asm volatile("or.b32 %0, %1, %2;" : "=r"(ha[i]) : "r"(ha[i]), "r"(zero));
            asm volatile("or.b32 %0, %1, %2;" : "=r"(hb[i]) : "r"(hb[i]), "r"(zero));
        }
        sts128(hta + lane * 16, ha[0], ha[1], ha[2], ha[3]); sts32(htb + lane * 4, ha[4]);
        sts128(hta + lane * 16 + 512, hb[0], hb[1], hb[2], hb[3]); sts32(htb + lane * 4 + 128, hb[4]);
        STAMP(11);
    }
    const int kq = warp / 5, mt = warp - 5 * kq;
    const int mi = lane >> 3, mr = lane & 7;
    const unsigned tk = (unsigned)tid / 72u, ck = tid - tk * 72;
    uint32_t A[9][4];
    auto loadA = [&]() {
        mbar_wait(mb + MB_W1 * 8);
        const uint32_t aa = sb + (mi & 1) * SM_WU + (8 * (mi >> 1) + mr) * 80 + (144 * 80 * kq + mt * 16);
#pragma unroll
        for (int s = 0; s < 9; s++) ldsm4t(A[s], aa + s * 1280);
    };
    const uint32_t par = (lds32(sb + SM_SC + 28) & 1) ? 0u : 0x40004000u;
    uint32_t go = (ck / 5u + ck) * 16, gs = sb + SM_SEL + 4 + (tk & 7) * 8;
    unsigned long long gb = (unsigned long long)((const char*)g_s.cand + go + (q & 1) * 92160);
    uint32_t xs = sb + SM_XS + tk * 16 + tid * 16;
    asm volatile("add.u64 %0, %0, %1;" : "+l"(gb) : "l"((unsigned long long)zero));
    PIN(xs); PIN(gs);
    auto outtile = [&]() {
        const uint2 sa = lds64(sb + SM_ST + tn * 8), sbb = lds64(sb + SM_ST + tn * 8 + 64);
#pragma unroll
        for (int i = 0; i < 5; i++) { ha[i] = badd2(ha[i], norm2(ha[i], sa.x, sa.y)); hb[i] = badd2(hb[i], norm2(hb[i], sbb.x, sbb.y)); }
        const bool hf = (c & 1) && cq == 0;
        const uint32_t o16 = sb + SM_XT + (hf ? 16384 + tn * 16 : tn * 64 + (cq - (c & 1)) * 16), o4 = sb + SM_XT + ((c & 1) ? tn * 64 + 48 : 16384 + tn * 16) + cq * 4;
        sts128(o16, ha[0], ha[1], ha[2], ha[3]); sts32(o4, ha[4]);
        sts128(o16 + (hf ? 128 : 512), hb[0], hb[1], hb[2], hb[3]); sts32(o4 + ((c & 1) ? 512 : 128), hb[4]);
    };
    if (warp < 8) {
        const float wsum = ldsf(sb + SM_SC + 24);
        const uint32_t idx = 2047 - (512 * ((tid >> 1) & 3) + 128 * ((tid >> 3) & 3) + 64 * (tid & 1) + 8 * q + warp);
        uint32_t km0 = mapa(mb + MB_KEY * 8, 2 * cq), km1 = mapa(mb + MB_KEY * 8, 2 * cq + 1), ka0 = mapa(sb + SM_RK + q * 32, 2 * cq), ka1 = mapa(sb + SM_RK + q * 32, 2 * cq + 1);
        unsigned long long c0 = (unsigned long long)((char*)g_s.cand + ((q * 8 * NCL + c) * 6 + cq) * 16), c1 = c0 + (64 - cq * 12);
        uint32_t hc = sb + SM_HT + cq * 16, h4a = sb + SM_HT + 16384 + cq * 4;
        uint32_t ca = sb + SM_KEY + warp * 128 + (warp & 1) * 32 + (lane & 28), r2a = sb + SM_KEY + cq * 16 + (cq >> 1) * 128;
        PIN(ca); PIN(r2a); PIN(km0); PIN(km1); PIN(ka0); PIN(ka1); PIN(hc); PIN(h4a);
        asm volatile("add.u64 %0, %0, %2; add.u64 %1, %1, %2;" : "+l"(c0), "+l"(c1) : "l"((unsigned long long)zero));
        uint4 s; int n = 0;
        uint32_t ox;
        do {
            s = ld_rlx128(&g_s.acc[256 * q + tid]);
            ox = __shfl_xor_sync(~0u, (lane & 1) ? s.z : s.w, 1);
        } while (__any_sync(~0u, __uint_as_float(s.x) != (float)NCL && ++n < SPIN_LIMIT));
        STAMP(16);
        const uint32_t ms = ln_stats(__uint_as_float((lane & 1) ? ox : s.z), __uint_as_float(s.y));
        const float rs = rcpf(bf_hi(ms));
        const uint32_t rb = pack_bf16(0.f, fmaf(-bf_lo(ms), wsum, __uint_as_float((lane & 1) ? s.w : ox)) * rs);
        const uint32_t key = (((rb ^ (((int)rb >> 31) | 0x80000000u)) >> 16) << 11) | idx;
        sts32(sb + SM_KEY + tid * 4, key);
        sts64(sb + SM_ST + tid * 8, ms, rsplit(rs));
        __syncwarp();
        uint32_t rank = rank4<8, 16>(sb + SM_KEY + warp * 128, key, ~zero);
        {
            const uint32_t sa = (rank * 4 ^ (warp & 1) * 32) + opaque(sb + SM_KEY + warp * 128);
            sts32(sa, key); sts32(sa + 1024, tid);
        }
        __syncwarp();
        const uint32_t mk = lds32(ca), t = lds32(ca + 1024);
        STAMP(17);
        bar_sync(12, 512);
        STAMP(18);
        const uint4 hv = lds128(hc + t * 64);
        const uint2 sv = lds64(sb + SM_ST + t * 8);
        const uint32_t h4 = lds32(h4a + t * 16);
        rank = rank4<4, 256>(r2a, mk, ~zero);
        const uint32_t rr = bmul2(sv.y, 0x3C803C80u);
        const uint32_t p0 = (norm2(hv.x, sv.x, rr) & 0xBFFFBFFFu) | par, p1 = (norm2(hv.y, sv.x, rr) & 0xBFFFBFFFu) | par, p2 = (norm2(hv.z, sv.x, rr) & 0xBFFFBFFFu) | par,
                       p3 = (norm2(hv.w, sv.x, rr) & 0xBFFFBFFFu) | par, p4 = (norm2(h4, sv.x, rr) & 0xBFFFBFFFu) | par;
        rank = quad_sum(rank);
        if (rank < 8) {
            st_async1(ka0 + rank * 4, mk, km0); st_async1(ka1 + rank * 4, mk, km1);
#pragma unroll
            for (int r = 0; r < 2; r++) {
                st_rlx128((void*)(c0 + (unsigned long long)rank * 1440 + r * 92160), p0, p1, p2, p3);
                asm volatile("st.relaxed.gpu.global.u32 [%0], %1;" :: "l"(c1 + (unsigned long long)rank * 1440 + r * 92160), "r"(p4) : "memory");
            }
        }
        __syncwarp();
    } else {
        mbar_wait(mb + MB_Y * 8); loadA();
        if (warp < 16) {
            bar_sync(12, 512);
        }
    }
    if (warp < 16) {
        outtile();
        if (warp >= 8) {
            uint32_t src = ((tid >> 2) - 64) * 1440, ma = sb + SM_RK - 256 + (tid >> 2) * 4, ra = sb + SM_RK + cq * 16;
            PIN(src); PIN(ma); PIN(ra);
            STAMP(19);
            mbar_wait(mb + MB_KEY * 8);
            STAMP(20);
            const uint32_t mk = lds32(ma);
            uint32_t rank = rank4<4, 64>(ra, mk, ~zero);
            rank = quad_sum(rank);
            sts64(sb + SM_SEL + rank * 8, mk, src);
        }
    }
    bar_sync(11, 672);
    STAMP(12);

    const char* gp = (const char*)gb + lds32(gs);
    uint4 hv = ld_rlx128(gp);
    if (warp < 8) loadA();
    uint32_t bx = sb + SM_XS + mr * 1168 + mi * 16 + 288 * kq, gd = mapa(sb, (kq & (NRED - 1)) * (8 / NRED)) + (SM_GU + (q * nslot + mt) * 128) + lane * 4;
    PIN(bx); PIN(gd);
    {
        if (warp < 18) {
            int n = 0;
            while (true) {
                sts128(xs, hv.x ^ par, hv.y ^ par, hv.z ^ par, hv.w ^ par);
                if (!__any_sync(~0u, ((hv.x ^ par) | (hv.y ^ par) | (hv.z ^ par) | (hv.w ^ par)) & 0x40004000u) || ++n >= SPIN_LIMIT) break;
                hv = ld_rlx128(gp);
            }
        }
    }
    bar_sync(14, 768);
    STAMP(13);
    float4 own;
    {
        float c0[4] = {0.f, 0.f, 0.f, 0.f}, c1[4] = {0.f, 0.f, 0.f, 0.f}, c2[4] = {0.f, 0.f, 0.f, 0.f};
        uint32_t b[5][4];
#pragma unroll
        for (int s = 0; s < 4; s++) ldsm4(b[s], bx + s * 64);
        asm volatile("ldmatrix.sync.aligned.m8n8.x2.shared.b16 {%0,%1}, [%2];" : "=r"(b[4][0]), "=r"(b[4][1]) : "r"(bx + 256) : "memory");
        mma_bf16(c0, A[0][0], A[0][1], A[0][2], A[0][3], b[0][0], b[0][1]);
        mma_bf16(c1, A[1][0], A[1][1], A[1][2], A[1][3], b[0][2], b[0][3]);
        mma_bf16(c2, A[2][0], A[2][1], A[2][2], A[2][3], b[1][0], b[1][1]);
        mma_bf16(c0, A[3][0], A[3][1], A[3][2], A[3][3], b[1][2], b[1][3]);
        mma_bf16(c1, A[4][0], A[4][1], A[4][2], A[4][3], b[2][0], b[2][1]);
        mma_bf16(c2, A[5][0], A[5][1], A[5][2], A[5][3], b[2][2], b[2][3]);
        mma_bf16(c0, A[6][0], A[6][1], A[6][2], A[6][3], b[3][0], b[3][1]);
        mma_bf16(c1, A[7][0], A[7][1], A[7][2], A[7][3], b[3][2], b[3][3]);
        mma_bf16(c2, A[8][0], A[8][1], A[8][2], A[8][3], b[4][0], b[4][1]);
        own = make_float4(c0[0] + c1[0] + c2[0], c0[1] + c1[1] + c2[1], c0[2] + c1[2] + c2[2], c0[3] + c1[3] + c2[3]);
        sts128f(sb + SM_RED + tid * 16, own.x, own.y, own.z, own.w);
    }
    if (kq < 4 - NRED) bar_arrive(1 + mt, 128); else
    bar_sync(1 + mt, 128);
    STAMP(21);
    if (mt < nslot && kq >= 4 - NRED) {
        const uint32_t ra = lane * 16 + opaque(sb + SM_RED + mt * 512);
        const float4 p0 = lds128f(ra), p1 = lds128f(ra + 2560), p2 = lds128f(lane * 16 + opaque(sb + SM_RED + mt * 512 + (5 - kq) * 2560)), p3 = own;
        const float g0 = bfr((p0.x + p1.x) + (p2.x + p3.x)), g1 = bfr((p0.y + p1.y) + (p2.y + p3.y));
        const uint32_t sg = pack_bf16(g0 * rcpf(1.f + ex2f(g0 * (-64.f * 1.4426950408889634f))), g1 * rcpf(1.f + ex2f(g1 * (-64.f * 1.4426950408889634f))));
        const uint32_t gu = bmul2(sg, pack_bf16(((p0.z + p1.z) + (p2.z + p3.z)) * 4096.f, ((p0.w + p1.w) + (p2.w + p3.w)) * 4096.f));
        const uint32_t pstep = mapa(sb, 1) - mapa(sb, 0), gm = mapa(mb + MB_GU * 8, (kq & (NRED - 1)) * (8 / NRED));
#pragma unroll
        for (int i = 0; i < 8 / NRED; i++) st_async1(gd + i * pstep, gu, gm + i * pstep);
    }
    mbar_wait(mb + MB_W2 * 8);
    {
        const uint32_t aa = sb + (8 * (mi >> 1) + mr) * 144 + (mi & 1) * 16 + (SM_FAR + 2304 * kq + mt * 32);
#pragma unroll
        for (int s = 0; s < 5; s++) ldsm4t(A[s], aa + s * FAR_SZ);
    }
    float sig; uint32_t ra2; unsigned long long fp, op;
    if (warp < 8) {
        const uint32_t key = lds32(sb + SM_SEL + warp * 8), k16 = key << 5, fj = 24 * q + lane;
        sig = bfr(rcpf(1.f + ex2f(__uint_as_float((k16 ^ (~((int)k16 >> 31) | 0x80000000u)) & 0xFFFF0000u) * -1.4426950408889634f)));
        ra2 = sb + SM_RED2 + warp * 304 + lane * 12;
        fp = (unsigned long long)(g_s.fin + warp * 192 + fj); op = (unsigned long long)(prm.out + (~key & 2047) * D_ + 3 * fj);
        PIN(ra2);
        asm volatile("add.u64 %0, %0, %3; add.u64 %1, %1, %3;" : "+l"(fp), "+l"(op), "+f"(sig) : "l"((unsigned long long)zero));
    }
    {
        uint32_t ba = sb + (SM_GU + 256 * kq) + (lane & 15) * 16 + (lane >> 4) * 1024, wa = sb + (SM_RED2 + kq * 2432 + mt * 64) + g * 4 + cq * 608;
        PIN(ba); PIN(wa);
        STAMP(22);
        mbar_wait(mb + MB_GU * 8);
        STAMP(23);
        float c0[4] = {0.f, 0.f, 0.f, 0.f}, c1[4] = {0.f, 0.f, 0.f, 0.f}, c2[4] = {0.f, 0.f, 0.f, 0.f};
        uint32_t b[2][4], b8, b9;
        ldsm4t(b[0], ba); ldsm4t(b[1], ba + 2048); ldsm2t(b8, b9, ba + 4096);
        mma_bf16(c0, A[0][0], A[0][1], A[0][2], A[0][3], b[0][0], b[0][1]);
        mma_bf16(c1, A[1][0], A[1][1], A[1][2], A[1][3], b[0][2], b[0][3]);
        if (nslot == 5) {
            mma_bf16(c2, A[4][0], A[4][1], A[4][2], A[4][3], b8, b9);
            mma_bf16(c0, A[2][0], A[2][1], A[2][2], A[2][3], b[1][0], b[1][1]);
            mma_bf16(c1, A[3][0], A[3][1], A[3][2], A[3][3], b[1][2], b[1][3]);
        }
        stsf(wa, c0[0] + c1[0] + c2[0]); stsf(wa + 304, c0[1] + c1[1] + c2[1]);
        if (mt < 4) { stsf(wa + 32, c0[2] + c1[2] + c2[2]); stsf(wa + 336, c0[3] + c1[3] + c2[3]); }
    }
    if (warp < 8) {
        float v[3];
        bar_sync(6, 640);
        STAMP(14);
        if (lane < 24) {
#pragma unroll
            for (int i = 0; i < 3; i++) v[i] = ((ldsf(ra2 + i * 4) + ldsf(ra2 + i * 4 + 2432)) + (ldsf(ra2 + i * 4 + 4864) + ldsf(ra2 + i * 4 + 7296))) * sig;
            asm volatile("{ .reg .f32 x, y, z, w; .reg .b16 a, b, c; .reg .pred p;\n"
                         "atom.relaxed.gpu.global.add.v4.f32 {x,y,z,w}, [%0], {%2,%3,%4,%5};\n"
                         "setp.eq.f32 p, w, %6; add.f32 x, x, %2; add.f32 y, y, %3; add.f32 z, z, %4;\n"
                         "cvt.rn.bf16.f32 a, x; cvt.rn.bf16.f32 b, y; cvt.rn.bf16.f32 c, z;\n"
                         "@p st.global.b16 [%1], a; @p st.global.b16 [%1 + 2], b; @p st.global.b16 [%1 + 4], c; }"
                         :: "l"(fp), "l"(op), "f"(v[0]), "f"(v[1]), "f"(v[2]), "f"(3.f), "f"(3.f * NCL) : "memory");
        }
    } else bar_arrive(6, 640);
    STAMP(15);
}

#undef pp
typedef __nv_bfloat16 bf16;
__device__ bf16 f_n[L_ * D_], f_h[L_ * D_];
__device__ float f_k[D_ * L_], f_r[L_], f_gu[8 * F_];
__device__ int f_idx[8];
__device__ __forceinline__ float b2f(bf16 v) { return __bfloat162float(v); }
__global__ void fb_ln(const bf16* in, const bf16* wr, bf16* out) {
    const int t = blockIdx.x * 8 + (threadIdx.x >> 5), lane = threadIdx.x & 31;
    const bf16* r = (in ? in : f_h) + t * D_;
    float s1 = 0.f, s2 = 0.f, s3 = 0.f;
    for (int i = lane; i < D_; i += 32) s1 += b2f(r[i]);
    for (int o = 16; o; o >>= 1) s1 += __shfl_xor_sync(~0u, s1, o);
    for (int i = lane; i < D_; i += 32) { const float d = b2f(r[i]) - s1 / D_; s2 += d * d; }
    for (int o = 16; o; o >>= 1) s2 += __shfl_xor_sync(~0u, s2, o);
    const float m = bfr(s1 / D_), sd = bfr(sqrtf(bfr(bfr(s2 / D_) + 1e-5f)));
    for (int i = lane; i < D_; i += 32) {
        const float v = bfr(bfr(b2f(r[i]) - m) / sd);
        f_n[t * D_ + i] = __float2bfloat16(v);
        if (!in) { s3 += v * b2f(wr[i]); out[t * D_ + i] = __float2bfloat16(b2f(r[i]) + v); }
    }
    for (int o = 16; o; o >>= 1) s3 += __shfl_xor_sync(~0u, s3, o);
    f_r[t] = bfr(s3);
}
__global__ void fb_taps(Params p) {
    const int d = blockIdx.x >> 3, l = (blockIdx.x & 7) * 256 + threadIdx.x;
    const float dt = bfr(expf(bf_lo(p.logdt[d]))), lf = bfr((float)l);
    float k = 0.f;
    for (int n = d * 128; n < d * 128 + 128; n++) {
        float wr, wi, sn, cs;
        cmul(wr, wi, bf_lo(p.prm6[4][n]), bf_lo(p.prm6[5][n]), dt * bf_lo(p.prm6[2][n]), dt * bf_lo(p.prm6[3][n]));
        sincosf(dt * bf_lo(p.prm6[1][n]) * lf, &sn, &cs);
        k += expf(dt * bf_lo(p.prm6[0][n]) * lf) * (wr * cs - wi * sn);
    }
    f_k[l * D_ + d] = k;
}
__global__ void fb_conv(Params p) {
    const int t = blockIdx.x, d = threadIdx.x;
    float y = 0.f;
    for (int l = 0; l <= t; l++) y += f_k[l * D_ + d] * b2f(f_n[(t - l) * D_ + d]);
    f_h[t * D_ + d] = __float2bfloat16(bf_lo(p.x[t * D_ + d]) + bfr(bfr(y) + bfr(b2f(f_n[t * D_ + d]) * bf_lo(p.dskip[d]))));
}
__global__ void fb_top() {
    const int t = blockIdx.x * 256 + threadIdx.x;
    int rank = 0;
    for (int j = 0; j < L_; j++) rank += f_r[j] > f_r[t] || (f_r[j] == f_r[t] && j < t);
    if (rank < 8) f_idx[rank] = t;
}
__global__ void fb_ffn1(const bf16* wg, const bf16* wu) {
    const int f = blockIdx.x * 256 + threadIdx.x, j = blockIdx.y;
    float g = 0.f, u = 0.f;
    for (int i = 0; i < D_; i++) { const float v = b2f(f_n[f_idx[j] * D_ + i]); g += v * b2f(wg[i * F_ + f]); u += v * b2f(wu[i * F_ + f]); }
    g = bfr(g);
    f_gu[j * F_ + f] = bfr(bfr(g / (1.f + expf(-g))) * bfr(u));
}
__global__ void fb_ffn2(const bf16* wd, bf16* out) {
    const int d = threadIdx.x, j = blockIdx.x, t = f_idx[j];
    float y = 0.f;
    for (int f = 0; f < F_; f++) y += f_gu[j * F_ + f] * b2f(wd[f * D_ + d]);
    out[t * D_ + d] = __float2bfloat16(b2f(f_h[t * D_ + d]) + bfr(b2f(f_n[t * D_ + d]) + bfr(bfr(y) * bfr(1.f / (1.f + expf(-f_r[t]))))));
}

typedef CUresult (*EncodeFn)(CUtensorMap*, CUtensorMapDataType, cuuint32_t, void*, const cuuint64_t*, const cuuint64_t*,
                             const cuuint32_t*, const cuuint32_t*, CUtensorMapInterleave, CUtensorMapSwizzle,
                             CUtensorMapL2promotion, CUtensorMapFloatOOBfill);

void make_map(EncodeFn fn, CUtensorMap* tm, const void* p, int cols, int rows, int bc, int br) {
    cuuint64_t dims[2] = {(cuuint64_t)cols, (cuuint64_t)rows};
    cuuint64_t strides[1] = {(cuuint64_t)cols * 2};
    cuuint32_t box[2] = {(cuuint32_t)bc, (cuuint32_t)br};
    cuuint32_t es[2] = {1, 1};
    fn(tm, CU_TENSOR_MAP_DATA_TYPE_BFLOAT16, 2, const_cast<void*>(p), dims, strides, box, es, CU_TENSOR_MAP_INTERLEAVE_NONE,
       CU_TENSOR_MAP_SWIZZLE_NONE, CU_TENSOR_MAP_L2_PROMOTION_L2_128B, CU_TENSOR_MAP_FLOAT_OOB_FILL_NONE);
}

void make_map3(EncodeFn fn, CUtensorMap* tm, const void* p) {
    cuuint64_t dims[5] = {(cuuint64_t)D_, 64, 2, 2, 8};
    cuuint64_t strides[4] = {(cuuint64_t)D_ * 2, (cuuint64_t)D_ * 2048, (cuuint64_t)D_ * 128, (cuuint64_t)D_ * 256};
    cuuint32_t box[5] = {XW, 9, 2, 2, 8};
    cuuint32_t es[5] = {1, 1, 1, 1, 1};
    fn(tm, CU_TENSOR_MAP_DATA_TYPE_BFLOAT16, 5, const_cast<void*>(p), dims, strides, box, es, CU_TENSOR_MAP_INTERLEAVE_NONE,
       CU_TENSOR_MAP_SWIZZLE_NONE, CU_TENSOR_MAP_L2_PROMOTION_NONE, CU_TENSOR_MAP_FLOAT_OOB_FILL_NONE);
}

void make_map5(EncodeFn fn, CUtensorMap* tm, const void* p, int bc) {
    cuuint64_t dims[5] = {(cuuint64_t)D_, 2, 4, 4, 64};
    cuuint64_t strides[4] = {(cuuint64_t)D_ * 128, (cuuint64_t)D_ * 1024, (cuuint64_t)D_ * 256, (cuuint64_t)D_ * 2};
    cuuint32_t box[5] = {(cuuint32_t)bc, 2, 4, 4, 8};
    cuuint32_t es[5] = {1, 1, 1, 1, 1};
    fn(tm, CU_TENSOR_MAP_DATA_TYPE_BFLOAT16, 5, const_cast<void*>(p), dims, strides, box, es, CU_TENSOR_MAP_INTERLEAVE_NONE,
       CU_TENSOR_MAP_SWIZZLE_NONE, CU_TENSOR_MAP_L2_PROMOTION_NONE, CU_TENSOR_MAP_FLOAT_OOB_FILL_NONE);
}

}

extern "C" void kernel_launch(void* const* d_in, const int* in_sizes, int n_in, void* d_out, int out_size) {
    (void)in_sizes; (void)n_in; (void)out_size;
    void* fp = nullptr;
    cudaDriverEntryPointQueryResult qr;
    cudaGetDriverEntryPoint("cuTensorMapEncodeTiled", &fp, cudaEnableDefault, &qr);
    EncodeFn fn = (EncodeFn)fp;
    CUtensorMap tmG, tmU, tmD, tmO, tmX, tmH;
    make_map3(fn, &tmX, d_in[0]);
    make_map(fn, &tmG, d_in[11], F_, D_, 40, 48);
    make_map(fn, &tmU, d_in[12], F_, D_, 40, 48);
    make_map(fn, &tmD, d_in[13], D_, F_, 72, 64);
    make_map5(fn, &tmO, d_out, 32);
    make_map5(fn, &tmH, d_out, 8);
    Params p;
    p.x = (const unsigned short*)d_in[0];
    for (int i = 0; i < 6; i++) p.prm6[i] = (const unsigned short*)d_in[1 + i];
    p.logdt = (const unsigned short*)d_in[7]; p.dskip = (const unsigned short*)d_in[8];
    p.wr = (const unsigned short*)d_in[10];
    p.out = (__nv_bfloat16*)d_out;
    p.zero = 0;
    cudaGetSymbolAddress((void**)&p.gs, g_s);
    cudaFuncSetAttribute(fused_kernel, cudaFuncAttributeMaxDynamicSharedMemorySize, SM_TOTAL);
    static int nclusters = -1;
    if (nclusters < 0) {
        cudaLaunchConfig_t cfg = {};
        cudaLaunchAttribute at;
        at.id = cudaLaunchAttributeClusterDimension; at.val.clusterDim.x = CS; at.val.clusterDim.y = 1; at.val.clusterDim.z = 1;
        cfg.gridDim = dim3(NCTA); cfg.blockDim = dim3(NTHR); cfg.dynamicSmemBytes = SM_TOTAL; cfg.attrs = &at; cfg.numAttrs = 1;
        if (cudaOccupancyMaxActiveClusters(&nclusters, fused_kernel, &cfg) != cudaSuccess) { (void)cudaGetLastError(); nclusters = NCL; }
    }
    if (nclusters >= NCL && !FORCE_FALLBACK) {
        fused_kernel<<<NCTA, NTHR, SM_TOTAL>>>(p, tmG, tmU, tmD, tmO, tmX, tmH);
        return;
    }
    fb_ln<<<L_ / 8, 256>>>((const bf16*)d_in[0], nullptr, nullptr);
    fb_taps<<<D_ * 8, 256>>>(p);
    fb_conv<<<L_, D_>>>(p);
    fb_ln<<<L_ / 8, 256>>>(nullptr, (const bf16*)d_in[10], p.out);
    fb_top<<<L_ / 256, 256>>>();
    fb_ffn1<<<dim3(F_ / 256, 8), 256>>>((const bf16*)d_in[11], (const bf16*)d_in[12]);
    fb_ffn2<<<8, D_>>>((const bf16*)d_in[13], p.out);
}
```
